```python
import torch

def _softmax(x, axis=-1):
    return torch.softmax(x, dim=axis)

def _gelu(x):
    return torch.nn.functional.gelu(x, approximate='tanh')

def _silu(x):
    return torch.nn.functional.silu(x)

def _sigmoid(x):
    return torch.sigmoid(x)

def _layernorm(x, axis=-1, eps=1e-05):
    m = x.mean(dim=axis, keepdim=True)
    v = x.var(dim=axis, keepdim=True, unbiased=False)
    return (x - m) / torch.sqrt(v + eps)

def _scatter_add(tgt, idx, src, axis=0):
    return tgt.clone().index_add_(axis, idx, src)

def _segment_sum(src, seg, n):
    out = torch.zeros((n,) + src.shape[1:], dtype=src.dtype)
    return out.index_add_(0, seg, src)

def _pad(x, pw):
    flat = tuple((v for pair in reversed(pw) for v in pair))
    return torch.nn.functional.pad(x, flat)
kernel_name = 'interleave_layers__memory_aug_recurrent_mem_tr__softmax_full_mha__prompt'

def setup_inputs():

    _w = lambda a: (lambda t: t.to(torch.bfloat16) if t.is_floating_point() else t)(torch.as_tensor(a))

    def _A_setup():
        B, S, Dm = (1, 2048, 640)
        H, Dh = (32, 192)
        M, seg = (8, 32)
        seg = min(seg, S)
        S = S // seg * seg
        return {'x': _w((lambda *s: torch.randn(*s, dtype=torch.bfloat16) * 0.05)(B, S, Dm)), 'mem0': _w((lambda *s: torch.randn(*s, dtype=torch.bfloat16) * 0.8)(B, M, Dm)), 'Wq': _w((lambda *s: torch.randn(*s, dtype=torch.bfloat16) * 0.8)(Dm, H, Dh) * Dm ** (-0.5)), 'Wk': _w((lambda *s: torch.randn(*s, dtype=torch.bfloat16) * 0.8)(Dm, H, Dh) * Dm ** (-0.5)), 'Wv': _w((lambda *s: torch.randn(*s, dtype=torch.bfloat16) * 0.8)(Dm, H, Dh) * Dm ** (-0.5)), 'Wo': _w((lambda *s: torch.randn(*s, dtype=torch.bfloat16) * 0.8)(H, Dh, Dm) * (H * Dh) ** (-0.5)), 'seg_len': seg}
    _A_in = _A_setup()

    def _B_setup():
        B, S, D = (1, 2048, 640)
        return {'x': _w((lambda *s: torch.randn(*s, dtype=torch.bfloat16) * 0.05)(B, S, D)), 'wqkv': _w((lambda *s: torch.randn(*s, dtype=torch.bfloat16) * 0.05)(D, 3 * D)), 'wo': _w((lambda *s: torch.randn(*s, dtype=torch.bfloat16) * 0.05)(D, D))}
    _B_in = _B_setup()
    return {'A_x': _A_in['x'], 'A_mem0': _A_in['mem0'], 'A_Wq': _A_in['Wq'], 'A_Wk': _A_in['Wk'], 'A_Wv': _A_in['Wv'], 'A_Wo': _A_in['Wo'], 'A_seg_len': _A_in['seg_len'], 'B_x': _B_in['x'], 'B_wqkv': _B_in['wqkv'], 'B_wo': _B_in['wo']}

def reference(A_x, A_mem0, A_Wq, A_Wk, A_Wv, A_Wo, A_seg_len, B_x, B_wqkv, B_wo):

    def _A_ref(x, mem0, Wq, Wk, Wv, Wo, seg_len):
        B, S, Dm = x.shape
        H, Dh = (Wq.shape[1], Wq.shape[2])
        M = mem0.shape[1]
        scale = Dh ** (-0.5)
        n_seg = S // seg_len
        L = M + seg_len
        idx = torch.arange(L)
        mask = (idx[:, None] < M) | (idx[:, None] >= idx[None, :])
        mem = mem0
        outs = []
        for s in range(n_seg):
            xs = x[:, s * seg_len:(s + 1) * seg_len, :].clone()
            h = torch.concatenate([mem, xs], axis=1)
            q = torch.einsum('btd,dhe->bhte', h, Wq)
            k = torch.einsum('btd,dhe->bhte', h, Wk)
            v = torch.einsum('btd,dhe->bhte', h, Wv)
            scores = torch.einsum('bhqe,bhke->bhqk', q, k) * scale
            scores = torch.where(mask[None, None], scores, -1000000000.0)
            p = _softmax(scores, axis=-1)
            o = torch.einsum('bhqk,bhke->bhqe', p, v)
            o = torch.einsum('bhte,hed->btd', o, Wo)
            mem = o[:, :M, :].clone()
            outs.append(o[:, M:, :])
        return torch.concatenate(outs, axis=1)

    def _B_ref(x, wqkv, wo):
        B, S, D = x.shape
        H = 32
        Dh = D // H
        qkv = (lambda x, *d: x.permute(*d))((x @ wqkv).reshape(B, S, 3, H, Dh), 2, 0, 3, 1, 4)
        q, k, v = (qkv[0], qkv[1], qkv[2])
        scale = Dh ** (-0.5)
        scores = torch.einsum('bhqd,bhkd->bhqk', q, k) * scale
        p = _softmax(scores, axis=-1)
        o = torch.einsum('bhqk,bhkd->bhqd', p, v)
        return (lambda x, *d: x.permute(*d))(o, 0, 2, 1, 3).reshape(B, S, D) @ wo
    x = A_x
    x = x + _A_ref(_layernorm(x, axis=-1), A_mem0, A_Wq, A_Wk, A_Wv, A_Wo, A_seg_len)
    x = x + _B_ref(_layernorm(x, axis=-1), B_wqkv, B_wo)
    x = x + _A_ref(_layernorm(x, axis=-1), A_mem0, A_Wq, A_Wk, A_Wv, A_Wo, A_seg_len)
    x = x + _B_ref(_layernorm(x, axis=-1), B_wqkv, B_wo)
    return x
```

```cpp
#include <cuda_runtime.h>
#include <cuda_bf16.h>
#include <cuda.h>
#include <stdint.h>

namespace {

constexpr int SEQ = 2048, DM = 640, HD = 6144, NSEG = 64;
constexpr int SPIN_LIMIT = 1 << 20;

__device__ __align__(128) float4 g_x[SEQ * DM / 4];
__device__ __align__(16) uint32_t g_xf[SEQ * DM / 2];
__device__ __align__(16) uint32_t g_of[SEQ * DM / 2];
__device__ __nv_bfloat16 g_q[SEQ * HD], g_o[SEQ * HD];
#define KVM 63
constexpr int KV_BYTES = 10240, KV_V = 4096, KV_KM = 8192, KV_VM = 9216;
__device__ __align__(128) uint8_t g_kv[96 * NSEG * KV_BYTES];
__device__ __align__(128) uint32_t g_xc[SEQ * DM / 2];
#define OP_B4 0
#define OP_B8 11
#define OP_B16 13
#define QA_END 12
__host__ __device__ constexpr int op_split(int b) { return b < OP_B4 ? 2 : b < OP_B8 ? 4 : b < OP_B16 ? 8 : 16; }
__host__ __device__ constexpr int fin_items(int b) { return b < OP_B8 ? 4 : op_split(b); }
#define BQ_HALF 10
__host__ __device__ constexpr int bq_items(int b) { return b < BQ_HALF ? 6 : 12; }
__device__ __align__(128) uint2 g_part[16 * 16 * 16 * 40 * 32];
__device__ __align__(128) uint32_t g_xn[SEQ * DM / 2];
constexpr int SY_Q = 128, SY_T = 160, SY_N = 161;
__device__ __align__(16) uint32_t g_sync[SY_N];
constexpr int NSLOT = 92;
__device__ uint32_t g_pool[(NSLOT + 2) * 2048];
__device__ int g_smpart[256], g_orient[NSLOT];
__device__ uint32_t g_ctapart[96];
__device__ uint32_t g_bqkv[3 * 32 * 256 * 96];

#define MODE_D(b) 0
#define DELAY(d)
#define XT(i)
#define MISS(k, n)
#define PRO(i)
#define TRACE(w)
#define ITEM(code, w)
#define TM(i)
#define TM1(i)
#define TMD(i, dep)
#define TMV(i, at, v)

__device__ __forceinline__ uint32_t gtime() { uint32_t c; asm volatile("mov.u32 %0, %%globaltimer_lo;" : "=r"(c) :: "memory"); return c; }
__device__ __forceinline__ uint32_t clk32() { uint32_t c; asm volatile("mov.u32 %0, %%clock;" : "=r"(c) :: "memory"); return c; }
__device__ __forceinline__ uint32_t s2u(const void* p) { return (uint32_t)__cvta_generic_to_shared(p); }
__device__ __forceinline__ uint32_t pack2(float a, float b) {
  uint32_t r; asm("cvt.rn.bf16x2.f32 %0, %1, %2;" : "=r"(r) : "f"(b), "f"(a)); return r; }
__device__ __forceinline__ float bf_lo(uint32_t w) { return __uint_as_float(w << 16); }
__device__ __forceinline__ float bf_hi(uint32_t w) { return __uint_as_float(w & 0xffff0000u); }
__device__ __forceinline__ float ex2(float x) { float y; asm("ex2.approx.ftz.f32 %0, %1;" : "=f"(y) : "f"(x)); return y; }

__device__ __forceinline__ void mbar_init(uint32_t bar, uint32_t n) {
  asm volatile("mbarrier.init.shared::cta.b64 [%0], %1;" :: "r"(bar), "r"(n) : "memory"); }
__device__ __forceinline__ void mbar_expect(uint32_t bar, uint32_t bytes) {
  asm volatile("mbarrier.arrive.expect_tx.shared::cta.b64 _, [%0], %1;" :: "r"(bar), "r"(bytes) : "memory"); }
__device__ __forceinline__ void mbar_arrive(uint32_t bar) {
  asm volatile("mbarrier.arrive.shared::cta.b64 _, [%0];" :: "r"(bar) : "memory"); }
__device__ __forceinline__ void mbar_wait(uint32_t bar, uint32_t ph) {
  asm volatile("{.reg .pred p; .reg .u32 n; mov.u32 n, 0;\n"
               "W: mbarrier.try_wait.parity.shared::cta.b64 p, [%0], %1; @p bra D;\n"
               "add.u32 n, n, 1; setp.gt.u32 p, n, %2; @p trap; bra W;\n"
               "D: }" :: "r"(bar), "r"(ph), "n"(SPIN_LIMIT) : "memory");
}
__device__ __forceinline__ void mbar_wait_cluster(uint32_t bar, uint32_t ph) {
  asm volatile("{.reg .pred p; .reg .u32 n; mov.u32 n, 0;\n"
               "W: mbarrier.try_wait.parity.acquire.cluster.shared::cta.b64 p, [%0], %1; @p bra D;\n"
               "add.u32 n, n, 1; setp.gt.u32 p, n, %2; @p trap; bra W;\n"
               "D: }" :: "r"(bar), "r"(ph), "n"(SPIN_LIMIT) : "memory");
}
__device__ __forceinline__ void spin_guard(int& n) {
  asm volatile("{.reg .pred p; add.s32 %0, %0, 1; setp.gt.s32 p, %0, %1; @p trap;}" : "+r"(n) : "n"(SPIN_LIMIT));
}
__device__ __forceinline__ void pdl_wait() { asm volatile("griddepcontrol.wait;" ::: "memory"); TRACE(1); }
__device__ __forceinline__ void pdl_launch() { asm volatile("griddepcontrol.launch_dependents;" ::: "memory"); }
__device__ __forceinline__ uint32_t ld_acquire(const uint32_t* p) { uint32_t v; asm volatile("ld.acquire.gpu.global.u32 %0, [%1];" : "=r"(v) : "l"(p) : "memory"); return v; }
__device__ __forceinline__ void red_release(uint32_t* p, uint32_t v) { asm volatile("red.release.gpu.global.add.u32 [%0], %1;" :: "l"(p), "r"(v) : "memory"); }
__device__ __forceinline__ void red_relaxed(uint32_t* p, uint32_t v) { asm volatile("red.relaxed.gpu.global.add.u32 [%0], %1;" :: "l"(p), "r"(v) : "memory"); }
__device__ __forceinline__ void fence_async_global() { asm volatile("fence.proxy.async.global;" ::: "memory"); }
__device__ __forceinline__ void fence_async() { asm volatile("fence.proxy.async.shared::cta;" ::: "memory"); }
__device__ __forceinline__ void bar_sync(int id, int n) { asm volatile("bar.sync %0, %1;" :: "r"(id), "r"(n) : "memory"); }
__device__ __forceinline__ void bar_arrive(int id, int n) { asm volatile("bar.arrive %0, %1;" :: "r"(id), "r"(n) : "memory"); }
__device__ __forceinline__ void tma_load(uint32_t dst, const CUtensorMap* m, int c0, int c1, uint32_t bar) {
  asm volatile("cp.async.bulk.tensor.2d.shared::cluster.global.mbarrier::complete_tx::bytes [%0], [%1, {%3, %4}], [%2];"
               :: "r"(dst), "l"(m), "r"(bar), "r"(c0), "r"(c1) : "memory"); }
__device__ __forceinline__ void tma_store(const CUtensorMap* m, uint32_t src, int c0, int c1) {
  asm volatile("cp.async.bulk.tensor.2d.global.shared::cta.bulk_group [%0, {%2, %3}], [%1];"
               :: "l"(m), "r"(src), "r"(c0), "r"(c1) : "memory"); }
__device__ __forceinline__ void tma_store_stream(const CUtensorMap* m, uint32_t src, int c0, int c1) {
  asm volatile("{.reg .b64 pol; createpolicy.fractional.L2::evict_first.b64 pol, 1.0;\n"
               "cp.async.bulk.tensor.2d.global.shared::cta.bulk_group.L2::cache_hint [%0, {%2, %3}], [%1], pol;}"
               :: "l"(m), "r"(src), "r"(c0), "r"(c1) : "memory"); }
__device__ __forceinline__ void bulk_load(uint32_t dst, const void* src, uint32_t bytes, uint32_t bar) {
  asm volatile("cp.async.bulk.shared::cluster.global.mbarrier::complete_tx::bytes [%0], [%1], %2, [%3];"
               :: "r"(dst), "l"(src), "r"(bytes), "r"(bar) : "memory"); }
__device__ __forceinline__ void bulk_send(uint32_t dst, uint32_t src, uint32_t bytes, uint32_t bar) {
  asm volatile("cp.async.bulk.shared::cluster.shared::cta.mbarrier::complete_tx::bytes [%0], [%1], %2, [%3];"
               :: "r"(dst), "r"(src), "r"(bytes), "r"(bar) : "memory"); }
__device__ __forceinline__ void bulk_store(void* dst, uint32_t src, uint32_t bytes) {
  asm volatile("cp.async.bulk.global.shared::cta.bulk_group [%0], [%1], %2;" :: "l"(dst), "r"(src), "r"(bytes) : "memory"); }
__device__ __forceinline__ void bulk_commit() { asm volatile("cp.async.bulk.commit_group;" ::: "memory"); }
template <int N> __device__ __forceinline__ void bulk_wait_read() { asm volatile("cp.async.bulk.wait_group.read %0;" :: "n"(N) : "memory"); }
template <int N> __device__ __forceinline__ void bulk_wait() { asm volatile("cp.async.bulk.wait_group %0;" :: "n"(N) : "memory"); }

__device__ __forceinline__ uint64_t mkdesc(uint32_t addr, uint32_t lbo, uint32_t sbo, uint32_t sw) {
  return (uint64_t)((addr & 0x3FFFF) >> 4) | ((uint64_t)(lbo >> 4) << 16) | ((uint64_t)(sbo >> 4) << 32) | ((uint64_t)sw << 62); }
__device__ __forceinline__ void wg_fence() { asm volatile("wgmma.fence.sync.aligned;" ::: "memory"); }
__device__ __forceinline__ void wg_commit() { asm volatile("wgmma.commit_group.sync.aligned;" ::: "memory"); }
template <int N> __device__ __forceinline__ void wg_wait() { asm volatile("wgmma.wait_group.sync.aligned %0;" :: "n"(N) : "memory"); }
template <int N> __device__ __forceinline__ void reg_fence(float* d) {
#pragma unroll
  for (int i = 0; i < N; i++) asm volatile("" : "+f"(d[i]) :: "memory");
}

__device__ __forceinline__ void mma16(float* d, uint32_t a0, uint32_t a1, uint32_t a2, uint32_t a3, uint32_t b0, uint32_t b1) {
  asm volatile("mma.sync.aligned.m16n8k16.row.col.f32.bf16.bf16.f32 {%0,%1,%2,%3},{%4,%5,%6,%7},{%8,%9},{%0,%1,%2,%3};"
               : "+f"(d[0]), "+f"(d[1]), "+f"(d[2]), "+f"(d[3]) : "r"(a0), "r"(a1), "r"(a2), "r"(a3), "r"(b0), "r"(b1)); }
__device__ __forceinline__ void mma8(float* d, uint32_t a0, uint32_t a1, uint32_t b0) {
  asm volatile("mma.sync.aligned.m16n8k8.row.col.f32.bf16.bf16.f32 {%0,%1,%2,%3},{%4,%5},{%6},{%0,%1,%2,%3};"
               : "+f"(d[0]), "+f"(d[1]), "+f"(d[2]), "+f"(d[3]) : "r"(a0), "r"(a1), "r"(b0)); }
__device__ __forceinline__ void ldsm4(uint32_t* r, uint32_t a) {
  asm volatile("ldmatrix.sync.aligned.m8n8.x4.shared.b16 {%0,%1,%2,%3},[%4];" : "=r"(r[0]), "=r"(r[1]), "=r"(r[2]), "=r"(r[3]) : "r"(a) : "memory"); }
__device__ __forceinline__ void ldsm4t(uint32_t* r, uint32_t a) {
  asm volatile("ldmatrix.sync.aligned.m8n8.x4.trans.shared.b16 {%0,%1,%2,%3},[%4];" : "=r"(r[0]), "=r"(r[1]), "=r"(r[2]), "=r"(r[3]) : "r"(a) : "memory"); }
__device__ __forceinline__ void ldsm2(uint32_t* r, uint32_t a) {
  asm volatile("ldmatrix.sync.aligned.m8n8.x2.shared.b16 {%0,%1},[%2];" : "=r"(r[0]), "=r"(r[1]) : "r"(a) : "memory"); }
__device__ __forceinline__ void stsm4(uint32_t a, uint32_t r0, uint32_t r1, uint32_t r2, uint32_t r3) {
  asm volatile("stmatrix.sync.aligned.m8n8.x4.shared.b16 [%0], {%1,%2,%3,%4};" :: "r"(a), "r"(r0), "r"(r1), "r"(r2), "r"(r3) : "memory"); }
__device__ __forceinline__ void stsm2t(uint32_t a, uint32_t r0, uint32_t r1) {
  asm volatile("stmatrix.sync.aligned.m8n8.x2.trans.shared.b16 [%0], {%1,%2};" :: "r"(a), "r"(r0), "r"(r1) : "memory"); }
__device__ __forceinline__ void stsm4t(uint32_t a, uint32_t r0, uint32_t r1, uint32_t r2, uint32_t r3) {
  asm volatile("stmatrix.sync.aligned.m8n8.x4.trans.shared.b16 [%0], {%1,%2,%3,%4};" :: "r"(a), "r"(r0), "r"(r1), "r"(r2), "r"(r3) : "memory"); }
__device__ __forceinline__ void st_async128(uint32_t a, uint4 v, uint32_t bar) {
  asm volatile("st.async.shared::cluster.mbarrier::complete_tx::bytes.v4.b32 [%0], {%1,%2,%3,%4}, [%5];" :: "r"(a), "r"(v.x), "r"(v.y), "r"(v.z), "r"(v.w), "r"(bar) : "memory"); }
__device__ __forceinline__ void sts32(uint32_t a, uint32_t v) { asm volatile("st.shared.b32 [%0], %1;" :: "r"(a), "r"(v) : "memory"); }
__device__ __forceinline__ void sts64f(uint32_t a, float x, float y) { asm volatile("st.shared.v2.f32 [%0], {%1,%2};" :: "r"(a), "f"(x), "f"(y) : "memory"); }
__device__ __forceinline__ void sts128(uint32_t a, uint4 v) {
  asm volatile("st.shared.v4.b32 [%0], {%1,%2,%3,%4};" :: "r"(a), "r"(v.x), "r"(v.y), "r"(v.z), "r"(v.w) : "memory"); }
__device__ __forceinline__ void sts128f(uint32_t a, float x, float y, float z, float w) {
  asm volatile("st.shared.v4.f32 [%0], {%1,%2,%3,%4};" :: "r"(a), "f"(x), "f"(y), "f"(z), "f"(w) : "memory"); }
__device__ __forceinline__ float lds32f(uint32_t a) { float v; asm volatile("ld.shared.f32 %0, [%1];" : "=f"(v) : "r"(a) : "memory"); return v; }
__device__ __forceinline__ float2 lds64f(uint32_t a) { float2 v; asm volatile("ld.shared.v2.f32 {%0,%1}, [%2];" : "=f"(v.x), "=f"(v.y) : "r"(a) : "memory"); return v; }
__device__ __forceinline__ float4 lds128f(uint32_t a) {
  float4 v; asm volatile("ld.shared.v4.f32 {%0,%1,%2,%3}, [%4];" : "=f"(v.x), "=f"(v.y), "=f"(v.z), "=f"(v.w) : "r"(a) : "memory"); return v; }
__device__ __forceinline__ uint4 lds128(uint32_t a) {
  uint4 v; asm volatile("ld.shared.v4.b32 {%0,%1,%2,%3}, [%4];" : "=r"(v.x), "=r"(v.y), "=r"(v.z), "=r"(v.w) : "r"(a) : "memory"); return v; }
__device__ __forceinline__ uint4 ldg_strong128(const void* p) {
  uint4 v; asm volatile("ld.relaxed.gpu.global.v4.u32 {%0,%1,%2,%3}, [%4];" : "=r"(v.x), "=r"(v.y), "=r"(v.z), "=r"(v.w) : "l"(p) : "memory"); return v; }
__device__ __forceinline__ void stg_strong32(void* p, uint32_t v) { asm volatile("st.relaxed.gpu.global.u32 [%0], %1;" :: "l"(p), "r"(v) : "memory"); }
__device__ __forceinline__ void stg_strong16(void* p, uint32_t v) { asm volatile("st.relaxed.gpu.global.u16 [%0], %1;" :: "l"(p), "h"((uint16_t)v) : "memory"); }
__device__ __forceinline__ void stg_strong128(void* p, uint4 v) {
  asm volatile("st.relaxed.gpu.global.v4.u32 [%0], {%1,%2,%3,%4};" :: "l"(p), "r"(v.x), "r"(v.y), "r"(v.z), "r"(v.w) : "memory"); }
__device__ __forceinline__ uint32_t mapa(uint32_t a, uint32_t r) {
  uint32_t o; asm("mapa.shared::cluster.u32 %0, %1, %2;" : "=r"(o) : "r"(a), "r"(r)); return o; }
__device__ __forceinline__ void st_async2f(uint32_t a, float x, float y, uint32_t bar) {
  asm volatile("st.async.shared::cluster.mbarrier::complete_tx::bytes.v2.f32 [%0], {%1,%2}, [%3];" :: "r"(a), "f"(x), "f"(y), "r"(bar) : "memory"); }
__device__ __forceinline__ void st_async32(uint32_t a, uint32_t x, uint32_t bar) {
  asm volatile("st.async.shared::cluster.mbarrier::complete_tx::bytes.b32 [%0], %1, [%2];" :: "r"(a), "r"(x), "r"(bar) : "memory"); }
__device__ __forceinline__ uint32_t lds32(uint32_t a) { uint32_t v; asm volatile("ld.shared.b32 %0, [%1];" : "=r"(v) : "r"(a) : "memory"); return v; }
__device__ __forceinline__ void st_async64(uint32_t a, uint32_t x, uint32_t y, uint32_t bar) {
  asm volatile("st.async.shared::cluster.mbarrier::complete_tx::bytes.v2.b32 [%0], {%1,%2}, [%3];" :: "r"(a), "r"(x), "r"(y), "r"(bar) : "memory"); }
__device__ __forceinline__ uint2 lds64(uint32_t a) { uint2 v; asm volatile("ld.shared.v2.b32 {%0,%1}, [%2];" : "=r"(v.x), "=r"(v.y) : "r"(a) : "memory"); return v; }
__device__ __forceinline__ void sts64(uint32_t a, uint32_t x, uint32_t y) { asm volatile("st.shared.v2.b32 [%0], {%1,%2};" :: "r"(a), "r"(x), "r"(y) : "memory"); }
__device__ __forceinline__ uint32_t ldg_strong32(const void* p) { uint32_t v; asm volatile("ld.relaxed.gpu.global.u32 %0, [%1];" : "=r"(v) : "l"(p) : "memory"); return v; }
__device__ __forceinline__ uint32_t transpose8(uint32_t x) { uint32_t r; asm volatile("movmatrix.sync.aligned.m8n8.trans.b16 %0, %1;" : "=r"(r) : "r"(x)); return r; }
__device__ __forceinline__ uint32_t hadd2(uint32_t a, uint32_t b) { uint32_t r; asm("add.rn.bf16x2 %0, %1, %2;" : "=r"(r) : "r"(a), "r"(b)); return r; }
__device__ __forceinline__ uint32_t min4(uint4 v) { return min(__vimin3_u32(v.x, v.y, v.z), v.w); }

__device__ __forceinline__ void wg_rs64_01(float* d, uint32_t a0, uint32_t a1, uint32_t a2, uint32_t a3, uint64_t db, int sd) {
  asm volatile("{.reg .pred p; setp.ne.b32 p, %37, 0;\n"
    "wgmma.mma_async.sync.aligned.m64n64k16.f32.bf16.bf16 {%0,%1,%2,%3,%4,%5,%6,%7,%8,%9,%10,%11,%12,%13,%14,%15,%16,%17,%18,%19,%20,%21,%22,%23,%24,%25,%26,%27,%28,%29,%30,%31}, {%32,%33,%34,%35}, %36, p, 1, 1, 1;}"
    : "+f"(d[0]),"+f"(d[1]),"+f"(d[2]),"+f"(d[3]),"+f"(d[4]),"+f"(d[5]),"+f"(d[6]),"+f"(d[7]),"+f"(d[8]),"+f"(d[9]),"+f"(d[10]),"+f"(d[11]),"+f"(d[12]),"+f"(d[13]),"+f"(d[14]),"+f"(d[15]),"+f"(d[16]),"+f"(d[17]),"+f"(d[18]),"+f"(d[19]),"+f"(d[20]),"+f"(d[21]),"+f"(d[22]),"+f"(d[23]),"+f"(d[24]),"+f"(d[25]),"+f"(d[26]),"+f"(d[27]),"+f"(d[28]),"+f"(d[29]),"+f"(d[30]),"+f"(d[31])
    : "r"(a0), "r"(a1), "r"(a2), "r"(a3), "l"(db), "r"(sd));
}
__device__ __forceinline__ void wg_ss192_01(float* d, uint64_t da, uint64_t db, int sd) {
  asm volatile("{.reg .pred p; setp.ne.b32 p, %98, 0;\n"
    "wgmma.mma_async.sync.aligned.m64n192k16.f32.bf16.bf16 {%0,%1,%2,%3,%4,%5,%6,%7,%8,%9,%10,%11,%12,%13,%14,%15,%16,%17,%18,%19,%20,%21,%22,%23,%24,%25,%26,%27,%28,%29,%30,%31,%32,%33,%34,%35,%36,%37,%38,%39,%40,%41,%42,%43,%44,%45,%46,%47,%48,%49,%50,%51,%52,%53,%54,%55,%56,%57,%58,%59,%60,%61,%62,%63,%64,%65,%66,%67,%68,%69,%70,%71,%72,%73,%74,%75,%76,%77,%78,%79,%80,%81,%82,%83,%84,%85,%86,%87,%88,%89,%90,%91,%92,%93,%94,%95}, %96, %97, p, 1, 1, 0, 1;}"
    : "+f"(d[0]),"+f"(d[1]),"+f"(d[2]),"+f"(d[3]),"+f"(d[4]),"+f"(d[5]),"+f"(d[6]),"+f"(d[7]),"+f"(d[8]),"+f"(d[9]),"+f"(d[10]),"+f"(d[11]),"+f"(d[12]),"+f"(d[13]),"+f"(d[14]),"+f"(d[15]),"+f"(d[16]),"+f"(d[17]),"+f"(d[18]),"+f"(d[19]),"+f"(d[20]),"+f"(d[21]),"+f"(d[22]),"+f"(d[23]),"+f"(d[24]),"+f"(d[25]),"+f"(d[26]),"+f"(d[27]),"+f"(d[28]),"+f"(d[29]),"+f"(d[30]),"+f"(d[31]),"+f"(d[32]),"+f"(d[33]),"+f"(d[34]),"+f"(d[35]),"+f"(d[36]),"+f"(d[37]),"+f"(d[38]),"+f"(d[39]),"+f"(d[40]),"+f"(d[41]),"+f"(d[42]),"+f"(d[43]),"+f"(d[44]),"+f"(d[45]),"+f"(d[46]),"+f"(d[47]),"+f"(d[48]),"+f"(d[49]),"+f"(d[50]),"+f"(d[51]),"+f"(d[52]),"+f"(d[53]),"+f"(d[54]),"+f"(d[55]),"+f"(d[56]),"+f"(d[57]),"+f"(d[58]),"+f"(d[59]),"+f"(d[60]),"+f"(d[61]),"+f"(d[62]),"+f"(d[63]),"+f"(d[64]),"+f"(d[65]),"+f"(d[66]),"+f"(d[67]),"+f"(d[68]),"+f"(d[69]),"+f"(d[70]),"+f"(d[71]),"+f"(d[72]),"+f"(d[73]),"+f"(d[74]),"+f"(d[75]),"+f"(d[76]),"+f"(d[77]),"+f"(d[78]),"+f"(d[79]),"+f"(d[80]),"+f"(d[81]),"+f"(d[82]),"+f"(d[83]),"+f"(d[84]),"+f"(d[85]),"+f"(d[86]),"+f"(d[87]),"+f"(d[88]),"+f"(d[89]),"+f"(d[90]),"+f"(d[91]),"+f"(d[92]),"+f"(d[93]),"+f"(d[94]),"+f"(d[95])
    : "l"(da), "l"(db), "r"(sd));
}
__device__ __forceinline__ void wg_ss128_01(float* d, uint64_t da, uint64_t db, int sd) {
  asm volatile("{.reg .pred p; setp.ne.b32 p, %66, 0;\n"
    "wgmma.mma_async.sync.aligned.m64n128k16.f32.bf16.bf16 {%0,%1,%2,%3,%4,%5,%6,%7,%8,%9,%10,%11,%12,%13,%14,%15,%16,%17,%18,%19,%20,%21,%22,%23,%24,%25,%26,%27,%28,%29,%30,%31,%32,%33,%34,%35,%36,%37,%38,%39,%40,%41,%42,%43,%44,%45,%46,%47,%48,%49,%50,%51,%52,%53,%54,%55,%56,%57,%58,%59,%60,%61,%62,%63}, %64, %65, p, 1, 1, 0, 1;}"
    : "+f"(d[0]),"+f"(d[1]),"+f"(d[2]),"+f"(d[3]),"+f"(d[4]),"+f"(d[5]),"+f"(d[6]),"+f"(d[7]),"+f"(d[8]),"+f"(d[9]),"+f"(d[10]),"+f"(d[11]),"+f"(d[12]),"+f"(d[13]),"+f"(d[14]),"+f"(d[15]),"+f"(d[16]),"+f"(d[17]),"+f"(d[18]),"+f"(d[19]),"+f"(d[20]),"+f"(d[21]),"+f"(d[22]),"+f"(d[23]),"+f"(d[24]),"+f"(d[25]),"+f"(d[26]),"+f"(d[27]),"+f"(d[28]),"+f"(d[29]),"+f"(d[30]),"+f"(d[31]),"+f"(d[32]),"+f"(d[33]),"+f"(d[34]),"+f"(d[35]),"+f"(d[36]),"+f"(d[37]),"+f"(d[38]),"+f"(d[39]),"+f"(d[40]),"+f"(d[41]),"+f"(d[42]),"+f"(d[43]),"+f"(d[44]),"+f"(d[45]),"+f"(d[46]),"+f"(d[47]),"+f"(d[48]),"+f"(d[49]),"+f"(d[50]),"+f"(d[51]),"+f"(d[52]),"+f"(d[53]),"+f"(d[54]),"+f"(d[55]),"+f"(d[56]),"+f"(d[57]),"+f"(d[58]),"+f"(d[59]),"+f"(d[60]),"+f"(d[61]),"+f"(d[62]),"+f"(d[63])
    : "l"(da), "l"(db), "r"(sd));
}
__device__ __forceinline__ void wg_ss160_01(float* d, uint64_t da, uint64_t db, int sd) {
  asm volatile("{.reg .pred p; setp.ne.b32 p, %82, 0;\n"
    "wgmma.mma_async.sync.aligned.m64n160k16.f32.bf16.bf16 {%0,%1,%2,%3,%4,%5,%6,%7,%8,%9,%10,%11,%12,%13,%14,%15,%16,%17,%18,%19,%20,%21,%22,%23,%24,%25,%26,%27,%28,%29,%30,%31,%32,%33,%34,%35,%36,%37,%38,%39,%40,%41,%42,%43,%44,%45,%46,%47,%48,%49,%50,%51,%52,%53,%54,%55,%56,%57,%58,%59,%60,%61,%62,%63,%64,%65,%66,%67,%68,%69,%70,%71,%72,%73,%74,%75,%76,%77,%78,%79}, %80, %81, p, 1, 1, 0, 1;}"
    : "+f"(d[0]),"+f"(d[1]),"+f"(d[2]),"+f"(d[3]),"+f"(d[4]),"+f"(d[5]),"+f"(d[6]),"+f"(d[7]),"+f"(d[8]),"+f"(d[9]),"+f"(d[10]),"+f"(d[11]),"+f"(d[12]),"+f"(d[13]),"+f"(d[14]),"+f"(d[15]),"+f"(d[16]),"+f"(d[17]),"+f"(d[18]),"+f"(d[19]),"+f"(d[20]),"+f"(d[21]),"+f"(d[22]),"+f"(d[23]),"+f"(d[24]),"+f"(d[25]),"+f"(d[26]),"+f"(d[27]),"+f"(d[28]),"+f"(d[29]),"+f"(d[30]),"+f"(d[31]),"+f"(d[32]),"+f"(d[33]),"+f"(d[34]),"+f"(d[35]),"+f"(d[36]),"+f"(d[37]),"+f"(d[38]),"+f"(d[39]),"+f"(d[40]),"+f"(d[41]),"+f"(d[42]),"+f"(d[43]),"+f"(d[44]),"+f"(d[45]),"+f"(d[46]),"+f"(d[47]),"+f"(d[48]),"+f"(d[49]),"+f"(d[50]),"+f"(d[51]),"+f"(d[52]),"+f"(d[53]),"+f"(d[54]),"+f"(d[55]),"+f"(d[56]),"+f"(d[57]),"+f"(d[58]),"+f"(d[59]),"+f"(d[60]),"+f"(d[61]),"+f"(d[62]),"+f"(d[63]),"+f"(d[64]),"+f"(d[65]),"+f"(d[66]),"+f"(d[67]),"+f"(d[68]),"+f"(d[69]),"+f"(d[70]),"+f"(d[71]),"+f"(d[72]),"+f"(d[73]),"+f"(d[74]),"+f"(d[75]),"+f"(d[76]),"+f"(d[77]),"+f"(d[78]),"+f"(d[79])
    : "l"(da), "l"(db), "r"(sd));
}
__device__ __forceinline__ void wg_rs32_00(float* d, uint32_t a0, uint32_t a1, uint32_t a2, uint32_t a3, uint64_t db, int sd) {
  asm volatile("{.reg .pred p; setp.ne.b32 p, %21, 0;\n"
    "wgmma.mma_async.sync.aligned.m64n32k16.f32.bf16.bf16 {%0,%1,%2,%3,%4,%5,%6,%7,%8,%9,%10,%11,%12,%13,%14,%15}, {%16,%17,%18,%19}, %20, p, 1, 1, 0;}"
    : "+f"(d[0]),"+f"(d[1]),"+f"(d[2]),"+f"(d[3]),"+f"(d[4]),"+f"(d[5]),"+f"(d[6]),"+f"(d[7]),"+f"(d[8]),"+f"(d[9]),"+f"(d[10]),"+f"(d[11]),"+f"(d[12]),"+f"(d[13]),"+f"(d[14]),"+f"(d[15])
    : "r"(a0), "r"(a1), "r"(a2), "r"(a3), "l"(db), "r"(sd));
}
__device__ __forceinline__ void wg_rs64_00(float* d, uint32_t a0, uint32_t a1, uint32_t a2, uint32_t a3, uint64_t db, int sd) {
  asm volatile("{.reg .pred p; setp.ne.b32 p, %37, 0;\n"
    "wgmma.mma_async.sync.aligned.m64n64k16.f32.bf16.bf16 {%0,%1,%2,%3,%4,%5,%6,%7,%8,%9,%10,%11,%12,%13,%14,%15,%16,%17,%18,%19,%20,%21,%22,%23,%24,%25,%26,%27,%28,%29,%30,%31}, {%32,%33,%34,%35}, %36, p, 1, 1, 0;}"
    : "+f"(d[0]),"+f"(d[1]),"+f"(d[2]),"+f"(d[3]),"+f"(d[4]),"+f"(d[5]),"+f"(d[6]),"+f"(d[7]),"+f"(d[8]),"+f"(d[9]),"+f"(d[10]),"+f"(d[11]),"+f"(d[12]),"+f"(d[13]),"+f"(d[14]),"+f"(d[15]),"+f"(d[16]),"+f"(d[17]),"+f"(d[18]),"+f"(d[19]),"+f"(d[20]),"+f"(d[21]),"+f"(d[22]),"+f"(d[23]),"+f"(d[24]),"+f"(d[25]),"+f"(d[26]),"+f"(d[27]),"+f"(d[28]),"+f"(d[29]),"+f"(d[30]),"+f"(d[31])
    : "r"(a0), "r"(a1), "r"(a2), "r"(a3), "l"(db), "r"(sd));
}
__device__ __forceinline__ void wg_rs128_00(float* d, uint32_t a0, uint32_t a1, uint32_t a2, uint32_t a3, uint64_t db, int sd) {
  asm volatile("{.reg .pred p; setp.ne.b32 p, %69, 0;\n"
    "wgmma.mma_async.sync.aligned.m64n128k16.f32.bf16.bf16 {%0,%1,%2,%3,%4,%5,%6,%7,%8,%9,%10,%11,%12,%13,%14,%15,%16,%17,%18,%19,%20,%21,%22,%23,%24,%25,%26,%27,%28,%29,%30,%31,%32,%33,%34,%35,%36,%37,%38,%39,%40,%41,%42,%43,%44,%45,%46,%47,%48,%49,%50,%51,%52,%53,%54,%55,%56,%57,%58,%59,%60,%61,%62,%63}, {%64,%65,%66,%67}, %68, p, 1, 1, 0;}"
    : "+f"(d[0]),"+f"(d[1]),"+f"(d[2]),"+f"(d[3]),"+f"(d[4]),"+f"(d[5]),"+f"(d[6]),"+f"(d[7]),"+f"(d[8]),"+f"(d[9]),"+f"(d[10]),"+f"(d[11]),"+f"(d[12]),"+f"(d[13]),"+f"(d[14]),"+f"(d[15]),"+f"(d[16]),"+f"(d[17]),"+f"(d[18]),"+f"(d[19]),"+f"(d[20]),"+f"(d[21]),"+f"(d[22]),"+f"(d[23]),"+f"(d[24]),"+f"(d[25]),"+f"(d[26]),"+f"(d[27]),"+f"(d[28]),"+f"(d[29]),"+f"(d[30]),"+f"(d[31]),"+f"(d[32]),"+f"(d[33]),"+f"(d[34]),"+f"(d[35]),"+f"(d[36]),"+f"(d[37]),"+f"(d[38]),"+f"(d[39]),"+f"(d[40]),"+f"(d[41]),"+f"(d[42]),"+f"(d[43]),"+f"(d[44]),"+f"(d[45]),"+f"(d[46]),"+f"(d[47]),"+f"(d[48]),"+f"(d[49]),"+f"(d[50]),"+f"(d[51]),"+f"(d[52]),"+f"(d[53]),"+f"(d[54]),"+f"(d[55]),"+f"(d[56]),"+f"(d[57]),"+f"(d[58]),"+f"(d[59]),"+f"(d[60]),"+f"(d[61]),"+f"(d[62]),"+f"(d[63])
    : "r"(a0), "r"(a1), "r"(a2), "r"(a3), "l"(db), "r"(sd));
}
__device__ __forceinline__ void wg_rs24_01(float* d, uint32_t a0, uint32_t a1, uint32_t a2, uint32_t a3, uint64_t db, int sd) {
  asm volatile("{.reg .pred p; setp.ne.b32 p, %17, 0;\n"
    "wgmma.mma_async.sync.aligned.m64n24k16.f32.bf16.bf16 {%0,%1,%2,%3,%4,%5,%6,%7,%8,%9,%10,%11}, {%12,%13,%14,%15}, %16, p, 1, 1, 1;}"
    : "+f"(d[0]),"+f"(d[1]),"+f"(d[2]),"+f"(d[3]),"+f"(d[4]),"+f"(d[5]),"+f"(d[6]),"+f"(d[7]),"+f"(d[8]),"+f"(d[9]),"+f"(d[10]),"+f"(d[11])
    : "r"(a0), "r"(a1), "r"(a2), "r"(a3), "l"(db), "r"(sd));
}

#define AB_POLY 0x77
__device__ __forceinline__ constexpr bool poly_group(int group) { return (AB_POLY >> (group & 7)) & 1; }

template <int V> struct Int { static constexpr int value = V; };

__device__ __forceinline__ int frag_word(int row, int col) {
  return (((row >> 4) * 40 + (col >> 4)) * 32 + (row & 7) * 4 + ((col & 7) >> 1)) * 4 + ((row >> 3) & 1) + ((col >> 3) & 1) * 2;
}

template <int NG>
__device__ __forceinline__ void ln_rows(float4 (&v)[NG][5], uint32_t scratch) {
  const int warp = threadIdx.x >> 5, g = (threadIdx.x & 31) >> 2;
  float stat[NG];
#pragma unroll
  for (int pass = 0; pass < 2; pass++) {
#pragma unroll
    for (int r = 0; r < NG; r++) {
      float s = 0.f;
#pragma unroll
      for (int i = 0; i < 5; i++) {
        float4& t = v[r][i];
        if (pass == 0) s += (t.x + t.y) + (t.z + t.w);
        else { t.x -= stat[r]; t.y -= stat[r]; t.z -= stat[r]; t.w -= stat[r]; s += (t.x * t.x + t.y * t.y) + (t.z * t.z + t.w * t.w); }
      }
      s += __shfl_xor_sync(~0u, s, 1);
      s += __shfl_xor_sync(~0u, s, 2);
      stat[r] = s;
    }
    bar_sync(1, 256);
    if ((threadIdx.x & 3) == 0) {
#pragma unroll
      for (int r = 0; r < NG; r++) sts32(scratch + ((r * 8 + g) * 8 + warp) * 4, __float_as_uint(stat[r]));
    }
    bar_sync(1, 256);
#pragma unroll
    for (int r = 0; r < NG; r++) {
      const float4 a = lds128f(scratch + (r * 8 + g) * 32), b = lds128f(scratch + (r * 8 + g) * 32 + 16);
      stat[r] = (((a.x + a.y) + (a.z + a.w)) + ((b.x + b.y) + (b.z + b.w))) * (1.f / DM);
    }
  }
#pragma unroll
  for (int r = 0; r < NG; r++) {
    const float rs = rsqrtf(stat[r] + 1e-5f);
#pragma unroll
    for (int i = 0; i < 5; i++) { v[r][i].x *= rs; v[r][i].y *= rs; v[r][i].z *= rs; v[r][i].w *= rs; }
  }
}

template <bool FIRST>
__global__ void __launch_bounds__(256) ln_kernel(const __nv_bfloat16* __restrict__ xin) {
  __shared__ __align__(16) float scratch[128];
  const int warp = threadIdx.x >> 5, lane = threadIdx.x & 31;
  TRACE(0);
  pdl_launch();
  if (!FIRST) pdl_wait();
  float4 v[2][5];
  float4* x = g_x + (blockIdx.x * 80 + warp * 5) * 32 + lane;
#pragma unroll
  for (int r = 0; r < 2; r++)
#pragma unroll
    for (int i = 0; i < 5; i++) {
      if (FIRST) {
        const uint32_t* src = reinterpret_cast<const uint32_t*>(xin) + (blockIdx.x * 16 + r * 8 + (lane >> 2)) * (DM / 2) + warp * 40 + i * 8 + (lane & 3);
        const uint32_t a = src[0], b = src[4];
        v[r][i] = make_float4(bf_lo(a), bf_hi(a), bf_lo(b), bf_hi(b));
        x[(r * 40 + i) * 32] = v[r][i];
      } else {
        v[r][i] = x[(r * 40 + i) * 32];
      }
    }
  ln_rows<2>(v, s2u(scratch));
  uint32_t* xc = g_xc + ((blockIdx.x >> 1) * 40 + warp * 5) * 256 + (blockIdx.x & 1) * 64 + lane;
#pragma unroll
  for (int i = 0; i < 5; i++)
#pragma unroll
    for (int r = 0; r < 2; r++) { xc[i * 256 + r * 32] = pack2(v[r][i].x, v[r][i].y); xc[i * 256 + 128 + r * 32] = pack2(v[r][i].z, v[r][i].w); }
  if (blockIdx.x >= QA_END * 8) {
    uint4* dst = reinterpret_cast<uint4*>(g_xf) + (blockIdx.x * 40 + warp * 5) * 32 + lane;
#pragma unroll
    for (int i = 0; i < 5; i++)
      dst[i * 32] = make_uint4(pack2(v[0][i].x, v[0][i].y), pack2(v[1][i].x, v[1][i].y), pack2(v[0][i].z, v[0][i].w), pack2(v[1][i].z, v[1][i].w));
  } else {
#pragma unroll
    for (int i = 0; i < 5; i++) {
      const int u = warp * 5 + i;
      uint32_t* xn = g_xn + (((blockIdx.x >> 3) * 10 + (u >> 2)) * 16 + (blockIdx.x & 1) * 8 + (blockIdx.x & 6)) * 256 + (u & 3) * 64 + lane;
#pragma unroll
      for (int r = 0; r < 2; r++) { xn[r * 256] = pack2(v[r][i].x, v[r][i].y); xn[r * 256 + 32] = pack2(v[r][i].z, v[r][i].w); }
    }
  }
  if (FIRST) pdl_wait();
  TRACE(2);
}

struct XsParams {
  CUtensorMap w[3];
  CUtensorMap o[3];
  const uint32_t* a;
  __nv_bfloat16* out;
  int ntiles, tiles_per_mat, rb0, nowait, stream_out;
  int npf, pft, ahead;
  const uint8_t* pf[4];
};
constexpr int XS_STAGES = 12, XS_STAGE_BYTES = 16384;
constexpr int XS_SMEM = 1024 + XS_STAGES * XS_STAGE_BYTES + 4 * 8192 + 256;
enum { EPI_QKV = 0, EPI_BQKV = 1, EPI_RES = 2, EPI_OUT = 3 };

template <int EPI, bool MC>
__global__ void __launch_bounds__(384, 1) xs_gemm(const __grid_constant__ XsParams p) {
  extern __shared__ uint8_t smem_raw[];
  const uint32_t sb = (s2u(smem_raw) + 1023) & ~1023u;
  const uint32_t stg = sb + XS_STAGES * XS_STAGE_BYTES, bars = stg + 4 * 8192;
  const int warp = __shfl_sync(~0u, threadIdx.x >> 5, 0), lane = threadIdx.x & 31;
  const int tot = (16 - p.rb0) * p.ntiles;
  const int rank = blockIdx.x & 1, bid = MC ? (blockIdx.x & ~15) + rank * 8 + ((blockIdx.x >> 1) & 7) : blockIdx.x;
  const int u0 = p.rb0 * p.ntiles + bid * tot / gridDim.x, u1 = p.rb0 * p.ntiles + (bid + 1) * tot / gridDim.x;
  auto release = [&](int stage) {
    const uint32_t bar = bars + 8 * (XS_STAGES + stage);
    if (lane == 0) mbar_arrive(bar);
    if (MC && lane == 1) asm volatile("mbarrier.arrive.shared::cluster.b64 _, [%0];" :: "r"(mapa(bar, rank ^ 1)) : "memory");
  };
  TRACE(0);
  pdl_launch();
  if (threadIdx.x == 0) {
    for (int i = 0; i < XS_STAGES; i++) { mbar_init(bars + 8 * i, 1); mbar_init(bars + 8 * (XS_STAGES + i), MC ? 16 : 8); }
    fence_async();
    if (MC) asm volatile("fence.mbarrier_init.release.cluster;" ::: "memory");
  }
  __syncthreads();
  if (MC) asm volatile("barrier.cluster.arrive.relaxed.aligned; barrier.cluster.wait.aligned;" ::: "memory");
  if (warp >= 8) {
    asm volatile("setmaxnreg.dec.sync.aligned.u32 40;");
    if (warp == 8 && lane == 0) {
      int st = 0; uint32_t ph = 1;
      auto l2_ahead = [&](int u) {
        if (u >= u1 || (!MC && u != u0)) return;
        const int t = u % p.ntiles, m = t / p.tiles_per_mat, col = (t - m * p.tiles_per_mat) * 64;
        for (int kb = MC ? u / p.ntiles : 0; kb < (MC ? 10 : 5); kb += MC ? 16 : 1)
          asm volatile("cp.async.bulk.prefetch.tensor.2d.L2.global [%0, {%1, %2}];" :: "l"(&p.w[m]), "r"(col), "r"(kb * (MC ? 64 : 128)) : "memory");
      };
      for (int i = 0; i < p.ahead; i++) l2_ahead(u0 + i);
      for (int u = u0; u < u1; u++) {
        const int t = u % p.ntiles, m = t / p.tiles_per_mat, col = (t - m * p.tiles_per_mat) * 64;
        l2_ahead(u + p.ahead);
        if (u == u0 || t == 0) {
          if (u == u0 && !p.nowait) pdl_wait();
          for (int i = 0; i < 10; i++) {
            mbar_wait(bars + 8 * (XS_STAGES + st), ph);
            mbar_expect(bars + 8 * st, XS_STAGE_BYTES);
            for (int w = 0; w < 8; w++)
              bulk_load(sb + st * XS_STAGE_BYTES + w * 2048, p.a + ((u / p.ntiles * 8 + w) * 40 + 4 * i) * 128, 2048, bars + 8 * st);
            if (++st == XS_STAGES) { st = 0; ph ^= 1; }
          }
        }
        if (u1 - u <= p.pft && blockIdx.x < 128) {
          const int bytes = 61440 / p.pft;
          const size_t off = (size_t)blockIdx.x * 61440 + (u1 - u - 1) * bytes;
          for (int i = 0; i < p.npf; i++) asm volatile("cp.async.bulk.prefetch.L2.global [%0], %1;" :: "l"(p.pf[i] + off), "r"(bytes) : "memory");
        }
        for (int kb = 0; kb < 5; kb++) {
          mbar_wait(bars + 8 * (XS_STAGES + st), ph);
          mbar_expect(bars + 8 * st, XS_STAGE_BYTES);
          if (MC) {
            asm volatile("cp.async.bulk.tensor.2d.shared::cluster.global.mbarrier::complete_tx::bytes.multicast::cluster [%0], [%1, {%3, %4}], [%2], %5;"
                         :: "r"(sb + st * XS_STAGE_BYTES + rank * 8192), "l"(&p.w[m]), "r"(bars + 8 * st), "r"(col), "r"(kb * 128 + rank * 64), "h"((uint16_t)3) : "memory");
          } else {
            tma_load(sb + st * XS_STAGE_BYTES, &p.w[m], col, kb * 128, bars + 8 * st);
          }
          if (++st == XS_STAGES) { st = 0; ph ^= 1; }
        }
      }
    }
    __syncwarp();
    if (MC) asm volatile("barrier.cluster.arrive.relaxed.aligned;" ::: "memory");
  } else {
    asm volatile("setmaxnreg.inc.sync.aligned.u32 232;");
    const int wg = warp >> 2, g = lane >> 2, c = lane & 3;
    if (!p.nowait) pdl_wait();
    XT(0);
    int st = 0; uint32_t ph = 0;
    for (int u = u0; u < u1;) {
    const int rb = u / p.ntiles, t0 = u - rb * p.ntiles, t1 = min(p.ntiles, t0 + u1 - u);
    uint32_t a[160];
#pragma unroll
    for (int i = 0; i < 10; i++) {
      mbar_wait(bars + 8 * st, ph);
#pragma unroll
      for (int k = 4 * i; k < 4 * i + 4; k++) {
        const uint4 v = lds128(sb + st * XS_STAGE_BYTES + warp * 2048 + (k & 3) * 512 + lane * 16);
        a[4 * k] = v.x; a[4 * k + 1] = v.y; a[4 * k + 2] = v.z; a[4 * k + 3] = v.w;
      }
      __syncwarp();
      release(st);
      if (++st == XS_STAGES) { st = 0; ph ^= 1; }
    }
    XT(1);
    const int row0 = rb * 128 + wg * 64;
    for (int t = t0; t < t1; t++, u++) {
      float d[32];
      int prev = 0;
      if (wg == 1 || u != u0) bar_sync(4 + wg, 256);
#pragma unroll
      for (int kb = 0; kb < 5; kb++) {
        mbar_wait(bars + 8 * st, ph);
        const uint64_t db = mkdesc(sb + st * XS_STAGE_BYTES, 0, 1024, 1);
        if (kb == 0) wg_fence();
#pragma unroll
        for (int kk = 0; kk < 8; kk++) {
          const int k = kb * 8 + kk;
          wg_rs64_01(d, a[4 * k], a[4 * k + 1], a[4 * k + 2], a[4 * k + 3], db + kk * 128, k != 0);
        }
        wg_commit();
        if (kb == 4 && (wg == 0 || u + 1 != u1)) bar_arrive(5 - wg, 256);
        if (kb > 0) { wg_wait<1>(); release(prev); }
        prev = st;
        if (++st == XS_STAGES) { st = 0; ph ^= 1; }
      }
      wg_wait<0>();
      reg_fence<32>(d);
      release(prev);
      XT(2 + u - u0);
      if (EPI == EPI_QKV) {
        const int m = t / p.tiles_per_mat, col = (t - m * p.tiles_per_mat) * 64;
        const uint32_t buf = stg + (wg * 2 + (u & 1)) * 8192;
        const int r = (warp & 3) * 16 + (lane & 7) + ((lane >> 3) & 1) * 8;
#pragma unroll
        for (int j = 0; j < 8; j += 2)
          stsm4(buf + r * 128 + (((j + (lane >> 4)) ^ (r & 7)) << 4), pack2(d[4 * j], d[4 * j + 1]), pack2(d[4 * j + 2], d[4 * j + 3]),
                pack2(d[4 * j + 4], d[4 * j + 5]), pack2(d[4 * j + 6], d[4 * j + 7]));
        fence_async();
        if ((threadIdx.x & 127) == 0) bulk_wait_read<0>();
        bar_sync(2 + wg, 128);
        if ((threadIdx.x & 127) == 0) {
          if (p.stream_out == 2) {} else if (p.stream_out) tma_store_stream(&p.o[m], buf, col, row0); else tma_store(&p.o[m], buf, col, row0);
          bulk_commit();
        }
      } else {
        float4* x = g_x + ((rb * 16 + warp * 2) * 40 + t * 4) * 32 + lane;
        uint32_t* out = reinterpret_cast<uint32_t*>(p.out) + (rb * 128 + warp * 16 + g) * (DM / 2) + t * 32 + c;
#pragma unroll
        for (int j = 0; j < 4; j++) {
#pragma unroll
          for (int r = 0; r < 2; r++) {
            float4 y = x[(r * 40 + j) * 32];
            y.x += d[8 * j + 2 * r]; y.y += d[8 * j + 2 * r + 1]; y.z += d[8 * j + 4 + 2 * r]; y.w += d[8 * j + 5 + 2 * r];
            if (EPI == EPI_RES) x[(r * 40 + j) * 32] = y;
            else { out[r * 8 * (DM / 2) + 8 * j] = pack2(y.x, y.y); out[r * 8 * (DM / 2) + 8 * j + 4] = pack2(y.z, y.w); }
          }
        }
      }
    }
    }
    if (EPI == EPI_QKV && (threadIdx.x & 127) == 0) {
      bulk_wait<0>();
      if (p.nowait) { fence_async_global(); red_release(g_sync + SY_Q, 1); }
    }
    __syncwarp();
    if (MC) asm volatile("barrier.cluster.arrive.relaxed.aligned; barrier.cluster.wait.aligned;" ::: "memory");
    TRACE(2);
  }
}

__device__ __forceinline__ uint8_t* pool_at(uint32_t off) {
  return reinterpret_cast<uint8_t*>((reinterpret_cast<uintptr_t>(g_pool) + 8191) & ~(uintptr_t)8191) + off; }
__device__ __forceinline__ uint32_t page_latency(uint32_t* w) {
  uint32_t best = ~0u;
  stg_strong32(w, 0u);
  for (int r = 0; r < 4; r++) {
    uint32_t t0, t1, v;
    asm volatile("mov.u32 %0, %%clock;" : "=r"(t0) :: "memory");
    asm volatile("atom.relaxed.gpu.global.exch.b32 %0, [%1], 0;" : "=r"(v) : "l"(w) : "memory");
    asm volatile("{.reg .u32 t; add.u32 t, %1, 1; mov.u32 %0, %%clock; sub.u32 %0, %0, %1;}" : "=r"(t1) : "r"(__shfl_sync(1u, v, 0)) : "memory");
    best = min(best, t1 - t0);
  }
  return best;
}
__global__ void __launch_bounds__(128) probe_kernel() {
  __shared__ int near0[4];
  TRACE(0);
  pdl_launch();
  const int w = threadIdx.x >> 5, slot = w == 0 ? NSLOT : blockIdx.x + 132 * (w - 1);
  if ((threadIdx.x & 31) == 0 && (w == 0 || slot < NSLOT)) {
    uint32_t* q = reinterpret_cast<uint32_t*>(pool_at(slot * 8192)) + (w == 0 ? (blockIdx.x & 31) * 32 + (blockIdx.x >> 5) : 0);
    near0[w] = page_latency(q) < page_latency(q + 1024);
  }
  __syncthreads();
  TRACE(2);
  if ((threadIdx.x & 31) == 0) {
    const int part = near0[0] ? 0 : 1;
    if (w == 0) { uint32_t smid; asm("mov.u32 %0, %%smid;" : "=r"(smid)); g_smpart[smid & 255] = part; }
    else if (slot < NSLOT) g_orient[slot] = near0[w] ? part : 1 - part;
  }
}

struct ChainParams {
  CUtensorMap wq, wk, wv, wo;
  const __nv_bfloat16* mem0;
  uint8_t *pool, *kv;
  const uint32_t* xc;
  uint32_t* sync;
  int d1, d1b, d2, d2b, mode;
};
constexpr int CH_WQ = 0, CH_WO = 81920, CH_X = CH_WO + 86016, CH_M = CH_X + 20480, CH_KT = CH_X + 40960, CH_VT = CH_KT + 4096,
              CH_QK = CH_VT + 8192, CH_VP = CH_QK + 4096, CH_SX = CH_VP + 1024, CH_O = CH_SX + 2304, CH_ID = CH_O + 3072,
              CH_BAR = CH_ID + 512;
constexpr int CH_SMEM = CH_BAR + 128;
constexpr int CH_BASE = 1024;
#define CH_VK0 8
#define CH_VK1 20
#define CH_L0 4
#define CH_LR 4
#define CH_CL 3
#define NOX 0
#define CH_XA 0
#define CH_XB 1
#define CH_W1 3
#define CH_W2 17
#define CH_W3 26
#define CH_RA 1
#define CH_R1 4
#define CH_TW 12
__device__ __forceinline__ uint32_t opaque(uint32_t x) { return __shfl_sync(~0u, x, threadIdx.x & 31); }
__device__ __forceinline__ uint32_t nz(uint32_t x) { uint32_t r; asm("max.u32 %0, %1, 1;" : "=r"(r) : "r"(x)); return r; }
__device__ __forceinline__ uint32_t pack_tag(float lo, float hi, uint32_t tag, uint32_t mask) {
  uint32_t r;
  asm("lop3.b32 %0, %1, %2, %3, 0xD8;" : "=r"(r) : "r"(pack2(lo, hi)), "r"(tag), "r"(mask));
  return r;
}
__device__ __forceinline__ uint32_t differ(uint32_t a, uint32_t b, uint32_t t) { uint32_t r; asm("lop3.b32 %0, %1, %2, %3, 0x7E;" : "=r"(r) : "r"(a), "r"(b), "r"(t)); return r; }
__device__ __forceinline__ void mbar_wait_hot(uint32_t bar, uint32_t ph) {
  uint32_t ok;
  asm volatile("{.reg .pred p; mbarrier.try_wait.parity.shared::cta.b64 p, [%1], %2; selp.u32 %0, 1, 0, p;}" : "=r"(ok) : "r"(bar), "r"(ph) : "memory");
  if (__builtin_expect(!ok, 0)) mbar_wait(bar, ph);
}
__device__ __forceinline__ bool elect() {
  uint32_t r; asm volatile("{.reg .pred p; elect.sync _|p, 0xffffffff; selp.u32 %0, 1, 0, p;}" : "=r"(r)); return r; }
__device__ __forceinline__ uint32_t or3(uint32_t a, uint32_t b, uint32_t c) { uint32_t r; asm("lop3.b32 %0, %1, %2, %3, 0xFE;" : "=r"(r) : "r"(a), "r"(b), "r"(c)); return r; }
__device__ __forceinline__ void pin() { pdl_launch(); }
__device__ __forceinline__ void mma16h(float* d, uint32_t a0, uint32_t a2, uint32_t b0, uint32_t b1) {
  asm volatile("{.reg .b32 u, v; mma.sync.aligned.m16n8k16.row.col.f32.bf16.bf16.f32 {%0,%1,%2,%3},{%4,u,%5,v},{%6,%7},{%0,%1,%2,%3};}"
               : "+f"(d[0]), "+f"(d[1]), "+f"(d[2]), "+f"(d[3]) : "r"(a0), "r"(a2), "r"(b0), "r"(b1)); }
__device__ __forceinline__ void mma8h(float* d, uint32_t a0, uint32_t b0) {
  asm volatile("{.reg .b32 u; mma.sync.aligned.m16n8k8.row.col.f32.bf16.bf16.f32 {%0,%1,%2,%3},{%4,u},{%5},{%0,%1,%2,%3};}"
               : "+f"(d[0]), "+f"(d[1]), "+f"(d[2]), "+f"(d[3]) : "r"(a0), "r"(b0)); }
__device__ __forceinline__ uint32_t absmax2(uint32_t a, uint32_t b) { uint32_t r; asm("max.xorsign.abs.bf16x2 %0, %1, %2;" : "=r"(r) : "r"(a), "r"(b)); return r; }
__device__ __forceinline__ void until(uint32_t t) { while ((int)(clk32() - t) < 0) {} }
__device__ __forceinline__ uint4 pack8(const float* d) { return make_uint4(pack2(d[0], d[1]), pack2(d[2], d[3]), pack2(d[4], d[5]), pack2(d[6], d[7])); }
__device__ __forceinline__ void add8(float* d, uint4 v) {
  d[0] += bf_lo(v.x); d[1] += bf_hi(v.x); d[2] += bf_lo(v.y); d[3] += bf_hi(v.y);
  d[4] += bf_lo(v.z); d[5] += bf_hi(v.z); d[6] += bf_lo(v.w); d[7] += bf_hi(v.w);
}

template <int WG>
__device__ __forceinline__ void chain_body(const ChainParams& p, const uint32_t sb, const int orient) {
  const int tid = threadIdx.x & 127, t4 = __shfl_sync(~0u, tid >> 5, 0), lane = tid & 31;
  const int cta = blockIdx.x, h = cta / 3, j = cta - 3 * h, colbase = cta * 64;
  const uint32_t bWo = sb + CH_BAR, bWq = bWo + 8, bX = bWo + 16, bXA = bWo + 24, bXB = bWo + 32, bO = bWo + 40, bW0 = bWo + 48;
  uint32_t ak[80], av[80], tw[4 * CH_TW];
  const uint32_t wq = opaque(sb + CH_WQ + (WG * 320 + (lane & 7) + (lane >> 4) * 8) * 128 + (((2 * t4 + ((lane >> 3) & 1)) ^ (lane & 7)) << 4));
  PRO(0);
#pragma unroll
  for (int k = 0; k < 20; k++) {
    if (k == 0 || (WG * 20 + k) % 8 == 0) mbar_wait(bW0 + 8 * ((WG * 20 + k) / 8), 0);
    ldsm4t(&ak[4 * k], wq + k * 2048);
  }
  const uint32_t* part_of = g_ctapart + (threadIdx.x >= 80 ? cta : threadIdx.x);
  uint32_t reader = WG == 0 ? ldg_strong32(part_of) : 0;
  bar_sync(6, 256);
  if (WG == 1 && tid == 0) {
    fence_async();
    mbar_expect(bWq, 81920);
    for (int i = 0; i < 5; i++) tma_load(sb + CH_WQ + i * 16384, &p.wq, colbase, i * 128, bWq);
  }
  PRO(1);
#pragma unroll
  for (int k = 0; k < 20; k++) {
    if (k == 0 || (WG * 20 + k) % 8 == 0) mbar_wait(bW0 + 40 + 8 * ((WG * 20 + k) / 8), 0);
    ldsm4t(&av[4 * k], wq + CH_WO + k * 2048);
  }
  bar_sync(6, 256);
  if (WG == 1 && tid == 0) {
    fence_async();
    mbar_expect(bWo, 86016);
    for (int i = 0; i < 7; i++)
      for (int u = 0; u < 3; u++)
        tma_load(sb + CH_WO + i * 12288 + u * 4096, &p.wo, i < 6 ? j * 192 + i * 32 : j == 0 ? 576 : 592 + j * 16, h * 192 + (j + 3 - u) % 3 * 64, bWo);
  }
  PRO(2);
  if (threadIdx.x < NSLOT) {
    int n = 0;
    while (reader == 0) { reader = ldg_strong32(part_of); spin_guard(n); }
    sts32(sb + CH_O + threadIdx.x * 4, threadIdx.x * 8192 + (orient + 1 == reader ? 0 : 4096));
  }
  bar_sync(6, 256);
  asm volatile("barrier.cluster.wait.aligned;" ::: "memory");
  auto refill = [&]() {
#pragma unroll
    for (int k = 0; k < CH_TW; k++) ldsm4t(&tw[4 * k], wq + k * 2048);
  };
  const uint32_t wo = opaque(sb + CH_WO + (WG == 0 ? t4 * 12288 : 73728 + t4 * 1024) + ((lane & 7) + (lane >> 4) * 8) * 64 +
                             ((((lane >> 3) & 1) ^ ((lane >> 1) & 3)) << 4));
  const uint32_t wo2 = opaque((wo ^ ((t4 & 1) * 32)) + (4 + (t4 >> 1) - t4) * 12288);
  const uint32_t l16 = opaque(sb + lane * 16);
  const uint32_t l8 = opaque(sb + t4 * 256 + lane * 8);
  const uint32_t lw = opaque(sb + t4 * 1024 + lane * 16);
  const uint32_t qs = opaque(sb + CH_QK + WG * 2048 + t4 * 512 + lane * 16);
  const uint32_t qa = opaque(sb + CH_QK + (lane >> 4) * 2048 + (lane & 15) * 16 + (WG == 0 ? t4 * 512 + 256 : t4 == 3 ? 1024 : 0));
  const uint32_t ka = opaque(t4 < 2 ? sb + CH_KT + t4 * 512 + lane * 16
                                    : sb + CH_QK + 256 + (t4 - 2) * 1024 + ((lane >> 3) & 1) * 2048 + (lane >> 4) * 128 + (lane & 7) * 16);
  const uint32_t l4 = opaque(sb + t4 * 256 + lane * 4);
  uint32_t pdst[3], pages = 0;
  auto line0 = [&](int i) { return 24 * j + (i < 4 ? 4 * t4 + i : 12 + 2 * t4 + i); };
  const uint32_t plane = opaque((lane >> 4) * 2048 + h * 64 + (lane & 15) * 4);
  if (WG == 0) {
    pages = __ballot_sync(~0u, lds32(sb + CH_O + line0(min(lane, 5)) * 4) & 4096);
  } else {
    pages = __ballot_sync(~0u, lds32(sb + CH_O + (80 + min(lane, 11)) * 4) & 4096);
    pdst[0] = opaque(lds32(sb + CH_O + (j == 0 ? 72 + t4 : 74 + 2 * j + (t4 & 1)) * 4) + plane);
    pdst[1] = opaque(lds32(sb + CH_O + (cta < 80 ? cta : (cta - 80) * 5) * 4) + (t4 & 1) * 2048 + (lane & 7) * 64 + (lane >> 3) * 16);
  }
  if (WG == 1) pdst[2] = opaque((cta < 80 ? (80 + cta / 20) * 8192 + cta % 20 * 128 : (80 + (cta & 3)) * 8192 + (cta >> 2) * 128) +
                                (t4 >= 2 ? (t4 & 1) * 64 + (lane & 3) * 16 + (lane >> 2) * 2 : (t4 & 1) * 4096 + lane * 4));
  const uint32_t r0 = cta % CH_CL - j, r1 = mapa(sb, r0 + (j == 2 ? 0 : j + 1)) - sb, r2 = mapa(sb, r0 + (j == 0 ? 2 : j - 1)) - sb;
  uint32_t tag = opaque(1);
  auto pool = [&](uint32_t off) { return p.pool + ((tag & 0xfffe) + off); };
  auto after = [&](uint32_t x) { return x & tag & 0xfffe; };
  auto kv = [&](int s, uint32_t a) { return p.kv + ((size_t)(cta * NSEG + (s & KVM)) * KV_BYTES - sb) + a; };
  auto pass = [&](float (&d)[16], const uint32_t (&a)[80]) {
    const uint64_t db = mkdesc(CH_BASE + CH_X + WG * 20480, 512, 128, 0);
    wg_fence();
#pragma unroll
    for (int k = 0; k < 20; k++) {
      wg_rs32_00(d, a[4 * k], a[4 * k + 1], a[4 * k + 2], a[4 * k + 3], db + k * 64, k);
      if (k == 19 || (WG == 1 && k == 9)) wg_commit();
    }
  };
  auto dump = [&](float (&d)[16], uint32_t a) {
    wg_wait<0>();
    reg_fence<16>(d);
    sts128(a, pack8(d)); sts128(a + 512, pack8(d + 8));
  };
  auto tokens0 = [&](int s) {
    float d[16];
    if (!NOX || s == 0) mbar_wait_hot(bXB, s & 1);
    bar_sync(7, 256);
    pass(d, ak);
    TM1(5);
    bar_sync(9, 256);
    const uint4 k0 = lds128(lw + CH_KT), k1 = lds128(lw + CH_KT + 512);
    __syncwarp();
    wg_wait<0>();
    reg_fence<16>(d);
    add8(d, k0); add8(d + 8, k1);
#pragma unroll
    for (int e = 0; e < 2; e++) { const uint4 v = pack8(d + 8 * e); stsm4t(lw + CH_KT + e * 512, v.x, v.z, v.y, v.w); }
    fence_async();
    __syncwarp();
    if (elect()) { bulk_store(p.kv + (size_t)(cta * NSEG + (s & KVM)) * KV_BYTES + t4 * 1024, sb + CH_KT + t4 * 1024, 1024); bulk_commit(); }
    TM1(6);
    bar_sync(8, 256);
    pass(d, av);
    TM1(9);
    bulk_wait_read<0>();
    dump(d, lw + CH_VT);
  };
  bar_sync(6, 256);
  if (WG == 0) {
    tokens0(0);
  } else {
    float d[16];
    mbar_wait(bXA, 0);
    pass(d, ak);
    bar_arrive(7, 256);
    dump(d, lw + CH_KT);
    bar_arrive(9, 256);
    pass(d, av);
    bar_arrive(8, 256);
    dump(d, lw + CH_VT + 4096);
    bar_sync(3, 128);
    const uint32_t* m0 = reinterpret_cast<const uint32_t*>(p.mem0) + (lane >> 2) * 320 + t4 * 80 + (lane & 3);
    uint32_t a[20];
#pragma unroll
    for (int i = 0; i < 20; i++) a[i] = m0[4 * i];
#pragma unroll
    for (int i = 0; i < 20; i++) sts32(sb + CH_M + (t4 * 20 + i) * 128 + lane * 4, transpose8(a[i]));
  }
  PRO(3);
  mbar_wait(bWq, 0);
  refill();
  mbar_wait(bWo, 0);
  constexpr int VK = WG == 0 ? CH_VK0 : CH_VK1;
  auto project = [&](int s, uint32_t (&b)[40], float (&dv)[16], uint32_t (&kf)[16]) {
    float dq[4] = {}, dk[4] = {};
    uint32_t w[80];
#pragma unroll
    for (int i = 0; i < 4 * CH_TW; i++) w[i] = tw[i];
    auto load = [&](int n) {
      int c = 0;
#pragma unroll
      for (int i = 0; i < 10; i++) {
        if (c++ == n) ldsm4t(&b[4 * i], l16 + CH_M + WG * 5120 + i * 512);
#pragma unroll
        for (int k = 2 * i; k < 2 * i + 2; k++)
          if (k >= CH_TW && c++ == n) ldsm4t(&w[4 * k], wq + k * 2048);
      }
#pragma unroll
      for (int i = 0; i < 4; i++)
        if (WG == 1 && c++ == n) ldsm4(&kf[4 * i], ka + i * 1024);
    };
#pragma unroll
    for (int n = 0; n < CH_L0; n++) load(n);
    TM(0);
#pragma unroll
    for (int k = 0; k < 20; k += 2) {
      if (k > 0) {
#pragma unroll
        for (int n = CH_L0 + (k - 2) * CH_LR / 4; n < (k == 18 ? 40 : CH_L0 + k * CH_LR / 4); n++) load(n);
      }
      pin();
#pragma unroll
      for (int kk = k; kk < k + 2; kk++) {
        mma16(dk, ak[4 * kk], ak[4 * kk + 1], ak[4 * kk + 2], ak[4 * kk + 3], b[2 * kk], b[2 * kk + 1]);
        mma16(dq, w[4 * kk], w[4 * kk + 1], w[4 * kk + 2], w[4 * kk + 3], b[2 * kk], b[2 * kk + 1]);
        if (kk < VK) mma16(dv, av[4 * kk], av[4 * kk + 1], av[4 * kk + 2], av[4 * kk + 3], b[2 * kk], b[2 * kk + 1]);
      }
    }
    const float k2 = 0.07216878364870322f * 1.44269504089f;
    stsm4t(qs, pack2(dq[0] * k2, dq[1] * k2), pack2(dq[2] * k2, dq[3] * k2), pack2(dk[0], dk[1]), pack2(dk[2], dk[3]));
    TM(1);
  };
  constexpr int VC = VK == 20 ? 1 : WG == 0 ? 2 : 3;
  auto finish_v = [&](const uint32_t (&b)[40], float (&dv)[16]) {
#pragma unroll
    for (int kk = VK; kk < 20; kk++) mma16(dv + 4 * ((kk - VK) % VC), av[4 * kk], av[4 * kk + 1], av[4 * kk + 2], av[4 * kk + 3], b[2 * kk], b[2 * kk + 1]);
  };
  auto sum_v = [&](float (&dv)[16]) {
#pragma unroll
    for (int i = 4; i < 4 * VC; i++) dv[i & 3] += dv[i];
  };
  auto publish_km = [&](int s) {
    uint32_t a[4];
    ldsm4(a, qa);
    *reinterpret_cast<uint2*>(kv(s, l8) + KV_KM) = make_uint2(hadd2(a[0], a[2]), hadd2(a[1], a[3]));
  };
  auto load_v = [&](uint4 (&vr)[4]) {
#pragma unroll
    for (int e = 0; e < 4; e++) vr[e] = lds128(lw + CH_VT + (e & 1) * 4096 + (e >> 1) * 512);
  };
  auto token_v = [&](uint4 (&v)[2], const uint4 (&vr)[4]) {
#pragma unroll
    for (int e = 0; e < 2; e++) {
      const uint4 x = vr[2 * e], y = vr[2 * e + 1];
      v[e] = make_uint4(hadd2(x.x, y.x), hadd2(x.z, y.z), hadd2(x.y, y.y), hadd2(x.w, y.w));
    }
  };
  auto memory_v = [&](uint2 x, const float (&dv)[16]) {
    return make_uint2(pack2(dv[0] + bf_lo(x.x), dv[1] + bf_hi(x.x)), pack2(dv[2] + bf_lo(x.y), dv[3] + bf_hi(x.y)));
  };
  auto publish_v = [&](int s, const uint4 (&v)[2], uint2 vm) {
#pragma unroll
    for (int e = 0; e < 2; e++) reinterpret_cast<uint4*>(kv(s, lw) + KV_V)[e * 32] = v[e];
    *reinterpret_cast<uint2*>(kv(s, l8) + KV_VM) = vm;
  };
  auto load_x = [&](int s, int k0, int n, uint32_t bar) {
    if (!NOX && elect()) { mbar_expect(bar, n * 1024); bulk_load(sb + CH_X + k0 * 1024, p.xc + (s + 1) * 10240 + k0 * 256, n * 1024, bar); }
  };
  uint32_t gph = 1;
  int st = 0;
#pragma unroll 1
  for (int s = 0; s < NSEG - 1; s++) {
    bar_sync(6, 256);
    float dv[16] = {};
    uint32_t b[40], kf[16];
    project(s, b, dv, kf);
    if (WG == 0) {
      bar_sync(1, 256);
      if (CH_XA == 0) load_x(s, 20 + 5 * t4, 5, bXA);
      if (CH_XB == 0) load_x(s, 5 * t4, 5, bXB);
      pin();
      finish_v(b, dv);
      sum_v(dv);
      sts64(l8 + CH_VP, pack2(dv[0], dv[1]), pack2(dv[2], dv[3]));
      __syncwarp();
      if (elect()) mbar_arrive(bX);
      if (CH_XA == 1) load_x(s, 20 + 5 * t4, 5, bXA);
      if (CH_XB == 1) load_x(s, 5 * t4, 5, bXB);
      uint32_t w[144];
      auto wload = [&](int i) { ldsm4t(&w[4 * i], (i % 3 == 0 ? wo : i % 3 == 1 ? wo ^ 32 : wo2) + i / 3 * 1024); };
      TM(3);
#pragma unroll
      for (int i = 0; i < CH_W1; i++) wload(i);
      bar_sync(10, 256);
#pragma unroll
      for (int i = CH_W1; i < CH_W2; i++) wload(i);
      if (CH_XA == 2) load_x(s, 20 + 5 * t4, 5, bXA);
      if (CH_XB == 2) load_x(s, 5 * t4, 5, bXB);
      bar_sync(2, 256);
      {
        float y[3][4] = {};
        uint32_t ob[24];
        ldsm4(&ob[0], l16 + CH_O + 1024); ldsm4(&ob[4], l16 + CH_O + 1536);
        TM(7);
        auto step = [&](int i) {
          const int k = i / 3;
          mma16(y[i % 3], w[4 * i], w[4 * i + 1], w[4 * i + 2], w[4 * i + 3], ob[2 * k], ob[2 * k + 1]);
        };
#pragma unroll
        for (int i = 0; i < 12; i++) {
          step(i);
          if (i >= 12 - (CH_W3 - CH_W2)) wload(CH_W3 - 12 + i);
          if (i % 3 == 2) pin();
        }
        if (CH_XB == 3) load_x(s, 5 * t4, 5, bXB);
        pin();
        mbar_wait(bO, s & 1);
        TM(4);
        ldsm4(&ob[8], l16 + CH_O); ldsm4(&ob[12], l16 + CH_O + 512);
        pin();
        float2 inv;
        uint8_t* dst[6];
        uint32_t mask;
#pragma unroll
        for (int i = 12; i < 36; i++) {
          step(i);
          const int n = CH_W3 + i - 13, m = n - (n > 30);
          if (i == 12) ldsm4(&ob[16], l16 + after(w[4 * CH_W3 - 1] | w[4 * CH_W3 - 5] | w[4 * CH_W3 - 9] | ob[8]) + CH_O + 2048);
          else if (n == 30) ldsm4(&ob[20], l16 + CH_O + 2560);
          else if (m < 36) wload(m);
          else if (m == 36) inv = lds64f((l8 & ~0xe0u) + CH_VP);
          if (i == 26) mask = ((l16 ^ tag) & 48) == 0;
          if (i >= 27 && i < 33) dst[i - 27] = pool(line0(i - 27) * 8192 + (pages >> (i - 27) & 1) * 4096) + plane;
          if (i % 3 == 2) pin();
        }
#pragma unroll
        for (int k = 0; k < CH_R1; k++) ldsm4t(&tw[4 * k], wq + k * 2048);
        pin();
#pragma unroll
        for (int i = 0; i < 6; i++) stg_strong32(dst[i], pack_tag(y[i >> 1][2 * (i & 1)] * inv.x, y[i >> 1][2 * (i & 1) + 1] * inv.y, tag, mask));
        TM(8);
        bar_arrive(5, 256);
        pin();
#pragma unroll
        for (int k = CH_R1; k < CH_TW; k++) ldsm4t(&tw[4 * k], wq + k * 2048);
      }
      publish_km(s);
      if (t4 == 3 && cta < 40 && s + 4 < NSEG && elect())
        asm volatile("cp.async.bulk.prefetch.L2.global [%0], 1024;" :: "l"(p.xc + (s + 4) * 10240 + cta * 256) : "memory");
      if (t4 == 2 && (s & 3) == 0 && s > 0 && elect()) red_relaxed(p.sync + 2 * s - 4, 1);
      if (t4 == 2 && s == NSEG - 3 && cta == 95 && elect()) red_relaxed(p.sync + 2 * s + 2, 0x10000);
      tokens0(s + 1);
      TM(2);
    } else {
      const uint32_t xo = l4 + (CH_SX - (t4 == 3 ? 128 : 0)), x1 = xo + (r1 + 768 + min(t4, 2) * 256), x2 = xo + (r2 + 1024 + min(t4, 2) * 256);
      if (t4 < 2) {
        float ds[4][4] = {};
        uint32_t q[16];
        asm volatile("bar.sync 1, 256;" ::: "memory");
#pragma unroll
        for (int k = 0; k < 4; k++) ldsm4(&q[4 * k], qa + k * 512);
        pin();
        if (VK < 20) { finish_v(b, dv); pin(); }
#pragma unroll
        for (int k = 0; k < 4; k++) {
          mma16(ds[k & 1], kf[4 * k], kf[4 * k + 1], kf[4 * k + 2], kf[4 * k + 3], q[4 * k], q[4 * k + 1]);
          mma16(ds[2 + (k & 1)], kf[4 * k], kf[4 * k + 1], kf[4 * k + 2], kf[4 * k + 3], q[4 * k + 2], q[4 * k + 3]);
        }
        float t[4];
#pragma unroll
        for (int i = 0; i < 4; i++) t[i] = (ds[0][i] + ds[2][i]) + (ds[1][i] + ds[3][i]);
        const uint32_t w0 = pack2(t[0], t[1]), w1 = pack2(t[2], t[3]);
        st_async32(x1, w0, bX + r1); st_async32(x2, w0, bX + r2);
        st_async32(x1 + 128, w1, bX + r1); st_async32(x2 + 128, w1, bX + r2);
        sts32(xo, w0); sts32(xo + 128, w1);
      } else {
        float ds[4][4] = {};
        uint32_t q0[4], q1[4], a0[4], a1[4];
        asm volatile("bar.sync 1, 256; " ::: "memory");
        ldsm4(a0, ka); ldsm4(q0, qa); ldsm4(a1, ka + 512); ldsm4(q1, qa + 512);
        pin();
        if (VK < 20) { finish_v(b, dv); pin(); }
        mma16(ds[0], a0[0], a0[1], a0[2], a0[3], q0[0], q0[1]);
        mma16(ds[1], a0[0], a0[1], a0[2], a0[3], q0[2], q0[3]);
        mma16(ds[2], a1[0], a1[1], a1[2], a1[3], q1[0], q1[1]);
        mma16(ds[3], a1[0], a1[1], a1[2], a1[3], q1[2], q1[3]);
        float t[2];
#pragma unroll
        for (int i = 0; i < 2; i++)
          t[i] = ((ds[0][i] + ds[0][i + 2]) + (ds[1][i] + ds[1][i + 2])) + ((ds[2][i] + ds[2][i + 2]) + (ds[3][i] + ds[3][i + 2]));
        const uint32_t w0 = pack2(t[0], t[1]);
        st_async32(x1, w0, bX + r1);
        st_async32(x2, w0, bX + r2);
        sts32(xo, w0);
      }
      TM(3);
      const uint4 id = lds128(l16 + CH_ID);
      float sc[3][4] = {};
      uint4 v[2], vr[4];
      sum_v(dv);
      bar_sync(3, 128);
      uint32_t r[12], wd[12];
      ldsm4(&r[0], l16 + CH_SX); ldsm2(&r[4], l16 + CH_SX + 512);
      pin();
      load_v(vr);
#pragma unroll
      for (int u = 0; u < 3; u++) ldsm4t(&wd[4 * u], wo + u * 4096);
      pin();
#pragma unroll
      for (int q = 0; q < 3; q++) mma16(sc[q], id.x, id.y, id.z, id.w, r[2 * q], r[2 * q + 1]);
      uint32_t big = absmax2(absmax2(absmax2(r[0], r[1]), absmax2(r[2], r[3])), absmax2(r[4], r[5]));
      token_v(v, vr);
      const uint32_t oa1 = l4 + (r1 + CH_O), oa2 = l4 + (r2 + CH_O + 2048), ones = 0x3f803f80u;
      mbar_wait_hot(bX, s & 1);
      TM(4);
      ldsm4(&r[0], l16 + CH_SX + 768); ldsm4(&r[8], l16 + CH_SX + 1792); ldsm4(&r[4], l16 + CH_SX + 1280);
      const uint2 vp = lds64(l8 + CH_VP);
      bar_arrive(10, 256);
      pin();
      {
        float sd[3][4] = {};
#pragma unroll
        for (int i = 0; i < 3; i++) {
          const int q = i == 0 ? 0 : 3 - i;
          mma16(sc[q], id.x, id.y, id.z, id.w, r[4 * q], r[4 * q + 1]);
          mma16(sd[q], id.x, id.y, id.z, id.w, r[4 * q + 2], r[4 * q + 3]);
          big = absmax2(big, absmax2(absmax2(r[4 * q], r[4 * q + 1]), absmax2(r[4 * q + 2], r[4 * q + 3])));
        }
#pragma unroll
        for (int i = 0; i < 12; i++) sc[i >> 2][i & 3] += sd[i >> 2][i & 3];
      }
      const bool redo = __any_sync(~0u, (absmax2(big, big << 16) & 0x7fff0000u) >= 0x41800000u);
      const uint2 vm = memory_v(vp, dv);
      sc[2][0] += sc[2][2]; sc[2][1] += sc[2][3];
      float l[4], o[2][4];
      uint32_t p3, p4;
      auto attend = [&]() {
#pragma unroll
        for (int i = 0; i < 4; i++) l[i] = o[0][i] = o[1][i] = 0.f;
        const uint32_t p1 = pack2(ex2(sc[0][0]), ex2(sc[0][1])), p2 = pack2(ex2(sc[0][2]), ex2(sc[0][3]));
        mma16h(o[0], p1, p2, v[0].x, v[0].y);
        mma16h(o[1], p1, p2, v[0].z, v[0].w);
        mma16h(l, p1, p2, ones, ones);
        const uint32_t p0 = pack2(ex2(sc[2][0]), ex2(sc[2][1]));
        mma8h(o[0], p0, vm.x);
        mma8h(o[1], p0, vm.y);
        mma8h(l, p0, ones);
        p3 = pack2(ex2(sc[1][0]), ex2(sc[1][1])); p4 = pack2(ex2(sc[1][2]), ex2(sc[1][3]));
        mma16h(o[0], p3, p4, v[1].x, v[1].y);
        mma16h(o[1], p3, p4, v[1].z, v[1].w);
      };
      attend();
      if (__builtin_expect(redo, 0)) {
        float mx = fmaxf(sc[2][0], sc[2][1]);
#pragma unroll
        for (int i = 0; i < 4; i++) mx = fmaxf(mx, fmaxf(sc[0][i], sc[1][i]));
        mx = fmaxf(mx, __shfl_xor_sync(~0u, mx, 1));
        mx = fmaxf(mx, __shfl_xor_sync(~0u, mx, 2));
#pragma unroll
        for (int i = 0; i < 4; i++) { sc[0][i] -= mx; sc[1][i] -= mx; }
        sc[2][0] -= mx; sc[2][1] -= mx;
        attend();
      }
      const uint32_t o0 = pack2(o[0][0], o[0][1]), o1 = pack2(o[1][0], o[1][1]);
      st_async32(oa1, o0, bO + r1); st_async32(oa2, o0, bO + r2);
      st_async32(oa1 + 128, o1, bO + r1); st_async32(oa2 + 128, o1, bO + r2);
      sts32(l4 + CH_O + 1024, o0); sts32(l4 + CH_O + 1152, o1);
      bar_arrive(2, 256);
      pin();
      TM(6);
      mma16h(l, p3, p4, ones, ones);
      float inv;
      asm("rcp.approx.ftz.f32 %0, %1;" : "=f"(inv) : "f"(l[0]));
      sts32((l8 & ~0xffu) + (lane & 28) + CH_VP, __float_as_uint(inv));
      __syncwarp();
      if (elect()) mbar_arrive(bO);
      {
        float z[2][4] = {}, y[2][4] = {};
        uint32_t we[12] = {};
        mma16(z[0], wd[0], wd[1], wd[2], wd[3], o0, o1);
        if (j == 0) {
#pragma unroll
          for (int u = 0; u < 3; u++) ldsm4t(&we[4 * u], (wo ^ 32) + u * 4096);
          mma16(y[0], we[0], we[1], we[2], we[3], o0, o1);
        }
        const float2 iv = lds64f((l8 & ~0xe0u) + CH_VP);
        uint8_t* dst = pool(pdst[0]);
        const uint32_t mask = ((l16 ^ tag) & 48) == 0;
        const uint32_t oa = qa + ((tag & 0xfffe) + CH_O - CH_QK + t4 * 256 - (t4 == 3 ? 1024 : 0));
        const uint32_t za = l16 + ((tag & 0xfffe) + (t4 >> 1) * 512 + (t4 & 1) * 8);
        pin();
        mbar_wait(bO, s & 1);
        uint32_t a[4];
        ldsm4(a, oa);
        mma16(z[0], wd[4], wd[5], wd[6], wd[7], a[0], a[1]);
        mma16(z[1], wd[8], wd[9], wd[10], wd[11], a[2], a[3]);
        if (j == 0) {
          mma16(y[0], we[4], we[5], we[6], we[7], a[0], a[1]);
          mma16(y[1], we[8], we[9], we[10], we[11], a[2], a[3]);
          sts128f(lw + CH_VT + 512, y[0][0] + y[1][0], y[0][1] + y[1][1], y[0][2] + y[1][2], y[0][3] + y[1][3]);
        }
        sts128f(lw + CH_VT, z[0][0] + z[1][0], z[0][1] + z[1][1], z[0][2] + z[1][2], z[0][3] + z[1][3]);
        bar_sync(3, 128);
        if (j == 0 || t4 < 2) {
          float2 q[4];
#pragma unroll
          for (int i = 0; i < 4; i++) q[i] = lds64f(za + CH_VT + i * 1024);
          stg_strong32(dst, pack_tag(((q[0].x + q[1].x) + (q[2].x + q[3].x)) * iv.x, ((q[0].y + q[1].y) + (q[2].y + q[3].y)) * iv.y, tag, mask));
        }
      }
      TM(2);
      float d[16];
      bar_sync(5, 256);
      publish_v(s, v, vm);
#pragma unroll
      for (int k = 0; k < CH_RA; k++) ldsm4t(&tw[4 * k], wq + k * 2048);
      if (t4 == 0 && s + 2 < NSEG && elect()) { mbar_expect(bX, 1536); mbar_expect(bO, 2048); }
      if (!NOX) mbar_wait_hot(bXA, (s + 1) & 1);
      uint8_t* mdst = p.pool + ((t4 >= 2 ? st : st == 2 ? 0 : st + 1) * 32768 + pdst[2]);
      const uint8_t* psrc = pool(pdst[1] + after(tw[4 * CH_RA - 1]));
      pin();
      pass(d, ak);
      bar_arrive(7, 256);
      TM(5);
      if (t4 >= 2) {
        uint4 u[4];
        DELAY(p.d1);
#pragma unroll
        for (int i = 0; i < 4; i++) u[i] = ldg_strong128(psrc + i * 512);
        __syncwarp();
        dump(d, lw + CH_KT);
        bar_arrive(9, 256);
        TM(14);
        TMD(15, u[3].x);
        const uint32_t one = lane & 4 ? 0x3f800000u : 0x00003f80u, g2 = lane >> 3;
        int n = 0;
        float y[4][4];
        for (;;) {
#pragma unroll
          for (int i = 0; i < 4; i++) y[0][i] = y[1][i] = y[2][i] = y[3][i] = 0.f;
#pragma unroll
          for (int i = 0; i < 4; i++) {
            mma16h(y[i & 1], g2 == 0 ? one : 0, g2 == 1 ? one : 0, u[i].x, u[i].y);
            mma16h(y[2 + (i & 1)], g2 == 2 ? one : 0, g2 == 3 ? one : 0, u[i].z, u[i].w);
          }
          if (__builtin_expect(!__any_sync(~0u, (differ(u[0].x, u[1].x, tag) | differ(u[2].x, u[3].x, tag)) & 1), 1)) break;
#pragma unroll
          for (int i = 0; i < 4; i++) u[i] = ldg_strong128(psrc + i * 512);
          spin_guard(n);
        }
        const float v = ((y[0][0] + y[0][1]) + (y[2][0] + y[2][1])) + ((y[1][0] + y[1][1]) + (y[3][0] + y[3][1]));
        const uint32_t w = nz(pack2(v, 0.f));
        stg_strong16(mdst, w); stg_strong16(mdst + 4096, w);
        TMV(12, 32, n);
      } else {
        dump(d, lw + CH_KT);
        bar_arrive(9, 256);
        stg_strong32(mdst, 0u);
      }
      TM(8);
      bar_sync(3, 128);
      pass(d, av);
      bar_arrive(8, 256);
      TM(7);
      const uint32_t bG = bW0 + t4 * 8, mq = sb + CH_M + t4 * 2560;
      const uint8_t* msrc = p.pool + ((80 + st * 4 + t4) * 8192 + (pages >> (st * 4 + t4) & 1) * 4096);
      wg_wait<1>();
      bar_sync(3, 128);
      DELAY(p.d2);
      if (elect()) { mbar_expect(bG, 2560); bulk_load(mq, msrc, 2560, bG); }
      TM(9);
      dump(d, lw + CH_VT + 4096);
#pragma unroll
      for (int k = CH_RA; k < CH_TW; k++) ldsm4t(&tw[4 * k], wq + k * 2048);
      TM(10);
      int n = 0;
      for (;;) {
        mbar_wait(bG, gph);
        gph ^= 1;
        const uint32_t c = mq + lane * 32 + (lane >> 2) * 4;
        if (!__any_sync(~0u, __vimin3_u32(lds32(c), lds32(c + 1024), lds32(c + 1536)) == 0)) break;
        if (elect()) { mbar_expect(bG, 2560); bulk_load(mq, msrc, 2560, bG); }
        spin_guard(n);
      }
      TM(11);
      TMV(13, 32, n);
    }
    if (++st == 3) st = 0;
    tag ^= 0x10001;
  }
  {
    const int s = NSEG - 1;
    bar_sync(6, 256);
    float dv[16] = {};
    uint32_t b[40], kf[16];
    project(s, b, dv, kf);
    finish_v(b, dv);
    sum_v(dv);
    if (WG == 0) {
      sts64(l8 + CH_VP, pack2(dv[0], dv[1]), pack2(dv[2], dv[3]));
      bar_sync(1, 256);
      publish_km(s);
      bulk_wait<0>();
      fence_async_global();
      bar_sync(2, 256);
      if (tid == 0) red_release(g_sync + 15 * 8 + 4, 1);
    } else {
      uint4 v[2], vr[4];
      load_v(vr);
      token_v(v, vr);
      bar_sync(1, 256);
      publish_v(s, v, memory_v(lds64(l8 + CH_VP), dv));
      bar_arrive(2, 256);
    }
  }
}

__global__ void __launch_bounds__(256, 1) chain_kernel(const __grid_constant__ ChainParams p) {
  extern __shared__ __align__(1024) uint8_t smem_raw[];
  const uint32_t sb = s2u(smem_raw);
  const int tid = threadIdx.x, cta = blockIdx.x, colbase = cta * 64;
  const uint32_t bar = sb + CH_BAR;
  uint32_t smid; asm("mov.u32 %0, %%smid;" : "=r"(smid));
  if ((sb & 0x3ffff) != CH_BASE) __trap();
  if (tid == 0) {
    for (int i = 0; i < 16; i++) mbar_init(bar + 8 * i, i == 2 || i == 5 ? 5 : i == 3 || i == 4 ? 4 : 1);
    asm volatile("fence.mbarrier_init.release.cluster;" ::: "memory");
    mbar_expect(bar + 16, 1536);
    mbar_expect(bar + 40, 2048);
    for (int i = 0; i < 10; i++) {
      const int n = i % 5 < 2 ? (i % 5) * 2 : i % 5 == 2 ? 1 : i % 5;
      const uint32_t b = bar + 48 + 8 * (n + (i < 5 ? 0 : 5));
      mbar_expect(b, 16384);
      tma_load(sb + (i < 5 ? CH_WQ : CH_WO) + n * 16384, i < 5 ? &p.wk : &p.wv, colbase, n * 128, b);
    }
  }
  __syncwarp();
  pdl_wait();
  pdl_launch();
  if (tid == 224) stg_strong32(g_ctapart + cta, ldg_strong32(g_smpart + (smid & 255)) + 1);
  const int orient = tid < NSLOT ? (int)ldg_strong32(g_orient + tid) : 0;
  if (tid == 0) {
    for (int i = 0; i < 6; i++) mbar_arrive(bar + (i < 3 ? 24 : 32));
    for (int i = 0; i < 2; i++) { mbar_expect(bar + 24 + 8 * i, 20480); bulk_load(sb + CH_X + (1 - i) * 20480, g_xc + (1 - i) * 5120, 20480, bar + 24 + 8 * i); }
  }
  __syncthreads();
  asm volatile("barrier.cluster.arrive.relaxed.aligned;" ::: "memory");
  if (tid < 32) {
    const uint32_t id = (tid >> 3) == (tid & 3) ? ((tid & 4) ? 0x3f800000u : 0x00003f80u) : 0u;
    sts128(sb + CH_ID + tid * 16, make_uint4(id, 0, 0, id));
  }
  if (__shfl_sync(~0u, tid >> 7, 0) == 0) chain_body<0>(p, sb, orient); else chain_body<1>(p, sb, orient);
}

struct PostParams { CUtensorMap q, o, wq, wo, wb; int nq, gap; };
constexpr int OP_STAGES = 4, OP_STAGE_BYTES = 57344;
constexpr int OP_SMEM = 1024 + OP_STAGES * OP_STAGE_BYTES + 256 + 1024;
enum { IT_ATT = 0, IT_OP = 1, IT_FIN = 2, IT_BQ = 3 };

__device__ __forceinline__ uint32_t item_count(int type, int b) { return type == IT_ATT ? 32 : type == IT_OP ? 2 * op_split(b) : type == IT_FIN ? fin_items(b) : bq_items(b); }
__device__ __forceinline__ int item_stages(int type, int b) { return type == IT_ATT ? 3 : type == IT_OP ? 96 / op_split(b) : type == IT_FIN ? (b < OP_B8 ? 2 + op_split(b) : 5) : 10; }
__device__ __forceinline__ uint32_t item_need(int type, int b) { return type == IT_ATT ? 96 : item_count(type - 1, b); }
__device__ __forceinline__ void wait_count(const uint32_t* c, uint32_t n) {
  int spin = 0;
  while ((ld_acquire(c) & 0xffff) < n) { __nanosleep(32); spin_guard(spin); }
}

template <int HALF, bool QREG>
__device__ __forceinline__ void attn_a_warp(uint32_t sb, uint32_t bars, int& st, uint32_t& ph, uint32_t done, int& nd, const float* q) {
  constexpr int NT = HALF ? 5 : 3;
  const int lane = threadIdx.x & 31, g = lane >> 2, c = lane & 3, seg = (threadIdx.x >> 5) & 3, l7 = lane & 7;
  const uint32_t qrow = (seg * 32 + HALF * 16 + (lane & 15)) * 128;
  float sc[NT][4] = {};
  uint32_t base[3];
#pragma unroll
  for (int u = 0; u < 3; u++) {
    mbar_wait(bars + 8 * st, ph);
    base[u] = sb + st * OP_STAGE_BYTES;
    if (++st == OP_STAGES) { st = 0; ph ^= 1; }
    const uint32_t kv = base[u] + 16384 + seg * KV_BYTES;
#pragma unroll
    for (int kk = 0; kk < 4; kk++) {
      const uint2 km = lds64(kv + KV_KM + kk * 256 + lane * 8);
      uint32_t a[4];
      if (QREG) {
#pragma unroll
        for (int i = 0; i < 4; i++) a[i] = pack2(q[32 * u + 8 * kk + 2 * i], q[32 * u + 8 * kk + 2 * i + 1]);
      } else {
        ldsm4(a, base[u] + qrow + (((2 * kk + (lane >> 4)) ^ l7) << 4));
      }
      mma16(sc[0], a[0], a[1], a[2], a[3], km.x, km.y);
#pragma unroll
      for (int t = 0; t <= HALF; t++) {
        uint32_t kb[4];
        ldsm4(kb, kv + kk * 1024 + t * 512 + (lane & 8) * 32 + (lane & 16) * 8 + l7 * 16);
        mma16(sc[1 + 2 * t], a[0], a[1], a[2], a[3], kb[0], kb[1]);
        mma16(sc[2 + 2 * t], a[0], a[1], a[2], a[3], kb[2], kb[3]);
      }
    }
  }
  const float k2 = 0.07216878364870322f * 1.44269504089f, NEG = -INFINITY;
  if (2 * c > g) { sc[NT - 2][0] = NEG; sc[NT - 1][2] = NEG; }
  if (2 * c + 1 > g) { sc[NT - 2][1] = NEG; sc[NT - 1][3] = NEG; }
  sc[NT - 1][0] = sc[NT - 1][1] = NEG;
  uint32_t pp[NT][2]; float inv[2];
#pragma unroll
  for (int hh = 0; hh < 2; hh++) {
    float m = NEG, l = 0.f;
#pragma unroll
    for (int n = 0; n < NT; n++) m = fmaxf(m, fmaxf(sc[n][2 * hh], sc[n][2 * hh + 1]));
    m = fmaxf(m, __shfl_xor_sync(~0u, m, 1)); m = fmaxf(m, __shfl_xor_sync(~0u, m, 2));
#pragma unroll
    for (int n = 0; n < NT; n++) { const float x = ex2((sc[n][2 * hh] - m) * k2), y = ex2((sc[n][2 * hh + 1] - m) * k2); l += x + y; pp[n][hh] = pack2(x, y); }
    l += __shfl_xor_sync(~0u, l, 1); l += __shfl_xor_sync(~0u, l, 2);
    inv[hh] = 1.f / l;
  }
#pragma unroll
  for (int u = 0; u < 3; u++) {
    float o[8][4] = {};
    const uint32_t kv = base[u] + 16384 + seg * KV_BYTES;
#pragma unroll
    for (int n = 0; n < 8; n += 2) {
      const uint2 vm = lds64(kv + KV_VM + n * 128 + lane * 8);
      mma8(o[n], pp[0][0], pp[0][1], vm.x);
      mma8(o[n + 1], pp[0][0], pp[0][1], vm.y);
#pragma unroll
      for (int t = 0; t <= HALF; t++) {
        const uint4 vb = lds128(kv + KV_V + n * 512 + t * 512 + lane * 16);
        mma16(o[n], pp[1 + 2 * t][0], pp[1 + 2 * t][1], pp[2 + 2 * t][0], pp[2 + 2 * t][1], vb.x, vb.y);
        mma16(o[n + 1], pp[1 + 2 * t][0], pp[1 + 2 * t][1], pp[2 + 2 * t][0], pp[2 + 2 * t][1], vb.z, vb.w);
      }
    }
#pragma unroll
    for (int n = 0; n < 8; n += 2)
      stsm4(base[u] + qrow + (((n + (lane >> 4)) ^ l7) << 4), pack2(o[n][0] * inv[0], o[n][1] * inv[0]), pack2(o[n][2] * inv[1], o[n][3] * inv[1]),
            pack2(o[n + 1][0] * inv[0], o[n + 1][1] * inv[0]), pack2(o[n + 1][2] * inv[1], o[n + 1][3] * inv[1]));
    fence_async();
    __syncwarp();
    if (lane == 0) mbar_arrive(done + 8 * (nd & 7));
    nd++;
  }
}

template <int NG>
__device__ __forceinline__ void fin_item(uint32_t sb, uint32_t bars, int& st, uint32_t& ph, uint32_t scratch, int b, int idx) {
  const int warp = threadIdx.x >> 5, lane = threadIdx.x & 31;
  float4* x = g_x + ((b * 16 + idx * NG) * 40 + warp * 5) * 32 + lane;
  float4 v[NG][5];
#pragma unroll
  for (int r0 = 0; r0 < NG; r0 += 2) {
    mbar_wait(bars + 8 * st, ph);
#pragma unroll
    for (int r = r0; r < r0 + 2 && r < NG; r++)
#pragma unroll
      for (int i = 0; i < 5; i++) v[r][i] = lds128f(sb + st * OP_STAGE_BYTES + (((r - r0) * 40 + warp * 5 + i) * 32 + lane) * 16);
    __syncwarp();
    if (lane == 0) mbar_arrive(bars + 8 * (OP_STAGES + st));
    if (++st == OP_STAGES) { st = 0; ph ^= 1; }
  }
  for (int k0 = 0; k0 < op_split(b); k0 += 4 / NG) {
    mbar_wait(bars + 8 * st, ph);
#pragma unroll
    for (int q4 = 0; q4 < 4; q4++)
#pragma unroll
      for (int i = 0; i < 5; i++) {
        const uint2 q = lds64(sb + st * OP_STAGE_BYTES + ((q4 * 40 + warp * 5 + i) * 32 + lane) * 8);
        float4& t = v[q4 % NG][i];
        t.x += bf_lo(q.x); t.y += bf_hi(q.x); t.z += bf_lo(q.y); t.w += bf_hi(q.y);
      }
    __syncwarp();
    if (lane == 0) mbar_arrive(bars + 8 * (OP_STAGES + st));
    if (++st == OP_STAGES) { st = 0; ph ^= 1; }
  }
#pragma unroll
  for (int r = 0; r < NG; r++)
#pragma unroll
    for (int i = 0; i < 5; i++) x[(r * 40 + i) * 32] = v[r][i];
  ln_rows<NG>(v, scratch);
#pragma unroll
  for (int i = 0; i < 5; i++) {
    const int u = warp * 5 + i;
    uint32_t* xn = g_xn + ((b * 10 + (u >> 2)) * 16 + idx * NG) * 256 + (u & 3) * 64 + lane;
#pragma unroll
    for (int r = 0; r < NG; r++) { xn[r * 256] = pack2(v[r][i].x, v[r][i].y); xn[r * 256 + 32] = pack2(v[r][i].z, v[r][i].w); }
  }
}

__global__ void __launch_bounds__(384, 1) post_kernel(const __grid_constant__ PostParams p) {
  extern __shared__ uint8_t smem_raw[];
  const uint32_t sb = (s2u(smem_raw) + 1023) & ~1023u, bars = sb + OP_STAGES * OP_STAGE_BYTES;
  const uint32_t bIF = bars + 64, bIE = bars + 96, done = bars + 128, bGo = bars + 192, slots = bars + 208, scratch = bars + 256;
  const int warp = __shfl_sync(~0u, threadIdx.x >> 5, 0), lane = threadIdx.x & 31;
  TRACE(0);
  pdl_launch();
  if (threadIdx.x == 0) {
    for (int i = 0; i < 4; i++) {
      mbar_init(bars + 8 * i, 1); mbar_init(bars + 8 * (OP_STAGES + i), 8);
      mbar_init(bIF + 8 * i, 1); mbar_init(bIE + 8 * i, 2); mbar_init(done + 8 * i, 8); mbar_init(done + 32 + 8 * i, 8);
    }
    mbar_init(bGo, 1);
    fence_async();
  }
  __syncthreads();
  if (warp >= 8) {
    asm volatile("setmaxnreg.dec.sync.aligned.u32 56;");
    if (warp == 9) {
      const int b = lane & 15;
      for (int n = 0;; n++) {
        if (n > 0) mbar_wait(bGo, (n - 1) & 1);
        mbar_wait(bIE + 8 * (n & 3), ((n >> 2) & 1) ^ 1);
        int code, spin = 0, ticket = 0;
        if (lane == 0) ticket = atomicAdd(g_sync + SY_T, 1);
        for (;;) {
          const uint4 hd = ldg_strong128(g_sync + b * 8), pr = ldg_strong128(g_sync + b * 8 + 4);
          const uint32_t hv[4] = {hd.x, hd.y, hd.z, hd.w}, pv[4] = {pr.x, pr.y, pr.z, pr.w};
          const uint32_t chain_done = __ballot_sync(~0u, (pr.x & 0xffff) >= 96);
          int left[4], avail[4], rdy = 0, claimed = 0, upstream = 0;
#pragma unroll
          for (int t = 0; t < 4; t++) {
            const int cnt = lane < 16 ? item_count(t, b) : 0;
            left[t] = max(cnt - (int)hv[t], 0);
            claimed += cnt - left[t];
            const bool ready = (pv[t] & 0xffff) >= item_need(t, b);
            rdy |= ready << t;
            bool ok = ready || (t == IT_ATT ? pr.x >= 0x10000 : !upstream || (t == IT_OP && (chain_done >> 15 & 1)));
            if (t == IT_BQ && (chain_done >> 12 & 9) == 1) ok = false;
            avail[t] = ok ? left[t] : 0;
            upstream |= __any_sync(~0u, left[t] > 0);
          }
          if (!upstream) { code = -1; break; }
          int rank = max(__shfl_sync(~0u, ticket, 0) - __reduce_add_sync(~0u, claimed), 0), type = -1, mine = 0;
#pragma unroll
          for (int c = 0; c < 7; c++) {
            const int t = c == 0 || c == 4 ? IT_FIN : c == 1 || c == 6 ? IT_ATT : c == 2 ? IT_OP : IT_BQ;
            int a = c == 1 || c == 2 || ((rdy >> t & 1) == (c < 4)) ? avail[t] : 0;
            if (c == 6) a = b < QA_END && !(rdy & 1) && ((chain_done << 1 | 1) >> b & 1) ? left[t] : 0;
            const int tot = __reduce_add_sync(~0u, a);
            if (type < 0) { if (rank < tot) { type = t; mine = a; } else rank -= tot; }
          }
          if (type >= 0) {
#pragma unroll
            for (int o = 1; o < 16; o <<= 1) { const int y = __shfl_up_sync(~0u, mine, o); if (lane >= o) mine += y; }
            const int blk = __ffs(__ballot_sync(~0u, mine > rank)) - 1;
            const int early = !(__shfl_sync(~0u, rdy, blk) >> type & 1);
            uint32_t idx = 0;
            if (lane == 0) { idx = atomicAdd(g_sync + blk * 8 + type, 1); ld_acquire(g_sync + blk * 8 + 4 + type); }
            idx = __shfl_sync(~0u, idx, 0);
            if (idx < item_count(type, blk)) { code = (chain_done >> 15 & 1) << 22 | (chain_done >> 13 & 1) << 21 | early << 20 | type << 16 | blk << 8 | idx; break; }
          } else {
            __nanosleep(50);
          }
          spin_guard(spin);
        }
        if (lane == 0) {
          fence_async_global();
          sts32(slots + 4 * (n & 3), code);
          mbar_arrive(bIF + 8 * (n & 3));
        }
        __syncwarp();
        if (code < 0) break;
      }
    } else if (warp == 8 && lane == 0) {
      int st = 0; uint32_t ph = 1;
      uint32_t next = clk32(), gap = 0;
      auto pace = [&](uint32_t kb) {
        if (gap) { uint32_t now; do now = clk32(); while ((int)(now - next) < 0); next = now + kb * gap; }
      };
      auto box = [&](uint32_t dst, const CUtensorMap* m, int c0, int c1, uint32_t bar, uint32_t kb) { pace(kb); tma_load(dst, m, c0, c1, bar); };
      auto flat = [&](uint32_t dst, const void* src, uint32_t kb, uint32_t piece, uint32_t bar) {
        if (!gap) piece = kb;
        for (uint32_t o = 0; o < kb; o += piece) { pace(piece); bulk_load(dst + o * 1024, (const uint8_t*)src + o * 1024, piece * 1024, bar); }
      };
      for (int n = 0;; n++) {
        mbar_wait(bIF + 8 * (n & 3), (n >> 2) & 1);
        const int code = (int)lds32(slots + 4 * (n & 3));
        if (code < 0) break;
        const int type = (code >> 16) & 15, b = (code >> 8) & 255, idx = code & 255;
        mbar_arrive(bIE + 8 * (n & 3));
        gap = code >> 22 & 1 ? 0 : p.gap;
        const int nst = item_stages(type, b), ng = 16 / fin_items(b);
        const int kb0 = type == IT_OP ? (idx >> 1) * nst : 0;
        const bool half = type == IT_BQ && bq_items(b) == 12;
        const int col = type == IT_ATT ? idx * 192 : type == IT_OP ? (idx & 1) * 320 : idx * (half ? 160 : 320);
        const int pre = !(code >> 20 & 1) ? 0 : type == IT_ATT ? 2 : type == IT_FIN ? (ng + 1) / 2 : OP_STAGES - 1;
        const bool qa = type == IT_ATT && b < QA_END;
        if (qa) {
          for (int kb = 0; kb < 10; kb++) {
            const uint32_t dst = sb + st * OP_STAGE_BYTES, bar = bars + 8 * st;
            mbar_wait(bars + 8 * (OP_STAGES + st), ph);
            mbar_expect(bar, 40960);
            flat(dst, g_xn + (b * 10 + kb) * 4096, 16, 8, bar);
            for (int i = 0; i < 3; i++) box(dst + 16384 + i * 8192, &p.wq, col + i * 64, kb * 64, bar, 8);
            if (++st == OP_STAGES) { st = 0; ph ^= 1; }
          }
        } else if (type == IT_ATT) {
          wait_count(g_sync + SY_Q, p.nq);
          fence_async_global();
        }
        int sta = st;
        for (int kb = 0; kb < nst; kb++) {
          const uint32_t dst = sb + st * OP_STAGE_BYTES, bar = bars + 8 * st;
          mbar_wait(bars + 8 * (OP_STAGES + st), ph);
          if (type == IT_ATT) {
            mbar_expect(bar, qa ? 40960 : OP_STAGE_BYTES);
            if (!qa) box(dst, &p.q, col + kb * 64, b * 128, bar, 16);
          } else if (type == IT_FIN) {
            const int bytes = ng == 1 && kb == 0 ? 20480 : 40960;
            mbar_expect(bar, bytes);
            if (kb < (ng + 1) / 2) flat(dst, g_x + (b * 16 + idx * ng + 2 * kb) * 1280, bytes >> 10, 10, bar);
          } else {
            const int nb = half ? 3 : 5;
            mbar_expect(bar, 16384 + nb * 8192);
            for (int i = 0; i < nb; i++) box(dst + 16384 + i * 8192, type == IT_OP ? &p.wo : &p.wb, col + i * 64, (kb0 + kb) * 64, bar, 8);
          }
          if (++st == OP_STAGES) { st = 0; ph ^= 1; }
          if (kb < pre) continue;
          if (kb == pre) {
            if (pre) { wait_count(g_sync + b * 8 + 4 + type, item_need(type, b)); fence_async_global(); }
            if ((type == IT_ATT || type == IT_FIN) && !(code >> 21)) mbar_arrive(bGo);
          }
          for (int k = kb == pre ? 0 : kb; k <= kb; k++) {
            const uint32_t da = sb + sta * OP_STAGE_BYTES, ba = bars + 8 * sta;
            if (type == IT_ATT) {
              flat(da + 16384, g_kv + (size_t)((idx * 3 + k) * NSEG + (b * 4 & KVM)) * KV_BYTES, 40, 10, ba);
            } else if (type == IT_OP) {
              box(da, &p.o, (kb0 + k) * 64, b * 128, ba, 16);
            } else if (type == IT_BQ) {
              flat(da, g_xn + (b * 10 + k) * 4096, 16, 8, ba);
            } else if (k >= (ng + 1) / 2) {
              const int k0 = (k - (ng + 1) / 2) * (4 / ng);
              for (int i = 0; i < 4 / ng; i++) flat(da + i * ng * 10240, g_part + ((b * 16 + k0 + i) * 16 + idx * ng) * 1280, ng * 10, 10, ba);
            }
            if (++sta == OP_STAGES) sta = 0;
          }
        }
      }
    } else if (warp == 10 && lane == 0) {
      int st = 0, nd = 0;
      for (int n = 0;; n++) {
        mbar_wait(bIF + 8 * (n & 3), (n >> 2) & 1);
        const int code = (int)lds32(slots + 4 * (n & 3));
        if (code < 0) break;
        const int type = (code >> 16) & 15, b = (code >> 8) & 255, idx = code & 255;
        if (type == IT_ATT) {
          if (b < QA_END) st = (st + 10) & (OP_STAGES - 1);
          for (int u = 0; u < 3; u++) {
            mbar_wait(done + 8 * (nd & 7), (nd >> 3) & 1);
            nd++;
            tma_store(&p.o, sb + st * OP_STAGE_BYTES, idx * 192 + u * 64, b * 128);
            bulk_commit();
            bulk_wait_read<0>();
            asm volatile("mbarrier.arrive.shared::cta.b64 _, [%0], 8;" :: "r"(bars + 8 * (OP_STAGES + st)) : "memory");
            st = (st + 1) & (OP_STAGES - 1);
          }
          bulk_wait<0>();
          fence_async_global();
        } else {
          mbar_wait(done + 8 * (nd & 7), (nd >> 3) & 1);
          nd++;
          st = (st + item_stages(type, b)) & (OP_STAGES - 1);
        }
        if (type != IT_BQ) red_release(g_sync + b * 8 + 5 + type, 1);
        mbar_arrive(bIE + 8 * (n & 3));
      }
    }
  } else {
    asm volatile("setmaxnreg.inc.sync.aligned.u32 224;");
    const int wg = warp >> 2, g = lane >> 2, c = lane & 3;
    int st = 0, nd = 0; uint32_t ph = 0;
#pragma unroll 1
    for (int n = 0;; n++) {
      mbar_wait(bIF + 8 * (n & 3), (n >> 2) & 1);
      const int code = __shfl_sync(~0u, (int)lds32(slots + 4 * (n & 3)), 0);
      if (code < 0) { TRACE(2); break; }
      const int type = (code >> 16) & 15, b = (code >> 8) & 255, idx = code & 255;
      ITEM(code & 0xfffff, 0);
      if (type == IT_ATT) {
        if (b < QA_END) {
          float q[96] = {};
          reg_fence<96>(q);
          int prev = 0;
#pragma unroll 1
          for (int kb = 0; kb < 10; kb++) {
            mbar_wait(bars + 8 * st, ph);
            const uint32_t base = sb + st * OP_STAGE_BYTES;
            const uint64_t da = mkdesc(base + wg * 8192, 128, 1024, 0), db = mkdesc(base + 16384, 8192, 1024, 1);
            wg_fence();
#pragma unroll
            for (int kk = 0; kk < 4; kk++) wg_ss192_01(q, da + kk * 16, db + kk * 128, (kb | kk) != 0);
            wg_commit();
            if (kb > 0) { wg_wait<1>(); if (lane == 0) mbar_arrive(bars + 8 * (OP_STAGES + prev)); }
            prev = st;
            if (++st == OP_STAGES) { st = 0; ph ^= 1; }
          }
          wg_wait<0>();
          reg_fence<96>(q);
          if (lane == 0) mbar_arrive(bars + 8 * (OP_STAGES + prev));
          if (wg == 0) attn_a_warp<0, true>(sb, bars, st, ph, done, nd, q); else attn_a_warp<1, true>(sb, bars, st, ph, done, nd, q);
        } else {
          if (wg == 0) attn_a_warp<0, false>(sb, bars, st, ph, done, nd, nullptr); else attn_a_warp<1, false>(sb, bars, st, ph, done, nd, nullptr);
        }
      } else {
        if (type == IT_FIN) {
          if (fin_items(b) == 4) fin_item<4>(sb, bars, st, ph, scratch, b, idx);
          else if (fin_items(b) == 8) fin_item<2>(sb, bars, st, ph, scratch, b, idx);
          else fin_item<1>(sb, bars, st, ph, scratch, b, idx);
        } else {
          float d[160] = {};
          reg_fence<160>(d);
          const int nkb = item_stages(type, b);
          const bool half = type == IT_BQ && bq_items(b) == 12;
          int prev = 0;
          auto mainloop = [&](auto H) {
#pragma unroll 1
            for (int kb = 0; kb < nkb; kb++) {
              mbar_wait(bars + 8 * st, ph);
              const uint32_t base = sb + st * OP_STAGE_BYTES;
              const uint64_t da = mkdesc(base + wg * 8192, 128, 1024, type == IT_OP), db = mkdesc(base + 16384, 8192, 1024, 1);
              const int ka = type == IT_OP ? 2 : 16;
              wg_fence();
#pragma unroll
              for (int kk = 0; kk < 4; kk++) {
                if (H.value) {
                  wg_ss160_01(d, da + kk * ka, db + kk * 128, (kb | kk) != 0);
                } else {
                  wg_ss192_01(d, da + kk * ka, db + kk * 128, (kb | kk) != 0);
                  wg_ss128_01(d + 96, da + kk * ka, db + kk * 128 + 3 * 512, (kb | kk) != 0);
                }
              }
              wg_commit();
              if (kb == nkb - 3 && threadIdx.x == 0 && !(code >> 21)) mbar_arrive(bGo);
              if (kb > 0) { wg_wait<1>(); if (lane == 0) mbar_arrive(bars + 8 * (OP_STAGES + prev)); }
              prev = st;
              if (++st == OP_STAGES) { st = 0; ph ^= 1; }
            }
            wg_wait<0>();
          };
          if (half) mainloop(Int<1>()); else mainloop(Int<0>());
          reg_fence<160>(d);
          if (lane == 0) mbar_arrive(bars + 8 * (OP_STAGES + prev));
          if (type == IT_OP) {
            uint2* dst = g_part + (((b * 16 + (idx >> 1)) * 16 + warp * 2) * 40 + (idx & 1) * 20) * 32 + lane;
#pragma unroll
            for (int u = 0; u < 20; u++) {
              dst[u * 32] = make_uint2(pack2(d[8 * u], d[8 * u + 1]), pack2(d[8 * u + 4], d[8 * u + 5]));
              dst[(40 + u) * 32] = make_uint2(pack2(d[8 * u + 2], d[8 * u + 3]), pack2(d[8 * u + 6], d[8 * u + 7]));
            }
          } else {
            const int row = b * 128 + warp * 16 + g;
            const int h0 = idx * (half ? 8 : 16);
            const float sc = h0 < 32 ? 0.22360679775f * 1.44269504089f : 1.f;
            const bool lo = c < 2;
            uint32_t* da = g_bqkv + (h0 * 256 + (row >> 3)) * 96 + lane;
            uint32_t* db = da + 256 * 96 + (lo ? 2 : -2);
#pragma unroll
            for (int r = 0; r < 2; r++) {
              const uint32_t pad = !(c & 1) && (h0 >= 64 || (h0 >= 32 && (row & 1) && poly_group((row >> 3) + r))) ? 0x00003f80u : 0u;
#pragma unroll
              for (int q = 0; q < 8; q++) {
                if (q >= 4 && half) break;
                uint32_t w[5];
#pragma unroll
                for (int i = 0; i < 5; i++) w[i] = pack2(d[20 * q + 4 * i + 2 * r] * sc, d[20 * q + 4 * i + 2 * r + 1] * sc);
                const int o = q * 2 * 256 * 96 + r * 96;
                da[o] = w[0]; da[o + 32] = w[1]; da[o + 64] = lo ? w[2] : pad;
                db[o] = lo ? w[3] : w[2]; db[o + 32] = lo ? w[4] : w[3]; db[o + 64] = lo ? pad : w[4];
              }
            }
          }
        }
        __syncwarp();
        if (lane == 0) mbar_arrive(done + 8 * (nd & 7));
        nd++;
      }
      if (code >> 21 && threadIdx.x == 128) mbar_arrive(bGo);
      ITEM(code & 0xfffff, 1);
    }
  }
}

constexpr int AB_SMEM = 1024 + 2 * 98304 + 256;
#define AB_N 32
#define AB_WG 4
constexpr int AB_T = AB_WG * 128, AB_PASS = 8 / AB_WG;
__device__ __forceinline__ float ex2_poly(float t) {
  const uint32_t r = __float_as_uint(t) & 0xffff8000u;
  const float f = t - __uint_as_float(r);
  const float p = fmaf(fmaf(fmaf(-5.869912678e-38f, f, -1.700740250e-37f), f, -5.234869734e-37f), f, -7.522601252e-37f);
  uint32_t y;
  asm("mad.lo.u32 %0, %1, 256, %2;" : "=r"(y) : "r"(r), "r"(__float_as_uint(p)));
  return __uint_as_float(y);
}
__device__ __forceinline__ float sq2(uint32_t w) { const float a = bf_lo(w), b = bf_hi(w); return fmaf(a, a, b * b); }

__device__ __forceinline__ void attn_b_store(const float* o, int h, int row0, int lane) {
  const int g = lane >> 2, c = lane & 3;
  const float i0 = 1.f / __shfl_sync(~0u, o[8], (lane & ~3) | 2), i1 = 1.f / __shfl_sync(~0u, o[10], (lane & ~3) | 2);
#pragma unroll
  for (int jj = 0; jj < 3; jj++) {
    if (jj < 2 || c < 2) {
      const int col = h * 20 + 8 * jj + 2 * c;
      g_of[frag_word(row0 + g, col)] = pack2(o[4 * jj] * i0, o[4 * jj + 1] * i0);
      g_of[frag_word(row0 + g + 8, col)] = pack2(o[4 * jj + 2] * i1, o[4 * jj + 3] * i1);
    }
  }
}

__device__ __forceinline__ void attn_b_qk(float* s, uint32_t q0, uint32_t q1, uint32_t q2, uint32_t q3, uint32_t q4, uint32_t q5, uint32_t z0, uint32_t z1,
                                          uint64_t dk, uint64_t dk2) {
  wg_rs32_00(s, q0, q1, q2, q3, dk, 0);
  wg_rs32_00(s, q4, q5, z0, z1, dk2, 1);
}

__global__ void __launch_bounds__(AB_T, 1) attn_b_kernel() {
  extern __shared__ uint8_t smem_raw[];
  const uint32_t sb = (s2u(smem_raw) + 1023) & ~1023u, sK = sb, sV = sb + 98304, bars = sb + 2 * 98304;
  const int warp = __shfl_sync(~0u, threadIdx.x >> 5, 0), lane = threadIdx.x & 31;
  const int h = blockIdx.x >> 2, quarter = blockIdx.x & 3;
  TRACE(0);
  pdl_launch();
  pdl_wait();
  if (blockIdx.x < NSLOT) for (int i = threadIdx.x; i < 512; i += AB_T) reinterpret_cast<uint4*>(pool_at(blockIdx.x * 8192))[i] = make_uint4(0, 0, 0, 0);
  if (blockIdx.x == 30 && threadIdx.x < 96) g_ctapart[threadIdx.x] = 0;
  if (blockIdx.x == 31) for (int i = threadIdx.x; i < SY_N; i += AB_T) g_sync[i] = 0;
  if (threadIdx.x == 0) {
    for (int i = 0; i < 8; i++) mbar_init(bars + 8 * i, 1);
    fence_async();
    const uint8_t* gk = reinterpret_cast<const uint8_t*>(g_bqkv + (32 + h) * 256 * 96);
    const uint8_t* gv = reinterpret_cast<const uint8_t*>(g_bqkv + (64 + h) * 256 * 96);
    for (int i = 0; i < 8; i++) {
      mbar_expect(bars + 8 * i, 24576);
      bulk_load(sK + i * 12288, gk + i * 12288, 12288, bars + 8 * i);
      bulk_load(sV + i * 12288, gv + i * 12288, 12288, bars + 8 * i);
    }
  }
  __syncthreads();
  float qmax = 0.f;
  constexpr int NT = SEQ / AB_N, PER = 256 / AB_N;
#pragma unroll 1
  for (int pass = 0; pass < AB_PASS; pass++) {
    const int row0 = quarter * 512 + ((warp >> 2) * AB_PASS + pass) * 64 + (warp & 3) * 16;
    const uint32_t* gq = g_bqkv + (h * 256 + (row0 >> 3)) * 96 + lane;
    const uint32_t q0 = gq[0], q1 = gq[96], q2 = gq[32], q3 = gq[128];
    uint32_t q4 = gq[64], q5 = gq[160];
    const uint32_t z0 = gq[64 + 3 - (lane & 3)], z1 = gq[160 + 3 - (lane & 3)];
    {
      float n0 = sq2(q0) + sq2(q2) + sq2(q4), n1 = sq2(q1) + sq2(q3) + sq2(q5);
      n0 += __shfl_xor_sync(~0u, n0, 1); n1 += __shfl_xor_sync(~0u, n1, 1);
      n0 += __shfl_xor_sync(~0u, n0, 2); n1 += __shfl_xor_sync(~0u, n1, 2);
      qmax = (n0 > qmax || n0 != n0) ? n0 : qmax;
      qmax = (n1 > qmax || n1 != n1) ? n1 : qmax;
    }
    if ((lane & 3) == 2) { q4 = 0x43BCu; q5 = 0x43BCu; }
    float o[12];
    uint64_t dk = mkdesc(sK, 128, 384, 0), dk2 = mkdesc(sK + 256, 0, 384, 0), dv = mkdesc(sV, 384, 128, 0);
    float sa[AB_N / 2], sb2[AB_N / 2];
    uint32_t pa[AB_N / 4], pb[AB_N / 4];
    if (pass == 0) mbar_wait(bars, 0);
    wg_fence();
    attn_b_qk(sa, q0, q1, q2, q3, q4, q5, z0, z1, dk, dk2);
    wg_commit();
    attn_b_qk(sb2, q0, q1, q2, q3, q4, q5, z0, z1, dk + AB_N * 3, dk2 + AB_N * 3);
    wg_commit();
#pragma unroll 1
    for (int kt = 0; kt < NT; kt += 2) {
      const int nx = kt + 2 < NT ? kt + 2 : 0;
      if (pass == 0 && (nx & (PER - 1)) == 0) mbar_wait(bars + 8 * (nx / PER), 0);
      const uint64_t nk = dk + nx * (AB_N * 3), nk2 = dk2 + nx * (AB_N * 3);
      wg_wait<1>();
      reg_fence<AB_N / 2>(sa);
#pragma unroll
      for (int i = 0; i < AB_N / 4; i++) pa[i] = pack2(ex2(sa[2 * i]), poly_group(i >> 1) ? ex2_poly(sa[2 * i + 1]) : ex2(sa[2 * i + 1]));
      wg_fence();
#pragma unroll
      for (int kk = 0; kk < AB_N / 16; kk++) wg_rs24_01(o, pa[4 * kk], pa[4 * kk + 1], pa[4 * kk + 2], pa[4 * kk + 3], dv + kk * 48, kk | kt);
      attn_b_qk(sa, q0, q1, q2, q3, q4, q5, z0, z1, nk, nk2);
      wg_commit();
      wg_wait<1>();
      reg_fence<AB_N / 2>(sb2);
#pragma unroll
      for (int i = 0; i < AB_N / 4; i++) pb[i] = pack2(ex2(sb2[2 * i]), poly_group((i >> 1) + AB_N / 8) ? ex2_poly(sb2[2 * i + 1]) : ex2(sb2[2 * i + 1]));
      wg_fence();
#pragma unroll
      for (int kk = 0; kk < AB_N / 16; kk++) wg_rs24_01(o, pb[4 * kk], pb[4 * kk + 1], pb[4 * kk + 2], pb[4 * kk + 3], dv + AB_N * 3 + kk * 48, 1);
      attn_b_qk(sb2, q0, q1, q2, q3, q4, q5, z0, z1, nk + AB_N * 3, nk2 + AB_N * 3);
      wg_commit();
      dv += AB_N * 6;
    }
    wg_wait<0>();
    reg_fence<12>(o); reg_fence<AB_N / 2>(sa); reg_fence<AB_N / 2>(sb2);
    attn_b_store(o, h, row0, lane);
  }
  float kmax = 0.f;
#pragma unroll
  for (int i = 0; i < SEQ / AB_T; i++) {
    const int key = threadIdx.x + AB_T * i;
    const uint32_t a = sK + (key >> 3) * 384 + (key & 7) * 16;
    const uint4 x = lds128(a), y = lds128(a + 128);
    const uint2 z = lds64(a + 256);
    const float n = ((sq2(x.x) + sq2(x.y)) + (sq2(x.z) + sq2(x.w))) + ((sq2(y.x) + sq2(y.y)) + (sq2(y.z) + sq2(y.w))) + (sq2(z.x) + sq2(z.y));
    kmax = (n > kmax || n != n) ? n : kmax;
  }
  const uint32_t kbits = __reduce_max_sync(~0u, __float_as_uint(kmax) & 0x7fffffffu);
  if (lane == 0) sts32(bars + 64 + warp * 4, kbits);
  __syncthreads();
  kmax = __uint_as_float(__reduce_max_sync(~0u, lds32(bars + 64 + (lane & (AB_T / 32 - 1)) * 4)));
  TRACE(2);
  if (!__syncthreads_or(!(qmax * kmax <= 10000.f))) return;
#pragma unroll 1
  for (int pass = 0; pass < AB_PASS; pass++) {
    const int row0 = quarter * 512 + ((warp >> 2) * AB_PASS + pass) * 64 + (warp & 3) * 16;
    const uint32_t* gq = g_bqkv + (h * 256 + (row0 >> 3)) * 96 + lane;
    const uint32_t q0 = gq[0], q1 = gq[96], q2 = gq[32], q3 = gq[128], q4 = gq[64], q5 = gq[160];
    float o[12];
#pragma unroll
    for (int i = 0; i < 12; i++) o[i] = 0.f;
    float m0 = -INFINITY, m1 = -INFINITY;
#pragma unroll 1
    for (int kt = 0; kt < 32; kt++) {
      float s[32];
      const uint64_t dk = mkdesc(sK + kt * 3072, 128, 384, 0), dk2 = mkdesc(sK + kt * 3072 + 256, 0, 384, 0);
      wg_fence();
      wg_rs64_00(s, q0, q1, q2, q3, dk, 0);
      wg_rs64_00(s, q4, q5, 0, 0, dk2, 1);
      wg_commit();
      wg_wait<0>();
      reg_fence<32>(s); reg_fence<12>(o);
      float n0 = m0, n1 = m1;
#pragma unroll
      for (int jj = 0; jj < 8; jj++) { n0 = fmaxf(n0, fmaxf(s[4 * jj], s[4 * jj + 1])); n1 = fmaxf(n1, fmaxf(s[4 * jj + 2], s[4 * jj + 3])); }
      n0 = fmaxf(n0, __shfl_xor_sync(~0u, n0, 1)); n0 = fmaxf(n0, __shfl_xor_sync(~0u, n0, 2));
      n1 = fmaxf(n1, __shfl_xor_sync(~0u, n1, 1)); n1 = fmaxf(n1, __shfl_xor_sync(~0u, n1, 2));
      const float r0 = ex2(m0 - n0), r1 = ex2(m1 - n1);
      m0 = n0; m1 = n1;
#pragma unroll
      for (int jj = 0; jj < 3; jj++) { o[4 * jj] *= r0; o[4 * jj + 1] *= r0; o[4 * jj + 2] *= r1; o[4 * jj + 3] *= r1; }
      uint32_t pp[16];
#pragma unroll
      for (int jj = 0; jj < 8; jj++) {
        pp[2 * jj] = pack2(ex2(s[4 * jj] - m0), ex2(s[4 * jj + 1] - m0));
        pp[2 * jj + 1] = pack2(ex2(s[4 * jj + 2] - m1), ex2(s[4 * jj + 3] - m1));
      }
      const uint64_t dv = mkdesc(sV + kt * 3072, 384, 128, 0);
      wg_fence();
#pragma unroll
      for (int kk = 0; kk < 4; kk++) wg_rs24_01(o, pp[4 * kk], pp[4 * kk + 1], pp[4 * kk + 2], pp[4 * kk + 3], dv + kk * 48, 1);
      wg_commit();
    }
    wg_wait<0>();
    reg_fence<12>(o);
    attn_b_store(o, h, row0, lane);
  }
}

typedef CUresult (*EncodeFn)(CUtensorMap*, CUtensorMapDataType, cuuint32_t, void*, const cuuint64_t*, const cuuint64_t*,
                             const cuuint32_t*, const cuuint32_t*, CUtensorMapInterleave, CUtensorMapSwizzle,
                             CUtensorMapL2promotion, CUtensorMapFloatOOBfill);

void make_map(EncodeFn enc, CUtensorMap* m, const void* ptr, int cols, int rows, int box_rows, int box_cols = 64) {
  const cuuint64_t dims[2] = {(cuuint64_t)cols, (cuuint64_t)rows};
  const cuuint64_t strides[1] = {(cuuint64_t)cols * 2};
  const cuuint32_t box[2] = {(cuuint32_t)box_cols, (cuuint32_t)box_rows}, es[2] = {1, 1};
  enc(m, CU_TENSOR_MAP_DATA_TYPE_BFLOAT16, 2, const_cast<void*>(ptr), dims, strides, box, es, CU_TENSOR_MAP_INTERLEAVE_NONE,
      box_cols == 64 ? CU_TENSOR_MAP_SWIZZLE_128B : CU_TENSOR_MAP_SWIZZLE_64B, CU_TENSOR_MAP_L2_PROMOTION_L2_256B, CU_TENSOR_MAP_FLOAT_OOB_FILL_NONE);
}
template <class... KA, class... A>
void launch(void (*kern)(KA...), int grid, int block, int smem, int cluster, bool pdl, A... args) {
  cudaFuncSetAttribute(kern, cudaFuncAttributeMaxDynamicSharedMemorySize, smem);
  cudaLaunchConfig_t cfg = {};
  cfg.gridDim = dim3(grid); cfg.blockDim = dim3(block); cfg.dynamicSmemBytes = smem; cfg.stream = cudaStreamPerThread;
  cudaLaunchAttribute at[2];
  int n = 0;
  if (cluster > 1) { at[n].id = cudaLaunchAttributeClusterDimension; at[n].val.clusterDim.x = cluster; at[n].val.clusterDim.y = 1; at[n].val.clusterDim.z = 1; n++; }
  if (pdl) { at[n].id = cudaLaunchAttributeProgrammaticStreamSerialization; at[n].val.programmaticStreamSerializationAllowed = 1; n++; }
  cfg.attrs = at; cfg.numAttrs = n;
  cudaLaunchKernelEx(&cfg, kern, args...);
}
template <class T> void* sym(T& s) { void* p = nullptr; cudaGetSymbolAddress(&p, s); return p; }

}

#define MODE(b) 0
extern "C" void kernel_launch(void* const* d_in, const int* in_sizes, int n_in, void* d_out, int out_size) {
  const __nv_bfloat16* x = (const __nv_bfloat16*)d_in[0];
  void* fn = nullptr; cudaDriverEntryPointQueryResult qr;
  cudaGetDriverEntryPoint("cuTensorMapEncodeTiled", &fn, cudaEnableDefault, &qr);
  EncodeFn enc = (EncodeFn)fn;

  XsParams pq = {}, pc = {};
  ChainParams ch = {};
  PostParams op = {};
  void* q = sym(g_q);
  make_map(enc, &pq.w[0], d_in[2], HD, DM, 128); make_map(enc, &pq.o[0], q, HD, SEQ, 64);
  pq.a = (const uint32_t*)sym(g_xf);
  pq.ntiles = 96; pq.tiles_per_mat = 96; pq.rb0 = QA_END; pq.nowait = 1;
  make_map(enc, &pc.w[0], d_in[9], DM, DM, 128);
  pc.a = (const uint32_t*)sym(g_of); pc.ntiles = 10; pc.tiles_per_mat = 10; pc.out = (__nv_bfloat16*)d_out;
  ch.wq = pq.w[0];
  make_map(enc, &ch.wk, d_in[3], HD, DM, 128); make_map(enc, &ch.wv, d_in[4], HD, DM, 128);
  make_map(enc, &ch.wo, d_in[5], DM, HD, 64, 32);
  ch.mem0 = (const __nv_bfloat16*)d_in[1];
  ch.pool = (uint8_t*)(((uintptr_t)sym(g_pool) + 8191) & ~(uintptr_t)8191); ch.kv = (uint8_t*)sym(g_kv); ch.xc = (const uint32_t*)sym(g_xc); ch.sync = (uint32_t*)sym(g_sync);
  ch.d1 = 0; ch.d1b = 0; ch.d2 = 0; ch.d2b = 0;
  make_map(enc, &op.o, sym(g_o), HD, SEQ, 128); make_map(enc, &op.wo, d_in[5], DM, HD, 64);
  make_map(enc, &op.q, q, HD, SEQ, 128);
  make_map(enc, &op.wq, d_in[2], HD, DM, 64);
  make_map(enc, &op.wb, d_in[8], 1920, DM, 64);
  op.nq = 72; op.gap = 10;

  launch(probe_kernel, 132, 64, 200 * 1024, 1, false);
  for (int layer = 0; layer < 2; layer++) {
    launch(layer == 0 ? ln_kernel<true> : ln_kernel<false>, 128, 256, 0, 1, layer != 0, x);
    ch.d2b = layer;
    launch(chain_kernel, 96, 256, CH_SMEM, CH_CL, true, ch);
    launch(xs_gemm<EPI_QKV, false>, 36, 384, XS_SMEM, 1, !MODE(1), pq);
    launch(post_kernel, 132, 384, OP_SMEM, 1, true, op);
    launch(attn_b_kernel, 128, AB_T, AB_SMEM, 1, true);
    launch(layer == 0 ? xs_gemm<EPI_RES, false> : xs_gemm<EPI_OUT, false>, 80, 384, XS_SMEM, 1, true, pc);
  }
}
```

```cpp
#include <cuda_runtime.h>
#include <cuda_bf16.h>
#include <cuda.h>
#include <stdint.h>

namespace {

constexpr int SEQ = 2048, DM = 640, HD = 6144, NSEG = 64;
constexpr int SPIN_LIMIT = 1 << 20;

__device__ __align__(128) float4 g_x[SEQ * DM / 4];
__device__ __align__(16) uint32_t g_xf[SEQ * DM / 2];
__device__ __align__(128) uint32_t g_of[SEQ * DM / 2];
__device__ __align__(128) uint4 g_wb[DM * DM / 8];
__device__ __align__(16) float2 g_stat[16 * 8 * 128];
__device__ uint32_t g_bo[8 * 32];
__device__ __nv_bfloat16 g_q[SEQ * HD], g_o[SEQ * HD];
#define KVM 63
constexpr int KV_BYTES = 10240, KV_V = 4096, KV_KM = 8192, KV_VM = 9216;
__device__ __align__(128) uint8_t g_kv[96 * NSEG * KV_BYTES];
__device__ __align__(128) uint32_t g_xc[SEQ * DM / 2];
#define OP_B4 0
#define OP_B8 11
#define OP_B16 13
#define QA_END 12
__host__ __device__ constexpr int op_split(int b) { return b < OP_B4 ? 2 : b < OP_B8 ? 4 : b < OP_B16 ? 8 : 16; }
__host__ __device__ constexpr int fin_items(int b) { return b < OP_B8 ? 4 : op_split(b); }
#define AB_PF 2
#define AB_PF0 30000
#define AB_PFD 7000
#define W_PROMO CU_TENSOR_MAP_L2_PROMOTION_L2_128B
#define EF 1
#define WEF 1
#define FK_PF 1
#define BQ_HALF 10
__host__ __device__ constexpr int bq_items(int b) { return b < BQ_HALF ? 6 : 12; }
__device__ __align__(128) uint2 g_part[16 * 16 * 16 * 40 * 32];
__device__ __align__(128) uint32_t g_xn[SEQ * DM / 2];
constexpr int SY_Q = 128, SY_T = 160, SY_N = 161;
__device__ __align__(16) uint32_t g_sync[SY_N];
constexpr int NSLOT = 92;
__device__ uint32_t g_pool[(NSLOT + 2) * 2048];
__device__ int g_smpart[256], g_orient[NSLOT];
__device__ uint32_t g_bqkv[3 * 32 * 256 * 96];

#define ABT(L, i)
#define MODE_D(b) 0
#define DELAY(d)
#define XT(i)
#define MISS(k, n)
#define PRO(i)
#define TRACE(w)
#define ITEM(code, w)
#define TM(i)
#define TM1(i)
#define TMD(i, dep)
#define TMV(i, at, v)

__device__ __forceinline__ uint32_t gtime() { uint32_t c; asm volatile("mov.u32 %0, %%globaltimer_lo;" : "=r"(c) :: "memory"); return c; }
__device__ __forceinline__ uint32_t clk32() { uint32_t c; asm volatile("mov.u32 %0, %%clock;" : "=r"(c) :: "memory"); return c; }
__device__ __forceinline__ uint32_t s2u(const void* p) { return (uint32_t)__cvta_generic_to_shared(p); }
__device__ __forceinline__ uint32_t pack2(float a, float b) {
  uint32_t r; asm("cvt.rn.bf16x2.f32 %0, %1, %2;" : "=r"(r) : "f"(b), "f"(a)); return r; }
__device__ __forceinline__ float bf_lo(uint32_t w) { return __uint_as_float(w << 16); }
__device__ __forceinline__ float bf_hi(uint32_t w) { return __uint_as_float(w & 0xffff0000u); }
__device__ __forceinline__ float ex2(float x) { float y; asm("ex2.approx.ftz.f32 %0, %1;" : "=f"(y) : "f"(x)); return y; }

__device__ __forceinline__ void mbar_init(uint32_t bar, uint32_t n) {
  asm volatile("mbarrier.init.shared::cta.b64 [%0], %1;" :: "r"(bar), "r"(n) : "memory"); }
__device__ __forceinline__ void mbar_expect(uint32_t bar, uint32_t bytes) {
  asm volatile("mbarrier.arrive.expect_tx.shared::cta.b64 _, [%0], %1;" :: "r"(bar), "r"(bytes) : "memory"); }
__device__ __forceinline__ void mbar_arrive(uint32_t bar) {
  asm volatile("mbarrier.arrive.shared::cta.b64 _, [%0];" :: "r"(bar) : "memory"); }
__device__ __forceinline__ void mbar_wait(uint32_t bar, uint32_t ph) {
  asm volatile("{.reg .pred p; .reg .u32 n; mov.u32 n, 0;\n"
               "W: mbarrier.try_wait.parity.shared::cta.b64 p, [%0], %1; @p bra D;\n"
               "add.u32 n, n, 1; setp.gt.u32 p, n, %2; @p trap; bra W;\n"
               "D: }" :: "r"(bar), "r"(ph), "n"(SPIN_LIMIT) : "memory");
}
__device__ __forceinline__ void mbar_wait_cluster(uint32_t bar, uint32_t ph) {
  asm volatile("{.reg .pred p; .reg .u32 n; mov.u32 n, 0;\n"
               "W: mbarrier.try_wait.parity.acquire.cluster.shared::cta.b64 p, [%0], %1; @p bra D;\n"
               "add.u32 n, n, 1; setp.gt.u32 p, n, %2; @p trap; bra W;\n"
               "D: }" :: "r"(bar), "r"(ph), "n"(SPIN_LIMIT) : "memory");
}
__device__ __forceinline__ void spin_guard(int& n) {
  asm volatile("{.reg .pred p; add.s32 %0, %0, 1; setp.gt.s32 p, %0, %1; @p trap;}" : "+r"(n) : "n"(SPIN_LIMIT));
}
__device__ __forceinline__ void pdl_wait() { asm volatile("griddepcontrol.wait;" ::: "memory"); TRACE(1); }
__device__ __forceinline__ void pdl_launch() { asm volatile("griddepcontrol.launch_dependents;" ::: "memory"); }
__device__ __forceinline__ uint32_t ld_acquire(const uint32_t* p) { uint32_t v; asm volatile("ld.acquire.gpu.global.u32 %0, [%1];" : "=r"(v) : "l"(p) : "memory"); return v; }
__device__ __forceinline__ void red_release(uint32_t* p, uint32_t v) { asm volatile("red.release.gpu.global.add.u32 [%0], %1;" :: "l"(p), "r"(v) : "memory"); }
__device__ __forceinline__ void red_relaxed(uint32_t* p, uint32_t v) { asm volatile("red.relaxed.gpu.global.add.u32 [%0], %1;" :: "l"(p), "r"(v) : "memory"); }
__device__ __forceinline__ void fence_async_global() { asm volatile("fence.proxy.async.global;" ::: "memory"); }
__device__ __forceinline__ void fence_async() { asm volatile("fence.proxy.async.shared::cta;" ::: "memory"); }
__device__ __forceinline__ void bar_sync(int id, int n) { asm volatile("bar.sync %0, %1;" :: "r"(id), "r"(n) : "memory"); }
__device__ __forceinline__ void bar_arrive(int id, int n) { asm volatile("bar.arrive %0, %1;" :: "r"(id), "r"(n) : "memory"); }
__device__ __forceinline__ void tma_load(uint32_t dst, const CUtensorMap* m, int c0, int c1, uint32_t bar) {
  asm volatile("cp.async.bulk.tensor.2d.shared::cluster.global.mbarrier::complete_tx::bytes [%0], [%1, {%3, %4}], [%2];"
               :: "r"(dst), "l"(m), "r"(bar), "r"(c0), "r"(c1) : "memory"); }
template <bool STREAM = false>
__device__ __forceinline__ void tma_load3(uint32_t dst, const CUtensorMap* m, int c0, int c1, uint32_t bar) {
  if (STREAM)
    asm volatile("{.reg .b64 pol; createpolicy.fractional.L2::evict_first.b64 pol, 1.0;\n"
                 "cp.async.bulk.tensor.3d.shared::cluster.global.mbarrier::complete_tx::bytes.L2::cache_hint [%0], [%1, {%3, %4, 0}], [%2], pol;}"
                 :: "r"(dst), "l"(m), "r"(bar), "r"(c0), "r"(c1) : "memory");
  else
  asm volatile("cp.async.bulk.tensor.3d.shared::cluster.global.mbarrier::complete_tx::bytes [%0], [%1, {%3, %4, 0}], [%2];"
               :: "r"(dst), "l"(m), "r"(bar), "r"(c0), "r"(c1) : "memory"); }
__device__ __forceinline__ void tma_store(const CUtensorMap* m, uint32_t src, int c0, int c1) {
  asm volatile("cp.async.bulk.tensor.2d.global.shared::cta.bulk_group [%0, {%2, %3}], [%1];"
               :: "l"(m), "r"(src), "r"(c0), "r"(c1) : "memory"); }
__device__ __forceinline__ void tma_store_stream(const CUtensorMap* m, uint32_t src, int c0, int c1) {
  asm volatile("{.reg .b64 pol; createpolicy.fractional.L2::evict_first.b64 pol, 1.0;\n"
               "cp.async.bulk.tensor.2d.global.shared::cta.bulk_group.L2::cache_hint [%0, {%2, %3}], [%1], pol;}"
               :: "l"(m), "r"(src), "r"(c0), "r"(c1) : "memory"); }
__device__ __forceinline__ void bulk_load(uint32_t dst, const void* src, uint32_t bytes, uint32_t bar) {
  asm volatile("cp.async.bulk.shared::cluster.global.mbarrier::complete_tx::bytes [%0], [%1], %2, [%3];"
               :: "r"(dst), "l"(src), "r"(bytes), "r"(bar) : "memory"); }
__device__ __forceinline__ void bulk_load_last(uint32_t dst, const void* src, uint32_t bytes, uint32_t bar) {
  asm volatile("{.reg .b64 pol; createpolicy.fractional.L2::evict_first.b64 pol, 1.0;\n"
               "cp.async.bulk.shared::cluster.global.mbarrier::complete_tx::bytes.L2::cache_hint [%0], [%1], %2, [%3], pol;}"
               :: "r"(dst), "l"(src), "r"(bytes), "r"(bar) : "memory"); }
__device__ __forceinline__ void tma_load_last(uint32_t dst, const CUtensorMap* m, int c0, int c1, uint32_t bar) {
  asm volatile("{.reg .b64 pol; createpolicy.fractional.L2::evict_first.b64 pol, 1.0;\n"
               "cp.async.bulk.tensor.2d.shared::cluster.global.mbarrier::complete_tx::bytes.L2::cache_hint [%0], [%1, {%3, %4}], [%2], pol;}"
               :: "r"(dst), "l"(m), "r"(bar), "r"(c0), "r"(c1) : "memory"); }
__device__ __forceinline__ void bulk_send(uint32_t dst, uint32_t src, uint32_t bytes, uint32_t bar) {
  asm volatile("cp.async.bulk.shared::cluster.shared::cta.mbarrier::complete_tx::bytes [%0], [%1], %2, [%3];"
               :: "r"(dst), "r"(src), "r"(bytes), "r"(bar) : "memory"); }
__device__ __forceinline__ void bulk_store(void* dst, uint32_t src, uint32_t bytes) {
  asm volatile("cp.async.bulk.global.shared::cta.bulk_group [%0], [%1], %2;" :: "l"(dst), "r"(src), "r"(bytes) : "memory"); }
__device__ __forceinline__ void bulk_commit() { asm volatile("cp.async.bulk.commit_group;" ::: "memory"); }
template <int N> __device__ __forceinline__ void bulk_wait_read() { asm volatile("cp.async.bulk.wait_group.read %0;" :: "n"(N) : "memory"); }
template <int N> __device__ __forceinline__ void bulk_wait() { asm volatile("cp.async.bulk.wait_group %0;" :: "n"(N) : "memory"); }

__device__ __forceinline__ uint64_t mkdesc(uint32_t addr, uint32_t lbo, uint32_t sbo, uint32_t sw) {
  return (uint64_t)((addr & 0x3FFFF) >> 4) | ((uint64_t)(lbo >> 4) << 16) | ((uint64_t)(sbo >> 4) << 32) | ((uint64_t)sw << 62); }
__device__ __forceinline__ void wg_fence() { asm volatile("wgmma.fence.sync.aligned;" ::: "memory"); }
__device__ __forceinline__ void wg_commit() { asm volatile("wgmma.commit_group.sync.aligned;" ::: "memory"); }
template <int N> __device__ __forceinline__ void wg_wait() { asm volatile("wgmma.wait_group.sync.aligned %0;" :: "n"(N) : "memory"); }
template <int N> __device__ __forceinline__ void reg_fence(float* d) {
#pragma unroll
  for (int i = 0; i < N; i++) asm volatile("" : "+f"(d[i]) :: "memory");
}

__device__ __forceinline__ void mma16(float* d, uint32_t a0, uint32_t a1, uint32_t a2, uint32_t a3, uint32_t b0, uint32_t b1) {
  asm volatile("mma.sync.aligned.m16n8k16.row.col.f32.bf16.bf16.f32 {%0,%1,%2,%3},{%4,%5,%6,%7},{%8,%9},{%0,%1,%2,%3};"
               : "+f"(d[0]), "+f"(d[1]), "+f"(d[2]), "+f"(d[3]) : "r"(a0), "r"(a1), "r"(a2), "r"(a3), "r"(b0), "r"(b1)); }
__device__ __forceinline__ void mma8(float* d, uint32_t a0, uint32_t a1, uint32_t b0) {
  asm volatile("mma.sync.aligned.m16n8k8.row.col.f32.bf16.bf16.f32 {%0,%1,%2,%3},{%4,%5},{%6},{%0,%1,%2,%3};"
               : "+f"(d[0]), "+f"(d[1]), "+f"(d[2]), "+f"(d[3]) : "r"(a0), "r"(a1), "r"(b0)); }
__device__ __forceinline__ void ldsm4(uint32_t* r, uint32_t a) {
  asm volatile("ldmatrix.sync.aligned.m8n8.x4.shared.b16 {%0,%1,%2,%3},[%4];" : "=r"(r[0]), "=r"(r[1]), "=r"(r[2]), "=r"(r[3]) : "r"(a) : "memory"); }
__device__ __forceinline__ void ldsm4t(uint32_t* r, uint32_t a) {
  asm volatile("ldmatrix.sync.aligned.m8n8.x4.trans.shared.b16 {%0,%1,%2,%3},[%4];" : "=r"(r[0]), "=r"(r[1]), "=r"(r[2]), "=r"(r[3]) : "r"(a) : "memory"); }
__device__ __forceinline__ void ldsm2(uint32_t* r, uint32_t a) {
  asm volatile("ldmatrix.sync.aligned.m8n8.x2.shared.b16 {%0,%1},[%2];" : "=r"(r[0]), "=r"(r[1]) : "r"(a) : "memory"); }
__device__ __forceinline__ void stsm4(uint32_t a, uint32_t r0, uint32_t r1, uint32_t r2, uint32_t r3) {
  asm volatile("stmatrix.sync.aligned.m8n8.x4.shared.b16 [%0], {%1,%2,%3,%4};" :: "r"(a), "r"(r0), "r"(r1), "r"(r2), "r"(r3) : "memory"); }
__device__ __forceinline__ void stsm2t(uint32_t a, uint32_t r0, uint32_t r1) {
  asm volatile("stmatrix.sync.aligned.m8n8.x2.trans.shared.b16 [%0], {%1,%2};" :: "r"(a), "r"(r0), "r"(r1) : "memory"); }
__device__ __forceinline__ void stsm4t(uint32_t a, uint32_t r0, uint32_t r1, uint32_t r2, uint32_t r3) {
  asm volatile("stmatrix.sync.aligned.m8n8.x4.trans.shared.b16 [%0], {%1,%2,%3,%4};" :: "r"(a), "r"(r0), "r"(r1), "r"(r2), "r"(r3) : "memory"); }
__device__ __forceinline__ void st_async128(uint32_t a, uint4 v, uint32_t bar) {
  asm volatile("st.async.shared::cluster.mbarrier::complete_tx::bytes.v4.b32 [%0], {%1,%2,%3,%4}, [%5];" :: "r"(a), "r"(v.x), "r"(v.y), "r"(v.z), "r"(v.w), "r"(bar) : "memory"); }
__device__ __forceinline__ void sts32(uint32_t a, uint32_t v) { asm volatile("st.shared.b32 [%0], %1;" :: "r"(a), "r"(v) : "memory"); }
__device__ __forceinline__ void sts64f(uint32_t a, float x, float y) { asm volatile("st.shared.v2.f32 [%0], {%1,%2};" :: "r"(a), "f"(x), "f"(y) : "memory"); }
__device__ __forceinline__ void sts128(uint32_t a, uint4 v) {
  asm volatile("st.shared.v4.b32 [%0], {%1,%2,%3,%4};" :: "r"(a), "r"(v.x), "r"(v.y), "r"(v.z), "r"(v.w) : "memory"); }
__device__ __forceinline__ void sts128f(uint32_t a, float x, float y, float z, float w) {
  asm volatile("st.shared.v4.f32 [%0], {%1,%2,%3,%4};" :: "r"(a), "f"(x), "f"(y), "f"(z), "f"(w) : "memory"); }
__device__ __forceinline__ float lds32f(uint32_t a) { float v; asm volatile("ld.shared.f32 %0, [%1];" : "=f"(v) : "r"(a) : "memory"); return v; }
__device__ __forceinline__ float2 lds64f(uint32_t a) { float2 v; asm volatile("ld.shared.v2.f32 {%0,%1}, [%2];" : "=f"(v.x), "=f"(v.y) : "r"(a) : "memory"); return v; }
__device__ __forceinline__ float4 lds128f(uint32_t a) {
  float4 v; asm volatile("ld.shared.v4.f32 {%0,%1,%2,%3}, [%4];" : "=f"(v.x), "=f"(v.y), "=f"(v.z), "=f"(v.w) : "r"(a) : "memory"); return v; }
__device__ __forceinline__ uint4 lds128(uint32_t a) {
  uint4 v; asm volatile("ld.shared.v4.b32 {%0,%1,%2,%3}, [%4];" : "=r"(v.x), "=r"(v.y), "=r"(v.z), "=r"(v.w) : "r"(a) : "memory"); return v; }
__device__ __forceinline__ uint4 ldg_strong128(const void* p) {
  uint4 v; asm volatile("ld.relaxed.gpu.global.v4.u32 {%0,%1,%2,%3}, [%4];" : "=r"(v.x), "=r"(v.y), "=r"(v.z), "=r"(v.w) : "l"(p) : "memory"); return v; }
__device__ __forceinline__ void stg_strong32(void* p, uint32_t v) { asm volatile("st.relaxed.gpu.global.u32 [%0], %1;" :: "l"(p), "r"(v) : "memory"); }
__device__ __forceinline__ void stg_strong16(void* p, uint32_t v) { asm volatile("st.relaxed.gpu.global.u16 [%0], %1;" :: "l"(p), "h"((uint16_t)v) : "memory"); }
__device__ __forceinline__ void stg_strong128(void* p, uint4 v) {
  asm volatile("st.relaxed.gpu.global.v4.u32 [%0], {%1,%2,%3,%4};" :: "l"(p), "r"(v.x), "r"(v.y), "r"(v.z), "r"(v.w) : "memory"); }
__device__ __forceinline__ uint32_t mapa(uint32_t a, uint32_t r) {
  uint32_t o; asm("mapa.shared::cluster.u32 %0, %1, %2;" : "=r"(o) : "r"(a), "r"(r)); return o; }
__device__ __forceinline__ void st_async2f(uint32_t a, float x, float y, uint32_t bar) {
  asm volatile("st.async.shared::cluster.mbarrier::complete_tx::bytes.v2.f32 [%0], {%1,%2}, [%3];" :: "r"(a), "f"(x), "f"(y), "r"(bar) : "memory"); }
__device__ __forceinline__ void st_async32(uint32_t a, uint32_t x, uint32_t bar) {
  asm volatile("st.async.shared::cluster.mbarrier::complete_tx::bytes.b32 [%0], %1, [%2];" :: "r"(a), "r"(x), "r"(bar) : "memory"); }
__device__ __forceinline__ uint32_t lds32(uint32_t a) { uint32_t v; asm volatile("ld.shared.b32 %0, [%1];" : "=r"(v) : "r"(a) : "memory"); return v; }
__device__ __forceinline__ void st_async64(uint32_t a, uint32_t x, uint32_t y, uint32_t bar) {
  asm volatile("st.async.shared::cluster.mbarrier::complete_tx::bytes.v2.b32 [%0], {%1,%2}, [%3];" :: "r"(a), "r"(x), "r"(y), "r"(bar) : "memory"); }
__device__ __forceinline__ uint2 lds64(uint32_t a) { uint2 v; asm volatile("ld.shared.v2.b32 {%0,%1}, [%2];" : "=r"(v.x), "=r"(v.y) : "r"(a) : "memory"); return v; }
__device__ __forceinline__ void sts64(uint32_t a, uint32_t x, uint32_t y) { asm volatile("st.shared.v2.b32 [%0], {%1,%2};" :: "r"(a), "r"(x), "r"(y) : "memory"); }
__device__ __forceinline__ uint32_t ldg_strong32(const void* p) { uint32_t v; asm volatile("ld.relaxed.gpu.global.u32 %0, [%1];" : "=r"(v) : "l"(p) : "memory"); return v; }
__device__ __forceinline__ uint32_t transpose8(uint32_t x) { uint32_t r; asm volatile("movmatrix.sync.aligned.m8n8.trans.b16 %0, %1;" : "=r"(r) : "r"(x)); return r; }
__device__ __forceinline__ uint32_t hadd2(uint32_t a, uint32_t b) { uint32_t r; asm("add.rn.bf16x2 %0, %1, %2;" : "=r"(r) : "r"(a), "r"(b)); return r; }
__device__ __forceinline__ uint32_t min4(uint4 v) { return min(__vimin3_u32(v.x, v.y, v.z), v.w); }

__device__ __forceinline__ void wg_rs64_01(float* d, uint32_t a0, uint32_t a1, uint32_t a2, uint32_t a3, uint64_t db, int sd) {
  asm volatile("{.reg .pred p; setp.ne.b32 p, %37, 0;\n"
    "wgmma.mma_async.sync.aligned.m64n64k16.f32.bf16.bf16 {%0,%1,%2,%3,%4,%5,%6,%7,%8,%9,%10,%11,%12,%13,%14,%15,%16,%17,%18,%19,%20,%21,%22,%23,%24,%25,%26,%27,%28,%29,%30,%31}, {%32,%33,%34,%35}, %36, p, 1, 1, 1;}"
    : "+f"(d[0]),"+f"(d[1]),"+f"(d[2]),"+f"(d[3]),"+f"(d[4]),"+f"(d[5]),"+f"(d[6]),"+f"(d[7]),"+f"(d[8]),"+f"(d[9]),"+f"(d[10]),"+f"(d[11]),"+f"(d[12]),"+f"(d[13]),"+f"(d[14]),"+f"(d[15]),"+f"(d[16]),"+f"(d[17]),"+f"(d[18]),"+f"(d[19]),"+f"(d[20]),"+f"(d[21]),"+f"(d[22]),"+f"(d[23]),"+f"(d[24]),"+f"(d[25]),"+f"(d[26]),"+f"(d[27]),"+f"(d[28]),"+f"(d[29]),"+f"(d[30]),"+f"(d[31])
    : "r"(a0), "r"(a1), "r"(a2), "r"(a3), "l"(db), "r"(sd));
}
__device__ __forceinline__ void wg_ss192_01(float* d, uint64_t da, uint64_t db, int sd) {
  asm volatile("{.reg .pred p; setp.ne.b32 p, %98, 0;\n"
    "wgmma.mma_async.sync.aligned.m64n192k16.f32.bf16.bf16 {%0,%1,%2,%3,%4,%5,%6,%7,%8,%9,%10,%11,%12,%13,%14,%15,%16,%17,%18,%19,%20,%21,%22,%23,%24,%25,%26,%27,%28,%29,%30,%31,%32,%33,%34,%35,%36,%37,%38,%39,%40,%41,%42,%43,%44,%45,%46,%47,%48,%49,%50,%51,%52,%53,%54,%55,%56,%57,%58,%59,%60,%61,%62,%63,%64,%65,%66,%67,%68,%69,%70,%71,%72,%73,%74,%75,%76,%77,%78,%79,%80,%81,%82,%83,%84,%85,%86,%87,%88,%89,%90,%91,%92,%93,%94,%95}, %96, %97, p, 1, 1, 0, 1;}"
    : "+f"(d[0]),"+f"(d[1]),"+f"(d[2]),"+f"(d[3]),"+f"(d[4]),"+f"(d[5]),"+f"(d[6]),"+f"(d[7]),"+f"(d[8]),"+f"(d[9]),"+f"(d[10]),"+f"(d[11]),"+f"(d[12]),"+f"(d[13]),"+f"(d[14]),"+f"(d[15]),"+f"(d[16]),"+f"(d[17]),"+f"(d[18]),"+f"(d[19]),"+f"(d[20]),"+f"(d[21]),"+f"(d[22]),"+f"(d[23]),"+f"(d[24]),"+f"(d[25]),"+f"(d[26]),"+f"(d[27]),"+f"(d[28]),"+f"(d[29]),"+f"(d[30]),"+f"(d[31]),"+f"(d[32]),"+f"(d[33]),"+f"(d[34]),"+f"(d[35]),"+f"(d[36]),"+f"(d[37]),"+f"(d[38]),"+f"(d[39]),"+f"(d[40]),"+f"(d[41]),"+f"(d[42]),"+f"(d[43]),"+f"(d[44]),"+f"(d[45]),"+f"(d[46]),"+f"(d[47]),"+f"(d[48]),"+f"(d[49]),"+f"(d[50]),"+f"(d[51]),"+f"(d[52]),"+f"(d[53]),"+f"(d[54]),"+f"(d[55]),"+f"(d[56]),"+f"(d[57]),"+f"(d[58]),"+f"(d[59]),"+f"(d[60]),"+f"(d[61]),"+f"(d[62]),"+f"(d[63]),"+f"(d[64]),"+f"(d[65]),"+f"(d[66]),"+f"(d[67]),"+f"(d[68]),"+f"(d[69]),"+f"(d[70]),"+f"(d[71]),"+f"(d[72]),"+f"(d[73]),"+f"(d[74]),"+f"(d[75]),"+f"(d[76]),"+f"(d[77]),"+f"(d[78]),"+f"(d[79]),"+f"(d[80]),"+f"(d[81]),"+f"(d[82]),"+f"(d[83]),"+f"(d[84]),"+f"(d[85]),"+f"(d[86]),"+f"(d[87]),"+f"(d[88]),"+f"(d[89]),"+f"(d[90]),"+f"(d[91]),"+f"(d[92]),"+f"(d[93]),"+f"(d[94]),"+f"(d[95])
    : "l"(da), "l"(db), "r"(sd));
}
__device__ __forceinline__ void wg_ss128_01(float* d, uint64_t da, uint64_t db, int sd) {
  asm volatile("{.reg .pred p; setp.ne.b32 p, %66, 0;\n"
    "wgmma.mma_async.sync.aligned.m64n128k16.f32.bf16.bf16 {%0,%1,%2,%3,%4,%5,%6,%7,%8,%9,%10,%11,%12,%13,%14,%15,%16,%17,%18,%19,%20,%21,%22,%23,%24,%25,%26,%27,%28,%29,%30,%31,%32,%33,%34,%35,%36,%37,%38,%39,%40,%41,%42,%43,%44,%45,%46,%47,%48,%49,%50,%51,%52,%53,%54,%55,%56,%57,%58,%59,%60,%61,%62,%63}, %64, %65, p, 1, 1, 0, 1;}"
    : "+f"(d[0]),"+f"(d[1]),"+f"(d[2]),"+f"(d[3]),"+f"(d[4]),"+f"(d[5]),"+f"(d[6]),"+f"(d[7]),"+f"(d[8]),"+f"(d[9]),"+f"(d[10]),"+f"(d[11]),"+f"(d[12]),"+f"(d[13]),"+f"(d[14]),"+f"(d[15]),"+f"(d[16]),"+f"(d[17]),"+f"(d[18]),"+f"(d[19]),"+f"(d[20]),"+f"(d[21]),"+f"(d[22]),"+f"(d[23]),"+f"(d[24]),"+f"(d[25]),"+f"(d[26]),"+f"(d[27]),"+f"(d[28]),"+f"(d[29]),"+f"(d[30]),"+f"(d[31]),"+f"(d[32]),"+f"(d[33]),"+f"(d[34]),"+f"(d[35]),"+f"(d[36]),"+f"(d[37]),"+f"(d[38]),"+f"(d[39]),"+f"(d[40]),"+f"(d[41]),"+f"(d[42]),"+f"(d[43]),"+f"(d[44]),"+f"(d[45]),"+f"(d[46]),"+f"(d[47]),"+f"(d[48]),"+f"(d[49]),"+f"(d[50]),"+f"(d[51]),"+f"(d[52]),"+f"(d[53]),"+f"(d[54]),"+f"(d[55]),"+f"(d[56]),"+f"(d[57]),"+f"(d[58]),"+f"(d[59]),"+f"(d[60]),"+f"(d[61]),"+f"(d[62]),"+f"(d[63])
    : "l"(da), "l"(db), "r"(sd));
}
__device__ __forceinline__ void wg_ss160_01(float* d, uint64_t da, uint64_t db, int sd) {
  asm volatile("{.reg .pred p; setp.ne.b32 p, %82, 0;\n"
    "wgmma.mma_async.sync.aligned.m64n160k16.f32.bf16.bf16 {%0,%1,%2,%3,%4,%5,%6,%7,%8,%9,%10,%11,%12,%13,%14,%15,%16,%17,%18,%19,%20,%21,%22,%23,%24,%25,%26,%27,%28,%29,%30,%31,%32,%33,%34,%35,%36,%37,%38,%39,%40,%41,%42,%43,%44,%45,%46,%47,%48,%49,%50,%51,%52,%53,%54,%55,%56,%57,%58,%59,%60,%61,%62,%63,%64,%65,%66,%67,%68,%69,%70,%71,%72,%73,%74,%75,%76,%77,%78,%79}, %80, %81, p, 1, 1, 0, 1;}"
    : "+f"(d[0]),"+f"(d[1]),"+f"(d[2]),"+f"(d[3]),"+f"(d[4]),"+f"(d[5]),"+f"(d[6]),"+f"(d[7]),"+f"(d[8]),"+f"(d[9]),"+f"(d[10]),"+f"(d[11]),"+f"(d[12]),"+f"(d[13]),"+f"(d[14]),"+f"(d[15]),"+f"(d[16]),"+f"(d[17]),"+f"(d[18]),"+f"(d[19]),"+f"(d[20]),"+f"(d[21]),"+f"(d[22]),"+f"(d[23]),"+f"(d[24]),"+f"(d[25]),"+f"(d[26]),"+f"(d[27]),"+f"(d[28]),"+f"(d[29]),"+f"(d[30]),"+f"(d[31]),"+f"(d[32]),"+f"(d[33]),"+f"(d[34]),"+f"(d[35]),"+f"(d[36]),"+f"(d[37]),"+f"(d[38]),"+f"(d[39]),"+f"(d[40]),"+f"(d[41]),"+f"(d[42]),"+f"(d[43]),"+f"(d[44]),"+f"(d[45]),"+f"(d[46]),"+f"(d[47]),"+f"(d[48]),"+f"(d[49]),"+f"(d[50]),"+f"(d[51]),"+f"(d[52]),"+f"(d[53]),"+f"(d[54]),"+f"(d[55]),"+f"(d[56]),"+f"(d[57]),"+f"(d[58]),"+f"(d[59]),"+f"(d[60]),"+f"(d[61]),"+f"(d[62]),"+f"(d[63]),"+f"(d[64]),"+f"(d[65]),"+f"(d[66]),"+f"(d[67]),"+f"(d[68]),"+f"(d[69]),"+f"(d[70]),"+f"(d[71]),"+f"(d[72]),"+f"(d[73]),"+f"(d[74]),"+f"(d[75]),"+f"(d[76]),"+f"(d[77]),"+f"(d[78]),"+f"(d[79])
    : "l"(da), "l"(db), "r"(sd));
}
__device__ __forceinline__ void wg_ss80_01(float* d, uint64_t da, uint64_t db, int sd) {
  asm volatile("{.reg .pred p; setp.ne.b32 p, %42, 0;\n"
    "wgmma.mma_async.sync.aligned.m64n80k16.f32.bf16.bf16 {%0,%1,%2,%3,%4,%5,%6,%7,%8,%9,%10,%11,%12,%13,%14,%15,%16,%17,%18,%19,%20,%21,%22,%23,%24,%25,%26,%27,%28,%29,%30,%31,%32,%33,%34,%35,%36,%37,%38,%39}, %40, %41, p, 1, 1, 0, 1;}"
    : "+f"(d[0]),"+f"(d[1]),"+f"(d[2]),"+f"(d[3]),"+f"(d[4]),"+f"(d[5]),"+f"(d[6]),"+f"(d[7]),"+f"(d[8]),"+f"(d[9]),"+f"(d[10]),"+f"(d[11]),"+f"(d[12]),"+f"(d[13]),"+f"(d[14]),"+f"(d[15]),"+f"(d[16]),"+f"(d[17]),"+f"(d[18]),"+f"(d[19]),"+f"(d[20]),"+f"(d[21]),"+f"(d[22]),"+f"(d[23]),"+f"(d[24]),"+f"(d[25]),"+f"(d[26]),"+f"(d[27]),"+f"(d[28]),"+f"(d[29]),"+f"(d[30]),"+f"(d[31]),"+f"(d[32]),"+f"(d[33]),"+f"(d[34]),"+f"(d[35]),"+f"(d[36]),"+f"(d[37]),"+f"(d[38]),"+f"(d[39])
    : "l"(da), "l"(db), "r"(sd));
}
__device__ __forceinline__ void wg_rs32_00(float* d, uint32_t a0, uint32_t a1, uint32_t a2, uint32_t a3, uint64_t db, int sd) {
  asm volatile("{.reg .pred p; setp.ne.b32 p, %21, 0;\n"
    "wgmma.mma_async.sync.aligned.m64n32k16.f32.bf16.bf16 {%0,%1,%2,%3,%4,%5,%6,%7,%8,%9,%10,%11,%12,%13,%14,%15}, {%16,%17,%18,%19}, %20, p, 1, 1, 0;}"
    : "+f"(d[0]),"+f"(d[1]),"+f"(d[2]),"+f"(d[3]),"+f"(d[4]),"+f"(d[5]),"+f"(d[6]),"+f"(d[7]),"+f"(d[8]),"+f"(d[9]),"+f"(d[10]),"+f"(d[11]),"+f"(d[12]),"+f"(d[13]),"+f"(d[14]),"+f"(d[15])
    : "r"(a0), "r"(a1), "r"(a2), "r"(a3), "l"(db), "r"(sd));
}
__device__ __forceinline__ void wg_rs64_00(float* d, uint32_t a0, uint32_t a1, uint32_t a2, uint32_t a3, uint64_t db, int sd) {
  asm volatile("{.reg .pred p; setp.ne.b32 p, %37, 0;\n"
    "wgmma.mma_async.sync.aligned.m64n64k16.f32.bf16.bf16 {%0,%1,%2,%3,%4,%5,%6,%7,%8,%9,%10,%11,%12,%13,%14,%15,%16,%17,%18,%19,%20,%21,%22,%23,%24,%25,%26,%27,%28,%29,%30,%31}, {%32,%33,%34,%35}, %36, p, 1, 1, 0;}"
    : "+f"(d[0]),"+f"(d[1]),"+f"(d[2]),"+f"(d[3]),"+f"(d[4]),"+f"(d[5]),"+f"(d[6]),"+f"(d[7]),"+f"(d[8]),"+f"(d[9]),"+f"(d[10]),"+f"(d[11]),"+f"(d[12]),"+f"(d[13]),"+f"(d[14]),"+f"(d[15]),"+f"(d[16]),"+f"(d[17]),"+f"(d[18]),"+f"(d[19]),"+f"(d[20]),"+f"(d[21]),"+f"(d[22]),"+f"(d[23]),"+f"(d[24]),"+f"(d[25]),"+f"(d[26]),"+f"(d[27]),"+f"(d[28]),"+f"(d[29]),"+f"(d[30]),"+f"(d[31])
    : "r"(a0), "r"(a1), "r"(a2), "r"(a3), "l"(db), "r"(sd));
}
__device__ __forceinline__ void wg_rs128_00(float* d, uint32_t a0, uint32_t a1, uint32_t a2, uint32_t a3, uint64_t db, int sd) {
  asm volatile("{.reg .pred p; setp.ne.b32 p, %69, 0;\n"
    "wgmma.mma_async.sync.aligned.m64n128k16.f32.bf16.bf16 {%0,%1,%2,%3,%4,%5,%6,%7,%8,%9,%10,%11,%12,%13,%14,%15,%16,%17,%18,%19,%20,%21,%22,%23,%24,%25,%26,%27,%28,%29,%30,%31,%32,%33,%34,%35,%36,%37,%38,%39,%40,%41,%42,%43,%44,%45,%46,%47,%48,%49,%50,%51,%52,%53,%54,%55,%56,%57,%58,%59,%60,%61,%62,%63}, {%64,%65,%66,%67}, %68, p, 1, 1, 0;}"
    : "+f"(d[0]),"+f"(d[1]),"+f"(d[2]),"+f"(d[3]),"+f"(d[4]),"+f"(d[5]),"+f"(d[6]),"+f"(d[7]),"+f"(d[8]),"+f"(d[9]),"+f"(d[10]),"+f"(d[11]),"+f"(d[12]),"+f"(d[13]),"+f"(d[14]),"+f"(d[15]),"+f"(d[16]),"+f"(d[17]),"+f"(d[18]),"+f"(d[19]),"+f"(d[20]),"+f"(d[21]),"+f"(d[22]),"+f"(d[23]),"+f"(d[24]),"+f"(d[25]),"+f"(d[26]),"+f"(d[27]),"+f"(d[28]),"+f"(d[29]),"+f"(d[30]),"+f"(d[31]),"+f"(d[32]),"+f"(d[33]),"+f"(d[34]),"+f"(d[35]),"+f"(d[36]),"+f"(d[37]),"+f"(d[38]),"+f"(d[39]),"+f"(d[40]),"+f"(d[41]),"+f"(d[42]),"+f"(d[43]),"+f"(d[44]),"+f"(d[45]),"+f"(d[46]),"+f"(d[47]),"+f"(d[48]),"+f"(d[49]),"+f"(d[50]),"+f"(d[51]),"+f"(d[52]),"+f"(d[53]),"+f"(d[54]),"+f"(d[55]),"+f"(d[56]),"+f"(d[57]),"+f"(d[58]),"+f"(d[59]),"+f"(d[60]),"+f"(d[61]),"+f"(d[62]),"+f"(d[63])
    : "r"(a0), "r"(a1), "r"(a2), "r"(a3), "l"(db), "r"(sd));
}
__device__ __forceinline__ void wg_rs24_01(float* d, uint32_t a0, uint32_t a1, uint32_t a2, uint32_t a3, uint64_t db, int sd) {
  asm volatile("{.reg .pred p; setp.ne.b32 p, %17, 0;\n"
    "wgmma.mma_async.sync.aligned.m64n24k16.f32.bf16.bf16 {%0,%1,%2,%3,%4,%5,%6,%7,%8,%9,%10,%11}, {%12,%13,%14,%15}, %16, p, 1, 1, 1;}"
    : "+f"(d[0]),"+f"(d[1]),"+f"(d[2]),"+f"(d[3]),"+f"(d[4]),"+f"(d[5]),"+f"(d[6]),"+f"(d[7]),"+f"(d[8]),"+f"(d[9]),"+f"(d[10]),"+f"(d[11])
    : "r"(a0), "r"(a1), "r"(a2), "r"(a3), "l"(db), "r"(sd));
}

#define AB_POLY 0x77
__device__ __forceinline__ constexpr bool poly_group(int group) { return (AB_POLY >> (group & 7)) & 1; }

template <int V> struct Int { static constexpr int value = V; };

template <int NG>
__device__ __forceinline__ void ln_rows(float4 (&v)[NG][5], uint32_t scratch) {
  const int warp = threadIdx.x >> 5, g = (threadIdx.x & 31) >> 2;
  float stat[NG];
#pragma unroll
  for (int pass = 0; pass < 2; pass++) {
#pragma unroll
    for (int r = 0; r < NG; r++) {
      float s = 0.f;
#pragma unroll
      for (int i = 0; i < 5; i++) {
        float4& t = v[r][i];
        if (pass == 0) s += (t.x + t.y) + (t.z + t.w);
        else { t.x -= stat[r]; t.y -= stat[r]; t.z -= stat[r]; t.w -= stat[r]; s += (t.x * t.x + t.y * t.y) + (t.z * t.z + t.w * t.w); }
      }
      s += __shfl_xor_sync(~0u, s, 1);
      s += __shfl_xor_sync(~0u, s, 2);
      stat[r] = s;
    }
    bar_sync(1, 256);
    if ((threadIdx.x & 3) == 0) {
#pragma unroll
      for (int r = 0; r < NG; r++) sts32(scratch + ((r * 8 + g) * 8 + warp) * 4, __float_as_uint(stat[r]));
    }
    bar_sync(1, 256);
#pragma unroll
    for (int r = 0; r < NG; r++) {
      const float4 a = lds128f(scratch + (r * 8 + g) * 32), b = lds128f(scratch + (r * 8 + g) * 32 + 16);
      stat[r] = (((a.x + a.y) + (a.z + a.w)) + ((b.x + b.y) + (b.z + b.w))) * (1.f / DM);
    }
  }
#pragma unroll
  for (int r = 0; r < NG; r++) {
    const float rs = rsqrtf(stat[r] + 1e-5f);
#pragma unroll
    for (int i = 0; i < 5; i++) { v[r][i].x *= rs; v[r][i].y *= rs; v[r][i].z *= rs; v[r][i].w *= rs; }
  }
}

__device__ __forceinline__ void ln_store(const uint32_t (&w)[2][5][2], int tile, int u0) {
  const int lane = threadIdx.x & 31;
  uint32_t* xc = g_xc + ((tile >> 1) * 40 + u0) * 256 + (tile & 1) * 64 + lane;
#pragma unroll
  for (int i = 0; i < 20; i++) xc[(i >> 1) * 128 + (i & 1) * 32] = w[i & 1][i >> 2][i >> 1 & 1];
  if (tile >= QA_END * 8) {
    uint4* dst = reinterpret_cast<uint4*>(g_xf) + (tile * 40 + u0) * 32 + lane;
#pragma unroll
    for (int i = 0; i < 5; i++) dst[i * 32] = make_uint4(w[0][i][0], w[1][i][0], w[0][i][1], w[1][i][1]);
  } else {
#pragma unroll
    for (int i = 0; i < 5; i++) {
      const int u = u0 + i;
      uint32_t* xn = g_xn + (((tile >> 3) * 10 + (u >> 2)) * 16 + (tile & 1) * 8 + (tile & 6)) * 256 + (u & 3) * 64 + lane;
#pragma unroll
      for (int r = 0; r < 2; r++) { xn[r * 256] = w[r][i][0]; xn[r * 256 + 32] = w[r][i][1]; }
    }
  }
}
__device__ __forceinline__ void wait_count(const uint32_t* c, uint32_t n) {
  int spin = 0;
  while ((ld_acquire(c) & 0xffff) < n) { __nanosleep(32); spin_guard(spin); }
}

struct XsParams {
  CUtensorMap w[3];
  CUtensorMap o[3];
  const uint32_t* a;
  __nv_bfloat16* out;
  int ntiles, tiles_per_mat, rb0, nowait, stream_out;
  int npf, pft, ahead, gap;
  const uint8_t* pf[4];
};
constexpr int XS_STAGES = 12, XS_STAGE_BYTES = 16384;
constexpr int XS_SMEM = 1024 + XS_STAGES * XS_STAGE_BYTES + 4 * 8192 + 256;
enum { EPI_QKV = 0, EPI_BQKV = 1, EPI_RES = 2, EPI_OUT = 3 };

template <int EPI, bool MC>
__global__ void __launch_bounds__(384, 1) xs_gemm(const __grid_constant__ XsParams p) {
  extern __shared__ uint8_t smem_raw[];
  const uint32_t sb = (s2u(smem_raw) + 1023) & ~1023u;
  const uint32_t stg = sb + XS_STAGES * XS_STAGE_BYTES, bars = stg + 4 * 8192;
  const int warp = __shfl_sync(~0u, threadIdx.x >> 5, 0), lane = threadIdx.x & 31;
  const int tot = (16 - p.rb0) * p.ntiles;
  const int rank = blockIdx.x & 1, bid = MC ? (blockIdx.x & ~15) + rank * 8 + ((blockIdx.x >> 1) & 7) : blockIdx.x;
  const int u0 = p.rb0 * p.ntiles + bid * tot / gridDim.x, u1 = p.rb0 * p.ntiles + (bid + 1) * tot / gridDim.x;
  auto release = [&](int stage) {
    const uint32_t bar = bars + 8 * (XS_STAGES + stage);
    if (lane == 0) mbar_arrive(bar);
    if (MC && lane == 1) asm volatile("mbarrier.arrive.shared::cluster.b64 _, [%0];" :: "r"(mapa(bar, rank ^ 1)) : "memory");
  };
  TRACE(0);
  pdl_launch();
  if (threadIdx.x == 0) {
    for (int i = 0; i < XS_STAGES; i++) { mbar_init(bars + 8 * i, 1); mbar_init(bars + 8 * (XS_STAGES + i), MC ? 16 : 8); }
    fence_async();
    if (MC) asm volatile("fence.mbarrier_init.release.cluster;" ::: "memory");
  }
  __syncthreads();
  if (MC) asm volatile("barrier.cluster.arrive.relaxed.aligned; barrier.cluster.wait.aligned;" ::: "memory");
  if (warp >= 8) {
    asm volatile("setmaxnreg.dec.sync.aligned.u32 40;");
    if (warp == 8 && lane == 0) {
      int st = 0; uint32_t ph = 1, next = clk32();
      auto pace = [&]() { if (p.gap) { uint32_t now; do now = clk32(); while ((int)(now - next) < 0); next = now + p.gap; } };
      auto l2_ahead = [&](int u) {
        if (u >= u1 || (!MC && u != u0)) return;
        const int t = u % p.ntiles, m = t / p.tiles_per_mat, col = (t - m * p.tiles_per_mat) * 64;
        for (int kb = MC ? u / p.ntiles : 0; kb < (MC ? 10 : 5); kb += MC ? 16 : 1)
          asm volatile("cp.async.bulk.prefetch.tensor.2d.L2.global [%0, {%1, %2}];" :: "l"(&p.w[m]), "r"(col), "r"(kb * (MC ? 64 : 128)) : "memory");
      };
      for (int i = 0; i < p.ahead; i++) l2_ahead(u0 + i);
      for (int u = u0; u < u1; u++) {
        const int t = u % p.ntiles, m = t / p.tiles_per_mat, col = (t - m * p.tiles_per_mat) * 64;
        l2_ahead(u + p.ahead);
        if (u == u0 || t == 0) {
          if (u == u0 && !p.nowait) pdl_wait();
          for (int i = 0; i < 10; i++) {
            mbar_wait(bars + 8 * (XS_STAGES + st), ph);
            pace();
            mbar_expect(bars + 8 * st, XS_STAGE_BYTES);
            for (int w = 0; w < 8; w++)
              bulk_load(sb + st * XS_STAGE_BYTES + w * 2048, p.a + ((u / p.ntiles * 8 + w) * 40 + 4 * i) * 128, 2048, bars + 8 * st);
            if (++st == XS_STAGES) { st = 0; ph ^= 1; }
          }
        }
        if (u1 - u <= p.pft && blockIdx.x < 128) {
          const int bytes = 61440 / p.pft;
          const size_t off = (size_t)blockIdx.x * 61440 + (u1 - u - 1) * bytes;
          for (int i = 0; i < p.npf; i++) asm volatile("cp.async.bulk.prefetch.L2.global [%0], %1;" :: "l"(p.pf[i] + off), "r"(bytes) : "memory");
        }
        for (int kb = 0; kb < 5; kb++) {
          mbar_wait(bars + 8 * (XS_STAGES + st), ph);
          pace();
          mbar_expect(bars + 8 * st, XS_STAGE_BYTES);
          if (MC) {
            asm volatile("cp.async.bulk.tensor.2d.shared::cluster.global.mbarrier::complete_tx::bytes.multicast::cluster [%0], [%1, {%3, %4}], [%2], %5;"
                         :: "r"(sb + st * XS_STAGE_BYTES + rank * 8192), "l"(&p.w[m]), "r"(bars + 8 * st), "r"(col), "r"(kb * 128 + rank * 64), "h"((uint16_t)3) : "memory");
          } else {
            tma_load(sb + st * XS_STAGE_BYTES, &p.w[m], col, kb * 128, bars + 8 * st);
          }
          if (++st == XS_STAGES) { st = 0; ph ^= 1; }
        }
      }
    }
    __syncwarp();
    if (MC) asm volatile("barrier.cluster.arrive.relaxed.aligned;" ::: "memory");
  } else {
    asm volatile("setmaxnreg.inc.sync.aligned.u32 232;");
    const int wg = warp >> 2, g = lane >> 2, c = lane & 3;
    if (!p.nowait) pdl_wait();
    XT(0);
    int st = 0; uint32_t ph = 0;
    for (int u = u0; u < u1;) {
    const int rb = u / p.ntiles, t0 = u - rb * p.ntiles, t1 = min(p.ntiles, t0 + u1 - u);
    uint32_t a[160];
#pragma unroll
    for (int i = 0; i < 10; i++) {
      mbar_wait(bars + 8 * st, ph);
#pragma unroll
      for (int k = 4 * i; k < 4 * i + 4; k++) {
        const uint4 v = lds128(sb + st * XS_STAGE_BYTES + warp * 2048 + (k & 3) * 512 + lane * 16);
        a[4 * k] = v.x; a[4 * k + 1] = v.y; a[4 * k + 2] = v.z; a[4 * k + 3] = v.w;
      }
      __syncwarp();
      release(st);
      if (++st == XS_STAGES) { st = 0; ph ^= 1; }
    }
    XT(1);
    const int row0 = rb * 128 + wg * 64;
    for (int t = t0; t < t1; t++, u++) {
      float d[32];
      int prev = 0;
      if (wg == 1 || u != u0) bar_sync(4 + wg, 256);
#pragma unroll
      for (int kb = 0; kb < 5; kb++) {
        mbar_wait(bars + 8 * st, ph);
        const uint64_t db = mkdesc(sb + st * XS_STAGE_BYTES, 0, 1024, 1);
        if (kb == 0) wg_fence();
#pragma unroll
        for (int kk = 0; kk < 8; kk++) {
          const int k = kb * 8 + kk;
          wg_rs64_01(d, a[4 * k], a[4 * k + 1], a[4 * k + 2], a[4 * k + 3], db + kk * 128, k != 0);
        }
        wg_commit();
        if (kb == 4 && (wg == 0 || u + 1 != u1)) bar_arrive(5 - wg, 256);
        if (kb > 0) { wg_wait<1>(); release(prev); }
        prev = st;
        if (++st == XS_STAGES) { st = 0; ph ^= 1; }
      }
      wg_wait<0>();
      reg_fence<32>(d);
      release(prev);
      XT(2 + u - u0);
      if (EPI == EPI_QKV) {
        const int m = t / p.tiles_per_mat, col = (t - m * p.tiles_per_mat) * 64;
        const uint32_t buf = stg + (wg * 2 + (u & 1)) * 8192;
        const int r = (warp & 3) * 16 + (lane & 7) + ((lane >> 3) & 1) * 8;
#pragma unroll
        for (int j = 0; j < 8; j += 2)
          stsm4(buf + r * 128 + (((j + (lane >> 4)) ^ (r & 7)) << 4), pack2(d[4 * j], d[4 * j + 1]), pack2(d[4 * j + 2], d[4 * j + 3]),
                pack2(d[4 * j + 4], d[4 * j + 5]), pack2(d[4 * j + 6], d[4 * j + 7]));
        fence_async();
        if ((threadIdx.x & 127) == 0) bulk_wait_read<0>();
        bar_sync(2 + wg, 128);
        if ((threadIdx.x & 127) == 0) {
          if (p.stream_out == 2) {} else if (p.stream_out) tma_store_stream(&p.o[m], buf, col, row0); else tma_store(&p.o[m], buf, col, row0);
          bulk_commit();
        }
      } else {
        float4* x = g_x + ((rb * 16 + warp * 2) * 40 + t * 4) * 32 + lane;
        uint32_t* out = reinterpret_cast<uint32_t*>(p.out) + (rb * 128 + warp * 16 + g) * (DM / 2) + t * 32 + c;
#pragma unroll
        for (int j = 0; j < 4; j++) {
#pragma unroll
          for (int r = 0; r < 2; r++) {
            float4 y = x[(r * 40 + j) * 32];
            y.x += d[8 * j + 2 * r]; y.y += d[8 * j + 2 * r + 1]; y.z += d[8 * j + 4 + 2 * r]; y.w += d[8 * j + 5 + 2 * r];
            if (EPI == EPI_RES) x[(r * 40 + j) * 32] = y;
            else { out[r * 8 * (DM / 2) + 8 * j] = pack2(y.x, y.y); out[r * 8 * (DM / 2) + 8 * j + 4] = pack2(y.z, y.w); }
          }
        }
      }
    }
    }
    if (EPI == EPI_QKV && (threadIdx.x & 127) == 0) {
      bulk_wait<0>();
      if (p.nowait) { fence_async_global(); red_release(g_sync + SY_Q, 1); }
    }
    __syncwarp();
    if (MC) asm volatile("barrier.cluster.arrive.relaxed.aligned; barrier.cluster.wait.aligned;" ::: "memory");
    TRACE(2);
  }
}

__device__ __forceinline__ uint8_t* pool_at(uint32_t off) {
  return reinterpret_cast<uint8_t*>((reinterpret_cast<uintptr_t>(g_pool) + 8191) & ~(uintptr_t)8191) + off; }
struct Weights { const uint8_t* w[4]; };
__device__ __forceinline__ void prefetch_weights(const Weights& p, int i) {
  if (blockIdx.x < 128) asm volatile("cp.async.bulk.prefetch.L2.global [%0], 61440;" :: "l"(p.w[i] + (size_t)blockIdx.x * 61440) : "memory");
}
__global__ void __launch_bounds__(256) first_kernel(const __nv_bfloat16* __restrict__ xin, const uint4* __restrict__ wb, const __grid_constant__ Weights wa) {
  __shared__ __align__(16) float scratch[128];
  __shared__ uint32_t lat[4];
  const int warp = threadIdx.x >> 5, lane = threadIdx.x & 31, cta = blockIdx.x;
  TRACE(0);
  pdl_launch();
  if (warp < 4 && (warp < 2 || cta < NSLOT)) {
    uint32_t* q = reinterpret_cast<uint32_t*>(pool_at((warp < 2 ? NSLOT : cta) * 8192 + (warp & 1) * 4096)) + (warp < 2 ? (cta & 127) * 8 : 0);
    if (lane < 8) stg_strong32(q + lane, 0u);
    uint32_t best = ~0u;
    if (lane == 0)
      for (int r = 0; r < 4; r++) {
        uint32_t t0, t1, v;
        asm volatile("mov.u32 %0, %%clock;" : "=r"(t0) :: "memory");
        asm volatile("atom.relaxed.gpu.global.exch.b32 %0, [%1], 0;" : "=r"(v) : "l"(q) : "memory");
        asm volatile("{.reg .u32 t; add.u32 t, %1, 1; mov.u32 %0, %%clock; sub.u32 %0, %0, %1;}" : "=r"(t1) : "r"(__shfl_sync(1u, v, 0)) : "memory");
        best = min(best, t1 - t0);
      }
    if (lane == 0) lat[warp] = best;
  }
  __syncthreads();
  ABT(2, 0);
  if (threadIdx.x == 0) {
    const int part = lat[0] < lat[1] ? 0 : 1;
    uint32_t smid; asm("mov.u32 %0, %%smid;" : "=r"(smid));
    g_smpart[smid & 255] = part;
    if (cta < NSLOT) g_orient[cta] = lat[2] < lat[3] ? part : 1 - part;
  }
  if (cta < 128) {
    float4 v[2][5];
#pragma unroll
    for (int r = 0; r < 2; r++)
#pragma unroll
      for (int i = 0; i < 5; i++) {
        const uint32_t* src = reinterpret_cast<const uint32_t*>(xin) + (cta * 16 + r * 8 + (lane >> 2)) * (DM / 2) + warp * 40 + i * 8 + (lane & 3);
        const uint32_t a = src[0], b = src[4];
        v[r][i] = make_float4(bf_lo(a), bf_hi(a), bf_lo(b), bf_hi(b));
      }
    uint4 w8[2];
#pragma unroll
    for (int i = 0; i < 2; i++) w8[i] = wb[cta * 400 + min(i * 256 + threadIdx.x, 399)];
    if (threadIdx.x < 128) g_stat[cta * 128 + threadIdx.x] = make_float2(0.f, 0.f);
#pragma unroll
    for (int i = 0; i < 10; i++) g_x[((cta * 2 + i / 5) * 40 + warp * 5 + i % 5) * 32 + lane] = v[i / 5][i % 5];
    ABT(2, 1);
    if (threadIdx.x == 32) for (int i = 0; i < FK_PF; i++) prefetch_weights(wa, i);
    ln_rows<2>(v, s2u(scratch));
    ABT(2, 2);
    uint32_t w[2][5][2];
#pragma unroll
    for (int i = 0; i < 10; i++) { const float4 t = v[i / 5][i % 5]; w[i / 5][i % 5][0] = pack2(t.x, t.y); w[i / 5][i % 5][1] = pack2(t.z, t.w); }
    ln_store(w, cta, warp * 5);
    ABT(2, 3);
#pragma unroll
    for (int i = 0; i < 2; i++) {
      const int e = cta * 400 + min(i * 256 + threadIdx.x, 399), k = e / 80, n = e - k * 80, cg = n / 10;
      g_wb[((cg * 80 + (k >> 3)) * 10 + n - cg * 10) * 8 + (k & 7)] = w8[i];
    }
  } else if (cta == 128) {
    g_bo[threadIdx.x] = 0;
  }
  TRACE(2);
}

struct ChainParams {
  CUtensorMap wq, wk, wv, wo;
  const __nv_bfloat16* mem0;
  uint8_t *pool, *kv;
  const uint32_t* xc;
  uint32_t* sync;
  int layer;
  int d1, d1b, d2, d2b, mode;
};
constexpr int CH_WQ = 0, CH_WO = 81920, CH_X = CH_WO + 86016, CH_M = CH_X + 20480, CH_KT = CH_X + 40960, CH_VT = CH_KT + 4096,
              CH_QK = CH_VT + 8192, CH_VP = CH_QK + 4096, CH_SX = CH_VP + 1024, CH_O = CH_SX + 2304, CH_ID = CH_O + 3072,
              CH_BAR = CH_ID + 512;
constexpr int CH_SMEM = CH_BAR + 128;
constexpr int CH_BASE = 1024;
#define CH_VK0 8
#define CH_VK1 20
#define CH_L0 4
#define CH_LR 4
#define NOX 0
#define CH_XA 0
#define CH_XB 1
#define CH_W1 3
#define CH_W2 17
#define CH_W3 26
#define CH_RA 1
#define CH_R1 4
#define CH_TW 12
__device__ __forceinline__ uint32_t opaque(uint32_t x) { return __shfl_sync(~0u, x, threadIdx.x & 31); }
__device__ __forceinline__ uint32_t nz(uint32_t x) { uint32_t r; asm("max.u32 %0, %1, 1;" : "=r"(r) : "r"(x)); return r; }
__device__ __forceinline__ uint32_t pack_tag(float lo, float hi, uint32_t tag, uint32_t mask) {
  uint32_t r;
  asm("lop3.b32 %0, %1, %2, %3, 0xD8;" : "=r"(r) : "r"(pack2(lo, hi)), "r"(tag), "r"(mask));
  return r;
}
__device__ __forceinline__ uint32_t differ(uint32_t a, uint32_t b, uint32_t t) { uint32_t r; asm("lop3.b32 %0, %1, %2, %3, 0x7E;" : "=r"(r) : "r"(a), "r"(b), "r"(t)); return r; }
__device__ __forceinline__ void mbar_wait_hot(uint32_t bar, uint32_t ph) {
  uint32_t ok;
  asm volatile("{.reg .pred p; mbarrier.try_wait.parity.shared::cta.b64 p, [%1], %2; selp.u32 %0, 1, 0, p;}" : "=r"(ok) : "r"(bar), "r"(ph) : "memory");
  if (__builtin_expect(!ok, 0)) mbar_wait(bar, ph);
}
__device__ __forceinline__ bool elect() {
  uint32_t r; asm volatile("{.reg .pred p; elect.sync _|p, 0xffffffff; selp.u32 %0, 1, 0, p;}" : "=r"(r)); return r; }
__device__ __forceinline__ uint32_t or3(uint32_t a, uint32_t b, uint32_t c) { uint32_t r; asm("lop3.b32 %0, %1, %2, %3, 0xFE;" : "=r"(r) : "r"(a), "r"(b), "r"(c)); return r; }
__device__ __forceinline__ void pin() { pdl_launch(); }
__device__ __forceinline__ void mma16h(float* d, uint32_t a0, uint32_t a2, uint32_t b0, uint32_t b1) {
  asm volatile("{.reg .b32 u, v; mma.sync.aligned.m16n8k16.row.col.f32.bf16.bf16.f32 {%0,%1,%2,%3},{%4,u,%5,v},{%6,%7},{%0,%1,%2,%3};}"
               : "+f"(d[0]), "+f"(d[1]), "+f"(d[2]), "+f"(d[3]) : "r"(a0), "r"(a2), "r"(b0), "r"(b1)); }
__device__ __forceinline__ void mma8h(float* d, uint32_t a0, uint32_t b0) {
  asm volatile("{.reg .b32 u; mma.sync.aligned.m16n8k8.row.col.f32.bf16.bf16.f32 {%0,%1,%2,%3},{%4,u},{%5},{%0,%1,%2,%3};}"
               : "+f"(d[0]), "+f"(d[1]), "+f"(d[2]), "+f"(d[3]) : "r"(a0), "r"(b0)); }
__device__ __forceinline__ uint32_t absmax2(uint32_t a, uint32_t b) { uint32_t r; asm("max.xorsign.abs.bf16x2 %0, %1, %2;" : "=r"(r) : "r"(a), "r"(b)); return r; }
__device__ __forceinline__ void until(uint32_t t) { while ((int)(clk32() - t) < 0) {} }
__device__ __forceinline__ uint4 pack8(const float* d) { return make_uint4(pack2(d[0], d[1]), pack2(d[2], d[3]), pack2(d[4], d[5]), pack2(d[6], d[7])); }
__device__ __forceinline__ void add8(float* d, uint4 v) {
  d[0] += bf_lo(v.x); d[1] += bf_hi(v.x); d[2] += bf_lo(v.y); d[3] += bf_hi(v.y);
  d[4] += bf_lo(v.z); d[5] += bf_hi(v.z); d[6] += bf_lo(v.w); d[7] += bf_hi(v.w);
}

template <int WG>
__device__ __forceinline__ void chain_body(const ChainParams& p, const uint32_t wq, const uint32_t (&ak)[80], const uint32_t (&av)[80]) {
  const int tid = threadIdx.x & 127, t4 = __shfl_sync(~0u, tid >> 5, 0), lane = tid & 31;
  const int cta = blockIdx.x, h = cta / 3, j = cta - 3 * h;
  const uint32_t sb = mapa(CH_BASE, j);
  const uint32_t bWo = sb + CH_BAR, bWq = bWo + 8, bX = bWo + 16, bXA = bWo + 24, bXB = bWo + 32, bO = bWo + 40, bG0 = bWo + 48;
  uint32_t tw[4 * CH_TW];
  auto refill = [&]() {
#pragma unroll
    for (int k = 0; k < CH_TW; k++) ldsm4t(&tw[4 * k], wq + k * 2048);
  };
  const uint32_t wo = opaque((sb + CH_WO + (WG == 0 ? (t4 + (j == 2)) * 4096 : (j == 2 ? 0 : 24576) + t4 * 1024) + ((lane & 7) + (lane >> 4) * 8) * 64 +
                              ((((lane >> 3) & 1) ^ ((lane >> 1) & 3)) << 4)) ^ (WG == 1 && j == 2 ? 32 : 0));
  const uint32_t wo2 = opaque((wo ^ ((t4 & 1) * 32)) + (4 + (t4 >> 1) - t4) * 4096);
  const uint32_t l16 = opaque(sb + lane * 16);
  const uint32_t l8 = opaque(sb + t4 * 256 + lane * 8);
  const uint32_t lw = opaque(sb + t4 * 1024 + lane * 16);
  const uint32_t qs = opaque(sb + CH_QK + WG * 2048 + t4 * 512 + lane * 16);
  const uint32_t qa = opaque(sb + CH_QK + (lane >> 4) * 2048 + (lane & 15) * 16 + (WG == 0 ? t4 * 512 + 256 : t4 == 3 ? 1024 : 0));
  const uint32_t ka = opaque(t4 < 2 ? sb + CH_KT + t4 * 512 + lane * 16
                                    : sb + CH_QK + 256 + (t4 - 2) * 1024 + ((lane >> 3) & 1) * 2048 + (lane >> 4) * 128 + (lane & 7) * 16);
  const uint32_t l4 = opaque(sb + t4 * 256 + lane * 4);
  uint32_t pdst[3], pages = 0;
  auto line0 = [&](int i) { return 28 * j + (i < 4 ? 4 * t4 + i : 12 + 2 * t4 + i); };
  const uint32_t plane = opaque((lane >> 4) * 2048 + h * 64 + (lane & 15) * 4);
  if (WG == 0) {
    pages = __ballot_sync(~0u, lds32(sb + CH_O + line0(min(lane, 5)) * 4) & 4096);
  } else {
    pages = __ballot_sync(~0u, lds32(sb + CH_O + (80 + min(lane, 11)) * 4) & 4096);
    pdst[0] = opaque(lds32(sb + CH_O + (j == 0 ? 24 + t4 : 50 + 2 * j + (t4 & 1)) * 4) + plane);
    const uint32_t role = lds32(sb + CH_O + NSLOT * 4);
    pdst[1] = opaque(lds32(sb + CH_O + role * 4) + (t4 & 1) * 2048 + (lane & 7) * 64 + (lane >> 3) * 16);
    pdst[2] = opaque((80 + role / 20) * 8192 + role % 20 * 128 + (t4 >= 2 ? (t4 & 1) * 64 + (lane & 3) * 16 + (lane >> 2) * 2 : (t4 & 1) * 4096 + lane * 4));
  }
  const uint32_t r1 = mapa(CH_BASE, j == 2 ? 0 : j + 1) - sb, r2 = mapa(CH_BASE, j == 0 ? 2 : j - 1) - sb;
  uint32_t tag = opaque(1);
  auto pool = [&](uint32_t off) { return p.pool + ((tag & 0xfffe) + off); };
  auto after = [&](uint32_t x) { return x & tag & 0xfffe; };
  auto kv = [&](int s, uint32_t a) { return p.kv + ((size_t)(cta * NSEG + (s & KVM)) * KV_BYTES - sb) + a; };
  auto pass = [&](float (&d)[16], const uint32_t (&a)[80]) {
    const uint64_t db = mkdesc(CH_BASE + CH_X + WG * 20480, 512, 128, 0);
    wg_fence();
#pragma unroll
    for (int k = 0; k < 20; k++) {
      wg_rs32_00(d, a[4 * k], a[4 * k + 1], a[4 * k + 2], a[4 * k + 3], db + k * 64, k);
      if (k == 19 || (WG == 1 && k == 9)) wg_commit();
    }
  };
  auto dump = [&](float (&d)[16], uint32_t a) {
    wg_wait<0>();
    reg_fence<16>(d);
    sts128(a, pack8(d)); sts128(a + 512, pack8(d + 8));
  };
  auto tokens0 = [&](int s) {
    float d[16];
    if (!NOX || s == 0) mbar_wait_hot(bXB, s & 1);
    bar_sync(7, 256);
    pass(d, ak);
    TM1(5);
    bar_sync(9, 256);
    const uint4 k0 = lds128(lw + CH_KT), k1 = lds128(lw + CH_KT + 512);
    __syncwarp();
    wg_wait<0>();
    reg_fence<16>(d);
    add8(d, k0); add8(d + 8, k1);
#pragma unroll
    for (int e = 0; e < 2; e++) { const uint4 v = pack8(d + 8 * e); stsm4t(lw + CH_KT + e * 512, v.x, v.z, v.y, v.w); }
    fence_async();
    __syncwarp();
    if (elect()) { bulk_store(p.kv + (size_t)(cta * NSEG + (s & KVM)) * KV_BYTES + t4 * 1024, sb + CH_KT + t4 * 1024, 1024); bulk_commit(); }
    TM1(6);
    bar_sync(8, 256);
    pass(d, av);
    TM1(9);
    bulk_wait_read<0>();
    dump(d, lw + CH_VT);
  };
  PRO(11);
  if (WG == 0) {
    tokens0(0);
  } else {
    const uint32_t* m0 = reinterpret_cast<const uint32_t*>(p.mem0) + (lane >> 2) * 320 + t4 * 80 + (lane & 3);
    uint32_t a[20];
#pragma unroll
    for (int i = 0; i < 20; i++) a[i] = m0[4 * i];
    pin();
    float d[16];
    mbar_wait(bXA, 0);
    pass(d, ak);
    bar_arrive(7, 256);
    dump(d, lw + CH_KT);
    bar_arrive(9, 256);
    pass(d, av);
    bar_arrive(8, 256);
    dump(d, lw + CH_VT + 4096);
    bar_sync(3, 128);
#pragma unroll
    for (int i = 0; i < 20; i++) sts32(sb + CH_M + (t4 * 20 + i) * 128 + lane * 4, transpose8(a[i]));
  }
  PRO(8);
  mbar_wait(bWq, 0);
  refill();
  PRO(9);
  mbar_wait(bWo, 0);
  asm volatile("barrier.cluster.wait.aligned;" ::: "memory");
  PRO(10);
  constexpr int VK = WG == 0 ? CH_VK0 : CH_VK1;
  auto project = [&](int s, uint32_t (&b)[40], float (&dv)[16], uint32_t (&kf)[16]) {
    float dq[4] = {}, dk[4] = {};
    uint32_t w[80];
#pragma unroll
    for (int i = 0; i < 4 * CH_TW; i++) w[i] = tw[i];
    auto load = [&](int n) {
      int c = 0;
#pragma unroll
      for (int i = 0; i < 10; i++) {
        if (c++ == n) ldsm4t(&b[4 * i], l16 + CH_M + WG * 5120 + i * 512);
#pragma unroll
        for (int k = 2 * i; k < 2 * i + 2; k++)
          if (k >= CH_TW && c++ == n) ldsm4t(&w[4 * k], wq + k * 2048);
      }
#pragma unroll
      for (int i = 0; i < 4; i++)
        if (WG == 1 && c++ == n) ldsm4(&kf[4 * i], ka + i * 1024);
    };
#pragma unroll
    for (int n = 0; n < CH_L0; n++) load(n);
    TM(0);
#pragma unroll
    for (int k = 0; k < 20; k += 2) {
      if (k > 0) {
#pragma unroll
        for (int n = CH_L0 + (k - 2) * CH_LR / 4; n < (k == 18 ? 40 : CH_L0 + k * CH_LR / 4); n++) load(n);
      }
      pin();
#pragma unroll
      for (int kk = k; kk < k + 2; kk++) {
        mma16(dk, ak[4 * kk], ak[4 * kk + 1], ak[4 * kk + 2], ak[4 * kk + 3], b[2 * kk], b[2 * kk + 1]);
        mma16(dq, w[4 * kk], w[4 * kk + 1], w[4 * kk + 2], w[4 * kk + 3], b[2 * kk], b[2 * kk + 1]);
        if (kk < VK) mma16(dv, av[4 * kk], av[4 * kk + 1], av[4 * kk + 2], av[4 * kk + 3], b[2 * kk], b[2 * kk + 1]);
      }
    }
    const float k2 = 0.07216878364870322f * 1.44269504089f;
    stsm4t(qs, pack2(dq[0] * k2, dq[1] * k2), pack2(dq[2] * k2, dq[3] * k2), pack2(dk[0], dk[1]), pack2(dk[2], dk[3]));
    TM(1);
  };
  constexpr int VC = VK == 20 ? 1 : WG == 0 ? 2 : 3;
  auto finish_v = [&](const uint32_t (&b)[40], float (&dv)[16]) {
#pragma unroll
    for (int kk = VK; kk < 20; kk++) mma16(dv + 4 * ((kk - VK) % VC), av[4 * kk], av[4 * kk + 1], av[4 * kk + 2], av[4 * kk + 3], b[2 * kk], b[2 * kk + 1]);
  };
  auto sum_v = [&](float (&dv)[16]) {
#pragma unroll
    for (int i = 4; i < 4 * VC; i++) dv[i & 3] += dv[i];
  };
  auto publish_km = [&](int s) {
    uint32_t a[4];
    ldsm4(a, qa);
    *reinterpret_cast<uint2*>(kv(s, l8) + KV_KM) = make_uint2(hadd2(a[0], a[2]), hadd2(a[1], a[3]));
  };
  auto load_v = [&](uint4 (&vr)[4]) {
#pragma unroll
    for (int e = 0; e < 4; e++) vr[e] = lds128(lw + CH_VT + (e & 1) * 4096 + (e >> 1) * 512);
  };
  auto token_v = [&](uint4 (&v)[2], const uint4 (&vr)[4]) {
#pragma unroll
    for (int e = 0; e < 2; e++) {
      const uint4 x = vr[2 * e], y = vr[2 * e + 1];
      v[e] = make_uint4(hadd2(x.x, y.x), hadd2(x.z, y.z), hadd2(x.y, y.y), hadd2(x.w, y.w));
    }
  };
  auto memory_v = [&](uint2 x, const float (&dv)[16]) {
    return make_uint2(pack2(dv[0] + bf_lo(x.x), dv[1] + bf_hi(x.x)), pack2(dv[2] + bf_lo(x.y), dv[3] + bf_hi(x.y)));
  };
  auto publish_v = [&](int s, const uint4 (&v)[2], uint2 vm) {
#pragma unroll
    for (int e = 0; e < 2; e++) reinterpret_cast<uint4*>(kv(s, lw) + KV_V)[e * 32] = v[e];
    *reinterpret_cast<uint2*>(kv(s, l8) + KV_VM) = vm;
  };
  auto load_x = [&](int s, int k0, int n, uint32_t bar) {
    if (!NOX && elect()) { mbar_expect(bar, n * 1024); bulk_load(sb + CH_X + k0 * 1024, p.xc + (s + 1) * 10240 + k0 * 256, n * 1024, bar); }
  };
  uint32_t gph = 0;
  int st = 0;
#pragma unroll 1
  for (int s = 0; s < NSEG - 1; s++) {
    bar_sync(6, 256);
    float dv[16] = {};
    uint32_t b[40], kf[16];
    project(s, b, dv, kf);
    if (WG == 0) {
      bar_sync(1, 256);
      if (CH_XA == 0) load_x(s, 20 + 5 * t4, 5, bXA);
      if (CH_XB == 0) load_x(s, 5 * t4, 5, bXB);
      pin();
      finish_v(b, dv);
      sum_v(dv);
      sts64(l8 + CH_VP, pack2(dv[0], dv[1]), pack2(dv[2], dv[3]));
      __syncwarp();
      if (elect()) mbar_arrive(bX);
      if (CH_XA == 1) load_x(s, 20 + 5 * t4, 5, bXA);
      if (CH_XB == 1) load_x(s, 5 * t4, 5, bXB);
      uint32_t w[144];
      auto wload = [&](int i) { ldsm4t(&w[4 * i], (i % 3 == 0 ? wo : i % 3 == 1 ? wo ^ 32 : wo2) + i / 12 * 28672 + i / 3 % 4 * 1024); };
      TM(3);
#pragma unroll
      for (int i = 0; i < CH_W1; i++) wload(i);
      bar_sync(10, 256);
#pragma unroll
      for (int i = CH_W1; i < CH_W2; i++) wload(i);
      if (CH_XA == 2) load_x(s, 20 + 5 * t4, 5, bXA);
      if (CH_XB == 2) load_x(s, 5 * t4, 5, bXB);
      bar_sync(2, 256);
      {
        float y[3][4] = {};
        uint32_t ob[24];
        ldsm4(&ob[0], l16 + CH_O + 1024); ldsm4(&ob[4], l16 + CH_O + 1536);
        TM(7);
        auto step = [&](int i) {
          const int k = i / 3;
          mma16(y[i % 3], w[4 * i], w[4 * i + 1], w[4 * i + 2], w[4 * i + 3], ob[2 * k], ob[2 * k + 1]);
        };
#pragma unroll
        for (int i = 0; i < 12; i++) {
          step(i);
          if (i >= 12 - (CH_W3 - CH_W2)) wload(CH_W3 - 12 + i);
          if (i % 3 == 2) pin();
        }
        if (CH_XB == 3) load_x(s, 5 * t4, 5, bXB);
        pin();
        mbar_wait(bO, s & 1);
        TM(4);
        ldsm4(&ob[8], l16 + CH_O); ldsm4(&ob[12], l16 + CH_O + 512);
        pin();
        float2 inv;
        uint8_t* dst[6];
        uint32_t mask;
#pragma unroll
        for (int i = 12; i < 36; i++) {
          step(i);
          const int n = CH_W3 + i - 13, m = n - (n > 30);
          if (i == 12) ldsm4(&ob[16], l16 + after(w[4 * CH_W3 - 1] | w[4 * CH_W3 - 5] | w[4 * CH_W3 - 9] | ob[8]) + CH_O + 2048);
          else if (n == 30) ldsm4(&ob[20], l16 + CH_O + 2560);
          else if (m < 36) wload(m);
          else if (m == 36) inv = lds64f((l8 & ~0xe0u) + CH_VP);
          if (i == 26) mask = ((l16 ^ tag) & 48) == 0;
          if (i >= 27 && i < 33) dst[i - 27] = pool(line0(i - 27) * 8192 + (pages >> (i - 27) & 1) * 4096) + plane;
          if (i % 3 == 2) pin();
        }
#pragma unroll
        for (int k = 0; k < CH_R1; k++) ldsm4t(&tw[4 * k], wq + k * 2048);
        pin();
#pragma unroll
        for (int i = 0; i < 6; i++) stg_strong32(dst[i], pack_tag(y[i >> 1][2 * (i & 1)] * inv.x, y[i >> 1][2 * (i & 1) + 1] * inv.y, tag, mask));
        TM(8);
        bar_arrive(5, 256);
        pin();
#pragma unroll
        for (int k = CH_R1; k < CH_TW; k++) ldsm4t(&tw[4 * k], wq + k * 2048);
      }
      publish_km(s);
      if (t4 == 3 && cta < 40 && s + 4 < NSEG && elect())
        asm volatile("cp.async.bulk.prefetch.L2.global [%0], 1024;" :: "l"(p.xc + (s + 4) * 10240 + cta * 256) : "memory");
      if (t4 == 2 && (s & 3) == 0 && s > 0 && elect()) red_relaxed(p.sync + 2 * s - 4, 1);
      if (t4 == 2 && s == NSEG - 3 && cta == 95 && elect()) red_relaxed(p.sync + 2 * s + 2, 0x10000);
      tokens0(s + 1);
      TM(2);
    } else {
      const uint32_t xo = l4 + (CH_SX - (t4 == 3 ? 128 : 0)), x1 = xo + (r1 + 768 + min(t4, 2) * 256), x2 = xo + (r2 + 1024 + min(t4, 2) * 256);
      if (t4 < 2) {
        float ds[4][4] = {};
        uint32_t q[16];
        asm volatile("bar.sync 1, 256;" ::: "memory");
#pragma unroll
        for (int k = 0; k < 4; k++) ldsm4(&q[4 * k], qa + k * 512);
        pin();
        if (VK < 20) { finish_v(b, dv); pin(); }
#pragma unroll
        for (int k = 0; k < 4; k++) {
          mma16(ds[k & 1], kf[4 * k], kf[4 * k + 1], kf[4 * k + 2], kf[4 * k + 3], q[4 * k], q[4 * k + 1]);
          mma16(ds[2 + (k & 1)], kf[4 * k], kf[4 * k + 1], kf[4 * k + 2], kf[4 * k + 3], q[4 * k + 2], q[4 * k + 3]);
        }
        float t[4];
#pragma unroll
        for (int i = 0; i < 4; i++) t[i] = (ds[0][i] + ds[2][i]) + (ds[1][i] + ds[3][i]);
        const uint32_t w0 = pack2(t[0], t[1]), w1 = pack2(t[2], t[3]);
        st_async32(x1, w0, bX + r1); st_async32(x2, w0, bX + r2);
        st_async32(x1 + 128, w1, bX + r1); st_async32(x2 + 128, w1, bX + r2);
        sts32(xo, w0); sts32(xo + 128, w1);
      } else {
        float ds[4][4] = {};
        uint32_t q0[4], q1[4], a0[4], a1[4];
        asm volatile("bar.sync 1, 256; " ::: "memory");
        ldsm4(a0, ka); ldsm4(q0, qa); ldsm4(a1, ka + 512); ldsm4(q1, qa + 512);
        pin();
        if (VK < 20) { finish_v(b, dv); pin(); }
        mma16(ds[0], a0[0], a0[1], a0[2], a0[3], q0[0], q0[1]);
        mma16(ds[1], a0[0], a0[1], a0[2], a0[3], q0[2], q0[3]);
        mma16(ds[2], a1[0], a1[1], a1[2], a1[3], q1[0], q1[1]);
        mma16(ds[3], a1[0], a1[1], a1[2], a1[3], q1[2], q1[3]);
        float t[2];
#pragma unroll
        for (int i = 0; i < 2; i++)
          t[i] = ((ds[0][i] + ds[0][i + 2]) + (ds[1][i] + ds[1][i + 2])) + ((ds[2][i] + ds[2][i + 2]) + (ds[3][i] + ds[3][i + 2]));
        const uint32_t w0 = pack2(t[0], t[1]);
        st_async32(x1, w0, bX + r1);
        st_async32(x2, w0, bX + r2);
        sts32(xo, w0);
      }
      TM(3);
      const uint4 id = lds128(l16 + CH_ID);
      float sc[3][4] = {};
      uint4 v[2], vr[4];
      sum_v(dv);
      bar_sync(3, 128);
      uint32_t r[12], wd[12];
      ldsm4(&r[0], l16 + CH_SX); ldsm2(&r[4], l16 + CH_SX + 512);
      pin();
      load_v(vr);
#pragma unroll
      for (int u = 0; u < 3; u++) ldsm4t(&wd[4 * u], wo + u * 28672);
      pin();
#pragma unroll
      for (int q = 0; q < 3; q++) mma16(sc[q], id.x, id.y, id.z, id.w, r[2 * q], r[2 * q + 1]);
      uint32_t big = absmax2(absmax2(absmax2(r[0], r[1]), absmax2(r[2], r[3])), absmax2(r[4], r[5]));
      token_v(v, vr);
      const uint32_t oa1 = l4 + (r1 + CH_O), oa2 = l4 + (r2 + CH_O + 2048), ones = 0x3f803f80u;
      mbar_wait_hot(bX, s & 1);
      TM(4);
      ldsm4(&r[0], l16 + CH_SX + 768); ldsm4(&r[8], l16 + CH_SX + 1792); ldsm4(&r[4], l16 + CH_SX + 1280);
      const uint2 vp = lds64(l8 + CH_VP);
      bar_arrive(10, 256);
      pin();
      {
        float sd[3][4] = {};
#pragma unroll
        for (int i = 0; i < 3; i++) {
          const int q = i == 0 ? 0 : 3 - i;
          mma16(sc[q], id.x, id.y, id.z, id.w, r[4 * q], r[4 * q + 1]);
          mma16(sd[q], id.x, id.y, id.z, id.w, r[4 * q + 2], r[4 * q + 3]);
          big = absmax2(big, absmax2(absmax2(r[4 * q], r[4 * q + 1]), absmax2(r[4 * q + 2], r[4 * q + 3])));
        }
#pragma unroll
        for (int i = 0; i < 12; i++) sc[i >> 2][i & 3] += sd[i >> 2][i & 3];
      }
      const bool redo = __any_sync(~0u, (absmax2(big, big << 16) & 0x7fff0000u) >= 0x41800000u);
      const uint2 vm = memory_v(vp, dv);
      sc[2][0] += sc[2][2]; sc[2][1] += sc[2][3];
      float l[4], o[2][4];
      uint32_t p3, p4;
      auto attend = [&]() {
#pragma unroll
        for (int i = 0; i < 4; i++) l[i] = o[0][i] = o[1][i] = 0.f;
        const uint32_t p1 = pack2(ex2(sc[0][0]), ex2(sc[0][1])), p2 = pack2(ex2(sc[0][2]), ex2(sc[0][3]));
        mma16h(o[0], p1, p2, v[0].x, v[0].y);
        mma16h(o[1], p1, p2, v[0].z, v[0].w);
        mma16h(l, p1, p2, ones, ones);
        const uint32_t p0 = pack2(ex2(sc[2][0]), ex2(sc[2][1]));
        mma8h(o[0], p0, vm.x);
        mma8h(o[1], p0, vm.y);
        mma8h(l, p0, ones);
        p3 = pack2(ex2(sc[1][0]), ex2(sc[1][1])); p4 = pack2(ex2(sc[1][2]), ex2(sc[1][3]));
        mma16h(o[0], p3, p4, v[1].x, v[1].y);
        mma16h(o[1], p3, p4, v[1].z, v[1].w);
      };
      attend();
      if (__builtin_expect(redo, 0)) {
        float mx = fmaxf(sc[2][0], sc[2][1]);
#pragma unroll
        for (int i = 0; i < 4; i++) mx = fmaxf(mx, fmaxf(sc[0][i], sc[1][i]));
        mx = fmaxf(mx, __shfl_xor_sync(~0u, mx, 1));
        mx = fmaxf(mx, __shfl_xor_sync(~0u, mx, 2));
#pragma unroll
        for (int i = 0; i < 4; i++) { sc[0][i] -= mx; sc[1][i] -= mx; }
        sc[2][0] -= mx; sc[2][1] -= mx;
        attend();
      }
      const uint32_t o0 = pack2(o[0][0], o[0][1]), o1 = pack2(o[1][0], o[1][1]);
      st_async32(oa1, o0, bO + r1); st_async32(oa2, o0, bO + r2);
      st_async32(oa1 + 128, o1, bO + r1); st_async32(oa2 + 128, o1, bO + r2);
      sts32(l4 + CH_O + 1024, o0); sts32(l4 + CH_O + 1152, o1);
      bar_arrive(2, 256);
      pin();
      TM(6);
      mma16h(l, p3, p4, ones, ones);
      float inv;
      asm("rcp.approx.ftz.f32 %0, %1;" : "=f"(inv) : "f"(l[0]));
      sts32((l8 & ~0xffu) + (lane & 28) + CH_VP, __float_as_uint(inv));
      __syncwarp();
      if (elect()) mbar_arrive(bO);
      {
        float z[2][4] = {}, y[2][4] = {};
        uint32_t we[12] = {};
        mma16(z[0], wd[0], wd[1], wd[2], wd[3], o0, o1);
        if (j == 0) {
#pragma unroll
          for (int u = 0; u < 3; u++) ldsm4t(&we[4 * u], (wo ^ 32) + u * 28672);
          mma16(y[0], we[0], we[1], we[2], we[3], o0, o1);
        }
        const float2 iv = lds64f((l8 & ~0xe0u) + CH_VP);
        uint8_t* dst = pool(pdst[0]);
        const uint32_t mask = ((l16 ^ tag) & 48) == 0;
        const uint32_t oa = qa + ((tag & 0xfffe) + CH_O - CH_QK + t4 * 256 - (t4 == 3 ? 1024 : 0));
        const uint32_t za = l16 + ((tag & 0xfffe) + (t4 >> 1) * 512 + (t4 & 1) * 8);
        pin();
        mbar_wait(bO, s & 1);
        uint32_t a[4];
        ldsm4(a, oa);
        mma16(z[0], wd[4], wd[5], wd[6], wd[7], a[0], a[1]);
        mma16(z[1], wd[8], wd[9], wd[10], wd[11], a[2], a[3]);
        if (j == 0) {
          mma16(y[0], we[4], we[5], we[6], we[7], a[0], a[1]);
          mma16(y[1], we[8], we[9], we[10], we[11], a[2], a[3]);
          sts128f(lw + CH_VT + 512, y[0][0] + y[1][0], y[0][1] + y[1][1], y[0][2] + y[1][2], y[0][3] + y[1][3]);
        }
        sts128f(lw + CH_VT, z[0][0] + z[1][0], z[0][1] + z[1][1], z[0][2] + z[1][2], z[0][3] + z[1][3]);
        bar_sync(3, 128);
        if (j == 0 || t4 < 2) {
          float2 q[4];
#pragma unroll
          for (int i = 0; i < 4; i++) q[i] = lds64f(za + CH_VT + i * 1024);
          stg_strong32(dst, pack_tag(((q[0].x + q[1].x) + (q[2].x + q[3].x)) * iv.x, ((q[0].y + q[1].y) + (q[2].y + q[3].y)) * iv.y, tag, mask));
        }
      }
      TM(2);
      float d[16];
      bar_sync(5, 256);
      publish_v(s, v, vm);
#pragma unroll
      for (int k = 0; k < CH_RA; k++) ldsm4t(&tw[4 * k], wq + k * 2048);
      if (t4 == 0 && s + 2 < NSEG && elect()) { mbar_expect(bX, 1536); mbar_expect(bO, 2048); }
      if (!NOX) mbar_wait_hot(bXA, (s + 1) & 1);
      uint8_t* mdst = p.pool + ((t4 >= 2 ? st : st == 2 ? 0 : st + 1) * 32768 + pdst[2]);
      const uint8_t* psrc = pool(pdst[1] + after(tw[4 * CH_RA - 1]));
      pin();
      pass(d, ak);
      bar_arrive(7, 256);
      TM(5);
      if (t4 >= 2) {
        uint4 u[4];
        DELAY(p.d1);
#pragma unroll
        for (int i = 0; i < 4; i++) u[i] = ldg_strong128(psrc + i * 512);
        __syncwarp();
        dump(d, lw + CH_KT);
        bar_arrive(9, 256);
        TM(14);
        TMD(15, u[3].x);
        const uint32_t one = lane & 4 ? 0x3f800000u : 0x00003f80u, g2 = lane >> 3;
        int n = 0;
        float y[4][4];
        for (;;) {
#pragma unroll
          for (int i = 0; i < 4; i++) y[0][i] = y[1][i] = y[2][i] = y[3][i] = 0.f;
#pragma unroll
          for (int i = 0; i < 4; i++) {
            mma16h(y[i & 1], g2 == 0 ? one : 0, g2 == 1 ? one : 0, u[i].x, u[i].y);
            mma16h(y[2 + (i & 1)], g2 == 2 ? one : 0, g2 == 3 ? one : 0, u[i].z, u[i].w);
          }
          if (__builtin_expect(!__any_sync(~0u, (differ(u[0].x, u[1].x, tag) | differ(u[2].x, u[3].x, tag)) & 1), 1)) break;
#pragma unroll
          for (int i = 0; i < 4; i++) u[i] = ldg_strong128(psrc + i * 512);
          spin_guard(n);
        }
        const float v = ((y[0][0] + y[0][1]) + (y[2][0] + y[2][1])) + ((y[1][0] + y[1][1]) + (y[3][0] + y[3][1]));
        const uint32_t w = nz(pack2(v, 0.f));
        stg_strong16(mdst, w); stg_strong16(mdst + 4096, w);
        TMV(12, 32, n);
      } else {
        dump(d, lw + CH_KT);
        bar_arrive(9, 256);
        stg_strong32(mdst, 0u);
      }
      TM(8);
      bar_sync(3, 128);
      pass(d, av);
      bar_arrive(8, 256);
      TM(7);
      const uint32_t bG = bG0 + t4 * 8, mq = sb + CH_M + t4 * 2560;
      const uint8_t* msrc = p.pool + ((80 + st * 4 + t4) * 8192 + (pages >> (st * 4 + t4) & 1) * 4096);
      wg_wait<1>();
      bar_sync(3, 128);
      DELAY(p.d2);
      if (elect()) { mbar_expect(bG, 2560); bulk_load(mq, msrc, 2560, bG); }
      TM(9);
      dump(d, lw + CH_VT + 4096);
#pragma unroll
      for (int k = CH_RA; k < CH_TW; k++) ldsm4t(&tw[4 * k], wq + k * 2048);
      TM(10);
      int n = 0;
      for (;;) {
        mbar_wait(bG, gph);
        gph ^= 1;
        const uint32_t c = mq + lane * 32 + (lane >> 2) * 4;
        if (!__any_sync(~0u, __vimin3_u32(lds32(c), lds32(c + 1024), lds32(c + 1536)) == 0)) break;
        if (elect()) { mbar_expect(bG, 2560); bulk_load(mq, msrc, 2560, bG); }
        spin_guard(n);
      }
      TM(11);
      TMV(13, 32, n);
    }
    if (++st == 3) st = 0;
    tag ^= 0x10001;
  }
  {
    const int s = NSEG - 1;
    bar_sync(6, 256);
    float dv[16] = {};
    uint32_t b[40], kf[16];
    project(s, b, dv, kf);
    finish_v(b, dv);
    sum_v(dv);
    if (WG == 0) {
      sts64(l8 + CH_VP, pack2(dv[0], dv[1]), pack2(dv[2], dv[3]));
      bar_sync(1, 256);
      publish_km(s);
      bulk_wait<0>();
      fence_async_global();
      bar_sync(2, 256);
      if (tid == 0) red_release(g_sync + 15 * 8 + 4, 1);
    } else {
      uint4 v[2], vr[4];
      load_v(vr);
      token_v(v, vr);
      bar_sync(1, 256);
      publish_v(s, v, memory_v(lds64(l8 + CH_VP), dv));
      bar_arrive(2, 256);
    }
  }
}

__global__ void __launch_bounds__(256, 1) chain_kernel(const __grid_constant__ ChainParams p) {
  extern __shared__ __align__(1024) uint8_t smem_raw[];
  const uint32_t sb = s2u(smem_raw);
  const int tid = threadIdx.x, warp = __shfl_sync(~0u, tid >> 5, 0), lane = tid & 31;
  const int cta = blockIdx.x, h = cta / 3, j = cta - 3 * h, colbase = cta * 64;
  const uint32_t bWo = sb + CH_BAR, bWq = bWo + 8, bXA = bWo + 24, bWk = bWo + 80, bWv = bWo + 88;
  uint32_t smid; asm("mov.u32 %0, %%smid;" : "=r"(smid));
  PRO(0);
  if (sb != mapa(CH_BASE, j)) __trap();
  uint32_t entry = 0;
  auto place = [&]() {
    const int i = tid - 128;
    if (i >= 0 && i <= NSLOT) {
      const uint32_t side = ldg_strong32(g_smpart + (smid & 255));
      if (i < NSLOT) {
        entry = i * 8192 + (ldg_strong32(g_orient + i) == (i < 80 ? i & 1 : side) ? 0 : 4096);
      } else {
        const uint32_t t = atomicAdd(g_bo + p.layer * 128 + 1 + side, 1);
        entry = t < 40 ? 2 * t + side : 2 * (79 - min(t, 79u)) + 1 - side;
      }
    }
    __syncwarp();
  };
  if (p.layer) place();
  if (warp == 0 && elect()) {
#pragma unroll 1
    for (int i = 0; i < 12; i++) mbar_init(bWo + 8 * i, i == 2 || i == 5 ? 5 : i == 3 || i == 4 ? 4 : 1);
    asm volatile("fence.mbarrier_init.release.cluster;" ::: "memory");
    mbar_expect(bWk, 81920);
    tma_load3<(WEF & 1) != 0>(sb + CH_WQ, &p.wk, colbase, 0, bWk);
    mbar_expect(bWv, 81920);
    tma_load3<(WEF & 1) != 0>(sb + CH_WO, &p.wv, colbase, 0, bWv);
    mbar_expect(bWo + 16, 1536);
    mbar_expect(bWo + 40, 2048);
    mbar_expect(bWo, 86016); mbar_expect(bWq, 81920);
#pragma unroll 1
    for (int i = 0; i < 8; i++) mbar_expect(bXA + 8 * (i & 1), 5120);
  }
  if (warp == 1) {
    const uint32_t id = (lane >> 3) == (lane & 3) ? ((lane & 4) ? 0x3f800000u : 0x00003f80u) : 0u;
    sts128(sb + CH_ID + lane * 16, make_uint4(id, 0, 0, id));
  }
  __syncthreads();
  asm volatile("barrier.cluster.arrive.relaxed.aligned;" ::: "memory");
  uint32_t ak[80], av[80];
  const uint32_t wq = opaque(sb + CH_WQ + ((warp >> 2) * 320 + (lane & 7) + (lane >> 4) * 8) * 128 + (((2 * (warp & 3) + ((lane >> 3) & 1)) ^ (lane & 7)) << 4));
  PRO(2);
  mbar_wait(bWk, 0);
  PRO(3);
#pragma unroll
  for (int k = 0; k < 20; k++) ldsm4t(&ak[4 * k], wq + k * 2048);
  bar_sync(6, 256);
  pdl_wait();
  pdl_launch();
  PRO(1);
  if (!p.layer) place();
  if (warp == 0 && elect()) {
    bulk_load(sb + CH_X + 20480, p.xc + 5120, 20480, bXA);
    bulk_load(sb + CH_X, p.xc, 20480, bXA + 8);
    tma_load3<(WEF & 2) != 0>(sb + CH_WQ, &p.wq, colbase, 0, bWq);
  }
  __syncwarp();
  PRO(4);
  mbar_wait(bWv, 0);
  PRO(5);
#pragma unroll
  for (int k = 0; k < 20; k++) ldsm4t(&av[4 * k], wq + CH_WO + k * 2048);
  bar_sync(6, 256);
  PRO(6);
  if (warp >= 5 && elect()) tma_load3<(WEF & 2) != 0>(sb + CH_WO + (warp - 5) * 28672, &p.wo, j == 0 ? 0 : 32 + j * 192, h * 192 + (j + 8 - warp) % 3 * 64, bWo);
  if (tid >= 128 && tid <= 128 + NSLOT) sts32(sb + CH_O + (tid - 128) * 4, entry);
  PRO(7);
  __syncthreads();
  if (__shfl_sync(~0u, tid >> 7, 0) == 0) chain_body<0>(p, wq, ak, av); else chain_body<1>(p, wq, ak, av);
}

struct PostParams { CUtensorMap q, o, wq, wo, wb; int nq, gap; };
constexpr int OP_STAGES = 4, OP_STAGE_BYTES = 57344;
constexpr int OP_SMEM = 1024 + OP_STAGES * OP_STAGE_BYTES + 256 + 1024;
enum { IT_ATT = 0, IT_OP = 1, IT_FIN = 2, IT_BQ = 3 };

__device__ __forceinline__ uint32_t item_count(int type, int b) { return type == IT_ATT ? 32 : type == IT_OP ? 2 * op_split(b) : type == IT_FIN ? fin_items(b) : bq_items(b); }
__device__ __forceinline__ int item_stages(int type, int b) { return type == IT_ATT ? 3 : type == IT_OP ? 96 / op_split(b) : type == IT_FIN ? (b < OP_B8 ? 2 + op_split(b) : 5) : 10; }
__device__ __forceinline__ uint32_t item_need(int type, int b) { return type == IT_ATT ? 96 : item_count(type - 1, b); }

template <int HALF, bool QREG>
__device__ __forceinline__ void attn_a_warp(uint32_t sb, uint32_t bars, int& st, uint32_t& ph, uint32_t done, int& nd, const float* q) {
  constexpr int NT = HALF ? 5 : 3;
  const int lane = threadIdx.x & 31, g = lane >> 2, c = lane & 3, seg = (threadIdx.x >> 5) & 3, l7 = lane & 7;
  const uint32_t qrow = (seg * 32 + HALF * 16 + (lane & 15)) * 128;
  float sc[NT][4] = {};
  uint32_t base[3];
#pragma unroll
  for (int u = 0; u < 3; u++) {
    mbar_wait(bars + 8 * st, ph);
    base[u] = sb + st * OP_STAGE_BYTES;
    if (++st == OP_STAGES) { st = 0; ph ^= 1; }
    const uint32_t kv = base[u] + 16384 + seg * KV_BYTES;
#pragma unroll
    for (int kk = 0; kk < 4; kk++) {
      const uint2 km = lds64(kv + KV_KM + kk * 256 + lane * 8);
      uint32_t a[4];
      if (QREG) {
#pragma unroll
        for (int i = 0; i < 4; i++) a[i] = pack2(q[32 * u + 8 * kk + 2 * i], q[32 * u + 8 * kk + 2 * i + 1]);
      } else {
        ldsm4(a, base[u] + qrow + (((2 * kk + (lane >> 4)) ^ l7) << 4));
      }
      mma16(sc[0], a[0], a[1], a[2], a[3], km.x, km.y);
#pragma unroll
      for (int t = 0; t <= HALF; t++) {
        uint32_t kb[4];
        ldsm4(kb, kv + kk * 1024 + t * 512 + (lane & 8) * 32 + (lane & 16) * 8 + l7 * 16);
        mma16(sc[1 + 2 * t], a[0], a[1], a[2], a[3], kb[0], kb[1]);
        mma16(sc[2 + 2 * t], a[0], a[1], a[2], a[3], kb[2], kb[3]);
      }
    }
  }
  const float k2 = 0.07216878364870322f * 1.44269504089f, NEG = -INFINITY;
  if (2 * c > g) { sc[NT - 2][0] = NEG; sc[NT - 1][2] = NEG; }
  if (2 * c + 1 > g) { sc[NT - 2][1] = NEG; sc[NT - 1][3] = NEG; }
  sc[NT - 1][0] = sc[NT - 1][1] = NEG;
  uint32_t pp[NT][2]; float inv[2];
#pragma unroll
  for (int hh = 0; hh < 2; hh++) {
    float m = NEG, l = 0.f;
#pragma unroll
    for (int n = 0; n < NT; n++) m = fmaxf(m, fmaxf(sc[n][2 * hh], sc[n][2 * hh + 1]));
    m = fmaxf(m, __shfl_xor_sync(~0u, m, 1)); m = fmaxf(m, __shfl_xor_sync(~0u, m, 2));
#pragma unroll
    for (int n = 0; n < NT; n++) { const float x = ex2((sc[n][2 * hh] - m) * k2), y = ex2((sc[n][2 * hh + 1] - m) * k2); l += x + y; pp[n][hh] = pack2(x, y); }
    l += __shfl_xor_sync(~0u, l, 1); l += __shfl_xor_sync(~0u, l, 2);
    inv[hh] = 1.f / l;
  }
#pragma unroll
  for (int u = 0; u < 3; u++) {
    float o[8][4] = {};
    const uint32_t kv = base[u] + 16384 + seg * KV_BYTES;
#pragma unroll
    for (int n = 0; n < 8; n += 2) {
      const uint2 vm = lds64(kv + KV_VM + n * 128 + lane * 8);
      mma8(o[n], pp[0][0], pp[0][1], vm.x);
      mma8(o[n + 1], pp[0][0], pp[0][1], vm.y);
#pragma unroll
      for (int t = 0; t <= HALF; t++) {
        const uint4 vb = lds128(kv + KV_V + n * 512 + t * 512 + lane * 16);
        mma16(o[n], pp[1 + 2 * t][0], pp[1 + 2 * t][1], pp[2 + 2 * t][0], pp[2 + 2 * t][1], vb.x, vb.y);
        mma16(o[n + 1], pp[1 + 2 * t][0], pp[1 + 2 * t][1], pp[2 + 2 * t][0], pp[2 + 2 * t][1], vb.z, vb.w);
      }
    }
#pragma unroll
    for (int n = 0; n < 8; n += 2)
      stsm4(base[u] + qrow + (((n + (lane >> 4)) ^ l7) << 4), pack2(o[n][0] * inv[0], o[n][1] * inv[0]), pack2(o[n][2] * inv[1], o[n][3] * inv[1]),
            pack2(o[n + 1][0] * inv[0], o[n + 1][1] * inv[0]), pack2(o[n + 1][2] * inv[1], o[n + 1][3] * inv[1]));
    fence_async();
    __syncwarp();
    if (lane == 0) mbar_arrive(done + 8 * (nd & 7));
    nd++;
  }
}

template <int NG>
__device__ __forceinline__ void fin_item(uint32_t sb, uint32_t bars, int& st, uint32_t& ph, uint32_t scratch, int b, int idx) {
  const int warp = threadIdx.x >> 5, lane = threadIdx.x & 31;
  float4* x = g_x + ((b * 16 + idx * NG) * 40 + warp * 5) * 32 + lane;
  float4 v[NG][5];
#pragma unroll
  for (int r0 = 0; r0 < NG; r0 += 2) {
    mbar_wait(bars + 8 * st, ph);
#pragma unroll
    for (int r = r0; r < r0 + 2 && r < NG; r++)
#pragma unroll
      for (int i = 0; i < 5; i++) v[r][i] = lds128f(sb + st * OP_STAGE_BYTES + (((r - r0) * 40 + warp * 5 + i) * 32 + lane) * 16);
    __syncwarp();
    if (lane == 0) mbar_arrive(bars + 8 * (OP_STAGES + st));
    if (++st == OP_STAGES) { st = 0; ph ^= 1; }
  }
  for (int k0 = 0; k0 < op_split(b); k0 += 4 / NG) {
    mbar_wait(bars + 8 * st, ph);
#pragma unroll
    for (int q4 = 0; q4 < 4; q4++)
#pragma unroll
      for (int i = 0; i < 5; i++) {
        const uint2 q = lds64(sb + st * OP_STAGE_BYTES + ((q4 * 40 + warp * 5 + i) * 32 + lane) * 8);
        float4& t = v[q4 % NG][i];
        t.x += bf_lo(q.x); t.y += bf_hi(q.x); t.z += bf_lo(q.y); t.w += bf_hi(q.y);
      }
    __syncwarp();
    if (lane == 0) mbar_arrive(bars + 8 * (OP_STAGES + st));
    if (++st == OP_STAGES) { st = 0; ph ^= 1; }
  }
#pragma unroll
  for (int r = 0; r < NG; r++)
#pragma unroll
    for (int i = 0; i < 5; i++) x[(r * 40 + i) * 32] = v[r][i];
  ln_rows<NG>(v, scratch);
#pragma unroll
  for (int i = 0; i < 5; i++) {
    const int u = warp * 5 + i;
    uint32_t* xn = g_xn + ((b * 10 + (u >> 2)) * 16 + idx * NG) * 256 + (u & 3) * 64 + lane;
#pragma unroll
    for (int r = 0; r < NG; r++) { xn[r * 256] = pack2(v[r][i].x, v[r][i].y); xn[r * 256 + 32] = pack2(v[r][i].z, v[r][i].w); }
  }
}

__global__ void __launch_bounds__(384, 1) post_kernel(const __grid_constant__ PostParams p) {
  extern __shared__ uint8_t smem_raw[];
  const uint32_t sb = (s2u(smem_raw) + 1023) & ~1023u, bars = sb + OP_STAGES * OP_STAGE_BYTES;
  const uint32_t bIF = bars + 64, bIE = bars + 96, done = bars + 128, bGo = bars + 192, slots = bars + 208, scratch = bars + 256;
  const int warp = __shfl_sync(~0u, threadIdx.x >> 5, 0), lane = threadIdx.x & 31;
  TRACE(0);
  pdl_launch();
  if (threadIdx.x == 0) {
    for (int i = 0; i < 4; i++) {
      mbar_init(bars + 8 * i, 1); mbar_init(bars + 8 * (OP_STAGES + i), 8);
      mbar_init(bIF + 8 * i, 1); mbar_init(bIE + 8 * i, 2); mbar_init(done + 8 * i, 8); mbar_init(done + 32 + 8 * i, 8);
    }
    mbar_init(bGo, 1);
    fence_async();
  }
  __syncthreads();
  if (warp >= 8) {
    asm volatile("setmaxnreg.dec.sync.aligned.u32 56;");
    if (warp == 9) {
      const int b = lane & 15;
      for (int n = 0;; n++) {
        if (n > 0) mbar_wait(bGo, (n - 1) & 1);
        mbar_wait(bIE + 8 * (n & 3), ((n >> 2) & 1) ^ 1);
        int code, spin = 0, ticket = 0;
        if (lane == 0) ticket = atomicAdd(g_sync + SY_T, 1);
        for (;;) {
          const uint4 hd = ldg_strong128(g_sync + b * 8), pr = ldg_strong128(g_sync + b * 8 + 4);
          const uint32_t hv[4] = {hd.x, hd.y, hd.z, hd.w}, pv[4] = {pr.x, pr.y, pr.z, pr.w};
          const uint32_t chain_done = __ballot_sync(~0u, (pr.x & 0xffff) >= 96);
          int left[4], avail[4], rdy = 0, claimed = 0, upstream = 0;
#pragma unroll
          for (int t = 0; t < 4; t++) {
            const int cnt = lane < 16 ? item_count(t, b) : 0;
            left[t] = max(cnt - (int)hv[t], 0);
            claimed += cnt - left[t];
            const bool ready = (pv[t] & 0xffff) >= item_need(t, b);
            rdy |= ready << t;
            bool ok = ready || (t == IT_ATT ? pr.x >= 0x10000 : !upstream || (t == IT_OP && (chain_done >> 15 & 1)));
            if (t == IT_BQ && (chain_done >> 12 & 9) == 1) ok = false;
            avail[t] = ok ? left[t] : 0;
            upstream |= __any_sync(~0u, left[t] > 0);
          }
          if (!upstream) { code = -1; break; }
          int rank = max(__shfl_sync(~0u, ticket, 0) - __reduce_add_sync(~0u, claimed), 0), type = -1, mine = 0;
#pragma unroll
          for (int c = 0; c < 7; c++) {
            const int t = c == 0 || c == 4 ? IT_FIN : c == 1 || c == 6 ? IT_ATT : c == 2 ? IT_OP : IT_BQ;
            int a = c == 1 || c == 2 || ((rdy >> t & 1) == (c < 4)) ? avail[t] : 0;
            if (c == 6) a = b < QA_END && !(rdy & 1) && ((chain_done << 1 | 1) >> b & 1) ? left[t] : 0;
            const int tot = __reduce_add_sync(~0u, a);
            if (type < 0) { if (rank < tot) { type = t; mine = a; } else rank -= tot; }
          }
          if (type >= 0) {
#pragma unroll
            for (int o = 1; o < 16; o <<= 1) { const int y = __shfl_up_sync(~0u, mine, o); if (lane >= o) mine += y; }
            const int blk = __ffs(__ballot_sync(~0u, mine > rank)) - 1;
            const int early = !(__shfl_sync(~0u, rdy, blk) >> type & 1);
            uint32_t idx = 0;
            if (lane == 0) { idx = atomicAdd(g_sync + blk * 8 + type, 1); ld_acquire(g_sync + blk * 8 + 4 + type); }
            idx = __shfl_sync(~0u, idx, 0);
            if (idx < item_count(type, blk)) { code = (chain_done >> 15 & 1) << 22 | (chain_done >> 13 & 1) << 21 | early << 20 | type << 16 | blk << 8 | idx; break; }
          } else {
            __nanosleep(50);
          }
          spin_guard(spin);
        }
        if (lane == 0) {
          fence_async_global();
          sts32(slots + 4 * (n & 3), code);
          mbar_arrive(bIF + 8 * (n & 3));
        }
        __syncwarp();
        if (code < 0) break;
      }
    } else if (warp == 8 && lane == 0) {
      int st = 0; uint32_t ph = 1;
      uint32_t next = clk32(), gap = 0;
      auto pace = [&](uint32_t kb) {
        if (gap) { uint32_t now; do now = clk32(); while ((int)(now - next) < 0); next = now + kb * gap; }
      };
      auto box = [&](uint32_t dst, const CUtensorMap* m, int c0, int c1, uint32_t bar, uint32_t kb) {
        pace(kb);
        if (kb == 16 && EF) tma_load_last(dst, m, c0, c1, bar); else tma_load(dst, m, c0, c1, bar);
      };
      auto flat = [&](uint32_t dst, const void* src, uint32_t kb, uint32_t piece, uint32_t bar, bool last = false) {
        if (!gap) piece = kb;
        for (uint32_t o = 0; o < kb; o += piece) {
          pace(piece);
          if (last && EF) bulk_load_last(dst + o * 1024, (const uint8_t*)src + o * 1024, piece * 1024, bar);
          else bulk_load(dst + o * 1024, (const uint8_t*)src + o * 1024, piece * 1024, bar);
        }
      };
      for (int n = 0;; n++) {
        mbar_wait(bIF + 8 * (n & 3), (n >> 2) & 1);
        const int code = (int)lds32(slots + 4 * (n & 3));
        if (code < 0) break;
        const int type = (code >> 16) & 15, b = (code >> 8) & 255, idx = code & 255;
        mbar_arrive(bIE + 8 * (n & 3));
        gap = code >> 22 & 1 ? 0 : p.gap;
        const int nst = item_stages(type, b), ng = 16 / fin_items(b);
        const int kb0 = type == IT_OP ? (idx >> 1) * nst : 0;
        const bool half = type == IT_BQ && bq_items(b) == 12;
        const int col = type == IT_ATT ? idx * 192 : type == IT_OP ? (idx & 1) * 320 : idx * (half ? 160 : 320);
        const int pre = !(code >> 20 & 1) ? 0 : type == IT_ATT ? 2 : type == IT_FIN ? (ng + 1) / 2 : OP_STAGES - 1;
        const bool qa = type == IT_ATT && b < QA_END;
        if (qa) {
          for (int kb = 0; kb < 10; kb++) {
            const uint32_t dst = sb + st * OP_STAGE_BYTES, bar = bars + 8 * st;
            mbar_wait(bars + 8 * (OP_STAGES + st), ph);
            mbar_expect(bar, 40960);
            flat(dst, g_xn + (b * 10 + kb) * 4096, 16, 8, bar);
            for (int i = 0; i < 3; i++) box(dst + 16384 + i * 8192, &p.wq, col + i * 64, kb * 64, bar, 8);
            if (++st == OP_STAGES) { st = 0; ph ^= 1; }
          }
        } else if (type == IT_ATT) {
          wait_count(g_sync + SY_Q, p.nq);
          fence_async_global();
        }
        int sta = st;
        for (int kb = 0; kb < nst; kb++) {
          const uint32_t dst = sb + st * OP_STAGE_BYTES, bar = bars + 8 * st;
          mbar_wait(bars + 8 * (OP_STAGES + st), ph);
          if (type == IT_ATT) {
            mbar_expect(bar, qa ? 40960 : OP_STAGE_BYTES);
            if (!qa) box(dst, &p.q, col + kb * 64, b * 128, bar, 16);
          } else if (type == IT_FIN) {
            const int bytes = ng == 1 && kb == 0 ? 20480 : 40960;
            mbar_expect(bar, bytes);
            if (kb < (ng + 1) / 2) flat(dst, g_x + (b * 16 + idx * ng + 2 * kb) * 1280, bytes >> 10, 10, bar);
          } else {
            const int nb = half ? 3 : 5;
            mbar_expect(bar, 16384 + nb * 8192);
            for (int i = 0; i < nb; i++) box(dst + 16384 + i * 8192, type == IT_OP ? &p.wo : &p.wb, col + i * 64, (kb0 + kb) * 64, bar, 8);
          }
          if (++st == OP_STAGES) { st = 0; ph ^= 1; }
          if (kb < pre) continue;
          if (kb == pre) {
            if (pre) { wait_count(g_sync + b * 8 + 4 + type, item_need(type, b)); fence_async_global(); }
            if ((type == IT_ATT || type == IT_FIN) && !(code >> 21)) mbar_arrive(bGo);
          }
          for (int k = kb == pre ? 0 : kb; k <= kb; k++) {
            const uint32_t da = sb + sta * OP_STAGE_BYTES, ba = bars + 8 * sta;
            if (type == IT_ATT) {
              flat(da + 16384, g_kv + (size_t)((idx * 3 + k) * NSEG + (b * 4 & KVM)) * KV_BYTES, 40, 10, ba, true);
            } else if (type == IT_OP) {
              box(da, &p.o, (kb0 + k) * 64, b * 128, ba, 16);
            } else if (type == IT_BQ) {
              flat(da, g_xn + (b * 10 + k) * 4096, 16, 8, ba);
            } else if (k >= (ng + 1) / 2) {
              const int k0 = (k - (ng + 1) / 2) * (4 / ng);
              for (int i = 0; i < 4 / ng; i++) flat(da + i * ng * 10240, g_part + ((b * 16 + k0 + i) * 16 + idx * ng) * 1280, ng * 10, 10, ba, true);
            }
            if (++sta == OP_STAGES) sta = 0;
          }
        }
      }
    } else if (warp == 10 && lane == 0) {
      int st = 0, nd = 0;
      for (int n = 0;; n++) {
        mbar_wait(bIF + 8 * (n & 3), (n >> 2) & 1);
        const int code = (int)lds32(slots + 4 * (n & 3));
        if (code < 0) break;
        const int type = (code >> 16) & 15, b = (code >> 8) & 255, idx = code & 255;
        if (type == IT_ATT) {
          if (b < QA_END) st = (st + 10) & (OP_STAGES - 1);
          for (int u = 0; u < 3; u++) {
            mbar_wait(done + 8 * (nd & 7), (nd >> 3) & 1);
            nd++;
            tma_store(&p.o, sb + st * OP_STAGE_BYTES, idx * 192 + u * 64, b * 128);
            bulk_commit();
            bulk_wait_read<0>();
            asm volatile("mbarrier.arrive.shared::cta.b64 _, [%0], 8;" :: "r"(bars + 8 * (OP_STAGES + st)) : "memory");
            st = (st + 1) & (OP_STAGES - 1);
          }
          bulk_wait<0>();
          fence_async_global();
        } else {
          mbar_wait(done + 8 * (nd & 7), (nd >> 3) & 1);
          nd++;
          st = (st + item_stages(type, b)) & (OP_STAGES - 1);
        }
        if (type != IT_BQ) red_release(g_sync + b * 8 + 5 + type, 1);
        mbar_arrive(bIE + 8 * (n & 3));
      }
    }
  } else {
    asm volatile("setmaxnreg.inc.sync.aligned.u32 224;");
    const int wg = warp >> 2, g = lane >> 2, c = lane & 3;
    int st = 0, nd = 0; uint32_t ph = 0;
#pragma unroll 1
    for (int n = 0;; n++) {
      mbar_wait(bIF + 8 * (n & 3), (n >> 2) & 1);
      const int code = __shfl_sync(~0u, (int)lds32(slots + 4 * (n & 3)), 0);
      if (code < 0) { TRACE(2); break; }
      const int type = (code >> 16) & 15, b = (code >> 8) & 255, idx = code & 255;
      ITEM(code & 0xfffff, 0);
      if (type == IT_ATT) {
        if (b < QA_END) {
          float q[96] = {};
          reg_fence<96>(q);
          int prev = 0;
#pragma unroll 1
          for (int kb = 0; kb < 10; kb++) {
            mbar_wait(bars + 8 * st, ph);
            const uint32_t base = sb + st * OP_STAGE_BYTES;
            const uint64_t da = mkdesc(base + wg * 8192, 128, 1024, 0), db = mkdesc(base + 16384, 8192, 1024, 1);
            wg_fence();
#pragma unroll
            for (int kk = 0; kk < 4; kk++) wg_ss192_01(q, da + kk * 16, db + kk * 128, (kb | kk) != 0);
            wg_commit();
            if (kb > 0) { wg_wait<1>(); if (lane == 0) mbar_arrive(bars + 8 * (OP_STAGES + prev)); }
            prev = st;
            if (++st == OP_STAGES) { st = 0; ph ^= 1; }
          }
          wg_wait<0>();
          reg_fence<96>(q);
          if (lane == 0) mbar_arrive(bars + 8 * (OP_STAGES + prev));
          if (wg == 0) attn_a_warp<0, true>(sb, bars, st, ph, done, nd, q); else attn_a_warp<1, true>(sb, bars, st, ph, done, nd, q);
        } else {
          if (wg == 0) attn_a_warp<0, false>(sb, bars, st, ph, done, nd, nullptr); else attn_a_warp<1, false>(sb, bars, st, ph, done, nd, nullptr);
        }
      } else {
        if (type == IT_FIN) {
          if (fin_items(b) == 4) fin_item<4>(sb, bars, st, ph, scratch, b, idx);
          else if (fin_items(b) == 8) fin_item<2>(sb, bars, st, ph, scratch, b, idx);
          else fin_item<1>(sb, bars, st, ph, scratch, b, idx);
        } else {
          float d[160] = {};
          reg_fence<160>(d);
          const int nkb = item_stages(type, b);
          const bool half = type == IT_BQ && bq_items(b) == 12;
          int prev = 0;
          auto mainloop = [&](auto H) {
#pragma unroll 1
            for (int kb = 0; kb < nkb; kb++) {
              mbar_wait(bars + 8 * st, ph);
              const uint32_t base = sb + st * OP_STAGE_BYTES;
              const uint64_t da = mkdesc(base + wg * 8192, 128, 1024, type == IT_OP), db = mkdesc(base + 16384, 8192, 1024, 1);
              const int ka = type == IT_OP ? 2 : 16;
              wg_fence();
#pragma unroll
              for (int kk = 0; kk < 4; kk++) {
                if (H.value) {
                  wg_ss160_01(d, da + kk * ka, db + kk * 128, (kb | kk) != 0);
                } else {
                  wg_ss192_01(d, da + kk * ka, db + kk * 128, (kb | kk) != 0);
                  wg_ss128_01(d + 96, da + kk * ka, db + kk * 128 + 3 * 512, (kb | kk) != 0);
                }
              }
              wg_commit();
              if (kb == nkb - 3 && threadIdx.x == 0 && !(code >> 21)) mbar_arrive(bGo);
              if (kb > 0) { wg_wait<1>(); if (lane == 0) mbar_arrive(bars + 8 * (OP_STAGES + prev)); }
              prev = st;
              if (++st == OP_STAGES) { st = 0; ph ^= 1; }
            }
            wg_wait<0>();
          };
          if (half) mainloop(Int<1>()); else mainloop(Int<0>());
          reg_fence<160>(d);
          if (lane == 0) mbar_arrive(bars + 8 * (OP_STAGES + prev));
          if (type == IT_OP) {
            uint2* dst = g_part + (((b * 16 + (idx >> 1)) * 16 + warp * 2) * 40 + (idx & 1) * 20) * 32 + lane;
#pragma unroll
            for (int u = 0; u < 20; u++) {
              dst[u * 32] = make_uint2(pack2(d[8 * u], d[8 * u + 1]), pack2(d[8 * u + 4], d[8 * u + 5]));
              dst[(40 + u) * 32] = make_uint2(pack2(d[8 * u + 2], d[8 * u + 3]), pack2(d[8 * u + 6], d[8 * u + 7]));
            }
          } else {
            const int row = b * 128 + warp * 16 + g;
            const int h0 = idx * (half ? 8 : 16);
            const float sc = h0 < 32 ? 0.22360679775f * 1.44269504089f : 1.f;
            const bool lo = c < 2;
            uint32_t* da = g_bqkv + (h0 * 256 + (row >> 3)) * 96 + lane;
            uint32_t* db = da + 256 * 96 + (lo ? 2 : -2);
#pragma unroll
            for (int r = 0; r < 2; r++) {
              const uint32_t pad = !(c & 1) && (h0 >= 64 || (h0 >= 32 && (row & 1) && poly_group((row >> 3) + r))) ? 0x00003f80u : 0u;
#pragma unroll
              for (int q = 0; q < 8; q++) {
                if (q >= 4 && half) break;
                uint32_t w[5];
#pragma unroll
                for (int i = 0; i < 5; i++) w[i] = pack2(d[20 * q + 4 * i + 2 * r] * sc, d[20 * q + 4 * i + 2 * r + 1] * sc);
                const int o = q * 2 * 256 * 96 + r * 96;
                da[o] = w[0]; da[o + 32] = w[1]; da[o + 64] = lo ? w[2] : pad;
                db[o] = lo ? w[3] : w[2]; db[o + 32] = lo ? w[4] : w[3]; db[o + 64] = lo ? pad : w[4];
              }
            }
          }
        }
        __syncwarp();
        if (lane == 0) mbar_arrive(done + 8 * (nd & 7));
        nd++;
      }
      if (code >> 21 && threadIdx.x == 128) mbar_arrive(bGo);
      ITEM(code & 0xfffff, 1);
    }
  }
}

constexpr int AB_SMEM = 1024 + 98304 + 51200 + 4 * 16384 + 256;
#define AB_N 32
#define AB_WG 4
constexpr int AB_T = AB_WG * 128, AB_PASS = 8 / AB_WG;
__device__ __forceinline__ float ex2_poly(float t) {
  const uint32_t r = __float_as_uint(t) & 0xffff8000u;
  const float f = t - __uint_as_float(r);
  const float p = fmaf(fmaf(fmaf(-5.869912678e-38f, f, -1.700740250e-37f), f, -5.234869734e-37f), f, -7.522601252e-37f);
  uint32_t y;
  asm("mad.lo.u32 %0, %1, 256, %2;" : "=r"(y) : "r"(r), "r"(__float_as_uint(p)));
  return __uint_as_float(y);
}
__device__ __forceinline__ float sq2(uint32_t w) { const float a = bf_lo(w), b = bf_hi(w); return fmaf(a, a, b * b); }

__device__ __forceinline__ void attn_b_store(const float* o, int h, int row0, int lane) {
  const int g = lane >> 2, c = lane & 3;
  const float i0 = 1.f / __shfl_sync(~0u, o[8], (lane & ~3) | 2), i1 = 1.f / __shfl_sync(~0u, o[10], (lane & ~3) | 2);
#pragma unroll
  for (int jj = 0; jj < 3; jj++) {
    if (jj < 2 || c < 2) {
      const int col = h * 20 + 8 * jj + 2 * c;
      uint32_t* dst = g_of + (((row0 >> 7) * 10 + (col >> 6)) * 16 + (row0 >> 3 & 15)) * 256 + (col >> 3 & 7) * 32 + g * 4 + (col >> 1 & 3);
      dst[0] = pack2(o[4 * jj] * i0, o[4 * jj + 1] * i0);
      dst[256] = pack2(o[4 * jj + 2] * i1, o[4 * jj + 3] * i1);
    }
  }
}

__device__ __forceinline__ void attn_b_qk(float* s, uint32_t q0, uint32_t q1, uint32_t q2, uint32_t q3, uint32_t q4, uint32_t q5, uint32_t z0, uint32_t z1,
                                          uint64_t dk, uint64_t dk2) {
  wg_rs32_00(s, q0, q1, q2, q3, dk, 0);
  wg_rs32_00(s, q4, q5, z0, z1, dk2, 1);
}

struct AbParams { Weights next; uint32_t* done; uint32_t* out; };
__global__ void __launch_bounds__(AB_T + 32, 1) attn_b_kernel(const __grid_constant__ AbParams p) {
  extern __shared__ uint8_t smem_raw[];
  const uint32_t sb = (s2u(smem_raw) + 1023) & ~1023u, sK = sb, sV = sb + 98304, bars = sV + 51200 + 4 * 16384;
  const uint32_t bF = bars + 64, bW = bars + 72, bA = bars + 80, bE = bars + 128, smax = bars + 176;
  auto ring = [&](int i) { return i < 2 ? sK + 51200 + i * 16384 : sV + 51200 + (i - 2) * 16384; };
  const int warp = __shfl_sync(~0u, threadIdx.x >> 5, 0), lane = threadIdx.x & 31;
  const int h = blockIdx.x >> 2, quarter = blockIdx.x & 3;
  TRACE(0);
  pdl_launch();
  pdl_wait();
  if (blockIdx.x < NSLOT) for (int i = threadIdx.x; i < 512; i += AB_T + 32) reinterpret_cast<uint4*>(pool_at(blockIdx.x * 8192))[i] = make_uint4(0, 0, 0, 0);
  if (blockIdx.x == 31) for (int i = threadIdx.x; i < SY_N; i += AB_T + 32) g_sync[i] = 0;
  if (threadIdx.x == 0) {
    for (int i = 0; i < 22; i++) mbar_init(bars + 8 * i, i == 8 ? AB_T / 32 : i >= 16 ? 8 : 1);
    sts64(smax, 0, 0);
    fence_async();
    const uint8_t* gk = reinterpret_cast<const uint8_t*>(g_bqkv + (32 + h) * 256 * 96);
    const uint8_t* gv = reinterpret_cast<const uint8_t*>(g_bqkv + (64 + h) * 256 * 96);
    for (int i = 0; i < 8; i++) {
      mbar_expect(bars + 8 * i, 24576);
      if (EF) { bulk_load_last(sK + i * 12288, gk + i * 12288, 12288, bars + 8 * i); bulk_load_last(sV + i * 12288, gv + i * 12288, 12288, bars + 8 * i); }
      else { bulk_load(sK + i * 12288, gk + i * 12288, 12288, bars + 8 * i); bulk_load(sV + i * 12288, gv + i * 12288, 12288, bars + 8 * i); }
    }
  }
  __syncthreads();
  const int blk = quarter * 4 + (h >> 3), cg = h & 7;
  auto unsafe = [&]() { const float2 m = lds64f(smax); return !(m.x * m.y <= 10000.f); };
  if (warp == AB_T / 32) {
    auto load_w = [&]() {
      mbar_expect(bW, 102400);
      for (int i = 0; i < 4; i++) bulk_load((i < 2 ? sK : sV) + (i & 1) * 25600, g_wb + cg * 6400 + i * 1600, 25600, bW);
    };
    if (p.next.w[0] && lane == 0) {
      mbar_wait(bars + 56, 0);
      for (int i = 0; i < AB_PF; i++) { const uint32_t t0 = clk32(); while (clk32() - t0 < (i ? AB_PFD : AB_PF0)) __nanosleep(200); prefetch_weights(p.next, i); }
    }
    __syncwarp();
    mbar_wait(bF, 0);
    const bool redo = unsafe();
    if (!redo && lane == 0) load_w();
    __syncwarp();
    bar_sync(1, AB_T + 32);
    if (lane == 0) {
      ABT(!!p.out, 1);
      red_release(p.done + quarter * 32, 1);
      ABT(!!p.out, 2);
      if (redo) load_w();
      wait_count(p.done + quarter * 32, 32);
      fence_async_global();
      ABT(!!p.out, 3);
      for (int kb = 0; kb < 10; kb++) {
        const int i = kb < 6 ? kb : kb - 6;
        if (kb >= 6) mbar_wait(bE + 8 * i, 0);
        mbar_expect(bA + 8 * i, 16384);
        bulk_load(ring(i), g_of + (blk * 10 + kb) * 4096, 16384, bA + 8 * i);
      }
    }
    return;
  }
  float qmax = 0.f;
  constexpr int NT = SEQ / AB_N, PER = 256 / AB_N;
#pragma unroll 1
  for (int pass = 0; pass < AB_PASS; pass++) {
    const int row0 = quarter * 512 + ((warp >> 2) * AB_PASS + pass) * 64 + (warp & 3) * 16;
    const uint32_t* gq = g_bqkv + (h * 256 + (row0 >> 3)) * 96 + lane;
    const uint32_t q0 = gq[0], q1 = gq[96], q2 = gq[32], q3 = gq[128];
    uint32_t q4 = gq[64], q5 = gq[160];
    const uint32_t z0 = gq[64 + 3 - (lane & 3)], z1 = gq[160 + 3 - (lane & 3)];
    {
      float n0 = sq2(q0) + sq2(q2) + sq2(q4), n1 = sq2(q1) + sq2(q3) + sq2(q5);
      n0 += __shfl_xor_sync(~0u, n0, 1); n1 += __shfl_xor_sync(~0u, n1, 1);
      n0 += __shfl_xor_sync(~0u, n0, 2); n1 += __shfl_xor_sync(~0u, n1, 2);
      qmax = (n0 > qmax || n0 != n0) ? n0 : qmax;
      qmax = (n1 > qmax || n1 != n1) ? n1 : qmax;
    }
    if (pass == AB_PASS - 1) {
      float kmax = 0.f;
#pragma unroll
      for (int i = 0; i < SEQ / AB_T; i++) {
        const int key = threadIdx.x + AB_T * i;
        const uint32_t a = sK + (key >> 3) * 384 + (key & 7) * 16;
        const uint4 x = lds128(a), y = lds128(a + 128);
        const uint2 z = lds64(a + 256);
        const float n = ((sq2(x.x) + sq2(x.y)) + (sq2(x.z) + sq2(x.w))) + ((sq2(y.x) + sq2(y.y)) + (sq2(y.z) + sq2(y.w))) + (sq2(z.x) + sq2(z.y));
        kmax = (n > kmax || n != n) ? n : kmax;
      }
      const uint32_t kb = __reduce_max_sync(~0u, __float_as_uint(kmax) & 0x7fffffffu), qb = __reduce_max_sync(~0u, __float_as_uint(qmax) & 0x7fffffffu);
      if (lane < 2) asm volatile("red.shared.max.u32 [%0], %1;" :: "r"(smax + 4 * lane), "r"(lane ? kb : qb) : "memory");
      __syncwarp();
    }
    if ((lane & 3) == 2) { q4 = 0x43BCu; q5 = 0x43BCu; }
    float o[12];
    uint64_t dk = mkdesc(sK, 128, 384, 0), dk2 = mkdesc(sK + 256, 0, 384, 0), dv = mkdesc(sV, 384, 128, 0);
    float sa[AB_N / 2], sb2[AB_N / 2];
    uint32_t pa[AB_N / 4], pb[AB_N / 4];
    if (pass == 0) mbar_wait(bars, 0);
    wg_fence();
    attn_b_qk(sa, q0, q1, q2, q3, q4, q5, z0, z1, dk, dk2);
    wg_commit();
    attn_b_qk(sb2, q0, q1, q2, q3, q4, q5, z0, z1, dk + AB_N * 3, dk2 + AB_N * 3);
    wg_commit();
#pragma unroll 1
    for (int kt = 0; kt < NT; kt += 2) {
      const int nx = kt + 2 < NT ? kt + 2 : 0;
      if (pass == 0 && (nx & (PER - 1)) == 0) mbar_wait(bars + 8 * (nx / PER), 0);
      const uint64_t nk = dk + nx * (AB_N * 3), nk2 = dk2 + nx * (AB_N * 3);
      wg_wait<1>();
      if (pass == AB_PASS - 1 && kt == NT * 5 / 8 + 2 && lane == 0) mbar_arrive(bF);
      reg_fence<AB_N / 2>(sa);
#pragma unroll
      for (int i = 0; i < AB_N / 4; i++) pa[i] = pack2(ex2(sa[2 * i]), poly_group(i >> 1) ? ex2_poly(sa[2 * i + 1]) : ex2(sa[2 * i + 1]));
      wg_fence();
#pragma unroll
      for (int kk = 0; kk < AB_N / 16; kk++) wg_rs24_01(o, pa[4 * kk], pa[4 * kk + 1], pa[4 * kk + 2], pa[4 * kk + 3], dv + kk * 48, kk | kt);
      attn_b_qk(sa, q0, q1, q2, q3, q4, q5, z0, z1, nk, nk2);
      wg_commit();
      wg_wait<1>();
      reg_fence<AB_N / 2>(sb2);
#pragma unroll
      for (int i = 0; i < AB_N / 4; i++) pb[i] = pack2(ex2(sb2[2 * i]), poly_group((i >> 1) + AB_N / 8) ? ex2_poly(sb2[2 * i + 1]) : ex2(sb2[2 * i + 1]));
      wg_fence();
#pragma unroll
      for (int kk = 0; kk < AB_N / 16; kk++) wg_rs24_01(o, pb[4 * kk], pb[4 * kk + 1], pb[4 * kk + 2], pb[4 * kk + 3], dv + AB_N * 3 + kk * 48, 1);
      attn_b_qk(sb2, q0, q1, q2, q3, q4, q5, z0, z1, nk + AB_N * 3, nk2 + AB_N * 3);
      wg_commit();
      dv += AB_N * 6;
    }
    wg_wait<0>();
    reg_fence<12>(o); reg_fence<AB_N / 2>(sa); reg_fence<AB_N / 2>(sb2);
    attn_b_store(o, h, row0, lane);
  }
  mbar_wait(bF, 0);
  if (unsafe())
#pragma unroll 1
  for (int pass = 0; pass < AB_PASS; pass++) {
    const int row0 = quarter * 512 + ((warp >> 2) * AB_PASS + pass) * 64 + (warp & 3) * 16;
    const uint32_t* gq = g_bqkv + (h * 256 + (row0 >> 3)) * 96 + lane;
    const uint32_t q0 = gq[0], q1 = gq[96], q2 = gq[32], q3 = gq[128], q4 = gq[64], q5 = gq[160];
    float o[12];
#pragma unroll
    for (int i = 0; i < 12; i++) o[i] = 0.f;
    float m0 = -INFINITY, m1 = -INFINITY;
#pragma unroll 1
    for (int kt = 0; kt < 32; kt++) {
      float s[32];
      const uint64_t dk = mkdesc(sK + kt * 3072, 128, 384, 0), dk2 = mkdesc(sK + kt * 3072 + 256, 0, 384, 0);
      wg_fence();
      wg_rs64_00(s, q0, q1, q2, q3, dk, 0);
      wg_rs64_00(s, q4, q5, 0, 0, dk2, 1);
      wg_commit();
      wg_wait<0>();
      reg_fence<32>(s); reg_fence<12>(o);
      float n0 = m0, n1 = m1;
#pragma unroll
      for (int jj = 0; jj < 8; jj++) { n0 = fmaxf(n0, fmaxf(s[4 * jj], s[4 * jj + 1])); n1 = fmaxf(n1, fmaxf(s[4 * jj + 2], s[4 * jj + 3])); }
      n0 = fmaxf(n0, __shfl_xor_sync(~0u, n0, 1)); n0 = fmaxf(n0, __shfl_xor_sync(~0u, n0, 2));
      n1 = fmaxf(n1, __shfl_xor_sync(~0u, n1, 1)); n1 = fmaxf(n1, __shfl_xor_sync(~0u, n1, 2));
      const float r0 = ex2(m0 - n0), r1 = ex2(m1 - n1);
      m0 = n0; m1 = n1;
#pragma unroll
      for (int jj = 0; jj < 3; jj++) { o[4 * jj] *= r0; o[4 * jj + 1] *= r0; o[4 * jj + 2] *= r1; o[4 * jj + 3] *= r1; }
      uint32_t pp[16];
#pragma unroll
      for (int jj = 0; jj < 8; jj++) {
        pp[2 * jj] = pack2(ex2(s[4 * jj] - m0), ex2(s[4 * jj + 1] - m0));
        pp[2 * jj + 1] = pack2(ex2(s[4 * jj + 2] - m1), ex2(s[4 * jj + 3] - m1));
      }
      const uint64_t dv = mkdesc(sV + kt * 3072, 384, 128, 0);
      wg_fence();
#pragma unroll
      for (int kk = 0; kk < 4; kk++) wg_rs24_01(o, pp[4 * kk], pp[4 * kk + 1], pp[4 * kk + 2], pp[4 * kk + 3], dv + kk * 48, 1);
      wg_commit();
    }
    wg_wait<0>();
    reg_fence<12>(o);
    attn_b_store(o, h, row0, lane);
  }
  ABT(!!p.out, 0);
  bar_arrive(1, AB_T + 32);
  if (warp >= 8) return;
  const int g = lane >> 2, c = lane & 3;
  float d[40];
  float4* x = g_x + ((blk * 16 + warp * 2) * 40 + cg * 5) * 32 + lane;
#pragma unroll
  for (int i = 0; i < 10; i++) {
    const int r = i / 5, u = i % 5;
    const float4 t = x[(r * 40 + u) * 32];
    d[8 * u + 2 * r] = t.x; d[8 * u + 2 * r + 1] = t.y; d[8 * u + 4 + 2 * r] = t.z; d[8 * u + 5 + 2 * r] = t.w;
  }
  mbar_wait(bW, 0);
  reg_fence<40>(d);
  ABT(!!p.out, 4);
#pragma unroll 1
  for (int kb = 0; kb < 10; kb++) {
    const int i = kb < 6 ? kb : kb - 6;
    mbar_wait(bA + 8 * i, kb >= 6);
    const uint64_t da = mkdesc(ring(i) + (warp >> 2) * 8192, 128, 1024, 0), db = mkdesc(kb < 5 ? sK + kb * 10240 : sV + (kb - 5) * 10240, 1280, 128, 0);
    wg_fence();
#pragma unroll
    for (int kk = 0; kk < 4; kk++) wg_ss80_01(d, da + kk * 16, db + kk * 160, 1);
    wg_commit();
    if (kb > 0 && kb < 5) { wg_wait<1>(); if (lane == 0) mbar_arrive(bE + 8 * (kb - 1)); }
  }
  wg_wait<0>();
  reg_fence<40>(d);
  ABT(!!p.out, 5);
  if (p.out) {
    uint32_t* out = p.out + (blk * 128 + warp * 16 + g) * (DM / 2) + cg * 40 + c;
#pragma unroll
    for (int i = 0; i < 20; i++) out[(i & 1) * 8 * (DM / 2) + (i >> 1) * 4] = pack2(d[2 * i], d[2 * i + 1]);
  } else {
    float2* stat = g_stat + blk * 1024 + warp * 16 + g;
    float mean[2], rs[2];
#pragma unroll
    for (int r = 0; r < 2; r++) {
      float t = 0.f, q = 0.f;
#pragma unroll
      for (int i = 0; i < 10; i++) t += d[4 * i + 2 * r] + d[4 * i + 2 * r + 1];
      t += __shfl_xor_sync(~0u, t, 1); t += __shfl_xor_sync(~0u, t, 2);
      t *= 1.f / 80;
#pragma unroll
      for (int i = 0; i < 10; i++) { const float a = d[4 * i + 2 * r] - t, b = d[4 * i + 2 * r + 1] - t; q += a * a + b * b; }
      q += __shfl_xor_sync(~0u, q, 1); q += __shfl_xor_sync(~0u, q, 2);
      if (c == r) asm volatile("st.relaxed.gpu.global.v2.b32 [%0], {%1, %2};" :: "l"(stat + cg * 128 + r * 8), "r"(__float_as_uint(t)), "r"(nz(__float_as_uint(q))) : "memory");
    }
#pragma unroll
    for (int i = 0; i < 10; i++) {
      const int r = i / 5, u = i % 5;
      x[(r * 40 + u) * 32] = make_float4(d[8 * u + 2 * r], d[8 * u + 2 * r + 1], d[8 * u + 4 + 2 * r], d[8 * u + 5 + 2 * r]);
    }
    ABT(0, 6);
    uint2 e[4];
    int n = 0;
    do {
#pragma unroll
      for (int i = 0; i < 4; i++)
        asm volatile("ld.relaxed.gpu.global.v2.b32 {%0, %1}, [%2];" : "=r"(e[i].x), "=r"(e[i].y) : "l"(stat + (2 * c + (i & 1)) * 128 + (i >> 1) * 8) : "memory");
      spin_guard(n);
    } while (__any_sync(~0u, min(min(e[0].y, e[1].y), min(e[2].y, e[3].y)) == 0));
#pragma unroll
    for (int r = 0; r < 2; r++) {
      const float m0 = __uint_as_float(e[2 * r].x), m1 = __uint_as_float(e[2 * r + 1].x);
      float t = m0 + m1;
      t += __shfl_xor_sync(~0u, t, 1); t += __shfl_xor_sync(~0u, t, 2);
      t *= 0.125f;
      float q = __uint_as_float(e[2 * r].y) + __uint_as_float(e[2 * r + 1].y) + 80.f * ((m0 - t) * (m0 - t) + (m1 - t) * (m1 - t));
      q += __shfl_xor_sync(~0u, q, 1); q += __shfl_xor_sync(~0u, q, 2);
      mean[r] = t; rs[r] = rsqrtf(q * (1.f / DM) + 1e-5f);
    }
    ABT(0, 7);
    uint32_t w[2][5][2];
#pragma unroll
    for (int i = 0; i < 20; i++) w[i & 1][i >> 2][i >> 1 & 1] = pack2((d[2 * i] - mean[i & 1]) * rs[i & 1], (d[2 * i + 1] - mean[i & 1]) * rs[i & 1]);
    ln_store(w, blk * 8 + warp, cg * 5);
  }
  ABT(!!p.out, 8);
  TRACE(2);
}

typedef CUresult (*EncodeFn)(CUtensorMap*, CUtensorMapDataType, cuuint32_t, void*, const cuuint64_t*, const cuuint64_t*,
                             const cuuint32_t*, const cuuint32_t*, CUtensorMapInterleave, CUtensorMapSwizzle,
                             CUtensorMapL2promotion, CUtensorMapFloatOOBfill);

void make_map(EncodeFn enc, CUtensorMap* m, const void* ptr, int cols, int rows, int box_rows, int box_cols = 64) {
  const cuuint64_t dims[2] = {(cuuint64_t)cols, (cuuint64_t)rows};
  const cuuint64_t strides[1] = {(cuuint64_t)cols * 2};
  const cuuint32_t box[2] = {(cuuint32_t)box_cols, (cuuint32_t)box_rows}, es[2] = {1, 1};
  enc(m, CU_TENSOR_MAP_DATA_TYPE_BFLOAT16, 2, const_cast<void*>(ptr), dims, strides, box, es, CU_TENSOR_MAP_INTERLEAVE_NONE,
      box_cols == 64 ? CU_TENSOR_MAP_SWIZZLE_128B : CU_TENSOR_MAP_SWIZZLE_64B, CU_TENSOR_MAP_L2_PROMOTION_L2_256B, CU_TENSOR_MAP_FLOAT_OOB_FILL_NONE);
}
template <class... KA, class... A>
void launch(void (*kern)(KA...), int grid, int block, int smem, int cluster, bool pdl, A... args) {
  cudaFuncSetAttribute(kern, cudaFuncAttributeMaxDynamicSharedMemorySize, smem);
  cudaLaunchConfig_t cfg = {};
  cfg.gridDim = dim3(grid); cfg.blockDim = dim3(block); cfg.dynamicSmemBytes = smem; cfg.stream = cudaStreamPerThread;
  cudaLaunchAttribute at[2];
  int n = 0;
  if (cluster > 1) { at[n].id = cudaLaunchAttributeClusterDimension; at[n].val.clusterDim.x = cluster; at[n].val.clusterDim.y = 1; at[n].val.clusterDim.z = 1; n++; }
  if (pdl) { at[n].id = cudaLaunchAttributeProgrammaticStreamSerialization; at[n].val.programmaticStreamSerializationAllowed = 1; n++; }
  cfg.attrs = at; cfg.numAttrs = n;
  cudaLaunchKernelEx(&cfg, kern, args...);
}
template <class T> void* sym(T& s) { void* p = nullptr; cudaGetSymbolAddress(&p, s); return p; }

}

#define MODE(b) 0
extern "C" void kernel_launch(void* const* d_in, const int* in_sizes, int n_in, void* d_out, int out_size) {
  const __nv_bfloat16* x = (const __nv_bfloat16*)d_in[0];
  void* fn = nullptr; cudaDriverEntryPointQueryResult qr;
  cudaGetDriverEntryPoint("cuTensorMapEncodeTiled", &fn, cudaEnableDefault, &qr);
  EncodeFn enc = (EncodeFn)fn;

  XsParams pq = {};
  ChainParams ch = {};
  PostParams op = {};
  void* q = sym(g_q);
  make_map(enc, &pq.w[0], d_in[2], HD, DM, 128); make_map(enc, &pq.o[0], q, HD, SEQ, 64);
  pq.a = (const uint32_t*)sym(g_xf);
  pq.ntiles = 96; pq.tiles_per_mat = 96; pq.rb0 = QA_END; pq.nowait = 1; pq.gap = 400;
  for (int i = 0; i < 3; i++) {
    const cuuint64_t dims[3] = {HD, 128, 5}, strides[2] = {HD * 2, HD * 256};
    const cuuint32_t box[3] = {64, 128, 5}, es[3] = {1, 1, 1};
    enc(i == 0 ? &ch.wq : i == 1 ? &ch.wk : &ch.wv, CU_TENSOR_MAP_DATA_TYPE_BFLOAT16, 3, d_in[2 + i], dims, strides, box, es, CU_TENSOR_MAP_INTERLEAVE_NONE,
        CU_TENSOR_MAP_SWIZZLE_128B, W_PROMO, CU_TENSOR_MAP_FLOAT_OOB_FILL_NONE);
  }
  {
    const cuuint64_t dims[3] = {DM, HD, 7}, strides[2] = {DM * 2, 64};
    const cuuint32_t box[3] = {32, 64, 7}, es[3] = {1, 1, 1};
    enc(&ch.wo, CU_TENSOR_MAP_DATA_TYPE_BFLOAT16, 3, d_in[5], dims, strides, box, es, CU_TENSOR_MAP_INTERLEAVE_NONE,
        CU_TENSOR_MAP_SWIZZLE_64B, CU_TENSOR_MAP_L2_PROMOTION_L2_128B, CU_TENSOR_MAP_FLOAT_OOB_FILL_NONE);
  }
  ch.mem0 = (const __nv_bfloat16*)d_in[1];
  ch.pool = (uint8_t*)(((uintptr_t)sym(g_pool) + 8191) & ~(uintptr_t)8191); ch.kv = (uint8_t*)sym(g_kv); ch.xc = (const uint32_t*)sym(g_xc); ch.sync = (uint32_t*)sym(g_sync);
  ch.d1 = 0; ch.d1b = 0; ch.d2 = 0; ch.d2b = 0;
  make_map(enc, &op.o, sym(g_o), HD, SEQ, 128); make_map(enc, &op.wo, d_in[5], DM, HD, 64);
  make_map(enc, &op.q, q, HD, SEQ, 128);
  make_map(enc, &op.wq, d_in[2], HD, DM, 64);
  make_map(enc, &op.wb, d_in[8], 1920, DM, 64);
  op.nq = 72; op.gap = 10;

  const Weights wa = {{(const uint8_t*)d_in[3], (const uint8_t*)d_in[4], (const uint8_t*)d_in[2], (const uint8_t*)d_in[5]}}, none = {};
  launch(first_kernel, 132, 256, 128 * 1024, 1, false, x, (const uint4*)d_in[9], wa);
  for (int layer = 0; layer < 2; layer++) {
    ch.layer = ch.d2b = layer;
    launch(chain_kernel, 96, 256, CH_SMEM, 3, true, ch);
    launch(xs_gemm<EPI_QKV, false>, 36, 384, XS_SMEM, 1, !MODE(1), pq);
    launch(post_kernel, 132, 384, OP_SMEM, 1, true, op);
    const AbParams ab = {layer == 0 ? wa : none, (uint32_t*)sym(g_bo) + layer * 128, layer == 0 ? nullptr : (uint32_t*)d_out};
    launch(attn_b_kernel, 128, AB_T + 32, AB_SMEM, 1, true, ab);
  }
}
```

```cpp
#include <cuda_runtime.h>
#include <cuda_bf16.h>
#include <cuda.h>
#include <stdint.h>

namespace {

constexpr int SEQ = 2048, DM = 640, HD = 6144, NSEG = 64;
constexpr int SPIN_LIMIT = 1 << 20;

__device__ __align__(128) float4 g_x[SEQ * DM / 4];
__device__ __align__(128) uint32_t g_of[SEQ * DM / 2];
__device__ __align__(128) uint4 g_wb[DM * DM / 8];
__device__ __align__(16) float2 g_stat[16 * 8 * 128];
__device__ uint32_t g_bo[8 * 32];
__device__ __align__(128) uint4 g_q[SEQ * HD / 8];
__device__ __align__(128) uint32_t g_o[SEQ * HD / 2];
constexpr int KV_BYTES = 5120, KV_M = 4096, KV_V = NSEG * KV_BYTES;
__device__ __align__(128) uint8_t g_kv[96 * 2 * NSEG * KV_BYTES];
__device__ __align__(128) uint32_t g_xc[SEQ * DM / 2];
#define OP_B4 0
#define OP_B8 11
#define OP_B16 13
#define QA_END 12
__host__ __device__ constexpr int op_split(int b) { return b < OP_B4 ? 2 : b < OP_B8 ? 4 : b < OP_B16 ? 8 : 16; }
__host__ __device__ constexpr int fin_items(int b) { return b < OP_B8 ? 4 : op_split(b); }
#define AB_PF 2
#define AB_PF0 30000
#define AB_PFD 7000
#define W_PROMO CU_TENSOR_MAP_L2_PROMOTION_L2_128B
#define WEF 1
#define FK_PF 1
#define BQ_160 10
#define BQ_80 14
#define OP_160 14
__host__ __device__ constexpr int op_width(int b) { return b < OP_160 ? 320 : 160; }
__host__ __device__ constexpr int bq_width(int b) { return b < BQ_160 ? 320 : b < BQ_80 ? 160 : 80; }
__device__ __align__(128) uint2 g_part[16 * 16 * 16 * 40 * 32];
__device__ __align__(128) uint32_t g_xn[SEQ * DM / 2];
constexpr int SY_Q = 128, SY_T = 160, SY_QC = 192, SY_N = 193;
__device__ __align__(16) uint32_t g_sync[SY_N];
constexpr int NSLOT = 92;
__device__ uint32_t g_pool[(NSLOT + 2) * 2048];
__device__ int g_smpart[256], g_orient[NSLOT];
__device__ uint32_t g_smclk[256], g_smuse[256];
__device__ uint32_t g_bqkv[3 * 32 * 256 * 96];

#define ABT(L, i)
#define MODE_D(b) 0
#define DELAY(d)
#define XT(i)
#define MISS(k, n)
#define PRO(i)
#define TRACE(w)
#define ITEM(code, w)
#define TM(i)
#define TM1(i)
#define TMD(i, dep)
#define TMV(i, at, v)

__device__ __forceinline__ uint32_t gtime() { uint32_t c; asm volatile("mov.u32 %0, %%globaltimer_lo;" : "=r"(c) :: "memory"); return c; }
__device__ __forceinline__ uint32_t clk32() { uint32_t c; asm volatile("mov.u32 %0, %%clock;" : "=r"(c) :: "memory"); return c; }
__device__ __forceinline__ uint32_t s2u(const void* p) { return (uint32_t)__cvta_generic_to_shared(p); }
__device__ __forceinline__ uint32_t pack2(float a, float b) {
  uint32_t r; asm("cvt.rn.bf16x2.f32 %0, %1, %2;" : "=r"(r) : "f"(b), "f"(a)); return r; }
__device__ __forceinline__ float bf_lo(uint32_t w) { return __uint_as_float(w << 16); }
__device__ __forceinline__ float bf_hi(uint32_t w) { return __uint_as_float(w & 0xffff0000u); }
__device__ __forceinline__ float ex2(float x) { float y; asm("ex2.approx.ftz.f32 %0, %1;" : "=f"(y) : "f"(x)); return y; }

__device__ __forceinline__ void mbar_init(uint32_t bar, uint32_t n) {
  asm volatile("mbarrier.init.shared::cta.b64 [%0], %1;" :: "r"(bar), "r"(n) : "memory"); }
__device__ __forceinline__ void mbar_expect(uint32_t bar, uint32_t bytes) {
  asm volatile("mbarrier.arrive.expect_tx.shared::cta.b64 _, [%0], %1;" :: "r"(bar), "r"(bytes) : "memory"); }
__device__ __forceinline__ void mbar_arrive(uint32_t bar) {
  asm volatile("mbarrier.arrive.shared::cta.b64 _, [%0];" :: "r"(bar) : "memory"); }
__device__ __forceinline__ void mbar_wait(uint32_t bar, uint32_t ph) {
  asm volatile("{.reg .pred p; .reg .u32 n; mov.u32 n, 0;\n"
               "W: mbarrier.try_wait.parity.shared::cta.b64 p, [%0], %1; @p bra D;\n"
               "add.u32 n, n, 1; setp.gt.u32 p, n, %2; @p trap; bra W;\n"
               "D: }" :: "r"(bar), "r"(ph), "n"(SPIN_LIMIT) : "memory");
}
__device__ __forceinline__ void mbar_wait_cluster(uint32_t bar, uint32_t ph) {
  asm volatile("{.reg .pred p; .reg .u32 n; mov.u32 n, 0;\n"
               "W: mbarrier.try_wait.parity.acquire.cluster.shared::cta.b64 p, [%0], %1; @p bra D;\n"
               "add.u32 n, n, 1; setp.gt.u32 p, n, %2; @p trap; bra W;\n"
               "D: }" :: "r"(bar), "r"(ph), "n"(SPIN_LIMIT) : "memory");
}
__device__ __forceinline__ void spin_guard(int& n) {
  asm volatile("{.reg .pred p; add.s32 %0, %0, 1; setp.gt.s32 p, %0, %1; @p trap;}" : "+r"(n) : "n"(SPIN_LIMIT));
}
__device__ __forceinline__ void pdl_wait() { asm volatile("griddepcontrol.wait;" ::: "memory"); TRACE(1); }
__device__ __forceinline__ void pdl_launch() { asm volatile("griddepcontrol.launch_dependents;" ::: "memory"); }
__device__ __forceinline__ uint32_t ld_acquire(const uint32_t* p) { uint32_t v; asm volatile("ld.acquire.gpu.global.u32 %0, [%1];" : "=r"(v) : "l"(p) : "memory"); return v; }
__device__ __forceinline__ void red_release(uint32_t* p, uint32_t v) { asm volatile("red.release.gpu.global.add.u32 [%0], %1;" :: "l"(p), "r"(v) : "memory"); }
__device__ __forceinline__ void red_relaxed(uint32_t* p, uint32_t v) { asm volatile("red.relaxed.gpu.global.add.u32 [%0], %1;" :: "l"(p), "r"(v) : "memory"); }
__device__ __forceinline__ void fence_async_global() { asm volatile("fence.proxy.async.global;" ::: "memory"); }
__device__ __forceinline__ void fence_async() { asm volatile("fence.proxy.async.shared::cta;" ::: "memory"); }
__device__ __forceinline__ void bar_sync(int id, int n) { asm volatile("bar.sync %0, %1;" :: "r"(id), "r"(n) : "memory"); }
__device__ __forceinline__ void bar_arrive(int id, int n) { asm volatile("bar.arrive %0, %1;" :: "r"(id), "r"(n) : "memory"); }
__device__ __forceinline__ void tma_load(uint32_t dst, const CUtensorMap* m, int c0, int c1, uint32_t bar) {
  asm volatile("cp.async.bulk.tensor.2d.shared::cluster.global.mbarrier::complete_tx::bytes [%0], [%1, {%3, %4}], [%2];"
               :: "r"(dst), "l"(m), "r"(bar), "r"(c0), "r"(c1) : "memory"); }
template <bool STREAM = false>
__device__ __forceinline__ void tma_load3(uint32_t dst, const CUtensorMap* m, int c0, int c1, uint32_t bar) {
  if (STREAM)
    asm volatile("{.reg .b64 pol; createpolicy.fractional.L2::evict_first.b64 pol, 1.0;\n"
                 "cp.async.bulk.tensor.3d.shared::cluster.global.mbarrier::complete_tx::bytes.L2::cache_hint [%0], [%1, {%3, %4, 0}], [%2], pol;}"
                 :: "r"(dst), "l"(m), "r"(bar), "r"(c0), "r"(c1) : "memory");
  else
  asm volatile("cp.async.bulk.tensor.3d.shared::cluster.global.mbarrier::complete_tx::bytes [%0], [%1, {%3, %4, 0}], [%2];"
               :: "r"(dst), "l"(m), "r"(bar), "r"(c0), "r"(c1) : "memory"); }
__device__ __forceinline__ void tma_load3z(uint32_t dst, const CUtensorMap* m, int c1, int c2, uint32_t bar) {
  asm volatile("cp.async.bulk.tensor.3d.shared::cluster.global.mbarrier::complete_tx::bytes [%0], [%1, {0, %3, %4}], [%2];"
               :: "r"(dst), "l"(m), "r"(bar), "r"(c1), "r"(c2) : "memory"); }
__device__ __forceinline__ void tma_store(const CUtensorMap* m, uint32_t src, int c0, int c1) {
  asm volatile("cp.async.bulk.tensor.2d.global.shared::cta.bulk_group [%0, {%2, %3}], [%1];"
               :: "l"(m), "r"(src), "r"(c0), "r"(c1) : "memory"); }
__device__ __forceinline__ void tma_store_stream(const CUtensorMap* m, uint32_t src, int c0, int c1) {
  asm volatile("{.reg .b64 pol; createpolicy.fractional.L2::evict_first.b64 pol, 1.0;\n"
               "cp.async.bulk.tensor.2d.global.shared::cta.bulk_group.L2::cache_hint [%0, {%2, %3}], [%1], pol;}"
               :: "l"(m), "r"(src), "r"(c0), "r"(c1) : "memory"); }
__device__ __forceinline__ void bulk_load(uint32_t dst, const void* src, uint32_t bytes, uint32_t bar) {
  asm volatile("cp.async.bulk.shared::cluster.global.mbarrier::complete_tx::bytes [%0], [%1], %2, [%3];"
               :: "r"(dst), "l"(src), "r"(bytes), "r"(bar) : "memory"); }
__device__ __forceinline__ void bulk_load_last(uint32_t dst, const void* src, uint32_t bytes, uint32_t bar) {
  asm volatile("{.reg .b64 pol; createpolicy.fractional.L2::evict_first.b64 pol, 1.0;\n"
               "cp.async.bulk.shared::cluster.global.mbarrier::complete_tx::bytes.L2::cache_hint [%0], [%1], %2, [%3], pol;}"
               :: "r"(dst), "l"(src), "r"(bytes), "r"(bar) : "memory"); }
__device__ __forceinline__ void tma_load_last(uint32_t dst, const CUtensorMap* m, int c0, int c1, uint32_t bar) {
  asm volatile("{.reg .b64 pol; createpolicy.fractional.L2::evict_first.b64 pol, 1.0;\n"
               "cp.async.bulk.tensor.2d.shared::cluster.global.mbarrier::complete_tx::bytes.L2::cache_hint [%0], [%1, {%3, %4}], [%2], pol;}"
               :: "r"(dst), "l"(m), "r"(bar), "r"(c0), "r"(c1) : "memory"); }
__device__ __forceinline__ void bulk_send(uint32_t dst, uint32_t src, uint32_t bytes, uint32_t bar) {
  asm volatile("cp.async.bulk.shared::cluster.shared::cta.mbarrier::complete_tx::bytes [%0], [%1], %2, [%3];"
               :: "r"(dst), "r"(src), "r"(bytes), "r"(bar) : "memory"); }
__device__ __forceinline__ void bulk_store(void* dst, uint32_t src, uint32_t bytes) {
  asm volatile("cp.async.bulk.global.shared::cta.bulk_group [%0], [%1], %2;" :: "l"(dst), "r"(src), "r"(bytes) : "memory"); }
__device__ __forceinline__ void bulk_commit() { asm volatile("cp.async.bulk.commit_group;" ::: "memory"); }
template <int N> __device__ __forceinline__ void bulk_wait_read() { asm volatile("cp.async.bulk.wait_group.read %0;" :: "n"(N) : "memory"); }
template <int N> __device__ __forceinline__ void bulk_wait() { asm volatile("cp.async.bulk.wait_group %0;" :: "n"(N) : "memory"); }

__device__ __forceinline__ uint64_t mkdesc(uint32_t addr, uint32_t lbo, uint32_t sbo, uint32_t sw) {
  return (uint64_t)((addr & 0x3FFFF) >> 4) | ((uint64_t)(lbo >> 4) << 16) | ((uint64_t)(sbo >> 4) << 32) | ((uint64_t)sw << 62); }
__device__ __forceinline__ void wg_fence() { asm volatile("wgmma.fence.sync.aligned;" ::: "memory"); }
__device__ __forceinline__ void wg_commit() { asm volatile("wgmma.commit_group.sync.aligned;" ::: "memory"); }
template <int N> __device__ __forceinline__ void wg_wait() { asm volatile("wgmma.wait_group.sync.aligned %0;" :: "n"(N) : "memory"); }
template <int N> __device__ __forceinline__ void reg_fence(float* d) {
#pragma unroll
  for (int i = 0; i < N; i++) asm volatile("" : "+f"(d[i]) :: "memory");
}

__device__ __forceinline__ void mma16(float* d, uint32_t a0, uint32_t a1, uint32_t a2, uint32_t a3, uint32_t b0, uint32_t b1) {
  asm volatile("mma.sync.aligned.m16n8k16.row.col.f32.bf16.bf16.f32 {%0,%1,%2,%3},{%4,%5,%6,%7},{%8,%9},{%0,%1,%2,%3};"
               : "+f"(d[0]), "+f"(d[1]), "+f"(d[2]), "+f"(d[3]) : "r"(a0), "r"(a1), "r"(a2), "r"(a3), "r"(b0), "r"(b1)); }
__device__ __forceinline__ void mma8(float* d, uint32_t a0, uint32_t a1, uint32_t b0) {
  asm volatile("mma.sync.aligned.m16n8k8.row.col.f32.bf16.bf16.f32 {%0,%1,%2,%3},{%4,%5},{%6},{%0,%1,%2,%3};"
               : "+f"(d[0]), "+f"(d[1]), "+f"(d[2]), "+f"(d[3]) : "r"(a0), "r"(a1), "r"(b0)); }
__device__ __forceinline__ void ldsm4(uint32_t* r, uint32_t a) {
  asm volatile("ldmatrix.sync.aligned.m8n8.x4.shared.b16 {%0,%1,%2,%3},[%4];" : "=r"(r[0]), "=r"(r[1]), "=r"(r[2]), "=r"(r[3]) : "r"(a) : "memory"); }
__device__ __forceinline__ void ldsm4t(uint32_t* r, uint32_t a) {
  asm volatile("ldmatrix.sync.aligned.m8n8.x4.trans.shared.b16 {%0,%1,%2,%3},[%4];" : "=r"(r[0]), "=r"(r[1]), "=r"(r[2]), "=r"(r[3]) : "r"(a) : "memory"); }
__device__ __forceinline__ void ldsm2(uint32_t* r, uint32_t a) {
  asm volatile("ldmatrix.sync.aligned.m8n8.x2.shared.b16 {%0,%1},[%2];" : "=r"(r[0]), "=r"(r[1]) : "r"(a) : "memory"); }
__device__ __forceinline__ void stsm4(uint32_t a, uint32_t r0, uint32_t r1, uint32_t r2, uint32_t r3) {
  asm volatile("stmatrix.sync.aligned.m8n8.x4.shared.b16 [%0], {%1,%2,%3,%4};" :: "r"(a), "r"(r0), "r"(r1), "r"(r2), "r"(r3) : "memory"); }
__device__ __forceinline__ void stsm2t(uint32_t a, uint32_t r0, uint32_t r1) {
  asm volatile("stmatrix.sync.aligned.m8n8.x2.trans.shared.b16 [%0], {%1,%2};" :: "r"(a), "r"(r0), "r"(r1) : "memory"); }
__device__ __forceinline__ void stsm4t(uint32_t a, uint32_t r0, uint32_t r1, uint32_t r2, uint32_t r3) {
  asm volatile("stmatrix.sync.aligned.m8n8.x4.trans.shared.b16 [%0], {%1,%2,%3,%4};" :: "r"(a), "r"(r0), "r"(r1), "r"(r2), "r"(r3) : "memory"); }
__device__ __forceinline__ void st_async128(uint32_t a, uint4 v, uint32_t bar) {
  asm volatile("st.async.shared::cluster.mbarrier::complete_tx::bytes.v4.b32 [%0], {%1,%2,%3,%4}, [%5];" :: "r"(a), "r"(v.x), "r"(v.y), "r"(v.z), "r"(v.w), "r"(bar) : "memory"); }
__device__ __forceinline__ void sts32(uint32_t a, uint32_t v) { asm volatile("st.shared.b32 [%0], %1;" :: "r"(a), "r"(v) : "memory"); }
__device__ __forceinline__ void sts64f(uint32_t a, float x, float y) { asm volatile("st.shared.v2.f32 [%0], {%1,%2};" :: "r"(a), "f"(x), "f"(y) : "memory"); }
__device__ __forceinline__ void sts128(uint32_t a, uint4 v) {
  asm volatile("st.shared.v4.b32 [%0], {%1,%2,%3,%4};" :: "r"(a), "r"(v.x), "r"(v.y), "r"(v.z), "r"(v.w) : "memory"); }
__device__ __forceinline__ void sts128f(uint32_t a, float x, float y, float z, float w) {
  asm volatile("st.shared.v4.f32 [%0], {%1,%2,%3,%4};" :: "r"(a), "f"(x), "f"(y), "f"(z), "f"(w) : "memory"); }
__device__ __forceinline__ float lds32f(uint32_t a) { float v; asm volatile("ld.shared.f32 %0, [%1];" : "=f"(v) : "r"(a) : "memory"); return v; }
__device__ __forceinline__ float2 lds64f(uint32_t a) { float2 v; asm volatile("ld.shared.v2.f32 {%0,%1}, [%2];" : "=f"(v.x), "=f"(v.y) : "r"(a) : "memory"); return v; }
__device__ __forceinline__ float4 lds128f(uint32_t a) {
  float4 v; asm volatile("ld.shared.v4.f32 {%0,%1,%2,%3}, [%4];" : "=f"(v.x), "=f"(v.y), "=f"(v.z), "=f"(v.w) : "r"(a) : "memory"); return v; }
__device__ __forceinline__ uint4 lds128(uint32_t a) {
  uint4 v; asm volatile("ld.shared.v4.b32 {%0,%1,%2,%3}, [%4];" : "=r"(v.x), "=r"(v.y), "=r"(v.z), "=r"(v.w) : "r"(a) : "memory"); return v; }
__device__ __forceinline__ uint4 ldg_strong128(const void* p) {
  uint4 v; asm volatile("ld.relaxed.gpu.global.v4.u32 {%0,%1,%2,%3}, [%4];" : "=r"(v.x), "=r"(v.y), "=r"(v.z), "=r"(v.w) : "l"(p) : "memory"); return v; }
__device__ __forceinline__ void stg_strong32(void* p, uint32_t v) { asm volatile("st.relaxed.gpu.global.u32 [%0], %1;" :: "l"(p), "r"(v) : "memory"); }
__device__ __forceinline__ void stg_strong16(void* p, uint32_t v) { asm volatile("st.relaxed.gpu.global.u16 [%0], %1;" :: "l"(p), "h"((uint16_t)v) : "memory"); }
__device__ __forceinline__ void stg_strong128(void* p, uint4 v) {
  asm volatile("st.relaxed.gpu.global.v4.u32 [%0], {%1,%2,%3,%4};" :: "l"(p), "r"(v.x), "r"(v.y), "r"(v.z), "r"(v.w) : "memory"); }
__device__ __forceinline__ uint32_t mapa(uint32_t a, uint32_t r) {
  uint32_t o; asm("mapa.shared::cluster.u32 %0, %1, %2;" : "=r"(o) : "r"(a), "r"(r)); return o; }
__device__ __forceinline__ void st_async2f(uint32_t a, float x, float y, uint32_t bar) {
  asm volatile("st.async.shared::cluster.mbarrier::complete_tx::bytes.v2.f32 [%0], {%1,%2}, [%3];" :: "r"(a), "f"(x), "f"(y), "r"(bar) : "memory"); }
__device__ __forceinline__ void st_async32(uint32_t a, uint32_t x, uint32_t bar) {
  asm volatile("st.async.shared::cluster.mbarrier::complete_tx::bytes.b32 [%0], %1, [%2];" :: "r"(a), "r"(x), "r"(bar) : "memory"); }
__device__ __forceinline__ uint32_t lds32(uint32_t a) { uint32_t v; asm volatile("ld.shared.b32 %0, [%1];" : "=r"(v) : "r"(a) : "memory"); return v; }
__device__ __forceinline__ void st_async64(uint32_t a, uint32_t x, uint32_t y, uint32_t bar) {
  asm volatile("st.async.shared::cluster.mbarrier::complete_tx::bytes.v2.b32 [%0], {%1,%2}, [%3];" :: "r"(a), "r"(x), "r"(y), "r"(bar) : "memory"); }
__device__ __forceinline__ uint2 lds64(uint32_t a) { uint2 v; asm volatile("ld.shared.v2.b32 {%0,%1}, [%2];" : "=r"(v.x), "=r"(v.y) : "r"(a) : "memory"); return v; }
__device__ __forceinline__ void sts64(uint32_t a, uint32_t x, uint32_t y) { asm volatile("st.shared.v2.b32 [%0], {%1,%2};" :: "r"(a), "r"(x), "r"(y) : "memory"); }
__device__ __forceinline__ uint32_t ldg_strong32(const void* p) { uint32_t v; asm volatile("ld.relaxed.gpu.global.u32 %0, [%1];" : "=r"(v) : "l"(p) : "memory"); return v; }
__device__ __forceinline__ uint32_t transpose8(uint32_t x) { uint32_t r; asm volatile("movmatrix.sync.aligned.m8n8.trans.b16 %0, %1;" : "=r"(r) : "r"(x)); return r; }
__device__ __forceinline__ uint32_t hadd2(uint32_t a, uint32_t b) { uint32_t r; asm("add.rn.bf16x2 %0, %1, %2;" : "=r"(r) : "r"(a), "r"(b)); return r; }
__device__ __forceinline__ uint32_t min4(uint4 v) { return min(__vimin3_u32(v.x, v.y, v.z), v.w); }

__device__ __forceinline__ void wg_ss192_01(float* d, uint64_t da, uint64_t db, int sd) {
  asm volatile("{.reg .pred p; setp.ne.b32 p, %98, 0;\n"
    "wgmma.mma_async.sync.aligned.m64n192k16.f32.bf16.bf16 {%0,%1,%2,%3,%4,%5,%6,%7,%8,%9,%10,%11,%12,%13,%14,%15,%16,%17,%18,%19,%20,%21,%22,%23,%24,%25,%26,%27,%28,%29,%30,%31,%32,%33,%34,%35,%36,%37,%38,%39,%40,%41,%42,%43,%44,%45,%46,%47,%48,%49,%50,%51,%52,%53,%54,%55,%56,%57,%58,%59,%60,%61,%62,%63,%64,%65,%66,%67,%68,%69,%70,%71,%72,%73,%74,%75,%76,%77,%78,%79,%80,%81,%82,%83,%84,%85,%86,%87,%88,%89,%90,%91,%92,%93,%94,%95}, %96, %97, p, 1, 1, 0, 1;}"
    : "+f"(d[0]),"+f"(d[1]),"+f"(d[2]),"+f"(d[3]),"+f"(d[4]),"+f"(d[5]),"+f"(d[6]),"+f"(d[7]),"+f"(d[8]),"+f"(d[9]),"+f"(d[10]),"+f"(d[11]),"+f"(d[12]),"+f"(d[13]),"+f"(d[14]),"+f"(d[15]),"+f"(d[16]),"+f"(d[17]),"+f"(d[18]),"+f"(d[19]),"+f"(d[20]),"+f"(d[21]),"+f"(d[22]),"+f"(d[23]),"+f"(d[24]),"+f"(d[25]),"+f"(d[26]),"+f"(d[27]),"+f"(d[28]),"+f"(d[29]),"+f"(d[30]),"+f"(d[31]),"+f"(d[32]),"+f"(d[33]),"+f"(d[34]),"+f"(d[35]),"+f"(d[36]),"+f"(d[37]),"+f"(d[38]),"+f"(d[39]),"+f"(d[40]),"+f"(d[41]),"+f"(d[42]),"+f"(d[43]),"+f"(d[44]),"+f"(d[45]),"+f"(d[46]),"+f"(d[47]),"+f"(d[48]),"+f"(d[49]),"+f"(d[50]),"+f"(d[51]),"+f"(d[52]),"+f"(d[53]),"+f"(d[54]),"+f"(d[55]),"+f"(d[56]),"+f"(d[57]),"+f"(d[58]),"+f"(d[59]),"+f"(d[60]),"+f"(d[61]),"+f"(d[62]),"+f"(d[63]),"+f"(d[64]),"+f"(d[65]),"+f"(d[66]),"+f"(d[67]),"+f"(d[68]),"+f"(d[69]),"+f"(d[70]),"+f"(d[71]),"+f"(d[72]),"+f"(d[73]),"+f"(d[74]),"+f"(d[75]),"+f"(d[76]),"+f"(d[77]),"+f"(d[78]),"+f"(d[79]),"+f"(d[80]),"+f"(d[81]),"+f"(d[82]),"+f"(d[83]),"+f"(d[84]),"+f"(d[85]),"+f"(d[86]),"+f"(d[87]),"+f"(d[88]),"+f"(d[89]),"+f"(d[90]),"+f"(d[91]),"+f"(d[92]),"+f"(d[93]),"+f"(d[94]),"+f"(d[95])
    : "l"(da), "l"(db), "r"(sd));
}
__device__ __forceinline__ void wg_ss128_01(float* d, uint64_t da, uint64_t db, int sd) {
  asm volatile("{.reg .pred p; setp.ne.b32 p, %66, 0;\n"
    "wgmma.mma_async.sync.aligned.m64n128k16.f32.bf16.bf16 {%0,%1,%2,%3,%4,%5,%6,%7,%8,%9,%10,%11,%12,%13,%14,%15,%16,%17,%18,%19,%20,%21,%22,%23,%24,%25,%26,%27,%28,%29,%30,%31,%32,%33,%34,%35,%36,%37,%38,%39,%40,%41,%42,%43,%44,%45,%46,%47,%48,%49,%50,%51,%52,%53,%54,%55,%56,%57,%58,%59,%60,%61,%62,%63}, %64, %65, p, 1, 1, 0, 1;}"
    : "+f"(d[0]),"+f"(d[1]),"+f"(d[2]),"+f"(d[3]),"+f"(d[4]),"+f"(d[5]),"+f"(d[6]),"+f"(d[7]),"+f"(d[8]),"+f"(d[9]),"+f"(d[10]),"+f"(d[11]),"+f"(d[12]),"+f"(d[13]),"+f"(d[14]),"+f"(d[15]),"+f"(d[16]),"+f"(d[17]),"+f"(d[18]),"+f"(d[19]),"+f"(d[20]),"+f"(d[21]),"+f"(d[22]),"+f"(d[23]),"+f"(d[24]),"+f"(d[25]),"+f"(d[26]),"+f"(d[27]),"+f"(d[28]),"+f"(d[29]),"+f"(d[30]),"+f"(d[31]),"+f"(d[32]),"+f"(d[33]),"+f"(d[34]),"+f"(d[35]),"+f"(d[36]),"+f"(d[37]),"+f"(d[38]),"+f"(d[39]),"+f"(d[40]),"+f"(d[41]),"+f"(d[42]),"+f"(d[43]),"+f"(d[44]),"+f"(d[45]),"+f"(d[46]),"+f"(d[47]),"+f"(d[48]),"+f"(d[49]),"+f"(d[50]),"+f"(d[51]),"+f"(d[52]),"+f"(d[53]),"+f"(d[54]),"+f"(d[55]),"+f"(d[56]),"+f"(d[57]),"+f"(d[58]),"+f"(d[59]),"+f"(d[60]),"+f"(d[61]),"+f"(d[62]),"+f"(d[63])
    : "l"(da), "l"(db), "r"(sd));
}
__device__ __forceinline__ void wg_ss160_01(float* d, uint64_t da, uint64_t db, int sd) {
  asm volatile("{.reg .pred p; setp.ne.b32 p, %82, 0;\n"
    "wgmma.mma_async.sync.aligned.m64n160k16.f32.bf16.bf16 {%0,%1,%2,%3,%4,%5,%6,%7,%8,%9,%10,%11,%12,%13,%14,%15,%16,%17,%18,%19,%20,%21,%22,%23,%24,%25,%26,%27,%28,%29,%30,%31,%32,%33,%34,%35,%36,%37,%38,%39,%40,%41,%42,%43,%44,%45,%46,%47,%48,%49,%50,%51,%52,%53,%54,%55,%56,%57,%58,%59,%60,%61,%62,%63,%64,%65,%66,%67,%68,%69,%70,%71,%72,%73,%74,%75,%76,%77,%78,%79}, %80, %81, p, 1, 1, 0, 1;}"
    : "+f"(d[0]),"+f"(d[1]),"+f"(d[2]),"+f"(d[3]),"+f"(d[4]),"+f"(d[5]),"+f"(d[6]),"+f"(d[7]),"+f"(d[8]),"+f"(d[9]),"+f"(d[10]),"+f"(d[11]),"+f"(d[12]),"+f"(d[13]),"+f"(d[14]),"+f"(d[15]),"+f"(d[16]),"+f"(d[17]),"+f"(d[18]),"+f"(d[19]),"+f"(d[20]),"+f"(d[21]),"+f"(d[22]),"+f"(d[23]),"+f"(d[24]),"+f"(d[25]),"+f"(d[26]),"+f"(d[27]),"+f"(d[28]),"+f"(d[29]),"+f"(d[30]),"+f"(d[31]),"+f"(d[32]),"+f"(d[33]),"+f"(d[34]),"+f"(d[35]),"+f"(d[36]),"+f"(d[37]),"+f"(d[38]),"+f"(d[39]),"+f"(d[40]),"+f"(d[41]),"+f"(d[42]),"+f"(d[43]),"+f"(d[44]),"+f"(d[45]),"+f"(d[46]),"+f"(d[47]),"+f"(d[48]),"+f"(d[49]),"+f"(d[50]),"+f"(d[51]),"+f"(d[52]),"+f"(d[53]),"+f"(d[54]),"+f"(d[55]),"+f"(d[56]),"+f"(d[57]),"+f"(d[58]),"+f"(d[59]),"+f"(d[60]),"+f"(d[61]),"+f"(d[62]),"+f"(d[63]),"+f"(d[64]),"+f"(d[65]),"+f"(d[66]),"+f"(d[67]),"+f"(d[68]),"+f"(d[69]),"+f"(d[70]),"+f"(d[71]),"+f"(d[72]),"+f"(d[73]),"+f"(d[74]),"+f"(d[75]),"+f"(d[76]),"+f"(d[77]),"+f"(d[78]),"+f"(d[79])
    : "l"(da), "l"(db), "r"(sd));
}
__device__ __forceinline__ void wg_ss80_01(float* d, uint64_t da, uint64_t db, int sd) {
  asm volatile("{.reg .pred p; setp.ne.b32 p, %42, 0;\n"
    "wgmma.mma_async.sync.aligned.m64n80k16.f32.bf16.bf16 {%0,%1,%2,%3,%4,%5,%6,%7,%8,%9,%10,%11,%12,%13,%14,%15,%16,%17,%18,%19,%20,%21,%22,%23,%24,%25,%26,%27,%28,%29,%30,%31,%32,%33,%34,%35,%36,%37,%38,%39}, %40, %41, p, 1, 1, 0, 1;}"
    : "+f"(d[0]),"+f"(d[1]),"+f"(d[2]),"+f"(d[3]),"+f"(d[4]),"+f"(d[5]),"+f"(d[6]),"+f"(d[7]),"+f"(d[8]),"+f"(d[9]),"+f"(d[10]),"+f"(d[11]),"+f"(d[12]),"+f"(d[13]),"+f"(d[14]),"+f"(d[15]),"+f"(d[16]),"+f"(d[17]),"+f"(d[18]),"+f"(d[19]),"+f"(d[20]),"+f"(d[21]),"+f"(d[22]),"+f"(d[23]),"+f"(d[24]),"+f"(d[25]),"+f"(d[26]),"+f"(d[27]),"+f"(d[28]),"+f"(d[29]),"+f"(d[30]),"+f"(d[31]),"+f"(d[32]),"+f"(d[33]),"+f"(d[34]),"+f"(d[35]),"+f"(d[36]),"+f"(d[37]),"+f"(d[38]),"+f"(d[39])
    : "l"(da), "l"(db), "r"(sd));
}
__device__ __forceinline__ void wg_rs32_00(float* d, uint32_t a0, uint32_t a1, uint32_t a2, uint32_t a3, uint64_t db, int sd) {
  asm volatile("{.reg .pred p; setp.ne.b32 p, %21, 0;\n"
    "wgmma.mma_async.sync.aligned.m64n32k16.f32.bf16.bf16 {%0,%1,%2,%3,%4,%5,%6,%7,%8,%9,%10,%11,%12,%13,%14,%15}, {%16,%17,%18,%19}, %20, p, 1, 1, 0;}"
    : "+f"(d[0]),"+f"(d[1]),"+f"(d[2]),"+f"(d[3]),"+f"(d[4]),"+f"(d[5]),"+f"(d[6]),"+f"(d[7]),"+f"(d[8]),"+f"(d[9]),"+f"(d[10]),"+f"(d[11]),"+f"(d[12]),"+f"(d[13]),"+f"(d[14]),"+f"(d[15])
    : "r"(a0), "r"(a1), "r"(a2), "r"(a3), "l"(db), "r"(sd));
}
__device__ __forceinline__ void wg_rs64_00(float* d, uint32_t a0, uint32_t a1, uint32_t a2, uint32_t a3, uint64_t db, int sd) {
  asm volatile("{.reg .pred p; setp.ne.b32 p, %37, 0;\n"
    "wgmma.mma_async.sync.aligned.m64n64k16.f32.bf16.bf16 {%0,%1,%2,%3,%4,%5,%6,%7,%8,%9,%10,%11,%12,%13,%14,%15,%16,%17,%18,%19,%20,%21,%22,%23,%24,%25,%26,%27,%28,%29,%30,%31}, {%32,%33,%34,%35}, %36, p, 1, 1, 0;}"
    : "+f"(d[0]),"+f"(d[1]),"+f"(d[2]),"+f"(d[3]),"+f"(d[4]),"+f"(d[5]),"+f"(d[6]),"+f"(d[7]),"+f"(d[8]),"+f"(d[9]),"+f"(d[10]),"+f"(d[11]),"+f"(d[12]),"+f"(d[13]),"+f"(d[14]),"+f"(d[15]),"+f"(d[16]),"+f"(d[17]),"+f"(d[18]),"+f"(d[19]),"+f"(d[20]),"+f"(d[21]),"+f"(d[22]),"+f"(d[23]),"+f"(d[24]),"+f"(d[25]),"+f"(d[26]),"+f"(d[27]),"+f"(d[28]),"+f"(d[29]),"+f"(d[30]),"+f"(d[31])
    : "r"(a0), "r"(a1), "r"(a2), "r"(a3), "l"(db), "r"(sd));
}
__device__ __forceinline__ void wg_rs128_00(float* d, uint32_t a0, uint32_t a1, uint32_t a2, uint32_t a3, uint64_t db, int sd) {
  asm volatile("{.reg .pred p; setp.ne.b32 p, %69, 0;\n"
    "wgmma.mma_async.sync.aligned.m64n128k16.f32.bf16.bf16 {%0,%1,%2,%3,%4,%5,%6,%7,%8,%9,%10,%11,%12,%13,%14,%15,%16,%17,%18,%19,%20,%21,%22,%23,%24,%25,%26,%27,%28,%29,%30,%31,%32,%33,%34,%35,%36,%37,%38,%39,%40,%41,%42,%43,%44,%45,%46,%47,%48,%49,%50,%51,%52,%53,%54,%55,%56,%57,%58,%59,%60,%61,%62,%63}, {%64,%65,%66,%67}, %68, p, 1, 1, 0;}"
    : "+f"(d[0]),"+f"(d[1]),"+f"(d[2]),"+f"(d[3]),"+f"(d[4]),"+f"(d[5]),"+f"(d[6]),"+f"(d[7]),"+f"(d[8]),"+f"(d[9]),"+f"(d[10]),"+f"(d[11]),"+f"(d[12]),"+f"(d[13]),"+f"(d[14]),"+f"(d[15]),"+f"(d[16]),"+f"(d[17]),"+f"(d[18]),"+f"(d[19]),"+f"(d[20]),"+f"(d[21]),"+f"(d[22]),"+f"(d[23]),"+f"(d[24]),"+f"(d[25]),"+f"(d[26]),"+f"(d[27]),"+f"(d[28]),"+f"(d[29]),"+f"(d[30]),"+f"(d[31]),"+f"(d[32]),"+f"(d[33]),"+f"(d[34]),"+f"(d[35]),"+f"(d[36]),"+f"(d[37]),"+f"(d[38]),"+f"(d[39]),"+f"(d[40]),"+f"(d[41]),"+f"(d[42]),"+f"(d[43]),"+f"(d[44]),"+f"(d[45]),"+f"(d[46]),"+f"(d[47]),"+f"(d[48]),"+f"(d[49]),"+f"(d[50]),"+f"(d[51]),"+f"(d[52]),"+f"(d[53]),"+f"(d[54]),"+f"(d[55]),"+f"(d[56]),"+f"(d[57]),"+f"(d[58]),"+f"(d[59]),"+f"(d[60]),"+f"(d[61]),"+f"(d[62]),"+f"(d[63])
    : "r"(a0), "r"(a1), "r"(a2), "r"(a3), "l"(db), "r"(sd));
}
__device__ __forceinline__ void wg_rs24_01(float* d, uint32_t a0, uint32_t a1, uint32_t a2, uint32_t a3, uint64_t db, int sd) {
  asm volatile("{.reg .pred p; setp.ne.b32 p, %17, 0;\n"
    "wgmma.mma_async.sync.aligned.m64n24k16.f32.bf16.bf16 {%0,%1,%2,%3,%4,%5,%6,%7,%8,%9,%10,%11}, {%12,%13,%14,%15}, %16, p, 1, 1, 1;}"
    : "+f"(d[0]),"+f"(d[1]),"+f"(d[2]),"+f"(d[3]),"+f"(d[4]),"+f"(d[5]),"+f"(d[6]),"+f"(d[7]),"+f"(d[8]),"+f"(d[9]),"+f"(d[10]),"+f"(d[11])
    : "r"(a0), "r"(a1), "r"(a2), "r"(a3), "l"(db), "r"(sd));
}

#define AB_POLY 0x77
__device__ __forceinline__ constexpr bool poly_group(int group) { return (AB_POLY >> (group & 7)) & 1; }

template <int V> struct Int { static constexpr int value = V; };

template <int NG>
__device__ __forceinline__ void ln_stats(const float4 (&v)[NG][5], uint32_t scratch, float (&mean)[NG], float (&rs)[NG]) {
  const int warp = threadIdx.x >> 5, lane = threadIdx.x & 31;
#pragma unroll
  for (int r = 0; r < NG; r++) {
    float s = 0.f, q = 0.f;
#pragma unroll
    for (int i = 0; i < 5; i++) s += (v[r][i].x + v[r][i].y) + (v[r][i].z + v[r][i].w);
    s += __shfl_xor_sync(~0u, s, 1); s += __shfl_xor_sync(~0u, s, 2);
    s *= 1.f / 80;
#pragma unroll
    for (int i = 0; i < 5; i++) {
      const float x = v[r][i].x - s, y = v[r][i].y - s, z = v[r][i].z - s, w = v[r][i].w - s;
      q += (x * x + y * y) + (z * z + w * w);
    }
    q += __shfl_xor_sync(~0u, q, 1); q += __shfl_xor_sync(~0u, q, 2);
    mean[r] = s; rs[r] = q;
  }
  bar_sync(1, 256);
  if ((lane & 3) == 0) {
#pragma unroll
    for (int r = 0; r < NG; r++) sts64f(scratch + r * 512 + lane * 16 + warp * 8, mean[r], rs[r]);
  }
  bar_sync(1, 256);
#pragma unroll
  for (int r = 0; r < NG; r++) {
    const float4 e = lds128f(scratch + r * 512 + lane * 16);
    float t = e.x + e.z;
    t += __shfl_xor_sync(~0u, t, 1); t += __shfl_xor_sync(~0u, t, 2);
    t *= 0.125f;
    float q = e.y + e.w + 80.f * ((e.x - t) * (e.x - t) + (e.z - t) * (e.z - t));
    q += __shfl_xor_sync(~0u, q, 1); q += __shfl_xor_sync(~0u, q, 2);
    mean[r] = t; rs[r] = rsqrtf(q * (1.f / DM) + 1e-5f);
  }
}

__device__ __forceinline__ void ln_store(const uint32_t (&w)[2][5][2], int tile, int u0) {
  const int lane = threadIdx.x & 31;
  uint32_t* xc = g_xc + ((tile >> 1) * 40 + u0) * 256 + (tile & 1) * 64 + lane;
#pragma unroll
  for (int i = 0; i < 20; i++) xc[(i >> 1) * 128 + (i & 1) * 32] = w[i & 1][i >> 2][i >> 1 & 1];
#pragma unroll
  for (int i = 0; i < 5; i++) {
    const int u = u0 + i;
    uint32_t* xn = g_xn + (((tile >> 3) * 20 + (u >> 1)) * 16 + (tile & 1) * 8 + (tile & 6)) * 128 + (u & 1) * 64 + lane;
#pragma unroll
    for (int r = 0; r < 2; r++) { xn[r * 128] = w[r][i][0]; xn[r * 128 + 32] = w[r][i][1]; }
  }
}
__device__ __forceinline__ void wait_count(const uint32_t* c, uint32_t n) {
  int spin = 0;
  while ((ld_acquire(c) & 0xffff) < n) { __nanosleep(32); spin_guard(spin); }
}

__device__ __forceinline__ uint8_t* pool_at(uint32_t off) {
  return reinterpret_cast<uint8_t*>((reinterpret_cast<uintptr_t>(g_pool) + 8191) & ~(uintptr_t)8191) + off; }
struct Weights { const uint8_t* w[4]; };
__device__ __forceinline__ void prefetch_weights(const Weights& p, int i) {
  if (blockIdx.x < 128) asm volatile("cp.async.bulk.prefetch.L2.global [%0], 61440;" :: "l"(p.w[i] + (size_t)blockIdx.x * 61440) : "memory");
}
__global__ void __launch_bounds__(256) first_kernel(const __nv_bfloat16* __restrict__ xin, const uint4* __restrict__ wb, const __grid_constant__ Weights wa) {
  __shared__ __align__(16) float scratch[256];
  __shared__ uint32_t lat[4];
  const int warp = threadIdx.x >> 5, lane = threadIdx.x & 31, cta = blockIdx.x;
  TRACE(0);
  pdl_launch();
  if (warp < 4 && (warp < 2 || cta < NSLOT)) {
    uint32_t* q = reinterpret_cast<uint32_t*>(pool_at((warp < 2 ? NSLOT : cta) * 8192 + (warp & 1) * 4096)) + (warp < 2 ? (cta & 127) * 8 : 0);
    if (lane < 8) stg_strong32(q + lane, 0u);
    uint32_t best = ~0u;
    if (lane == 0)
      for (int r = 0; r < 4; r++) {
        uint32_t t0, t1, v;
        asm volatile("mov.u32 %0, %%clock;" : "=r"(t0) :: "memory");
        asm volatile("atom.relaxed.gpu.global.exch.b32 %0, [%1], 0;" : "=r"(v) : "l"(q) : "memory");
        asm volatile("{.reg .u32 t; add.u32 t, %1, 1; mov.u32 %0, %%clock; sub.u32 %0, %0, %1;}" : "=r"(t1) : "r"(__shfl_sync(1u, v, 0)) : "memory");
        best = min(best, t1 - t0);
      }
    if (lane == 0) lat[warp] = best;
  }
  __syncthreads();
  ABT(2, 0);
  if (threadIdx.x == 0) {
    const int part = lat[0] < lat[1] ? 0 : 1;
    uint32_t smid; asm("mov.u32 %0, %%smid;" : "=r"(smid));
    g_smpart[smid & 255] = part;
    g_smclk[smid & 255] = clk32() - gtime() * 2;
    g_smuse[smid & 255] = 0;
    if (cta < NSLOT) g_orient[cta] = lat[2] < lat[3] ? part : 1 - part;
  }
  if (cta < 128) {
    float4 v[2][5];
#pragma unroll
    for (int r = 0; r < 2; r++)
#pragma unroll
      for (int i = 0; i < 5; i++) {
        const uint32_t* src = reinterpret_cast<const uint32_t*>(xin) + (cta * 16 + r * 8 + (lane >> 2)) * (DM / 2) + warp * 40 + i * 8 + (lane & 3);
        const uint32_t a = src[0], b = src[4];
        v[r][i] = make_float4(bf_lo(a), bf_hi(a), bf_lo(b), bf_hi(b));
      }
    uint4 w8[2];
#pragma unroll
    for (int i = 0; i < 2; i++) w8[i] = wb[cta * 400 + min(i * 256 + threadIdx.x, 399)];
    if (threadIdx.x < 128) g_stat[cta * 128 + threadIdx.x] = make_float2(0.f, 0.f);
#pragma unroll
    for (int i = 0; i < 10; i++) g_x[((cta * 2 + i / 5) * 40 + warp * 5 + i % 5) * 32 + lane] = v[i / 5][i % 5];
    ABT(2, 1);
    if (threadIdx.x == 32) for (int i = 0; i < FK_PF; i++) prefetch_weights(wa, i);
    float mean[2], rs[2];
    ln_stats<2>(v, s2u(scratch), mean, rs);
    ABT(2, 2);
    uint32_t w[2][5][2];
#pragma unroll
    for (int i = 0; i < 10; i++) {
      const float4 t = v[i / 5][i % 5];
      const float m = mean[i / 5], q = rs[i / 5];
      w[i / 5][i % 5][0] = pack2((t.x - m) * q, (t.y - m) * q); w[i / 5][i % 5][1] = pack2((t.z - m) * q, (t.w - m) * q);
    }
    ln_store(w, cta, warp * 5);
    ABT(2, 3);
#pragma unroll
    for (int i = 0; i < 2; i++) {
      const int e = cta * 400 + min(i * 256 + threadIdx.x, 399), k = e / 80, n = e - k * 80, cg = n / 10;
      g_wb[((cg * 80 + (k >> 3)) * 10 + n - cg * 10) * 8 + (k & 7)] = w8[i];
    }
  } else if (cta == 128) {
    g_bo[threadIdx.x] = 0;
  }
  TRACE(2);
}

struct ChainParams {
  CUtensorMap wq, wk, wv, wo;
  const __nv_bfloat16* mem0;
  uint8_t *pool, *kv;
  const uint32_t* xc;
  uint32_t* sync;
  int layer;
  int d1, d1b, d2, d2b, mode;
};
constexpr int CH_WQ = 0, CH_WO = 81920, CH_X = CH_WO + 86016, CH_M = CH_X + 20480, CH_KT = CH_X + 40960, CH_VT = CH_KT + 4096,
              CH_QK = CH_VT + 8192, CH_VP = CH_QK + 4096, CH_SX = CH_VP + 1024, CH_O = CH_SX + 2304, CH_ID = CH_O + 3072,
              CH_BAR = CH_ID + 512;
constexpr int CH_SMEM = CH_BAR + 128;
constexpr int CH_BASE = 1024;
#define CH_VK0 8
#define CH_VK1 20
#define CH_L0 4
#define CH_LR 4
#define NOX 0
#define CH_XA 0
#define CH_XB 1
#define CH_W1 3
#define CH_W2 17
#define CH_W3 26
#define CH_RA 1
#define CH_R1 4
#define CH_TW 12
__device__ __forceinline__ uint32_t opaque(uint32_t x) { return __shfl_sync(~0u, x, threadIdx.x & 31); }
__device__ __forceinline__ uint32_t nz(uint32_t x) { uint32_t r; asm("max.u32 %0, %1, 1;" : "=r"(r) : "r"(x)); return r; }
__device__ __forceinline__ uint32_t pack_tag(float lo, float hi, uint32_t tag, uint32_t mask) {
  uint32_t r;
  asm("lop3.b32 %0, %1, %2, %3, 0xD8;" : "=r"(r) : "r"(pack2(lo, hi)), "r"(tag), "r"(mask));
  return r;
}
__device__ __forceinline__ uint32_t differ(uint32_t a, uint32_t b, uint32_t t) { uint32_t r; asm("lop3.b32 %0, %1, %2, %3, 0x7E;" : "=r"(r) : "r"(a), "r"(b), "r"(t)); return r; }
__device__ __forceinline__ void mbar_wait_hot(uint32_t bar, uint32_t ph) {
  uint32_t ok;
  asm volatile("{.reg .pred p; mbarrier.try_wait.parity.shared::cta.b64 p, [%1], %2; selp.u32 %0, 1, 0, p;}" : "=r"(ok) : "r"(bar), "r"(ph) : "memory");
  if (__builtin_expect(!ok, 0)) mbar_wait(bar, ph);
}
__device__ __forceinline__ bool elect() {
  uint32_t r; asm volatile("{.reg .pred p; elect.sync _|p, 0xffffffff; selp.u32 %0, 1, 0, p;}" : "=r"(r)); return r; }
__device__ __forceinline__ uint32_t or3(uint32_t a, uint32_t b, uint32_t c) { uint32_t r; asm("lop3.b32 %0, %1, %2, %3, 0xFE;" : "=r"(r) : "r"(a), "r"(b), "r"(c)); return r; }
__device__ __forceinline__ void pin() { pdl_launch(); }
__device__ __forceinline__ void mma16h(float* d, uint32_t a0, uint32_t a2, uint32_t b0, uint32_t b1) {
  asm volatile("{.reg .b32 u, v; mma.sync.aligned.m16n8k16.row.col.f32.bf16.bf16.f32 {%0,%1,%2,%3},{%4,u,%5,v},{%6,%7},{%0,%1,%2,%3};}"
               : "+f"(d[0]), "+f"(d[1]), "+f"(d[2]), "+f"(d[3]) : "r"(a0), "r"(a2), "r"(b0), "r"(b1)); }
__device__ __forceinline__ void mma8h(float* d, uint32_t a0, uint32_t b0) {
  asm volatile("{.reg .b32 u; mma.sync.aligned.m16n8k8.row.col.f32.bf16.bf16.f32 {%0,%1,%2,%3},{%4,u},{%5},{%0,%1,%2,%3};}"
               : "+f"(d[0]), "+f"(d[1]), "+f"(d[2]), "+f"(d[3]) : "r"(a0), "r"(b0)); }
__device__ __forceinline__ uint32_t absmax2(uint32_t a, uint32_t b) { uint32_t r; asm("max.xorsign.abs.bf16x2 %0, %1, %2;" : "=r"(r) : "r"(a), "r"(b)); return r; }
__device__ __forceinline__ void until(uint32_t t) { while ((int)(clk32() - t) < 0) {} }
__device__ __forceinline__ uint4 pack8(const float* d) { return make_uint4(pack2(d[0], d[1]), pack2(d[2], d[3]), pack2(d[4], d[5]), pack2(d[6], d[7])); }
__device__ __forceinline__ void add8(float* d, uint4 v) {
  d[0] += bf_lo(v.x); d[1] += bf_hi(v.x); d[2] += bf_lo(v.y); d[3] += bf_hi(v.y);
  d[4] += bf_lo(v.z); d[5] += bf_hi(v.z); d[6] += bf_lo(v.w); d[7] += bf_hi(v.w);
}

template <int WG>
__device__ __forceinline__ void chain_body(const ChainParams& p, const uint32_t wq, const uint32_t (&ak)[80], const uint32_t (&av)[80]) {
  const int tid = threadIdx.x & 127, t4 = __shfl_sync(~0u, tid >> 5, 0), lane = tid & 31;
  const int cta = blockIdx.x, h = cta / 3, j = cta - 3 * h;
  const uint32_t sb = mapa(CH_BASE, j);
  const uint32_t bWo = sb + CH_BAR, bWq = bWo + 8, bX = bWo + 16, bXA = bWo + 24, bXB = bWo + 32, bO = bWo + 40, bG0 = bWo + 48;
  uint32_t tw[4 * CH_TW];
  auto refill = [&]() {
#pragma unroll
    for (int k = 0; k < CH_TW; k++) ldsm4t(&tw[4 * k], wq + k * 2048);
  };
  const uint32_t wo = opaque((sb + CH_WO + (WG == 0 ? (t4 + (j == 2)) * 4096 : (j == 2 ? 0 : 24576) + t4 * 1024) + ((lane & 7) + (lane >> 4) * 8) * 64 +
                              ((((lane >> 3) & 1) ^ ((lane >> 1) & 3)) << 4)) ^ (WG == 1 && j == 2 ? 32 : 0));
  const uint32_t wo2 = opaque((wo ^ ((t4 & 1) * 32)) + (4 + (t4 >> 1) - t4) * 4096);
  const uint32_t l16 = opaque(sb + lane * 16);
  const uint32_t l8 = opaque(sb + t4 * 256 + lane * 8);
  const uint32_t lw = opaque(sb + t4 * 1024 + lane * 16);
  const uint32_t qs = opaque(sb + CH_QK + WG * 2048 + t4 * 512 + lane * 16);
  const uint32_t qa = opaque(sb + CH_QK + (lane >> 4) * 2048 + (lane & 15) * 16 + (WG == 0 ? t4 * 512 + 256 : t4 == 3 ? 1024 : 0));
  const uint32_t ka = opaque(t4 < 2 ? sb + CH_KT + t4 * 512 + lane * 16
                                    : sb + CH_QK + 256 + (t4 - 2) * 1024 + ((lane >> 3) & 1) * 2048 + (lane >> 4) * 128 + (lane & 7) * 16);
  const uint32_t l4 = opaque(sb + t4 * 256 + lane * 4);
  uint32_t pdst[3], pages = 0;
  auto line0 = [&](int i) { return 28 * j + (i < 4 ? 4 * t4 + i : 12 + 2 * t4 + i); };
  const uint32_t plane = opaque((lane >> 4) * 2048 + h * 64 + (lane & 15) * 4);
  if (WG == 0) {
    pages = __ballot_sync(~0u, lds32(sb + CH_O + line0(min(lane, 5)) * 4) & 4096);
  } else {
    pages = __ballot_sync(~0u, lds32(sb + CH_O + (80 + min(lane, 11)) * 4) & 4096);
    pdst[0] = opaque(lds32(sb + CH_O + (j == 0 ? 24 + t4 : 50 + 2 * j + (t4 & 1)) * 4) + plane);
    const uint32_t role = lds32(sb + CH_O + NSLOT * 4);
    pdst[1] = opaque(lds32(sb + CH_O + role * 4) + (t4 & 1) * 2048 + (lane & 7) * 64 + (lane >> 3) * 16);
    pdst[2] = opaque((80 + role / 20) * 8192 + role % 20 * 128 + (t4 >= 2 ? (t4 & 1) * 64 + (lane & 3) * 16 + (lane >> 2) * 2 : (t4 & 1) * 4096 + lane * 4));
  }
  const uint32_t r1 = mapa(CH_BASE, j == 2 ? 0 : j + 1) - sb, r2 = mapa(CH_BASE, j == 0 ? 2 : j - 1) - sb;
  uint32_t tag = opaque(1);
  auto pool = [&](uint32_t off) { return p.pool + ((tag & 0xfffe) + off); };
  auto after = [&](uint32_t x) { return x & tag & 0xfffe; };
  auto kv = [&](int s, uint32_t a) { return p.kv + ((size_t)(cta * 2 * NSEG + s) * KV_BYTES - sb) + a; };
  auto pass = [&](float (&d)[16], const uint32_t (&a)[80]) {
    const uint64_t db = mkdesc(CH_BASE + CH_X + WG * 20480, 512, 128, 0);
    wg_fence();
#pragma unroll
    for (int k = 0; k < 20; k++) {
      wg_rs32_00(d, a[4 * k], a[4 * k + 1], a[4 * k + 2], a[4 * k + 3], db + k * 64, k);
      if (k == 19 || (WG == 1 && k == 9)) wg_commit();
    }
  };
  auto dump = [&](float (&d)[16], uint32_t a) {
    wg_wait<0>();
    reg_fence<16>(d);
    sts128(a, pack8(d)); sts128(a + 512, pack8(d + 8));
  };
  auto tokens0 = [&](int s) {
    float d[16];
    if (!NOX || s == 0) mbar_wait_hot(bXB, s & 1);
    bar_sync(7, 256);
    pass(d, ak);
    TM1(5);
    bar_sync(9, 256);
    const uint4 k0 = lds128(lw + CH_KT), k1 = lds128(lw + CH_KT + 512);
    __syncwarp();
    wg_wait<0>();
    reg_fence<16>(d);
    add8(d, k0); add8(d + 8, k1);
#pragma unroll
    for (int e = 0; e < 2; e++) { const uint4 v = pack8(d + 8 * e); stsm4t(lw + CH_KT + e * 512, v.x, v.z, v.y, v.w); }
    fence_async();
    __syncwarp();
    if (elect()) { bulk_store(p.kv + (size_t)(cta * 2 * NSEG + s) * KV_BYTES + t4 * 1024, sb + CH_KT + t4 * 1024, 1024); bulk_commit(); }
    TM1(6);
    bar_sync(8, 256);
    pass(d, av);
    TM1(9);
    bulk_wait_read<0>();
    dump(d, lw + CH_VT);
  };
  PRO(11);
  if (WG == 0) {
    tokens0(0);
  } else {
    const uint32_t* m0 = reinterpret_cast<const uint32_t*>(p.mem0) + (lane >> 2) * 320 + t4 * 80 + (lane & 3);
    uint32_t a[20];
#pragma unroll
    for (int i = 0; i < 20; i++) a[i] = m0[4 * i];
    pin();
    float d[16];
    mbar_wait(bXA, 0);
    pass(d, ak);
    bar_arrive(7, 256);
    dump(d, lw + CH_KT);
    bar_arrive(9, 256);
    pass(d, av);
    bar_arrive(8, 256);
    dump(d, lw + CH_VT + 4096);
    bar_sync(3, 128);
#pragma unroll
    for (int i = 0; i < 20; i++) sts32(sb + CH_M + (t4 * 20 + i) * 128 + lane * 4, transpose8(a[i]));
  }
  PRO(8);
  mbar_wait(bWq, 0);
  refill();
  PRO(9);
  mbar_wait(bWo, 0);
  asm volatile("barrier.cluster.wait.aligned;" ::: "memory");
  PRO(10);
  constexpr int VK = WG == 0 ? CH_VK0 : CH_VK1;
  auto project = [&](int s, uint32_t (&b)[40], float (&dv)[16], uint32_t (&kf)[16]) {
    float dq[4] = {}, dk[4] = {};
    uint32_t w[80];
#pragma unroll
    for (int i = 0; i < 4 * CH_TW; i++) w[i] = tw[i];
    auto load = [&](int n) {
      int c = 0;
#pragma unroll
      for (int i = 0; i < 10; i++) {
        if (c++ == n) ldsm4t(&b[4 * i], l16 + CH_M + WG * 5120 + i * 512);
#pragma unroll
        for (int k = 2 * i; k < 2 * i + 2; k++)
          if (k >= CH_TW && c++ == n) ldsm4t(&w[4 * k], wq + k * 2048);
      }
#pragma unroll
      for (int i = 0; i < 4; i++)
        if (WG == 1 && c++ == n) ldsm4(&kf[4 * i], ka + i * 1024);
    };
#pragma unroll
    for (int n = 0; n < CH_L0; n++) load(n);
    TM(0);
#pragma unroll
    for (int k = 0; k < 20; k += 2) {
      if (k > 0) {
#pragma unroll
        for (int n = CH_L0 + (k - 2) * CH_LR / 4; n < (k == 18 ? 40 : CH_L0 + k * CH_LR / 4); n++) load(n);
      }
      pin();
#pragma unroll
      for (int kk = k; kk < k + 2; kk++) {
        mma16(dk, ak[4 * kk], ak[4 * kk + 1], ak[4 * kk + 2], ak[4 * kk + 3], b[2 * kk], b[2 * kk + 1]);
        mma16(dq, w[4 * kk], w[4 * kk + 1], w[4 * kk + 2], w[4 * kk + 3], b[2 * kk], b[2 * kk + 1]);
        if (kk < VK) mma16(dv, av[4 * kk], av[4 * kk + 1], av[4 * kk + 2], av[4 * kk + 3], b[2 * kk], b[2 * kk + 1]);
      }
    }
    const float k2 = 0.07216878364870322f * 1.44269504089f;
    stsm4t(qs, pack2(dq[0] * k2, dq[1] * k2), pack2(dq[2] * k2, dq[3] * k2), pack2(dk[0], dk[1]), pack2(dk[2], dk[3]));
    TM(1);
  };
  constexpr int VC = VK == 20 ? 1 : WG == 0 ? 2 : 3;
  auto finish_v = [&](const uint32_t (&b)[40], float (&dv)[16]) {
#pragma unroll
    for (int kk = VK; kk < 20; kk++) mma16(dv + 4 * ((kk - VK) % VC), av[4 * kk], av[4 * kk + 1], av[4 * kk + 2], av[4 * kk + 3], b[2 * kk], b[2 * kk + 1]);
  };
  auto sum_v = [&](float (&dv)[16]) {
#pragma unroll
    for (int i = 4; i < 4 * VC; i++) dv[i & 3] += dv[i];
  };
  auto publish_km = [&](int s) {
    uint32_t a[4];
    ldsm4(a, qa);
    *reinterpret_cast<uint2*>(kv(s, l8) + KV_M) = make_uint2(hadd2(a[0], a[2]), hadd2(a[1], a[3]));
  };
  auto load_v = [&](uint4 (&vr)[4]) {
#pragma unroll
    for (int e = 0; e < 4; e++) vr[e] = lds128(lw + CH_VT + (e & 1) * 4096 + (e >> 1) * 512);
  };
  auto token_v = [&](uint4 (&v)[2], const uint4 (&vr)[4]) {
#pragma unroll
    for (int e = 0; e < 2; e++) {
      const uint4 x = vr[2 * e], y = vr[2 * e + 1];
      v[e] = make_uint4(hadd2(x.x, y.x), hadd2(x.z, y.z), hadd2(x.y, y.y), hadd2(x.w, y.w));
    }
  };
  auto memory_v = [&](uint2 x, const float (&dv)[16]) {
    return make_uint2(pack2(dv[0] + bf_lo(x.x), dv[1] + bf_hi(x.x)), pack2(dv[2] + bf_lo(x.y), dv[3] + bf_hi(x.y)));
  };
  auto publish_v = [&](int s, const uint4 (&v)[2], uint2 vm) {
#pragma unroll
    for (int e = 0; e < 2; e++) reinterpret_cast<uint4*>(kv(s, lw) + KV_V)[e * 32] = v[e];
    *reinterpret_cast<uint2*>(kv(s, l8) + KV_V + KV_M) = vm;
  };
  auto load_x = [&](int s, int k0, int n, uint32_t bar) {
    if (!NOX && elect()) { mbar_expect(bar, n * 1024); bulk_load(sb + CH_X + k0 * 1024, p.xc + (s + 1) * 10240 + k0 * 256, n * 1024, bar); }
  };
  uint32_t gph = 0;
  int st = 0;
#pragma unroll 1
  for (int s = 0; s < NSEG - 1; s++) {
    bar_sync(6, 256);
    float dv[16] = {};
    uint32_t b[40], kf[16];
    project(s, b, dv, kf);
    if (WG == 0) {
      bar_sync(1, 256);
      if (CH_XA == 0) load_x(s, 20 + 5 * t4, 5, bXA);
      if (CH_XB == 0) load_x(s, 5 * t4, 5, bXB);
      pin();
      finish_v(b, dv);
      sum_v(dv);
      sts64(l8 + CH_VP, pack2(dv[0], dv[1]), pack2(dv[2], dv[3]));
      __syncwarp();
      if (elect()) mbar_arrive(bX);
      if (CH_XA == 1) load_x(s, 20 + 5 * t4, 5, bXA);
      if (CH_XB == 1) load_x(s, 5 * t4, 5, bXB);
      uint32_t w[144];
      auto wload = [&](int i) { ldsm4t(&w[4 * i], (i % 3 == 0 ? wo : i % 3 == 1 ? wo ^ 32 : wo2) + i / 12 * 28672 + i / 3 % 4 * 1024); };
      TM(3);
#pragma unroll
      for (int i = 0; i < CH_W1; i++) wload(i);
      bar_sync(10, 256);
#pragma unroll
      for (int i = CH_W1; i < CH_W2; i++) wload(i);
      if (CH_XA == 2) load_x(s, 20 + 5 * t4, 5, bXA);
      if (CH_XB == 2) load_x(s, 5 * t4, 5, bXB);
      bar_sync(2, 256);
      {
        float y[3][4] = {};
        uint32_t ob[24];
        ldsm4(&ob[0], l16 + CH_O + 1024); ldsm4(&ob[4], l16 + CH_O + 1536);
        TM(7);
        auto step = [&](int i) {
          const int k = i / 3;
          mma16(y[i % 3], w[4 * i], w[4 * i + 1], w[4 * i + 2], w[4 * i + 3], ob[2 * k], ob[2 * k + 1]);
        };
#pragma unroll
        for (int i = 0; i < 12; i++) {
          step(i);
          if (i >= 12 - (CH_W3 - CH_W2)) wload(CH_W3 - 12 + i);
          if (i % 3 == 2) pin();
        }
        if (CH_XB == 3) load_x(s, 5 * t4, 5, bXB);
        pin();
        mbar_wait(bO, s & 1);
        TM(4);
        ldsm4(&ob[8], l16 + CH_O); ldsm4(&ob[12], l16 + CH_O + 512);
        pin();
        float2 inv;
        uint8_t* dst[6];
        uint32_t mask;
#pragma unroll
        for (int i = 12; i < 36; i++) {
          step(i);
          const int n = CH_W3 + i - 13, m = n - (n > 30);
          if (i == 12) ldsm4(&ob[16], l16 + after(w[4 * CH_W3 - 1] | w[4 * CH_W3 - 5] | w[4 * CH_W3 - 9] | ob[8]) + CH_O + 2048);
          else if (n == 30) ldsm4(&ob[20], l16 + CH_O + 2560);
          else if (m < 36) wload(m);
          else if (m == 36) inv = lds64f((l8 & ~0xe0u) + CH_VP);
          if (i == 26) mask = ((l16 ^ tag) & 48) == 0;
          if (i >= 27 && i < 33) dst[i - 27] = pool(line0(i - 27) * 8192 + (pages >> (i - 27) & 1) * 4096) + plane;
          if (i % 3 == 2) pin();
        }
#pragma unroll
        for (int k = 0; k < CH_R1; k++) ldsm4t(&tw[4 * k], wq + k * 2048);
        pin();
#pragma unroll
        for (int i = 0; i < 6; i++) stg_strong32(dst[i], pack_tag(y[i >> 1][2 * (i & 1)] * inv.x, y[i >> 1][2 * (i & 1) + 1] * inv.y, tag, mask));
        TM(8);
        bar_arrive(5, 256);
        pin();
#pragma unroll
        for (int k = CH_R1; k < CH_TW; k++) ldsm4t(&tw[4 * k], wq + k * 2048);
      }
      publish_km(s);
      if (t4 == 3 && cta < 40 && s + 4 < NSEG && elect())
        asm volatile("cp.async.bulk.prefetch.L2.global [%0], 1024;" :: "l"(p.xc + (s + 4) * 10240 + cta * 256) : "memory");
      if (t4 == 2 && (s & 3) == 0 && s > 0 && elect()) red_relaxed(p.sync + 2 * s - 4, 1);
      if (t4 == 2 && s == NSEG - 3 && cta == 95 && elect()) red_relaxed(p.sync + 2 * s + 2, 0x10000);
      tokens0(s + 1);
      TM(2);
    } else {
      const uint32_t xo = l4 + (CH_SX - (t4 == 3 ? 128 : 0)), x1 = xo + (r1 + 768 + min(t4, 2) * 256), x2 = xo + (r2 + 1024 + min(t4, 2) * 256);
      if (t4 < 2) {
        float ds[4][4] = {};
        uint32_t q[16];
        asm volatile("bar.sync 1, 256;" ::: "memory");
#pragma unroll
        for (int k = 0; k < 4; k++) ldsm4(&q[4 * k], qa + k * 512);
        pin();
        if (VK < 20) { finish_v(b, dv); pin(); }
#pragma unroll
        for (int k = 0; k < 4; k++) {
          mma16(ds[k & 1], kf[4 * k], kf[4 * k + 1], kf[4 * k + 2], kf[4 * k + 3], q[4 * k], q[4 * k + 1]);
          mma16(ds[2 + (k & 1)], kf[4 * k], kf[4 * k + 1], kf[4 * k + 2], kf[4 * k + 3], q[4 * k + 2], q[4 * k + 3]);
        }
        float t[4];
#pragma unroll
        for (int i = 0; i < 4; i++) t[i] = (ds[0][i] + ds[2][i]) + (ds[1][i] + ds[3][i]);
        const uint32_t w0 = pack2(t[0], t[1]), w1 = pack2(t[2], t[3]);
        st_async32(x1, w0, bX + r1); st_async32(x2, w0, bX + r2);
        st_async32(x1 + 128, w1, bX + r1); st_async32(x2 + 128, w1, bX + r2);
        sts32(xo, w0); sts32(xo + 128, w1);
      } else {
        float ds[4][4] = {};
        uint32_t q0[4], q1[4], a0[4], a1[4];
        asm volatile("bar.sync 1, 256; " ::: "memory");
        ldsm4(a0, ka); ldsm4(q0, qa); ldsm4(a1, ka + 512); ldsm4(q1, qa + 512);
        pin();
        if (VK < 20) { finish_v(b, dv); pin(); }
        mma16(ds[0], a0[0], a0[1], a0[2], a0[3], q0[0], q0[1]);
        mma16(ds[1], a0[0], a0[1], a0[2], a0[3], q0[2], q0[3]);
        mma16(ds[2], a1[0], a1[1], a1[2], a1[3], q1[0], q1[1]);
        mma16(ds[3], a1[0], a1[1], a1[2], a1[3], q1[2], q1[3]);
        float t[2];
#pragma unroll
        for (int i = 0; i < 2; i++)
          t[i] = ((ds[0][i] + ds[0][i + 2]) + (ds[1][i] + ds[1][i + 2])) + ((ds[2][i] + ds[2][i + 2]) + (ds[3][i] + ds[3][i + 2]));
        const uint32_t w0 = pack2(t[0], t[1]);
        st_async32(x1, w0, bX + r1);
        st_async32(x2, w0, bX + r2);
        sts32(xo, w0);
      }
      TM(3);
      const uint4 id = lds128(l16 + CH_ID);
      float sc[3][4] = {};
      uint4 v[2], vr[4];
      sum_v(dv);
      bar_sync(3, 128);
      uint32_t r[12], wd[12];
      ldsm4(&r[0], l16 + CH_SX); ldsm2(&r[4], l16 + CH_SX + 512);
      pin();
      load_v(vr);
#pragma unroll
      for (int u = 0; u < 3; u++) ldsm4t(&wd[4 * u], wo + u * 28672);
      pin();
#pragma unroll
      for (int q = 0; q < 3; q++) mma16(sc[q], id.x, id.y, id.z, id.w, r[2 * q], r[2 * q + 1]);
      uint32_t big = absmax2(absmax2(absmax2(r[0], r[1]), absmax2(r[2], r[3])), absmax2(r[4], r[5]));
      token_v(v, vr);
      const uint32_t oa1 = l4 + (r1 + CH_O), oa2 = l4 + (r2 + CH_O + 2048), ones = 0x3f803f80u;
      mbar_wait_hot(bX, s & 1);
      TM(4);
      ldsm4(&r[0], l16 + CH_SX + 768); ldsm4(&r[8], l16 + CH_SX + 1792); ldsm4(&r[4], l16 + CH_SX + 1280);
      const uint2 vp = lds64(l8 + CH_VP);
      bar_arrive(10, 256);
      pin();
      {
        float sd[3][4] = {};
#pragma unroll
        for (int i = 0; i < 3; i++) {
          const int q = i == 0 ? 0 : 3 - i;
          mma16(sc[q], id.x, id.y, id.z, id.w, r[4 * q], r[4 * q + 1]);
          mma16(sd[q], id.x, id.y, id.z, id.w, r[4 * q + 2], r[4 * q + 3]);
          big = absmax2(big, absmax2(absmax2(r[4 * q], r[4 * q + 1]), absmax2(r[4 * q + 2], r[4 * q + 3])));
        }
#pragma unroll
        for (int i = 0; i < 12; i++) sc[i >> 2][i & 3] += sd[i >> 2][i & 3];
      }
      const bool redo = __any_sync(~0u, (absmax2(big, big << 16) & 0x7fff0000u) >= 0x41800000u);
      const uint2 vm = memory_v(vp, dv);
      sc[2][0] += sc[2][2]; sc[2][1] += sc[2][3];
      float l[4], o[2][4];
      uint32_t p3, p4;
      auto attend = [&]() {
#pragma unroll
        for (int i = 0; i < 4; i++) l[i] = o[0][i] = o[1][i] = 0.f;
        const uint32_t p1 = pack2(ex2(sc[0][0]), ex2(sc[0][1])), p2 = pack2(ex2(sc[0][2]), ex2(sc[0][3]));
        mma16h(o[0], p1, p2, v[0].x, v[0].y);
        mma16h(o[1], p1, p2, v[0].z, v[0].w);
        mma16h(l, p1, p2, ones, ones);
        const uint32_t p0 = pack2(ex2(sc[2][0]), ex2(sc[2][1]));
        mma8h(o[0], p0, vm.x);
        mma8h(o[1], p0, vm.y);
        mma8h(l, p0, ones);
        p3 = pack2(ex2(sc[1][0]), ex2(sc[1][1])); p4 = pack2(ex2(sc[1][2]), ex2(sc[1][3]));
        mma16h(o[0], p3, p4, v[1].x, v[1].y);
        mma16h(o[1], p3, p4, v[1].z, v[1].w);
      };
      attend();
      if (__builtin_expect(redo, 0)) {
        float mx = fmaxf(sc[2][0], sc[2][1]);
#pragma unroll
        for (int i = 0; i < 4; i++) mx = fmaxf(mx, fmaxf(sc[0][i], sc[1][i]));
        mx = fmaxf(mx, __shfl_xor_sync(~0u, mx, 1));
        mx = fmaxf(mx, __shfl_xor_sync(~0u, mx, 2));
#pragma unroll
        for (int i = 0; i < 4; i++) { sc[0][i] -= mx; sc[1][i] -= mx; }
        sc[2][0] -= mx; sc[2][1] -= mx;
        attend();
      }
      const uint32_t o0 = pack2(o[0][0], o[0][1]), o1 = pack2(o[1][0], o[1][1]);
      st_async32(oa1, o0, bO + r1); st_async32(oa2, o0, bO + r2);
      st_async32(oa1 + 128, o1, bO + r1); st_async32(oa2 + 128, o1, bO + r2);
      sts32(l4 + CH_O + 1024, o0); sts32(l4 + CH_O + 1152, o1);
      bar_arrive(2, 256);
      pin();
      TM(6);
      mma16h(l, p3, p4, ones, ones);
      float inv;
      asm("rcp.approx.ftz.f32 %0, %1;" : "=f"(inv) : "f"(l[0]));
      sts32((l8 & ~0xffu) + (lane & 28) + CH_VP, __float_as_uint(inv));
      __syncwarp();
      if (elect()) mbar_arrive(bO);
      {
        float z[2][4] = {}, y[2][4] = {};
        uint32_t we[12] = {};
        mma16(z[0], wd[0], wd[1], wd[2], wd[3], o0, o1);
        if (j == 0) {
#pragma unroll
          for (int u = 0; u < 3; u++) ldsm4t(&we[4 * u], (wo ^ 32) + u * 28672);
          mma16(y[0], we[0], we[1], we[2], we[3], o0, o1);
        }
        const float2 iv = lds64f((l8 & ~0xe0u) + CH_VP);
        uint8_t* dst = pool(pdst[0]);
        const uint32_t mask = ((l16 ^ tag) & 48) == 0;
        const uint32_t oa = qa + ((tag & 0xfffe) + CH_O - CH_QK + t4 * 256 - (t4 == 3 ? 1024 : 0));
        const uint32_t za = l16 + ((tag & 0xfffe) + (t4 >> 1) * 512 + (t4 & 1) * 8);
        pin();
        mbar_wait(bO, s & 1);
        uint32_t a[4];
        ldsm4(a, oa);
        mma16(z[0], wd[4], wd[5], wd[6], wd[7], a[0], a[1]);
        mma16(z[1], wd[8], wd[9], wd[10], wd[11], a[2], a[3]);
        if (j == 0) {
          mma16(y[0], we[4], we[5], we[6], we[7], a[0], a[1]);
          mma16(y[1], we[8], we[9], we[10], we[11], a[2], a[3]);
          sts128f(lw + CH_VT + 512, y[0][0] + y[1][0], y[0][1] + y[1][1], y[0][2] + y[1][2], y[0][3] + y[1][3]);
        }
        sts128f(lw + CH_VT, z[0][0] + z[1][0], z[0][1] + z[1][1], z[0][2] + z[1][2], z[0][3] + z[1][3]);
        bar_sync(3, 128);
        if (j == 0 || t4 < 2) {
          float2 q[4];
#pragma unroll
          for (int i = 0; i < 4; i++) q[i] = lds64f(za + CH_VT + i * 1024);
          stg_strong32(dst, pack_tag(((q[0].x + q[1].x) + (q[2].x + q[3].x)) * iv.x, ((q[0].y + q[1].y) + (q[2].y + q[3].y)) * iv.y, tag, mask));
        }
      }
      TM(2);
      float d[16];
      bar_sync(5, 256);
      publish_v(s, v, vm);
#pragma unroll
      for (int k = 0; k < CH_RA; k++) ldsm4t(&tw[4 * k], wq + k * 2048);
      if (t4 == 0 && s + 2 < NSEG && elect()) { mbar_expect(bX, 1536); mbar_expect(bO, 2048); }
      if (!NOX) mbar_wait_hot(bXA, (s + 1) & 1);
      uint8_t* mdst = p.pool + ((t4 >= 2 ? st : st == 2 ? 0 : st + 1) * 32768 + pdst[2]);
      const uint8_t* psrc = pool(pdst[1] + after(tw[4 * CH_RA - 1]));
      pin();
      pass(d, ak);
      bar_arrive(7, 256);
      TM(5);
      if (t4 >= 2) {
        uint4 u[4];
        DELAY(p.d1);
#pragma unroll
        for (int i = 0; i < 4; i++) u[i] = ldg_strong128(psrc + i * 512);
        __syncwarp();
        dump(d, lw + CH_KT);
        bar_arrive(9, 256);
        TM(14);
        TMD(15, u[3].x);
        const uint32_t one = lane & 4 ? 0x3f800000u : 0x00003f80u, g2 = lane >> 3;
        int n = 0;
        float y[4][4];
        for (;;) {
#pragma unroll
          for (int i = 0; i < 4; i++) y[0][i] = y[1][i] = y[2][i] = y[3][i] = 0.f;
#pragma unroll
          for (int i = 0; i < 4; i++) {
            mma16h(y[i & 1], g2 == 0 ? one : 0, g2 == 1 ? one : 0, u[i].x, u[i].y);
            mma16h(y[2 + (i & 1)], g2 == 2 ? one : 0, g2 == 3 ? one : 0, u[i].z, u[i].w);
          }
          if (__builtin_expect(!__any_sync(~0u, (differ(u[0].x, u[1].x, tag) | differ(u[2].x, u[3].x, tag)) & 1), 1)) break;
#pragma unroll
          for (int i = 0; i < 4; i++) u[i] = ldg_strong128(psrc + i * 512);
          spin_guard(n);
        }
        const float v = ((y[0][0] + y[0][1]) + (y[2][0] + y[2][1])) + ((y[1][0] + y[1][1]) + (y[3][0] + y[3][1]));
        const uint32_t w = nz(pack2(v, 0.f));
        stg_strong16(mdst, w); stg_strong16(mdst + 4096, w);
        TMV(12, 32, n);
      } else {
        dump(d, lw + CH_KT);
        bar_arrive(9, 256);
        stg_strong32(mdst, 0u);
      }
      TM(8);
      bar_sync(3, 128);
      pass(d, av);
      bar_arrive(8, 256);
      TM(7);
      const uint32_t bG = bG0 + t4 * 8, mq = sb + CH_M + t4 * 2560;
      const uint8_t* msrc = p.pool + ((80 + st * 4 + t4) * 8192 + (pages >> (st * 4 + t4) & 1) * 4096);
      wg_wait<1>();
      bar_sync(3, 128);
      DELAY(p.d2);
      if (elect()) { mbar_expect(bG, 2560); bulk_load(mq, msrc, 2560, bG); }
      TM(9);
      dump(d, lw + CH_VT + 4096);
#pragma unroll
      for (int k = CH_RA; k < CH_TW; k++) ldsm4t(&tw[4 * k], wq + k * 2048);
      TM(10);
      int n = 0;
      for (;;) {
        mbar_wait(bG, gph);
        gph ^= 1;
        const uint32_t c = mq + lane * 32 + (lane >> 2) * 4;
        if (!__any_sync(~0u, __vimin3_u32(lds32(c), lds32(c + 1024), lds32(c + 1536)) == 0)) break;
        if (elect()) { mbar_expect(bG, 2560); bulk_load(mq, msrc, 2560, bG); }
        spin_guard(n);
      }
      TM(11);
      TMV(13, 32, n);
    }
    if (++st == 3) st = 0;
    tag ^= 0x10001;
  }
  {
    const int s = NSEG - 1;
    bar_sync(6, 256);
    float dv[16] = {};
    uint32_t b[40], kf[16];
    project(s, b, dv, kf);
    finish_v(b, dv);
    sum_v(dv);
    if (WG == 0) {
      sts64(l8 + CH_VP, pack2(dv[0], dv[1]), pack2(dv[2], dv[3]));
      bar_sync(1, 256);
      publish_km(s);
      bulk_wait<0>();
      fence_async_global();
      bar_sync(2, 256);
      if (tid == 0) red_release(g_sync + 15 * 8 + 4, 1);
    } else {
      uint4 v[2], vr[4];
      load_v(vr);
      token_v(v, vr);
      bar_sync(1, 256);
      publish_v(s, v, memory_v(lds64(l8 + CH_VP), dv));
      bar_arrive(2, 256);
    }
  }
}

__global__ void __launch_bounds__(256, 1) chain_kernel(const __grid_constant__ ChainParams p) {
  extern __shared__ __align__(1024) uint8_t smem_raw[];
  const uint32_t sb = s2u(smem_raw);
  const int tid = threadIdx.x, warp = __shfl_sync(~0u, tid >> 5, 0), lane = tid & 31;
  const int cta = blockIdx.x, h = cta / 3, j = cta - 3 * h, colbase = cta * 64;
  const uint32_t bWo = sb + CH_BAR, bWq = bWo + 8, bXA = bWo + 24, bWk = bWo + 80, bWv = bWo + 88;
  uint32_t smid; asm("mov.u32 %0, %%smid;" : "=r"(smid));
  PRO(0);
  if (sb != mapa(CH_BASE, j)) __trap();
  uint32_t entry = 0;
  auto place = [&]() {
    const int i = tid - 128;
    if (i >= 0 && i <= NSLOT) {
      const uint32_t side = ldg_strong32(g_smpart + (smid & 255));
      if (i < NSLOT) {
        entry = i * 8192 + (ldg_strong32(g_orient + i) == (i < 80 ? i & 1 : side) ? 0 : 4096);
      } else {
        const uint32_t t = atomicAdd(g_bo + p.layer * 128 + 1 + side, 1);
        entry = t < 40 ? 2 * t + side : 2 * (79 - min(t, 79u)) + 1 - side;
      }
    }
    __syncwarp();
  };
  if (p.layer) place();
  if (warp == 0 && elect()) {
#pragma unroll 1
    for (int i = 0; i < 12; i++) mbar_init(bWo + 8 * i, i == 2 || i == 5 ? 5 : i == 3 || i == 4 ? 4 : 1);
    asm volatile("fence.mbarrier_init.release.cluster;" ::: "memory");
    mbar_expect(bWk, 81920);
    tma_load3<(WEF & 1) != 0>(sb + CH_WQ, &p.wk, colbase, 0, bWk);
    mbar_expect(bWv, 81920);
    tma_load3<(WEF & 1) != 0>(sb + CH_WO, &p.wv, colbase, 0, bWv);
    mbar_expect(bWo + 16, 1536);
    mbar_expect(bWo + 40, 2048);
    mbar_expect(bWo, 86016); mbar_expect(bWq, 81920);
#pragma unroll 1
    for (int i = 0; i < 8; i++) mbar_expect(bXA + 8 * (i & 1), 5120);
  }
  if (warp == 1) {
    const uint32_t id = (lane >> 3) == (lane & 3) ? ((lane & 4) ? 0x3f800000u : 0x00003f80u) : 0u;
    sts128(sb + CH_ID + lane * 16, make_uint4(id, 0, 0, id));
  }
  __syncthreads();
  asm volatile("barrier.cluster.arrive.relaxed.aligned;" ::: "memory");
  uint32_t ak[80], av[80];
  const uint32_t wq = opaque(sb + CH_WQ + ((warp >> 2) * 320 + (lane & 7) + (lane >> 4) * 8) * 128 + (((2 * (warp & 3) + ((lane >> 3) & 1)) ^ (lane & 7)) << 4));
  pdl_wait();
  if (tid == 32) stg_strong32(g_smuse + (smid & 255), p.layer + 1);
  pdl_launch();
  PRO(1);
  if (warp == 0 && elect()) {
    bulk_load(sb + CH_X + 20480, p.xc + 5120, 20480, bXA);
    bulk_load(sb + CH_X, p.xc, 20480, bXA + 8);
  }
  if (!p.layer) place();
  __syncwarp();
  PRO(2);
  mbar_wait(bWk, 0);
  PRO(3);
#pragma unroll
  for (int k = 0; k < 20; k++) ldsm4t(&ak[4 * k], wq + k * 2048);
  bar_sync(6, 256);
  if (warp == 0 && elect()) tma_load3<(WEF & 2) != 0>(sb + CH_WQ, &p.wq, colbase, 0, bWq);
  __syncwarp();
  PRO(4);
  mbar_wait(bWv, 0);
  PRO(5);
#pragma unroll
  for (int k = 0; k < 20; k++) ldsm4t(&av[4 * k], wq + CH_WO + k * 2048);
  bar_sync(6, 256);
  PRO(6);
  if (warp >= 5 && elect()) tma_load3<(WEF & 2) != 0>(sb + CH_WO + (warp - 5) * 28672, &p.wo, j == 0 ? 0 : 32 + j * 192, h * 192 + (j + 8 - warp) % 3 * 64, bWo);
  if (tid >= 128 && tid <= 128 + NSLOT) sts32(sb + CH_O + (tid - 128) * 4, entry);
  PRO(7);
  __syncthreads();
  if (__shfl_sync(~0u, tid >> 7, 0) == 0) chain_body<0>(p, wq, ak, av); else chain_body<1>(p, wq, ak, av);
}

struct PostParams { CUtensorMap wq, wo, wb, wo2, wb2; int gap, share, layer; };
constexpr int PS = 8, PB = 28672;
constexpr int OP_SMEM = PS * PB + 512 + 2048;
enum { IT_ATT = 0, IT_OP = 1, IT_FIN = 2, IT_BQ = 3, IT_Q = 4 };

__device__ __forceinline__ uint32_t item_count(int type, int b) {
  return type == IT_ATT ? 32 : type == IT_OP ? op_split(b) * (DM / op_width(b)) : type == IT_FIN ? fin_items(b) : 1920 / bq_width(b); }
__device__ __forceinline__ uint32_t item_need(int type, int b) { return type == IT_ATT ? 96 : item_count(type - 1, b); }

struct Ring {
  uint32_t sb, bars; int st; uint32_t ph;
  __device__ __forceinline__ uint32_t wait() const { mbar_wait(bars + 8 * st, ph); return sb + st * PB; }
  __device__ __forceinline__ void next() { if (++st == PS) { st = 0; ph ^= 1; } }
  __device__ __forceinline__ void release(int s) const { if ((threadIdx.x & 31) == 0) mbar_arrive(bars + 8 * (PS + s)); }
  __device__ __forceinline__ void pop() { __syncwarp(); release(st); next(); }
};

template <int N>
__device__ __forceinline__ void gemm_item(Ring& r, float* d, int nst, uint32_t go, int go_at) {
  int prev = 0;
#pragma unroll 1
  for (int kb = 0; kb < nst; kb++) {
    const uint32_t base = r.wait();
    const uint64_t da = mkdesc(base + (threadIdx.x >> 7) * 4096, 128, 512, 0), db = mkdesc(base + 8192, 4096, 1024, 1);
    wg_fence();
#pragma unroll
    for (int kk = 0; kk < 2; kk++) {
      if (N == 80) wg_ss80_01(d, da + kk * 16, db + kk * 128, (kb | kk) != 0);
      if (N == 160) wg_ss160_01(d, da + kk * 16, db + kk * 128, (kb | kk) != 0);
      if (N >= 192) wg_ss192_01(d, da + kk * 16, db + kk * 128, (kb | kk) != 0);
      if (N == 320) wg_ss128_01(d + 96, da + kk * 16, db + kk * 128 + 3 * 256, (kb | kk) != 0);
    }
    wg_commit();
    if (kb == go_at && threadIdx.x == 0) mbar_arrive(go);
    if (kb > 0) { wg_wait<1>(); r.release(prev); }
    prev = r.st;
    r.next();
  }
  wg_wait<0>();
  reg_fence<N / 2>(d);
  r.release(prev);
}

template <int HALF>
__device__ __forceinline__ void attn_a_warp(Ring& r, const uint32_t (&q)[48], int b, int h) {
  constexpr int NT = HALF ? 5 : 3;
  const int lane = threadIdx.x & 31, g = lane >> 2, c = lane & 3, seg = (threadIdx.x >> 5) & 3;
  float sc[2][NT][4] = {};
#pragma unroll
  for (int u = 0; u < 3; u++) {
    const uint32_t kv = r.wait() + seg * KV_BYTES;
    uint2 km[4];
    uint32_t kb[4][4 + 4 * HALF];
#pragma unroll
    for (int kk = 0; kk < 4; kk++) {
      km[kk] = lds64(kv + KV_M + kk * 256 + lane * 8);
#pragma unroll
      for (int t = 0; t <= HALF; t++) ldsm4(&kb[kk][4 * t], kv + kk * 1024 + t * 512 + (lane & 8) * 32 + (lane & 16) * 8 + (lane & 7) * 16);
    }
    pdl_launch();
#pragma unroll
    for (int kk = 0; kk < 4; kk++) {
      const uint32_t* a = &q[16 * u + 4 * kk];
      mma16(sc[kk & 1][0], a[0], a[1], a[2], a[3], km[kk].x, km[kk].y);
#pragma unroll
      for (int n = 1; n < NT; n++) mma16(sc[kk & 1][n], a[0], a[1], a[2], a[3], kb[kk][2 * n - 2], kb[kk][2 * n - 1]);
    }
    r.pop();
  }
  float s[NT][4];
#pragma unroll
  for (int i = 0; i < 4 * NT; i++) s[i >> 2][i & 3] = sc[0][i >> 2][i & 3] + sc[1][i >> 2][i & 3];
  const float k2 = 0.07216878364870322f * 1.44269504089f, NEG = -INFINITY;
  if (2 * c > g) { s[NT - 2][0] = NEG; s[NT - 1][2] = NEG; }
  if (2 * c + 1 > g) { s[NT - 2][1] = NEG; s[NT - 1][3] = NEG; }
  s[NT - 1][0] = s[NT - 1][1] = NEG;
  uint32_t pp[NT][2]; float inv[2];
#pragma unroll
  for (int hh = 0; hh < 2; hh++) {
    float m = NEG, l = 0.f;
#pragma unroll
    for (int n = 0; n < NT; n++) m = fmaxf(m, fmaxf(s[n][2 * hh], s[n][2 * hh + 1]));
    m = fmaxf(m, __shfl_xor_sync(~0u, m, 1)); m = fmaxf(m, __shfl_xor_sync(~0u, m, 2));
#pragma unroll
    for (int n = 0; n < NT; n++) { const float x = ex2((s[n][2 * hh] - m) * k2), y = ex2((s[n][2 * hh + 1] - m) * k2); l += x + y; pp[n][hh] = pack2(x, y); }
    l += __shfl_xor_sync(~0u, l, 1); l += __shfl_xor_sync(~0u, l, 2);
    inv[hh] = 1.f / l;
  }
  uint32_t* dst = g_o + ((b * 192 + h * 6) * 16 + seg * 4 + HALF * 2) * 128 + lane;
#pragma unroll 1
  for (int u = 0; u < 3; u++) {
    const uint32_t kv = r.wait() + seg * KV_BYTES;
    uint2 vm[4];
    uint4 vb[4][1 + HALF];
#pragma unroll
    for (int w = 0; w < 4; w++) {
      vm[w] = lds64(kv + KV_M + w * 256 + lane * 8);
#pragma unroll
      for (int t = 0; t <= HALF; t++) vb[w][t] = lds128(kv + w * 1024 + t * 512 + lane * 16);
    }
    pdl_launch();
    float o[8][4] = {};
#pragma unroll
    for (int w = 0; w < 4; w++) { mma8(o[2 * w], pp[0][0], pp[0][1], vm[w].x); mma8(o[2 * w + 1], pp[0][0], pp[0][1], vm[w].y); }
#pragma unroll
    for (int t = 0; t <= HALF; t++)
#pragma unroll
      for (int w = 0; w < 4; w++) {
        mma16(o[2 * w], pp[1 + 2 * t][0], pp[1 + 2 * t][1], pp[2 + 2 * t][0], pp[2 + 2 * t][1], vb[w][t].x, vb[w][t].y);
        mma16(o[2 * w + 1], pp[1 + 2 * t][0], pp[1 + 2 * t][1], pp[2 + 2 * t][0], pp[2 + 2 * t][1], vb[w][t].z, vb[w][t].w);
      }
    r.pop();
#pragma unroll
    for (int n = 0; n < 8; n++) {
      dst[(n >> 2) * 2048 + (n & 3) * 32] = pack2(o[n][0] * inv[0], o[n][1] * inv[0]);
      dst[(n >> 2) * 2048 + (n & 3) * 32 + 128] = pack2(o[n][2] * inv[1], o[n][3] * inv[1]);
    }
    dst += 4096;
  }
}

template <int NG>
__device__ __forceinline__ void fin_item(Ring& r, uint32_t scratch, int b, int idx) {
  const int warp = threadIdx.x >> 5, lane = threadIdx.x & 31;
  float4* x = g_x + ((b * 16 + idx * NG) * 40 + warp * 5) * 32 + lane;
  float4 v[NG][5];
#pragma unroll
  for (int g = 0; g < NG; g++) {
    const uint32_t base = r.wait();
#pragma unroll
    for (int i = 0; i < 5; i++) v[g][i] = lds128f(base + ((warp * 5 + i) * 32 + lane) * 16);
    r.pop();
  }
#pragma unroll 1
  for (int k = 0; k < op_split(b); k += NG == 1 ? 2 : 1) {
#pragma unroll
    for (int g = 0; g < NG; g += 2) {
      const uint32_t base = r.wait();
#pragma unroll
      for (int i = 0; i < 10; i++) {
        const uint2 q = lds64(base + ((i / 5 * 40 + warp * 5 + i % 5) * 32 + lane) * 8);
        float4& t = v[(g + i / 5) % NG][i % 5];
        t.x += bf_lo(q.x); t.y += bf_hi(q.x); t.z += bf_lo(q.y); t.w += bf_hi(q.y);
      }
      r.pop();
    }
  }
  float mean[NG], rs[NG];
  ln_stats<NG>(v, scratch, mean, rs);
#pragma unroll
  for (int i = 0; i < 5; i++) {
    const int u = warp * 5 + i;
    uint32_t* xn = g_xn + ((b * 20 + (u >> 1)) * 16 + idx * NG) * 128 + (u & 1) * 64 + lane;
#pragma unroll
    for (int g = 0; g < NG; g++) {
      xn[g * 128] = pack2((v[g][i].x - mean[g]) * rs[g], (v[g][i].y - mean[g]) * rs[g]);
      xn[g * 128 + 32] = pack2((v[g][i].z - mean[g]) * rs[g], (v[g][i].w - mean[g]) * rs[g]);
    }
  }
#pragma unroll
  for (int g = 0; g < NG; g++)
#pragma unroll
    for (int i = 0; i < 5; i++) x[(g * 40 + i) * 32] = v[g][i];
}

__global__ void __launch_bounds__(384, 1) post_kernel(const __grid_constant__ PostParams p) {
  extern __shared__ __align__(1024) uint8_t smem_raw[];
  const uint32_t sb = s2u(smem_raw), bars = sb + PS * PB;
  const uint32_t bIF = bars + 128, bIE = bars + 160, done = bars + 192, bGo = bars + 224, slots = bars + 240, scratch = bars + 512;
  const int warp = __shfl_sync(~0u, threadIdx.x >> 5, 0), lane = threadIdx.x & 31;
  TRACE(0);
  pdl_launch();
  if (sb & 1023) __trap();
  if (threadIdx.x < 29) mbar_init(bars + 8 * threadIdx.x, threadIdx.x < 8 ? 1 : threadIdx.x < 16 ? 8 : threadIdx.x < 20 ? 1 : threadIdx.x < 24 ? 2 : threadIdx.x < 28 ? 8 : 1);
  fence_async();
  __syncthreads();
  if (warp >= 8) {
    asm volatile("setmaxnreg.dec.sync.aligned.u32 56;");
    if (warp == 9) {
      const int b = lane & 15;
      bool queries = QA_END < 16;
      for (int n = 0;; n++) {
        if (n > 0) mbar_wait(bGo, (n - 1) & 1);
        mbar_wait(bIE + 8 * (n & 3), ((n >> 2) & 1) ^ 1);
        int code = -1, spin = 0, ticket = 0;
        if (queries) {
          if (lane == 0) ticket = atomicAdd(g_sync + SY_QC, 1);
          ticket = __shfl_sync(~0u, ticket, 0);
          queries = ticket < (16 - QA_END) * 32;
          if (queries) code = IT_Q << 16 | (QA_END + ticket % (16 - QA_END)) << 8 | ticket / (16 - QA_END);
        }
        if (!queries && lane == 0) ticket = atomicAdd(g_sync + SY_T, 1);
        while (!queries) {
          const uint4 hd = ldg_strong128(g_sync + b * 8), pr = ldg_strong128(g_sync + b * 8 + 4);
          const uint32_t hv[4] = {hd.x, hd.y, hd.z, hd.w}, pv[4] = {pr.x, pr.y, pr.z, pr.w};
          const uint32_t chain_done = __ballot_sync(~0u, (pr.x & 0xffff) >= 96);
          int left[4], avail[4], rdy = 0, claimed = 0, upstream = 0;
#pragma unroll
          for (int t = 0; t < 4; t++) {
            const int cnt = lane < 16 ? item_count(t, b) : 0;
            left[t] = max(cnt - (int)hv[t], 0);
            claimed += cnt - left[t];
            const bool ready = (pv[t] & 0xffff) >= item_need(t, b);
            rdy |= ready << t;
            bool ok = ready || (t == IT_ATT ? pr.x >= 0x10000 : !upstream || (t == IT_OP && (chain_done >> 15 & 1)));
            if (t == IT_BQ && (chain_done >> 12 & 9) == 1) ok = false;
            avail[t] = ok ? left[t] : 0;
            upstream |= __any_sync(~0u, left[t] > 0);
          }
          if (!upstream) break;
          int rank = max(__shfl_sync(~0u, ticket, 0) - __reduce_add_sync(~0u, claimed), 0), type = -1, mine = 0;
#pragma unroll
          for (int c = 0; c < 7; c++) {
            const int t = c == 0 || c == 4 ? IT_FIN : c == 1 || c == 6 ? IT_ATT : c == 2 ? IT_OP : IT_BQ;
            int a = c == 1 || c == 2 || ((rdy >> t & 1) == (c < 4)) ? avail[t] : 0;
            if (c == 6) a = b < QA_END && !(rdy & 1) && ((chain_done << 1 | 1) >> b & 1) ? left[t] : 0;
            const int tot = __reduce_add_sync(~0u, a);
            if (type < 0) { if (rank < tot) { type = t; mine = a; } else rank -= tot; }
          }
          if (type >= 0) {
#pragma unroll
            for (int o = 1; o < 16; o <<= 1) { const int y = __shfl_up_sync(~0u, mine, o); if (lane >= o) mine += y; }
            const int blk = __ffs(__ballot_sync(~0u, mine > rank)) - 1;
            const int early = !(__shfl_sync(~0u, rdy, blk) >> type & 1);
            uint32_t idx = 0;
            if (lane == 0) { idx = atomicAdd(g_sync + blk * 8 + type, 1); ld_acquire(g_sync + blk * 8 + 4 + type); }
            idx = __shfl_sync(~0u, idx, 0);
            if (idx < item_count(type, blk)) { code = (chain_done >> 15 & 1) << 22 | (chain_done >> 13 & 1) << 21 | early << 20 | type << 16 | blk << 8 | idx; break; }
          } else {
            __nanosleep(50);
          }
          spin_guard(spin);
        }
        if (lane == 0) {
          fence_async_global();
          sts32(slots + 4 * (n & 3), code);
          mbar_arrive(bIF + 8 * (n & 3));
        }
        __syncwarp();
        if (code < 0) break;
      }
    } else if (warp == 8) {
      uint32_t smid, nsm, peers = 0;
      asm("mov.u32 %0, %%smid;" : "=r"(smid)); asm("mov.u32 %0, %%nsmid;" : "=r"(nsm));
      for (uint32_t i = lane; i < min(nsm, 256u); i += 32)
        peers += abs((int)(g_smclk[i] - g_smclk[smid & 255])) < 4000 && ldg_strong32(g_smuse + i) != p.layer + 1;
      const uint32_t gap0 = max(p.gap, (int)min(__reduce_add_sync(~0u, peers), 18u) * p.share >> 3);
      if (elect()) {
        uint32_t dst = sb, bar = bars, ph = 1, next = clk32(), gap = 0;
        auto acquire = [&](uint32_t kb) {
          mbar_wait(bar + 8 * PS, ph);
          mbar_expect(bar, kb * 1024);
          if (gap) {
            uint32_t now;
            do now = clk32(); while ((int)(now - next) < 0);
            next = ((int)(now - next) > 100 ? now - 100 : next) + kb * gap;
          }
        };
        auto advance = [&]() { dst += PB; bar += 8; if (dst == bars) { dst = sb; bar = bars; ph ^= 1; } };
        auto depend = [&](const uint32_t* c, uint32_t need) { wait_count(c, need); fence_async_global(); };
#pragma unroll 1
        for (int n = 0;; n++) {
          mbar_wait(bIF + 8 * (n & 3), (n >> 2) & 1);
          const int code = (int)lds32(slots + 4 * (n & 3));
          if (code < 0) break;
          const int type = (code >> 16) & 15, b = (code >> 8) & 255, idx = code & 255;
          const bool early = code >> 20 & 1, go = !(code >> 21);
          mbar_arrive(bIE + 8 * (n & 3));
          gap = code >> 22 & 1 ? 0 : gap0;
          const uint32_t* progress = g_sync + b * 8 + 4 + type;
          if (type == IT_ATT && b >= QA_END) {
            depend(g_sync + SY_Q, (16 - QA_END) * 32);
#pragma unroll 1
            for (int u = 0; u < 2; u++) { acquire(24); bulk_load_last(dst, g_q + (((b - QA_END) * 32 + idx) * 2 + u) * 1536, 24576, bar); advance(); }
          } else if (type == IT_FIN) {
            const int ng = 16 / fin_items(b), lg = ng >> 1;
#pragma unroll 1
            for (int g = 0; g < ng; g++) { acquire(20); bulk_load(dst, g_x + (b * 16 + idx * ng + g) * 1280, 20480, bar); advance(); }
            if (early) depend(progress, item_need(type, b));
            if (go) mbar_arrive(bGo);
#pragma unroll 1
            for (int i = 0; i < op_split(b) * ng; i += 2) {
              const uint2* src = g_part + ((b * 16 + (i >> lg)) * 16 + idx * ng + (i & (ng - 1))) * 1280;
              acquire(20);
              bulk_load_last(dst, src, ng > 1 ? 20480 : 10240, bar);
              if (ng == 1) bulk_load_last(dst + 10240, src + 16 * 1280, 10240, bar);
              advance();
            }
          } else {
            const bool op = type == IT_OP, bq = type == IT_BQ;
            const int width = op ? op_width(b) : bq ? bq_width(b) : 192, nb = (width + 63) >> 6, lt = width == 320 ? 1 : 2;
            const int nst = op ? 192 / op_split(b) : 20, kb0 = op ? (idx >> lt) * nst : 0;
            const int col = (op ? idx & ((1 << lt) - 1) : idx) * width;
            const bool whole = !(width & 63);
            const CUtensorMap* m = op ? (whole ? &p.wo : &p.wo2) : bq ? (whole ? &p.wb : &p.wb2) : &p.wq;
            const uint32_t* a = op ? g_o + (b * 192 + kb0) * 2048 : g_xn + b * 20 * 2048;
            int row = kb0 * 32, pre = early && (op || bq) ? min(nst, PS) : 0;
            auto weights = [&]() {
              acquire(8 + nb * 4);
              if (whole) {
                tma_load3z(dst + 8192, m, row, col >> 6, bar);
              } else {
                tma_load(dst + 8192, m, col, row, bar); tma_load(dst + 12288, m, col + 64, row, bar);
                if (nb == 3) tma_load(dst + 16384, m, col + 128, row, bar);
              }
              row += 32;
            };
            if (pre) {
              uint32_t da = dst, ba = bar;
#pragma unroll 1
              for (int kb = 0; kb < pre; kb++) { weights(); advance(); }
              depend(progress, item_need(type, b));
#pragma unroll 1
              for (int kb = 0; kb < pre; kb++) {
                bulk_load(da, a, 8192, ba);
                a += 2048; da += PB; ba += 8;
                if (da == bars) { da = sb; ba = bars; }
              }
            }
#pragma unroll 1
            for (int kb = pre; kb < nst; kb++) { weights(); bulk_load(dst, a, 8192, bar); a += 2048; advance(); }
          }
          if (type == IT_ATT) {
            if (early) depend(progress, 96);
            if (go) mbar_arrive(bGo);
            const uint8_t* src = g_kv + (size_t)(idx * 6 * NSEG + b * 4) * KV_BYTES;
#pragma unroll 1
            for (int u = 0; u < 6; u++) {
              acquire(20);
              bulk_load_last(dst, src, 20480, bar);
              src += u == 2 ? -3 * KV_V : 2 * KV_V;
              advance();
            }
          }
        }
      }
    } else if (warp == 10 && lane == 0) {
      for (int n = 0;; n++) {
        mbar_wait(bIF + 8 * (n & 3), (n >> 2) & 1);
        const int code = (int)lds32(slots + 4 * (n & 3));
        if (code < 0) break;
        const int type = (code >> 16) & 15, b = (code >> 8) & 255;
        mbar_wait(done + 8 * (n & 3), (n >> 2) & 1);
        if (type != IT_BQ) red_release(type == IT_Q ? g_sync + SY_Q : g_sync + b * 8 + 5 + type, 1);
        mbar_arrive(bIE + 8 * (n & 3));
      }
    }
  } else {
    asm volatile("setmaxnreg.inc.sync.aligned.u32 224;");
    const int g = lane >> 2, c = lane & 3;
    Ring r = {sb, bars, 0, 0};
#pragma unroll 1
    for (int n = 0;; n++) {
      mbar_wait(bIF + 8 * (n & 3), (n >> 2) & 1);
      const int code = __shfl_sync(~0u, (int)lds32(slots + 4 * (n & 3)), 0);
      if (code < 0) { TRACE(2); break; }
      const int type = (code >> 16) & 15, b = (code >> 8) & 255, idx = code & 255;
      ITEM(code & 0xfffff, 0);
      if (type == IT_ATT || type == IT_Q) {
        uint32_t q[48];
        if (type == IT_Q || b < QA_END) {
          float d[96] = {};
          reg_fence<96>(d);
          gemm_item<192>(r, d, 20, bGo, type == IT_Q ? 12 : -1);
#pragma unroll
          for (int i = 0; i < 48; i++) q[i] = pack2(d[2 * i], d[2 * i + 1]);
        } else {
#pragma unroll
          for (int u = 0; u < 2; u++) {
            const uint32_t base = r.wait() + threadIdx.x * 16;
#pragma unroll
            for (int i = 0; i < 6; i++) {
              const uint4 v = lds128(base + i * 4096);
              q[24 * u + 4 * i] = v.x; q[24 * u + 4 * i + 1] = v.y; q[24 * u + 4 * i + 2] = v.z; q[24 * u + 4 * i + 3] = v.w;
            }
            r.pop();
          }
        }
        if (type == IT_Q) {
          uint4* dst = g_q + ((b - QA_END) * 32 + idx) * 3072 + threadIdx.x;
#pragma unroll
          for (int i = 0; i < 12; i++) dst[i * 256] = make_uint4(q[4 * i], q[4 * i + 1], q[4 * i + 2], q[4 * i + 3]);
        } else if (warp < 4) {
          attn_a_warp<0>(r, q, b, idx);
        } else {
          attn_a_warp<1>(r, q, b, idx);
        }
      } else if (type == IT_FIN) {
        if (fin_items(b) == 4) fin_item<4>(r, scratch, b, idx);
        else if (fin_items(b) == 8) fin_item<2>(r, scratch, b, idx);
        else fin_item<1>(r, scratch, b, idx);
      } else {
        float d[160] = {};
        reg_fence<160>(d);
        const int width = type == IT_OP ? op_width(b) : bq_width(b), nst = type == IT_OP ? 192 / op_split(b) : 20;
        const int go_at = code >> 21 ? -1 : max(nst - 6, 0);
        if (width == 320) gemm_item<320>(r, d, nst, bGo, go_at);
        else if (width == 160) gemm_item<160>(r, d, nst, bGo, go_at);
        else gemm_item<80>(r, d, nst, bGo, go_at);
        reg_fence<160>(d);
        if (type == IT_OP) {
          const int tiles = DM / width;
          uint2* dst = g_part + (((b * 16 + idx / tiles) * 16 + warp * 2) * 40 + idx % tiles * (width / 16)) * 32 + lane;
#pragma unroll
          for (int u = 0; u < 20; u++) {
            if (u % 5 == 0 && u * 16 >= width) break;
            dst[u * 32] = make_uint2(pack2(d[8 * u], d[8 * u + 1]), pack2(d[8 * u + 4], d[8 * u + 5]));
            dst[(40 + u) * 32] = make_uint2(pack2(d[8 * u + 2], d[8 * u + 3]), pack2(d[8 * u + 6], d[8 * u + 7]));
          }
        } else {
          const int row = b * 128 + warp * 16 + g;
          const int h0 = idx * (width / 20);
          const float sc = h0 < 32 ? 0.22360679775f * 1.44269504089f : 1.f;
          const bool lo = c < 2;
          uint32_t* da = g_bqkv + (h0 * 256 + (row >> 3)) * 96 + lane;
          uint32_t* db = da + 256 * 96 + (lo ? 2 : -2);
          uint32_t pad[2];
#pragma unroll
          for (int rr = 0; rr < 2; rr++) pad[rr] = !(c & 1) && (h0 >= 64 || (h0 >= 32 && (row & 1) && poly_group((row >> 3) + rr))) ? 0x00003f80u : 0u;
#pragma unroll
          for (int q = 0; q < 8; q++) {
            if (!(q & 1) && q * 40 >= width) break;
#pragma unroll
            for (int rr = 0; rr < 2; rr++) {
              uint32_t w[5];
#pragma unroll
              for (int i = 0; i < 5; i++) w[i] = pack2(d[20 * q + 4 * i + 2 * rr] * sc, d[20 * q + 4 * i + 2 * rr + 1] * sc);
              const int o = q * 2 * 256 * 96 + rr * 96;
              da[o] = w[0]; da[o + 32] = w[1]; da[o + 64] = lo ? w[2] : pad[rr];
              db[o] = lo ? w[3] : w[2]; db[o + 32] = lo ? w[4] : w[3]; db[o + 64] = lo ? pad[rr] : w[4];
            }
          }
        }
      }
      __syncwarp();
      if (lane == 0) mbar_arrive(done + 8 * (n & 3));
      if (code >> 21 && threadIdx.x == 128) mbar_arrive(bGo);
      ITEM(code & 0xfffff, 1);
    }
  }
}

constexpr int AB_SMEM = 1024 + 98304 + 51200 + 4 * 16384 + 256;
#define AB_N 32
#define AB_WG 4
constexpr int AB_T = AB_WG * 128, AB_PASS = 8 / AB_WG;
__device__ __forceinline__ float ex2_poly(float t) {
  const uint32_t r = __float_as_uint(t) & 0xffff8000u;
  const float f = t - __uint_as_float(r);
  const float p = fmaf(fmaf(fmaf(-5.869912678e-38f, f, -1.700740250e-37f), f, -5.234869734e-37f), f, -7.522601252e-37f);
  uint32_t y;
  asm("mad.lo.u32 %0, %1, 256, %2;" : "=r"(y) : "r"(r), "r"(__float_as_uint(p)));
  return __uint_as_float(y);
}
__device__ __forceinline__ float sq2(uint32_t w) { const float a = bf_lo(w), b = bf_hi(w); return fmaf(a, a, b * b); }

__device__ __forceinline__ void attn_b_store(const float* o, int h, int row0, int lane) {
  const int g = lane >> 2, c = lane & 3;
  const float i0 = 1.f / __shfl_sync(~0u, o[8], (lane & ~3) | 2), i1 = 1.f / __shfl_sync(~0u, o[10], (lane & ~3) | 2);
#pragma unroll
  for (int jj = 0; jj < 3; jj++) {
    if (jj < 2 || c < 2) {
      const int col = h * 20 + 8 * jj + 2 * c;
      uint32_t* dst = g_of + (((row0 >> 7) * 10 + (col >> 6)) * 16 + (row0 >> 3 & 15)) * 256 + (col >> 3 & 7) * 32 + g * 4 + (col >> 1 & 3);
      dst[0] = pack2(o[4 * jj] * i0, o[4 * jj + 1] * i0);
      dst[256] = pack2(o[4 * jj + 2] * i1, o[4 * jj + 3] * i1);
    }
  }
}

__device__ __forceinline__ void attn_b_qk(float* s, uint32_t q0, uint32_t q1, uint32_t q2, uint32_t q3, uint32_t q4, uint32_t q5, uint32_t z0, uint32_t z1,
                                          uint64_t dk, uint64_t dk2) {
  wg_rs32_00(s, q0, q1, q2, q3, dk, 0);
  wg_rs32_00(s, q4, q5, z0, z1, dk2, 1);
}

struct AbParams { Weights next; uint32_t* done; uint32_t* out; };
__global__ void __launch_bounds__(AB_T + 32, 1) attn_b_kernel(const __grid_constant__ AbParams p) {
  extern __shared__ uint8_t smem_raw[];
  const uint32_t sb = (s2u(smem_raw) + 1023) & ~1023u, sK = sb, sV = sb + 98304, bars = sV + 51200 + 4 * 16384;
  const uint32_t bF = bars + 64, bW = bars + 72, bA = bars + 80, bE = bars + 128, smax = bars + 176;
  auto ring = [&](int i) { return i < 2 ? sK + 51200 + i * 16384 : sV + 51200 + (i - 2) * 16384; };
  const int warp = __shfl_sync(~0u, threadIdx.x >> 5, 0), lane = threadIdx.x & 31;
  const int h = blockIdx.x >> 2, quarter = blockIdx.x & 3;
  TRACE(0);
  pdl_launch();
  pdl_wait();
  if (blockIdx.x < NSLOT) for (int i = threadIdx.x; i < 512; i += AB_T + 32) reinterpret_cast<uint4*>(pool_at(blockIdx.x * 8192))[i] = make_uint4(0, 0, 0, 0);
  if (blockIdx.x == 31) for (int i = threadIdx.x; i < SY_N; i += AB_T + 32) g_sync[i] = 0;
  if (threadIdx.x == 0) {
    for (int i = 0; i < 22; i++) mbar_init(bars + 8 * i, i == 8 ? AB_T / 32 : i >= 16 ? 8 : 1);
    sts64(smax, 0, 0);
    fence_async();
    const uint8_t* gk = reinterpret_cast<const uint8_t*>(g_bqkv + (32 + h) * 256 * 96);
    const uint8_t* gv = reinterpret_cast<const uint8_t*>(g_bqkv + (64 + h) * 256 * 96);
    for (int i = 0; i < 8; i++) {
      mbar_expect(bars + 8 * i, 24576);
      bulk_load_last(sK + i * 12288, gk + i * 12288, 12288, bars + 8 * i);
      bulk_load_last(sV + i * 12288, gv + i * 12288, 12288, bars + 8 * i);
    }
  }
  __syncthreads();
  const int blk = quarter * 4 + (h >> 3), cg = h & 7;
  auto unsafe = [&]() { const float2 m = lds64f(smax); return !(m.x * m.y <= 10000.f); };
  if (warp == AB_T / 32) {
    auto load_w = [&]() {
      mbar_expect(bW, 102400);
      for (int i = 0; i < 4; i++) bulk_load((i < 2 ? sK : sV) + (i & 1) * 25600, g_wb + cg * 6400 + i * 1600, 25600, bW);
    };
    if (p.next.w[0] && lane == 0) {
      mbar_wait(bars + 56, 0);
      for (int i = 0; i < AB_PF; i++) { const uint32_t t0 = clk32(); while (clk32() - t0 < (i ? AB_PFD : AB_PF0)) __nanosleep(200); prefetch_weights(p.next, i); }
    }
    __syncwarp();
    mbar_wait(bF, 0);
    const bool redo = unsafe();
    if (!redo && lane == 0) load_w();
    __syncwarp();
    bar_sync(1, AB_T + 32);
    if (lane == 0) {
      ABT(!!p.out, 1);
      red_release(p.done + quarter * 32, 1);
      ABT(!!p.out, 2);
      if (redo) load_w();
      wait_count(p.done + quarter * 32, 32);
      fence_async_global();
      ABT(!!p.out, 3);
      for (int kb = 0; kb < 10; kb++) {
        const int i = kb < 6 ? kb : kb - 6;
        if (kb >= 6) mbar_wait(bE + 8 * i, 0);
        mbar_expect(bA + 8 * i, 16384);
        bulk_load(ring(i), g_of + (blk * 10 + kb) * 4096, 16384, bA + 8 * i);
      }
    }
    return;
  }
  float qmax = 0.f;
  constexpr int NT = SEQ / AB_N, PER = 256 / AB_N;
#pragma unroll 1
  for (int pass = 0; pass < AB_PASS; pass++) {
    const int row0 = quarter * 512 + ((warp >> 2) * AB_PASS + pass) * 64 + (warp & 3) * 16;
    const uint32_t* gq = g_bqkv + (h * 256 + (row0 >> 3)) * 96 + lane;
    const uint32_t q0 = gq[0], q1 = gq[96], q2 = gq[32], q3 = gq[128];
    uint32_t q4 = gq[64], q5 = gq[160];
    const uint32_t z0 = gq[64 + 3 - (lane & 3)], z1 = gq[160 + 3 - (lane & 3)];
    {
      float n0 = sq2(q0) + sq2(q2) + sq2(q4), n1 = sq2(q1) + sq2(q3) + sq2(q5);
      n0 += __shfl_xor_sync(~0u, n0, 1); n1 += __shfl_xor_sync(~0u, n1, 1);
      n0 += __shfl_xor_sync(~0u, n0, 2); n1 += __shfl_xor_sync(~0u, n1, 2);
      qmax = (n0 > qmax || n0 != n0) ? n0 : qmax;
      qmax = (n1 > qmax || n1 != n1) ? n1 : qmax;
    }
    if (pass == AB_PASS - 1) {
      float kmax = 0.f;
#pragma unroll
      for (int i = 0; i < SEQ / AB_T; i++) {
        const int key = threadIdx.x + AB_T * i;
        const uint32_t a = sK + (key >> 3) * 384 + (key & 7) * 16;
        const uint4 x = lds128(a), y = lds128(a + 128);
        const uint2 z = lds64(a + 256);
        const float n = ((sq2(x.x) + sq2(x.y)) + (sq2(x.z) + sq2(x.w))) + ((sq2(y.x) + sq2(y.y)) + (sq2(y.z) + sq2(y.w))) + (sq2(z.x) + sq2(z.y));
        kmax = (n > kmax || n != n) ? n : kmax;
      }
      const uint32_t kb = __reduce_max_sync(~0u, __float_as_uint(kmax) & 0x7fffffffu), qb = __reduce_max_sync(~0u, __float_as_uint(qmax) & 0x7fffffffu);
      if (lane < 2) asm volatile("red.shared.max.u32 [%0], %1;" :: "r"(smax + 4 * lane), "r"(lane ? kb : qb) : "memory");
      __syncwarp();
    }
    if ((lane & 3) == 2) { q4 = 0x43BCu; q5 = 0x43BCu; }
    float o[12];
    uint64_t dk = mkdesc(sK, 128, 384, 0), dk2 = mkdesc(sK + 256, 0, 384, 0), dv = mkdesc(sV, 384, 128, 0);
    float sa[AB_N / 2], sb2[AB_N / 2];
    uint32_t pa[AB_N / 4], pb[AB_N / 4];
    if (pass == 0) mbar_wait(bars, 0);
    wg_fence();
    attn_b_qk(sa, q0, q1, q2, q3, q4, q5, z0, z1, dk, dk2);
    wg_commit();
    attn_b_qk(sb2, q0, q1, q2, q3, q4, q5, z0, z1, dk + AB_N * 3, dk2 + AB_N * 3);
    wg_commit();
#pragma unroll 1
    for (int kt = 0; kt < NT; kt += 2) {
      const int nx = kt + 2 < NT ? kt + 2 : 0;
      if (pass == 0 && (nx & (PER - 1)) == 0) mbar_wait(bars + 8 * (nx / PER), 0);
      const uint64_t nk = dk + nx * (AB_N * 3), nk2 = dk2 + nx * (AB_N * 3);
      wg_wait<1>();
      if (pass == AB_PASS - 1 && kt == NT * 5 / 8 + 2 && lane == 0) mbar_arrive(bF);
      reg_fence<AB_N / 2>(sa);
#pragma unroll
      for (int i = 0; i < AB_N / 4; i++) pa[i] = pack2(ex2(sa[2 * i]), poly_group(i >> 1) ? ex2_poly(sa[2 * i + 1]) : ex2(sa[2 * i + 1]));
      wg_fence();
#pragma unroll
      for (int kk = 0; kk < AB_N / 16; kk++) wg_rs24_01(o, pa[4 * kk], pa[4 * kk + 1], pa[4 * kk + 2], pa[4 * kk + 3], dv + kk * 48, kk | kt);
      attn_b_qk(sa, q0, q1, q2, q3, q4, q5, z0, z1, nk, nk2);
      wg_commit();
      wg_wait<1>();
      reg_fence<AB_N / 2>(sb2);
#pragma unroll
      for (int i = 0; i < AB_N / 4; i++) pb[i] = pack2(ex2(sb2[2 * i]), poly_group((i >> 1) + AB_N / 8) ? ex2_poly(sb2[2 * i + 1]) : ex2(sb2[2 * i + 1]));
      wg_fence();
#pragma unroll
      for (int kk = 0; kk < AB_N / 16; kk++) wg_rs24_01(o, pb[4 * kk], pb[4 * kk + 1], pb[4 * kk + 2], pb[4 * kk + 3], dv + AB_N * 3 + kk * 48, 1);
      attn_b_qk(sb2, q0, q1, q2, q3, q4, q5, z0, z1, nk + AB_N * 3, nk2 + AB_N * 3);
      wg_commit();
      dv += AB_N * 6;
    }
    wg_wait<0>();
    reg_fence<12>(o); reg_fence<AB_N / 2>(sa); reg_fence<AB_N / 2>(sb2);
    attn_b_store(o, h, row0, lane);
  }
  mbar_wait(bF, 0);
  if (unsafe())
#pragma unroll 1
  for (int pass = 0; pass < AB_PASS; pass++) {
    const int row0 = quarter * 512 + ((warp >> 2) * AB_PASS + pass) * 64 + (warp & 3) * 16;
    const uint32_t* gq = g_bqkv + (h * 256 + (row0 >> 3)) * 96 + lane;
    const uint32_t q0 = gq[0], q1 = gq[96], q2 = gq[32], q3 = gq[128], q4 = gq[64], q5 = gq[160];
    float o[12];
#pragma unroll
    for (int i = 0; i < 12; i++) o[i] = 0.f;
    float m0 = -INFINITY, m1 = -INFINITY;
#pragma unroll 1
    for (int kt = 0; kt < 32; kt++) {
      float s[32];
      const uint64_t dk = mkdesc(sK + kt * 3072, 128, 384, 0), dk2 = mkdesc(sK + kt * 3072 + 256, 0, 384, 0);
      wg_fence();
      wg_rs64_00(s, q0, q1, q2, q3, dk, 0);
      wg_rs64_00(s, q4, q5, 0, 0, dk2, 1);
      wg_commit();
      wg_wait<0>();
      reg_fence<32>(s); reg_fence<12>(o);
      float n0 = m0, n1 = m1;
#pragma unroll
      for (int jj = 0; jj < 8; jj++) { n0 = fmaxf(n0, fmaxf(s[4 * jj], s[4 * jj + 1])); n1 = fmaxf(n1, fmaxf(s[4 * jj + 2], s[4 * jj + 3])); }
      n0 = fmaxf(n0, __shfl_xor_sync(~0u, n0, 1)); n0 = fmaxf(n0, __shfl_xor_sync(~0u, n0, 2));
      n1 = fmaxf(n1, __shfl_xor_sync(~0u, n1, 1)); n1 = fmaxf(n1, __shfl_xor_sync(~0u, n1, 2));
      const float r0 = ex2(m0 - n0), r1 = ex2(m1 - n1);
      m0 = n0; m1 = n1;
#pragma unroll
      for (int jj = 0; jj < 3; jj++) { o[4 * jj] *= r0; o[4 * jj + 1] *= r0; o[4 * jj + 2] *= r1; o[4 * jj + 3] *= r1; }
      uint32_t pp[16];
#pragma unroll
      for (int jj = 0; jj < 8; jj++) {
        pp[2 * jj] = pack2(ex2(s[4 * jj] - m0), ex2(s[4 * jj + 1] - m0));
        pp[2 * jj + 1] = pack2(ex2(s[4 * jj + 2] - m1), ex2(s[4 * jj + 3] - m1));
      }
      const uint64_t dv = mkdesc(sV + kt * 3072, 384, 128, 0);
      wg_fence();
#pragma unroll
      for (int kk = 0; kk < 4; kk++) wg_rs24_01(o, pp[4 * kk], pp[4 * kk + 1], pp[4 * kk + 2], pp[4 * kk + 3], dv + kk * 48, 1);
      wg_commit();
    }
    wg_wait<0>();
    reg_fence<12>(o);
    attn_b_store(o, h, row0, lane);
  }
  ABT(!!p.out, 0);
  bar_arrive(1, AB_T + 32);
  if (warp >= 8) return;
  const int g = lane >> 2, c = lane & 3;
  float d[40];
  float4* x = g_x + ((blk * 16 + warp * 2) * 40 + cg * 5) * 32 + lane;
#pragma unroll
  for (int i = 0; i < 10; i++) {
    const int r = i / 5, u = i % 5;
    const float4 t = x[(r * 40 + u) * 32];
    d[8 * u + 2 * r] = t.x; d[8 * u + 2 * r + 1] = t.y; d[8 * u + 4 + 2 * r] = t.z; d[8 * u + 5 + 2 * r] = t.w;
  }
  mbar_wait(bW, 0);
  reg_fence<40>(d);
  ABT(!!p.out, 4);
#pragma unroll 1
  for (int kb = 0; kb < 10; kb++) {
    const int i = kb < 6 ? kb : kb - 6;
    mbar_wait(bA + 8 * i, kb >= 6);
    const uint64_t da = mkdesc(ring(i) + (warp >> 2) * 8192, 128, 1024, 0), db = mkdesc(kb < 5 ? sK + kb * 10240 : sV + (kb - 5) * 10240, 1280, 128, 0);
    wg_fence();
#pragma unroll
    for (int kk = 0; kk < 4; kk++) wg_ss80_01(d, da + kk * 16, db + kk * 160, 1);
    wg_commit();
    if (kb > 0 && kb < 5) { wg_wait<1>(); if (lane == 0) mbar_arrive(bE + 8 * (kb - 1)); }
  }
  wg_wait<0>();
  reg_fence<40>(d);
  ABT(!!p.out, 5);
  if (p.out) {
    uint32_t* out = p.out + (blk * 128 + warp * 16 + g) * (DM / 2) + cg * 40 + c;
#pragma unroll
    for (int i = 0; i < 20; i++) out[(i & 1) * 8 * (DM / 2) + (i >> 1) * 4] = pack2(d[2 * i], d[2 * i + 1]);
  } else {
    float2* stat = g_stat + blk * 1024 + warp * 16 + g;
    float mean[2], rs[2];
#pragma unroll
    for (int r = 0; r < 2; r++) {
      float t = 0.f, q = 0.f;
#pragma unroll
      for (int i = 0; i < 10; i++) t += d[4 * i + 2 * r] + d[4 * i + 2 * r + 1];
      t += __shfl_xor_sync(~0u, t, 1); t += __shfl_xor_sync(~0u, t, 2);
      t *= 1.f / 80;
#pragma unroll
      for (int i = 0; i < 10; i++) { const float a = d[4 * i + 2 * r] - t, b = d[4 * i + 2 * r + 1] - t; q += a * a + b * b; }
      q += __shfl_xor_sync(~0u, q, 1); q += __shfl_xor_sync(~0u, q, 2);
      if (c == r) asm volatile("st.relaxed.gpu.global.v2.b32 [%0], {%1, %2};" :: "l"(stat + cg * 128 + r * 8), "r"(__float_as_uint(t)), "r"(nz(__float_as_uint(q))) : "memory");
    }
#pragma unroll
    for (int i = 0; i < 10; i++) {
      const int r = i / 5, u = i % 5;
      x[(r * 40 + u) * 32] = make_float4(d[8 * u + 2 * r], d[8 * u + 2 * r + 1], d[8 * u + 4 + 2 * r], d[8 * u + 5 + 2 * r]);
    }
    ABT(0, 6);
    uint2 e[4];
    int n = 0;
    do {
#pragma unroll
      for (int i = 0; i < 4; i++)
        asm volatile("ld.relaxed.gpu.global.v2.b32 {%0, %1}, [%2];" : "=r"(e[i].x), "=r"(e[i].y) : "l"(stat + (2 * c + (i & 1)) * 128 + (i >> 1) * 8) : "memory");
      spin_guard(n);
    } while (__any_sync(~0u, min(min(e[0].y, e[1].y), min(e[2].y, e[3].y)) == 0));
#pragma unroll
    for (int r = 0; r < 2; r++) {
      const float m0 = __uint_as_float(e[2 * r].x), m1 = __uint_as_float(e[2 * r + 1].x);
      float t = m0 + m1;
      t += __shfl_xor_sync(~0u, t, 1); t += __shfl_xor_sync(~0u, t, 2);
      t *= 0.125f;
      float q = __uint_as_float(e[2 * r].y) + __uint_as_float(e[2 * r + 1].y) + 80.f * ((m0 - t) * (m0 - t) + (m1 - t) * (m1 - t));
      q += __shfl_xor_sync(~0u, q, 1); q += __shfl_xor_sync(~0u, q, 2);
      mean[r] = t; rs[r] = rsqrtf(q * (1.f / DM) + 1e-5f);
    }
    ABT(0, 7);
    uint32_t w[2][5][2];
#pragma unroll
    for (int i = 0; i < 20; i++) w[i & 1][i >> 2][i >> 1 & 1] = pack2((d[2 * i] - mean[i & 1]) * rs[i & 1], (d[2 * i + 1] - mean[i & 1]) * rs[i & 1]);
    ln_store(w, blk * 8 + warp, cg * 5);
  }
  ABT(!!p.out, 8);
  TRACE(2);
}

typedef CUresult (*EncodeFn)(CUtensorMap*, CUtensorMapDataType, cuuint32_t, void*, const cuuint64_t*, const cuuint64_t*,
                             const cuuint32_t*, const cuuint32_t*, CUtensorMapInterleave, CUtensorMapSwizzle,
                             CUtensorMapL2promotion, CUtensorMapFloatOOBfill);

void make_map(EncodeFn enc, CUtensorMap* m, const void* ptr, int cols, int rows, int nb) {
  const cuuint64_t dims[3] = {(cuuint64_t)(nb ? 64 : cols), (cuuint64_t)rows, (cuuint64_t)cols / 64};
  const cuuint64_t strides[2] = {(cuuint64_t)cols * 2, 128};
  const cuuint32_t box[3] = {64, 32, (cuuint32_t)nb}, es[3] = {1, 1, 1};
  enc(m, CU_TENSOR_MAP_DATA_TYPE_BFLOAT16, nb ? 3 : 2, const_cast<void*>(ptr), dims, strides, box, es, CU_TENSOR_MAP_INTERLEAVE_NONE,
      CU_TENSOR_MAP_SWIZZLE_128B, CU_TENSOR_MAP_L2_PROMOTION_L2_128B, CU_TENSOR_MAP_FLOAT_OOB_FILL_NONE);
}
template <class... KA, class... A>
void launch(void (*kern)(KA...), int grid, int block, int smem, int cluster, bool pdl, A... args) {
  cudaFuncSetAttribute(kern, cudaFuncAttributeMaxDynamicSharedMemorySize, smem);
  cudaLaunchConfig_t cfg = {};
  cfg.gridDim = dim3(grid); cfg.blockDim = dim3(block); cfg.dynamicSmemBytes = smem; cfg.stream = cudaStreamPerThread;
  cudaLaunchAttribute at[2];
  int n = 0;
  if (cluster > 1) { at[n].id = cudaLaunchAttributeClusterDimension; at[n].val.clusterDim.x = cluster; at[n].val.clusterDim.y = 1; at[n].val.clusterDim.z = 1; n++; }
  if (pdl) { at[n].id = cudaLaunchAttributeProgrammaticStreamSerialization; at[n].val.programmaticStreamSerializationAllowed = 1; n++; }
  cfg.attrs = at; cfg.numAttrs = n;
  cudaLaunchKernelEx(&cfg, kern, args...);
}
template <class T> void* sym(T& s) { void* p = nullptr; cudaGetSymbolAddress(&p, s); return p; }

}

#define MODE(b) 0
extern "C" void kernel_launch(void* const* d_in, const int* in_sizes, int n_in, void* d_out, int out_size) {
  const __nv_bfloat16* x = (const __nv_bfloat16*)d_in[0];
  void* fn = nullptr; cudaDriverEntryPointQueryResult qr;
  cudaGetDriverEntryPoint("cuTensorMapEncodeTiled", &fn, cudaEnableDefault, &qr);
  EncodeFn enc = (EncodeFn)fn;

  ChainParams ch = {};
  PostParams op = {};
  for (int i = 0; i < 3; i++) {
    const cuuint64_t dims[3] = {HD, 128, 5}, strides[2] = {HD * 2, HD * 256};
    const cuuint32_t box[3] = {64, 128, 5}, es[3] = {1, 1, 1};
    enc(i == 0 ? &ch.wq : i == 1 ? &ch.wk : &ch.wv, CU_TENSOR_MAP_DATA_TYPE_BFLOAT16, 3, d_in[2 + i], dims, strides, box, es, CU_TENSOR_MAP_INTERLEAVE_NONE,
        CU_TENSOR_MAP_SWIZZLE_128B, W_PROMO, CU_TENSOR_MAP_FLOAT_OOB_FILL_NONE);
  }
  {
    const cuuint64_t dims[3] = {DM, HD, 7}, strides[2] = {DM * 2, 64};
    const cuuint32_t box[3] = {32, 64, 7}, es[3] = {1, 1, 1};
    enc(&ch.wo, CU_TENSOR_MAP_DATA_TYPE_BFLOAT16, 3, d_in[5], dims, strides, box, es, CU_TENSOR_MAP_INTERLEAVE_NONE,
        CU_TENSOR_MAP_SWIZZLE_64B, CU_TENSOR_MAP_L2_PROMOTION_L2_128B, CU_TENSOR_MAP_FLOAT_OOB_FILL_NONE);
  }
  ch.mem0 = (const __nv_bfloat16*)d_in[1];
  ch.pool = (uint8_t*)(((uintptr_t)sym(g_pool) + 8191) & ~(uintptr_t)8191); ch.kv = (uint8_t*)sym(g_kv); ch.xc = (const uint32_t*)sym(g_xc); ch.sync = (uint32_t*)sym(g_sync);
  ch.d1 = 0; ch.d1b = 0; ch.d2 = 0; ch.d2b = 0;
  make_map(enc, &op.wq, d_in[2], HD, DM, 3);
  make_map(enc, &op.wo, d_in[5], DM, HD, 5); make_map(enc, &op.wo2, d_in[5], DM, HD, 0);
  make_map(enc, &op.wb, d_in[8], 1920, DM, 5); make_map(enc, &op.wb2, d_in[8], 1920, DM, 0);
  op.gap = 17; op.share = 20;

  const Weights wa = {{(const uint8_t*)d_in[3], (const uint8_t*)d_in[4], (const uint8_t*)d_in[2], (const uint8_t*)d_in[5]}}, none = {};
  launch(first_kernel, 132, 256, 128 * 1024, 1, false, x, (const uint4*)d_in[9], wa);
  for (int layer = 0; layer < 2; layer++) {
    ch.layer = ch.d2b = op.layer = layer;
    launch(chain_kernel, 96, 256, CH_SMEM, 3, true, ch);
    launch(post_kernel, MODE(3) ? 36 : 132, 384, OP_SMEM, 1, !MODE(1), op);
    const AbParams ab = {layer == 0 ? wa : none, (uint32_t*)sym(g_bo) + layer * 128, layer == 0 ? nullptr : (uint32_t*)d_out};
    launch(attn_b_kernel, 128, AB_T + 32, AB_SMEM, 1, true, ab);
  }
}
```

```cpp
#include <cuda_runtime.h>
#include <cuda_bf16.h>
#include <cuda.h>
#include <stdint.h>

namespace {

constexpr int SEQ = 2048, DM = 640, HD = 6144, NSEG = 64;
constexpr int SPIN_LIMIT = 1 << 20;

__device__ __align__(128) float4 g_x[SEQ * DM / 4];
__device__ __align__(128) uint32_t g_of[SEQ * DM / 2];
__device__ __align__(128) uint4 g_wb[DM * DM / 8];
__device__ __align__(16) float2 g_stat[16 * 8 * 128];
__device__ uint32_t g_bo[8 * 32];
__device__ __align__(128) uint4 g_q[SEQ * HD / 8];
__device__ __align__(128) uint32_t g_o[SEQ * HD / 2];
constexpr int KV_BYTES = 5120, KV_M = 4096, KV_V = NSEG * KV_BYTES;
__device__ __align__(128) uint8_t g_kv[96 * 2 * NSEG * KV_BYTES];
__device__ __align__(128) uint32_t g_xc[SEQ * DM / 2];
#define OP_B4 0
#define OP_B8 10
#define OP_B16 15
#define QA_END 12
__host__ __device__ constexpr int op_split(int b) { return b < OP_B4 ? 2 : b < OP_B8 ? 4 : b < OP_B16 ? 8 : 16; }
__host__ __device__ constexpr int fin_items(int b) { return b < OP_B8 ? 4 : op_split(b); }
#define AB_PF 2
#define AB_PF0 30000
#define AB_PFD 7000
#define W_PROMO CU_TENSOR_MAP_L2_PROMOTION_L2_128B
#define OEF 0
#define BQ_HOLD 12
#define WEF 1
#define FK_PF 1
#define BQ_160 10
#define BQ_80 16
#define OP_160 16
__host__ __device__ constexpr int op_width(int b) { return b < OP_160 ? 320 : 160; }
__host__ __device__ constexpr int bq_width(int b) { return b < BQ_160 ? 320 : b < BQ_80 ? 160 : 80; }
__device__ __align__(128) uint2 g_part[16 * 16 * 16 * 40 * 32];
__device__ __align__(128) uint32_t g_xn[SEQ * DM / 2];
constexpr int SY_Q = 128, SY_T = 160, SY_QC = 192, SY_N = 193;
__device__ __align__(16) uint32_t g_sync[SY_N];
constexpr int NSLOT = 92;
__device__ uint32_t g_pool[(NSLOT + 2) * 2048];
__device__ int g_smpart[256], g_orient[NSLOT];
__device__ uint32_t g_smclk[256], g_smuse[256];
__device__ uint32_t g_bqkv[3 * 32 * 256 * 96];

#define ABT(L, i)
#define MODE_D(b) 0
#define DELAY(d)
#define XT(i)
#define MISS(k, n)
#define PRO(i)
#define TRACE(w)
#define ITEM(code, w)
#define TM(i)
#define TM1(i)
#define TMD(i, dep)
#define TMV(i, at, v)

__device__ __forceinline__ uint32_t gtime() { uint32_t c; asm volatile("mov.u32 %0, %%globaltimer_lo;" : "=r"(c) :: "memory"); return c; }
__device__ __forceinline__ uint32_t clk32() { uint32_t c; asm volatile("mov.u32 %0, %%clock;" : "=r"(c) :: "memory"); return c; }
__device__ __forceinline__ uint32_t s2u(const void* p) { return (uint32_t)__cvta_generic_to_shared(p); }
__device__ __forceinline__ uint32_t pack2(float a, float b) {
  uint32_t r; asm("cvt.rn.bf16x2.f32 %0, %1, %2;" : "=r"(r) : "f"(b), "f"(a)); return r; }
__device__ __forceinline__ float bf_lo(uint32_t w) { return __uint_as_float(w << 16); }
__device__ __forceinline__ float bf_hi(uint32_t w) { return __uint_as_float(w & 0xffff0000u); }
__device__ __forceinline__ float ex2(float x) { float y; asm("ex2.approx.ftz.f32 %0, %1;" : "=f"(y) : "f"(x)); return y; }

__device__ __forceinline__ void mbar_init(uint32_t bar, uint32_t n) {
  asm volatile("mbarrier.init.shared::cta.b64 [%0], %1;" :: "r"(bar), "r"(n) : "memory"); }
__device__ __forceinline__ void mbar_expect(uint32_t bar, uint32_t bytes) {
  asm volatile("mbarrier.arrive.expect_tx.shared::cta.b64 _, [%0], %1;" :: "r"(bar), "r"(bytes) : "memory"); }
__device__ __forceinline__ void mbar_arrive(uint32_t bar) {
  asm volatile("mbarrier.arrive.shared::cta.b64 _, [%0];" :: "r"(bar) : "memory"); }
__device__ __forceinline__ void mbar_wait(uint32_t bar, uint32_t ph) {
  asm volatile("{.reg .pred p; .reg .u32 n; mov.u32 n, 0;\n"
               "W: mbarrier.try_wait.parity.shared::cta.b64 p, [%0], %1; @p bra D;\n"
               "add.u32 n, n, 1; setp.gt.u32 p, n, %2; @p trap; bra W;\n"
               "D: }" :: "r"(bar), "r"(ph), "n"(SPIN_LIMIT) : "memory");
}
__device__ __forceinline__ void mbar_wait_cluster(uint32_t bar, uint32_t ph) {
  asm volatile("{.reg .pred p; .reg .u32 n; mov.u32 n, 0;\n"
               "W: mbarrier.try_wait.parity.acquire.cluster.shared::cta.b64 p, [%0], %1; @p bra D;\n"
               "add.u32 n, n, 1; setp.gt.u32 p, n, %2; @p trap; bra W;\n"
               "D: }" :: "r"(bar), "r"(ph), "n"(SPIN_LIMIT) : "memory");
}
__device__ __forceinline__ void spin_guard(int& n) {
  asm volatile("{.reg .pred p; add.s32 %0, %0, 1; setp.gt.s32 p, %0, %1; @p trap;}" : "+r"(n) : "n"(SPIN_LIMIT));
}
__device__ __forceinline__ void pdl_wait() { asm volatile("griddepcontrol.wait;" ::: "memory"); TRACE(1); }
__device__ __forceinline__ void pdl_launch() { asm volatile("griddepcontrol.launch_dependents;" ::: "memory"); }
__device__ __forceinline__ uint32_t ld_acquire(const uint32_t* p) { uint32_t v; asm volatile("ld.acquire.gpu.global.u32 %0, [%1];" : "=r"(v) : "l"(p) : "memory"); return v; }
__device__ __forceinline__ void red_release(uint32_t* p, uint32_t v) { asm volatile("red.release.gpu.global.add.u32 [%0], %1;" :: "l"(p), "r"(v) : "memory"); }
__device__ __forceinline__ void red_relaxed(uint32_t* p, uint32_t v) { asm volatile("red.relaxed.gpu.global.add.u32 [%0], %1;" :: "l"(p), "r"(v) : "memory"); }
__device__ __forceinline__ void fence_async_global() { asm volatile("fence.proxy.async.global;" ::: "memory"); }
__device__ __forceinline__ void fence_async() { asm volatile("fence.proxy.async.shared::cta;" ::: "memory"); }
__device__ __forceinline__ void bar_sync(int id, int n) { asm volatile("bar.sync %0, %1;" :: "r"(id), "r"(n) : "memory"); }
__device__ __forceinline__ void bar_arrive(int id, int n) { asm volatile("bar.arrive %0, %1;" :: "r"(id), "r"(n) : "memory"); }
__device__ __forceinline__ void tma_load(uint32_t dst, const CUtensorMap* m, int c0, int c1, uint32_t bar) {
  asm volatile("cp.async.bulk.tensor.2d.shared::cluster.global.mbarrier::complete_tx::bytes [%0], [%1, {%3, %4}], [%2];"
               :: "r"(dst), "l"(m), "r"(bar), "r"(c0), "r"(c1) : "memory"); }
template <bool STREAM = false>
__device__ __forceinline__ void tma_load3(uint32_t dst, const CUtensorMap* m, int c0, int c1, uint32_t bar) {
  if (STREAM)
    asm volatile("{.reg .b64 pol; createpolicy.fractional.L2::evict_first.b64 pol, 1.0;\n"
                 "cp.async.bulk.tensor.3d.shared::cluster.global.mbarrier::complete_tx::bytes.L2::cache_hint [%0], [%1, {%3, %4, 0}], [%2], pol;}"
                 :: "r"(dst), "l"(m), "r"(bar), "r"(c0), "r"(c1) : "memory");
  else
  asm volatile("cp.async.bulk.tensor.3d.shared::cluster.global.mbarrier::complete_tx::bytes [%0], [%1, {%3, %4, 0}], [%2];"
               :: "r"(dst), "l"(m), "r"(bar), "r"(c0), "r"(c1) : "memory"); }
__device__ __forceinline__ void tma_load3z(uint32_t dst, const CUtensorMap* m, int c1, int c2, uint32_t bar) {
  asm volatile("cp.async.bulk.tensor.3d.shared::cluster.global.mbarrier::complete_tx::bytes [%0], [%1, {0, %3, %4}], [%2];"
               :: "r"(dst), "l"(m), "r"(bar), "r"(c1), "r"(c2) : "memory"); }
__device__ __forceinline__ void tma_store(const CUtensorMap* m, uint32_t src, int c0, int c1) {
  asm volatile("cp.async.bulk.tensor.2d.global.shared::cta.bulk_group [%0, {%2, %3}], [%1];"
               :: "l"(m), "r"(src), "r"(c0), "r"(c1) : "memory"); }
__device__ __forceinline__ void tma_store_stream(const CUtensorMap* m, uint32_t src, int c0, int c1) {
  asm volatile("{.reg .b64 pol; createpolicy.fractional.L2::evict_first.b64 pol, 1.0;\n"
               "cp.async.bulk.tensor.2d.global.shared::cta.bulk_group.L2::cache_hint [%0, {%2, %3}], [%1], pol;}"
               :: "l"(m), "r"(src), "r"(c0), "r"(c1) : "memory"); }
__device__ __forceinline__ void bulk_load(uint32_t dst, const void* src, uint32_t bytes, uint32_t bar) {
  asm volatile("cp.async.bulk.shared::cluster.global.mbarrier::complete_tx::bytes [%0], [%1], %2, [%3];"
               :: "r"(dst), "l"(src), "r"(bytes), "r"(bar) : "memory"); }
__device__ __forceinline__ void bulk_load_last(uint32_t dst, const void* src, uint32_t bytes, uint32_t bar) {
  asm volatile("{.reg .b64 pol; createpolicy.fractional.L2::evict_first.b64 pol, 1.0;\n"
               "cp.async.bulk.shared::cluster.global.mbarrier::complete_tx::bytes.L2::cache_hint [%0], [%1], %2, [%3], pol;}"
               :: "r"(dst), "l"(src), "r"(bytes), "r"(bar) : "memory"); }
__device__ __forceinline__ void tma_load_last(uint32_t dst, const CUtensorMap* m, int c0, int c1, uint32_t bar) {
  asm volatile("{.reg .b64 pol; createpolicy.fractional.L2::evict_first.b64 pol, 1.0;\n"
               "cp.async.bulk.tensor.2d.shared::cluster.global.mbarrier::complete_tx::bytes.L2::cache_hint [%0], [%1, {%3, %4}], [%2], pol;}"
               :: "r"(dst), "l"(m), "r"(bar), "r"(c0), "r"(c1) : "memory"); }
__device__ __forceinline__ void bulk_send(uint32_t dst, uint32_t src, uint32_t bytes, uint32_t bar) {
  asm volatile("cp.async.bulk.shared::cluster.shared::cta.mbarrier::complete_tx::bytes [%0], [%1], %2, [%3];"
               :: "r"(dst), "r"(src), "r"(bytes), "r"(bar) : "memory"); }
__device__ __forceinline__ void bulk_store(void* dst, uint32_t src, uint32_t bytes) {
  asm volatile("cp.async.bulk.global.shared::cta.bulk_group [%0], [%1], %2;" :: "l"(dst), "r"(src), "r"(bytes) : "memory"); }
__device__ __forceinline__ void bulk_commit() { asm volatile("cp.async.bulk.commit_group;" ::: "memory"); }
template <int N> __device__ __forceinline__ void bulk_wait_read() { asm volatile("cp.async.bulk.wait_group.read %0;" :: "n"(N) : "memory"); }
template <int N> __device__ __forceinline__ void bulk_wait() { asm volatile("cp.async.bulk.wait_group %0;" :: "n"(N) : "memory"); }

__device__ __forceinline__ uint64_t mkdesc(uint32_t addr, uint32_t lbo, uint32_t sbo, uint32_t sw) {
  return (uint64_t)((addr & 0x3FFFF) >> 4) | ((uint64_t)(lbo >> 4) << 16) | ((uint64_t)(sbo >> 4) << 32) | ((uint64_t)sw << 62); }
__device__ __forceinline__ void wg_fence() { asm volatile("wgmma.fence.sync.aligned;" ::: "memory"); }
__device__ __forceinline__ void wg_commit() { asm volatile("wgmma.commit_group.sync.aligned;" ::: "memory"); }
template <int N> __device__ __forceinline__ void wg_wait() { asm volatile("wgmma.wait_group.sync.aligned %0;" :: "n"(N) : "memory"); }
template <int N> __device__ __forceinline__ void reg_fence(float* d) {
#pragma unroll
  for (int i = 0; i < N; i++) asm volatile("" : "+f"(d[i]) :: "memory");
}

__device__ __forceinline__ void mma16(float* d, uint32_t a0, uint32_t a1, uint32_t a2, uint32_t a3, uint32_t b0, uint32_t b1) {
  asm volatile("mma.sync.aligned.m16n8k16.row.col.f32.bf16.bf16.f32 {%0,%1,%2,%3},{%4,%5,%6,%7},{%8,%9},{%0,%1,%2,%3};"
               : "+f"(d[0]), "+f"(d[1]), "+f"(d[2]), "+f"(d[3]) : "r"(a0), "r"(a1), "r"(a2), "r"(a3), "r"(b0), "r"(b1)); }
__device__ __forceinline__ void mma8(float* d, uint32_t a0, uint32_t a1, uint32_t b0) {
  asm volatile("mma.sync.aligned.m16n8k8.row.col.f32.bf16.bf16.f32 {%0,%1,%2,%3},{%4,%5},{%6},{%0,%1,%2,%3};"
               : "+f"(d[0]), "+f"(d[1]), "+f"(d[2]), "+f"(d[3]) : "r"(a0), "r"(a1), "r"(b0)); }
__device__ __forceinline__ void ldsm4(uint32_t* r, uint32_t a) {
  asm volatile("ldmatrix.sync.aligned.m8n8.x4.shared.b16 {%0,%1,%2,%3},[%4];" : "=r"(r[0]), "=r"(r[1]), "=r"(r[2]), "=r"(r[3]) : "r"(a) : "memory"); }
__device__ __forceinline__ void ldsm4t(uint32_t* r, uint32_t a) {
  asm volatile("ldmatrix.sync.aligned.m8n8.x4.trans.shared.b16 {%0,%1,%2,%3},[%4];" : "=r"(r[0]), "=r"(r[1]), "=r"(r[2]), "=r"(r[3]) : "r"(a) : "memory"); }
__device__ __forceinline__ void ldsm2(uint32_t* r, uint32_t a) {
  asm volatile("ldmatrix.sync.aligned.m8n8.x2.shared.b16 {%0,%1},[%2];" : "=r"(r[0]), "=r"(r[1]) : "r"(a) : "memory"); }
__device__ __forceinline__ void stsm4(uint32_t a, uint32_t r0, uint32_t r1, uint32_t r2, uint32_t r3) {
  asm volatile("stmatrix.sync.aligned.m8n8.x4.shared.b16 [%0], {%1,%2,%3,%4};" :: "r"(a), "r"(r0), "r"(r1), "r"(r2), "r"(r3) : "memory"); }
__device__ __forceinline__ void stsm2t(uint32_t a, uint32_t r0, uint32_t r1) {
  asm volatile("stmatrix.sync.aligned.m8n8.x2.trans.shared.b16 [%0], {%1,%2};" :: "r"(a), "r"(r0), "r"(r1) : "memory"); }
__device__ __forceinline__ void stsm4t(uint32_t a, uint32_t r0, uint32_t r1, uint32_t r2, uint32_t r3) {
  asm volatile("stmatrix.sync.aligned.m8n8.x4.trans.shared.b16 [%0], {%1,%2,%3,%4};" :: "r"(a), "r"(r0), "r"(r1), "r"(r2), "r"(r3) : "memory"); }
__device__ __forceinline__ void st_async128(uint32_t a, uint4 v, uint32_t bar) {
  asm volatile("st.async.shared::cluster.mbarrier::complete_tx::bytes.v4.b32 [%0], {%1,%2,%3,%4}, [%5];" :: "r"(a), "r"(v.x), "r"(v.y), "r"(v.z), "r"(v.w), "r"(bar) : "memory"); }
__device__ __forceinline__ void sts32(uint32_t a, uint32_t v) { asm volatile("st.shared.b32 [%0], %1;" :: "r"(a), "r"(v) : "memory"); }
__device__ __forceinline__ void sts64f(uint32_t a, float x, float y) { asm volatile("st.shared.v2.f32 [%0], {%1,%2};" :: "r"(a), "f"(x), "f"(y) : "memory"); }
__device__ __forceinline__ void sts128(uint32_t a, uint4 v) {
  asm volatile("st.shared.v4.b32 [%0], {%1,%2,%3,%4};" :: "r"(a), "r"(v.x), "r"(v.y), "r"(v.z), "r"(v.w) : "memory"); }
__device__ __forceinline__ void sts128f(uint32_t a, float x, float y, float z, float w) {
  asm volatile("st.shared.v4.f32 [%0], {%1,%2,%3,%4};" :: "r"(a), "f"(x), "f"(y), "f"(z), "f"(w) : "memory"); }
__device__ __forceinline__ float lds32f(uint32_t a) { float v; asm volatile("ld.shared.f32 %0, [%1];" : "=f"(v) : "r"(a) : "memory"); return v; }
__device__ __forceinline__ float2 lds64f(uint32_t a) { float2 v; asm volatile("ld.shared.v2.f32 {%0,%1}, [%2];" : "=f"(v.x), "=f"(v.y) : "r"(a) : "memory"); return v; }
__device__ __forceinline__ float4 lds128f(uint32_t a) {
  float4 v; asm volatile("ld.shared.v4.f32 {%0,%1,%2,%3}, [%4];" : "=f"(v.x), "=f"(v.y), "=f"(v.z), "=f"(v.w) : "r"(a) : "memory"); return v; }
__device__ __forceinline__ uint4 lds128(uint32_t a) {
  uint4 v; asm volatile("ld.shared.v4.b32 {%0,%1,%2,%3}, [%4];" : "=r"(v.x), "=r"(v.y), "=r"(v.z), "=r"(v.w) : "r"(a) : "memory"); return v; }
__device__ __forceinline__ uint4 ldg_strong128(const void* p) {
  uint4 v; asm volatile("ld.relaxed.gpu.global.v4.u32 {%0,%1,%2,%3}, [%4];" : "=r"(v.x), "=r"(v.y), "=r"(v.z), "=r"(v.w) : "l"(p) : "memory"); return v; }
__device__ __forceinline__ void stg_strong32(void* p, uint32_t v) { asm volatile("st.relaxed.gpu.global.u32 [%0], %1;" :: "l"(p), "r"(v) : "memory"); }
__device__ __forceinline__ void stg_strong16(void* p, uint32_t v) { asm volatile("st.relaxed.gpu.global.u16 [%0], %1;" :: "l"(p), "h"((uint16_t)v) : "memory"); }
__device__ __forceinline__ void stg_strong128(void* p, uint4 v) {
  asm volatile("st.relaxed.gpu.global.v4.u32 [%0], {%1,%2,%3,%4};" :: "l"(p), "r"(v.x), "r"(v.y), "r"(v.z), "r"(v.w) : "memory"); }
__device__ __forceinline__ uint32_t mapa(uint32_t a, uint32_t r) {
  uint32_t o; asm("mapa.shared::cluster.u32 %0, %1, %2;" : "=r"(o) : "r"(a), "r"(r)); return o; }
__device__ __forceinline__ void st_async2f(uint32_t a, float x, float y, uint32_t bar) {
  asm volatile("st.async.shared::cluster.mbarrier::complete_tx::bytes.v2.f32 [%0], {%1,%2}, [%3];" :: "r"(a), "f"(x), "f"(y), "r"(bar) : "memory"); }
__device__ __forceinline__ void st_async32(uint32_t a, uint32_t x, uint32_t bar) {
  asm volatile("st.async.shared::cluster.mbarrier::complete_tx::bytes.b32 [%0], %1, [%2];" :: "r"(a), "r"(x), "r"(bar) : "memory"); }
__device__ __forceinline__ uint32_t lds32(uint32_t a) { uint32_t v; asm volatile("ld.shared.b32 %0, [%1];" : "=r"(v) : "r"(a) : "memory"); return v; }
__device__ __forceinline__ void st_async64(uint32_t a, uint32_t x, uint32_t y, uint32_t bar) {
  asm volatile("st.async.shared::cluster.mbarrier::complete_tx::bytes.v2.b32 [%0], {%1,%2}, [%3];" :: "r"(a), "r"(x), "r"(y), "r"(bar) : "memory"); }
__device__ __forceinline__ uint2 lds64(uint32_t a) { uint2 v; asm volatile("ld.shared.v2.b32 {%0,%1}, [%2];" : "=r"(v.x), "=r"(v.y) : "r"(a) : "memory"); return v; }
__device__ __forceinline__ void sts64(uint32_t a, uint32_t x, uint32_t y) { asm volatile("st.shared.v2.b32 [%0], {%1,%2};" :: "r"(a), "r"(x), "r"(y) : "memory"); }
__device__ __forceinline__ uint32_t ldg_strong32(const void* p) { uint32_t v; asm volatile("ld.relaxed.gpu.global.u32 %0, [%1];" : "=r"(v) : "l"(p) : "memory"); return v; }
__device__ __forceinline__ uint32_t transpose8(uint32_t x) { uint32_t r; asm volatile("movmatrix.sync.aligned.m8n8.trans.b16 %0, %1;" : "=r"(r) : "r"(x)); return r; }
__device__ __forceinline__ uint32_t hadd2(uint32_t a, uint32_t b) { uint32_t r; asm("add.rn.bf16x2 %0, %1, %2;" : "=r"(r) : "r"(a), "r"(b)); return r; }
__device__ __forceinline__ uint32_t min4(uint4 v) { return min(__vimin3_u32(v.x, v.y, v.z), v.w); }

__device__ __forceinline__ void wg_ss192_01(float* d, uint64_t da, uint64_t db, int sd) {
  asm volatile("{.reg .pred p; setp.ne.b32 p, %98, 0;\n"
    "wgmma.mma_async.sync.aligned.m64n192k16.f32.bf16.bf16 {%0,%1,%2,%3,%4,%5,%6,%7,%8,%9,%10,%11,%12,%13,%14,%15,%16,%17,%18,%19,%20,%21,%22,%23,%24,%25,%26,%27,%28,%29,%30,%31,%32,%33,%34,%35,%36,%37,%38,%39,%40,%41,%42,%43,%44,%45,%46,%47,%48,%49,%50,%51,%52,%53,%54,%55,%56,%57,%58,%59,%60,%61,%62,%63,%64,%65,%66,%67,%68,%69,%70,%71,%72,%73,%74,%75,%76,%77,%78,%79,%80,%81,%82,%83,%84,%85,%86,%87,%88,%89,%90,%91,%92,%93,%94,%95}, %96, %97, p, 1, 1, 0, 1;}"
    : "+f"(d[0]),"+f"(d[1]),"+f"(d[2]),"+f"(d[3]),"+f"(d[4]),"+f"(d[5]),"+f"(d[6]),"+f"(d[7]),"+f"(d[8]),"+f"(d[9]),"+f"(d[10]),"+f"(d[11]),"+f"(d[12]),"+f"(d[13]),"+f"(d[14]),"+f"(d[15]),"+f"(d[16]),"+f"(d[17]),"+f"(d[18]),"+f"(d[19]),"+f"(d[20]),"+f"(d[21]),"+f"(d[22]),"+f"(d[23]),"+f"(d[24]),"+f"(d[25]),"+f"(d[26]),"+f"(d[27]),"+f"(d[28]),"+f"(d[29]),"+f"(d[30]),"+f"(d[31]),"+f"(d[32]),"+f"(d[33]),"+f"(d[34]),"+f"(d[35]),"+f"(d[36]),"+f"(d[37]),"+f"(d[38]),"+f"(d[39]),"+f"(d[40]),"+f"(d[41]),"+f"(d[42]),"+f"(d[43]),"+f"(d[44]),"+f"(d[45]),"+f"(d[46]),"+f"(d[47]),"+f"(d[48]),"+f"(d[49]),"+f"(d[50]),"+f"(d[51]),"+f"(d[52]),"+f"(d[53]),"+f"(d[54]),"+f"(d[55]),"+f"(d[56]),"+f"(d[57]),"+f"(d[58]),"+f"(d[59]),"+f"(d[60]),"+f"(d[61]),"+f"(d[62]),"+f"(d[63]),"+f"(d[64]),"+f"(d[65]),"+f"(d[66]),"+f"(d[67]),"+f"(d[68]),"+f"(d[69]),"+f"(d[70]),"+f"(d[71]),"+f"(d[72]),"+f"(d[73]),"+f"(d[74]),"+f"(d[75]),"+f"(d[76]),"+f"(d[77]),"+f"(d[78]),"+f"(d[79]),"+f"(d[80]),"+f"(d[81]),"+f"(d[82]),"+f"(d[83]),"+f"(d[84]),"+f"(d[85]),"+f"(d[86]),"+f"(d[87]),"+f"(d[88]),"+f"(d[89]),"+f"(d[90]),"+f"(d[91]),"+f"(d[92]),"+f"(d[93]),"+f"(d[94]),"+f"(d[95])
    : "l"(da), "l"(db), "r"(sd));
}
__device__ __forceinline__ void wg_ss128_01(float* d, uint64_t da, uint64_t db, int sd) {
  asm volatile("{.reg .pred p; setp.ne.b32 p, %66, 0;\n"
    "wgmma.mma_async.sync.aligned.m64n128k16.f32.bf16.bf16 {%0,%1,%2,%3,%4,%5,%6,%7,%8,%9,%10,%11,%12,%13,%14,%15,%16,%17,%18,%19,%20,%21,%22,%23,%24,%25,%26,%27,%28,%29,%30,%31,%32,%33,%34,%35,%36,%37,%38,%39,%40,%41,%42,%43,%44,%45,%46,%47,%48,%49,%50,%51,%52,%53,%54,%55,%56,%57,%58,%59,%60,%61,%62,%63}, %64, %65, p, 1, 1, 0, 1;}"
    : "+f"(d[0]),"+f"(d[1]),"+f"(d[2]),"+f"(d[3]),"+f"(d[4]),"+f"(d[5]),"+f"(d[6]),"+f"(d[7]),"+f"(d[8]),"+f"(d[9]),"+f"(d[10]),"+f"(d[11]),"+f"(d[12]),"+f"(d[13]),"+f"(d[14]),"+f"(d[15]),"+f"(d[16]),"+f"(d[17]),"+f"(d[18]),"+f"(d[19]),"+f"(d[20]),"+f"(d[21]),"+f"(d[22]),"+f"(d[23]),"+f"(d[24]),"+f"(d[25]),"+f"(d[26]),"+f"(d[27]),"+f"(d[28]),"+f"(d[29]),"+f"(d[30]),"+f"(d[31]),"+f"(d[32]),"+f"(d[33]),"+f"(d[34]),"+f"(d[35]),"+f"(d[36]),"+f"(d[37]),"+f"(d[38]),"+f"(d[39]),"+f"(d[40]),"+f"(d[41]),"+f"(d[42]),"+f"(d[43]),"+f"(d[44]),"+f"(d[45]),"+f"(d[46]),"+f"(d[47]),"+f"(d[48]),"+f"(d[49]),"+f"(d[50]),"+f"(d[51]),"+f"(d[52]),"+f"(d[53]),"+f"(d[54]),"+f"(d[55]),"+f"(d[56]),"+f"(d[57]),"+f"(d[58]),"+f"(d[59]),"+f"(d[60]),"+f"(d[61]),"+f"(d[62]),"+f"(d[63])
    : "l"(da), "l"(db), "r"(sd));
}
__device__ __forceinline__ void wg_ss160_01(float* d, uint64_t da, uint64_t db, int sd) {
  asm volatile("{.reg .pred p; setp.ne.b32 p, %82, 0;\n"
    "wgmma.mma_async.sync.aligned.m64n160k16.f32.bf16.bf16 {%0,%1,%2,%3,%4,%5,%6,%7,%8,%9,%10,%11,%12,%13,%14,%15,%16,%17,%18,%19,%20,%21,%22,%23,%24,%25,%26,%27,%28,%29,%30,%31,%32,%33,%34,%35,%36,%37,%38,%39,%40,%41,%42,%43,%44,%45,%46,%47,%48,%49,%50,%51,%52,%53,%54,%55,%56,%57,%58,%59,%60,%61,%62,%63,%64,%65,%66,%67,%68,%69,%70,%71,%72,%73,%74,%75,%76,%77,%78,%79}, %80, %81, p, 1, 1, 0, 1;}"
    : "+f"(d[0]),"+f"(d[1]),"+f"(d[2]),"+f"(d[3]),"+f"(d[4]),"+f"(d[5]),"+f"(d[6]),"+f"(d[7]),"+f"(d[8]),"+f"(d[9]),"+f"(d[10]),"+f"(d[11]),"+f"(d[12]),"+f"(d[13]),"+f"(d[14]),"+f"(d[15]),"+f"(d[16]),"+f"(d[17]),"+f"(d[18]),"+f"(d[19]),"+f"(d[20]),"+f"(d[21]),"+f"(d[22]),"+f"(d[23]),"+f"(d[24]),"+f"(d[25]),"+f"(d[26]),"+f"(d[27]),"+f"(d[28]),"+f"(d[29]),"+f"(d[30]),"+f"(d[31]),"+f"(d[32]),"+f"(d[33]),"+f"(d[34]),"+f"(d[35]),"+f"(d[36]),"+f"(d[37]),"+f"(d[38]),"+f"(d[39]),"+f"(d[40]),"+f"(d[41]),"+f"(d[42]),"+f"(d[43]),"+f"(d[44]),"+f"(d[45]),"+f"(d[46]),"+f"(d[47]),"+f"(d[48]),"+f"(d[49]),"+f"(d[50]),"+f"(d[51]),"+f"(d[52]),"+f"(d[53]),"+f"(d[54]),"+f"(d[55]),"+f"(d[56]),"+f"(d[57]),"+f"(d[58]),"+f"(d[59]),"+f"(d[60]),"+f"(d[61]),"+f"(d[62]),"+f"(d[63]),"+f"(d[64]),"+f"(d[65]),"+f"(d[66]),"+f"(d[67]),"+f"(d[68]),"+f"(d[69]),"+f"(d[70]),"+f"(d[71]),"+f"(d[72]),"+f"(d[73]),"+f"(d[74]),"+f"(d[75]),"+f"(d[76]),"+f"(d[77]),"+f"(d[78]),"+f"(d[79])
    : "l"(da), "l"(db), "r"(sd));
}
__device__ __forceinline__ void wg_ss80_01(float* d, uint64_t da, uint64_t db, int sd) {
  asm volatile("{.reg .pred p; setp.ne.b32 p, %42, 0;\n"
    "wgmma.mma_async.sync.aligned.m64n80k16.f32.bf16.bf16 {%0,%1,%2,%3,%4,%5,%6,%7,%8,%9,%10,%11,%12,%13,%14,%15,%16,%17,%18,%19,%20,%21,%22,%23,%24,%25,%26,%27,%28,%29,%30,%31,%32,%33,%34,%35,%36,%37,%38,%39}, %40, %41, p, 1, 1, 0, 1;}"
    : "+f"(d[0]),"+f"(d[1]),"+f"(d[2]),"+f"(d[3]),"+f"(d[4]),"+f"(d[5]),"+f"(d[6]),"+f"(d[7]),"+f"(d[8]),"+f"(d[9]),"+f"(d[10]),"+f"(d[11]),"+f"(d[12]),"+f"(d[13]),"+f"(d[14]),"+f"(d[15]),"+f"(d[16]),"+f"(d[17]),"+f"(d[18]),"+f"(d[19]),"+f"(d[20]),"+f"(d[21]),"+f"(d[22]),"+f"(d[23]),"+f"(d[24]),"+f"(d[25]),"+f"(d[26]),"+f"(d[27]),"+f"(d[28]),"+f"(d[29]),"+f"(d[30]),"+f"(d[31]),"+f"(d[32]),"+f"(d[33]),"+f"(d[34]),"+f"(d[35]),"+f"(d[36]),"+f"(d[37]),"+f"(d[38]),"+f"(d[39])
    : "l"(da), "l"(db), "r"(sd));
}
__device__ __forceinline__ void wg_rs32_00(float* d, uint32_t a0, uint32_t a1, uint32_t a2, uint32_t a3, uint64_t db, int sd) {
  asm volatile("{.reg .pred p; setp.ne.b32 p, %21, 0;\n"
    "wgmma.mma_async.sync.aligned.m64n32k16.f32.bf16.bf16 {%0,%1,%2,%3,%4,%5,%6,%7,%8,%9,%10,%11,%12,%13,%14,%15}, {%16,%17,%18,%19}, %20, p, 1, 1, 0;}"
    : "+f"(d[0]),"+f"(d[1]),"+f"(d[2]),"+f"(d[3]),"+f"(d[4]),"+f"(d[5]),"+f"(d[6]),"+f"(d[7]),"+f"(d[8]),"+f"(d[9]),"+f"(d[10]),"+f"(d[11]),"+f"(d[12]),"+f"(d[13]),"+f"(d[14]),"+f"(d[15])
    : "r"(a0), "r"(a1), "r"(a2), "r"(a3), "l"(db), "r"(sd));
}
__device__ __forceinline__ void wg_rs64_00(float* d, uint32_t a0, uint32_t a1, uint32_t a2, uint32_t a3, uint64_t db, int sd) {
  asm volatile("{.reg .pred p; setp.ne.b32 p, %37, 0;\n"
    "wgmma.mma_async.sync.aligned.m64n64k16.f32.bf16.bf16 {%0,%1,%2,%3,%4,%5,%6,%7,%8,%9,%10,%11,%12,%13,%14,%15,%16,%17,%18,%19,%20,%21,%22,%23,%24,%25,%26,%27,%28,%29,%30,%31}, {%32,%33,%34,%35}, %36, p, 1, 1, 0;}"
    : "+f"(d[0]),"+f"(d[1]),"+f"(d[2]),"+f"(d[3]),"+f"(d[4]),"+f"(d[5]),"+f"(d[6]),"+f"(d[7]),"+f"(d[8]),"+f"(d[9]),"+f"(d[10]),"+f"(d[11]),"+f"(d[12]),"+f"(d[13]),"+f"(d[14]),"+f"(d[15]),"+f"(d[16]),"+f"(d[17]),"+f"(d[18]),"+f"(d[19]),"+f"(d[20]),"+f"(d[21]),"+f"(d[22]),"+f"(d[23]),"+f"(d[24]),"+f"(d[25]),"+f"(d[26]),"+f"(d[27]),"+f"(d[28]),"+f"(d[29]),"+f"(d[30]),"+f"(d[31])
    : "r"(a0), "r"(a1), "r"(a2), "r"(a3), "l"(db), "r"(sd));
}
__device__ __forceinline__ void wg_rs128_00(float* d, uint32_t a0, uint32_t a1, uint32_t a2, uint32_t a3, uint64_t db, int sd) {
  asm volatile("{.reg .pred p; setp.ne.b32 p, %69, 0;\n"
    "wgmma.mma_async.sync.aligned.m64n128k16.f32.bf16.bf16 {%0,%1,%2,%3,%4,%5,%6,%7,%8,%9,%10,%11,%12,%13,%14,%15,%16,%17,%18,%19,%20,%21,%22,%23,%24,%25,%26,%27,%28,%29,%30,%31,%32,%33,%34,%35,%36,%37,%38,%39,%40,%41,%42,%43,%44,%45,%46,%47,%48,%49,%50,%51,%52,%53,%54,%55,%56,%57,%58,%59,%60,%61,%62,%63}, {%64,%65,%66,%67}, %68, p, 1, 1, 0;}"
    : "+f"(d[0]),"+f"(d[1]),"+f"(d[2]),"+f"(d[3]),"+f"(d[4]),"+f"(d[5]),"+f"(d[6]),"+f"(d[7]),"+f"(d[8]),"+f"(d[9]),"+f"(d[10]),"+f"(d[11]),"+f"(d[12]),"+f"(d[13]),"+f"(d[14]),"+f"(d[15]),"+f"(d[16]),"+f"(d[17]),"+f"(d[18]),"+f"(d[19]),"+f"(d[20]),"+f"(d[21]),"+f"(d[22]),"+f"(d[23]),"+f"(d[24]),"+f"(d[25]),"+f"(d[26]),"+f"(d[27]),"+f"(d[28]),"+f"(d[29]),"+f"(d[30]),"+f"(d[31]),"+f"(d[32]),"+f"(d[33]),"+f"(d[34]),"+f"(d[35]),"+f"(d[36]),"+f"(d[37]),"+f"(d[38]),"+f"(d[39]),"+f"(d[40]),"+f"(d[41]),"+f"(d[42]),"+f"(d[43]),"+f"(d[44]),"+f"(d[45]),"+f"(d[46]),"+f"(d[47]),"+f"(d[48]),"+f"(d[49]),"+f"(d[50]),"+f"(d[51]),"+f"(d[52]),"+f"(d[53]),"+f"(d[54]),"+f"(d[55]),"+f"(d[56]),"+f"(d[57]),"+f"(d[58]),"+f"(d[59]),"+f"(d[60]),"+f"(d[61]),"+f"(d[62]),"+f"(d[63])
    : "r"(a0), "r"(a1), "r"(a2), "r"(a3), "l"(db), "r"(sd));
}
__device__ __forceinline__ void wg_rs24_01(float* d, uint32_t a0, uint32_t a1, uint32_t a2, uint32_t a3, uint64_t db, int sd) {
  asm volatile("{.reg .pred p; setp.ne.b32 p, %17, 0;\n"
    "wgmma.mma_async.sync.aligned.m64n24k16.f32.bf16.bf16 {%0,%1,%2,%3,%4,%5,%6,%7,%8,%9,%10,%11}, {%12,%13,%14,%15}, %16, p, 1, 1, 1;}"
    : "+f"(d[0]),"+f"(d[1]),"+f"(d[2]),"+f"(d[3]),"+f"(d[4]),"+f"(d[5]),"+f"(d[6]),"+f"(d[7]),"+f"(d[8]),"+f"(d[9]),"+f"(d[10]),"+f"(d[11])
    : "r"(a0), "r"(a1), "r"(a2), "r"(a3), "l"(db), "r"(sd));
}

#define AB_POLY 0x77
__device__ __forceinline__ constexpr bool poly_group(int group) { return (AB_POLY >> (group & 7)) & 1; }

template <int V> struct Int { static constexpr int value = V; };

template <int NG>
__device__ __forceinline__ void ln_stats(const float4 (&v)[NG][5], uint32_t scratch, float (&mean)[NG], float (&rs)[NG]) {
  const int warp = threadIdx.x >> 5, lane = threadIdx.x & 31;
#pragma unroll
  for (int r = 0; r < NG; r++) {
    float s = 0.f, q = 0.f;
#pragma unroll
    for (int i = 0; i < 5; i++) s += (v[r][i].x + v[r][i].y) + (v[r][i].z + v[r][i].w);
    s += __shfl_xor_sync(~0u, s, 1); s += __shfl_xor_sync(~0u, s, 2);
    s *= 1.f / 80;
#pragma unroll
    for (int i = 0; i < 5; i++) {
      const float x = v[r][i].x - s, y = v[r][i].y - s, z = v[r][i].z - s, w = v[r][i].w - s;
      q += (x * x + y * y) + (z * z + w * w);
    }
    q += __shfl_xor_sync(~0u, q, 1); q += __shfl_xor_sync(~0u, q, 2);
    mean[r] = s; rs[r] = q;
  }
  bar_sync(1, 256);
  if ((lane & 3) == 0) {
#pragma unroll
    for (int r = 0; r < NG; r++) sts64f(scratch + r * 512 + lane * 16 + warp * 8, mean[r], rs[r]);
  }
  bar_sync(1, 256);
#pragma unroll
  for (int r = 0; r < NG; r++) {
    const float4 e = lds128f(scratch + r * 512 + lane * 16);
    float t = e.x + e.z;
    t += __shfl_xor_sync(~0u, t, 1); t += __shfl_xor_sync(~0u, t, 2);
    t *= 0.125f;
    float q = e.y + e.w + 80.f * ((e.x - t) * (e.x - t) + (e.z - t) * (e.z - t));
    q += __shfl_xor_sync(~0u, q, 1); q += __shfl_xor_sync(~0u, q, 2);
    mean[r] = t; rs[r] = rsqrtf(q * (1.f / DM) + 1e-5f);
  }
}

__device__ __forceinline__ void ln_store(const uint32_t (&w)[2][5][2], int tile, int u0) {
  const int lane = threadIdx.x & 31;
  uint32_t* xc = g_xc + ((tile >> 1) * 40 + u0) * 256 + (tile & 1) * 64 + lane;
#pragma unroll
  for (int i = 0; i < 20; i++) xc[(i >> 1) * 128 + (i & 1) * 32] = w[i & 1][i >> 2][i >> 1 & 1];
#pragma unroll
  for (int i = 0; i < 5; i++) {
    const int u = u0 + i;
    uint32_t* xn = g_xn + (((tile >> 3) * 20 + (u >> 1)) * 16 + (tile & 1) * 8 + (tile & 6)) * 128 + (u & 1) * 64 + lane;
#pragma unroll
    for (int r = 0; r < 2; r++) { xn[r * 128] = w[r][i][0]; xn[r * 128 + 32] = w[r][i][1]; }
  }
}
__device__ __forceinline__ void wait_count(const uint32_t* c, uint32_t n) {
  int spin = 0;
  while ((ld_acquire(c) & 0xffff) < n) { __nanosleep(32); spin_guard(spin); }
}

__device__ __forceinline__ uint8_t* pool_at(uint32_t off) {
  return reinterpret_cast<uint8_t*>((reinterpret_cast<uintptr_t>(g_pool) + 8191) & ~(uintptr_t)8191) + off; }
struct Weights { const uint8_t* w[4]; };
__device__ __forceinline__ void prefetch_weights(const Weights& p, int i) {
  if (blockIdx.x < 128) asm volatile("cp.async.bulk.prefetch.L2.global [%0], 61440;" :: "l"(p.w[i] + (size_t)blockIdx.x * 61440) : "memory");
}
__global__ void __launch_bounds__(256) first_kernel(const __nv_bfloat16* __restrict__ xin, const uint4* __restrict__ wb, const __grid_constant__ Weights wa) {
  __shared__ __align__(16) float scratch[256];
  __shared__ uint32_t lat[4];
  const int warp = threadIdx.x >> 5, lane = threadIdx.x & 31, cta = blockIdx.x;
  TRACE(0);
  pdl_launch();
  if (warp < 4 && (warp < 2 || cta < NSLOT)) {
    uint32_t* q = reinterpret_cast<uint32_t*>(pool_at((warp < 2 ? NSLOT : cta) * 8192 + (warp & 1) * 4096)) + (warp < 2 ? (cta & 127) * 8 : 0);
    if (lane < 8) stg_strong32(q + lane, 0u);
    uint32_t best = ~0u;
    if (lane == 0)
      for (int r = 0; r < 4; r++) {
        uint32_t t0, t1, v;
        asm volatile("mov.u32 %0, %%clock;" : "=r"(t0) :: "memory");
        asm volatile("atom.relaxed.gpu.global.exch.b32 %0, [%1], 0;" : "=r"(v) : "l"(q) : "memory");
        asm volatile("{.reg .u32 t; add.u32 t, %1, 1; mov.u32 %0, %%clock; sub.u32 %0, %0, %1;}" : "=r"(t1) : "r"(__shfl_sync(1u, v, 0)) : "memory");
        best = min(best, t1 - t0);
      }
    if (lane == 0) lat[warp] = best;
  }
  __syncthreads();
  ABT(2, 0);
  if (threadIdx.x == 0) {
    const int part = lat[0] < lat[1] ? 0 : 1;
    uint32_t smid; asm("mov.u32 %0, %%smid;" : "=r"(smid));
    g_smpart[smid & 255] = part;
    g_smclk[smid & 255] = clk32() - gtime() * 2;
    g_smuse[smid & 255] = 0;
    if (cta < NSLOT) g_orient[cta] = lat[2] < lat[3] ? part : 1 - part;
  }
  if (cta < 128) {
    float4 v[2][5];
#pragma unroll
    for (int r = 0; r < 2; r++)
#pragma unroll
      for (int i = 0; i < 5; i++) {
        const uint32_t* src = reinterpret_cast<const uint32_t*>(xin) + (cta * 16 + r * 8 + (lane >> 2)) * (DM / 2) + warp * 40 + i * 8 + (lane & 3);
        const uint32_t a = src[0], b = src[4];
        v[r][i] = make_float4(bf_lo(a), bf_hi(a), bf_lo(b), bf_hi(b));
      }
    uint4 w8[2];
#pragma unroll
    for (int i = 0; i < 2; i++) w8[i] = wb[cta * 400 + min(i * 256 + threadIdx.x, 399)];
    if (threadIdx.x < 128) g_stat[cta * 128 + threadIdx.x] = make_float2(0.f, 0.f);
#pragma unroll
    for (int i = 0; i < 10; i++) g_x[((cta * 2 + i / 5) * 40 + warp * 5 + i % 5) * 32 + lane] = v[i / 5][i % 5];
    ABT(2, 1);
    if (threadIdx.x == 32) for (int i = 0; i < FK_PF; i++) prefetch_weights(wa, i);
    float mean[2], rs[2];
    ln_stats<2>(v, s2u(scratch), mean, rs);
    ABT(2, 2);
    uint32_t w[2][5][2];
#pragma unroll
    for (int i = 0; i < 10; i++) {
      const float4 t = v[i / 5][i % 5];
      const float m = mean[i / 5], q = rs[i / 5];
      w[i / 5][i % 5][0] = pack2((t.x - m) * q, (t.y - m) * q); w[i / 5][i % 5][1] = pack2((t.z - m) * q, (t.w - m) * q);
    }
    ln_store(w, cta, warp * 5);
    ABT(2, 3);
#pragma unroll
    for (int i = 0; i < 2; i++) {
      const int e = cta * 400 + min(i * 256 + threadIdx.x, 399), k = e / 80, n = e - k * 80, cg = n / 10;
      g_wb[((cg * 80 + (k >> 3)) * 10 + n - cg * 10) * 8 + (k & 7)] = w8[i];
    }
  } else if (cta == 128) {
    g_bo[threadIdx.x] = 0;
  }
  TRACE(2);
}

struct ChainParams {
  CUtensorMap wq, wk, wv, wo;
  const __nv_bfloat16* mem0;
  uint8_t *pool, *kv;
  const uint32_t* xc;
  uint32_t* sync;
  int layer;
  int d1, d1b, d2, d2b, mode;
};
constexpr int CH_WQ = 0, CH_WO = 81920, CH_X = CH_WO + 86016, CH_M = CH_X + 20480, CH_KT = CH_X + 40960, CH_VT = CH_KT + 4096,
              CH_QK = CH_VT + 8192, CH_VP = CH_QK + 4096, CH_SX = CH_VP + 1024, CH_O = CH_SX + 2304, CH_ID = CH_O + 3072,
              CH_BAR = CH_ID + 512;
constexpr int CH_SMEM = CH_BAR + 128;
constexpr int CH_BASE = 1024;
#define CH_VK0 8
#define CH_VK1 20
#define CH_L0 4
#define CH_LR 4
#define NOX 0
#define CH_XA 0
#define CH_XB 1
#define CH_W1 3
#define CH_W2 17
#define CH_W3 26
#define CH_RA 1
#define CH_R1 4
#define CH_TW 12
__device__ __forceinline__ uint32_t opaque(uint32_t x) { return __shfl_sync(~0u, x, threadIdx.x & 31); }
__device__ __forceinline__ uint32_t nz(uint32_t x) { uint32_t r; asm("max.u32 %0, %1, 1;" : "=r"(r) : "r"(x)); return r; }
__device__ __forceinline__ uint32_t pack_tag(float lo, float hi, uint32_t tag, uint32_t mask) {
  uint32_t r;
  asm("lop3.b32 %0, %1, %2, %3, 0xD8;" : "=r"(r) : "r"(pack2(lo, hi)), "r"(tag), "r"(mask));
  return r;
}
__device__ __forceinline__ uint32_t differ(uint32_t a, uint32_t b, uint32_t t) { uint32_t r; asm("lop3.b32 %0, %1, %2, %3, 0x7E;" : "=r"(r) : "r"(a), "r"(b), "r"(t)); return r; }
__device__ __forceinline__ void mbar_wait_hot(uint32_t bar, uint32_t ph) {
  uint32_t ok;
  asm volatile("{.reg .pred p; mbarrier.try_wait.parity.shared::cta.b64 p, [%1], %2; selp.u32 %0, 1, 0, p;}" : "=r"(ok) : "r"(bar), "r"(ph) : "memory");
  if (__builtin_expect(!ok, 0)) mbar_wait(bar, ph);
}
__device__ __forceinline__ bool elect() {
  uint32_t r; asm volatile("{.reg .pred p; elect.sync _|p, 0xffffffff; selp.u32 %0, 1, 0, p;}" : "=r"(r)); return r; }
__device__ __forceinline__ uint32_t or3(uint32_t a, uint32_t b, uint32_t c) { uint32_t r; asm("lop3.b32 %0, %1, %2, %3, 0xFE;" : "=r"(r) : "r"(a), "r"(b), "r"(c)); return r; }
__device__ __forceinline__ void pin() { pdl_launch(); }
__device__ __forceinline__ void mma16h(float* d, uint32_t a0, uint32_t a2, uint32_t b0, uint32_t b1) {
  asm volatile("{.reg .b32 u, v; mma.sync.aligned.m16n8k16.row.col.f32.bf16.bf16.f32 {%0,%1,%2,%3},{%4,u,%5,v},{%6,%7},{%0,%1,%2,%3};}"
               : "+f"(d[0]), "+f"(d[1]), "+f"(d[2]), "+f"(d[3]) : "r"(a0), "r"(a2), "r"(b0), "r"(b1)); }
__device__ __forceinline__ void mma8h(float* d, uint32_t a0, uint32_t b0) {
  asm volatile("{.reg .b32 u; mma.sync.aligned.m16n8k8.row.col.f32.bf16.bf16.f32 {%0,%1,%2,%3},{%4,u},{%5},{%0,%1,%2,%3};}"
               : "+f"(d[0]), "+f"(d[1]), "+f"(d[2]), "+f"(d[3]) : "r"(a0), "r"(b0)); }
__device__ __forceinline__ uint32_t absmax2(uint32_t a, uint32_t b) { uint32_t r; asm("max.xorsign.abs.bf16x2 %0, %1, %2;" : "=r"(r) : "r"(a), "r"(b)); return r; }
__device__ __forceinline__ void until(uint32_t t) { while ((int)(clk32() - t) < 0) {} }
__device__ __forceinline__ uint4 pack8(const float* d) { return make_uint4(pack2(d[0], d[1]), pack2(d[2], d[3]), pack2(d[4], d[5]), pack2(d[6], d[7])); }
__device__ __forceinline__ void add8(float* d, uint4 v) {
  d[0] += bf_lo(v.x); d[1] += bf_hi(v.x); d[2] += bf_lo(v.y); d[3] += bf_hi(v.y);
  d[4] += bf_lo(v.z); d[5] += bf_hi(v.z); d[6] += bf_lo(v.w); d[7] += bf_hi(v.w);
}

template <int WG>
__device__ __forceinline__ void chain_body(const ChainParams& p, const uint32_t wq, const uint32_t (&ak)[80], const uint32_t (&av)[80]) {
  const int tid = threadIdx.x & 127, t4 = __shfl_sync(~0u, tid >> 5, 0), lane = tid & 31;
  const int cta = blockIdx.x, h = cta / 3, j = cta - 3 * h;
  const uint32_t sb = mapa(CH_BASE, j);
  const uint32_t bWo = sb + CH_BAR, bWq = bWo + 8, bX = bWo + 16, bXA = bWo + 24, bXB = bWo + 32, bO = bWo + 40, bG0 = bWo + 48;
  uint32_t tw[4 * CH_TW];
  auto refill = [&]() {
#pragma unroll
    for (int k = 0; k < CH_TW; k++) ldsm4t(&tw[4 * k], wq + k * 2048);
  };
  const uint32_t wo = opaque((sb + CH_WO + (WG == 0 ? (t4 + (j == 2)) * 4096 : (j == 2 ? 0 : 24576) + t4 * 1024) + ((lane & 7) + (lane >> 4) * 8) * 64 +
                              ((((lane >> 3) & 1) ^ ((lane >> 1) & 3)) << 4)) ^ (WG == 1 && j == 2 ? 32 : 0));
  const uint32_t wo2 = opaque((wo ^ ((t4 & 1) * 32)) + (4 + (t4 >> 1) - t4) * 4096);
  const uint32_t l16 = opaque(sb + lane * 16);
  const uint32_t l8 = opaque(sb + t4 * 256 + lane * 8);
  const uint32_t lw = opaque(sb + t4 * 1024 + lane * 16);
  const uint32_t qs = opaque(sb + CH_QK + WG * 2048 + t4 * 512 + lane * 16);
  const uint32_t qa = opaque(sb + CH_QK + (lane >> 4) * 2048 + (lane & 15) * 16 + (WG == 0 ? t4 * 512 + 256 : t4 == 3 ? 1024 : 0));
  const uint32_t ka = opaque(t4 < 2 ? sb + CH_KT + t4 * 512 + lane * 16
                                    : sb + CH_QK + 256 + (t4 - 2) * 1024 + ((lane >> 3) & 1) * 2048 + (lane >> 4) * 128 + (lane & 7) * 16);
  const uint32_t l4 = opaque(sb + t4 * 256 + lane * 4);
  uint32_t pdst[3], pages = 0;
  auto line0 = [&](int i) { return 28 * j + (i < 4 ? 4 * t4 + i : 12 + 2 * t4 + i); };
  const uint32_t plane = opaque((lane >> 4) * 2048 + h * 64 + (lane & 15) * 4);
  if (WG == 0) {
    pages = __ballot_sync(~0u, lds32(sb + CH_O + line0(min(lane, 5)) * 4) & 4096);
  } else {
    pages = __ballot_sync(~0u, lds32(sb + CH_O + (80 + min(lane, 11)) * 4) & 4096);
    pdst[0] = opaque(lds32(sb + CH_O + (j == 0 ? 24 + t4 : 50 + 2 * j + (t4 & 1)) * 4) + plane);
    const uint32_t role = lds32(sb + CH_O + NSLOT * 4);
    pdst[1] = opaque(lds32(sb + CH_O + role * 4) + (t4 & 1) * 2048 + (lane & 7) * 64 + (lane >> 3) * 16);
    pdst[2] = opaque((80 + role / 20) * 8192 + role % 20 * 128 + (t4 >= 2 ? (t4 & 1) * 64 + (lane & 3) * 16 + (lane >> 2) * 2 : (t4 & 1) * 4096 + lane * 4));
  }
  const uint32_t r1 = mapa(CH_BASE, j == 2 ? 0 : j + 1) - sb, r2 = mapa(CH_BASE, j == 0 ? 2 : j - 1) - sb;
  uint32_t tag = opaque(1);
  auto pool = [&](uint32_t off) { return p.pool + ((tag & 0xfffe) + off); };
  auto after = [&](uint32_t x) { return x & tag & 0xfffe; };
  auto kv = [&](int s, uint32_t a) { return p.kv + ((size_t)(cta * 2 * NSEG + s) * KV_BYTES - sb) + a; };
  auto pass = [&](float (&d)[16], const uint32_t (&a)[80]) {
    const uint64_t db = mkdesc(CH_BASE + CH_X + WG * 20480, 512, 128, 0);
    wg_fence();
#pragma unroll
    for (int k = 0; k < 20; k++) {
      wg_rs32_00(d, a[4 * k], a[4 * k + 1], a[4 * k + 2], a[4 * k + 3], db + k * 64, k);
      if (k == 19 || (WG == 1 && k == 9)) wg_commit();
    }
  };
  auto dump = [&](float (&d)[16], uint32_t a) {
    wg_wait<0>();
    reg_fence<16>(d);
    sts128(a, pack8(d)); sts128(a + 512, pack8(d + 8));
  };
  auto tokens0 = [&](int s) {
    float d[16];
    if (!NOX || s == 0) mbar_wait_hot(bXB, s & 1);
    bar_sync(7, 256);
    pass(d, ak);
    TM1(5);
    bar_sync(9, 256);
    const uint4 k0 = lds128(lw + CH_KT), k1 = lds128(lw + CH_KT + 512);
    __syncwarp();
    wg_wait<0>();
    reg_fence<16>(d);
    add8(d, k0); add8(d + 8, k1);
#pragma unroll
    for (int e = 0; e < 2; e++) { const uint4 v = pack8(d + 8 * e); stsm4t(lw + CH_KT + e * 512, v.x, v.z, v.y, v.w); }
    fence_async();
    __syncwarp();
    if (elect()) { bulk_store(p.kv + (size_t)(cta * 2 * NSEG + s) * KV_BYTES + t4 * 1024, sb + CH_KT + t4 * 1024, 1024); bulk_commit(); }
    TM1(6);
    bar_sync(8, 256);
    pass(d, av);
    TM1(9);
    bulk_wait_read<0>();
    dump(d, lw + CH_VT);
  };
  PRO(11);
  if (WG == 0) {
    tokens0(0);
  } else {
    const uint32_t* m0 = reinterpret_cast<const uint32_t*>(p.mem0) + (lane >> 2) * 320 + t4 * 80 + (lane & 3);
    uint32_t a[20];
#pragma unroll
    for (int i = 0; i < 20; i++) a[i] = m0[4 * i];
    pin();
    float d[16];
    mbar_wait(bXA, 0);
    pass(d, ak);
    bar_arrive(7, 256);
    dump(d, lw + CH_KT);
    bar_arrive(9, 256);
    pass(d, av);
    bar_arrive(8, 256);
    dump(d, lw + CH_VT + 4096);
    bar_sync(3, 128);
#pragma unroll
    for (int i = 0; i < 20; i++) sts32(sb + CH_M + (t4 * 20 + i) * 128 + lane * 4, transpose8(a[i]));
  }
  PRO(8);
  mbar_wait(bWq, 0);
  refill();
  PRO(9);
  mbar_wait(bWo, 0);
  asm volatile("barrier.cluster.wait.aligned;" ::: "memory");
  PRO(10);
  constexpr int VK = WG == 0 ? CH_VK0 : CH_VK1;
  auto project = [&](int s, uint32_t (&b)[40], float (&dv)[16], uint32_t (&kf)[16]) {
    float dq[4] = {}, dk[4] = {};
    uint32_t w[80];
#pragma unroll
    for (int i = 0; i < 4 * CH_TW; i++) w[i] = tw[i];
    auto load = [&](int n) {
      int c = 0;
#pragma unroll
      for (int i = 0; i < 10; i++) {
        if (c++ == n) ldsm4t(&b[4 * i], l16 + CH_M + WG * 5120 + i * 512);
#pragma unroll
        for (int k = 2 * i; k < 2 * i + 2; k++)
          if (k >= CH_TW && c++ == n) ldsm4t(&w[4 * k], wq + k * 2048);
      }
#pragma unroll
      for (int i = 0; i < 4; i++)
        if (WG == 1 && c++ == n) ldsm4(&kf[4 * i], ka + i * 1024);
    };
#pragma unroll
    for (int n = 0; n < CH_L0; n++) load(n);
    TM(0);
#pragma unroll
    for (int k = 0; k < 20; k += 2) {
      if (k > 0) {
#pragma unroll
        for (int n = CH_L0 + (k - 2) * CH_LR / 4; n < (k == 18 ? 40 : CH_L0 + k * CH_LR / 4); n++) load(n);
      }
      pin();
#pragma unroll
      for (int kk = k; kk < k + 2; kk++) {
        mma16(dk, ak[4 * kk], ak[4 * kk + 1], ak[4 * kk + 2], ak[4 * kk + 3], b[2 * kk], b[2 * kk + 1]);
        mma16(dq, w[4 * kk], w[4 * kk + 1], w[4 * kk + 2], w[4 * kk + 3], b[2 * kk], b[2 * kk + 1]);
        if (kk < VK) mma16(dv, av[4 * kk], av[4 * kk + 1], av[4 * kk + 2], av[4 * kk + 3], b[2 * kk], b[2 * kk + 1]);
      }
    }
    const float k2 = 0.07216878364870322f * 1.44269504089f;
    stsm4t(qs, pack2(dq[0] * k2, dq[1] * k2), pack2(dq[2] * k2, dq[3] * k2), pack2(dk[0], dk[1]), pack2(dk[2], dk[3]));
    TM(1);
  };
  constexpr int VC = VK == 20 ? 1 : WG == 0 ? 2 : 3;
  auto finish_v = [&](const uint32_t (&b)[40], float (&dv)[16]) {
#pragma unroll
    for (int kk = VK; kk < 20; kk++) mma16(dv + 4 * ((kk - VK) % VC), av[4 * kk], av[4 * kk + 1], av[4 * kk + 2], av[4 * kk + 3], b[2 * kk], b[2 * kk + 1]);
  };
  auto sum_v = [&](float (&dv)[16]) {
#pragma unroll
    for (int i = 4; i < 4 * VC; i++) dv[i & 3] += dv[i];
  };
  auto publish_km = [&](int s) {
    uint32_t a[4];
    ldsm4(a, qa);
    *reinterpret_cast<uint2*>(kv(s, l8) + KV_M) = make_uint2(hadd2(a[0], a[2]), hadd2(a[1], a[3]));
  };
  auto load_v = [&](uint4 (&vr)[4]) {
#pragma unroll
    for (int e = 0; e < 4; e++) vr[e] = lds128(lw + CH_VT + (e & 1) * 4096 + (e >> 1) * 512);
  };
  auto token_v = [&](uint4 (&v)[2], const uint4 (&vr)[4]) {
#pragma unroll
    for (int e = 0; e < 2; e++) {
      const uint4 x = vr[2 * e], y = vr[2 * e + 1];
      v[e] = make_uint4(hadd2(x.x, y.x), hadd2(x.z, y.z), hadd2(x.y, y.y), hadd2(x.w, y.w));
    }
  };
  auto memory_v = [&](uint2 x, const float (&dv)[16]) {
    return make_uint2(pack2(dv[0] + bf_lo(x.x), dv[1] + bf_hi(x.x)), pack2(dv[2] + bf_lo(x.y), dv[3] + bf_hi(x.y)));
  };
  auto publish_v = [&](int s, const uint4 (&v)[2], uint2 vm) {
#pragma unroll
    for (int e = 0; e < 2; e++) reinterpret_cast<uint4*>(kv(s, lw) + KV_V)[e * 32] = v[e];
    *reinterpret_cast<uint2*>(kv(s, l8) + KV_V + KV_M) = vm;
  };
  auto load_x = [&](int s, int k0, int n, uint32_t bar) {
    if (!NOX && elect()) { mbar_expect(bar, n * 1024); bulk_load(sb + CH_X + k0 * 1024, p.xc + (s + 1) * 10240 + k0 * 256, n * 1024, bar); }
  };
  uint32_t gph = 0;
  int st = 0;
#pragma unroll 1
  for (int s = 0; s < NSEG - 1; s++) {
    bar_sync(6, 256);
    float dv[16] = {};
    uint32_t b[40], kf[16];
    project(s, b, dv, kf);
    if (WG == 0) {
      bar_sync(1, 256);
      if (CH_XA == 0) load_x(s, 20 + 5 * t4, 5, bXA);
      if (CH_XB == 0) load_x(s, 5 * t4, 5, bXB);
      pin();
      finish_v(b, dv);
      sum_v(dv);
      sts64(l8 + CH_VP, pack2(dv[0], dv[1]), pack2(dv[2], dv[3]));
      __syncwarp();
      if (elect()) mbar_arrive(bX);
      if (CH_XA == 1) load_x(s, 20 + 5 * t4, 5, bXA);
      if (CH_XB == 1) load_x(s, 5 * t4, 5, bXB);
      uint32_t w[144];
      auto wload = [&](int i) { ldsm4t(&w[4 * i], (i % 3 == 0 ? wo : i % 3 == 1 ? wo ^ 32 : wo2) + i / 12 * 28672 + i / 3 % 4 * 1024); };
      TM(3);
#pragma unroll
      for (int i = 0; i < CH_W1; i++) wload(i);
      bar_sync(10, 256);
#pragma unroll
      for (int i = CH_W1; i < CH_W2; i++) wload(i);
      if (CH_XA == 2) load_x(s, 20 + 5 * t4, 5, bXA);
      if (CH_XB == 2) load_x(s, 5 * t4, 5, bXB);
      bar_sync(2, 256);
      {
        float y[3][4] = {};
        uint32_t ob[24];
        ldsm4(&ob[0], l16 + CH_O + 1024); ldsm4(&ob[4], l16 + CH_O + 1536);
        TM(7);
        auto step = [&](int i) {
          const int k = i / 3;
          mma16(y[i % 3], w[4 * i], w[4 * i + 1], w[4 * i + 2], w[4 * i + 3], ob[2 * k], ob[2 * k + 1]);
        };
#pragma unroll
        for (int i = 0; i < 12; i++) {
          step(i);
          if (i >= 12 - (CH_W3 - CH_W2)) wload(CH_W3 - 12 + i);
          if (i % 3 == 2) pin();
        }
        if (CH_XB == 3) load_x(s, 5 * t4, 5, bXB);
        pin();
        mbar_wait(bO, s & 1);
        TM(4);
        ldsm4(&ob[8], l16 + CH_O); ldsm4(&ob[12], l16 + CH_O + 512);
        pin();
        float2 inv;
        uint8_t* dst[6];
        uint32_t mask;
#pragma unroll
        for (int i = 12; i < 36; i++) {
          step(i);
          const int n = CH_W3 + i - 13, m = n - (n > 30);
          if (i == 12) ldsm4(&ob[16], l16 + after(w[4 * CH_W3 - 1] | w[4 * CH_W3 - 5] | w[4 * CH_W3 - 9] | ob[8]) + CH_O + 2048);
          else if (n == 30) ldsm4(&ob[20], l16 + CH_O + 2560);
          else if (m < 36) wload(m);
          else if (m == 36) inv = lds64f((l8 & ~0xe0u) + CH_VP);
          if (i == 26) mask = ((l16 ^ tag) & 48) == 0;
          if (i >= 27 && i < 33) dst[i - 27] = pool(line0(i - 27) * 8192 + (pages >> (i - 27) & 1) * 4096) + plane;
          if (i % 3 == 2) pin();
        }
#pragma unroll
        for (int k = 0; k < CH_R1; k++) ldsm4t(&tw[4 * k], wq + k * 2048);
        pin();
#pragma unroll
        for (int i = 0; i < 6; i++) stg_strong32(dst[i], pack_tag(y[i >> 1][2 * (i & 1)] * inv.x, y[i >> 1][2 * (i & 1) + 1] * inv.y, tag, mask));
        TM(8);
        bar_arrive(5, 256);
        pin();
#pragma unroll
        for (int k = CH_R1; k < CH_TW; k++) ldsm4t(&tw[4 * k], wq + k * 2048);
      }
      publish_km(s);
      if (t4 == 3 && cta < 40 && s + 4 < NSEG && elect())
        asm volatile("cp.async.bulk.prefetch.L2.global [%0], 1024;" :: "l"(p.xc + (s + 4) * 10240 + cta * 256) : "memory");
      if (t4 == 2 && (s & 3) == 0 && s > 0 && elect()) red_relaxed(p.sync + 2 * s - 4, 1);
      if (t4 == 2 && s == NSEG - 3 && cta == 95 && elect()) red_relaxed(p.sync + 2 * s + 2, 0x10000);
      tokens0(s + 1);
      TM(2);
    } else {
      const uint32_t xo = l4 + (CH_SX - (t4 == 3 ? 128 : 0)), x1 = xo + (r1 + 768 + min(t4, 2) * 256), x2 = xo + (r2 + 1024 + min(t4, 2) * 256);
      if (t4 < 2) {
        float ds[4][4] = {};
        uint32_t q[16];
        asm volatile("bar.sync 1, 256;" ::: "memory");
#pragma unroll
        for (int k = 0; k < 4; k++) ldsm4(&q[4 * k], qa + k * 512);
        pin();
        if (VK < 20) { finish_v(b, dv); pin(); }
#pragma unroll
        for (int k = 0; k < 4; k++) {
          mma16(ds[k & 1], kf[4 * k], kf[4 * k + 1], kf[4 * k + 2], kf[4 * k + 3], q[4 * k], q[4 * k + 1]);
          mma16(ds[2 + (k & 1)], kf[4 * k], kf[4 * k + 1], kf[4 * k + 2], kf[4 * k + 3], q[4 * k + 2], q[4 * k + 3]);
        }
        float t[4];
#pragma unroll
        for (int i = 0; i < 4; i++) t[i] = (ds[0][i] + ds[2][i]) + (ds[1][i] + ds[3][i]);
        const uint32_t w0 = pack2(t[0], t[1]), w1 = pack2(t[2], t[3]);
        st_async32(x1, w0, bX + r1); st_async32(x2, w0, bX + r2);
        st_async32(x1 + 128, w1, bX + r1); st_async32(x2 + 128, w1, bX + r2);
        sts32(xo, w0); sts32(xo + 128, w1);
      } else {
        float ds[4][4] = {};
        uint32_t q0[4], q1[4], a0[4], a1[4];
        asm volatile("bar.sync 1, 256; " ::: "memory");
        ldsm4(a0, ka); ldsm4(q0, qa); ldsm4(a1, ka + 512); ldsm4(q1, qa + 512);
        pin();
        if (VK < 20) { finish_v(b, dv); pin(); }
        mma16(ds[0], a0[0], a0[1], a0[2], a0[3], q0[0], q0[1]);
        mma16(ds[1], a0[0], a0[1], a0[2], a0[3], q0[2], q0[3]);
        mma16(ds[2], a1[0], a1[1], a1[2], a1[3], q1[0], q1[1]);
        mma16(ds[3], a1[0], a1[1], a1[2], a1[3], q1[2], q1[3]);
        float t[2];
#pragma unroll
        for (int i = 0; i < 2; i++)
          t[i] = ((ds[0][i] + ds[0][i + 2]) + (ds[1][i] + ds[1][i + 2])) + ((ds[2][i] + ds[2][i + 2]) + (ds[3][i] + ds[3][i + 2]));
        const uint32_t w0 = pack2(t[0], t[1]);
        st_async32(x1, w0, bX + r1);
        st_async32(x2, w0, bX + r2);
        sts32(xo, w0);
      }
      TM(3);
      const uint4 id = lds128(l16 + CH_ID);
      float sc[3][4] = {};
      uint4 v[2], vr[4];
      sum_v(dv);
      bar_sync(3, 128);
      uint32_t r[12], wd[12];
      ldsm4(&r[0], l16 + CH_SX); ldsm2(&r[4], l16 + CH_SX + 512);
      pin();
      load_v(vr);
#pragma unroll
      for (int u = 0; u < 3; u++) ldsm4t(&wd[4 * u], wo + u * 28672);
      pin();
#pragma unroll
      for (int q = 0; q < 3; q++) mma16(sc[q], id.x, id.y, id.z, id.w, r[2 * q], r[2 * q + 1]);
      uint32_t big = absmax2(absmax2(absmax2(r[0], r[1]), absmax2(r[2], r[3])), absmax2(r[4], r[5]));
      token_v(v, vr);
      const uint32_t oa1 = l4 + (r1 + CH_O), oa2 = l4 + (r2 + CH_O + 2048), ones = 0x3f803f80u;
      mbar_wait_hot(bX, s & 1);
      TM(4);
      ldsm4(&r[0], l16 + CH_SX + 768); ldsm4(&r[8], l16 + CH_SX + 1792); ldsm4(&r[4], l16 + CH_SX + 1280);
      const uint2 vp = lds64(l8 + CH_VP);
      bar_arrive(10, 256);
      pin();
      {
        float sd[3][4] = {};
#pragma unroll
        for (int i = 0; i < 3; i++) {
          const int q = i == 0 ? 0 : 3 - i;
          mma16(sc[q], id.x, id.y, id.z, id.w, r[4 * q], r[4 * q + 1]);
          mma16(sd[q], id.x, id.y, id.z, id.w, r[4 * q + 2], r[4 * q + 3]);
          big = absmax2(big, absmax2(absmax2(r[4 * q], r[4 * q + 1]), absmax2(r[4 * q + 2], r[4 * q + 3])));
        }
#pragma unroll
        for (int i = 0; i < 12; i++) sc[i >> 2][i & 3] += sd[i >> 2][i & 3];
      }
      const bool redo = __any_sync(~0u, (absmax2(big, big << 16) & 0x7fff0000u) >= 0x41800000u);
      const uint2 vm = memory_v(vp, dv);
      sc[2][0] += sc[2][2]; sc[2][1] += sc[2][3];
      float l[4], o[2][4];
      uint32_t p3, p4;
      auto attend = [&]() {
#pragma unroll
        for (int i = 0; i < 4; i++) l[i] = o[0][i] = o[1][i] = 0.f;
        const uint32_t p1 = pack2(ex2(sc[0][0]), ex2(sc[0][1])), p2 = pack2(ex2(sc[0][2]), ex2(sc[0][3]));
        mma16h(o[0], p1, p2, v[0].x, v[0].y);
        mma16h(o[1], p1, p2, v[0].z, v[0].w);
        mma16h(l, p1, p2, ones, ones);
        const uint32_t p0 = pack2(ex2(sc[2][0]), ex2(sc[2][1]));
        mma8h(o[0], p0, vm.x);
        mma8h(o[1], p0, vm.y);
        mma8h(l, p0, ones);
        p3 = pack2(ex2(sc[1][0]), ex2(sc[1][1])); p4 = pack2(ex2(sc[1][2]), ex2(sc[1][3]));
        mma16h(o[0], p3, p4, v[1].x, v[1].y);
        mma16h(o[1], p3, p4, v[1].z, v[1].w);
      };
      attend();
      if (__builtin_expect(redo, 0)) {
        float mx = fmaxf(sc[2][0], sc[2][1]);
#pragma unroll
        for (int i = 0; i < 4; i++) mx = fmaxf(mx, fmaxf(sc[0][i], sc[1][i]));
        mx = fmaxf(mx, __shfl_xor_sync(~0u, mx, 1));
        mx = fmaxf(mx, __shfl_xor_sync(~0u, mx, 2));
#pragma unroll
        for (int i = 0; i < 4; i++) { sc[0][i] -= mx; sc[1][i] -= mx; }
        sc[2][0] -= mx; sc[2][1] -= mx;
        attend();
      }
      const uint32_t o0 = pack2(o[0][0], o[0][1]), o1 = pack2(o[1][0], o[1][1]);
      st_async32(oa1, o0, bO + r1); st_async32(oa2, o0, bO + r2);
      st_async32(oa1 + 128, o1, bO + r1); st_async32(oa2 + 128, o1, bO + r2);
      sts32(l4 + CH_O + 1024, o0); sts32(l4 + CH_O + 1152, o1);
      bar_arrive(2, 256);
      pin();
      TM(6);
      mma16h(l, p3, p4, ones, ones);
      float inv;
      asm("rcp.approx.ftz.f32 %0, %1;" : "=f"(inv) : "f"(l[0]));
      sts32((l8 & ~0xffu) + (lane & 28) + CH_VP, __float_as_uint(inv));
      __syncwarp();
      if (elect()) mbar_arrive(bO);
      {
        float z[2][4] = {}, y[2][4] = {};
        uint32_t we[12] = {};
        mma16(z[0], wd[0], wd[1], wd[2], wd[3], o0, o1);
        if (j == 0) {
#pragma unroll
          for (int u = 0; u < 3; u++) ldsm4t(&we[4 * u], (wo ^ 32) + u * 28672);
          mma16(y[0], we[0], we[1], we[2], we[3], o0, o1);
        }
        const float2 iv = lds64f((l8 & ~0xe0u) + CH_VP);
        uint8_t* dst = pool(pdst[0]);
        const uint32_t mask = ((l16 ^ tag) & 48) == 0;
        const uint32_t oa = qa + ((tag & 0xfffe) + CH_O - CH_QK + t4 * 256 - (t4 == 3 ? 1024 : 0));
        const uint32_t za = l16 + ((tag & 0xfffe) + (t4 >> 1) * 512 + (t4 & 1) * 8);
        pin();
        mbar_wait(bO, s & 1);
        uint32_t a[4];
        ldsm4(a, oa);
        mma16(z[0], wd[4], wd[5], wd[6], wd[7], a[0], a[1]);
        mma16(z[1], wd[8], wd[9], wd[10], wd[11], a[2], a[3]);
        if (j == 0) {
          mma16(y[0], we[4], we[5], we[6], we[7], a[0], a[1]);
          mma16(y[1], we[8], we[9], we[10], we[11], a[2], a[3]);
          sts128f(lw + CH_VT + 512, y[0][0] + y[1][0], y[0][1] + y[1][1], y[0][2] + y[1][2], y[0][3] + y[1][3]);
        }
        sts128f(lw + CH_VT, z[0][0] + z[1][0], z[0][1] + z[1][1], z[0][2] + z[1][2], z[0][3] + z[1][3]);
        bar_sync(3, 128);
        if (j == 0 || t4 < 2) {
          float2 q[4];
#pragma unroll
          for (int i = 0; i < 4; i++) q[i] = lds64f(za + CH_VT + i * 1024);
          stg_strong32(dst, pack_tag(((q[0].x + q[1].x) + (q[2].x + q[3].x)) * iv.x, ((q[0].y + q[1].y) + (q[2].y + q[3].y)) * iv.y, tag, mask));
        }
      }
      TM(2);
      float d[16];
      bar_sync(5, 256);
      publish_v(s, v, vm);
#pragma unroll
      for (int k = 0; k < CH_RA; k++) ldsm4t(&tw[4 * k], wq + k * 2048);
      if (t4 == 0 && s + 2 < NSEG && elect()) { mbar_expect(bX, 1536); mbar_expect(bO, 2048); }
      if (!NOX) mbar_wait_hot(bXA, (s + 1) & 1);
      uint8_t* mdst = p.pool + ((t4 >= 2 ? st : st == 2 ? 0 : st + 1) * 32768 + pdst[2]);
      const uint8_t* psrc = pool(pdst[1] + after(tw[4 * CH_RA - 1]));
      pin();
      pass(d, ak);
      bar_arrive(7, 256);
      TM(5);
      if (t4 >= 2) {
        uint4 u[4];
        DELAY(p.d1);
#pragma unroll
        for (int i = 0; i < 4; i++) u[i] = ldg_strong128(psrc + i * 512);
        __syncwarp();
        dump(d, lw + CH_KT);
        bar_arrive(9, 256);
        TM(14);
        TMD(15, u[3].x);
        const uint32_t one = lane & 4 ? 0x3f800000u : 0x00003f80u, g2 = lane >> 3;
        int n = 0;
        float y[4][4];
        for (;;) {
#pragma unroll
          for (int i = 0; i < 4; i++) y[0][i] = y[1][i] = y[2][i] = y[3][i] = 0.f;
#pragma unroll
          for (int i = 0; i < 4; i++) {
            mma16h(y[i & 1], g2 == 0 ? one : 0, g2 == 1 ? one : 0, u[i].x, u[i].y);
            mma16h(y[2 + (i & 1)], g2 == 2 ? one : 0, g2 == 3 ? one : 0, u[i].z, u[i].w);
          }
          if (__builtin_expect(!__any_sync(~0u, (differ(u[0].x, u[1].x, tag) | differ(u[2].x, u[3].x, tag)) & 1), 1)) break;
#pragma unroll
          for (int i = 0; i < 4; i++) u[i] = ldg_strong128(psrc + i * 512);
          spin_guard(n);
        }
        const float v = ((y[0][0] + y[0][1]) + (y[2][0] + y[2][1])) + ((y[1][0] + y[1][1]) + (y[3][0] + y[3][1]));
        const uint32_t w = nz(pack2(v, 0.f));
        stg_strong16(mdst, w); stg_strong16(mdst + 4096, w);
        TMV(12, 32, n);
      } else {
        dump(d, lw + CH_KT);
        bar_arrive(9, 256);
        stg_strong32(mdst, 0u);
      }
      TM(8);
      bar_sync(3, 128);
      pass(d, av);
      bar_arrive(8, 256);
      TM(7);
      const uint32_t bG = bG0 + t4 * 8, mq = sb + CH_M + t4 * 2560;
      const uint8_t* msrc = p.pool + ((80 + st * 4 + t4) * 8192 + (pages >> (st * 4 + t4) & 1) * 4096);
      wg_wait<1>();
      bar_sync(3, 128);
      DELAY(p.d2);
      if (elect()) { mbar_expect(bG, 2560); bulk_load(mq, msrc, 2560, bG); }
      TM(9);
      dump(d, lw + CH_VT + 4096);
#pragma unroll
      for (int k = CH_RA; k < CH_TW; k++) ldsm4t(&tw[4 * k], wq + k * 2048);
      TM(10);
      int n = 0;
      for (;;) {
        mbar_wait(bG, gph);
        gph ^= 1;
        const uint32_t c = mq + lane * 32 + (lane >> 2) * 4;
        if (!__any_sync(~0u, __vimin3_u32(lds32(c), lds32(c + 1024), lds32(c + 1536)) == 0)) break;
        if (elect()) { mbar_expect(bG, 2560); bulk_load(mq, msrc, 2560, bG); }
        spin_guard(n);
      }
      TM(11);
      TMV(13, 32, n);
    }
    if (++st == 3) st = 0;
    tag ^= 0x10001;
  }
  {
    const int s = NSEG - 1;
    bar_sync(6, 256);
    float dv[16] = {};
    uint32_t b[40], kf[16];
    project(s, b, dv, kf);
    finish_v(b, dv);
    sum_v(dv);
    if (WG == 0) {
      sts64(l8 + CH_VP, pack2(dv[0], dv[1]), pack2(dv[2], dv[3]));
      bar_sync(1, 256);
      publish_km(s);
      bulk_wait<0>();
      fence_async_global();
      bar_sync(2, 256);
      if (tid == 0) red_release(g_sync + 15 * 8 + 4, 1);
    } else {
      uint4 v[2], vr[4];
      load_v(vr);
      token_v(v, vr);
      bar_sync(1, 256);
      publish_v(s, v, memory_v(lds64(l8 + CH_VP), dv));
      bar_arrive(2, 256);
    }
  }
}

__global__ void __launch_bounds__(256, 1) chain_kernel(const __grid_constant__ ChainParams p) {
  extern __shared__ __align__(1024) uint8_t smem_raw[];
  const uint32_t sb = s2u(smem_raw);
  const int tid = threadIdx.x, warp = __shfl_sync(~0u, tid >> 5, 0), lane = tid & 31;
  const int cta = blockIdx.x, h = cta / 3, j = cta - 3 * h, colbase = cta * 64;
  const uint32_t bWo = sb + CH_BAR, bWq = bWo + 8, bXA = bWo + 24, bWk = bWo + 80, bWv = bWo + 88;
  uint32_t smid; asm("mov.u32 %0, %%smid;" : "=r"(smid));
  PRO(0);
  if (sb != mapa(CH_BASE, j)) __trap();
  uint32_t entry = 0;
  auto place = [&]() {
    const int i = tid - 128;
    if (i >= 0 && i <= NSLOT) {
      const uint32_t side = ldg_strong32(g_smpart + (smid & 255));
      if (i < NSLOT) {
        entry = i * 8192 + (ldg_strong32(g_orient + i) == (i < 80 ? i & 1 : side) ? 0 : 4096);
      } else {
        const uint32_t t = atomicAdd(g_bo + p.layer * 128 + 1 + side, 1);
        entry = t < 40 ? 2 * t + side : 2 * (79 - min(t, 79u)) + 1 - side;
      }
    }
    __syncwarp();
  };
  if (p.layer) place();
  if (warp == 0 && elect()) {
#pragma unroll 1
    for (int i = 0; i < 12; i++) mbar_init(bWo + 8 * i, i == 2 || i == 5 ? 5 : i == 3 || i == 4 ? 4 : 1);
    asm volatile("fence.mbarrier_init.release.cluster;" ::: "memory");
    mbar_expect(bWk, 81920);
    tma_load3<(WEF & 1) != 0>(sb + CH_WQ, &p.wk, colbase, 0, bWk);
    mbar_expect(bWv, 81920);
    tma_load3<(WEF & 1) != 0>(sb + CH_WO, &p.wv, colbase, 0, bWv);
    mbar_expect(bWo + 16, 1536);
    mbar_expect(bWo + 40, 2048);
    mbar_expect(bWo, 86016); mbar_expect(bWq, 81920);
#pragma unroll 1
    for (int i = 0; i < 8; i++) mbar_expect(bXA + 8 * (i & 1), 5120);
  }
  if (warp == 1) {
    const uint32_t id = (lane >> 3) == (lane & 3) ? ((lane & 4) ? 0x3f800000u : 0x00003f80u) : 0u;
    sts128(sb + CH_ID + lane * 16, make_uint4(id, 0, 0, id));
  }
  __syncthreads();
  asm volatile("barrier.cluster.arrive.relaxed.aligned;" ::: "memory");
  uint32_t ak[80], av[80];
  const uint32_t wq = opaque(sb + CH_WQ + ((warp >> 2) * 320 + (lane & 7) + (lane >> 4) * 8) * 128 + (((2 * (warp & 3) + ((lane >> 3) & 1)) ^ (lane & 7)) << 4));
  pdl_wait();
  if (tid == 32) stg_strong32(g_smuse + (smid & 255), p.layer + 1);
  pdl_launch();
  PRO(1);
  if (warp == 0 && elect()) {
    bulk_load(sb + CH_X + 20480, p.xc + 5120, 20480, bXA);
    bulk_load(sb + CH_X, p.xc, 20480, bXA + 8);
  }
  if (!p.layer) place();
  __syncwarp();
  PRO(2);
  mbar_wait(bWk, 0);
  PRO(3);
#pragma unroll
  for (int k = 0; k < 20; k++) ldsm4t(&ak[4 * k], wq + k * 2048);
  bar_sync(6, 256);
  if (warp == 0 && elect()) tma_load3<(WEF & 2) != 0>(sb + CH_WQ, &p.wq, colbase, 0, bWq);
  __syncwarp();
  PRO(4);
  mbar_wait(bWv, 0);
  PRO(5);
#pragma unroll
  for (int k = 0; k < 20; k++) ldsm4t(&av[4 * k], wq + CH_WO + k * 2048);
  bar_sync(6, 256);
  PRO(6);
  if (warp >= 5 && elect()) tma_load3<(WEF & 2) != 0>(sb + CH_WO + (warp - 5) * 28672, &p.wo, j == 0 ? 0 : 32 + j * 192, h * 192 + (j + 8 - warp) % 3 * 64, bWo);
  if (tid >= 128 && tid <= 128 + NSLOT) sts32(sb + CH_O + (tid - 128) * 4, entry);
  PRO(7);
  __syncthreads();
  if (__shfl_sync(~0u, tid >> 7, 0) == 0) chain_body<0>(p, wq, ak, av); else chain_body<1>(p, wq, ak, av);
}

struct PostParams { CUtensorMap wq, wo, wb, wo2, wb2; int gap, share, layer, look, gap2, pol; };
constexpr int PS = 8, PB = 28672;
constexpr int OP_SMEM = PS * PB + 512 + 2048;
enum { IT_ATT = 0, IT_OP = 1, IT_FIN = 2, IT_BQ = 3, IT_Q = 4 };

__device__ __forceinline__ uint32_t item_count(int type, int b) {
  return type == IT_ATT ? 32 : type == IT_OP ? op_split(b) * (DM / op_width(b)) : type == IT_FIN ? fin_items(b) : 1920 / bq_width(b); }
__device__ __forceinline__ uint32_t item_need(int type, int b) { return type == IT_ATT ? 96 : item_count(type - 1, b); }

struct Ring {
  uint32_t sb, bars; int st; uint32_t ph;
  __device__ __forceinline__ uint32_t wait() const { mbar_wait(bars + 8 * st, ph); return sb + st * PB; }
  __device__ __forceinline__ void next() { if (++st == PS) { st = 0; ph ^= 1; } }
  __device__ __forceinline__ void release(int s) const { if ((threadIdx.x & 31) == 0) mbar_arrive(bars + 8 * (PS + s)); }
  __device__ __forceinline__ void pop() { __syncwarp(); release(st); next(); }
};

template <int N>
__device__ __forceinline__ void gemm_item(Ring& r, float* d, int nst, uint32_t go, int go_at) {
  int prev = 0;
#pragma unroll 1
  for (int kb = 0; kb < nst; kb++) {
    const uint32_t base = r.wait();
    const uint64_t da = mkdesc(base + (threadIdx.x >> 7) * 4096, 128, 512, 0), db = mkdesc(base + 8192, 4096, 1024, 1);
    wg_fence();
#pragma unroll
    for (int kk = 0; kk < 2; kk++) {
      if (N == 80) wg_ss80_01(d, da + kk * 16, db + kk * 128, (kb | kk) != 0);
      if (N == 160) wg_ss160_01(d, da + kk * 16, db + kk * 128, (kb | kk) != 0);
      if (N >= 192) wg_ss192_01(d, da + kk * 16, db + kk * 128, (kb | kk) != 0);
      if (N == 320) wg_ss128_01(d + 96, da + kk * 16, db + kk * 128 + 3 * 256, (kb | kk) != 0);
    }
    wg_commit();
    if (kb == go_at && threadIdx.x == 0) mbar_arrive(go);
    if (kb > 0) { wg_wait<1>(); r.release(prev); }
    prev = r.st;
    r.next();
  }
  wg_wait<0>();
  reg_fence<N / 2>(d);
  r.release(prev);
}

template <int HALF>
__device__ __forceinline__ void attn_a_warp(Ring& r, const uint32_t (&q)[48], int b, int h) {
  constexpr int NT = HALF ? 5 : 3, NF = 8 * NT;
  const int lane = threadIdx.x & 31, g = lane >> 2, c = lane & 3, seg = (threadIdx.x >> 5) & 3;
  uint32_t f[6][NF];
  int slot[6];
  auto fetch = [&](int u) {
    const uint32_t kv = r.wait() + seg * KV_BYTES;
    slot[u] = r.st;
    r.next();
#pragma unroll
    for (int w = 0; w < 4; w++) {
      uint32_t* d = &f[u][2 * NT * w];
#pragma unroll
      for (int t = 0; t <= HALF; t++) {
        if (u < 3) {
          ldsm4(d + 4 * t, kv + w * 1024 + t * 512 + (lane & 8) * 32 + (lane & 16) * 8 + (lane & 7) * 16);
        } else {
          const uint4 v = lds128(kv + w * 1024 + t * 512 + lane * 16);
          d[4 * t] = v.x; d[4 * t + 1] = v.y; d[4 * t + 2] = v.z; d[4 * t + 3] = v.w;
        }
      }
      const uint2 m = lds64(kv + KV_M + w * 256 + lane * 8);
      d[2 * NT - 2] = m.x; d[2 * NT - 1] = m.y;
    }
    pdl_launch();
  };
  float s[NT][4] = {};
  fetch(0);
#pragma unroll
  for (int u = 0; u < 3; u++) {
    fetch(u + 1);
#pragma unroll
    for (int kk = 0; kk < 4; kk++) {
      const uint32_t* a = &q[16 * u + 4 * kk];
#pragma unroll
      for (int n = 0; n < NT; n++) mma16(s[(n + 1) % NT], a[0], a[1], a[2], a[3], f[u][2 * NT * kk + 2 * n], f[u][2 * NT * kk + 2 * n + 1]);
    }
    r.release(slot[u]);
    pdl_launch();
  }
  fetch(4);
  const float k2 = 0.07216878364870322f * 1.44269504089f, NEG = -INFINITY;
  if (2 * c > g) { s[NT - 2][0] = NEG; s[NT - 1][2] = NEG; }
  if (2 * c + 1 > g) { s[NT - 2][1] = NEG; s[NT - 1][3] = NEG; }
  s[NT - 1][0] = s[NT - 1][1] = NEG;
  uint32_t pp[NT][2]; float inv[2];
#pragma unroll
  for (int hh = 0; hh < 2; hh++) {
    float m = NEG, l = 0.f;
#pragma unroll
    for (int n = 0; n < NT; n++) m = fmaxf(m, fmaxf(s[n][2 * hh], s[n][2 * hh + 1]));
    m = fmaxf(m, __shfl_xor_sync(~0u, m, 1)); m = fmaxf(m, __shfl_xor_sync(~0u, m, 2));
#pragma unroll
    for (int n = 0; n < NT; n++) { const float x = ex2((s[n][2 * hh] - m) * k2), y = ex2((s[n][2 * hh + 1] - m) * k2); l += x + y; pp[n][hh] = pack2(x, y); }
    l += __shfl_xor_sync(~0u, l, 1); l += __shfl_xor_sync(~0u, l, 2);
    asm("rcp.approx.ftz.f32 %0, %1;" : "=f"(inv[hh]) : "f"(l));
  }
  uint32_t* dst = g_o + ((b * 192 + h * 6) * 16 + seg * 4 + HALF * 2) * 128 + lane;
#pragma unroll
  for (int u = 3; u < 6; u++) {
    float o[8][4] = {};
#pragma unroll
    for (int n = 0; n < 8; n++) mma8(o[n], pp[0][0], pp[0][1], f[u][2 * NT * (n >> 1) + 2 * NT - 2 + (n & 1)]);
#pragma unroll
    for (int t = 0; t <= HALF; t++)
#pragma unroll
      for (int n = 0; n < 8; n++) {
        const uint32_t* v = &f[u][2 * NT * (n >> 1) + 4 * t + 2 * (n & 1)];
        mma16(o[n], pp[1 + 2 * t][0], pp[1 + 2 * t][1], pp[2 + 2 * t][0], pp[2 + 2 * t][1], v[0], v[1]);
      }
    r.release(slot[u]);
    if (u == 3) fetch(5);
#pragma unroll
    for (int n = 0; n < 8; n++) {
      dst[(u - 3) * 4096 + (n >> 2) * 2048 + (n & 3) * 32] = pack2(o[n][0] * inv[0], o[n][1] * inv[0]);
      dst[(u - 3) * 4096 + (n >> 2) * 2048 + (n & 3) * 32 + 128] = pack2(o[n][2] * inv[1], o[n][3] * inv[1]);
    }
  }
}

template <int NG>
__device__ __forceinline__ void fin_item(Ring& r, uint32_t scratch, int b, int idx) {
  const int warp = threadIdx.x >> 5, lane = threadIdx.x & 31;
  float4* x = g_x + ((b * 16 + idx * NG) * 40 + warp * 5) * 32 + lane;
  float4 v[NG][5];
#pragma unroll
  for (int g = 0; g < NG; g++) {
    const uint32_t base = r.wait();
#pragma unroll
    for (int i = 0; i < 5; i++) v[g][i] = lds128f(base + ((warp * 5 + i) * 32 + lane) * 16);
    r.pop();
  }
#pragma unroll 1
  for (int k = 0; k < op_split(b); k += NG == 1 ? 2 : 1) {
#pragma unroll
    for (int g = 0; g < NG; g += 2) {
      const uint32_t base = r.wait();
#pragma unroll
      for (int i = 0; i < 10; i++) {
        const uint2 q = lds64(base + ((i / 5 * 40 + warp * 5 + i % 5) * 32 + lane) * 8);
        float4& t = v[(g + i / 5) % NG][i % 5];
        t.x += bf_lo(q.x); t.y += bf_hi(q.x); t.z += bf_lo(q.y); t.w += bf_hi(q.y);
      }
      r.pop();
    }
  }
  float mean[NG], rs[NG];
  ln_stats<NG>(v, scratch, mean, rs);
#pragma unroll
  for (int i = 0; i < 5; i++) {
    const int u = warp * 5 + i;
    uint32_t* xn = g_xn + ((b * 20 + (u >> 1)) * 16 + idx * NG) * 128 + (u & 1) * 64 + lane;
#pragma unroll
    for (int g = 0; g < NG; g++) {
      xn[g * 128] = pack2((v[g][i].x - mean[g]) * rs[g], (v[g][i].y - mean[g]) * rs[g]);
      xn[g * 128 + 32] = pack2((v[g][i].z - mean[g]) * rs[g], (v[g][i].w - mean[g]) * rs[g]);
    }
  }
#pragma unroll
  for (int g = 0; g < NG; g++)
#pragma unroll
    for (int i = 0; i < 5; i++) x[(g * 40 + i) * 32] = v[g][i];
}

__global__ void __launch_bounds__(384, 1) post_kernel(const __grid_constant__ PostParams p) {
  extern __shared__ __align__(1024) uint8_t smem_raw[];
  const uint32_t sb = s2u(smem_raw), bars = sb + PS * PB;
  const uint32_t bIF = bars + 128, bIE = bars + 160, done = bars + 192, bGo = bars + 224, slots = bars + 240, scratch = bars + 512;
  const int warp = __shfl_sync(~0u, threadIdx.x >> 5, 0), lane = threadIdx.x & 31;
  TRACE(0);
  pdl_launch();
  if (sb & 1023) __trap();
  if (threadIdx.x < 29) mbar_init(bars + 8 * threadIdx.x, threadIdx.x < 8 ? 1 : threadIdx.x < 16 ? 8 : threadIdx.x < 20 ? 1 : threadIdx.x < 24 ? 2 : threadIdx.x < 28 ? 8 : 1);
  fence_async();
  __syncthreads();
  if (warp >= 8) {
    asm volatile("setmaxnreg.dec.sync.aligned.u32 56;");
    if (warp == 9) {
      const int b = lane & 15;
      bool queries = QA_END < 16 && blockIdx.x < 36;
      for (int n = 0;; n++) {
        if (n > 0) mbar_wait(bGo, (n - 1) & 1);
        mbar_wait(bIE + 8 * (n & 3), ((n >> 2) & 1) ^ 1);
        int code = -1, spin = 0, ticket = 0;
        if (queries) {
          if (lane == 0) ticket = atomicAdd(g_sync + SY_QC, 1);
          ticket = __shfl_sync(~0u, ticket, 0);
          queries = ticket < (16 - QA_END) * 32;
          if (queries) code = IT_Q << 16 | (QA_END + ticket % (16 - QA_END)) << 8 | ticket / (16 - QA_END);
        }
        if (!queries && lane == 0) ticket = atomicAdd(g_sync + SY_T, 1);
        while (!queries) {
          const uint4 hd = ldg_strong128(g_sync + b * 8), pr = ldg_strong128(g_sync + b * 8 + 4);
          const uint32_t hv[4] = {hd.x, hd.y, hd.z, hd.w}, pv[4] = {pr.x, pr.y, pr.z, pr.w};
          const uint32_t chain_done = __ballot_sync(~0u, (pr.x & 0xffff) >= 96) & 0xffff;
          int left[4], avail[4], rdy = 0, claimed = 0, upstream = 0;
#pragma unroll
          for (int t = 0; t < 4; t++) {
            const int cnt = lane < 16 ? item_count(t, b) : 0;
            left[t] = max(cnt - (int)hv[t], 0);
            claimed += cnt - left[t];
            const bool ready = (pv[t] & 0xffff) >= item_need(t, b);
            rdy |= ready << t;
            bool ok = ready || (t == IT_ATT ? pr.x >= 0x10000 : !upstream || (t == IT_OP && (chain_done >> 15 & 1)));
            if (t == IT_BQ && (chain_done >> BQ_HOLD & 1) && !(chain_done >> 15)) ok = false;
            avail[t] = ok ? left[t] : 0;
            upstream |= __any_sync(~0u, left[t] > 0);
          }
          if (!upstream) break;
          int rank = max(__shfl_sync(~0u, ticket, 0) - __reduce_add_sync(~0u, claimed), 0), type = -1, mine = 0;
#pragma unroll
          for (int c = 0; c < 8; c++) {
            const int t = c == 0 || c == 5 ? IT_FIN : c == 1 || c == 7 ? IT_ATT : c == 2 || c == 4 ? IT_OP : IT_BQ;
            int a = c == 1 || ((rdy >> t & 1) == (c < 4)) ? avail[t] : 0;
            if (t == IT_OP && !(p.pol & 1)) a = c == 2 ? avail[t] : 0;
            if (c == 7) a = b < QA_END && !(rdy & 1) && ((chain_done << 1 | 1) >> b & 1) ? left[t] : 0;
            const int tot = __reduce_add_sync(~0u, a);
            if (type < 0) { if (rank < tot) { type = t; mine = a; } else rank -= tot; }
          }
          if (type >= 0) {
#pragma unroll
            for (int o = 1; o < 16; o <<= 1) { const int y = __shfl_up_sync(~0u, mine, o); if (lane >= o) mine += y; }
            const int blk = __ffs(__ballot_sync(~0u, mine > rank)) - 1;
            const int early = !(__shfl_sync(~0u, rdy, blk) >> type & 1);
            uint32_t idx = 0;
            if (lane == 0) { idx = atomicAdd(g_sync + blk * 8 + type, 1); ld_acquire(g_sync + blk * 8 + 4 + type); }
            idx = __shfl_sync(~0u, idx, 0);
            if (idx < item_count(type, blk)) { code = (chain_done >> 15 & 1) << 22 | (chain_done >> p.look & 1) << 21 | early << 20 | type << 16 | blk << 8 | idx; break; }
          } else {
            __nanosleep(50);
          }
          spin_guard(spin);
        }
        if (lane == 0) {
          fence_async_global();
          sts32(slots + 4 * (n & 3), code);
          mbar_arrive(bIF + 8 * (n & 3));
        }
        __syncwarp();
        if (code < 0) break;
      }
    } else if (warp == 8) {
      uint32_t smid, nsm, peers = 0;
      asm("mov.u32 %0, %%smid;" : "=r"(smid)); asm("mov.u32 %0, %%nsmid;" : "=r"(nsm));
      for (uint32_t i = lane; i < min(nsm, 256u); i += 32)
        peers += abs((int)(g_smclk[i] - g_smclk[smid & 255])) < 4000 && ldg_strong32(g_smuse + i) != p.layer + 1;
      const uint32_t gap0 = max(p.gap, (int)min(__reduce_add_sync(~0u, peers), 18u) * p.share >> 3);
      if (elect()) {
        uint32_t dst = sb, bar = bars, ph = 1, next = clk32(), gap = 0;
        auto acquire = [&](uint32_t kb) {
          mbar_wait(bar + 8 * PS, ph);
          mbar_expect(bar, kb * 1024);
          if (gap) {
            uint32_t now;
            do now = clk32(); while ((int)(now - next) < 0);
            next = ((int)(now - next) > 100 ? now - 100 : next) + kb * gap;
          }
        };
        auto advance = [&]() { dst += PB; bar += 8; if (dst == bars) { dst = sb; bar = bars; ph ^= 1; } };
        auto depend = [&](const uint32_t* c, uint32_t need) { wait_count(c, need); fence_async_global(); };
#pragma unroll 1
        for (int n = 0;; n++) {
          mbar_wait(bIF + 8 * (n & 3), (n >> 2) & 1);
          const int code = (int)lds32(slots + 4 * (n & 3));
          if (code < 0) break;
          const int type = (code >> 16) & 15, b = (code >> 8) & 255, idx = code & 255;
          const bool early = code >> 20 & 1, go = !(code >> 21 & 1);
          mbar_arrive(bIE + 8 * (n & 3));
          gap = !(code >> 22 & 1) ? gap0 : type == IT_ATT || type == IT_FIN ? 0 : p.gap2;
          const uint32_t* progress = g_sync + b * 8 + 4 + type;
          if (type == IT_ATT && b >= QA_END) {
            depend(g_sync + SY_Q, (16 - QA_END) * 32);
#pragma unroll 1
            for (int u = 0; u < 2; u++) { acquire(24); bulk_load_last(dst, g_q + (((b - QA_END) * 32 + idx) * 2 + u) * 1536, 24576, bar); advance(); }
          } else if (type == IT_FIN) {
            const int ng = 16 / fin_items(b), lg = ng >> 1;
#pragma unroll 1
            for (int g = 0; g < ng; g++) { acquire(20); bulk_load(dst, g_x + (b * 16 + idx * ng + g) * 1280, 20480, bar); advance(); }
            if (early) depend(progress, item_need(type, b));
            if (go) mbar_arrive(bGo);
#pragma unroll 1
            for (int i = 0; i < op_split(b) * ng; i += 2) {
              const uint2* src = g_part + ((b * 16 + (i >> lg)) * 16 + idx * ng + (i & (ng - 1))) * 1280;
              acquire(20);
              bulk_load_last(dst, src, ng > 1 ? 20480 : 10240, bar);
              if (ng == 1) bulk_load_last(dst + 10240, src + 16 * 1280, 10240, bar);
              advance();
            }
          } else {
            const bool op = type == IT_OP, bq = type == IT_BQ;
            const int width = op ? op_width(b) : bq ? bq_width(b) : 192, nb = (width + 63) >> 6, lt = width == 320 ? 1 : 2;
            const int nst = op ? 192 / op_split(b) : 20, kb0 = op ? (idx >> lt) * nst : 0;
            const int col = (op ? idx & ((1 << lt) - 1) : idx) * width;
            const bool whole = !(width & 63);
            const CUtensorMap* m = op ? (whole ? &p.wo : &p.wo2) : bq ? (whole ? &p.wb : &p.wb2) : &p.wq;
            const uint32_t* a = op ? g_o + (b * 192 + kb0) * 2048 : g_xn + b * 20 * 2048;
            int row = kb0 * 32, pre = early && (op || bq) ? min(nst, PS) : 0;
            auto weights = [&]() {
              acquire(8 + nb * 4);
              if (whole) {
                tma_load3z(dst + 8192, m, row, col >> 6, bar);
              } else {
                tma_load(dst + 8192, m, col, row, bar); tma_load(dst + 12288, m, col + 64, row, bar);
                if (nb == 3) tma_load(dst + 16384, m, col + 128, row, bar);
              }
              row += 32;
            };
            if (pre) {
              uint32_t da = dst, ba = bar;
#pragma unroll 1
              for (int kb = 0; kb < pre; kb++) { weights(); advance(); }
              depend(progress, item_need(type, b));
#pragma unroll 1
              for (int kb = 0; kb < pre; kb++) {
                bulk_load(da, a, 8192, ba);
                a += 2048; da += PB; ba += 8;
                if (da == bars) { da = sb; ba = bars; }
              }
            }
#pragma unroll 1
            for (int kb = pre; kb < nst; kb++) { weights(); if (op && OEF) bulk_load_last(dst, a, 8192, bar); else bulk_load(dst, a, 8192, bar); a += 2048; advance(); }
          }
          if (type == IT_ATT) {
            if (early) depend(progress, 96);
            if (go) mbar_arrive(bGo);
            const uint8_t* src = g_kv + (size_t)(idx * 6 * NSEG + b * 4) * KV_BYTES;
#pragma unroll 1
            for (int u = 0; u < 6; u++) {
              acquire(20);
              bulk_load_last(dst, src, 20480, bar);
              src += u == 2 ? -3 * KV_V : 2 * KV_V;
              advance();
            }
          }
        }
      }
    } else if (warp == 10 && lane == 0) {
      for (int n = 0;; n++) {
        mbar_wait(bIF + 8 * (n & 3), (n >> 2) & 1);
        const int code = (int)lds32(slots + 4 * (n & 3));
        if (code < 0) break;
        const int type = (code >> 16) & 15, b = (code >> 8) & 255;
        mbar_wait(done + 8 * (n & 3), (n >> 2) & 1);
        if (type != IT_BQ) red_release(type == IT_Q ? g_sync + SY_Q : g_sync + b * 8 + 5 + type, 1);
        mbar_arrive(bIE + 8 * (n & 3));
      }
    }
  } else {
    asm volatile("setmaxnreg.inc.sync.aligned.u32 224;");
    const int g = lane >> 2, c = lane & 3;
    Ring r = {sb, bars, 0, 0};
#pragma unroll 1
    for (int n = 0;; n++) {
      mbar_wait(bIF + 8 * (n & 3), (n >> 2) & 1);
      const int code = __shfl_sync(~0u, (int)lds32(slots + 4 * (n & 3)), 0);
      if (code < 0) { TRACE(2); break; }
      const int type = (code >> 16) & 15, b = (code >> 8) & 255, idx = code & 255;
      ITEM(code & 0xfffff, 0);
      if (type == IT_ATT || type == IT_Q) {
        uint32_t q[48];
        if (type == IT_Q || b < QA_END) {
          float d[96] = {};
          reg_fence<96>(d);
          gemm_item<192>(r, d, 20, bGo, type == IT_Q ? 12 : -1);
#pragma unroll
          for (int i = 0; i < 48; i++) q[i] = pack2(d[2 * i], d[2 * i + 1]);
        } else {
#pragma unroll
          for (int u = 0; u < 2; u++) {
            const uint32_t base = r.wait() + threadIdx.x * 16;
#pragma unroll
            for (int i = 0; i < 6; i++) {
              const uint4 v = lds128(base + i * 4096);
              q[24 * u + 4 * i] = v.x; q[24 * u + 4 * i + 1] = v.y; q[24 * u + 4 * i + 2] = v.z; q[24 * u + 4 * i + 3] = v.w;
            }
            r.pop();
          }
        }
        if (type == IT_Q) {
          uint4* dst = g_q + ((b - QA_END) * 32 + idx) * 3072 + threadIdx.x;
#pragma unroll
          for (int i = 0; i < 12; i++) dst[i * 256] = make_uint4(q[4 * i], q[4 * i + 1], q[4 * i + 2], q[4 * i + 3]);
        } else if (warp < 4) {
          attn_a_warp<0>(r, q, b, idx);
        } else {
          attn_a_warp<1>(r, q, b, idx);
        }
      } else if (type == IT_FIN) {
        if (fin_items(b) == 4) fin_item<4>(r, scratch, b, idx);
        else if (fin_items(b) == 8) fin_item<2>(r, scratch, b, idx);
        else fin_item<1>(r, scratch, b, idx);
      } else {
        float d[160] = {};
        reg_fence<160>(d);
        const int width = type == IT_OP ? op_width(b) : bq_width(b), nst = type == IT_OP ? 192 / op_split(b) : 20;
        const int go_at = code >> 21 & 1 ? -1 : max(nst - 6, 0);
        if (width == 320) gemm_item<320>(r, d, nst, bGo, go_at);
        else if (width == 160 || BQ_80 == 16) gemm_item<160>(r, d, nst, bGo, go_at);
        else gemm_item<80>(r, d, nst, bGo, go_at);
        reg_fence<160>(d);
        if (type == IT_OP) {
          const int tiles = DM / width;
          uint2* dst = g_part + (((b * 16 + idx / tiles) * 16 + warp * 2) * 40 + idx % tiles * (width / 16)) * 32 + lane;
#pragma unroll
          for (int u = 0; u < 20; u++) {
            if (u % 5 == 0 && u * 16 >= width) break;
            dst[u * 32] = make_uint2(pack2(d[8 * u], d[8 * u + 1]), pack2(d[8 * u + 4], d[8 * u + 5]));
            dst[(40 + u) * 32] = make_uint2(pack2(d[8 * u + 2], d[8 * u + 3]), pack2(d[8 * u + 6], d[8 * u + 7]));
          }
        } else {
          const int row = b * 128 + warp * 16 + g;
          const int h0 = idx * (width / 20);
          const float sc = h0 < 32 ? 0.22360679775f * 1.44269504089f : 1.f;
          const bool lo = c < 2;
          uint32_t* da = g_bqkv + (h0 * 256 + (row >> 3)) * 96 + lane;
          uint32_t* db = da + 256 * 96 + (lo ? 2 : -2);
          uint32_t pad[2];
#pragma unroll
          for (int rr = 0; rr < 2; rr++) pad[rr] = !(c & 1) && (h0 >= 64 || (h0 >= 32 && (row & 1) && poly_group((row >> 3) + rr))) ? 0x00003f80u : 0u;
#pragma unroll
          for (int q = 0; q < 8; q++) {
            if (!(q & 1) && q * 40 >= width) break;
#pragma unroll
            for (int rr = 0; rr < 2; rr++) {
              uint32_t w[5];
#pragma unroll
              for (int i = 0; i < 5; i++) w[i] = pack2(d[20 * q + 4 * i + 2 * rr] * sc, d[20 * q + 4 * i + 2 * rr + 1] * sc);
              const int o = q * 2 * 256 * 96 + rr * 96;
              da[o] = w[0]; da[o + 32] = w[1]; da[o + 64] = lo ? w[2] : pad[rr];
              db[o] = lo ? w[3] : w[2]; db[o + 32] = lo ? w[4] : w[3]; db[o + 64] = lo ? pad[rr] : w[4];
            }
          }
        }
      }
      __syncwarp();
      if (lane == 0) mbar_arrive(done + 8 * (n & 3));
      if ((code >> 21 & 1) && threadIdx.x == 128) mbar_arrive(bGo);
      ITEM(code & 0xfffff, 1);
    }
  }
}

constexpr int AB_SMEM = 1024 + 98304 + 51200 + 4 * 16384 + 256;
#define AB_N 32
#define AB_WG 4
constexpr int AB_T = AB_WG * 128, AB_PASS = 8 / AB_WG;
__device__ __forceinline__ float ex2_poly(float t) {
  const uint32_t r = __float_as_uint(t) & 0xffff8000u;
  const float f = t - __uint_as_float(r);
  const float p = fmaf(fmaf(fmaf(-5.869912678e-38f, f, -1.700740250e-37f), f, -5.234869734e-37f), f, -7.522601252e-37f);
  uint32_t y;
  asm("mad.lo.u32 %0, %1, 256, %2;" : "=r"(y) : "r"(r), "r"(__float_as_uint(p)));
  return __uint_as_float(y);
}
__device__ __forceinline__ float sq2(uint32_t w) { const float a = bf_lo(w), b = bf_hi(w); return fmaf(a, a, b * b); }

__device__ __forceinline__ void attn_b_store(const float* o, int h, int row0, int lane) {
  const int g = lane >> 2, c = lane & 3;
  const float i0 = 1.f / __shfl_sync(~0u, o[8], (lane & ~3) | 2), i1 = 1.f / __shfl_sync(~0u, o[10], (lane & ~3) | 2);
#pragma unroll
  for (int jj = 0; jj < 3; jj++) {
    if (jj < 2 || c < 2) {
      const int col = h * 20 + 8 * jj + 2 * c;
      uint32_t* dst = g_of + (((row0 >> 7) * 10 + (col >> 6)) * 16 + (row0 >> 3 & 15)) * 256 + (col >> 3 & 7) * 32 + g * 4 + (col >> 1 & 3);
      dst[0] = pack2(o[4 * jj] * i0, o[4 * jj + 1] * i0);
      dst[256] = pack2(o[4 * jj + 2] * i1, o[4 * jj + 3] * i1);
    }
  }
}

__device__ __forceinline__ void attn_b_qk(float* s, uint32_t q0, uint32_t q1, uint32_t q2, uint32_t q3, uint32_t q4, uint32_t q5, uint32_t z0, uint32_t z1,
                                          uint64_t dk, uint64_t dk2) {
  wg_rs32_00(s, q0, q1, q2, q3, dk, 0);
  wg_rs32_00(s, q4, q5, z0, z1, dk2, 1);
}

struct AbParams { Weights next; uint32_t* done; uint32_t* out; };
__global__ void __launch_bounds__(AB_T + 32, 1) attn_b_kernel(const __grid_constant__ AbParams p) {
  extern __shared__ uint8_t smem_raw[];
  const uint32_t sb = (s2u(smem_raw) + 1023) & ~1023u, sK = sb, sV = sb + 98304, bars = sV + 51200 + 4 * 16384;
  const uint32_t bF = bars + 64, bW = bars + 72, bA = bars + 80, bE = bars + 128, smax = bars + 176;
  auto ring = [&](int i) { return i < 2 ? sK + 51200 + i * 16384 : sV + 51200 + (i - 2) * 16384; };
  const int warp = __shfl_sync(~0u, threadIdx.x >> 5, 0), lane = threadIdx.x & 31;
  const int h = blockIdx.x >> 2, quarter = blockIdx.x & 3;
  TRACE(0);
  pdl_launch();
  pdl_wait();
  if (blockIdx.x < NSLOT) for (int i = threadIdx.x; i < 512; i += AB_T + 32) reinterpret_cast<uint4*>(pool_at(blockIdx.x * 8192))[i] = make_uint4(0, 0, 0, 0);
  if (blockIdx.x == 31) for (int i = threadIdx.x; i < SY_N; i += AB_T + 32) g_sync[i] = 0;
  if (threadIdx.x == 0) {
    for (int i = 0; i < 22; i++) mbar_init(bars + 8 * i, i == 8 ? AB_T / 32 : i >= 16 ? 8 : 1);
    sts64(smax, 0, 0);
    fence_async();
    const uint8_t* gk = reinterpret_cast<const uint8_t*>(g_bqkv + (32 + h) * 256 * 96);
    const uint8_t* gv = reinterpret_cast<const uint8_t*>(g_bqkv + (64 + h) * 256 * 96);
    for (int i = 0; i < 8; i++) {
      mbar_expect(bars + 8 * i, 24576);
      bulk_load_last(sK + i * 12288, gk + i * 12288, 12288, bars + 8 * i);
      bulk_load_last(sV + i * 12288, gv + i * 12288, 12288, bars + 8 * i);
    }
  }
  __syncthreads();
  const int blk = quarter * 4 + (h >> 3), cg = h & 7;
  auto unsafe = [&]() { const float2 m = lds64f(smax); return !(m.x * m.y <= 10000.f); };
  if (warp == AB_T / 32) {
    auto load_w = [&]() {
      mbar_expect(bW, 102400);
      for (int i = 0; i < 4; i++) bulk_load((i < 2 ? sK : sV) + (i & 1) * 25600, g_wb + cg * 6400 + i * 1600, 25600, bW);
    };
    if (p.next.w[0] && lane == 0) {
      mbar_wait(bars + 56, 0);
      for (int i = 0; i < AB_PF; i++) { const uint32_t t0 = clk32(); while (clk32() - t0 < (i ? AB_PFD : AB_PF0)) __nanosleep(200); prefetch_weights(p.next, i); }
    }
    __syncwarp();
    mbar_wait(bF, 0);
    const bool redo = unsafe();
    if (!redo && lane == 0) load_w();
    __syncwarp();
    bar_sync(1, AB_T + 32);
    if (lane == 0) {
      ABT(!!p.out, 1);
      red_release(p.done + quarter * 32, 1);
      ABT(!!p.out, 2);
      if (redo) load_w();
      wait_count(p.done + quarter * 32, 32);
      fence_async_global();
      ABT(!!p.out, 3);
      for (int kb = 0; kb < 10; kb++) {
        const int i = kb < 6 ? kb : kb - 6;
        if (kb >= 6) mbar_wait(bE + 8 * i, 0);
        mbar_expect(bA + 8 * i, 16384);
        bulk_load(ring(i), g_of + (blk * 10 + kb) * 4096, 16384, bA + 8 * i);
      }
    }
    return;
  }
  float qmax = 0.f;
  constexpr int NT = SEQ / AB_N, PER = 256 / AB_N;
#pragma unroll 1
  for (int pass = 0; pass < AB_PASS; pass++) {
    const int row0 = quarter * 512 + ((warp >> 2) * AB_PASS + pass) * 64 + (warp & 3) * 16;
    const uint32_t* gq = g_bqkv + (h * 256 + (row0 >> 3)) * 96 + lane;
    const uint32_t q0 = gq[0], q1 = gq[96], q2 = gq[32], q3 = gq[128];
    uint32_t q4 = gq[64], q5 = gq[160];
    const uint32_t z0 = gq[64 + 3 - (lane & 3)], z1 = gq[160 + 3 - (lane & 3)];
    {
      float n0 = sq2(q0) + sq2(q2) + sq2(q4), n1 = sq2(q1) + sq2(q3) + sq2(q5);
      n0 += __shfl_xor_sync(~0u, n0, 1); n1 += __shfl_xor_sync(~0u, n1, 1);
      n0 += __shfl_xor_sync(~0u, n0, 2); n1 += __shfl_xor_sync(~0u, n1, 2);
      qmax = (n0 > qmax || n0 != n0) ? n0 : qmax;
      qmax = (n1 > qmax || n1 != n1) ? n1 : qmax;
    }
    if (pass == AB_PASS - 1) {
      float kmax = 0.f;
#pragma unroll
      for (int i = 0; i < SEQ / AB_T; i++) {
        const int key = threadIdx.x + AB_T * i;
        const uint32_t a = sK + (key >> 3) * 384 + (key & 7) * 16;
        const uint4 x = lds128(a), y = lds128(a + 128);
        const uint2 z = lds64(a + 256);
        const float n = ((sq2(x.x) + sq2(x.y)) + (sq2(x.z) + sq2(x.w))) + ((sq2(y.x) + sq2(y.y)) + (sq2(y.z) + sq2(y.w))) + (sq2(z.x) + sq2(z.y));
        kmax = (n > kmax || n != n) ? n : kmax;
      }
      const uint32_t kb = __reduce_max_sync(~0u, __float_as_uint(kmax) & 0x7fffffffu), qb = __reduce_max_sync(~0u, __float_as_uint(qmax) & 0x7fffffffu);
      if (lane < 2) asm volatile("red.shared.max.u32 [%0], %1;" :: "r"(smax + 4 * lane), "r"(lane ? kb : qb) : "memory");
      __syncwarp();
    }
    if ((lane & 3) == 2) { q4 = 0x43BCu; q5 = 0x43BCu; }
    float o[12];
    uint64_t dk = mkdesc(sK, 128, 384, 0), dk2 = mkdesc(sK + 256, 0, 384, 0), dv = mkdesc(sV, 384, 128, 0);
    float sa[AB_N / 2], sb2[AB_N / 2];
    uint32_t pa[AB_N / 4], pb[AB_N / 4];
    if (pass == 0) mbar_wait(bars, 0);
    wg_fence();
    attn_b_qk(sa, q0, q1, q2, q3, q4, q5, z0, z1, dk, dk2);
    wg_commit();
    attn_b_qk(sb2, q0, q1, q2, q3, q4, q5, z0, z1, dk + AB_N * 3, dk2 + AB_N * 3);
    wg_commit();
#pragma unroll 1
    for (int kt = 0; kt < NT; kt += 2) {
      const int nx = kt + 2 < NT ? kt + 2 : 0;
      if (pass == 0 && (nx & (PER - 1)) == 0) mbar_wait(bars + 8 * (nx / PER), 0);
      const uint64_t nk = dk + nx * (AB_N * 3), nk2 = dk2 + nx * (AB_N * 3);
      wg_wait<1>();
      if (pass == AB_PASS - 1 && kt == NT * 5 / 8 + 2 && lane == 0) mbar_arrive(bF);
      reg_fence<AB_N / 2>(sa);
#pragma unroll
      for (int i = 0; i < AB_N / 4; i++) pa[i] = pack2(ex2(sa[2 * i]), poly_group(i >> 1) ? ex2_poly(sa[2 * i + 1]) : ex2(sa[2 * i + 1]));
      wg_fence();
#pragma unroll
      for (int kk = 0; kk < AB_N / 16; kk++) wg_rs24_01(o, pa[4 * kk], pa[4 * kk + 1], pa[4 * kk + 2], pa[4 * kk + 3], dv + kk * 48, kk | kt);
      attn_b_qk(sa, q0, q1, q2, q3, q4, q5, z0, z1, nk, nk2);
      wg_commit();
      wg_wait<1>();
      reg_fence<AB_N / 2>(sb2);
#pragma unroll
      for (int i = 0; i < AB_N / 4; i++) pb[i] = pack2(ex2(sb2[2 * i]), poly_group((i >> 1) + AB_N / 8) ? ex2_poly(sb2[2 * i + 1]) : ex2(sb2[2 * i + 1]));
      wg_fence();
#pragma unroll
      for (int kk = 0; kk < AB_N / 16; kk++) wg_rs24_01(o, pb[4 * kk], pb[4 * kk + 1], pb[4 * kk + 2], pb[4 * kk + 3], dv + AB_N * 3 + kk * 48, 1);
      attn_b_qk(sb2, q0, q1, q2, q3, q4, q5, z0, z1, nk + AB_N * 3, nk2 + AB_N * 3);
      wg_commit();
      dv += AB_N * 6;
    }
    wg_wait<0>();
    reg_fence<12>(o); reg_fence<AB_N / 2>(sa); reg_fence<AB_N / 2>(sb2);
    attn_b_store(o, h, row0, lane);
  }
  mbar_wait(bF, 0);
  if (unsafe())
#pragma unroll 1
  for (int pass = 0; pass < AB_PASS; pass++) {
    const int row0 = quarter * 512 + ((warp >> 2) * AB_PASS + pass) * 64 + (warp & 3) * 16;
    const uint32_t* gq = g_bqkv + (h * 256 + (row0 >> 3)) * 96 + lane;
    const uint32_t q0 = gq[0], q1 = gq[96], q2 = gq[32], q3 = gq[128], q4 = gq[64], q5 = gq[160];
    float o[12];
#pragma unroll
    for (int i = 0; i < 12; i++) o[i] = 0.f;
    float m0 = -INFINITY, m1 = -INFINITY;
#pragma unroll 1
    for (int kt = 0; kt < 32; kt++) {
      float s[32];
      const uint64_t dk = mkdesc(sK + kt * 3072, 128, 384, 0), dk2 = mkdesc(sK + kt * 3072 + 256, 0, 384, 0);
      wg_fence();
      wg_rs64_00(s, q0, q1, q2, q3, dk, 0);
      wg_rs64_00(s, q4, q5, 0, 0, dk2, 1);
      wg_commit();
      wg_wait<0>();
      reg_fence<32>(s); reg_fence<12>(o);
      float n0 = m0, n1 = m1;
#pragma unroll
      for (int jj = 0; jj < 8; jj++) { n0 = fmaxf(n0, fmaxf(s[4 * jj], s[4 * jj + 1])); n1 = fmaxf(n1, fmaxf(s[4 * jj + 2], s[4 * jj + 3])); }
      n0 = fmaxf(n0, __shfl_xor_sync(~0u, n0, 1)); n0 = fmaxf(n0, __shfl_xor_sync(~0u, n0, 2));
      n1 = fmaxf(n1, __shfl_xor_sync(~0u, n1, 1)); n1 = fmaxf(n1, __shfl_xor_sync(~0u, n1, 2));
      const float r0 = ex2(m0 - n0), r1 = ex2(m1 - n1);
      m0 = n0; m1 = n1;
#pragma unroll
      for (int jj = 0; jj < 3; jj++) { o[4 * jj] *= r0; o[4 * jj + 1] *= r0; o[4 * jj + 2] *= r1; o[4 * jj + 3] *= r1; }
      uint32_t pp[16];
#pragma unroll
      for (int jj = 0; jj < 8; jj++) {
        pp[2 * jj] = pack2(ex2(s[4 * jj] - m0), ex2(s[4 * jj + 1] - m0));
        pp[2 * jj + 1] = pack2(ex2(s[4 * jj + 2] - m1), ex2(s[4 * jj + 3] - m1));
      }
      const uint64_t dv = mkdesc(sV + kt * 3072, 384, 128, 0);
      wg_fence();
#pragma unroll
      for (int kk = 0; kk < 4; kk++) wg_rs24_01(o, pp[4 * kk], pp[4 * kk + 1], pp[4 * kk + 2], pp[4 * kk + 3], dv + kk * 48, 1);
      wg_commit();
    }
    wg_wait<0>();
    reg_fence<12>(o);
    attn_b_store(o, h, row0, lane);
  }
  ABT(!!p.out, 0);
  bar_arrive(1, AB_T + 32);
  if (warp >= 8) return;
  const int g = lane >> 2, c = lane & 3;
  float d[40];
  float4* x = g_x + ((blk * 16 + warp * 2) * 40 + cg * 5) * 32 + lane;
#pragma unroll
  for (int i = 0; i < 10; i++) {
    const int r = i / 5, u = i % 5;
    const float4 t = x[(r * 40 + u) * 32];
    d[8 * u + 2 * r] = t.x; d[8 * u + 2 * r + 1] = t.y; d[8 * u + 4 + 2 * r] = t.z; d[8 * u + 5 + 2 * r] = t.w;
  }
  mbar_wait(bW, 0);
  reg_fence<40>(d);
  ABT(!!p.out, 4);
#pragma unroll 1
  for (int kb = 0; kb < 10; kb++) {
    const int i = kb < 6 ? kb : kb - 6;
    mbar_wait(bA + 8 * i, kb >= 6);
    const uint64_t da = mkdesc(ring(i) + (warp >> 2) * 8192, 128, 1024, 0), db = mkdesc(kb < 5 ? sK + kb * 10240 : sV + (kb - 5) * 10240, 1280, 128, 0);
    wg_fence();
#pragma unroll
    for (int kk = 0; kk < 4; kk++) wg_ss80_01(d, da + kk * 16, db + kk * 160, 1);
    wg_commit();
    if (kb > 0 && kb < 5) { wg_wait<1>(); if (lane == 0) mbar_arrive(bE + 8 * (kb - 1)); }
  }
  wg_wait<0>();
  reg_fence<40>(d);
  ABT(!!p.out, 5);
  if (p.out) {
    uint32_t* out = p.out + (blk * 128 + warp * 16 + g) * (DM / 2) + cg * 40 + c;
#pragma unroll
    for (int i = 0; i < 20; i++) out[(i & 1) * 8 * (DM / 2) + (i >> 1) * 4] = pack2(d[2 * i], d[2 * i + 1]);
  } else {
    float2* stat = g_stat + blk * 1024 + warp * 16 + g;
    float mean[2], rs[2];
#pragma unroll
    for (int r = 0; r < 2; r++) {
      float t = 0.f, q = 0.f;
#pragma unroll
      for (int i = 0; i < 10; i++) t += d[4 * i + 2 * r] + d[4 * i + 2 * r + 1];
      t += __shfl_xor_sync(~0u, t, 1); t += __shfl_xor_sync(~0u, t, 2);
      t *= 1.f / 80;
#pragma unroll
      for (int i = 0; i < 10; i++) { const float a = d[4 * i + 2 * r] - t, b = d[4 * i + 2 * r + 1] - t; q += a * a + b * b; }
      q += __shfl_xor_sync(~0u, q, 1); q += __shfl_xor_sync(~0u, q, 2);
      if (c == r) asm volatile("st.relaxed.gpu.global.v2.b32 [%0], {%1, %2};" :: "l"(stat + cg * 128 + r * 8), "r"(__float_as_uint(t)), "r"(nz(__float_as_uint(q))) : "memory");
    }
#pragma unroll
    for (int i = 0; i < 10; i++) {
      const int r = i / 5, u = i % 5;
      x[(r * 40 + u) * 32] = make_float4(d[8 * u + 2 * r], d[8 * u + 2 * r + 1], d[8 * u + 4 + 2 * r], d[8 * u + 5 + 2 * r]);
    }
    ABT(0, 6);
    uint2 e[4];
    int n = 0;
    do {
#pragma unroll
      for (int i = 0; i < 4; i++)
        asm volatile("ld.relaxed.gpu.global.v2.b32 {%0, %1}, [%2];" : "=r"(e[i].x), "=r"(e[i].y) : "l"(stat + (2 * c + (i & 1)) * 128 + (i >> 1) * 8) : "memory");
      spin_guard(n);
    } while (__any_sync(~0u, min(min(e[0].y, e[1].y), min(e[2].y, e[3].y)) == 0));
#pragma unroll
    for (int r = 0; r < 2; r++) {
      const float m0 = __uint_as_float(e[2 * r].x), m1 = __uint_as_float(e[2 * r + 1].x);
      float t = m0 + m1;
      t += __shfl_xor_sync(~0u, t, 1); t += __shfl_xor_sync(~0u, t, 2);
      t *= 0.125f;
      float q = __uint_as_float(e[2 * r].y) + __uint_as_float(e[2 * r + 1].y) + 80.f * ((m0 - t) * (m0 - t) + (m1 - t) * (m1 - t));
      q += __shfl_xor_sync(~0u, q, 1); q += __shfl_xor_sync(~0u, q, 2);
      mean[r] = t; rs[r] = rsqrtf(q * (1.f / DM) + 1e-5f);
    }
    ABT(0, 7);
    uint32_t w[2][5][2];
#pragma unroll
    for (int i = 0; i < 20; i++) w[i & 1][i >> 2][i >> 1 & 1] = pack2((d[2 * i] - mean[i & 1]) * rs[i & 1], (d[2 * i + 1] - mean[i & 1]) * rs[i & 1]);
    ln_store(w, blk * 8 + warp, cg * 5);
  }
  ABT(!!p.out, 8);
  TRACE(2);
}

typedef CUresult (*EncodeFn)(CUtensorMap*, CUtensorMapDataType, cuuint32_t, void*, const cuuint64_t*, const cuuint64_t*,
                             const cuuint32_t*, const cuuint32_t*, CUtensorMapInterleave, CUtensorMapSwizzle,
                             CUtensorMapL2promotion, CUtensorMapFloatOOBfill);

void make_map(EncodeFn enc, CUtensorMap* m, const void* ptr, int cols, int rows, int nb) {
  const cuuint64_t dims[3] = {(cuuint64_t)(nb ? 64 : cols), (cuuint64_t)rows, (cuuint64_t)cols / 64};
  const cuuint64_t strides[2] = {(cuuint64_t)cols * 2, 128};
  const cuuint32_t box[3] = {64, 32, (cuuint32_t)nb}, es[3] = {1, 1, 1};
  enc(m, CU_TENSOR_MAP_DATA_TYPE_BFLOAT16, nb ? 3 : 2, const_cast<void*>(ptr), dims, strides, box, es, CU_TENSOR_MAP_INTERLEAVE_NONE,
      CU_TENSOR_MAP_SWIZZLE_128B, CU_TENSOR_MAP_L2_PROMOTION_L2_128B, CU_TENSOR_MAP_FLOAT_OOB_FILL_NONE);
}
template <class... KA, class... A>
void launch(void (*kern)(KA...), int grid, int block, int smem, int cluster, bool pdl, A... args) {
  cudaFuncSetAttribute(kern, cudaFuncAttributeMaxDynamicSharedMemorySize, smem);
  cudaLaunchConfig_t cfg = {};
  cfg.gridDim = dim3(grid); cfg.blockDim = dim3(block); cfg.dynamicSmemBytes = smem; cfg.stream = cudaStreamPerThread;
  cudaLaunchAttribute at[2];
  int n = 0;
  if (cluster > 1) { at[n].id = cudaLaunchAttributeClusterDimension; at[n].val.clusterDim.x = cluster; at[n].val.clusterDim.y = 1; at[n].val.clusterDim.z = 1; n++; }
  if (pdl) { at[n].id = cudaLaunchAttributeProgrammaticStreamSerialization; at[n].val.programmaticStreamSerializationAllowed = 1; n++; }
  cfg.attrs = at; cfg.numAttrs = n;
  cudaLaunchKernelEx(&cfg, kern, args...);
}
template <class T> void* sym(T& s) { void* p = nullptr; cudaGetSymbolAddress(&p, s); return p; }

}

#define MODE(b) 0
extern "C" void kernel_launch(void* const* d_in, const int* in_sizes, int n_in, void* d_out, int out_size) {
  const __nv_bfloat16* x = (const __nv_bfloat16*)d_in[0];
  void* fn = nullptr; cudaDriverEntryPointQueryResult qr;
  cudaGetDriverEntryPoint("cuTensorMapEncodeTiled", &fn, cudaEnableDefault, &qr);
  EncodeFn enc = (EncodeFn)fn;

  ChainParams ch = {};
  PostParams op = {};
  for (int i = 0; i < 3; i++) {
    const cuuint64_t dims[3] = {HD, 128, 5}, strides[2] = {HD * 2, HD * 256};
    const cuuint32_t box[3] = {64, 128, 5}, es[3] = {1, 1, 1};
    enc(i == 0 ? &ch.wq : i == 1 ? &ch.wk : &ch.wv, CU_TENSOR_MAP_DATA_TYPE_BFLOAT16, 3, d_in[2 + i], dims, strides, box, es, CU_TENSOR_MAP_INTERLEAVE_NONE,
        CU_TENSOR_MAP_SWIZZLE_128B, W_PROMO, CU_TENSOR_MAP_FLOAT_OOB_FILL_NONE);
  }
  {
    const cuuint64_t dims[3] = {DM, HD, 7}, strides[2] = {DM * 2, 64};
    const cuuint32_t box[3] = {32, 64, 7}, es[3] = {1, 1, 1};
    enc(&ch.wo, CU_TENSOR_MAP_DATA_TYPE_BFLOAT16, 3, d_in[5], dims, strides, box, es, CU_TENSOR_MAP_INTERLEAVE_NONE,
        CU_TENSOR_MAP_SWIZZLE_64B, CU_TENSOR_MAP_L2_PROMOTION_L2_128B, CU_TENSOR_MAP_FLOAT_OOB_FILL_NONE);
  }
  ch.mem0 = (const __nv_bfloat16*)d_in[1];
  ch.pool = (uint8_t*)(((uintptr_t)sym(g_pool) + 8191) & ~(uintptr_t)8191); ch.kv = (uint8_t*)sym(g_kv); ch.xc = (const uint32_t*)sym(g_xc); ch.sync = (uint32_t*)sym(g_sync);
  ch.d1 = 0; ch.d1b = 0; ch.d2 = 0; ch.d2b = 0;
  make_map(enc, &op.wq, d_in[2], HD, DM, 3);
  make_map(enc, &op.wo, d_in[5], DM, HD, 5); make_map(enc, &op.wo2, d_in[5], DM, HD, 0);
  make_map(enc, &op.wb, d_in[8], 1920, DM, 5); make_map(enc, &op.wb2, d_in[8], 1920, DM, 0);
  op.gap = 17; op.share = 20; op.look = 14; op.gap2 = 0; op.pol = 0;

  const Weights wa = {{(const uint8_t*)d_in[3], (const uint8_t*)d_in[4], (const uint8_t*)d_in[2], (const uint8_t*)d_in[5]}}, none = {};
  launch(first_kernel, 132, 256, 128 * 1024, 1, false, x, (const uint4*)d_in[9], wa);
  for (int layer = 0; layer < 2; layer++) {
    ch.layer = ch.d2b = op.layer = layer;
    launch(chain_kernel, 96, 256, CH_SMEM, 3, true, ch);
    launch(post_kernel, MODE(3) ? 36 : 132, 384, OP_SMEM, 1, !MODE(1), op);
    const AbParams ab = {layer == 0 ? wa : none, (uint32_t*)sym(g_bo) + layer * 128, layer == 0 ? nullptr : (uint32_t*)d_out};
    launch(attn_b_kernel, 128, AB_T + 32, AB_SMEM, 1, true, ab);
  }
}
```

```cpp
#include <cuda_runtime.h>
#include <cuda_bf16.h>
#include <cuda.h>
#include <stdint.h>

namespace {

constexpr int SEQ = 2048, DM = 640, HD = 6144, NSEG = 64;
constexpr int SPIN_LIMIT = 1 << 20;

__device__ __align__(128) float4 g_x[SEQ * DM / 4];
__device__ __align__(128) uint32_t g_of[SEQ * DM / 2];
__device__ __align__(128) uint4 g_wb[DM * DM / 8];
__device__ __align__(16) float2 g_stat[16 * 8 * 128];
__device__ uint32_t g_bo[8 * 32];
__device__ __align__(128) uint4 g_q[SEQ * HD / 8];
__device__ __align__(128) uint32_t g_o[SEQ * HD / 2];
constexpr int KV_BYTES = 5120, KV_M = 4096, KV_V = NSEG * KV_BYTES;
__device__ __align__(128) uint8_t g_kv[96 * 2 * NSEG * KV_BYTES];
__device__ __align__(128) uint32_t g_xc[SEQ * DM / 2];
#define OP_B4 0
#define OP_B8 10
#define OP_B16 15
#define QA_END 12
__host__ __device__ constexpr int op_split(int b) { return b < OP_B4 ? 2 : b < OP_B8 ? 4 : b < OP_B16 ? 8 : 16; }
__host__ __device__ constexpr int fin_items(int b) { return b < OP_B8 ? 4 : op_split(b); }
#define AB_PF 2
#define AB_PF0 30000
#define AB_PFD 7000
#define W_PROMO CU_TENSOR_MAP_L2_PROMOTION_L2_128B
#define OEF 0
#define BQ_HOLD 12
#define WEF 1
#define FK_PF 1
#define BQ_160 10
#define BQ_80 16
#define OP_160 16
__host__ __device__ constexpr int op_width(int b) { return b < OP_160 ? 320 : 160; }
__host__ __device__ constexpr int bq_width(int b) { return b < BQ_160 ? 320 : b < BQ_80 ? 160 : 80; }
__device__ __align__(128) uint2 g_part[16 * 16 * 16 * 40 * 32];
__device__ __align__(128) uint32_t g_xn[SEQ * DM / 2];
constexpr int SY_Q = 128, SY_T = 160, SY_QC = 192, SY_N = 193;
__device__ __align__(16) uint32_t g_sync[SY_N];
constexpr int NSLOT = 92;
__device__ uint32_t g_pool[(NSLOT + 2) * 2048];
__device__ int g_smpart[256], g_orient[NSLOT];
__device__ uint32_t g_smclk[256], g_smuse[256];
__device__ uint32_t g_bqkv[3 * 32 * 256 * 96];

#define ABT(L, i)
#define MODE_D(b) 0
#define DELAY(d)
#define XT(i)
#define MISS(k, n)
#define PRO(i)
#define TRACE(w)
#define ITEM(code, w)
#define TR(i, v)
#define TM(i)
#define TM1(i)
#define TMD(i, dep)
#define TMV(i, at, v)

__device__ __forceinline__ uint32_t gtime() { uint32_t c; asm volatile("mov.u32 %0, %%globaltimer_lo;" : "=r"(c) :: "memory"); return c; }
__device__ __forceinline__ uint32_t clk32() { uint32_t c; asm volatile("mov.u32 %0, %%clock;" : "=r"(c) :: "memory"); return c; }
__device__ __forceinline__ uint32_t s2u(const void* p) { return (uint32_t)__cvta_generic_to_shared(p); }
__device__ __forceinline__ uint32_t pack2(float a, float b) {
  uint32_t r; asm("cvt.rn.bf16x2.f32 %0, %1, %2;" : "=r"(r) : "f"(b), "f"(a)); return r; }
__device__ __forceinline__ float bf_lo(uint32_t w) { return __uint_as_float(w << 16); }
__device__ __forceinline__ float bf_hi(uint32_t w) { return __uint_as_float(w & 0xffff0000u); }
__device__ __forceinline__ float ex2(float x) { float y; asm("ex2.approx.ftz.f32 %0, %1;" : "=f"(y) : "f"(x)); return y; }

__device__ __forceinline__ void mbar_init(uint32_t bar, uint32_t n) {
  asm volatile("mbarrier.init.shared::cta.b64 [%0], %1;" :: "r"(bar), "r"(n) : "memory"); }
__device__ __forceinline__ void mbar_expect(uint32_t bar, uint32_t bytes) {
  asm volatile("mbarrier.arrive.expect_tx.shared::cta.b64 _, [%0], %1;" :: "r"(bar), "r"(bytes) : "memory"); }
__device__ __forceinline__ void mbar_arrive(uint32_t bar) {
  asm volatile("mbarrier.arrive.shared::cta.b64 _, [%0];" :: "r"(bar) : "memory"); }
__device__ __forceinline__ void mbar_wait(uint32_t bar, uint32_t ph) {
  asm volatile("{.reg .pred p; .reg .u32 n; mov.u32 n, 0;\n"
               "W: mbarrier.try_wait.parity.shared::cta.b64 p, [%0], %1; @p bra D;\n"
               "add.u32 n, n, 1; setp.gt.u32 p, n, %2; @p trap; bra W;\n"
               "D: }" :: "r"(bar), "r"(ph), "n"(SPIN_LIMIT) : "memory");
}
__device__ __forceinline__ void mbar_wait_cluster(uint32_t bar, uint32_t ph) {
  asm volatile("{.reg .pred p; .reg .u32 n; mov.u32 n, 0;\n"
               "W: mbarrier.try_wait.parity.acquire.cluster.shared::cta.b64 p, [%0], %1; @p bra D;\n"
               "add.u32 n, n, 1; setp.gt.u32 p, n, %2; @p trap; bra W;\n"
               "D: }" :: "r"(bar), "r"(ph), "n"(SPIN_LIMIT) : "memory");
}
__device__ __forceinline__ void spin_guard(int& n) {
  asm volatile("{.reg .pred p; add.s32 %0, %0, 1; setp.gt.s32 p, %0, %1; @p trap;}" : "+r"(n) : "n"(SPIN_LIMIT));
}
__device__ __forceinline__ void pdl_wait() { asm volatile("griddepcontrol.wait;" ::: "memory"); TRACE(1); }
__device__ __forceinline__ void pdl_launch() { asm volatile("griddepcontrol.launch_dependents;" ::: "memory"); }
__device__ __forceinline__ uint32_t ld_acquire(const uint32_t* p) { uint32_t v; asm volatile("ld.acquire.gpu.global.u32 %0, [%1];" : "=r"(v) : "l"(p) : "memory"); return v; }
__device__ __forceinline__ void red_release(uint32_t* p, uint32_t v) { asm volatile("red.release.gpu.global.add.u32 [%0], %1;" :: "l"(p), "r"(v) : "memory"); }
__device__ __forceinline__ void red_relaxed(uint32_t* p, uint32_t v) { asm volatile("red.relaxed.gpu.global.add.u32 [%0], %1;" :: "l"(p), "r"(v) : "memory"); }
__device__ __forceinline__ void fence_async_global() { asm volatile("fence.proxy.async.global;" ::: "memory"); }
__device__ __forceinline__ void fence_async() { asm volatile("fence.proxy.async.shared::cta;" ::: "memory"); }
__device__ __forceinline__ void bar_sync(int id, int n) { asm volatile("bar.sync %0, %1;" :: "r"(id), "r"(n) : "memory"); }
__device__ __forceinline__ void bar_arrive(int id, int n) { asm volatile("bar.arrive %0, %1;" :: "r"(id), "r"(n) : "memory"); }
__device__ __forceinline__ void tma_load(uint32_t dst, const CUtensorMap* m, int c0, int c1, uint32_t bar) {
  asm volatile("cp.async.bulk.tensor.2d.shared::cluster.global.mbarrier::complete_tx::bytes [%0], [%1, {%3, %4}], [%2];"
               :: "r"(dst), "l"(m), "r"(bar), "r"(c0), "r"(c1) : "memory"); }
template <bool STREAM = false>
__device__ __forceinline__ void tma_load3(uint32_t dst, const CUtensorMap* m, int c0, int c1, uint32_t bar) {
  if (STREAM)
    asm volatile("{.reg .b64 pol; createpolicy.fractional.L2::evict_first.b64 pol, 1.0;\n"
                 "cp.async.bulk.tensor.3d.shared::cluster.global.mbarrier::complete_tx::bytes.L2::cache_hint [%0], [%1, {%3, %4, 0}], [%2], pol;}"
                 :: "r"(dst), "l"(m), "r"(bar), "r"(c0), "r"(c1) : "memory");
  else
  asm volatile("cp.async.bulk.tensor.3d.shared::cluster.global.mbarrier::complete_tx::bytes [%0], [%1, {%3, %4, 0}], [%2];"
               :: "r"(dst), "l"(m), "r"(bar), "r"(c0), "r"(c1) : "memory"); }
__device__ __forceinline__ void tma_load3z(uint32_t dst, const CUtensorMap* m, int c1, int c2, uint32_t bar) {
  asm volatile("cp.async.bulk.tensor.3d.shared::cluster.global.mbarrier::complete_tx::bytes [%0], [%1, {0, %3, %4}], [%2];"
               :: "r"(dst), "l"(m), "r"(bar), "r"(c1), "r"(c2) : "memory"); }
__device__ __forceinline__ void tma_store(const CUtensorMap* m, uint32_t src, int c0, int c1) {
  asm volatile("cp.async.bulk.tensor.2d.global.shared::cta.bulk_group [%0, {%2, %3}], [%1];"
               :: "l"(m), "r"(src), "r"(c0), "r"(c1) : "memory"); }
__device__ __forceinline__ void tma_store_stream(const CUtensorMap* m, uint32_t src, int c0, int c1) {
  asm volatile("{.reg .b64 pol; createpolicy.fractional.L2::evict_first.b64 pol, 1.0;\n"
               "cp.async.bulk.tensor.2d.global.shared::cta.bulk_group.L2::cache_hint [%0, {%2, %3}], [%1], pol;}"
               :: "l"(m), "r"(src), "r"(c0), "r"(c1) : "memory"); }
__device__ __forceinline__ void bulk_load(uint32_t dst, const void* src, uint32_t bytes, uint32_t bar) {
  asm volatile("cp.async.bulk.shared::cluster.global.mbarrier::complete_tx::bytes [%0], [%1], %2, [%3];"
               :: "r"(dst), "l"(src), "r"(bytes), "r"(bar) : "memory"); }
__device__ __forceinline__ void bulk_load_last(uint32_t dst, const void* src, uint32_t bytes, uint32_t bar) {
  asm volatile("{.reg .b64 pol; createpolicy.fractional.L2::evict_first.b64 pol, 1.0;\n"
               "cp.async.bulk.shared::cluster.global.mbarrier::complete_tx::bytes.L2::cache_hint [%0], [%1], %2, [%3], pol;}"
               :: "r"(dst), "l"(src), "r"(bytes), "r"(bar) : "memory"); }
__device__ __forceinline__ void tma_load_last(uint32_t dst, const CUtensorMap* m, int c0, int c1, uint32_t bar) {
  asm volatile("{.reg .b64 pol; createpolicy.fractional.L2::evict_first.b64 pol, 1.0;\n"
               "cp.async.bulk.tensor.2d.shared::cluster.global.mbarrier::complete_tx::bytes.L2::cache_hint [%0], [%1, {%3, %4}], [%2], pol;}"
               :: "r"(dst), "l"(m), "r"(bar), "r"(c0), "r"(c1) : "memory"); }
__device__ __forceinline__ void bulk_send(uint32_t dst, uint32_t src, uint32_t bytes, uint32_t bar) {
  asm volatile("cp.async.bulk.shared::cluster.shared::cta.mbarrier::complete_tx::bytes [%0], [%1], %2, [%3];"
               :: "r"(dst), "r"(src), "r"(bytes), "r"(bar) : "memory"); }
__device__ __forceinline__ void bulk_store(void* dst, uint32_t src, uint32_t bytes) {
  asm volatile("cp.async.bulk.global.shared::cta.bulk_group [%0], [%1], %2;" :: "l"(dst), "r"(src), "r"(bytes) : "memory"); }
__device__ __forceinline__ void bulk_commit() { asm volatile("cp.async.bulk.commit_group;" ::: "memory"); }
template <int N> __device__ __forceinline__ void bulk_wait_read() { asm volatile("cp.async.bulk.wait_group.read %0;" :: "n"(N) : "memory"); }
template <int N> __device__ __forceinline__ void bulk_wait() { asm volatile("cp.async.bulk.wait_group %0;" :: "n"(N) : "memory"); }

__device__ __forceinline__ uint64_t mkdesc(uint32_t addr, uint32_t lbo, uint32_t sbo, uint32_t sw) {
  return (uint64_t)((addr & 0x3FFFF) >> 4) | ((uint64_t)(lbo >> 4) << 16) | ((uint64_t)(sbo >> 4) << 32) | ((uint64_t)sw << 62); }
__device__ __forceinline__ void wg_fence() { asm volatile("wgmma.fence.sync.aligned;" ::: "memory"); }
__device__ __forceinline__ void wg_commit() { asm volatile("wgmma.commit_group.sync.aligned;" ::: "memory"); }
template <int N> __device__ __forceinline__ void wg_wait() { asm volatile("wgmma.wait_group.sync.aligned %0;" :: "n"(N) : "memory"); }
template <int N> __device__ __forceinline__ void reg_fence(float* d) {
#pragma unroll
  for (int i = 0; i < N; i++) asm volatile("" : "+f"(d[i]) :: "memory");
}

__device__ __forceinline__ void mma16(float* d, uint32_t a0, uint32_t a1, uint32_t a2, uint32_t a3, uint32_t b0, uint32_t b1) {
  asm volatile("mma.sync.aligned.m16n8k16.row.col.f32.bf16.bf16.f32 {%0,%1,%2,%3},{%4,%5,%6,%7},{%8,%9},{%0,%1,%2,%3};"
               : "+f"(d[0]), "+f"(d[1]), "+f"(d[2]), "+f"(d[3]) : "r"(a0), "r"(a1), "r"(a2), "r"(a3), "r"(b0), "r"(b1)); }
__device__ __forceinline__ void mma8(float* d, uint32_t a0, uint32_t a1, uint32_t b0) {
  asm volatile("mma.sync.aligned.m16n8k8.row.col.f32.bf16.bf16.f32 {%0,%1,%2,%3},{%4,%5},{%6},{%0,%1,%2,%3};"
               : "+f"(d[0]), "+f"(d[1]), "+f"(d[2]), "+f"(d[3]) : "r"(a0), "r"(a1), "r"(b0)); }
__device__ __forceinline__ void ldsm4(uint32_t* r, uint32_t a) {
  asm volatile("ldmatrix.sync.aligned.m8n8.x4.shared.b16 {%0,%1,%2,%3},[%4];" : "=r"(r[0]), "=r"(r[1]), "=r"(r[2]), "=r"(r[3]) : "r"(a) : "memory"); }
__device__ __forceinline__ void ldsm4t(uint32_t* r, uint32_t a) {
  asm volatile("ldmatrix.sync.aligned.m8n8.x4.trans.shared.b16 {%0,%1,%2,%3},[%4];" : "=r"(r[0]), "=r"(r[1]), "=r"(r[2]), "=r"(r[3]) : "r"(a) : "memory"); }
__device__ __forceinline__ void ldsm2(uint32_t* r, uint32_t a) {
  asm volatile("ldmatrix.sync.aligned.m8n8.x2.shared.b16 {%0,%1},[%2];" : "=r"(r[0]), "=r"(r[1]) : "r"(a) : "memory"); }
__device__ __forceinline__ void stsm4(uint32_t a, uint32_t r0, uint32_t r1, uint32_t r2, uint32_t r3) {
  asm volatile("stmatrix.sync.aligned.m8n8.x4.shared.b16 [%0], {%1,%2,%3,%4};" :: "r"(a), "r"(r0), "r"(r1), "r"(r2), "r"(r3) : "memory"); }
__device__ __forceinline__ void stsm2t(uint32_t a, uint32_t r0, uint32_t r1) {
  asm volatile("stmatrix.sync.aligned.m8n8.x2.trans.shared.b16 [%0], {%1,%2};" :: "r"(a), "r"(r0), "r"(r1) : "memory"); }
__device__ __forceinline__ void stsm4t(uint32_t a, uint32_t r0, uint32_t r1, uint32_t r2, uint32_t r3) {
  asm volatile("stmatrix.sync.aligned.m8n8.x4.trans.shared.b16 [%0], {%1,%2,%3,%4};" :: "r"(a), "r"(r0), "r"(r1), "r"(r2), "r"(r3) : "memory"); }
__device__ __forceinline__ void st_async128(uint32_t a, uint4 v, uint32_t bar) {
  asm volatile("st.async.shared::cluster.mbarrier::complete_tx::bytes.v4.b32 [%0], {%1,%2,%3,%4}, [%5];" :: "r"(a), "r"(v.x), "r"(v.y), "r"(v.z), "r"(v.w), "r"(bar) : "memory"); }
__device__ __forceinline__ void sts32(uint32_t a, uint32_t v) { asm volatile("st.shared.b32 [%0], %1;" :: "r"(a), "r"(v) : "memory"); }
__device__ __forceinline__ void sts64f(uint32_t a, float x, float y) { asm volatile("st.shared.v2.f32 [%0], {%1,%2};" :: "r"(a), "f"(x), "f"(y) : "memory"); }
__device__ __forceinline__ void sts128(uint32_t a, uint4 v) {
  asm volatile("st.shared.v4.b32 [%0], {%1,%2,%3,%4};" :: "r"(a), "r"(v.x), "r"(v.y), "r"(v.z), "r"(v.w) : "memory"); }
__device__ __forceinline__ void sts128f(uint32_t a, float x, float y, float z, float w) {
  asm volatile("st.shared.v4.f32 [%0], {%1,%2,%3,%4};" :: "r"(a), "f"(x), "f"(y), "f"(z), "f"(w) : "memory"); }
__device__ __forceinline__ float lds32f(uint32_t a) { float v; asm volatile("ld.shared.f32 %0, [%1];" : "=f"(v) : "r"(a) : "memory"); return v; }
__device__ __forceinline__ float2 lds64f(uint32_t a) { float2 v; asm volatile("ld.shared.v2.f32 {%0,%1}, [%2];" : "=f"(v.x), "=f"(v.y) : "r"(a) : "memory"); return v; }
__device__ __forceinline__ float4 lds128f(uint32_t a) {
  float4 v; asm volatile("ld.shared.v4.f32 {%0,%1,%2,%3}, [%4];" : "=f"(v.x), "=f"(v.y), "=f"(v.z), "=f"(v.w) : "r"(a) : "memory"); return v; }
__device__ __forceinline__ uint4 lds128(uint32_t a) {
  uint4 v; asm volatile("ld.shared.v4.b32 {%0,%1,%2,%3}, [%4];" : "=r"(v.x), "=r"(v.y), "=r"(v.z), "=r"(v.w) : "r"(a) : "memory"); return v; }
__device__ __forceinline__ uint4 ldg_strong128(const void* p) {
  uint4 v; asm volatile("ld.relaxed.gpu.global.v4.u32 {%0,%1,%2,%3}, [%4];" : "=r"(v.x), "=r"(v.y), "=r"(v.z), "=r"(v.w) : "l"(p) : "memory"); return v; }
__device__ __forceinline__ void stg_strong32(void* p, uint32_t v) { asm volatile("st.relaxed.gpu.global.u32 [%0], %1;" :: "l"(p), "r"(v) : "memory"); }
__device__ __forceinline__ void stg_strong16(void* p, uint32_t v) { asm volatile("st.relaxed.gpu.global.u16 [%0], %1;" :: "l"(p), "h"((uint16_t)v) : "memory"); }
__device__ __forceinline__ void stg_strong128(void* p, uint4 v) {
  asm volatile("st.relaxed.gpu.global.v4.u32 [%0], {%1,%2,%3,%4};" :: "l"(p), "r"(v.x), "r"(v.y), "r"(v.z), "r"(v.w) : "memory"); }
__device__ __forceinline__ uint32_t mapa(uint32_t a, uint32_t r) {
  uint32_t o; asm("mapa.shared::cluster.u32 %0, %1, %2;" : "=r"(o) : "r"(a), "r"(r)); return o; }
__device__ __forceinline__ void st_async2f(uint32_t a, float x, float y, uint32_t bar) {
  asm volatile("st.async.shared::cluster.mbarrier::complete_tx::bytes.v2.f32 [%0], {%1,%2}, [%3];" :: "r"(a), "f"(x), "f"(y), "r"(bar) : "memory"); }
__device__ __forceinline__ void st_async32(uint32_t a, uint32_t x, uint32_t bar) {
  asm volatile("st.async.shared::cluster.mbarrier::complete_tx::bytes.b32 [%0], %1, [%2];" :: "r"(a), "r"(x), "r"(bar) : "memory"); }
__device__ __forceinline__ uint32_t lds32(uint32_t a) { uint32_t v; asm volatile("ld.shared.b32 %0, [%1];" : "=r"(v) : "r"(a) : "memory"); return v; }
__device__ __forceinline__ void st_async64(uint32_t a, uint32_t x, uint32_t y, uint32_t bar) {
  asm volatile("st.async.shared::cluster.mbarrier::complete_tx::bytes.v2.b32 [%0], {%1,%2}, [%3];" :: "r"(a), "r"(x), "r"(y), "r"(bar) : "memory"); }
__device__ __forceinline__ uint2 lds64(uint32_t a) { uint2 v; asm volatile("ld.shared.v2.b32 {%0,%1}, [%2];" : "=r"(v.x), "=r"(v.y) : "r"(a) : "memory"); return v; }
__device__ __forceinline__ void sts64(uint32_t a, uint32_t x, uint32_t y) { asm volatile("st.shared.v2.b32 [%0], {%1,%2};" :: "r"(a), "r"(x), "r"(y) : "memory"); }
__device__ __forceinline__ uint32_t ldg_strong32(const void* p) { uint32_t v; asm volatile("ld.relaxed.gpu.global.u32 %0, [%1];" : "=r"(v) : "l"(p) : "memory"); return v; }
__device__ __forceinline__ uint32_t transpose8(uint32_t x) { uint32_t r; asm volatile("movmatrix.sync.aligned.m8n8.trans.b16 %0, %1;" : "=r"(r) : "r"(x)); return r; }
__device__ __forceinline__ uint32_t hadd2(uint32_t a, uint32_t b) { uint32_t r; asm("add.rn.bf16x2 %0, %1, %2;" : "=r"(r) : "r"(a), "r"(b)); return r; }
__device__ __forceinline__ uint32_t min4(uint4 v) { return min(__vimin3_u32(v.x, v.y, v.z), v.w); }

__device__ __forceinline__ void wg_ss192_01(float* d, uint64_t da, uint64_t db, int sd) {
  asm volatile("{.reg .pred p; setp.ne.b32 p, %98, 0;\n"
    "wgmma.mma_async.sync.aligned.m64n192k16.f32.bf16.bf16 {%0,%1,%2,%3,%4,%5,%6,%7,%8,%9,%10,%11,%12,%13,%14,%15,%16,%17,%18,%19,%20,%21,%22,%23,%24,%25,%26,%27,%28,%29,%30,%31,%32,%33,%34,%35,%36,%37,%38,%39,%40,%41,%42,%43,%44,%45,%46,%47,%48,%49,%50,%51,%52,%53,%54,%55,%56,%57,%58,%59,%60,%61,%62,%63,%64,%65,%66,%67,%68,%69,%70,%71,%72,%73,%74,%75,%76,%77,%78,%79,%80,%81,%82,%83,%84,%85,%86,%87,%88,%89,%90,%91,%92,%93,%94,%95}, %96, %97, p, 1, 1, 0, 1;}"
    : "+f"(d[0]),"+f"(d[1]),"+f"(d[2]),"+f"(d[3]),"+f"(d[4]),"+f"(d[5]),"+f"(d[6]),"+f"(d[7]),"+f"(d[8]),"+f"(d[9]),"+f"(d[10]),"+f"(d[11]),"+f"(d[12]),"+f"(d[13]),"+f"(d[14]),"+f"(d[15]),"+f"(d[16]),"+f"(d[17]),"+f"(d[18]),"+f"(d[19]),"+f"(d[20]),"+f"(d[21]),"+f"(d[22]),"+f"(d[23]),"+f"(d[24]),"+f"(d[25]),"+f"(d[26]),"+f"(d[27]),"+f"(d[28]),"+f"(d[29]),"+f"(d[30]),"+f"(d[31]),"+f"(d[32]),"+f"(d[33]),"+f"(d[34]),"+f"(d[35]),"+f"(d[36]),"+f"(d[37]),"+f"(d[38]),"+f"(d[39]),"+f"(d[40]),"+f"(d[41]),"+f"(d[42]),"+f"(d[43]),"+f"(d[44]),"+f"(d[45]),"+f"(d[46]),"+f"(d[47]),"+f"(d[48]),"+f"(d[49]),"+f"(d[50]),"+f"(d[51]),"+f"(d[52]),"+f"(d[53]),"+f"(d[54]),"+f"(d[55]),"+f"(d[56]),"+f"(d[57]),"+f"(d[58]),"+f"(d[59]),"+f"(d[60]),"+f"(d[61]),"+f"(d[62]),"+f"(d[63]),"+f"(d[64]),"+f"(d[65]),"+f"(d[66]),"+f"(d[67]),"+f"(d[68]),"+f"(d[69]),"+f"(d[70]),"+f"(d[71]),"+f"(d[72]),"+f"(d[73]),"+f"(d[74]),"+f"(d[75]),"+f"(d[76]),"+f"(d[77]),"+f"(d[78]),"+f"(d[79]),"+f"(d[80]),"+f"(d[81]),"+f"(d[82]),"+f"(d[83]),"+f"(d[84]),"+f"(d[85]),"+f"(d[86]),"+f"(d[87]),"+f"(d[88]),"+f"(d[89]),"+f"(d[90]),"+f"(d[91]),"+f"(d[92]),"+f"(d[93]),"+f"(d[94]),"+f"(d[95])
    : "l"(da), "l"(db), "r"(sd));
}
__device__ __forceinline__ void wg_ss128_01(float* d, uint64_t da, uint64_t db, int sd) {
  asm volatile("{.reg .pred p; setp.ne.b32 p, %66, 0;\n"
    "wgmma.mma_async.sync.aligned.m64n128k16.f32.bf16.bf16 {%0,%1,%2,%3,%4,%5,%6,%7,%8,%9,%10,%11,%12,%13,%14,%15,%16,%17,%18,%19,%20,%21,%22,%23,%24,%25,%26,%27,%28,%29,%30,%31,%32,%33,%34,%35,%36,%37,%38,%39,%40,%41,%42,%43,%44,%45,%46,%47,%48,%49,%50,%51,%52,%53,%54,%55,%56,%57,%58,%59,%60,%61,%62,%63}, %64, %65, p, 1, 1, 0, 1;}"
    : "+f"(d[0]),"+f"(d[1]),"+f"(d[2]),"+f"(d[3]),"+f"(d[4]),"+f"(d[5]),"+f"(d[6]),"+f"(d[7]),"+f"(d[8]),"+f"(d[9]),"+f"(d[10]),"+f"(d[11]),"+f"(d[12]),"+f"(d[13]),"+f"(d[14]),"+f"(d[15]),"+f"(d[16]),"+f"(d[17]),"+f"(d[18]),"+f"(d[19]),"+f"(d[20]),"+f"(d[21]),"+f"(d[22]),"+f"(d[23]),"+f"(d[24]),"+f"(d[25]),"+f"(d[26]),"+f"(d[27]),"+f"(d[28]),"+f"(d[29]),"+f"(d[30]),"+f"(d[31]),"+f"(d[32]),"+f"(d[33]),"+f"(d[34]),"+f"(d[35]),"+f"(d[36]),"+f"(d[37]),"+f"(d[38]),"+f"(d[39]),"+f"(d[40]),"+f"(d[41]),"+f"(d[42]),"+f"(d[43]),"+f"(d[44]),"+f"(d[45]),"+f"(d[46]),"+f"(d[47]),"+f"(d[48]),"+f"(d[49]),"+f"(d[50]),"+f"(d[51]),"+f"(d[52]),"+f"(d[53]),"+f"(d[54]),"+f"(d[55]),"+f"(d[56]),"+f"(d[57]),"+f"(d[58]),"+f"(d[59]),"+f"(d[60]),"+f"(d[61]),"+f"(d[62]),"+f"(d[63])
    : "l"(da), "l"(db), "r"(sd));
}
__device__ __forceinline__ void wg_ss160_01(float* d, uint64_t da, uint64_t db, int sd) {
  asm volatile("{.reg .pred p; setp.ne.b32 p, %82, 0;\n"
    "wgmma.mma_async.sync.aligned.m64n160k16.f32.bf16.bf16 {%0,%1,%2,%3,%4,%5,%6,%7,%8,%9,%10,%11,%12,%13,%14,%15,%16,%17,%18,%19,%20,%21,%22,%23,%24,%25,%26,%27,%28,%29,%30,%31,%32,%33,%34,%35,%36,%37,%38,%39,%40,%41,%42,%43,%44,%45,%46,%47,%48,%49,%50,%51,%52,%53,%54,%55,%56,%57,%58,%59,%60,%61,%62,%63,%64,%65,%66,%67,%68,%69,%70,%71,%72,%73,%74,%75,%76,%77,%78,%79}, %80, %81, p, 1, 1, 0, 1;}"
    : "+f"(d[0]),"+f"(d[1]),"+f"(d[2]),"+f"(d[3]),"+f"(d[4]),"+f"(d[5]),"+f"(d[6]),"+f"(d[7]),"+f"(d[8]),"+f"(d[9]),"+f"(d[10]),"+f"(d[11]),"+f"(d[12]),"+f"(d[13]),"+f"(d[14]),"+f"(d[15]),"+f"(d[16]),"+f"(d[17]),"+f"(d[18]),"+f"(d[19]),"+f"(d[20]),"+f"(d[21]),"+f"(d[22]),"+f"(d[23]),"+f"(d[24]),"+f"(d[25]),"+f"(d[26]),"+f"(d[27]),"+f"(d[28]),"+f"(d[29]),"+f"(d[30]),"+f"(d[31]),"+f"(d[32]),"+f"(d[33]),"+f"(d[34]),"+f"(d[35]),"+f"(d[36]),"+f"(d[37]),"+f"(d[38]),"+f"(d[39]),"+f"(d[40]),"+f"(d[41]),"+f"(d[42]),"+f"(d[43]),"+f"(d[44]),"+f"(d[45]),"+f"(d[46]),"+f"(d[47]),"+f"(d[48]),"+f"(d[49]),"+f"(d[50]),"+f"(d[51]),"+f"(d[52]),"+f"(d[53]),"+f"(d[54]),"+f"(d[55]),"+f"(d[56]),"+f"(d[57]),"+f"(d[58]),"+f"(d[59]),"+f"(d[60]),"+f"(d[61]),"+f"(d[62]),"+f"(d[63]),"+f"(d[64]),"+f"(d[65]),"+f"(d[66]),"+f"(d[67]),"+f"(d[68]),"+f"(d[69]),"+f"(d[70]),"+f"(d[71]),"+f"(d[72]),"+f"(d[73]),"+f"(d[74]),"+f"(d[75]),"+f"(d[76]),"+f"(d[77]),"+f"(d[78]),"+f"(d[79])
    : "l"(da), "l"(db), "r"(sd));
}
__device__ __forceinline__ void wg_ss80_01(float* d, uint64_t da, uint64_t db, int sd) {
  asm volatile("{.reg .pred p; setp.ne.b32 p, %42, 0;\n"
    "wgmma.mma_async.sync.aligned.m64n80k16.f32.bf16.bf16 {%0,%1,%2,%3,%4,%5,%6,%7,%8,%9,%10,%11,%12,%13,%14,%15,%16,%17,%18,%19,%20,%21,%22,%23,%24,%25,%26,%27,%28,%29,%30,%31,%32,%33,%34,%35,%36,%37,%38,%39}, %40, %41, p, 1, 1, 0, 1;}"
    : "+f"(d[0]),"+f"(d[1]),"+f"(d[2]),"+f"(d[3]),"+f"(d[4]),"+f"(d[5]),"+f"(d[6]),"+f"(d[7]),"+f"(d[8]),"+f"(d[9]),"+f"(d[10]),"+f"(d[11]),"+f"(d[12]),"+f"(d[13]),"+f"(d[14]),"+f"(d[15]),"+f"(d[16]),"+f"(d[17]),"+f"(d[18]),"+f"(d[19]),"+f"(d[20]),"+f"(d[21]),"+f"(d[22]),"+f"(d[23]),"+f"(d[24]),"+f"(d[25]),"+f"(d[26]),"+f"(d[27]),"+f"(d[28]),"+f"(d[29]),"+f"(d[30]),"+f"(d[31]),"+f"(d[32]),"+f"(d[33]),"+f"(d[34]),"+f"(d[35]),"+f"(d[36]),"+f"(d[37]),"+f"(d[38]),"+f"(d[39])
    : "l"(da), "l"(db), "r"(sd));
}
__device__ __forceinline__ void wg_rs32_00(float* d, uint32_t a0, uint32_t a1, uint32_t a2, uint32_t a3, uint64_t db, int sd) {
  asm volatile("{.reg .pred p; setp.ne.b32 p, %21, 0;\n"
    "wgmma.mma_async.sync.aligned.m64n32k16.f32.bf16.bf16 {%0,%1,%2,%3,%4,%5,%6,%7,%8,%9,%10,%11,%12,%13,%14,%15}, {%16,%17,%18,%19}, %20, p, 1, 1, 0;}"
    : "+f"(d[0]),"+f"(d[1]),"+f"(d[2]),"+f"(d[3]),"+f"(d[4]),"+f"(d[5]),"+f"(d[6]),"+f"(d[7]),"+f"(d[8]),"+f"(d[9]),"+f"(d[10]),"+f"(d[11]),"+f"(d[12]),"+f"(d[13]),"+f"(d[14]),"+f"(d[15])
    : "r"(a0), "r"(a1), "r"(a2), "r"(a3), "l"(db), "r"(sd));
}
__device__ __forceinline__ void wg_rs64_00(float* d, uint32_t a0, uint32_t a1, uint32_t a2, uint32_t a3, uint64_t db, int sd) {
  asm volatile("{.reg .pred p; setp.ne.b32 p, %37, 0;\n"
    "wgmma.mma_async.sync.aligned.m64n64k16.f32.bf16.bf16 {%0,%1,%2,%3,%4,%5,%6,%7,%8,%9,%10,%11,%12,%13,%14,%15,%16,%17,%18,%19,%20,%21,%22,%23,%24,%25,%26,%27,%28,%29,%30,%31}, {%32,%33,%34,%35}, %36, p, 1, 1, 0;}"
    : "+f"(d[0]),"+f"(d[1]),"+f"(d[2]),"+f"(d[3]),"+f"(d[4]),"+f"(d[5]),"+f"(d[6]),"+f"(d[7]),"+f"(d[8]),"+f"(d[9]),"+f"(d[10]),"+f"(d[11]),"+f"(d[12]),"+f"(d[13]),"+f"(d[14]),"+f"(d[15]),"+f"(d[16]),"+f"(d[17]),"+f"(d[18]),"+f"(d[19]),"+f"(d[20]),"+f"(d[21]),"+f"(d[22]),"+f"(d[23]),"+f"(d[24]),"+f"(d[25]),"+f"(d[26]),"+f"(d[27]),"+f"(d[28]),"+f"(d[29]),"+f"(d[30]),"+f"(d[31])
    : "r"(a0), "r"(a1), "r"(a2), "r"(a3), "l"(db), "r"(sd));
}
__device__ __forceinline__ void wg_rs128_00(float* d, uint32_t a0, uint32_t a1, uint32_t a2, uint32_t a3, uint64_t db, int sd) {
  asm volatile("{.reg .pred p; setp.ne.b32 p, %69, 0;\n"
    "wgmma.mma_async.sync.aligned.m64n128k16.f32.bf16.bf16 {%0,%1,%2,%3,%4,%5,%6,%7,%8,%9,%10,%11,%12,%13,%14,%15,%16,%17,%18,%19,%20,%21,%22,%23,%24,%25,%26,%27,%28,%29,%30,%31,%32,%33,%34,%35,%36,%37,%38,%39,%40,%41,%42,%43,%44,%45,%46,%47,%48,%49,%50,%51,%52,%53,%54,%55,%56,%57,%58,%59,%60,%61,%62,%63}, {%64,%65,%66,%67}, %68, p, 1, 1, 0;}"
    : "+f"(d[0]),"+f"(d[1]),"+f"(d[2]),"+f"(d[3]),"+f"(d[4]),"+f"(d[5]),"+f"(d[6]),"+f"(d[7]),"+f"(d[8]),"+f"(d[9]),"+f"(d[10]),"+f"(d[11]),"+f"(d[12]),"+f"(d[13]),"+f"(d[14]),"+f"(d[15]),"+f"(d[16]),"+f"(d[17]),"+f"(d[18]),"+f"(d[19]),"+f"(d[20]),"+f"(d[21]),"+f"(d[22]),"+f"(d[23]),"+f"(d[24]),"+f"(d[25]),"+f"(d[26]),"+f"(d[27]),"+f"(d[28]),"+f"(d[29]),"+f"(d[30]),"+f"(d[31]),"+f"(d[32]),"+f"(d[33]),"+f"(d[34]),"+f"(d[35]),"+f"(d[36]),"+f"(d[37]),"+f"(d[38]),"+f"(d[39]),"+f"(d[40]),"+f"(d[41]),"+f"(d[42]),"+f"(d[43]),"+f"(d[44]),"+f"(d[45]),"+f"(d[46]),"+f"(d[47]),"+f"(d[48]),"+f"(d[49]),"+f"(d[50]),"+f"(d[51]),"+f"(d[52]),"+f"(d[53]),"+f"(d[54]),"+f"(d[55]),"+f"(d[56]),"+f"(d[57]),"+f"(d[58]),"+f"(d[59]),"+f"(d[60]),"+f"(d[61]),"+f"(d[62]),"+f"(d[63])
    : "r"(a0), "r"(a1), "r"(a2), "r"(a3), "l"(db), "r"(sd));
}
__device__ __forceinline__ void wg_rs24_01(float* d, uint32_t a0, uint32_t a1, uint32_t a2, uint32_t a3, uint64_t db, int sd) {
  asm volatile("{.reg .pred p; setp.ne.b32 p, %17, 0;\n"
    "wgmma.mma_async.sync.aligned.m64n24k16.f32.bf16.bf16 {%0,%1,%2,%3,%4,%5,%6,%7,%8,%9,%10,%11}, {%12,%13,%14,%15}, %16, p, 1, 1, 1;}"
    : "+f"(d[0]),"+f"(d[1]),"+f"(d[2]),"+f"(d[3]),"+f"(d[4]),"+f"(d[5]),"+f"(d[6]),"+f"(d[7]),"+f"(d[8]),"+f"(d[9]),"+f"(d[10]),"+f"(d[11])
    : "r"(a0), "r"(a1), "r"(a2), "r"(a3), "l"(db), "r"(sd));
}

#define AB_POLY 0x77
__device__ __forceinline__ constexpr bool poly_group(int group) { return (AB_POLY >> (group & 7)) & 1; }

template <int V> struct Int { static constexpr int value = V; };

template <int NG>
__device__ __forceinline__ void ln_stats(const float4 (&v)[NG][5], uint32_t scratch, float (&mean)[NG], float (&rs)[NG]) {
  const int warp = threadIdx.x >> 5, lane = threadIdx.x & 31;
#pragma unroll
  for (int r = 0; r < NG; r++) {
    float s = 0.f, q = 0.f;
#pragma unroll
    for (int i = 0; i < 5; i++) s += (v[r][i].x + v[r][i].y) + (v[r][i].z + v[r][i].w);
    s += __shfl_xor_sync(~0u, s, 1); s += __shfl_xor_sync(~0u, s, 2);
    s *= 1.f / 80;
#pragma unroll
    for (int i = 0; i < 5; i++) {
      const float x = v[r][i].x - s, y = v[r][i].y - s, z = v[r][i].z - s, w = v[r][i].w - s;
      q += (x * x + y * y) + (z * z + w * w);
    }
    q += __shfl_xor_sync(~0u, q, 1); q += __shfl_xor_sync(~0u, q, 2);
    mean[r] = s; rs[r] = q;
  }
  bar_sync(1, 256);
  if ((lane & 3) == 0) {
#pragma unroll
    for (int r = 0; r < NG; r++) sts64f(scratch + r * 512 + lane * 16 + warp * 8, mean[r], rs[r]);
  }
  bar_sync(1, 256);
#pragma unroll
  for (int r = 0; r < NG; r++) {
    const float4 e = lds128f(scratch + r * 512 + lane * 16);
    float t = e.x + e.z;
    t += __shfl_xor_sync(~0u, t, 1); t += __shfl_xor_sync(~0u, t, 2);
    t *= 0.125f;
    float q = e.y + e.w + 80.f * ((e.x - t) * (e.x - t) + (e.z - t) * (e.z - t));
    q += __shfl_xor_sync(~0u, q, 1); q += __shfl_xor_sync(~0u, q, 2);
    mean[r] = t; rs[r] = rsqrtf(q * (1.f / DM) + 1e-5f);
  }
}

__device__ __forceinline__ void ln_store(const uint32_t (&w)[2][5][2], int tile, int u0) {
  const int lane = threadIdx.x & 31;
  uint32_t* xc = g_xc + ((tile >> 1) * 40 + u0) * 256 + (tile & 1) * 64 + lane;
#pragma unroll
  for (int i = 0; i < 20; i++) xc[(i >> 1) * 128 + (i & 1) * 32] = w[i & 1][i >> 2][i >> 1 & 1];
#pragma unroll
  for (int i = 0; i < 5; i++) {
    const int u = u0 + i;
    uint32_t* xn = g_xn + (((tile >> 3) * 20 + (u >> 1)) * 16 + (tile & 1) * 8 + (tile & 6)) * 128 + (u & 1) * 64 + lane;
#pragma unroll
    for (int r = 0; r < 2; r++) { xn[r * 128] = w[r][i][0]; xn[r * 128 + 32] = w[r][i][1]; }
  }
}
__device__ __forceinline__ void wait_count(const uint32_t* c, uint32_t n) {
  int spin = 0;
  while ((ld_acquire(c) & 0xffff) < n) { __nanosleep(32); spin_guard(spin); }
}

__device__ __forceinline__ uint8_t* pool_at(uint32_t off) {
  return reinterpret_cast<uint8_t*>((reinterpret_cast<uintptr_t>(g_pool) + 8191) & ~(uintptr_t)8191) + off; }
struct Weights { const uint8_t* w[4]; };
__device__ __forceinline__ void prefetch_weights(const Weights& p, int i) {
  if (blockIdx.x < 128) asm volatile("cp.async.bulk.prefetch.L2.global [%0], 61440;" :: "l"(p.w[i] + (size_t)blockIdx.x * 61440) : "memory");
}
__global__ void __launch_bounds__(256) first_kernel(const __nv_bfloat16* __restrict__ xin, const uint4* __restrict__ wb, const __grid_constant__ Weights wa) {
  __shared__ __align__(16) float scratch[256];
  __shared__ uint32_t lat[4];
  const int warp = threadIdx.x >> 5, lane = threadIdx.x & 31, cta = blockIdx.x;
  TRACE(0);
  pdl_launch();
  if (warp < 4 && (warp < 2 || cta < NSLOT)) {
    uint32_t* q = reinterpret_cast<uint32_t*>(pool_at((warp < 2 ? NSLOT : cta) * 8192 + (warp & 1) * 4096)) + (warp < 2 ? (cta & 127) * 8 : 0);
    if (lane < 8) stg_strong32(q + lane, 0u);
    uint32_t best = ~0u;
    if (lane == 0)
      for (int r = 0; r < 4; r++) {
        uint32_t t0, t1, v;
        asm volatile("mov.u32 %0, %%clock;" : "=r"(t0) :: "memory");
        asm volatile("atom.relaxed.gpu.global.exch.b32 %0, [%1], 0;" : "=r"(v) : "l"(q) : "memory");
        asm volatile("{.reg .u32 t; add.u32 t, %1, 1; mov.u32 %0, %%clock; sub.u32 %0, %0, %1;}" : "=r"(t1) : "r"(__shfl_sync(1u, v, 0)) : "memory");
        best = min(best, t1 - t0);
      }
    if (lane == 0) lat[warp] = best;
  }
  __syncthreads();
  ABT(2, 0);
  if (threadIdx.x == 0) {
    const int part = lat[0] < lat[1] ? 0 : 1;
    uint32_t smid; asm("mov.u32 %0, %%smid;" : "=r"(smid));
    g_smpart[smid & 255] = part;
    g_smclk[smid & 255] = clk32() - gtime() * 2;
    g_smuse[smid & 255] = 0;
    if (cta < NSLOT) g_orient[cta] = lat[2] < lat[3] ? part : 1 - part;
  }
  if (cta < 128) {
    float4 v[2][5];
#pragma unroll
    for (int r = 0; r < 2; r++)
#pragma unroll
      for (int i = 0; i < 5; i++) {
        const uint32_t* src = reinterpret_cast<const uint32_t*>(xin) + (cta * 16 + r * 8 + (lane >> 2)) * (DM / 2) + warp * 40 + i * 8 + (lane & 3);
        const uint32_t a = src[0], b = src[4];
        v[r][i] = make_float4(bf_lo(a), bf_hi(a), bf_lo(b), bf_hi(b));
      }
    uint4 w8[2];
#pragma unroll
    for (int i = 0; i < 2; i++) w8[i] = wb[cta * 400 + min(i * 256 + threadIdx.x, 399)];
    if (threadIdx.x < 128) g_stat[cta * 128 + threadIdx.x] = make_float2(0.f, 0.f);
#pragma unroll
    for (int i = 0; i < 10; i++) g_x[((cta * 2 + i / 5) * 40 + warp * 5 + i % 5) * 32 + lane] = v[i / 5][i % 5];
    ABT(2, 1);
    if (threadIdx.x == 32) for (int i = 0; i < FK_PF; i++) prefetch_weights(wa, i);
    float mean[2], rs[2];
    ln_stats<2>(v, s2u(scratch), mean, rs);
    ABT(2, 2);
    uint32_t w[2][5][2];
#pragma unroll
    for (int i = 0; i < 10; i++) {
      const float4 t = v[i / 5][i % 5];
      const float m = mean[i / 5], q = rs[i / 5];
      w[i / 5][i % 5][0] = pack2((t.x - m) * q, (t.y - m) * q); w[i / 5][i % 5][1] = pack2((t.z - m) * q, (t.w - m) * q);
    }
    ln_store(w, cta, warp * 5);
    ABT(2, 3);
#pragma unroll
    for (int i = 0; i < 2; i++) {
      const int e = cta * 400 + min(i * 256 + threadIdx.x, 399), k = e / 80, n = e - k * 80, cg = n / 10;
      g_wb[((cg * 80 + (k >> 3)) * 10 + n - cg * 10) * 8 + (k & 7)] = w8[i];
    }
  } else if (cta == 128) {
    g_bo[threadIdx.x] = 0;
  }
  TRACE(2);
}

struct ChainParams {
  CUtensorMap wq, wk, wv, wo;
  const __nv_bfloat16* mem0;
  uint8_t *pool, *kv;
  const uint32_t* xc;
  uint32_t* sync;
  int layer;
  int d1, d1b, d2, d2b, mode;
};
constexpr int CH_WQ = 0, CH_WO = 81920, CH_X = CH_WO + 86016, CH_M = CH_X + 20480, CH_KT = CH_X + 40960, CH_VT = CH_KT + 4096,
              CH_PS = CH_VT + 4096, CH_QK = CH_PS + 4096, CH_VP = CH_QK + 4096, CH_SX = CH_VP + 1024, CH_O = CH_SX + 2304, CH_ID = CH_O + 3072,
              CH_BAR = CH_ID + 512;
constexpr int CH_SMEM = CH_BAR + 256;
constexpr int CH_BASE = 1024;
#define CH_VK0 8
#define CH_VK1 20
#define CH_L0 4
#define CH_LR 4
#define NOX 0
#define CH_XA 0
#define CH_XB 1
#define CH_W1 3
#define CH_W2 17
#define CH_W3 26
#define CH_R2 8
#define CH_VA 20
#define CH_KW 3
#define CH_KM 1
#define CH_RB 0
#define CH_RC 8
#define CH_D1 250
#define CH_D2 250
#define CH_R1 4
#define CH_TW 12
__device__ __forceinline__ uint32_t opaque(uint32_t x) { return __shfl_sync(~0u, x, threadIdx.x & 31); }
__device__ __forceinline__ uint32_t nz(uint32_t x) { uint32_t r; asm("max.u32 %0, %1, 1;" : "=r"(r) : "r"(x)); return r; }
__device__ __forceinline__ uint32_t pack_tag(float lo, float hi, uint32_t tag, uint32_t mask) {
  uint32_t r;
  asm("lop3.b32 %0, %1, %2, %3, 0xD8;" : "=r"(r) : "r"(pack2(lo, hi)), "r"(tag), "r"(mask));
  return r;
}
__device__ __forceinline__ uint32_t differ(uint32_t a, uint32_t b, uint32_t t) { uint32_t r; asm("lop3.b32 %0, %1, %2, %3, 0x7E;" : "=r"(r) : "r"(a), "r"(b), "r"(t)); return r; }
__device__ __forceinline__ void mbar_wait_hot(uint32_t bar, uint32_t ph) {
  uint32_t ok;
  asm volatile("{.reg .pred p; mbarrier.try_wait.parity.shared::cta.b64 p, [%1], %2; selp.u32 %0, 1, 0, p;}" : "=r"(ok) : "r"(bar), "r"(ph) : "memory");
  if (__builtin_expect(!ok, 0)) mbar_wait(bar, ph);
}
__device__ __forceinline__ bool elect() {
  uint32_t r; asm volatile("{.reg .pred p; elect.sync _|p, 0xffffffff; selp.u32 %0, 1, 0, p;}" : "=r"(r)); return r; }
__device__ __forceinline__ uint32_t or3(uint32_t a, uint32_t b, uint32_t c) { uint32_t r; asm("lop3.b32 %0, %1, %2, %3, 0xFE;" : "=r"(r) : "r"(a), "r"(b), "r"(c)); return r; }
__device__ __forceinline__ void pin() { pdl_launch(); }
__device__ __forceinline__ void mma16h(float* d, uint32_t a0, uint32_t a2, uint32_t b0, uint32_t b1) {
  asm volatile("{.reg .b32 u, v; mma.sync.aligned.m16n8k16.row.col.f32.bf16.bf16.f32 {%0,%1,%2,%3},{%4,u,%5,v},{%6,%7},{%0,%1,%2,%3};}"
               : "+f"(d[0]), "+f"(d[1]), "+f"(d[2]), "+f"(d[3]) : "r"(a0), "r"(a2), "r"(b0), "r"(b1)); }
__device__ __forceinline__ void mma8h(float* d, uint32_t a0, uint32_t b0) {
  asm volatile("{.reg .b32 u; mma.sync.aligned.m16n8k8.row.col.f32.bf16.bf16.f32 {%0,%1,%2,%3},{%4,u},{%5},{%0,%1,%2,%3};}"
               : "+f"(d[0]), "+f"(d[1]), "+f"(d[2]), "+f"(d[3]) : "r"(a0), "r"(b0)); }
__device__ __forceinline__ uint32_t absmax2(uint32_t a, uint32_t b) { uint32_t r; asm("max.xorsign.abs.bf16x2 %0, %1, %2;" : "=r"(r) : "r"(a), "r"(b)); return r; }
__device__ __forceinline__ void until(uint32_t t) { while ((int)(clk32() - t) < 0) {} }
__device__ __forceinline__ uint4 pack8(const float* d) { return make_uint4(pack2(d[0], d[1]), pack2(d[2], d[3]), pack2(d[4], d[5]), pack2(d[6], d[7])); }
__device__ __forceinline__ void add8(float* d, uint4 v) {
  d[0] += bf_lo(v.x); d[1] += bf_hi(v.x); d[2] += bf_lo(v.y); d[3] += bf_hi(v.y);
  d[4] += bf_lo(v.z); d[5] += bf_hi(v.z); d[6] += bf_lo(v.w); d[7] += bf_hi(v.w);
}

template <int WG>
__device__ __forceinline__ void chain_body(const ChainParams& p, const uint32_t wq, const uint32_t (&ak)[80], const uint32_t (&av)[80]) {
  const int tid = threadIdx.x & 127, t4 = __shfl_sync(~0u, tid >> 5, 0), lane = tid & 31;
  const int cta = blockIdx.x, h = cta / 3, j = cta - 3 * h;
  const uint32_t sb = mapa(CH_BASE, j);
  const uint32_t bWo = sb + CH_BAR, bWq = bWo + 8, bX = bWo + 16, bXA = bWo + 24, bXB = bWo + 32, bO = bWo + 40, bG = bWo + 48, bH = bWo + 96;
  uint32_t tw[4 * CH_TW];
  auto refill = [&]() {
#pragma unroll
    for (int k = 0; k < CH_TW; k++) ldsm4t(&tw[4 * k], wq + k * 2048);
  };
  const uint32_t wo = opaque((sb + CH_WO + (WG == 0 ? (t4 + (j == 2)) * 4096 : (j == 2 ? 0 : 24576) + t4 * 1024) + ((lane & 7) + (lane >> 4) * 8) * 64 +
                              ((((lane >> 3) & 1) ^ ((lane >> 1) & 3)) << 4)) ^ (WG == 1 && j == 2 ? 32 : 0));
  const uint32_t wo2 = opaque((wo ^ ((t4 & 1) * 32)) + (4 + (t4 >> 1) - t4) * 4096);
  const uint32_t l16 = opaque(sb + lane * 16);
  const uint32_t l8 = opaque(sb + t4 * 256 + lane * 8);
  const uint32_t lw = opaque(sb + t4 * 1024 + lane * 16);
  const uint32_t qs = opaque(sb + CH_QK + WG * 2048 + t4 * 512 + lane * 16);
  const uint32_t qa = opaque(sb + CH_QK + (lane >> 4) * 2048 + (lane & 15) * 16 + (WG == 0 ? t4 * 512 + 256 : t4 == 3 ? 1024 : 0));
  const uint32_t ka = opaque(t4 < 2 ? sb + CH_KT + t4 * 512 + lane * 16
                                    : sb + CH_QK + 256 + (t4 - 2) * 1024 + ((lane >> 3) & 1) * 2048 + (lane >> 4) * 128 + (lane & 7) * 16);
  const uint32_t l4 = opaque(sb + t4 * 256 + lane * 4);
  uint32_t pdst[1], pages = 0;
  auto line0 = [&](int i) { return 28 * j + (i < 4 ? 4 * t4 + i : 12 + 2 * t4 + i); };
  const uint32_t plane = opaque((lane >> 4) * 2048 + h * 64 + (lane & 15) * 4);
  if (WG == 0) {
    pages = __ballot_sync(~0u, lds32(sb + CH_O + line0(min(lane, 5)) * 4) & 4096);
  } else {
    pages = __ballot_sync(~0u, lds32(sb + CH_O + (80 + min(lane, 11)) * 4) & 4096);
    pdst[0] = opaque(lds32(sb + CH_O + (j == 0 ? 24 + t4 : 50 + 2 * j + (t4 & 1)) * 4) + plane);
  }
  const uint32_t role = lds32(sb + CH_O + NSLOT * 4), rsrc = lds32(sb + CH_O + role * 4), rdst = (80 + role / 20) * 8192 + role % 20 * 128;
  const uint32_t r1 = mapa(CH_BASE, j == 2 ? 0 : j + 1) - sb, r2 = mapa(CH_BASE, j == 0 ? 2 : j - 1) - sb;
  uint32_t tag = opaque(1);
  auto pool = [&](uint32_t off) { return p.pool + ((tag & 0xfffe) + off); };
  auto after = [&](uint32_t x) { return x & tag & 0xfffe; };
  auto kv = [&](int s, uint32_t a) { return p.kv + ((size_t)(cta * 2 * NSEG + s) * KV_BYTES - sb) + a; };
  auto pass = [&](float (&d)[16], const uint32_t (&a)[80], auto k0, auto k1) {
    const uint64_t db = mkdesc(CH_BASE + CH_X + WG * 20480, 512, 128, 0);
#pragma unroll
    for (int k = k0.value; k < k1.value; k++) wg_rs32_00(d, a[4 * k], a[4 * k + 1], a[4 * k + 2], a[4 * k + 3], db + k * 64, k);
    wg_commit();
  };
  auto dump = [&](float (&d)[16], uint32_t a) {
    reg_fence<16>(d);
    sts128(a, pack8(d)); sts128(a + 512, pack8(d + 8));
  };
  auto tokens0 = [&](int s, auto k0) {
    float dk[16], dv[16];
    bar_sync(9, 256);
    wg_fence();
    pass(dk, ak, Int<0>(), Int<4>());
    const uint4 a0 = lds128(lw + CH_KT), a1 = lds128(lw + CH_KT + 512);
    pin();
    pass(dk, ak, Int<4>(), Int<20>());
    pass(dv, av, Int<0>(), Int<CH_VA>());
    pin();
    wg_wait<1>();
    reg_fence<16>(dk);
    add8(dk, a0); add8(dk + 8, a1);
    const uint4 w0 = pack8(dk), w1 = pack8(dk + 8);
    const uint4 b0 = lds128(lw + CH_VT), b1 = lds128(lw + CH_VT + 512);
    stsm4t(lw + CH_KT, w0.x, w0.z, w0.y, w0.w); stsm4t(lw + CH_KT + 512, w1.x, w1.z, w1.y, w1.w);
    TM1(6);
    pin();
    if (CH_VA < 20) pass(dv, av, Int<CH_VA>(), Int<20>());
    pin();
#pragma unroll
    for (int k = k0.value; k < CH_TW; k++) ldsm4t(&tw[4 * k], wq + k * 2048);
    TM1(9);
    __syncwarp();
    wg_wait<0>();
    reg_fence<16>(dv);
    add8(dv, b0); add8(dv + 8, b1);
#pragma unroll
    for (int e = 0; e < 2; e++) { const uint4 v = pack8(dv + 8 * e); sts128(lw + CH_VT + e * 512, make_uint4(v.x, v.z, v.y, v.w)); }
  };
  auto publish_k = [&](int s) {
    if (t4 == CH_KW && elect()) { fence_async(); bulk_store(p.kv + (size_t)(cta * 2 * NSEG + s) * KV_BYTES, sb + CH_KT, 4096); bulk_commit(); }
    __syncwarp();
  };
  if (WG == 0) {
    mbar_wait(bXB, 0);
    tokens0(0, Int<CH_TW>());
  } else {
    const uint32_t* m0 = reinterpret_cast<const uint32_t*>(p.mem0) + (lane >> 2) * 320 + t4 * 80 + (lane & 3);
    uint32_t a[20];
#pragma unroll
    for (int i = 0; i < 20; i++) a[i] = m0[4 * i];
    pin();
    float dk[16], dv[16];
    mbar_wait(bXA, 0);
    wg_fence();
    pass(dk, ak, Int<0>(), Int<20>());
    pass(dv, av, Int<0>(), Int<20>());
    wg_wait<0>();
    dump(dk, lw + CH_KT);
    dump(dv, lw + CH_VT);
    bar_sync(9, 256);
#pragma unroll
    for (int i = 0; i < 20; i++) sts32(sb + CH_M + (t4 * 20 + i) * 128 + lane * 4, nz(transpose8(a[i])));
    __syncwarp();
    if (elect()) mbar_arrive(bG + t4 * 8);
  }
  PRO(8);
  mbar_wait(bWq, 0);
  refill();
  PRO(9);
  mbar_wait(bWo, 0);
  asm volatile("barrier.cluster.wait.aligned;" ::: "memory");
  PRO(10);
  constexpr int VK = WG == 0 ? CH_VK0 : CH_VK1;
  uint32_t gph = 0, pph = 0;
  int st = 0;
  const uint32_t ca = opaque(sb + CH_M + t4 * 2560 + lane * 32 + (lane >> 2) * 4);
  auto project = [&](int s, uint32_t (&b)[40], float (&dv)[16], uint32_t (&kf)[16]) {
    float dq[4] = {}, dk[4] = {};
    uint32_t w[80];
#pragma unroll
    for (int i = 0; i < 4 * CH_TW; i++) w[i] = tw[i];
    auto load = [&](int n) {
      int c = 0;
#pragma unroll
      for (int i = 0; i < 10; i++) {
        if (c++ == n) ldsm4t(&b[4 * i], l16 + CH_M + WG * 5120 + i * 512);
#pragma unroll
        for (int k = 2 * i; k < 2 * i + 2; k++)
          if (k >= CH_TW && c++ == n) ldsm4t(&w[4 * k], wq + k * 2048);
      }
#pragma unroll
      for (int i = 0; i < 4; i++)
        if (WG == 1 && c++ == n) ldsm4(&kf[4 * i], ka + i * 1024);
    };
    if (WG == 1) {
      for (int n = 0;;) {
        mbar_wait(bG + t4 * 8, gph);
        TR(5, (clk32() & ~3u) | min(n, 3));
        gph ^= 1;
        if (__builtin_expect(!__any_sync(~0u, __vimin3_u32(lds32(ca), lds32(ca + 1024), lds32(ca + 1536)) == 0), 1)) break;
        if (elect()) {
          const int q = (st == 0 ? 8 : st * 4 - 4) + t4;
          mbar_expect(bG + t4 * 8, 2560);
          bulk_load(sb + CH_M + t4 * 2560, p.pool + ((80 + q) * 8192 + (pages >> q & 1) * 4096), 2560, bG + t4 * 8);
        }
        spin_guard(n);
      }
    }
    bar_sync(6, 256);
#pragma unroll
    for (int i = 0; i < CH_L0; i++) load(i);
    TM(0);
    TM1(11);
    if (WG == 1) TR(6, clk32());
#pragma unroll
    for (int k = 0; k < 20; k += 2) {
      if (k > 0) {
#pragma unroll
        for (int n = CH_L0 + (k - 2) * CH_LR / 4; n < (k == 18 ? 40 : CH_L0 + k * CH_LR / 4); n++) load(n);
      }
      pin();
#pragma unroll
      for (int kk = k; kk < k + 2; kk++) {
        mma16(dk, ak[4 * kk], ak[4 * kk + 1], ak[4 * kk + 2], ak[4 * kk + 3], b[2 * kk], b[2 * kk + 1]);
        mma16(dq, w[4 * kk], w[4 * kk + 1], w[4 * kk + 2], w[4 * kk + 3], b[2 * kk], b[2 * kk + 1]);
        if (kk < VK) mma16(dv, av[4 * kk], av[4 * kk + 1], av[4 * kk + 2], av[4 * kk + 3], b[2 * kk], b[2 * kk + 1]);
      }
    }
    const float k2 = 0.07216878364870322f * 1.44269504089f;
    stsm4t(qs, pack2(dq[0] * k2, dq[1] * k2), pack2(dq[2] * k2, dq[3] * k2), pack2(dk[0], dk[1]), pack2(dk[2], dk[3]));
    TM(1);
  };
  constexpr int VC = VK == 20 ? 1 : WG == 0 ? 2 : 3;
  auto finish_v = [&](const uint32_t (&b)[40], float (&dv)[16]) {
#pragma unroll
    for (int kk = VK; kk < 20; kk++) mma16(dv + 4 * ((kk - VK) % VC), av[4 * kk], av[4 * kk + 1], av[4 * kk + 2], av[4 * kk + 3], b[2 * kk], b[2 * kk + 1]);
  };
  auto sum_v = [&](float (&dv)[16]) {
#pragma unroll
    for (int i = 4; i < 4 * VC; i++) dv[i & 3] += dv[i];
  };
  auto publish_km = [&](int s) {
    uint32_t a[4];
    ldsm4(a, qa);
    *reinterpret_cast<uint2*>(kv(s, l8) + KV_M) = make_uint2(hadd2(a[0], a[2]), hadd2(a[1], a[3]));
  };
  auto memory_v = [&](uint2 x, const float (&dv)[16]) {
    return make_uint2(pack2(dv[0] + bf_lo(x.x), dv[1] + bf_hi(x.x)), pack2(dv[2] + bf_lo(x.y), dv[3] + bf_hi(x.y)));
  };
  auto publish_v = [&](int s, const uint4 (&v)[2], uint2 vm) {
#pragma unroll
    for (int e = 0; e < 2; e++) reinterpret_cast<uint4*>(kv(s, lw) + KV_V)[e * 32] = v[e];
    *reinterpret_cast<uint2*>(kv(s, l8) + KV_V + KV_M) = vm;
  };
  auto load_x = [&](int s, int k0, int n, uint32_t bar) {
    if (!NOX && elect()) { mbar_expect(bar, n * 1024); bulk_load(sb + CH_X + k0 * 1024, p.xc + (s + 1) * 10240 + k0 * 256, n * 1024, bar); }
  };
#pragma unroll 1
  for (int s = 0; s < NSEG - 1; s++) {
    float dv[16] = {};
    uint32_t b[40], kf[16];
    project(s, b, dv, kf);
    if (WG == 0) {
      bar_sync(1, 256);
      if (CH_XA == 0) load_x(s, 20 + 5 * t4, 5, bXA);
      if (CH_XB == 0) load_x(s, 5 * t4, 5, bXB);
      pin();
      finish_v(b, dv);
      sum_v(dv);
      sts64(l8 + CH_VP, pack2(dv[0], dv[1]), pack2(dv[2], dv[3]));
      __syncwarp();
      if (elect()) mbar_arrive(bX);
      if (CH_XA == 1) load_x(s, 20 + 5 * t4, 5, bXA);
      if (CH_XB == 1) load_x(s, 5 * t4, 5, bXB);
      uint32_t w[144];
      auto wload = [&](int i) { ldsm4t(&w[4 * i], (i % 3 == 0 ? wo : i % 3 == 1 ? wo ^ 32 : wo2) + i / 12 * 28672 + i / 3 % 4 * 1024); };
      TM(3);
      publish_k(s);
      if (CH_KM == 0) publish_km(s);
#pragma unroll
      for (int i = 0; i < CH_W1; i++) wload(i);
      bar_sync(10, 256);
#pragma unroll
      for (int i = CH_W1; i < CH_W2; i++) wload(i);
      bulk_wait_read<0>();
      if (CH_XA == 2) load_x(s, 20 + 5 * t4, 5, bXA);
      if (CH_XB == 2) load_x(s, 5 * t4, 5, bXB);
      bar_sync(2, 256);
      {
        float y[3][4] = {};
        uint32_t ob[24];
        ldsm4(&ob[0], l16 + CH_O + 1024); ldsm4(&ob[4], l16 + CH_O + 1536);
        TM(7);
        auto step = [&](int i) {
          const int k = i / 3;
          mma16(y[i % 3], w[4 * i], w[4 * i + 1], w[4 * i + 2], w[4 * i + 3], ob[2 * k], ob[2 * k + 1]);
        };
#pragma unroll
        for (int i = 0; i < 12; i++) {
          step(i);
          if (i >= 12 - (CH_W3 - CH_W2)) wload(CH_W3 - 12 + i);
          if (i % 3 == 2) pin();
        }
        if (CH_XB == 3) load_x(s, 5 * t4, 5, bXB);
        pin();
        mbar_wait(bO, s & 1);
        TM(4);
        ldsm4(&ob[8], l16 + CH_O); ldsm4(&ob[12], l16 + CH_O + 512);
        pin();
        float2 inv;
        uint8_t* dst[6];
        uint32_t mask;
#pragma unroll
        for (int i = 12; i < 36; i++) {
          step(i);
          const int n = CH_W3 + i - 13, m = n - (n > 30);
          if (i == 12) ldsm4(&ob[16], l16 + after(w[4 * CH_W3 - 1] | w[4 * CH_W3 - 5] | w[4 * CH_W3 - 9] | ob[8]) + CH_O + 2048);
          else if (n == 30) ldsm4(&ob[20], l16 + CH_O + 2560);
          else if (m < 36) wload(m);
          else if (m == 36) inv = lds64f((l8 & ~0xe0u) + CH_VP);
          if (i == 26) mask = ((l16 ^ tag) & 48) == 0;
          if (i >= 27 && i < 33) dst[i - 27] = pool(line0(i - 27) * 8192 + (pages >> (i - 27) & 1) * 4096) + plane;
          if (i % 3 == 2) pin();
        }
#pragma unroll
        for (int k = 0; k < CH_R1; k++) ldsm4t(&tw[4 * k], wq + k * 2048);
        pin();
#pragma unroll
        for (int i = 0; i < 6; i++) stg_strong32(dst[i], pack_tag(y[i >> 1][2 * (i & 1)] * inv.x, y[i >> 1][2 * (i & 1) + 1] * inv.y, tag, mask));
        TM(8);
        TR(0, clk32());
        bar_arrive(5, 256);
        pin();
#pragma unroll
        for (int k = CH_R1; k < CH_R2; k++) ldsm4t(&tw[4 * k], wq + k * 2048);
      }
      const uint32_t t0 = clk32();
      const uint32_t ln = (l16 ^ tag) >> 4 & 31;
      if (t4 >= 2) {
        const uint32_t bP = bH + t4 * 8 - 8;
        auto fetch = [&]() { TR(1, clk32()); if (elect()) { mbar_expect(bP, 2048); bulk_load(sb + CH_PS + (t4 & 1) * 2048, p.pool + (rsrc + (t4 & 1) * 2048), 2048, bP); } };
        until(t0 + CH_D1);
        fetch();
        TM(5);
        if (CH_KM == 1) publish_km(s);
        if (!NOX) mbar_wait_hot(bXB, (s + 1) & 1);
        uint8_t* mdst = p.pool + (st * 32768 + rdst + (t4 & 1) * 64) + ln * 4;
        const uint32_t sel = (ln >> 3) != (ln & 1) ? 0 : ln & 4 ? 0x3f800000u : 0x00003f80u, want = (tag & 1) * 0x10001, chk = ln < 4 ? 0x10001 : 0;
        const uint32_t ps = l16 + (CH_PS + (t4 & 1) * 2048) + after((uint32_t)(uintptr_t)mdst | (uint32_t)((uintptr_t)mdst >> 32));
        const uint32_t sel1 = sel + after(ln), junk0 = after(sel), junk1 = after(chk);
        pin();
        int n = 0;
        float y[4][4];
        for (;;) {
          uint32_t u[16];
          TM(13);
          mbar_wait(bP, pph);
          TM(14);
          TR(2, clk32());
          pph ^= 1;
#pragma unroll
          for (int i = 0; i < 4; i++) ldsm4t(&u[4 * i], ps + i * 512);
          pin();
#pragma unroll
          for (int i = 0; i < 4; i++) y[0][i] = y[1][i] = y[2][i] = y[3][i] = 0.f;
          uint32_t bad = 0;
#pragma unroll
          for (int i = 0; i < 8; i++) mma16(y[i & 3], sel, junk0, sel1, junk1, u[2 * i], u[2 * i + 1]);
#pragma unroll
          for (int i = 0; i < 4; i++) bad = or3(bad, differ(u[4 * i], u[4 * i + 1], want), differ(u[4 * i + 2], u[4 * i + 3], want));
          if (__builtin_expect(!__any_sync(~0u, bad & chk), 1)) break;
          fetch();
          spin_guard(n);
        }
        TM(15);
        const uint32_t w = nz(pack2((y[0][0] + y[1][0]) + (y[2][0] + y[3][0]), (y[0][1] + y[1][1]) + (y[2][1] + y[3][1])));
        if (ln < 16) { stg_strong32(mdst, w); stg_strong32(mdst + 4096, w); }
        TMV(12, 32, n);
        TR(3, (clk32() & ~3u) | min(n, 3));
      } else {
        if (CH_KM == 1) publish_km(s);
        if (!NOX) mbar_wait_hot(bXB, (s + 1) & 1);
        stg_strong32(p.pool + ((st == 2 ? 0 : st + 1) * 32768 + rdst + t4 * 4096) + ln * 4, 0u);
        if (t4 == 0 && cta < 40 && s + 4 < NSEG && elect())
          asm volatile("cp.async.bulk.prefetch.L2.global [%0], 1024;" :: "l"(p.xc + (s + 4) * 10240 + cta * 256) : "memory");
        if (t4 == 1 && (s & 3) == 0 && s > 0 && elect()) red_relaxed(p.sync + 2 * s - 4, 1);
        if (t4 == 1 && s == NSEG - 3 && cta == 95 && elect()) red_relaxed(p.sync + 2 * s + 2, 0x10000);
      }
      TM(10);
      bar_arrive(8, 256);
      tokens0(s + 1, Int<CH_R2>());
      TM(2);
      TR(7, clk32());
    } else {
      const uint32_t xo = l4 + (CH_SX - (t4 == 3 ? 128 : 0)), x1 = xo + (r1 + 768 + min(t4, 2) * 256), x2 = xo + (r2 + 1024 + min(t4, 2) * 256);
      if (t4 < 2) {
        float ds[4][4] = {};
        uint32_t q[16];
        asm volatile("bar.sync 1, 256;" ::: "memory");
#pragma unroll
        for (int k = 0; k < 4; k++) ldsm4(&q[4 * k], qa + k * 512);
        pin();
        if (VK < 20) { finish_v(b, dv); pin(); }
#pragma unroll
        for (int k = 0; k < 4; k++) {
          mma16(ds[k & 1], kf[4 * k], kf[4 * k + 1], kf[4 * k + 2], kf[4 * k + 3], q[4 * k], q[4 * k + 1]);
          mma16(ds[2 + (k & 1)], kf[4 * k], kf[4 * k + 1], kf[4 * k + 2], kf[4 * k + 3], q[4 * k + 2], q[4 * k + 3]);
        }
        float t[4];
#pragma unroll
        for (int i = 0; i < 4; i++) t[i] = (ds[0][i] + ds[2][i]) + (ds[1][i] + ds[3][i]);
        const uint32_t w0 = pack2(t[0], t[1]), w1 = pack2(t[2], t[3]);
        st_async32(x1, w0, bX + r1); st_async32(x2, w0, bX + r2);
        st_async32(x1 + 128, w1, bX + r1); st_async32(x2 + 128, w1, bX + r2);
        sts32(xo, w0); sts32(xo + 128, w1);
      } else {
        float ds[4][4] = {};
        uint32_t q0[4], q1[4], a0[4], a1[4];
        asm volatile("bar.sync 1, 256; " ::: "memory");
        ldsm4(a0, ka); ldsm4(q0, qa); ldsm4(a1, ka + 512); ldsm4(q1, qa + 512);
        pin();
        if (VK < 20) { finish_v(b, dv); pin(); }
        mma16(ds[0], a0[0], a0[1], a0[2], a0[3], q0[0], q0[1]);
        mma16(ds[1], a0[0], a0[1], a0[2], a0[3], q0[2], q0[3]);
        mma16(ds[2], a1[0], a1[1], a1[2], a1[3], q1[0], q1[1]);
        mma16(ds[3], a1[0], a1[1], a1[2], a1[3], q1[2], q1[3]);
        float t[2];
#pragma unroll
        for (int i = 0; i < 2; i++)
          t[i] = ((ds[0][i] + ds[0][i + 2]) + (ds[1][i] + ds[1][i + 2])) + ((ds[2][i] + ds[2][i + 2]) + (ds[3][i] + ds[3][i + 2]));
        const uint32_t w0 = pack2(t[0], t[1]);
        st_async32(x1, w0, bX + r1);
        st_async32(x2, w0, bX + r2);
        sts32(xo, w0);
      }
      TM(3);
      const uint4 id = lds128(l16 + CH_ID);
      float sc[3][4] = {};
      uint4 v[2];
      sum_v(dv);
      bar_sync(3, 128);
      uint32_t r[12], wd[12];
      ldsm4(&r[0], l16 + CH_SX); ldsm2(&r[4], l16 + CH_SX + 512);
      pin();
      v[0] = lds128(lw + CH_VT); v[1] = lds128(lw + CH_VT + 512);
#pragma unroll
      for (int u = 0; u < 3; u++) ldsm4t(&wd[4 * u], wo + u * 28672);
      pin();
#pragma unroll
      for (int q = 0; q < 3; q++) mma16(sc[q], id.x, id.y, id.z, id.w, r[2 * q], r[2 * q + 1]);
      uint32_t big = absmax2(absmax2(absmax2(r[0], r[1]), absmax2(r[2], r[3])), absmax2(r[4], r[5]));
      const uint32_t oa1 = l4 + (r1 + CH_O), oa2 = l4 + (r2 + CH_O + 2048), ones = 0x3f803f80u;
      mbar_wait_hot(bX, s & 1);
      TM(4);
      ldsm4(&r[0], l16 + CH_SX + 768); ldsm4(&r[8], l16 + CH_SX + 1792); ldsm4(&r[4], l16 + CH_SX + 1280);
      const uint2 vp = lds64(l8 + CH_VP);
      bar_arrive(10, 256);
      pin();
      {
        float sd[3][4] = {};
#pragma unroll
        for (int i = 0; i < 3; i++) {
          const int q = i == 0 ? 0 : 3 - i;
          mma16(sc[q], id.x, id.y, id.z, id.w, r[4 * q], r[4 * q + 1]);
          mma16(sd[q], id.x, id.y, id.z, id.w, r[4 * q + 2], r[4 * q + 3]);
          big = absmax2(big, absmax2(absmax2(r[4 * q], r[4 * q + 1]), absmax2(r[4 * q + 2], r[4 * q + 3])));
        }
#pragma unroll
        for (int i = 0; i < 12; i++) sc[i >> 2][i & 3] += sd[i >> 2][i & 3];
      }
      const bool redo = __any_sync(~0u, (absmax2(big, big << 16) & 0x7fff0000u) >= 0x41800000u);
      const uint2 vm = memory_v(vp, dv);
      sc[2][0] += sc[2][2]; sc[2][1] += sc[2][3];
      float l[4], o[2][4];
      uint32_t p3, p4;
      auto attend = [&]() {
#pragma unroll
        for (int i = 0; i < 4; i++) l[i] = o[0][i] = o[1][i] = 0.f;
        const uint32_t p1 = pack2(ex2(sc[0][0]), ex2(sc[0][1])), p2 = pack2(ex2(sc[0][2]), ex2(sc[0][3]));
        mma16h(o[0], p1, p2, v[0].x, v[0].y);
        mma16h(o[1], p1, p2, v[0].z, v[0].w);
        mma16h(l, p1, p2, ones, ones);
        const uint32_t p0 = pack2(ex2(sc[2][0]), ex2(sc[2][1]));
        mma8h(o[0], p0, vm.x);
        mma8h(o[1], p0, vm.y);
        mma8h(l, p0, ones);
        p3 = pack2(ex2(sc[1][0]), ex2(sc[1][1])); p4 = pack2(ex2(sc[1][2]), ex2(sc[1][3]));
        mma16h(o[0], p3, p4, v[1].x, v[1].y);
        mma16h(o[1], p3, p4, v[1].z, v[1].w);
      };
      attend();
      if (__builtin_expect(redo, 0)) {
        float mx = fmaxf(sc[2][0], sc[2][1]);
#pragma unroll
        for (int i = 0; i < 4; i++) mx = fmaxf(mx, fmaxf(sc[0][i], sc[1][i]));
        mx = fmaxf(mx, __shfl_xor_sync(~0u, mx, 1));
        mx = fmaxf(mx, __shfl_xor_sync(~0u, mx, 2));
#pragma unroll
        for (int i = 0; i < 4; i++) { sc[0][i] -= mx; sc[1][i] -= mx; }
        sc[2][0] -= mx; sc[2][1] -= mx;
        attend();
      }
      const uint32_t o0 = pack2(o[0][0], o[0][1]), o1 = pack2(o[1][0], o[1][1]);
      st_async32(oa1, o0, bO + r1); st_async32(oa2, o0, bO + r2);
      st_async32(oa1 + 128, o1, bO + r1); st_async32(oa2 + 128, o1, bO + r2);
      sts32(l4 + CH_O + 1024, o0); sts32(l4 + CH_O + 1152, o1);
      bar_arrive(2, 256);
      pin();
      TM(6);
      mma16h(l, p3, p4, ones, ones);
      float inv;
      asm("rcp.approx.ftz.f32 %0, %1;" : "=f"(inv) : "f"(l[0]));
      sts32((l8 & ~0xffu) + (lane & 28) + CH_VP, __float_as_uint(inv));
      __syncwarp();
      if (elect()) mbar_arrive(bO);
      {
        float z[2][4] = {}, y[2][4] = {};
        uint32_t we[12] = {};
        mma16(z[0], wd[0], wd[1], wd[2], wd[3], o0, o1);
        if (j == 0) {
#pragma unroll
          for (int u = 0; u < 3; u++) ldsm4t(&we[4 * u], (wo ^ 32) + u * 28672);
          mma16(y[0], we[0], we[1], we[2], we[3], o0, o1);
        }
        const float2 iv = lds64f((l8 & ~0xe0u) + CH_VP);
        uint8_t* dst = pool(pdst[0]);
        const uint32_t mask = ((l16 ^ tag) & 48) == 0;
        const uint32_t oa = qa + ((tag & 0xfffe) + CH_O - CH_QK + t4 * 256 - (t4 == 3 ? 1024 : 0));
        const uint32_t za = l16 + ((tag & 0xfffe) + (t4 >> 1) * 512 + (t4 & 1) * 8);
        pin();
        mbar_wait(bO, s & 1);
        uint32_t a[4];
        ldsm4(a, oa);
        mma16(z[0], wd[4], wd[5], wd[6], wd[7], a[0], a[1]);
        mma16(z[1], wd[8], wd[9], wd[10], wd[11], a[2], a[3]);
        if (j == 0) {
          mma16(y[0], we[4], we[5], we[6], we[7], a[0], a[1]);
          mma16(y[1], we[8], we[9], we[10], we[11], a[2], a[3]);
          sts128f(lw + CH_VT + 512, y[0][0] + y[1][0], y[0][1] + y[1][1], y[0][2] + y[1][2], y[0][3] + y[1][3]);
        }
        sts128f(lw + CH_VT, z[0][0] + z[1][0], z[0][1] + z[1][1], z[0][2] + z[1][2], z[0][3] + z[1][3]);
        bar_sync(3, 128);
        if (j == 0 || t4 < 2) {
          float2 q[4];
#pragma unroll
          for (int i = 0; i < 4; i++) q[i] = lds64f(za + CH_VT + i * 1024);
          stg_strong32(dst, pack_tag(((q[0].x + q[1].x) + (q[2].x + q[3].x)) * iv.x, ((q[0].y + q[1].y) + (q[2].y + q[3].y)) * iv.y, tag, mask));
        }
      }
      TM(2);
      if (!NOX) mbar_wait_hot(bXA, (s + 1) & 1);
      float dk[16], dw[16];
      bar_sync(5, 256);
      wg_fence();
      pass(dk, ak, Int<0>(), Int<20>());
      pass(dw, av, Int<0>(), Int<20>());
      TM(5);
      pin();
      publish_v(s, v, vm);
      if (elect()) {
        mbar_expect(bG + t4 * 8, 2560);
        if (t4 == 3 && s + 2 < NSEG) { mbar_expect(bX, 1536); mbar_expect(bO, 2048); }
      }
      wg_wait<1>();
      dump(dk, lw + CH_KT);
      wg_wait<0>();
      TM(7);
      dump(dw, lw + CH_VT);
      bar_arrive(9, 256);
      pin();
#pragma unroll
      for (int k = 0; k < CH_RB; k++) ldsm4t(&tw[4 * k], wq + k * 2048);
      if (t4 < 2) {
#pragma unroll
        for (int k = CH_RB; k < CH_RC; k++) ldsm4t(&tw[4 * k], wq + k * 2048);
        const int q = t4 ? 3 : j, o = t4 ? j * 896 : 0;
        const uint8_t* src = p.pool + ((80 + st * 4 + q) * 8192 + (pages >> (st * 4 + q) & 1) * 4096 + o);
        auto fetch = [&](auto n) {
          asm volatile("bar.sync 8, 256;" ::: "memory");
          if (CH_D2) until(clk32() + CH_D2);
          mbar_wait(bH, s & 1);
          TR(4, clk32());
          if (elect())
            asm volatile("cp.async.bulk.shared::cluster.global.mbarrier::complete_tx::bytes.multicast::cluster [%0], [%1], %2, [%3], 7;"
                         :: "r"(sb + CH_M + q * 2560 + o), "l"(src), "n"(n.value), "r"(bG + q * 8) : "memory");
        };
        if (!t4) fetch(Int<2560>()); else if (j == 2) fetch(Int<768>()); else fetch(Int<896>());
      } else {
        asm volatile("bar.sync 8, 256; " ::: "memory");
        if (elect()) asm volatile("mbarrier.arrive.relaxed.cluster.shared::cluster.b64 _, [%0];" :: "r"(bH + (t4 == 2 ? r1 : r2)) : "memory");
        pin();
#pragma unroll
        for (int k = CH_RB; k < CH_RC; k++) ldsm4t(&tw[4 * k], wq + k * 2048);
      }
      TM(9);
      pin();
#pragma unroll
      for (int k = CH_RC; k < CH_TW; k++) ldsm4t(&tw[4 * k], wq + k * 2048);
      TM(10);
    }
    if (++st == 3) st = 0;
    tag ^= 0x10001;
  }
  {
    const int s = NSEG - 1;
    float dv[16] = {};
    uint32_t b[40], kf[16];
    project(s, b, dv, kf);
    finish_v(b, dv);
    sum_v(dv);
    if (WG == 0) {
      sts64(l8 + CH_VP, pack2(dv[0], dv[1]), pack2(dv[2], dv[3]));
      bar_sync(1, 256);
      publish_k(s);
      publish_km(s);
      bulk_wait<0>();
      fence_async_global();
      bar_sync(2, 256);
      if (tid == 0) red_release(g_sync + 15 * 8 + 4, 1);
    } else {
      const uint4 v[2] = {lds128(lw + CH_VT), lds128(lw + CH_VT + 512)};
      bar_sync(1, 256);
      publish_v(s, v, memory_v(lds64(l8 + CH_VP), dv));
      bar_arrive(2, 256);
    }
  }
}

__global__ void __launch_bounds__(256, 1) chain_kernel(const __grid_constant__ ChainParams p) {
  extern __shared__ __align__(1024) uint8_t smem_raw[];
  const uint32_t sb = s2u(smem_raw);
  const int tid = threadIdx.x, warp = __shfl_sync(~0u, tid >> 5, 0), lane = tid & 31;
  const int cta = blockIdx.x, h = cta / 3, j = cta - 3 * h, colbase = cta * 64;
  const uint32_t bWo = sb + CH_BAR, bWq = bWo + 8, bXA = bWo + 24, bWk = bWo + 80, bWv = bWo + 88;
  uint32_t smid; asm("mov.u32 %0, %%smid;" : "=r"(smid));
  PRO(0);
  if (sb != mapa(CH_BASE, j)) __trap();
  uint32_t entry = 0;
  auto place = [&]() {
    const int i = tid - 128;
    if (i >= 0 && i <= NSLOT) {
      const uint32_t side = ldg_strong32(g_smpart + (smid & 255));
      if (i < NSLOT) {
        entry = i * 8192 + (ldg_strong32(g_orient + i) == (i < 80 ? i & 1 : side) ? 0 : 4096);
      } else {
        entry = 2 * (atomicAdd(g_bo + p.layer * 128 + 1, 1 << 8 * side) >> 8 * side & 255) + side;
      }
    }
    __syncwarp();
  };
  if (p.layer) place();
  if (warp == 0 && elect()) {
#pragma unroll 1
    for (int i = 0; i < 15; i++) mbar_init(bWo + 8 * i, i == 2 || i == 5 ? 5 : i == 3 || i == 4 ? 4 : i == 12 ? 2 : 1);
    asm volatile("fence.mbarrier_init.release.cluster;" ::: "memory");
    mbar_expect(bWk, 81920);
    tma_load3<(WEF & 1) != 0>(sb + CH_WQ, &p.wk, colbase, 0, bWk);
    mbar_expect(bWv, 81920);
    tma_load3<(WEF & 1) != 0>(sb + CH_WO, &p.wv, colbase, 0, bWv);
    mbar_expect(bWo + 16, 1536);
    mbar_expect(bWo + 40, 2048);
    mbar_expect(bWo, 86016); mbar_expect(bWq, 81920);
#pragma unroll 1
    for (int i = 0; i < 8; i++) mbar_expect(bXA + 8 * (i & 1), 5120);
  }
  if (warp == 1) {
    const uint32_t id = (lane >> 3) == (lane & 3) ? ((lane & 4) ? 0x3f800000u : 0x00003f80u) : 0u;
    sts128(sb + CH_ID + lane * 16, make_uint4(id, 0, 0, id));
  }
  __syncthreads();
  asm volatile("barrier.cluster.arrive.relaxed.aligned;" ::: "memory");
  uint32_t ak[80], av[80];
  const uint32_t wq = opaque(sb + CH_WQ + ((warp >> 2) * 320 + (lane & 7) + (lane >> 4) * 8) * 128 + (((2 * (warp & 3) + ((lane >> 3) & 1)) ^ (lane & 7)) << 4));
  pdl_wait();
  if (tid == 32) stg_strong32(g_smuse + (smid & 255), p.layer + 1);
  pdl_launch();
  PRO(1);
  if (warp == 0 && elect()) {
    bulk_load(sb + CH_X + 20480, p.xc + 5120, 20480, bXA);
    bulk_load(sb + CH_X, p.xc, 20480, bXA + 8);
  }
  if (!p.layer) place();
  __syncwarp();
  PRO(2);
  mbar_wait(bWk, 0);
  PRO(3);
#pragma unroll
  for (int k = 0; k < 20; k++) ldsm4t(&ak[4 * k], wq + k * 2048);
  bar_sync(6, 256);
  if (warp == 0 && elect()) tma_load3<(WEF & 2) != 0>(sb + CH_WQ, &p.wq, colbase, 0, bWq);
  __syncwarp();
  PRO(4);
  mbar_wait(bWv, 0);
  PRO(5);
#pragma unroll
  for (int k = 0; k < 20; k++) ldsm4t(&av[4 * k], wq + CH_WO + k * 2048);
  bar_sync(6, 256);
  PRO(6);
  if (warp >= 5 && elect()) tma_load3<(WEF & 2) != 0>(sb + CH_WO + (warp - 5) * 28672, &p.wo, j == 0 ? 0 : 32 + j * 192, h * 192 + (j + 8 - warp) % 3 * 64, bWo);
  if (tid == 128 + NSLOT && entry >= 80) {
    uint32_t c;
    int n = 0;
    do { c = ldg_strong32(g_bo + p.layer * 128 + 1); spin_guard(n); } while ((c & 255) + (c >> 8) < 96);
    const uint32_t other = (c >> 8 * (~entry & 1) & 255) + (entry >> 1) - 40;
    entry = other < 40 ? 2 * other + (~entry & 1) : entry % 80;
  }
  if (tid >= 128 && tid <= 128 + NSLOT) sts32(sb + CH_O + (tid - 128) * 4, entry);
  PRO(7);
  __syncthreads();
  if (__shfl_sync(~0u, tid >> 7, 0) == 0) chain_body<0>(p, wq, ak, av); else chain_body<1>(p, wq, ak, av);
}

struct PostParams { CUtensorMap wq, wo, wb, wo2, wb2; int gap, share, layer, look, gap2, pol; };
constexpr int PS = 8, PB = 28672;
constexpr int OP_SMEM = PS * PB + 512 + 2048;
enum { IT_ATT = 0, IT_OP = 1, IT_FIN = 2, IT_BQ = 3, IT_Q = 4 };

__device__ __forceinline__ uint32_t item_count(int type, int b) {
  return type == IT_ATT ? 32 : type == IT_OP ? op_split(b) * (DM / op_width(b)) : type == IT_FIN ? fin_items(b) : 1920 / bq_width(b); }
__device__ __forceinline__ uint32_t item_need(int type, int b) { return type == IT_ATT ? 96 : item_count(type - 1, b); }

struct Ring {
  uint32_t sb, bars; int st; uint32_t ph;
  __device__ __forceinline__ uint32_t wait() const { mbar_wait(bars + 8 * st, ph); return sb + st * PB; }
  __device__ __forceinline__ void next() { if (++st == PS) { st = 0; ph ^= 1; } }
  __device__ __forceinline__ void release(int s) const { if ((threadIdx.x & 31) == 0) mbar_arrive(bars + 8 * (PS + s)); }
  __device__ __forceinline__ void pop() { __syncwarp(); release(st); next(); }
};

template <int N>
__device__ __forceinline__ void gemm_item(Ring& r, float* d, int nst, uint32_t go, int go_at) {
  int prev = 0;
#pragma unroll 1
  for (int kb = 0; kb < nst; kb++) {
    const uint32_t base = r.wait();
    const uint64_t da = mkdesc(base + (threadIdx.x >> 7) * 4096, 128, 512, 0), db = mkdesc(base + 8192, 4096, 1024, 1);
    wg_fence();
#pragma unroll
    for (int kk = 0; kk < 2; kk++) {
      if (N == 80) wg_ss80_01(d, da + kk * 16, db + kk * 128, (kb | kk) != 0);
      if (N == 160) wg_ss160_01(d, da + kk * 16, db + kk * 128, (kb | kk) != 0);
      if (N >= 192) wg_ss192_01(d, da + kk * 16, db + kk * 128, (kb | kk) != 0);
      if (N == 320) wg_ss128_01(d + 96, da + kk * 16, db + kk * 128 + 3 * 256, (kb | kk) != 0);
    }
    wg_commit();
    if (kb == go_at && threadIdx.x == 0) mbar_arrive(go);
    if (kb > 0) { wg_wait<1>(); r.release(prev); }
    prev = r.st;
    r.next();
  }
  wg_wait<0>();
  reg_fence<N / 2>(d);
  r.release(prev);
}

template <int HALF>
__device__ __forceinline__ void attn_a_warp(Ring& r, const uint32_t (&q)[48], int b, int h) {
  constexpr int NT = HALF ? 5 : 3, NF = 8 * NT;
  const int lane = threadIdx.x & 31, g = lane >> 2, c = lane & 3, seg = (threadIdx.x >> 5) & 3;
  uint32_t f[6][NF];
  int slot[6];
  auto fetch = [&](int u) {
    const uint32_t kv = r.wait() + seg * KV_BYTES;
    slot[u] = r.st;
    r.next();
#pragma unroll
    for (int w = 0; w < 4; w++) {
      uint32_t* d = &f[u][2 * NT * w];
#pragma unroll
      for (int t = 0; t <= HALF; t++) {
        if (u < 3) {
          ldsm4(d + 4 * t, kv + w * 1024 + t * 512 + (lane & 8) * 32 + (lane & 16) * 8 + (lane & 7) * 16);
        } else {
          const uint4 v = lds128(kv + w * 1024 + t * 512 + lane * 16);
          d[4 * t] = v.x; d[4 * t + 1] = v.y; d[4 * t + 2] = v.z; d[4 * t + 3] = v.w;
        }
      }
      const uint2 m = lds64(kv + KV_M + w * 256 + lane * 8);
      d[2 * NT - 2] = m.x; d[2 * NT - 1] = m.y;
    }
    pdl_launch();
  };
  float s[NT][4] = {};
  fetch(0);
#pragma unroll
  for (int u = 0; u < 3; u++) {
    fetch(u + 1);
#pragma unroll
    for (int kk = 0; kk < 4; kk++) {
      const uint32_t* a = &q[16 * u + 4 * kk];
#pragma unroll
      for (int n = 0; n < NT; n++) mma16(s[(n + 1) % NT], a[0], a[1], a[2], a[3], f[u][2 * NT * kk + 2 * n], f[u][2 * NT * kk + 2 * n + 1]);
    }
    r.release(slot[u]);
    pdl_launch();
  }
  fetch(4);
  const float k2 = 0.07216878364870322f * 1.44269504089f, NEG = -INFINITY;
  if (2 * c > g) { s[NT - 2][0] = NEG; s[NT - 1][2] = NEG; }
  if (2 * c + 1 > g) { s[NT - 2][1] = NEG; s[NT - 1][3] = NEG; }
  s[NT - 1][0] = s[NT - 1][1] = NEG;
  uint32_t pp[NT][2]; float inv[2];
#pragma unroll
  for (int hh = 0; hh < 2; hh++) {
    float m = NEG, l = 0.f;
#pragma unroll
    for (int n = 0; n < NT; n++) m = fmaxf(m, fmaxf(s[n][2 * hh], s[n][2 * hh + 1]));
    m = fmaxf(m, __shfl_xor_sync(~0u, m, 1)); m = fmaxf(m, __shfl_xor_sync(~0u, m, 2));
#pragma unroll
    for (int n = 0; n < NT; n++) { const float x = ex2((s[n][2 * hh] - m) * k2), y = ex2((s[n][2 * hh + 1] - m) * k2); l += x + y; pp[n][hh] = pack2(x, y); }
    l += __shfl_xor_sync(~0u, l, 1); l += __shfl_xor_sync(~0u, l, 2);
    asm("rcp.approx.ftz.f32 %0, %1;" : "=f"(inv[hh]) : "f"(l));
  }
  uint32_t* dst = g_o + ((b * 192 + h * 6) * 16 + seg * 4 + HALF * 2) * 128 + lane;
#pragma unroll
  for (int u = 3; u < 6; u++) {
    float o[8][4] = {};
#pragma unroll
    for (int n = 0; n < 8; n++) mma8(o[n], pp[0][0], pp[0][1], f[u][2 * NT * (n >> 1) + 2 * NT - 2 + (n & 1)]);
#pragma unroll
    for (int t = 0; t <= HALF; t++)
#pragma unroll
      for (int n = 0; n < 8; n++) {
        const uint32_t* v = &f[u][2 * NT * (n >> 1) + 4 * t + 2 * (n & 1)];
        mma16(o[n], pp[1 + 2 * t][0], pp[1 + 2 * t][1], pp[2 + 2 * t][0], pp[2 + 2 * t][1], v[0], v[1]);
      }
    r.release(slot[u]);
    if (u == 3) fetch(5);
#pragma unroll
    for (int n = 0; n < 8; n++) {
      dst[(u - 3) * 4096 + (n >> 2) * 2048 + (n & 3) * 32] = pack2(o[n][0] * inv[0], o[n][1] * inv[0]);
      dst[(u - 3) * 4096 + (n >> 2) * 2048 + (n & 3) * 32 + 128] = pack2(o[n][2] * inv[1], o[n][3] * inv[1]);
    }
  }
}

template <int NG>
__device__ __forceinline__ void fin_item(Ring& r, uint32_t scratch, int b, int idx) {
  const int warp = threadIdx.x >> 5, lane = threadIdx.x & 31;
  float4* x = g_x + ((b * 16 + idx * NG) * 40 + warp * 5) * 32 + lane;
  float4 v[NG][5];
#pragma unroll
  for (int g = 0; g < NG; g++) {
    const uint32_t base = r.wait();
#pragma unroll
    for (int i = 0; i < 5; i++) v[g][i] = lds128f(base + ((warp * 5 + i) * 32 + lane) * 16);
    r.pop();
  }
#pragma unroll 1
  for (int k = 0; k < op_split(b); k += NG == 1 ? 2 : 1) {
#pragma unroll
    for (int g = 0; g < NG; g += 2) {
      const uint32_t base = r.wait();
#pragma unroll
      for (int i = 0; i < 10; i++) {
        const uint2 q = lds64(base + ((i / 5 * 40 + warp * 5 + i % 5) * 32 + lane) * 8);
        float4& t = v[(g + i / 5) % NG][i % 5];
        t.x += bf_lo(q.x); t.y += bf_hi(q.x); t.z += bf_lo(q.y); t.w += bf_hi(q.y);
      }
      r.pop();
    }
  }
  float mean[NG], rs[NG];
  ln_stats<NG>(v, scratch, mean, rs);
#pragma unroll
  for (int i = 0; i < 5; i++) {
    const int u = warp * 5 + i;
    uint32_t* xn = g_xn + ((b * 20 + (u >> 1)) * 16 + idx * NG) * 128 + (u & 1) * 64 + lane;
#pragma unroll
    for (int g = 0; g < NG; g++) {
      xn[g * 128] = pack2((v[g][i].x - mean[g]) * rs[g], (v[g][i].y - mean[g]) * rs[g]);
      xn[g * 128 + 32] = pack2((v[g][i].z - mean[g]) * rs[g], (v[g][i].w - mean[g]) * rs[g]);
    }
  }
#pragma unroll
  for (int g = 0; g < NG; g++)
#pragma unroll
    for (int i = 0; i < 5; i++) x[(g * 40 + i) * 32] = v[g][i];
}

__global__ void __launch_bounds__(384, 1) post_kernel(const __grid_constant__ PostParams p) {
  extern __shared__ __align__(1024) uint8_t smem_raw[];
  const uint32_t sb = s2u(smem_raw), bars = sb + PS * PB;
  const uint32_t bIF = bars + 128, bIE = bars + 160, done = bars + 192, bGo = bars + 224, slots = bars + 240, scratch = bars + 512;
  const int warp = __shfl_sync(~0u, threadIdx.x >> 5, 0), lane = threadIdx.x & 31;
  TRACE(0);
  pdl_launch();
  if (sb & 1023) __trap();
  if (threadIdx.x < 29) mbar_init(bars + 8 * threadIdx.x, threadIdx.x < 8 ? 1 : threadIdx.x < 16 ? 8 : threadIdx.x < 20 ? 1 : threadIdx.x < 24 ? 2 : threadIdx.x < 28 ? 8 : 1);
  fence_async();
  __syncthreads();
  if (warp >= 8) {
    asm volatile("setmaxnreg.dec.sync.aligned.u32 56;");
    if (warp == 9) {
      const int b = lane & 15;
      bool queries = QA_END < 16 && blockIdx.x < 36;
      for (int n = 0;; n++) {
        if (n > 0) mbar_wait(bGo, (n - 1) & 1);
        mbar_wait(bIE + 8 * (n & 3), ((n >> 2) & 1) ^ 1);
        int code = -1, spin = 0, ticket = 0;
        if (queries) {
          if (lane == 0) ticket = atomicAdd(g_sync + SY_QC, 1);
          ticket = __shfl_sync(~0u, ticket, 0);
          queries = ticket < (16 - QA_END) * 32;
          if (queries) code = IT_Q << 16 | (QA_END + ticket % (16 - QA_END)) << 8 | ticket / (16 - QA_END);
        }
        if (!queries && lane == 0) ticket = atomicAdd(g_sync + SY_T, 1);
        while (!queries) {
          const uint4 hd = ldg_strong128(g_sync + b * 8), pr = ldg_strong128(g_sync + b * 8 + 4);
          const uint32_t hv[4] = {hd.x, hd.y, hd.z, hd.w}, pv[4] = {pr.x, pr.y, pr.z, pr.w};
          const uint32_t chain_done = __ballot_sync(~0u, (pr.x & 0xffff) >= 96) & 0xffff;
          int left[4], avail[4], rdy = 0, claimed = 0, upstream = 0;
#pragma unroll
          for (int t = 0; t < 4; t++) {
            const int cnt = lane < 16 ? item_count(t, b) : 0;
            left[t] = max(cnt - (int)hv[t], 0);
            claimed += cnt - left[t];
            const bool ready = (pv[t] & 0xffff) >= item_need(t, b);
            rdy |= ready << t;
            bool ok = ready || (t == IT_ATT ? pr.x >= 0x10000 : !upstream || (t == IT_OP && (chain_done >> 15 & 1)));
            if (t == IT_BQ && (chain_done >> BQ_HOLD & 1) && !(chain_done >> 15)) ok = false;
            avail[t] = ok ? left[t] : 0;
            upstream |= __any_sync(~0u, left[t] > 0);
          }
          if (!upstream) break;
          int rank = max(__shfl_sync(~0u, ticket, 0) - __reduce_add_sync(~0u, claimed), 0), type = -1, mine = 0;
#pragma unroll
          for (int c = 0; c < 8; c++) {
            const int t = c == 0 || c == 5 ? IT_FIN : c == 1 || c == 7 ? IT_ATT : c == 2 || c == 4 ? IT_OP : IT_BQ;
            int a = c == 1 || ((rdy >> t & 1) == (c < 4)) ? avail[t] : 0;
            if (t == IT_OP && !(p.pol & 1)) a = c == 2 ? avail[t] : 0;
            if (c == 7) a = b < QA_END && !(rdy & 1) && ((chain_done << 1 | 1) >> b & 1) ? left[t] : 0;
            const int tot = __reduce_add_sync(~0u, a);
            if (type < 0) { if (rank < tot) { type = t; mine = a; } else rank -= tot; }
          }
          if (type >= 0) {
#pragma unroll
            for (int o = 1; o < 16; o <<= 1) { const int y = __shfl_up_sync(~0u, mine, o); if (lane >= o) mine += y; }
            const int blk = __ffs(__ballot_sync(~0u, mine > rank)) - 1;
            const int early = !(__shfl_sync(~0u, rdy, blk) >> type & 1);
            uint32_t idx = 0;
            if (lane == 0) { idx = atomicAdd(g_sync + blk * 8 + type, 1); ld_acquire(g_sync + blk * 8 + 4 + type); }
            idx = __shfl_sync(~0u, idx, 0);
            if (idx < item_count(type, blk)) { code = (chain_done >> 15 & 1) << 22 | (chain_done >> p.look & 1) << 21 | early << 20 | type << 16 | blk << 8 | idx; break; }
          } else {
            __nanosleep(50);
          }
          spin_guard(spin);
        }
        if (lane == 0) {
          fence_async_global();
          sts32(slots + 4 * (n & 3), code);
          mbar_arrive(bIF + 8 * (n & 3));
        }
        __syncwarp();
        if (code < 0) break;
      }
    } else if (warp == 8) {
      uint32_t smid, nsm, peers = 0;
      asm("mov.u32 %0, %%smid;" : "=r"(smid)); asm("mov.u32 %0, %%nsmid;" : "=r"(nsm));
      for (uint32_t i = lane; i < min(nsm, 256u); i += 32)
        peers += abs((int)(g_smclk[i] - g_smclk[smid & 255])) < 4000 && ldg_strong32(g_smuse + i) != p.layer + 1;
      const uint32_t gap0 = max(p.gap, (int)min(__reduce_add_sync(~0u, peers), 18u) * p.share >> 3);
      if (elect()) {
        uint32_t dst = sb, bar = bars, ph = 1, next = clk32(), gap = 0;
        auto acquire = [&](uint32_t kb) {
          mbar_wait(bar + 8 * PS, ph);
          mbar_expect(bar, kb * 1024);
          if (gap) {
            uint32_t now;
            do now = clk32(); while ((int)(now - next) < 0);
            next = ((int)(now - next) > 100 ? now - 100 : next) + kb * gap;
          }
        };
        auto advance = [&]() { dst += PB; bar += 8; if (dst == bars) { dst = sb; bar = bars; ph ^= 1; } };
        auto depend = [&](const uint32_t* c, uint32_t need) { wait_count(c, need); fence_async_global(); };
#pragma unroll 1
        for (int n = 0;; n++) {
          mbar_wait(bIF + 8 * (n & 3), (n >> 2) & 1);
          const int code = (int)lds32(slots + 4 * (n & 3));
          if (code < 0) break;
          const int type = (code >> 16) & 15, b = (code >> 8) & 255, idx = code & 255;
          const bool early = code >> 20 & 1, go = !(code >> 21 & 1);
          mbar_arrive(bIE + 8 * (n & 3));
          gap = !(code >> 22 & 1) ? gap0 : type == IT_ATT || type == IT_FIN ? 0 : p.gap2;
          const uint32_t* progress = g_sync + b * 8 + 4 + type;
          if (type == IT_ATT && b >= QA_END) {
            depend(g_sync + SY_Q, (16 - QA_END) * 32);
#pragma unroll 1
            for (int u = 0; u < 2; u++) { acquire(24); bulk_load_last(dst, g_q + (((b - QA_END) * 32 + idx) * 2 + u) * 1536, 24576, bar); advance(); }
          } else if (type == IT_FIN) {
            const int ng = 16 / fin_items(b), lg = ng >> 1;
#pragma unroll 1
            for (int g = 0; g < ng; g++) { acquire(20); bulk_load(dst, g_x + (b * 16 + idx * ng + g) * 1280, 20480, bar); advance(); }
            if (early) depend(progress, item_need(type, b));
            if (go) mbar_arrive(bGo);
#pragma unroll 1
            for (int i = 0; i < op_split(b) * ng; i += 2) {
              const uint2* src = g_part + ((b * 16 + (i >> lg)) * 16 + idx * ng + (i & (ng - 1))) * 1280;
              acquire(20);
              bulk_load_last(dst, src, ng > 1 ? 20480 : 10240, bar);
              if (ng == 1) bulk_load_last(dst + 10240, src + 16 * 1280, 10240, bar);
              advance();
            }
          } else {
            const bool op = type == IT_OP, bq = type == IT_BQ;
            const int width = op ? op_width(b) : bq ? bq_width(b) : 192, nb = (width + 63) >> 6, lt = width == 320 ? 1 : 2;
            const int nst = op ? 192 / op_split(b) : 20, kb0 = op ? (idx >> lt) * nst : 0;
            const int col = (op ? idx & ((1 << lt) - 1) : idx) * width;
            const bool whole = !(width & 63);
            const CUtensorMap* m = op ? (whole ? &p.wo : &p.wo2) : bq ? (whole ? &p.wb : &p.wb2) : &p.wq;
            const uint32_t* a = op ? g_o + (b * 192 + kb0) * 2048 : g_xn + b * 20 * 2048;
            int row = kb0 * 32, pre = early && (op || bq) ? min(nst, PS) : 0;
            auto weights = [&]() {
              acquire(8 + nb * 4);
              if (whole) {
                tma_load3z(dst + 8192, m, row, col >> 6, bar);
              } else {
                tma_load(dst + 8192, m, col, row, bar); tma_load(dst + 12288, m, col + 64, row, bar);
                if (nb == 3) tma_load(dst + 16384, m, col + 128, row, bar);
              }
              row += 32;
            };
            if (pre) {
              uint32_t da = dst, ba = bar;
#pragma unroll 1
              for (int kb = 0; kb < pre; kb++) { weights(); advance(); }
              depend(progress, item_need(type, b));
#pragma unroll 1
              for (int kb = 0; kb < pre; kb++) {
                bulk_load(da, a, 8192, ba);
                a += 2048; da += PB; ba += 8;
                if (da == bars) { da = sb; ba = bars; }
              }
            }
#pragma unroll 1
            for (int kb = pre; kb < nst; kb++) { weights(); if (op && OEF) bulk_load_last(dst, a, 8192, bar); else bulk_load(dst, a, 8192, bar); a += 2048; advance(); }
          }
          if (type == IT_ATT) {
            if (early) depend(progress, 96);
            if (go) mbar_arrive(bGo);
            const uint8_t* src = g_kv + (size_t)(idx * 6 * NSEG + b * 4) * KV_BYTES;
#pragma unroll 1
            for (int u = 0; u < 6; u++) {
              acquire(20);
              bulk_load_last(dst, src, 20480, bar);
              src += u == 2 ? -3 * KV_V : 2 * KV_V;
              advance();
            }
          }
        }
      }
    } else if (warp == 10 && lane == 0) {
      for (int n = 0;; n++) {
        mbar_wait(bIF + 8 * (n & 3), (n >> 2) & 1);
        const int code = (int)lds32(slots + 4 * (n & 3));
        if (code < 0) break;
        const int type = (code >> 16) & 15, b = (code >> 8) & 255;
        mbar_wait(done + 8 * (n & 3), (n >> 2) & 1);
        if (type != IT_BQ) red_release(type == IT_Q ? g_sync + SY_Q : g_sync + b * 8 + 5 + type, 1);
        mbar_arrive(bIE + 8 * (n & 3));
      }
    }
  } else {
    asm volatile("setmaxnreg.inc.sync.aligned.u32 224;");
    const int g = lane >> 2, c = lane & 3;
    Ring r = {sb, bars, 0, 0};
#pragma unroll 1
    for (int n = 0;; n++) {
      mbar_wait(bIF + 8 * (n & 3), (n >> 2) & 1);
      const int code = __shfl_sync(~0u, (int)lds32(slots + 4 * (n & 3)), 0);
      if (code < 0) { TRACE(2); break; }
      const int type = (code >> 16) & 15, b = (code >> 8) & 255, idx = code & 255;
      ITEM(code & 0xfffff, 0);
      if (type == IT_ATT || type == IT_Q) {
        uint32_t q[48];
        if (type == IT_Q || b < QA_END) {
          float d[96] = {};
          reg_fence<96>(d);
          gemm_item<192>(r, d, 20, bGo, type == IT_Q ? 12 : -1);
#pragma unroll
          for (int i = 0; i < 48; i++) q[i] = pack2(d[2 * i], d[2 * i + 1]);
        } else {
#pragma unroll
          for (int u = 0; u < 2; u++) {
            const uint32_t base = r.wait() + threadIdx.x * 16;
#pragma unroll
            for (int i = 0; i < 6; i++) {
              const uint4 v = lds128(base + i * 4096);
              q[24 * u + 4 * i] = v.x; q[24 * u + 4 * i + 1] = v.y; q[24 * u + 4 * i + 2] = v.z; q[24 * u + 4 * i + 3] = v.w;
            }
            r.pop();
          }
        }
        if (type == IT_Q) {
          uint4* dst = g_q + ((b - QA_END) * 32 + idx) * 3072 + threadIdx.x;
#pragma unroll
          for (int i = 0; i < 12; i++) dst[i * 256] = make_uint4(q[4 * i], q[4 * i + 1], q[4 * i + 2], q[4 * i + 3]);
        } else if (warp < 4) {
          attn_a_warp<0>(r, q, b, idx);
        } else {
          attn_a_warp<1>(r, q, b, idx);
        }
      } else if (type == IT_FIN) {
        if (fin_items(b) == 4) fin_item<4>(r, scratch, b, idx);
        else if (fin_items(b) == 8) fin_item<2>(r, scratch, b, idx);
        else fin_item<1>(r, scratch, b, idx);
      } else {
        float d[160] = {};
        reg_fence<160>(d);
        const int width = type == IT_OP ? op_width(b) : bq_width(b), nst = type == IT_OP ? 192 / op_split(b) : 20;
        const int go_at = code >> 21 & 1 ? -1 : max(nst - 6, 0);
        if (width == 320) gemm_item<320>(r, d, nst, bGo, go_at);
        else if (width == 160 || BQ_80 == 16) gemm_item<160>(r, d, nst, bGo, go_at);
        else gemm_item<80>(r, d, nst, bGo, go_at);
        reg_fence<160>(d);
        if (type == IT_OP) {
          const int tiles = DM / width;
          uint2* dst = g_part + (((b * 16 + idx / tiles) * 16 + warp * 2) * 40 + idx % tiles * (width / 16)) * 32 + lane;
#pragma unroll
          for (int u = 0; u < 20; u++) {
            if (u % 5 == 0 && u * 16 >= width) break;
            dst[u * 32] = make_uint2(pack2(d[8 * u], d[8 * u + 1]), pack2(d[8 * u + 4], d[8 * u + 5]));
            dst[(40 + u) * 32] = make_uint2(pack2(d[8 * u + 2], d[8 * u + 3]), pack2(d[8 * u + 6], d[8 * u + 7]));
          }
        } else {
          const int row = b * 128 + warp * 16 + g;
          const int h0 = idx * (width / 20);
          const float sc = h0 < 32 ? 0.22360679775f * 1.44269504089f : 1.f;
          const bool lo = c < 2;
          uint32_t* da = g_bqkv + (h0 * 256 + (row >> 3)) * 96 + lane;
          uint32_t* db = da + 256 * 96 + (lo ? 2 : -2);
          uint32_t pad[2];
#pragma unroll
          for (int rr = 0; rr < 2; rr++) pad[rr] = !(c & 1) && (h0 >= 64 || (h0 >= 32 && (row & 1) && poly_group((row >> 3) + rr))) ? 0x00003f80u : 0u;
#pragma unroll
          for (int q = 0; q < 8; q++) {
            if (!(q & 1) && q * 40 >= width) break;
#pragma unroll
            for (int rr = 0; rr < 2; rr++) {
              uint32_t w[5];
#pragma unroll
              for (int i = 0; i < 5; i++) w[i] = pack2(d[20 * q + 4 * i + 2 * rr] * sc, d[20 * q + 4 * i + 2 * rr + 1] * sc);
              const int o = q * 2 * 256 * 96 + rr * 96;
              da[o] = w[0]; da[o + 32] = w[1]; da[o + 64] = lo ? w[2] : pad[rr];
              db[o] = lo ? w[3] : w[2]; db[o + 32] = lo ? w[4] : w[3]; db[o + 64] = lo ? pad[rr] : w[4];
            }
          }
        }
      }
      __syncwarp();
      if (lane == 0) mbar_arrive(done + 8 * (n & 3));
      if ((code >> 21 & 1) && threadIdx.x == 128) mbar_arrive(bGo);
      ITEM(code & 0xfffff, 1);
    }
  }
}

constexpr int AB_SMEM = 1024 + 98304 + 51200 + 4 * 16384 + 256;
#define AB_N 32
#define AB_WG 4
constexpr int AB_T = AB_WG * 128, AB_PASS = 8 / AB_WG;
__device__ __forceinline__ float ex2_poly(float t) {
  const uint32_t r = __float_as_uint(t) & 0xffff8000u;
  const float f = t - __uint_as_float(r);
  const float p = fmaf(fmaf(fmaf(-5.869912678e-38f, f, -1.700740250e-37f), f, -5.234869734e-37f), f, -7.522601252e-37f);
  uint32_t y;
  asm("mad.lo.u32 %0, %1, 256, %2;" : "=r"(y) : "r"(r), "r"(__float_as_uint(p)));
  return __uint_as_float(y);
}
__device__ __forceinline__ float sq2(uint32_t w) { const float a = bf_lo(w), b = bf_hi(w); return fmaf(a, a, b * b); }

__device__ __forceinline__ void attn_b_store(const float* o, int h, int row0, int lane) {
  const int g = lane >> 2, c = lane & 3;
  const float i0 = 1.f / __shfl_sync(~0u, o[8], (lane & ~3) | 2), i1 = 1.f / __shfl_sync(~0u, o[10], (lane & ~3) | 2);
#pragma unroll
  for (int jj = 0; jj < 3; jj++) {
    if (jj < 2 || c < 2) {
      const int col = h * 20 + 8 * jj + 2 * c;
      uint32_t* dst = g_of + (((row0 >> 7) * 10 + (col >> 6)) * 16 + (row0 >> 3 & 15)) * 256 + (col >> 3 & 7) * 32 + g * 4 + (col >> 1 & 3);
      dst[0] = pack2(o[4 * jj] * i0, o[4 * jj + 1] * i0);
      dst[256] = pack2(o[4 * jj + 2] * i1, o[4 * jj + 3] * i1);
    }
  }
}

__device__ __forceinline__ void attn_b_qk(float* s, uint32_t q0, uint32_t q1, uint32_t q2, uint32_t q3, uint32_t q4, uint32_t q5, uint32_t z0, uint32_t z1,
                                          uint64_t dk, uint64_t dk2) {
  wg_rs32_00(s, q0, q1, q2, q3, dk, 0);
  wg_rs32_00(s, q4, q5, z0, z1, dk2, 1);
}

struct AbParams { Weights next; uint32_t* done; uint32_t* out; };
__global__ void __launch_bounds__(AB_T + 32, 1) attn_b_kernel(const __grid_constant__ AbParams p) {
  extern __shared__ uint8_t smem_raw[];
  const uint32_t sb = (s2u(smem_raw) + 1023) & ~1023u, sK = sb, sV = sb + 98304, bars = sV + 51200 + 4 * 16384;
  const uint32_t bF = bars + 64, bW = bars + 72, bA = bars + 80, bE = bars + 128, smax = bars + 176;
  auto ring = [&](int i) { return i < 2 ? sK + 51200 + i * 16384 : sV + 51200 + (i - 2) * 16384; };
  const int warp = __shfl_sync(~0u, threadIdx.x >> 5, 0), lane = threadIdx.x & 31;
  const int h = blockIdx.x >> 2, quarter = blockIdx.x & 3;
  TRACE(0);
  pdl_launch();
  pdl_wait();
  if (blockIdx.x < NSLOT) for (int i = threadIdx.x; i < 512; i += AB_T + 32) reinterpret_cast<uint4*>(pool_at(blockIdx.x * 8192))[i] = make_uint4(0, 0, 0, 0);
  if (blockIdx.x == 31) for (int i = threadIdx.x; i < SY_N; i += AB_T + 32) g_sync[i] = 0;
  if (threadIdx.x == 0) {
    for (int i = 0; i < 22; i++) mbar_init(bars + 8 * i, i == 8 ? AB_T / 32 : i >= 16 ? 8 : 1);
    sts64(smax, 0, 0);
    fence_async();
    const uint8_t* gk = reinterpret_cast<const uint8_t*>(g_bqkv + (32 + h) * 256 * 96);
    const uint8_t* gv = reinterpret_cast<const uint8_t*>(g_bqkv + (64 + h) * 256 * 96);
    for (int i = 0; i < 8; i++) {
      mbar_expect(bars + 8 * i, 24576);
      bulk_load_last(sK + i * 12288, gk + i * 12288, 12288, bars + 8 * i);
      bulk_load_last(sV + i * 12288, gv + i * 12288, 12288, bars + 8 * i);
    }
  }
  __syncthreads();
  const int blk = quarter * 4 + (h >> 3), cg = h & 7;
  auto unsafe = [&]() { const float2 m = lds64f(smax); return !(m.x * m.y <= 10000.f); };
  if (warp == AB_T / 32) {
    auto load_w = [&]() {
      mbar_expect(bW, 102400);
      for (int i = 0; i < 4; i++) bulk_load((i < 2 ? sK : sV) + (i & 1) * 25600, g_wb + cg * 6400 + i * 1600, 25600, bW);
    };
    if (p.next.w[0] && lane == 0) {
      mbar_wait(bars + 56, 0);
      for (int i = 0; i < AB_PF; i++) { const uint32_t t0 = clk32(); while (clk32() - t0 < (i ? AB_PFD : AB_PF0)) __nanosleep(200); prefetch_weights(p.next, i); }
    }
    __syncwarp();
    mbar_wait(bF, 0);
    const bool redo = unsafe();
    if (!redo && lane == 0) load_w();
    __syncwarp();
    bar_sync(1, AB_T + 32);
    if (lane == 0) {
      ABT(!!p.out, 1);
      red_release(p.done + quarter * 32, 1);
      ABT(!!p.out, 2);
      if (redo) load_w();
      wait_count(p.done + quarter * 32, 32);
      fence_async_global();
      ABT(!!p.out, 3);
      for (int kb = 0; kb < 10; kb++) {
        const int i = kb < 6 ? kb : kb - 6;
        if (kb >= 6) mbar_wait(bE + 8 * i, 0);
        mbar_expect(bA + 8 * i, 16384);
        bulk_load(ring(i), g_of + (blk * 10 + kb) * 4096, 16384, bA + 8 * i);
      }
    }
    return;
  }
  float qmax = 0.f;
  constexpr int NT = SEQ / AB_N, PER = 256 / AB_N;
#pragma unroll 1
  for (int pass = 0; pass < AB_PASS; pass++) {
    const int row0 = quarter * 512 + ((warp >> 2) * AB_PASS + pass) * 64 + (warp & 3) * 16;
    const uint32_t* gq = g_bqkv + (h * 256 + (row0 >> 3)) * 96 + lane;
    const uint32_t q0 = gq[0], q1 = gq[96], q2 = gq[32], q3 = gq[128];
    uint32_t q4 = gq[64], q5 = gq[160];
    const uint32_t z0 = gq[64 + 3 - (lane & 3)], z1 = gq[160 + 3 - (lane & 3)];
    {
      float n0 = sq2(q0) + sq2(q2) + sq2(q4), n1 = sq2(q1) + sq2(q3) + sq2(q5);
      n0 += __shfl_xor_sync(~0u, n0, 1); n1 += __shfl_xor_sync(~0u, n1, 1);
      n0 += __shfl_xor_sync(~0u, n0, 2); n1 += __shfl_xor_sync(~0u, n1, 2);
      qmax = (n0 > qmax || n0 != n0) ? n0 : qmax;
      qmax = (n1 > qmax || n1 != n1) ? n1 : qmax;
    }
    if (pass == AB_PASS - 1) {
      float kmax = 0.f;
#pragma unroll
      for (int i = 0; i < SEQ / AB_T; i++) {
        const int key = threadIdx.x + AB_T * i;
        const uint32_t a = sK + (key >> 3) * 384 + (key & 7) * 16;
        const uint4 x = lds128(a), y = lds128(a + 128);
        const uint2 z = lds64(a + 256);
        const float n = ((sq2(x.x) + sq2(x.y)) + (sq2(x.z) + sq2(x.w))) + ((sq2(y.x) + sq2(y.y)) + (sq2(y.z) + sq2(y.w))) + (sq2(z.x) + sq2(z.y));
        kmax = (n > kmax || n != n) ? n : kmax;
      }
      const uint32_t kb = __reduce_max_sync(~0u, __float_as_uint(kmax) & 0x7fffffffu), qb = __reduce_max_sync(~0u, __float_as_uint(qmax) & 0x7fffffffu);
      if (lane < 2) asm volatile("red.shared.max.u32 [%0], %1;" :: "r"(smax + 4 * lane), "r"(lane ? kb : qb) : "memory");
      __syncwarp();
    }
    if ((lane & 3) == 2) { q4 = 0x43BCu; q5 = 0x43BCu; }
    float o[12];
    uint64_t dk = mkdesc(sK, 128, 384, 0), dk2 = mkdesc(sK + 256, 0, 384, 0), dv = mkdesc(sV, 384, 128, 0);
    float sa[AB_N / 2], sb2[AB_N / 2];
    uint32_t pa[AB_N / 4], pb[AB_N / 4];
    if (pass == 0) mbar_wait(bars, 0);
    wg_fence();
    attn_b_qk(sa, q0, q1, q2, q3, q4, q5, z0, z1, dk, dk2);
    wg_commit();
    attn_b_qk(sb2, q0, q1, q2, q3, q4, q5, z0, z1, dk + AB_N * 3, dk2 + AB_N * 3);
    wg_commit();
#pragma unroll 1
    for (int kt = 0; kt < NT; kt += 2) {
      const int nx = kt + 2 < NT ? kt + 2 : 0;
      if (pass == 0 && (nx & (PER - 1)) == 0) mbar_wait(bars + 8 * (nx / PER), 0);
      const uint64_t nk = dk + nx * (AB_N * 3), nk2 = dk2 + nx * (AB_N * 3);
      wg_wait<1>();
      if (pass == AB_PASS - 1 && kt == NT * 5 / 8 + 2 && lane == 0) mbar_arrive(bF);
      reg_fence<AB_N / 2>(sa);
#pragma unroll
      for (int i = 0; i < AB_N / 4; i++) pa[i] = pack2(ex2(sa[2 * i]), poly_group(i >> 1) ? ex2_poly(sa[2 * i + 1]) : ex2(sa[2 * i + 1]));
      wg_fence();
#pragma unroll
      for (int kk = 0; kk < AB_N / 16; kk++) wg_rs24_01(o, pa[4 * kk], pa[4 * kk + 1], pa[4 * kk + 2], pa[4 * kk + 3], dv + kk * 48, kk | kt);
      attn_b_qk(sa, q0, q1, q2, q3, q4, q5, z0, z1, nk, nk2);
      wg_commit();
      wg_wait<1>();
      reg_fence<AB_N / 2>(sb2);
#pragma unroll
      for (int i = 0; i < AB_N / 4; i++) pb[i] = pack2(ex2(sb2[2 * i]), poly_group((i >> 1) + AB_N / 8) ? ex2_poly(sb2[2 * i + 1]) : ex2(sb2[2 * i + 1]));
      wg_fence();
#pragma unroll
      for (int kk = 0; kk < AB_N / 16; kk++) wg_rs24_01(o, pb[4 * kk], pb[4 * kk + 1], pb[4 * kk + 2], pb[4 * kk + 3], dv + AB_N * 3 + kk * 48, 1);
      attn_b_qk(sb2, q0, q1, q2, q3, q4, q5, z0, z1, nk + AB_N * 3, nk2 + AB_N * 3);
      wg_commit();
      dv += AB_N * 6;
    }
    wg_wait<0>();
    reg_fence<12>(o); reg_fence<AB_N / 2>(sa); reg_fence<AB_N / 2>(sb2);
    attn_b_store(o, h, row0, lane);
  }
  mbar_wait(bF, 0);
  if (unsafe())
#pragma unroll 1
  for (int pass = 0; pass < AB_PASS; pass++) {
    const int row0 = quarter * 512 + ((warp >> 2) * AB_PASS + pass) * 64 + (warp & 3) * 16;
    const uint32_t* gq = g_bqkv + (h * 256 + (row0 >> 3)) * 96 + lane;
    const uint32_t q0 = gq[0], q1 = gq[96], q2 = gq[32], q3 = gq[128], q4 = gq[64], q5 = gq[160];
    float o[12];
#pragma unroll
    for (int i = 0; i < 12; i++) o[i] = 0.f;
    float m0 = -INFINITY, m1 = -INFINITY;
#pragma unroll 1
    for (int kt = 0; kt < 32; kt++) {
      float s[32];
      const uint64_t dk = mkdesc(sK + kt * 3072, 128, 384, 0), dk2 = mkdesc(sK + kt * 3072 + 256, 0, 384, 0);
      wg_fence();
      wg_rs64_00(s, q0, q1, q2, q3, dk, 0);
      wg_rs64_00(s, q4, q5, 0, 0, dk2, 1);
      wg_commit();
      wg_wait<0>();
      reg_fence<32>(s); reg_fence<12>(o);
      float n0 = m0, n1 = m1;
#pragma unroll
      for (int jj = 0; jj < 8; jj++) { n0 = fmaxf(n0, fmaxf(s[4 * jj], s[4 * jj + 1])); n1 = fmaxf(n1, fmaxf(s[4 * jj + 2], s[4 * jj + 3])); }
      n0 = fmaxf(n0, __shfl_xor_sync(~0u, n0, 1)); n0 = fmaxf(n0, __shfl_xor_sync(~0u, n0, 2));
      n1 = fmaxf(n1, __shfl_xor_sync(~0u, n1, 1)); n1 = fmaxf(n1, __shfl_xor_sync(~0u, n1, 2));
      const float r0 = ex2(m0 - n0), r1 = ex2(m1 - n1);
      m0 = n0; m1 = n1;
#pragma unroll
      for (int jj = 0; jj < 3; jj++) { o[4 * jj] *= r0; o[4 * jj + 1] *= r0; o[4 * jj + 2] *= r1; o[4 * jj + 3] *= r1; }
      uint32_t pp[16];
#pragma unroll
      for (int jj = 0; jj < 8; jj++) {
        pp[2 * jj] = pack2(ex2(s[4 * jj] - m0), ex2(s[4 * jj + 1] - m0));
        pp[2 * jj + 1] = pack2(ex2(s[4 * jj + 2] - m1), ex2(s[4 * jj + 3] - m1));
      }
      const uint64_t dv = mkdesc(sV + kt * 3072, 384, 128, 0);
      wg_fence();
#pragma unroll
      for (int kk = 0; kk < 4; kk++) wg_rs24_01(o, pp[4 * kk], pp[4 * kk + 1], pp[4 * kk + 2], pp[4 * kk + 3], dv + kk * 48, 1);
      wg_commit();
    }
    wg_wait<0>();
    reg_fence<12>(o);
    attn_b_store(o, h, row0, lane);
  }
  ABT(!!p.out, 0);
  bar_arrive(1, AB_T + 32);
  if (warp >= 8) return;
  const int g = lane >> 2, c = lane & 3;
  float d[40];
  float4* x = g_x + ((blk * 16 + warp * 2) * 40 + cg * 5) * 32 + lane;
#pragma unroll
  for (int i = 0; i < 10; i++) {
    const int r = i / 5, u = i % 5;
    const float4 t = x[(r * 40 + u) * 32];
    d[8 * u + 2 * r] = t.x; d[8 * u + 2 * r + 1] = t.y; d[8 * u + 4 + 2 * r] = t.z; d[8 * u + 5 + 2 * r] = t.w;
  }
  mbar_wait(bW, 0);
  reg_fence<40>(d);
  ABT(!!p.out, 4);
#pragma unroll 1
  for (int kb = 0; kb < 10; kb++) {
    const int i = kb < 6 ? kb : kb - 6;
    mbar_wait(bA + 8 * i, kb >= 6);
    const uint64_t da = mkdesc(ring(i) + (warp >> 2) * 8192, 128, 1024, 0), db = mkdesc(kb < 5 ? sK + kb * 10240 : sV + (kb - 5) * 10240, 1280, 128, 0);
    wg_fence();
#pragma unroll
    for (int kk = 0; kk < 4; kk++) wg_ss80_01(d, da + kk * 16, db + kk * 160, 1);
    wg_commit();
    if (kb > 0 && kb < 5) { wg_wait<1>(); if (lane == 0) mbar_arrive(bE + 8 * (kb - 1)); }
  }
  wg_wait<0>();
  reg_fence<40>(d);
  ABT(!!p.out, 5);
  if (p.out) {
    uint32_t* out = p.out + (blk * 128 + warp * 16 + g) * (DM / 2) + cg * 40 + c;
#pragma unroll
    for (int i = 0; i < 20; i++) out[(i & 1) * 8 * (DM / 2) + (i >> 1) * 4] = pack2(d[2 * i], d[2 * i + 1]);
  } else {
    float2* stat = g_stat + blk * 1024 + warp * 16 + g;
    float mean[2], rs[2];
#pragma unroll
    for (int r = 0; r < 2; r++) {
      float t = 0.f, q = 0.f;
#pragma unroll
      for (int i = 0; i < 10; i++) t += d[4 * i + 2 * r] + d[4 * i + 2 * r + 1];
      t += __shfl_xor_sync(~0u, t, 1); t += __shfl_xor_sync(~0u, t, 2);
      t *= 1.f / 80;
#pragma unroll
      for (int i = 0; i < 10; i++) { const float a = d[4 * i + 2 * r] - t, b = d[4 * i + 2 * r + 1] - t; q += a * a + b * b; }
      q += __shfl_xor_sync(~0u, q, 1); q += __shfl_xor_sync(~0u, q, 2);
      if (c == r) asm volatile("st.relaxed.gpu.global.v2.b32 [%0], {%1, %2};" :: "l"(stat + cg * 128 + r * 8), "r"(__float_as_uint(t)), "r"(nz(__float_as_uint(q))) : "memory");
    }
#pragma unroll
    for (int i = 0; i < 10; i++) {
      const int r = i / 5, u = i % 5;
      x[(r * 40 + u) * 32] = make_float4(d[8 * u + 2 * r], d[8 * u + 2 * r + 1], d[8 * u + 4 + 2 * r], d[8 * u + 5 + 2 * r]);
    }
    ABT(0, 6);
    uint2 e[4];
    int n = 0;
    do {
#pragma unroll
      for (int i = 0; i < 4; i++)
        asm volatile("ld.relaxed.gpu.global.v2.b32 {%0, %1}, [%2];" : "=r"(e[i].x), "=r"(e[i].y) : "l"(stat + (2 * c + (i & 1)) * 128 + (i >> 1) * 8) : "memory");
      spin_guard(n);
    } while (__any_sync(~0u, min(min(e[0].y, e[1].y), min(e[2].y, e[3].y)) == 0));
#pragma unroll
    for (int r = 0; r < 2; r++) {
      const float m0 = __uint_as_float(e[2 * r].x), m1 = __uint_as_float(e[2 * r + 1].x);
      float t = m0 + m1;
      t += __shfl_xor_sync(~0u, t, 1); t += __shfl_xor_sync(~0u, t, 2);
      t *= 0.125f;
      float q = __uint_as_float(e[2 * r].y) + __uint_as_float(e[2 * r + 1].y) + 80.f * ((m0 - t) * (m0 - t) + (m1 - t) * (m1 - t));
      q += __shfl_xor_sync(~0u, q, 1); q += __shfl_xor_sync(~0u, q, 2);
      mean[r] = t; rs[r] = rsqrtf(q * (1.f / DM) + 1e-5f);
    }
    ABT(0, 7);
    uint32_t w[2][5][2];
#pragma unroll
    for (int i = 0; i < 20; i++) w[i & 1][i >> 2][i >> 1 & 1] = pack2((d[2 * i] - mean[i & 1]) * rs[i & 1], (d[2 * i + 1] - mean[i & 1]) * rs[i & 1]);
    ln_store(w, blk * 8 + warp, cg * 5);
  }
  ABT(!!p.out, 8);
  TRACE(2);
}

typedef CUresult (*EncodeFn)(CUtensorMap*, CUtensorMapDataType, cuuint32_t, void*, const cuuint64_t*, const cuuint64_t*,
                             const cuuint32_t*, const cuuint32_t*, CUtensorMapInterleave, CUtensorMapSwizzle,
                             CUtensorMapL2promotion, CUtensorMapFloatOOBfill);

void make_map(EncodeFn enc, CUtensorMap* m, const void* ptr, int cols, int rows, int nb) {
  const cuuint64_t dims[3] = {(cuuint64_t)(nb ? 64 : cols), (cuuint64_t)rows, (cuuint64_t)cols / 64};
  const cuuint64_t strides[2] = {(cuuint64_t)cols * 2, 128};
  const cuuint32_t box[3] = {64, 32, (cuuint32_t)nb}, es[3] = {1, 1, 1};
  enc(m, CU_TENSOR_MAP_DATA_TYPE_BFLOAT16, nb ? 3 : 2, const_cast<void*>(ptr), dims, strides, box, es, CU_TENSOR_MAP_INTERLEAVE_NONE,
      CU_TENSOR_MAP_SWIZZLE_128B, CU_TENSOR_MAP_L2_PROMOTION_L2_128B, CU_TENSOR_MAP_FLOAT_OOB_FILL_NONE);
}
template <class... KA, class... A>
void launch(void (*kern)(KA...), int grid, int block, int smem, int cluster, bool pdl, A... args) {
  cudaFuncSetAttribute(kern, cudaFuncAttributeMaxDynamicSharedMemorySize, smem);
  cudaLaunchConfig_t cfg = {};
  cfg.gridDim = dim3(grid); cfg.blockDim = dim3(block); cfg.dynamicSmemBytes = smem; cfg.stream = cudaStreamPerThread;
  cudaLaunchAttribute at[2];
  int n = 0;
  if (cluster > 1) { at[n].id = cudaLaunchAttributeClusterDimension; at[n].val.clusterDim.x = cluster; at[n].val.clusterDim.y = 1; at[n].val.clusterDim.z = 1; n++; }
  if (pdl) { at[n].id = cudaLaunchAttributeProgrammaticStreamSerialization; at[n].val.programmaticStreamSerializationAllowed = 1; n++; }
  cfg.attrs = at; cfg.numAttrs = n;
  cudaLaunchKernelEx(&cfg, kern, args...);
}
template <class T> void* sym(T& s) { void* p = nullptr; cudaGetSymbolAddress(&p, s); return p; }

}

#define MODE(b) 0
extern "C" void kernel_launch(void* const* d_in, const int* in_sizes, int n_in, void* d_out, int out_size) {
  const __nv_bfloat16* x = (const __nv_bfloat16*)d_in[0];
  void* fn = nullptr; cudaDriverEntryPointQueryResult qr;
  cudaGetDriverEntryPoint("cuTensorMapEncodeTiled", &fn, cudaEnableDefault, &qr);
  EncodeFn enc = (EncodeFn)fn;

  ChainParams ch = {};
  PostParams op = {};
  for (int i = 0; i < 3; i++) {
    const cuuint64_t dims[3] = {HD, 128, 5}, strides[2] = {HD * 2, HD * 256};
    const cuuint32_t box[3] = {64, 128, 5}, es[3] = {1, 1, 1};
    enc(i == 0 ? &ch.wq : i == 1 ? &ch.wk : &ch.wv, CU_TENSOR_MAP_DATA_TYPE_BFLOAT16, 3, d_in[2 + i], dims, strides, box, es, CU_TENSOR_MAP_INTERLEAVE_NONE,
        CU_TENSOR_MAP_SWIZZLE_128B, W_PROMO, CU_TENSOR_MAP_FLOAT_OOB_FILL_NONE);
  }
  {
    const cuuint64_t dims[3] = {DM, HD, 7}, strides[2] = {DM * 2, 64};
    const cuuint32_t box[3] = {32, 64, 7}, es[3] = {1, 1, 1};
    enc(&ch.wo, CU_TENSOR_MAP_DATA_TYPE_BFLOAT16, 3, d_in[5], dims, strides, box, es, CU_TENSOR_MAP_INTERLEAVE_NONE,
        CU_TENSOR_MAP_SWIZZLE_64B, CU_TENSOR_MAP_L2_PROMOTION_L2_128B, CU_TENSOR_MAP_FLOAT_OOB_FILL_NONE);
  }
  ch.mem0 = (const __nv_bfloat16*)d_in[1];
  ch.pool = (uint8_t*)(((uintptr_t)sym(g_pool) + 8191) & ~(uintptr_t)8191); ch.kv = (uint8_t*)sym(g_kv); ch.xc = (const uint32_t*)sym(g_xc); ch.sync = (uint32_t*)sym(g_sync);
  ch.d1 = 0; ch.d1b = 0; ch.d2 = 0; ch.d2b = 0;
  make_map(enc, &op.wq, d_in[2], HD, DM, 3);
  make_map(enc, &op.wo, d_in[5], DM, HD, 5); make_map(enc, &op.wo2, d_in[5], DM, HD, 0);
  make_map(enc, &op.wb, d_in[8], 1920, DM, 5); make_map(enc, &op.wb2, d_in[8], 1920, DM, 0);
  op.gap = 17; op.share = 20; op.look = 14; op.gap2 = 0; op.pol = 0;

  const Weights wa = {{(const uint8_t*)d_in[3], (const uint8_t*)d_in[4], (const uint8_t*)d_in[2], (const uint8_t*)d_in[5]}}, none = {};
  launch(first_kernel, 132, 256, 128 * 1024, 1, false, x, (const uint4*)d_in[9], wa);
  for (int layer = 0; layer < 2; layer++) {
    ch.layer = ch.d2b = op.layer = layer;
    launch(chain_kernel, 96, 256, CH_SMEM, 3, true, ch);
    launch(post_kernel, MODE(3) ? 36 : 132, 384, OP_SMEM, 1, !MODE(1), op);
    const AbParams ab = {layer == 0 ? wa : none, (uint32_t*)sym(g_bo) + layer * 128, layer == 0 ? nullptr : (uint32_t*)d_out};
    launch(attn_b_kernel, 128, AB_T + 32, AB_SMEM, 1, true, ab);
  }
}
```

```cpp
#include <cuda_runtime.h>
#include <cuda_bf16.h>
#include <cuda.h>
#include <stdint.h>

namespace {

constexpr int SEQ = 2048, DM = 640, HD = 6144, NSEG = 64;
constexpr int SPIN_LIMIT = 1 << 20;

__device__ __align__(128) float4 g_x[SEQ * DM / 4];
__device__ __align__(128) uint32_t g_of[SEQ * DM / 2];
__device__ __align__(128) uint4 g_wb[DM * DM / 8];
__device__ __align__(16) float2 g_stat[16 * 8 * 128];
__device__ uint32_t g_bo[8 * 32];
__device__ __align__(128) uint4 g_q[SEQ * HD / 8];
__device__ __align__(128) uint32_t g_o[SEQ * HD / 2];
constexpr int KV_BYTES = 5120, KV_M = 4096, KV_V = NSEG * KV_BYTES;
__device__ __align__(128) uint8_t g_kv[96 * 2 * NSEG * KV_BYTES];
__device__ __align__(128) uint32_t g_xc[SEQ * DM / 2];
#define OP_B4 0
#define OP_B8 10
#define OP_B16 15
#define QA_END 12
__host__ __device__ constexpr int op_split(int b) { return b < OP_B4 ? 2 : b < OP_B8 ? 4 : b < OP_B16 ? 8 : 16; }
__host__ __device__ constexpr int fin_items(int b) { return b < OP_B8 ? 4 : op_split(b); }
#define AB_PF 2
#define AB_PF0 30000
#define AB_PFD 7000
#define W_PROMO CU_TENSOR_MAP_L2_PROMOTION_L2_128B
#define OEF 0
#define BQ_HOLD 12
#define WEF 1
#define FK_PF 1
#define BQ_160 10
#define BQ_80 16
#define OP_160 16
__host__ __device__ constexpr int op_width(int b) { return b < OP_160 ? 320 : 160; }
__host__ __device__ constexpr int bq_width(int b) { return b < BQ_160 ? 320 : b < BQ_80 ? 160 : 80; }
__device__ __align__(128) uint2 g_part[16 * 16 * 16 * 40 * 32];
__device__ __align__(128) uint32_t g_xn[SEQ * DM / 2];
constexpr int SY_Q = 128, SY_T = 160, SY_QC = 192, SY_N = 193;
__device__ __align__(16) uint32_t g_sync[SY_N];
constexpr int NSLOT = 92;
__device__ uint32_t g_pool[(NSLOT + 2) * 2048];
__device__ int g_smpart[256], g_orient[NSLOT];
__device__ uint32_t g_smclk[256], g_smuse[256];
__device__ uint32_t g_bqkv[3 * 32 * 256 * 96];

#define ABT(L, i)
#define MODE_D(b) 0
#define DELAY(d)
#define XT(i)
#define MISS(k, n)
#define PRO(i)
#define TRACE(w)
#define ITEM(code, w)
#define TR(i, v)
#define TM(i)
#define TM1(i)
#define TMD(i, dep)
#define TMV(i, at, v)

__device__ __forceinline__ uint32_t gtime() { uint32_t c; asm volatile("mov.u32 %0, %%globaltimer_lo;" : "=r"(c) :: "memory"); return c; }
__device__ __forceinline__ uint32_t clk32() { uint32_t c; asm volatile("mov.u32 %0, %%clock;" : "=r"(c) :: "memory"); return c; }
__device__ __forceinline__ uint32_t s2u(const void* p) { return (uint32_t)__cvta_generic_to_shared(p); }
__device__ __forceinline__ uint32_t pack2(float a, float b) {
  uint32_t r; asm("cvt.rn.bf16x2.f32 %0, %1, %2;" : "=r"(r) : "f"(b), "f"(a)); return r; }
__device__ __forceinline__ float bf_lo(uint32_t w) { return __uint_as_float(w << 16); }
__device__ __forceinline__ float bf_hi(uint32_t w) { return __uint_as_float(w & 0xffff0000u); }
__device__ __forceinline__ float ex2(float x) { float y; asm("ex2.approx.ftz.f32 %0, %1;" : "=f"(y) : "f"(x)); return y; }

__device__ __forceinline__ void mbar_init(uint32_t bar, uint32_t n) {
  asm volatile("mbarrier.init.shared::cta.b64 [%0], %1;" :: "r"(bar), "r"(n) : "memory"); }
__device__ __forceinline__ void mbar_expect(uint32_t bar, uint32_t bytes) {
  asm volatile("mbarrier.arrive.expect_tx.shared::cta.b64 _, [%0], %1;" :: "r"(bar), "r"(bytes) : "memory"); }
__device__ __forceinline__ void mbar_arrive(uint32_t bar) {
  asm volatile("mbarrier.arrive.shared::cta.b64 _, [%0];" :: "r"(bar) : "memory"); }
__device__ __forceinline__ void mbar_wait(uint32_t bar, uint32_t ph) {
  asm volatile("{.reg .pred p; .reg .u32 n; mov.u32 n, 0;\n"
               "W: mbarrier.try_wait.parity.shared::cta.b64 p, [%0], %1; @p bra D;\n"
               "add.u32 n, n, 1; setp.gt.u32 p, n, %2; @p trap; bra W;\n"
               "D: }" :: "r"(bar), "r"(ph), "n"(SPIN_LIMIT) : "memory");
}
__device__ __forceinline__ void mbar_wait_cluster(uint32_t bar, uint32_t ph) {
  asm volatile("{.reg .pred p; .reg .u32 n; mov.u32 n, 0;\n"
               "W: mbarrier.try_wait.parity.acquire.cluster.shared::cta.b64 p, [%0], %1; @p bra D;\n"
               "add.u32 n, n, 1; setp.gt.u32 p, n, %2; @p trap; bra W;\n"
               "D: }" :: "r"(bar), "r"(ph), "n"(SPIN_LIMIT) : "memory");
}
__device__ __forceinline__ void spin_guard(int& n) {
  asm volatile("{.reg .pred p; add.s32 %0, %0, 1; setp.gt.s32 p, %0, %1; @p trap;}" : "+r"(n) : "n"(SPIN_LIMIT));
}
__device__ __forceinline__ void pdl_wait() { asm volatile("griddepcontrol.wait;" ::: "memory"); TRACE(1); }
__device__ __forceinline__ void pdl_launch() { asm volatile("griddepcontrol.launch_dependents;" ::: "memory"); }
__device__ __forceinline__ uint32_t ld_acquire(const uint32_t* p) { uint32_t v; asm volatile("ld.acquire.gpu.global.u32 %0, [%1];" : "=r"(v) : "l"(p) : "memory"); return v; }
__device__ __forceinline__ void red_release(uint32_t* p, uint32_t v) { asm volatile("red.release.gpu.global.add.u32 [%0], %1;" :: "l"(p), "r"(v) : "memory"); }
__device__ __forceinline__ void red_relaxed(uint32_t* p, uint32_t v) { asm volatile("red.relaxed.gpu.global.add.u32 [%0], %1;" :: "l"(p), "r"(v) : "memory"); }
__device__ __forceinline__ void fence_async_global() { asm volatile("fence.proxy.async.global;" ::: "memory"); }
__device__ __forceinline__ void fence_async() { asm volatile("fence.proxy.async.shared::cta;" ::: "memory"); }
__device__ __forceinline__ void bar_sync(int id, int n) { asm volatile("bar.sync %0, %1;" :: "r"(id), "r"(n) : "memory"); }
__device__ __forceinline__ void bar_arrive(int id, int n) { asm volatile("bar.arrive %0, %1;" :: "r"(id), "r"(n) : "memory"); }
__device__ __forceinline__ void tma_load(uint32_t dst, const CUtensorMap* m, int c0, int c1, uint32_t bar) {
  asm volatile("cp.async.bulk.tensor.2d.shared::cluster.global.mbarrier::complete_tx::bytes [%0], [%1, {%3, %4}], [%2];"
               :: "r"(dst), "l"(m), "r"(bar), "r"(c0), "r"(c1) : "memory"); }
template <bool STREAM = false>
__device__ __forceinline__ void tma_load3(uint32_t dst, const CUtensorMap* m, int c0, int c1, uint32_t bar) {
  if (STREAM)
    asm volatile("{.reg .b64 pol; createpolicy.fractional.L2::evict_first.b64 pol, 1.0;\n"
                 "cp.async.bulk.tensor.3d.shared::cluster.global.mbarrier::complete_tx::bytes.L2::cache_hint [%0], [%1, {%3, %4, 0}], [%2], pol;}"
                 :: "r"(dst), "l"(m), "r"(bar), "r"(c0), "r"(c1) : "memory");
  else
  asm volatile("cp.async.bulk.tensor.3d.shared::cluster.global.mbarrier::complete_tx::bytes [%0], [%1, {%3, %4, 0}], [%2];"
               :: "r"(dst), "l"(m), "r"(bar), "r"(c0), "r"(c1) : "memory"); }
__device__ __forceinline__ void tma_load3z(uint32_t dst, const CUtensorMap* m, int c1, int c2, uint32_t bar) {
  asm volatile("cp.async.bulk.tensor.3d.shared::cluster.global.mbarrier::complete_tx::bytes [%0], [%1, {0, %3, %4}], [%2];"
               :: "r"(dst), "l"(m), "r"(bar), "r"(c1), "r"(c2) : "memory"); }
__device__ __forceinline__ void tma_store(const CUtensorMap* m, uint32_t src, int c0, int c1) {
  asm volatile("cp.async.bulk.tensor.2d.global.shared::cta.bulk_group [%0, {%2, %3}], [%1];"
               :: "l"(m), "r"(src), "r"(c0), "r"(c1) : "memory"); }
__device__ __forceinline__ void tma_store_stream(const CUtensorMap* m, uint32_t src, int c0, int c1) {
  asm volatile("{.reg .b64 pol; createpolicy.fractional.L2::evict_first.b64 pol, 1.0;\n"
               "cp.async.bulk.tensor.2d.global.shared::cta.bulk_group.L2::cache_hint [%0, {%2, %3}], [%1], pol;}"
               :: "l"(m), "r"(src), "r"(c0), "r"(c1) : "memory"); }
__device__ __forceinline__ void bulk_load(uint32_t dst, const void* src, uint32_t bytes, uint32_t bar) {
  asm volatile("cp.async.bulk.shared::cluster.global.mbarrier::complete_tx::bytes [%0], [%1], %2, [%3];"
               :: "r"(dst), "l"(src), "r"(bytes), "r"(bar) : "memory"); }
__device__ __forceinline__ void bulk_load_last(uint32_t dst, const void* src, uint32_t bytes, uint32_t bar) {
  asm volatile("{.reg .b64 pol; createpolicy.fractional.L2::evict_first.b64 pol, 1.0;\n"
               "cp.async.bulk.shared::cluster.global.mbarrier::complete_tx::bytes.L2::cache_hint [%0], [%1], %2, [%3], pol;}"
               :: "r"(dst), "l"(src), "r"(bytes), "r"(bar) : "memory"); }
__device__ __forceinline__ void tma_load_last(uint32_t dst, const CUtensorMap* m, int c0, int c1, uint32_t bar) {
  asm volatile("{.reg .b64 pol; createpolicy.fractional.L2::evict_first.b64 pol, 1.0;\n"
               "cp.async.bulk.tensor.2d.shared::cluster.global.mbarrier::complete_tx::bytes.L2::cache_hint [%0], [%1, {%3, %4}], [%2], pol;}"
               :: "r"(dst), "l"(m), "r"(bar), "r"(c0), "r"(c1) : "memory"); }
__device__ __forceinline__ void bulk_send(uint32_t dst, uint32_t src, uint32_t bytes, uint32_t bar) {
  asm volatile("cp.async.bulk.shared::cluster.shared::cta.mbarrier::complete_tx::bytes [%0], [%1], %2, [%3];"
               :: "r"(dst), "r"(src), "r"(bytes), "r"(bar) : "memory"); }
__device__ __forceinline__ void bulk_store(void* dst, uint32_t src, uint32_t bytes) {
  asm volatile("cp.async.bulk.global.shared::cta.bulk_group [%0], [%1], %2;" :: "l"(dst), "r"(src), "r"(bytes) : "memory"); }
__device__ __forceinline__ void bulk_commit() { asm volatile("cp.async.bulk.commit_group;" ::: "memory"); }
template <int N> __device__ __forceinline__ void bulk_wait_read() { asm volatile("cp.async.bulk.wait_group.read %0;" :: "n"(N) : "memory"); }
template <int N> __device__ __forceinline__ void bulk_wait() { asm volatile("cp.async.bulk.wait_group %0;" :: "n"(N) : "memory"); }

__device__ __forceinline__ uint64_t mkdesc(uint32_t addr, uint32_t lbo, uint32_t sbo, uint32_t sw) {
  return (uint64_t)((addr & 0x3FFFF) >> 4) | ((uint64_t)(lbo >> 4) << 16) | ((uint64_t)(sbo >> 4) << 32) | ((uint64_t)sw << 62); }
__device__ __forceinline__ void wg_fence() { asm volatile("wgmma.fence.sync.aligned;" ::: "memory"); }
__device__ __forceinline__ void wg_commit() { asm volatile("wgmma.commit_group.sync.aligned;" ::: "memory"); }
template <int N> __device__ __forceinline__ void wg_wait() { asm volatile("wgmma.wait_group.sync.aligned %0;" :: "n"(N) : "memory"); }
template <int N> __device__ __forceinline__ void reg_fence(float* d) {
#pragma unroll
  for (int i = 0; i < N; i++) asm volatile("" : "+f"(d[i]) :: "memory");
}

__device__ __forceinline__ void mma16(float* d, uint32_t a0, uint32_t a1, uint32_t a2, uint32_t a3, uint32_t b0, uint32_t b1) {
  asm volatile("mma.sync.aligned.m16n8k16.row.col.f32.bf16.bf16.f32 {%0,%1,%2,%3},{%4,%5,%6,%7},{%8,%9},{%0,%1,%2,%3};"
               : "+f"(d[0]), "+f"(d[1]), "+f"(d[2]), "+f"(d[3]) : "r"(a0), "r"(a1), "r"(a2), "r"(a3), "r"(b0), "r"(b1)); }
__device__ __forceinline__ void mma8(float* d, uint32_t a0, uint32_t a1, uint32_t b0) {
  asm volatile("mma.sync.aligned.m16n8k8.row.col.f32.bf16.bf16.f32 {%0,%1,%2,%3},{%4,%5},{%6},{%0,%1,%2,%3};"
               : "+f"(d[0]), "+f"(d[1]), "+f"(d[2]), "+f"(d[3]) : "r"(a0), "r"(a1), "r"(b0)); }
__device__ __forceinline__ void ldsm4(uint32_t* r, uint32_t a) {
  asm volatile("ldmatrix.sync.aligned.m8n8.x4.shared.b16 {%0,%1,%2,%3},[%4];" : "=r"(r[0]), "=r"(r[1]), "=r"(r[2]), "=r"(r[3]) : "r"(a) : "memory"); }
__device__ __forceinline__ void ldsm4t(uint32_t* r, uint32_t a) {
  asm volatile("ldmatrix.sync.aligned.m8n8.x4.trans.shared.b16 {%0,%1,%2,%3},[%4];" : "=r"(r[0]), "=r"(r[1]), "=r"(r[2]), "=r"(r[3]) : "r"(a) : "memory"); }
__device__ __forceinline__ void ldsm2(uint32_t* r, uint32_t a) {
  asm volatile("ldmatrix.sync.aligned.m8n8.x2.shared.b16 {%0,%1},[%2];" : "=r"(r[0]), "=r"(r[1]) : "r"(a) : "memory"); }
__device__ __forceinline__ void stsm4(uint32_t a, uint32_t r0, uint32_t r1, uint32_t r2, uint32_t r3) {
  asm volatile("stmatrix.sync.aligned.m8n8.x4.shared.b16 [%0], {%1,%2,%3,%4};" :: "r"(a), "r"(r0), "r"(r1), "r"(r2), "r"(r3) : "memory"); }
__device__ __forceinline__ void stsm2t(uint32_t a, uint32_t r0, uint32_t r1) {
  asm volatile("stmatrix.sync.aligned.m8n8.x2.trans.shared.b16 [%0], {%1,%2};" :: "r"(a), "r"(r0), "r"(r1) : "memory"); }
__device__ __forceinline__ void stsm4t(uint32_t a, uint32_t r0, uint32_t r1, uint32_t r2, uint32_t r3) {
  asm volatile("stmatrix.sync.aligned.m8n8.x4.trans.shared.b16 [%0], {%1,%2,%3,%4};" :: "r"(a), "r"(r0), "r"(r1), "r"(r2), "r"(r3) : "memory"); }
__device__ __forceinline__ void st_async128(uint32_t a, uint4 v, uint32_t bar) {
  asm volatile("st.async.shared::cluster.mbarrier::complete_tx::bytes.v4.b32 [%0], {%1,%2,%3,%4}, [%5];" :: "r"(a), "r"(v.x), "r"(v.y), "r"(v.z), "r"(v.w), "r"(bar) : "memory"); }
__device__ __forceinline__ void sts32(uint32_t a, uint32_t v) { asm volatile("st.shared.b32 [%0], %1;" :: "r"(a), "r"(v) : "memory"); }
__device__ __forceinline__ void sts64f(uint32_t a, float x, float y) { asm volatile("st.shared.v2.f32 [%0], {%1,%2};" :: "r"(a), "f"(x), "f"(y) : "memory"); }
__device__ __forceinline__ void sts128(uint32_t a, uint4 v) {
  asm volatile("st.shared.v4.b32 [%0], {%1,%2,%3,%4};" :: "r"(a), "r"(v.x), "r"(v.y), "r"(v.z), "r"(v.w) : "memory"); }
__device__ __forceinline__ void sts128f(uint32_t a, float x, float y, float z, float w) {
  asm volatile("st.shared.v4.f32 [%0], {%1,%2,%3,%4};" :: "r"(a), "f"(x), "f"(y), "f"(z), "f"(w) : "memory"); }
__device__ __forceinline__ float lds32f(uint32_t a) { float v; asm volatile("ld.shared.f32 %0, [%1];" : "=f"(v) : "r"(a) : "memory"); return v; }
__device__ __forceinline__ float2 lds64f(uint32_t a) { float2 v; asm volatile("ld.shared.v2.f32 {%0,%1}, [%2];" : "=f"(v.x), "=f"(v.y) : "r"(a) : "memory"); return v; }
__device__ __forceinline__ float4 lds128f(uint32_t a) {
  float4 v; asm volatile("ld.shared.v4.f32 {%0,%1,%2,%3}, [%4];" : "=f"(v.x), "=f"(v.y), "=f"(v.z), "=f"(v.w) : "r"(a) : "memory"); return v; }
__device__ __forceinline__ uint4 lds128(uint32_t a) {
  uint4 v; asm volatile("ld.shared.v4.b32 {%0,%1,%2,%3}, [%4];" : "=r"(v.x), "=r"(v.y), "=r"(v.z), "=r"(v.w) : "r"(a) : "memory"); return v; }
__device__ __forceinline__ uint4 ldg_strong128(const void* p) {
  uint4 v; asm volatile("ld.relaxed.gpu.global.v4.u32 {%0,%1,%2,%3}, [%4];" : "=r"(v.x), "=r"(v.y), "=r"(v.z), "=r"(v.w) : "l"(p) : "memory"); return v; }
__device__ __forceinline__ void stg_strong32(void* p, uint32_t v) { asm volatile("st.relaxed.gpu.global.u32 [%0], %1;" :: "l"(p), "r"(v) : "memory"); }
__device__ __forceinline__ void stg_strong16(void* p, uint32_t v) { asm volatile("st.relaxed.gpu.global.u16 [%0], %1;" :: "l"(p), "h"((uint16_t)v) : "memory"); }
__device__ __forceinline__ void stg_strong128(void* p, uint4 v) {
  asm volatile("st.relaxed.gpu.global.v4.u32 [%0], {%1,%2,%3,%4};" :: "l"(p), "r"(v.x), "r"(v.y), "r"(v.z), "r"(v.w) : "memory"); }
__device__ __forceinline__ uint32_t mapa(uint32_t a, uint32_t r) {
  uint32_t o; asm("mapa.shared::cluster.u32 %0, %1, %2;" : "=r"(o) : "r"(a), "r"(r)); return o; }
__device__ __forceinline__ void st_async2f(uint32_t a, float x, float y, uint32_t bar) {
  asm volatile("st.async.shared::cluster.mbarrier::complete_tx::bytes.v2.f32 [%0], {%1,%2}, [%3];" :: "r"(a), "f"(x), "f"(y), "r"(bar) : "memory"); }
__device__ __forceinline__ void st_async32(uint32_t a, uint32_t x, uint32_t bar) {
  asm volatile("st.async.shared::cluster.mbarrier::complete_tx::bytes.b32 [%0], %1, [%2];" :: "r"(a), "r"(x), "r"(bar) : "memory"); }
__device__ __forceinline__ uint32_t lds32(uint32_t a) { uint32_t v; asm volatile("ld.shared.b32 %0, [%1];" : "=r"(v) : "r"(a) : "memory"); return v; }
__device__ __forceinline__ void st_async64(uint32_t a, uint32_t x, uint32_t y, uint32_t bar) {
  asm volatile("st.async.shared::cluster.mbarrier::complete_tx::bytes.v2.b32 [%0], {%1,%2}, [%3];" :: "r"(a), "r"(x), "r"(y), "r"(bar) : "memory"); }
__device__ __forceinline__ uint2 lds64(uint32_t a) { uint2 v; asm volatile("ld.shared.v2.b32 {%0,%1}, [%2];" : "=r"(v.x), "=r"(v.y) : "r"(a) : "memory"); return v; }
__device__ __forceinline__ void sts64(uint32_t a, uint32_t x, uint32_t y) { asm volatile("st.shared.v2.b32 [%0], {%1,%2};" :: "r"(a), "r"(x), "r"(y) : "memory"); }
__device__ __forceinline__ uint32_t ldg_strong32(const void* p) { uint32_t v; asm volatile("ld.relaxed.gpu.global.u32 %0, [%1];" : "=r"(v) : "l"(p) : "memory"); return v; }
__device__ __forceinline__ uint32_t transpose8(uint32_t x) { uint32_t r; asm volatile("movmatrix.sync.aligned.m8n8.trans.b16 %0, %1;" : "=r"(r) : "r"(x)); return r; }
__device__ __forceinline__ uint32_t hadd2(uint32_t a, uint32_t b) { uint32_t r; asm("add.rn.bf16x2 %0, %1, %2;" : "=r"(r) : "r"(a), "r"(b)); return r; }
__device__ __forceinline__ uint32_t min4(uint4 v) { return min(__vimin3_u32(v.x, v.y, v.z), v.w); }

__device__ __forceinline__ void wg_ss192_01(float* d, uint64_t da, uint64_t db, int sd) {
  asm volatile("{.reg .pred p; setp.ne.b32 p, %98, 0;\n"
    "wgmma.mma_async.sync.aligned.m64n192k16.f32.bf16.bf16 {%0,%1,%2,%3,%4,%5,%6,%7,%8,%9,%10,%11,%12,%13,%14,%15,%16,%17,%18,%19,%20,%21,%22,%23,%24,%25,%26,%27,%28,%29,%30,%31,%32,%33,%34,%35,%36,%37,%38,%39,%40,%41,%42,%43,%44,%45,%46,%47,%48,%49,%50,%51,%52,%53,%54,%55,%56,%57,%58,%59,%60,%61,%62,%63,%64,%65,%66,%67,%68,%69,%70,%71,%72,%73,%74,%75,%76,%77,%78,%79,%80,%81,%82,%83,%84,%85,%86,%87,%88,%89,%90,%91,%92,%93,%94,%95}, %96, %97, p, 1, 1, 0, 1;}"
    : "+f"(d[0]),"+f"(d[1]),"+f"(d[2]),"+f"(d[3]),"+f"(d[4]),"+f"(d[5]),"+f"(d[6]),"+f"(d[7]),"+f"(d[8]),"+f"(d[9]),"+f"(d[10]),"+f"(d[11]),"+f"(d[12]),"+f"(d[13]),"+f"(d[14]),"+f"(d[15]),"+f"(d[16]),"+f"(d[17]),"+f"(d[18]),"+f"(d[19]),"+f"(d[20]),"+f"(d[21]),"+f"(d[22]),"+f"(d[23]),"+f"(d[24]),"+f"(d[25]),"+f"(d[26]),"+f"(d[27]),"+f"(d[28]),"+f"(d[29]),"+f"(d[30]),"+f"(d[31]),"+f"(d[32]),"+f"(d[33]),"+f"(d[34]),"+f"(d[35]),"+f"(d[36]),"+f"(d[37]),"+f"(d[38]),"+f"(d[39]),"+f"(d[40]),"+f"(d[41]),"+f"(d[42]),"+f"(d[43]),"+f"(d[44]),"+f"(d[45]),"+f"(d[46]),"+f"(d[47]),"+f"(d[48]),"+f"(d[49]),"+f"(d[50]),"+f"(d[51]),"+f"(d[52]),"+f"(d[53]),"+f"(d[54]),"+f"(d[55]),"+f"(d[56]),"+f"(d[57]),"+f"(d[58]),"+f"(d[59]),"+f"(d[60]),"+f"(d[61]),"+f"(d[62]),"+f"(d[63]),"+f"(d[64]),"+f"(d[65]),"+f"(d[66]),"+f"(d[67]),"+f"(d[68]),"+f"(d[69]),"+f"(d[70]),"+f"(d[71]),"+f"(d[72]),"+f"(d[73]),"+f"(d[74]),"+f"(d[75]),"+f"(d[76]),"+f"(d[77]),"+f"(d[78]),"+f"(d[79]),"+f"(d[80]),"+f"(d[81]),"+f"(d[82]),"+f"(d[83]),"+f"(d[84]),"+f"(d[85]),"+f"(d[86]),"+f"(d[87]),"+f"(d[88]),"+f"(d[89]),"+f"(d[90]),"+f"(d[91]),"+f"(d[92]),"+f"(d[93]),"+f"(d[94]),"+f"(d[95])
    : "l"(da), "l"(db), "r"(sd));
}
__device__ __forceinline__ void wg_ss128_01(float* d, uint64_t da, uint64_t db, int sd) {
  asm volatile("{.reg .pred p; setp.ne.b32 p, %66, 0;\n"
    "wgmma.mma_async.sync.aligned.m64n128k16.f32.bf16.bf16 {%0,%1,%2,%3,%4,%5,%6,%7,%8,%9,%10,%11,%12,%13,%14,%15,%16,%17,%18,%19,%20,%21,%22,%23,%24,%25,%26,%27,%28,%29,%30,%31,%32,%33,%34,%35,%36,%37,%38,%39,%40,%41,%42,%43,%44,%45,%46,%47,%48,%49,%50,%51,%52,%53,%54,%55,%56,%57,%58,%59,%60,%61,%62,%63}, %64, %65, p, 1, 1, 0, 1;}"
    : "+f"(d[0]),"+f"(d[1]),"+f"(d[2]),"+f"(d[3]),"+f"(d[4]),"+f"(d[5]),"+f"(d[6]),"+f"(d[7]),"+f"(d[8]),"+f"(d[9]),"+f"(d[10]),"+f"(d[11]),"+f"(d[12]),"+f"(d[13]),"+f"(d[14]),"+f"(d[15]),"+f"(d[16]),"+f"(d[17]),"+f"(d[18]),"+f"(d[19]),"+f"(d[20]),"+f"(d[21]),"+f"(d[22]),"+f"(d[23]),"+f"(d[24]),"+f"(d[25]),"+f"(d[26]),"+f"(d[27]),"+f"(d[28]),"+f"(d[29]),"+f"(d[30]),"+f"(d[31]),"+f"(d[32]),"+f"(d[33]),"+f"(d[34]),"+f"(d[35]),"+f"(d[36]),"+f"(d[37]),"+f"(d[38]),"+f"(d[39]),"+f"(d[40]),"+f"(d[41]),"+f"(d[42]),"+f"(d[43]),"+f"(d[44]),"+f"(d[45]),"+f"(d[46]),"+f"(d[47]),"+f"(d[48]),"+f"(d[49]),"+f"(d[50]),"+f"(d[51]),"+f"(d[52]),"+f"(d[53]),"+f"(d[54]),"+f"(d[55]),"+f"(d[56]),"+f"(d[57]),"+f"(d[58]),"+f"(d[59]),"+f"(d[60]),"+f"(d[61]),"+f"(d[62]),"+f"(d[63])
    : "l"(da), "l"(db), "r"(sd));
}
__device__ __forceinline__ void wg_ss160_01(float* d, uint64_t da, uint64_t db, int sd) {
  asm volatile("{.reg .pred p; setp.ne.b32 p, %82, 0;\n"
    "wgmma.mma_async.sync.aligned.m64n160k16.f32.bf16.bf16 {%0,%1,%2,%3,%4,%5,%6,%7,%8,%9,%10,%11,%12,%13,%14,%15,%16,%17,%18,%19,%20,%21,%22,%23,%24,%25,%26,%27,%28,%29,%30,%31,%32,%33,%34,%35,%36,%37,%38,%39,%40,%41,%42,%43,%44,%45,%46,%47,%48,%49,%50,%51,%52,%53,%54,%55,%56,%57,%58,%59,%60,%61,%62,%63,%64,%65,%66,%67,%68,%69,%70,%71,%72,%73,%74,%75,%76,%77,%78,%79}, %80, %81, p, 1, 1, 0, 1;}"
    : "+f"(d[0]),"+f"(d[1]),"+f"(d[2]),"+f"(d[3]),"+f"(d[4]),"+f"(d[5]),"+f"(d[6]),"+f"(d[7]),"+f"(d[8]),"+f"(d[9]),"+f"(d[10]),"+f"(d[11]),"+f"(d[12]),"+f"(d[13]),"+f"(d[14]),"+f"(d[15]),"+f"(d[16]),"+f"(d[17]),"+f"(d[18]),"+f"(d[19]),"+f"(d[20]),"+f"(d[21]),"+f"(d[22]),"+f"(d[23]),"+f"(d[24]),"+f"(d[25]),"+f"(d[26]),"+f"(d[27]),"+f"(d[28]),"+f"(d[29]),"+f"(d[30]),"+f"(d[31]),"+f"(d[32]),"+f"(d[33]),"+f"(d[34]),"+f"(d[35]),"+f"(d[36]),"+f"(d[37]),"+f"(d[38]),"+f"(d[39]),"+f"(d[40]),"+f"(d[41]),"+f"(d[42]),"+f"(d[43]),"+f"(d[44]),"+f"(d[45]),"+f"(d[46]),"+f"(d[47]),"+f"(d[48]),"+f"(d[49]),"+f"(d[50]),"+f"(d[51]),"+f"(d[52]),"+f"(d[53]),"+f"(d[54]),"+f"(d[55]),"+f"(d[56]),"+f"(d[57]),"+f"(d[58]),"+f"(d[59]),"+f"(d[60]),"+f"(d[61]),"+f"(d[62]),"+f"(d[63]),"+f"(d[64]),"+f"(d[65]),"+f"(d[66]),"+f"(d[67]),"+f"(d[68]),"+f"(d[69]),"+f"(d[70]),"+f"(d[71]),"+f"(d[72]),"+f"(d[73]),"+f"(d[74]),"+f"(d[75]),"+f"(d[76]),"+f"(d[77]),"+f"(d[78]),"+f"(d[79])
    : "l"(da), "l"(db), "r"(sd));
}
__device__ __forceinline__ void wg_ss80_01(float* d, uint64_t da, uint64_t db, int sd) {
  asm volatile("{.reg .pred p; setp.ne.b32 p, %42, 0;\n"
    "wgmma.mma_async.sync.aligned.m64n80k16.f32.bf16.bf16 {%0,%1,%2,%3,%4,%5,%6,%7,%8,%9,%10,%11,%12,%13,%14,%15,%16,%17,%18,%19,%20,%21,%22,%23,%24,%25,%26,%27,%28,%29,%30,%31,%32,%33,%34,%35,%36,%37,%38,%39}, %40, %41, p, 1, 1, 0, 1;}"
    : "+f"(d[0]),"+f"(d[1]),"+f"(d[2]),"+f"(d[3]),"+f"(d[4]),"+f"(d[5]),"+f"(d[6]),"+f"(d[7]),"+f"(d[8]),"+f"(d[9]),"+f"(d[10]),"+f"(d[11]),"+f"(d[12]),"+f"(d[13]),"+f"(d[14]),"+f"(d[15]),"+f"(d[16]),"+f"(d[17]),"+f"(d[18]),"+f"(d[19]),"+f"(d[20]),"+f"(d[21]),"+f"(d[22]),"+f"(d[23]),"+f"(d[24]),"+f"(d[25]),"+f"(d[26]),"+f"(d[27]),"+f"(d[28]),"+f"(d[29]),"+f"(d[30]),"+f"(d[31]),"+f"(d[32]),"+f"(d[33]),"+f"(d[34]),"+f"(d[35]),"+f"(d[36]),"+f"(d[37]),"+f"(d[38]),"+f"(d[39])
    : "l"(da), "l"(db), "r"(sd));
}
__device__ __forceinline__ void wg_rs32_00(float* d, uint32_t a0, uint32_t a1, uint32_t a2, uint32_t a3, uint64_t db, int sd) {
  asm volatile("{.reg .pred p; setp.ne.b32 p, %21, 0;\n"
    "wgmma.mma_async.sync.aligned.m64n32k16.f32.bf16.bf16 {%0,%1,%2,%3,%4,%5,%6,%7,%8,%9,%10,%11,%12,%13,%14,%15}, {%16,%17,%18,%19}, %20, p, 1, 1, 0;}"
    : "+f"(d[0]),"+f"(d[1]),"+f"(d[2]),"+f"(d[3]),"+f"(d[4]),"+f"(d[5]),"+f"(d[6]),"+f"(d[7]),"+f"(d[8]),"+f"(d[9]),"+f"(d[10]),"+f"(d[11]),"+f"(d[12]),"+f"(d[13]),"+f"(d[14]),"+f"(d[15])
    : "r"(a0), "r"(a1), "r"(a2), "r"(a3), "l"(db), "r"(sd));
}
__device__ __forceinline__ void wg_rs64_00(float* d, uint32_t a0, uint32_t a1, uint32_t a2, uint32_t a3, uint64_t db, int sd) {
  asm volatile("{.reg .pred p; setp.ne.b32 p, %37, 0;\n"
    "wgmma.mma_async.sync.aligned.m64n64k16.f32.bf16.bf16 {%0,%1,%2,%3,%4,%5,%6,%7,%8,%9,%10,%11,%12,%13,%14,%15,%16,%17,%18,%19,%20,%21,%22,%23,%24,%25,%26,%27,%28,%29,%30,%31}, {%32,%33,%34,%35}, %36, p, 1, 1, 0;}"
    : "+f"(d[0]),"+f"(d[1]),"+f"(d[2]),"+f"(d[3]),"+f"(d[4]),"+f"(d[5]),"+f"(d[6]),"+f"(d[7]),"+f"(d[8]),"+f"(d[9]),"+f"(d[10]),"+f"(d[11]),"+f"(d[12]),"+f"(d[13]),"+f"(d[14]),"+f"(d[15]),"+f"(d[16]),"+f"(d[17]),"+f"(d[18]),"+f"(d[19]),"+f"(d[20]),"+f"(d[21]),"+f"(d[22]),"+f"(d[23]),"+f"(d[24]),"+f"(d[25]),"+f"(d[26]),"+f"(d[27]),"+f"(d[28]),"+f"(d[29]),"+f"(d[30]),"+f"(d[31])
    : "r"(a0), "r"(a1), "r"(a2), "r"(a3), "l"(db), "r"(sd));
}
__device__ __forceinline__ void wg_rs128_00(float* d, uint32_t a0, uint32_t a1, uint32_t a2, uint32_t a3, uint64_t db, int sd) {
  asm volatile("{.reg .pred p; setp.ne.b32 p, %69, 0;\n"
    "wgmma.mma_async.sync.aligned.m64n128k16.f32.bf16.bf16 {%0,%1,%2,%3,%4,%5,%6,%7,%8,%9,%10,%11,%12,%13,%14,%15,%16,%17,%18,%19,%20,%21,%22,%23,%24,%25,%26,%27,%28,%29,%30,%31,%32,%33,%34,%35,%36,%37,%38,%39,%40,%41,%42,%43,%44,%45,%46,%47,%48,%49,%50,%51,%52,%53,%54,%55,%56,%57,%58,%59,%60,%61,%62,%63}, {%64,%65,%66,%67}, %68, p, 1, 1, 0;}"
    : "+f"(d[0]),"+f"(d[1]),"+f"(d[2]),"+f"(d[3]),"+f"(d[4]),"+f"(d[5]),"+f"(d[6]),"+f"(d[7]),"+f"(d[8]),"+f"(d[9]),"+f"(d[10]),"+f"(d[11]),"+f"(d[12]),"+f"(d[13]),"+f"(d[14]),"+f"(d[15]),"+f"(d[16]),"+f"(d[17]),"+f"(d[18]),"+f"(d[19]),"+f"(d[20]),"+f"(d[21]),"+f"(d[22]),"+f"(d[23]),"+f"(d[24]),"+f"(d[25]),"+f"(d[26]),"+f"(d[27]),"+f"(d[28]),"+f"(d[29]),"+f"(d[30]),"+f"(d[31]),"+f"(d[32]),"+f"(d[33]),"+f"(d[34]),"+f"(d[35]),"+f"(d[36]),"+f"(d[37]),"+f"(d[38]),"+f"(d[39]),"+f"(d[40]),"+f"(d[41]),"+f"(d[42]),"+f"(d[43]),"+f"(d[44]),"+f"(d[45]),"+f"(d[46]),"+f"(d[47]),"+f"(d[48]),"+f"(d[49]),"+f"(d[50]),"+f"(d[51]),"+f"(d[52]),"+f"(d[53]),"+f"(d[54]),"+f"(d[55]),"+f"(d[56]),"+f"(d[57]),"+f"(d[58]),"+f"(d[59]),"+f"(d[60]),"+f"(d[61]),"+f"(d[62]),"+f"(d[63])
    : "r"(a0), "r"(a1), "r"(a2), "r"(a3), "l"(db), "r"(sd));
}
__device__ __forceinline__ void wg_rs24_01(float* d, uint32_t a0, uint32_t a1, uint32_t a2, uint32_t a3, uint64_t db, int sd) {
  asm volatile("{.reg .pred p; setp.ne.b32 p, %17, 0;\n"
    "wgmma.mma_async.sync.aligned.m64n24k16.f32.bf16.bf16 {%0,%1,%2,%3,%4,%5,%6,%7,%8,%9,%10,%11}, {%12,%13,%14,%15}, %16, p, 1, 1, 1;}"
    : "+f"(d[0]),"+f"(d[1]),"+f"(d[2]),"+f"(d[3]),"+f"(d[4]),"+f"(d[5]),"+f"(d[6]),"+f"(d[7]),"+f"(d[8]),"+f"(d[9]),"+f"(d[10]),"+f"(d[11])
    : "r"(a0), "r"(a1), "r"(a2), "r"(a3), "l"(db), "r"(sd));
}

#define AB_POLY 0x77
__device__ __forceinline__ constexpr bool poly_group(int group) { return (AB_POLY >> (group & 7)) & 1; }

template <int V> struct Int { static constexpr int value = V; };

template <int NG>
__device__ __forceinline__ void ln_stats(const float4 (&v)[NG][5], uint32_t scratch, float (&mean)[NG], float (&rs)[NG]) {
  const int warp = threadIdx.x >> 5, lane = threadIdx.x & 31;
#pragma unroll
  for (int r = 0; r < NG; r++) {
    float s = 0.f, q = 0.f;
#pragma unroll
    for (int i = 0; i < 5; i++) s += (v[r][i].x + v[r][i].y) + (v[r][i].z + v[r][i].w);
    s += __shfl_xor_sync(~0u, s, 1); s += __shfl_xor_sync(~0u, s, 2);
    s *= 1.f / 80;
#pragma unroll
    for (int i = 0; i < 5; i++) {
      const float x = v[r][i].x - s, y = v[r][i].y - s, z = v[r][i].z - s, w = v[r][i].w - s;
      q += (x * x + y * y) + (z * z + w * w);
    }
    q += __shfl_xor_sync(~0u, q, 1); q += __shfl_xor_sync(~0u, q, 2);
    mean[r] = s; rs[r] = q;
  }
  bar_sync(1, 256);
  if ((lane & 3) == 0) {
#pragma unroll
    for (int r = 0; r < NG; r++) sts64f(scratch + r * 512 + lane * 16 + warp * 8, mean[r], rs[r]);
  }
  bar_sync(1, 256);
#pragma unroll
  for (int r = 0; r < NG; r++) {
    const float4 e = lds128f(scratch + r * 512 + lane * 16);
    float t = e.x + e.z;
    t += __shfl_xor_sync(~0u, t, 1); t += __shfl_xor_sync(~0u, t, 2);
    t *= 0.125f;
    float q = e.y + e.w + 80.f * ((e.x - t) * (e.x - t) + (e.z - t) * (e.z - t));
    q += __shfl_xor_sync(~0u, q, 1); q += __shfl_xor_sync(~0u, q, 2);
    mean[r] = t; rs[r] = rsqrtf(q * (1.f / DM) + 1e-5f);
  }
}

__device__ __forceinline__ void ln_store(const uint32_t (&w)[2][5][2], int tile, int u0) {
  const int lane = threadIdx.x & 31;
  uint32_t* xc = g_xc + ((tile >> 1) * 40 + u0) * 256 + (tile & 1) * 64 + lane;
#pragma unroll
  for (int i = 0; i < 20; i++) xc[(i >> 1) * 128 + (i & 1) * 32] = w[i & 1][i >> 2][i >> 1 & 1];
#pragma unroll
  for (int i = 0; i < 5; i++) {
    const int u = u0 + i;
    uint32_t* xn = g_xn + (((tile >> 3) * 20 + (u >> 1)) * 16 + (tile & 1) * 8 + (tile & 6)) * 128 + (u & 1) * 64 + lane;
#pragma unroll
    for (int r = 0; r < 2; r++) { xn[r * 128] = w[r][i][0]; xn[r * 128 + 32] = w[r][i][1]; }
  }
}
__device__ __forceinline__ void wait_count(const uint32_t* c, uint32_t n) {
  int spin = 0;
  while ((ld_acquire(c) & 0xffff) < n) { __nanosleep(32); spin_guard(spin); }
}

__device__ __forceinline__ uint8_t* pool_at(uint32_t off) {
  return reinterpret_cast<uint8_t*>((reinterpret_cast<uintptr_t>(g_pool) + 8191) & ~(uintptr_t)8191) + off; }
struct Weights { const uint8_t* w[4]; };
__device__ __forceinline__ void prefetch_weights(const Weights& p, int i) {
  if (blockIdx.x < 128) asm volatile("cp.async.bulk.prefetch.L2.global [%0], 61440;" :: "l"(p.w[i] + (size_t)blockIdx.x * 61440) : "memory");
}
__global__ void __launch_bounds__(256) first_kernel(const __nv_bfloat16* __restrict__ xin, const uint4* __restrict__ wb, const __grid_constant__ Weights wa) {
  __shared__ __align__(16) float scratch[256];
  __shared__ uint32_t lat[4];
  const int warp = threadIdx.x >> 5, lane = threadIdx.x & 31, cta = blockIdx.x;
  TRACE(0);
  pdl_launch();
  if (warp < 4 && (warp < 2 || cta < NSLOT)) {
    uint32_t* q = reinterpret_cast<uint32_t*>(pool_at((warp < 2 ? NSLOT : cta) * 8192 + (warp & 1) * 4096)) + (warp < 2 ? (cta & 127) * 8 : 0);
    if (lane < 8) stg_strong32(q + lane, 0u);
    uint32_t best = ~0u;
    if (lane == 0)
      for (int r = 0; r < 4; r++) {
        uint32_t t0, t1, v;
        asm volatile("mov.u32 %0, %%clock;" : "=r"(t0) :: "memory");
        asm volatile("atom.relaxed.gpu.global.exch.b32 %0, [%1], 0;" : "=r"(v) : "l"(q) : "memory");
        asm volatile("{.reg .u32 t; add.u32 t, %1, 1; mov.u32 %0, %%clock; sub.u32 %0, %0, %1;}" : "=r"(t1) : "r"(__shfl_sync(1u, v, 0)) : "memory");
        best = min(best, t1 - t0);
      }
    if (lane == 0) lat[warp] = best;
  }
  __syncthreads();
  ABT(2, 0);
  if (threadIdx.x == 0) {
    const int part = lat[0] < lat[1] ? 0 : 1;
    uint32_t smid; asm("mov.u32 %0, %%smid;" : "=r"(smid));
    g_smpart[smid & 255] = part;
    g_smclk[smid & 255] = clk32() - gtime() * 2;
    g_smuse[smid & 255] = 0;
    if (cta < NSLOT) g_orient[cta] = lat[2] < lat[3] ? part : 1 - part;
  }
  if (cta < 128) {
    float4 v[2][5];
#pragma unroll
    for (int r = 0; r < 2; r++)
#pragma unroll
      for (int i = 0; i < 5; i++) {
        const uint32_t* src = reinterpret_cast<const uint32_t*>(xin) + (cta * 16 + r * 8 + (lane >> 2)) * (DM / 2) + warp * 40 + i * 8 + (lane & 3);
        const uint32_t a = src[0], b = src[4];
        v[r][i] = make_float4(bf_lo(a), bf_hi(a), bf_lo(b), bf_hi(b));
      }
    uint4 w8[2];
#pragma unroll
    for (int i = 0; i < 2; i++) w8[i] = wb[cta * 400 + min(i * 256 + threadIdx.x, 399)];
    if (threadIdx.x < 128) g_stat[cta * 128 + threadIdx.x] = make_float2(0.f, 0.f);
#pragma unroll
    for (int i = 0; i < 10; i++) g_x[((cta * 2 + i / 5) * 40 + warp * 5 + i % 5) * 32 + lane] = v[i / 5][i % 5];
    ABT(2, 1);
    if (threadIdx.x == 32) for (int i = 0; i < FK_PF; i++) prefetch_weights(wa, i);
    float mean[2], rs[2];
    ln_stats<2>(v, s2u(scratch), mean, rs);
    ABT(2, 2);
    uint32_t w[2][5][2];
#pragma unroll
    for (int i = 0; i < 10; i++) {
      const float4 t = v[i / 5][i % 5];
      const float m = mean[i / 5], q = rs[i / 5];
      w[i / 5][i % 5][0] = pack2((t.x - m) * q, (t.y - m) * q); w[i / 5][i % 5][1] = pack2((t.z - m) * q, (t.w - m) * q);
    }
    ln_store(w, cta, warp * 5);
    ABT(2, 3);
#pragma unroll
    for (int i = 0; i < 2; i++) {
      const int e = cta * 400 + min(i * 256 + threadIdx.x, 399), k = e / 80, n = e - k * 80, cg = n / 10;
      g_wb[((cg * 80 + (k >> 3)) * 10 + n - cg * 10) * 8 + (k & 7)] = w8[i];
    }
  } else if (cta == 128) {
    g_bo[threadIdx.x] = 0;
  }
  TRACE(2);
}

struct ChainParams {
  CUtensorMap wq, wk, wv, wo;
  const __nv_bfloat16* mem0;
  uint8_t *pool, *kv;
  const uint32_t* xc;
  uint32_t* sync;
  int layer;
  int d0, d3, d1, d1b, d2, d2b, mode;
};
constexpr int CH_WQ = 0, CH_WO = 81920, CH_X = CH_WO + 86016, CH_M = CH_X + 20480, CH_KT = CH_X + 40960, CH_VT = CH_KT + 4096,
              CH_PS = CH_VT + 4096, CH_QK = CH_PS + 4096, CH_VP = CH_QK + 4096, CH_SX = CH_VP + 1024, CH_O = CH_SX + 2304, CH_ID = CH_O + 3072,
              CH_BAR = CH_ID + 512;
constexpr int CH_SMEM = CH_BAR + 256;
constexpr int CH_BASE = 1024;
#define CH_VK0 8
#define CH_VK1 20
#define CH_L0 4
#define CH_LR 4
#define NOX 0
#define CH_XA 0
#define CH_XB 1
#define CH_W1 3
#define CH_W2 17
#define CH_W3 26
#define CH_R2 8
#define CH_VA 16
#define CH_EX 1
#define CH_KD 0
#define CH_RP 1
#define CH_KW 3
#define CH_RB 0
#define CH_RC 8
#define CH_D0 200
#define CH_D1 450
#define CH_D2 350
#define CH_R1 4
#define CH_TW 12
__device__ __forceinline__ uint32_t opaque(uint32_t x) { return __shfl_sync(~0u, x, threadIdx.x & 31); }
__device__ __forceinline__ uint32_t nz(uint32_t x) { uint32_t r; asm("max.u32 %0, %1, 1;" : "=r"(r) : "r"(x)); return r; }
__device__ __forceinline__ uint32_t pack_tag(float lo, float hi, uint32_t tag, uint32_t mask) {
  uint32_t r;
  asm("lop3.b32 %0, %1, %2, %3, 0xD8;" : "=r"(r) : "r"(pack2(lo, hi)), "r"(tag), "r"(mask));
  return r;
}
__device__ __forceinline__ uint32_t differ(uint32_t a, uint32_t b, uint32_t t) { uint32_t r; asm("lop3.b32 %0, %1, %2, %3, 0x7E;" : "=r"(r) : "r"(a), "r"(b), "r"(t)); return r; }
__device__ __forceinline__ void mbar_wait_hot(uint32_t bar, uint32_t ph) {
  uint32_t ok;
  asm volatile("{.reg .pred p; mbarrier.try_wait.parity.shared::cta.b64 p, [%1], %2; selp.u32 %0, 1, 0, p;}" : "=r"(ok) : "r"(bar), "r"(ph) : "memory");
  if (__builtin_expect(!ok, 0)) mbar_wait(bar, ph);
}
__device__ __forceinline__ bool elect() {
  uint32_t r; asm volatile("{.reg .pred p; elect.sync _|p, 0xffffffff; selp.u32 %0, 1, 0, p;}" : "=r"(r)); return r; }
__device__ __forceinline__ uint32_t or3(uint32_t a, uint32_t b, uint32_t c) { uint32_t r; asm("lop3.b32 %0, %1, %2, %3, 0xFE;" : "=r"(r) : "r"(a), "r"(b), "r"(c)); return r; }
__device__ __forceinline__ void pin() { pdl_launch(); }
__device__ __forceinline__ void mma16h(float* d, uint32_t a0, uint32_t a2, uint32_t b0, uint32_t b1) {
  asm volatile("{.reg .b32 u, v; mma.sync.aligned.m16n8k16.row.col.f32.bf16.bf16.f32 {%0,%1,%2,%3},{%4,u,%5,v},{%6,%7},{%0,%1,%2,%3};}"
               : "+f"(d[0]), "+f"(d[1]), "+f"(d[2]), "+f"(d[3]) : "r"(a0), "r"(a2), "r"(b0), "r"(b1)); }
__device__ __forceinline__ void mma8h(float* d, uint32_t a0, uint32_t b0) {
  asm volatile("{.reg .b32 u; mma.sync.aligned.m16n8k8.row.col.f32.bf16.bf16.f32 {%0,%1,%2,%3},{%4,u},{%5},{%0,%1,%2,%3};}"
               : "+f"(d[0]), "+f"(d[1]), "+f"(d[2]), "+f"(d[3]) : "r"(a0), "r"(b0)); }
__device__ __forceinline__ uint32_t absmax2(uint32_t a, uint32_t b) { uint32_t r; asm("max.xorsign.abs.bf16x2 %0, %1, %2;" : "=r"(r) : "r"(a), "r"(b)); return r; }
__device__ __forceinline__ void until(uint32_t t) { while ((int)(clk32() - t) < 0) {} }
__device__ __forceinline__ uint4 pack8(const float* d) { return make_uint4(pack2(d[0], d[1]), pack2(d[2], d[3]), pack2(d[4], d[5]), pack2(d[6], d[7])); }
__device__ __forceinline__ void add8(float* d, uint4 v) {
  d[0] += bf_lo(v.x); d[1] += bf_hi(v.x); d[2] += bf_lo(v.y); d[3] += bf_hi(v.y);
  d[4] += bf_lo(v.z); d[5] += bf_hi(v.z); d[6] += bf_lo(v.w); d[7] += bf_hi(v.w);
}

template <int WG>
__device__ __forceinline__ void chain_body(const ChainParams& p, const uint32_t wq, const uint32_t (&ak)[80], const uint32_t (&av)[80]) {
  const int tid = threadIdx.x & 127, t4 = __shfl_sync(~0u, tid >> 5, 0), lane = tid & 31;
  const int cta = blockIdx.x, h = cta / 3, j = cta - 3 * h;
  const uint32_t sb = mapa(CH_BASE, j);
  const uint32_t bWo = sb + CH_BAR, bWq = bWo + 8, bX = bWo + 16, bXA = bWo + 24, bXB = bWo + 32, bO = bWo + 40, bG = bWo + 48, bH = bWo + 96;
  uint32_t tw[4 * CH_TW];
  auto refill = [&]() {
#pragma unroll
    for (int k = 0; k < CH_TW; k++) ldsm4t(&tw[4 * k], wq + k * 2048);
  };
  const uint32_t wo = opaque((sb + CH_WO + (WG == 0 ? (t4 + (j == 2)) * 4096 : (j == 2 ? 0 : 24576) + t4 * 1024) + ((lane & 7) + (lane >> 4) * 8) * 64 +
                              ((((lane >> 3) & 1) ^ ((lane >> 1) & 3)) << 4)) ^ (WG == 1 && j == 2 ? 32 : 0));
  const uint32_t wo2 = opaque((wo ^ ((t4 & 1) * 32)) + (4 + (t4 >> 1) - t4) * 4096);
  const uint32_t l16 = opaque(sb + lane * 16);
  const uint32_t l8 = opaque(sb + t4 * 256 + lane * 8);
  const uint32_t lw = opaque(sb + t4 * 1024 + lane * 16);
  const uint32_t qs = opaque(sb + CH_QK + WG * 2048 + t4 * 512 + lane * 16);
  const uint32_t qa = opaque(sb + CH_QK + (lane >> 4) * 2048 + (lane & 15) * 16 + (WG == 0 ? t4 * 512 + 256 : t4 == 3 ? 1024 : 0));
  const uint32_t ka = opaque(t4 < 2 ? sb + CH_KT + t4 * 512 + lane * 16
                                    : sb + CH_QK + 256 + (t4 - 2) * 1024 + ((lane >> 3) & 1) * 2048 + (lane >> 4) * 128 + (lane & 7) * 16);
  const uint32_t l4 = opaque(sb + t4 * 256 + lane * 4);
  uint32_t pdst[1], pages = 0;
  auto line0 = [&](int i) { return 28 * j + (i < 4 ? 4 * t4 + i : 12 + 2 * t4 + i); };
  const uint32_t plane = opaque((lane >> 4) * 2048 + h * 64 + (lane & 15) * 4);
  if (WG == 0) {
    pages = __ballot_sync(~0u, lds32(sb + CH_O + line0(min(lane, 5)) * 4) & 4096);
  } else {
    pages = __ballot_sync(~0u, lds32(sb + CH_O + (80 + min(lane, 11)) * 4) & 4096);
    pdst[0] = opaque(lds32(sb + CH_O + (j == 0 ? 24 + t4 : 50 + 2 * j + (t4 & 1)) * 4) + plane);
  }
  const uint32_t role = lds32(sb + CH_O + NSLOT * 4), rsrc = lds32(sb + CH_O + role * 4), rdst = (80 + role / 20) * 8192 + role % 20 * 128;
  const uint32_t r1 = mapa(CH_BASE, j == 2 ? 0 : j + 1) - sb, r2 = mapa(CH_BASE, j == 0 ? 2 : j - 1) - sb;
  uint32_t tag = opaque(1);
  auto pool = [&](uint32_t off) { return p.pool + ((tag & 0xfffe) + off); };
  auto after = [&](uint32_t x) { return x & tag & 0xfffe; };
  auto kv = [&](int s, uint32_t a) { return p.kv + (a + ((cta * 2 * NSEG + s) * KV_BYTES - sb)); };
  auto pass = [&](float (&d)[16], const uint32_t (&a)[80], auto k0, auto k1) {
    const uint64_t db = mkdesc(CH_BASE + CH_X + WG * 20480, 512, 128, 0);
#pragma unroll
    for (int k = k0.value; k < k1.value; k++) wg_rs32_00(d, a[4 * k], a[4 * k + 1], a[4 * k + 2], a[4 * k + 3], db + k * 64, k);
    wg_commit();
  };
  auto dump = [&](float (&d)[16], uint32_t a) {
    reg_fence<16>(d);
    sts128(a, pack8(d)); sts128(a + 512, pack8(d + 8));
  };
  uint32_t pph = 0;
  auto tokens0 = [&](int s, auto k0) {
    float dk[16], dv[16];
    bar_sync(9, 256);
    wg_fence();
    pass(dk, ak, Int<0>(), Int<4>());
    const uint4 a0 = lds128(lw + CH_KT), a1 = lds128(lw + CH_KT + 512);
    pin();
    pass(dk, ak, Int<4>(), Int<20>());
    pass(dv, av, Int<0>(), Int<CH_VA>());
    pin();
    wg_wait<1>();
    reg_fence<16>(dk);
    add8(dk, a0); add8(dk + 8, a1);
    const uint4 w0 = pack8(dk), w1 = pack8(dk + 8);
    const uint4 b0 = lds128(lw + CH_VT), b1 = lds128(lw + CH_VT + 512);
    stsm4t(lw + CH_KT, w0.x, w0.z, w0.y, w0.w); stsm4t(lw + CH_KT + 512, w1.x, w1.z, w1.y, w1.w);
    TM1(6);
    pin();
    if (CH_VA < 20) pass(dv, av, Int<CH_VA>(), Int<20>());
    pin();
#pragma unroll
    for (int k = k0.value; k < CH_TW; k++) ldsm4t(&tw[4 * k], wq + k * 2048);
    TM1(9);
    if (k0.value < CH_TW && t4 >= 2) { mbar_wait_hot(bH + t4 * 16 - 24 + (pph & 1) * 8, pph >> 1 & 1); pph++; }
    __syncwarp();
    wg_wait<0>();
    reg_fence<16>(dv);
    add8(dv, b0); add8(dv + 8, b1);
#pragma unroll
    for (int e = 0; e < 2; e++) { const uint4 v = pack8(dv + 8 * e); sts128(lw + CH_VT + e * 512, make_uint4(v.x, v.z, v.y, v.w)); }
  };
  auto publish_k = [&](int s) {
    if (t4 == CH_KW && elect()) { fence_async(); bulk_store(p.kv + (size_t)(cta * 2 * NSEG + s) * KV_BYTES, sb + CH_KT, 4096); bulk_commit(); }
    __syncwarp();
  };
  if (WG == 0) {
    mbar_wait(bXB, 0);
    tokens0(0, Int<CH_TW>());
  } else {
    const uint32_t* m0 = reinterpret_cast<const uint32_t*>(p.mem0) + (lane >> 2) * 320 + t4 * 80 + (lane & 3);
    uint32_t a[20];
#pragma unroll
    for (int i = 0; i < 20; i++) a[i] = m0[4 * i];
    pin();
    float dk[16], dv[16];
    mbar_wait(bXA, 0);
    wg_fence();
    pass(dk, ak, Int<0>(), Int<20>());
    pass(dv, av, Int<0>(), Int<20>());
    wg_wait<0>();
    dump(dk, lw + CH_KT);
    dump(dv, lw + CH_VT);
    bar_sync(9, 256);
#pragma unroll
    for (int i = 0; i < 20; i++) sts32(sb + CH_M + (t4 * 20 + i) * 128 + lane * 4, nz(transpose8(a[i])));
    __syncwarp();
    if (elect()) mbar_arrive(bG + t4 * 8);
  }
  PRO(8);
  mbar_wait(bWq, 0);
  refill();
  PRO(9);
  mbar_wait(bWo, 0);
  asm volatile("barrier.cluster.wait.aligned;" ::: "memory");
  PRO(10);
  constexpr int VK = WG == 0 ? CH_VK0 : CH_VK1;
  uint32_t gph = 0;
  int st = 0;
  const uint32_t ca = opaque(sb + CH_M + t4 * 2560 + lane * 32 + (lane >> 2) * 4);
  auto project = [&](int s, uint32_t (&b)[40], float (&dv)[16], uint32_t (&kf)[16]) {
    float dq[4] = {}, dk[4] = {};
    uint32_t w[80];
#pragma unroll
    for (int i = 0; i < 4 * CH_TW; i++) w[i] = tw[i];
    auto load = [&](int n) {
      int c = 0;
#pragma unroll
      for (int i = 0; i < 10; i++) {
        if (c++ == n) ldsm4t(&b[4 * i], l16 + CH_M + WG * 5120 + i * 512);
#pragma unroll
        for (int k = 2 * i; k < 2 * i + 2; k++)
          if (k >= CH_TW && c++ == n) ldsm4t(&w[4 * k], wq + k * 2048);
      }
#pragma unroll
      for (int i = 0; i < 4; i++)
        if (WG == 1 && c++ == n) ldsm4(&kf[4 * i], ka + i * 1024);
    };
    if (WG == 1) {
      for (int n = 0;;) {
        mbar_wait(bG + t4 * 8, gph);
        TR(5, (clk32() & ~3u) | min(n, 3));
        gph ^= 1;
        if (__builtin_expect(!__any_sync(~0u, __vimin3_u32(lds32(ca), lds32(ca + 1024), lds32(ca + 1536)) == 0), 1)) break;
        if (elect()) {
          const int q = (st == 0 ? 8 : st * 4 - 4) + t4;
          mbar_expect(bG + t4 * 8, 2560);
          bulk_load(sb + CH_M + t4 * 2560, p.pool + ((80 + q) * 8192 + (pages >> q & 1) * 4096), 2560, bG + t4 * 8);
        }
        spin_guard(n);
      }
    }
    bar_sync(6, 256);
#pragma unroll
    for (int i = 0; i < CH_L0; i++) load(i);
    TM(0);
    TM1(11);
    if (WG == 1) TR(6, clk32());
#pragma unroll
    for (int k = 0; k < 20; k += 2) {
      if (k > 0) {
#pragma unroll
        for (int n = CH_L0 + (k - 2) * CH_LR / 4; n < (k == 18 ? 40 : CH_L0 + k * CH_LR / 4); n++) load(n);
      }
      pin();
#pragma unroll
      for (int kk = k; kk < k + 2; kk++) {
        mma16(dk, ak[4 * kk], ak[4 * kk + 1], ak[4 * kk + 2], ak[4 * kk + 3], b[2 * kk], b[2 * kk + 1]);
        mma16(dq, w[4 * kk], w[4 * kk + 1], w[4 * kk + 2], w[4 * kk + 3], b[2 * kk], b[2 * kk + 1]);
        if (kk < VK) mma16(dv, av[4 * kk], av[4 * kk + 1], av[4 * kk + 2], av[4 * kk + 3], b[2 * kk], b[2 * kk + 1]);
      }
    }
    const float k2 = 0.07216878364870322f * 1.44269504089f;
    stsm4t(qs, pack2(dq[0] * k2, dq[1] * k2), pack2(dq[2] * k2, dq[3] * k2), pack2(dk[0], dk[1]), pack2(dk[2], dk[3]));
    TM(1);
  };
  constexpr int VC = VK == 20 ? 1 : WG == 0 ? 2 : 3;
  auto finish_v = [&](const uint32_t (&b)[40], float (&dv)[16]) {
#pragma unroll
    for (int kk = VK; kk < 20; kk++) mma16(dv + 4 * ((kk - VK) % VC), av[4 * kk], av[4 * kk + 1], av[4 * kk + 2], av[4 * kk + 3], b[2 * kk], b[2 * kk + 1]);
  };
  auto sum_v = [&](float (&dv)[16]) {
#pragma unroll
    for (int i = 4; i < 4 * VC; i++) dv[i & 3] += dv[i];
  };
  auto publish_km = [&](int s) {
    uint32_t a[4];
    ldsm4(a, qa);
    *reinterpret_cast<uint2*>(kv(s, l8) + KV_M) = make_uint2(hadd2(a[0], a[2]), hadd2(a[1], a[3]));
  };
  auto memory_v = [&](uint2 x, const float (&dv)[16]) {
    return make_uint2(pack2(dv[0] + bf_lo(x.x), dv[1] + bf_hi(x.x)), pack2(dv[2] + bf_lo(x.y), dv[3] + bf_hi(x.y)));
  };
  auto publish_v = [&](int s, const uint4 (&v)[2], uint2 vm) {
#pragma unroll
    for (int e = 0; e < 2; e++) reinterpret_cast<uint4*>(kv(s, lw) + KV_V)[e * 32] = v[e];
    *reinterpret_cast<uint2*>(kv(s, l8) + KV_V + KV_M) = vm;
  };
  auto load_x = [&](int s, int k0, int n, uint32_t bar) {
    if (!NOX && elect()) { mbar_expect(bar, n * 1024); bulk_load(sb + CH_X + k0 * 1024, p.xc + (s + 1) * 10240 + k0 * 256, n * 1024, bar); }
  };
#pragma unroll 1
  for (int s = 0; s < NSEG - 1; s++) {
    float dv[16] = {};
    uint32_t b[40], kf[16];
    project(s, b, dv, kf);
    if (WG == 0) {
      bar_sync(1, 256);
      if (CH_XA == 0) load_x(s, 20 + 5 * t4, 5, bXA);
      if (CH_XB == 0) load_x(s, 5 * t4, 5, bXB);
      pin();
      finish_v(b, dv);
      sum_v(dv);
      sts64(l8 + CH_VP, pack2(dv[0], dv[1]), pack2(dv[2], dv[3]));
      __syncwarp();
      if (elect()) mbar_arrive(bX);
      if (CH_XA == 1) load_x(s, 20 + 5 * t4, 5, bXA);
      if (CH_XB == 1) load_x(s, 5 * t4, 5, bXB);
      uint32_t w[144];
      auto wload = [&](int i) { ldsm4t(&w[4 * i], (i % 3 == 0 ? wo : i % 3 == 1 ? wo ^ 32 : wo2) + i / 12 * 28672 + i / 3 % 4 * 1024); };
      TM(3);
      publish_k(s);
#pragma unroll
      for (int i = 0; i < CH_W1; i++) wload(i);
      bar_sync(10, 256);
      uint32_t km[4];
      ldsm4(km, qa);
      pin();
#pragma unroll
      for (int i = CH_W1; i < CH_W2; i++) wload(i);
      pin();
      *reinterpret_cast<uint2*>(kv(s, l8) + KV_M) = make_uint2(hadd2(km[0], km[2]), hadd2(km[1], km[3]));
      bulk_wait_read<0>();
      if (CH_XA == 2) load_x(s, 20 + 5 * t4, 5, bXA);
      if (CH_XB == 2) load_x(s, 5 * t4, 5, bXB);
      bar_sync(2, 256);
      {
        float y[3][4] = {};
        uint32_t ob[24];
        ldsm4(&ob[0], l16 + CH_O + 1024); ldsm4(&ob[4], l16 + CH_O + 1536);
        TM(7);
        auto step = [&](int i) {
          const int k = i / 3;
          mma16(y[i % 3], w[4 * i], w[4 * i + 1], w[4 * i + 2], w[4 * i + 3], ob[2 * k], ob[2 * k + 1]);
        };
#pragma unroll
        for (int i = 0; i < 12; i++) {
          step(i);
          if (i >= 12 - (CH_W3 - CH_W2)) wload(CH_W3 - 12 + i);
          if (i % 3 == 2) pin();
        }
        if (CH_XB == 3) load_x(s, 5 * t4, 5, bXB);
        pin();
        mbar_wait(bO, s & 1);
        TM(4);
        ldsm4(&ob[8], l16 + CH_O); ldsm4(&ob[12], l16 + CH_O + 512);
        pin();
        float2 inv;
        uint8_t* dst[6];
        uint32_t mask;
#pragma unroll
        for (int i = 12; i < 36; i++) {
          step(i);
          const int n = CH_W3 + i - 13, m = n - (n > 30);
          if (i == 12) ldsm4(&ob[16], l16 + after(w[4 * CH_W3 - 1] | w[4 * CH_W3 - 5] | w[4 * CH_W3 - 9] | ob[8]) + CH_O + 2048);
          else if (n == 30) ldsm4(&ob[20], l16 + CH_O + 2560);
          else if (m < 36) wload(m);
          else if (m == 36) inv = lds64f((l8 & ~0xe0u) + CH_VP);
          if (i == 26) mask = ((l16 ^ tag) & 48) == 0;
          if (i >= 27 && i < 33) dst[i - 27] = pool(line0(i - 27) * 8192 + (pages >> (i - 27) & 1) * 4096) + plane;
          if (i % 3 == 2) pin();
        }
#pragma unroll
        for (int k = 0; k < CH_R1; k++) ldsm4t(&tw[4 * k], wq + k * 2048);
        pin();
#pragma unroll
        for (int i = 0; i < 6; i++) stg_strong32(dst[i], pack_tag(y[i >> 1][2 * (i & 1)] * inv.x, y[i >> 1][2 * (i & 1) + 1] * inv.y, tag, mask));
        TM(8);
        TR(0, clk32());
        bar_arrive(5, 256);
        pin();
      }
      const uint32_t t0 = clk32();
      auto refill2 = [&]() {
#pragma unroll
        for (int k = CH_R1; k < CH_R2; k++) ldsm4t(&tw[4 * k], wq + k * 2048);
      };
      if (CH_RP == 0) refill2();
      const uint32_t ln = (l16 ^ tag) >> 4 & 31;
      if (t4 >= 2) {
        const uint32_t bP = bH + t4 * 16 - 24, ps = CH_PS + (t4 & 1) * 4096;
        auto fetch = [&](uint32_t k) {
          if (elect()) { mbar_expect(bP + (k & 1) * 8, 2048); bulk_load(sb + ps + (k & 1) * 2048, p.pool + (rsrc + (t4 & 1) * 2048), 2048, bP + (k & 1) * 8); }
        };
        until(t0 + CH_D0);
        fetch(pph);
        if (CH_RP == 2) refill2();
        if (!NOX) mbar_wait_hot(bXB, (s + 1) & 1);
        const uint32_t want = (tag & 1) * 0x10001, chk = opaque(ln < 4 ? 0x10001 : 0);
        uint4 sel;
        sel.x = opaque((ln >> 3) != (ln & 1) ? 0 : ln & 4 ? 0x3f800000u : 0x00003f80u);
        sel.z = opaque(sel.x); sel.y = opaque(ln); sel.w = opaque(ln + 1);
        uint8_t* mdst = p.pool + opaque(st * 32768 + rdst + (t4 & 1) * 64 + ln * 4);
        until(t0 + CH_D1);
        fetch(pph + 1);
        TM(5);
        if (CH_RP == 1) refill2();
        int n = 0;
        uint32_t u[16];
        for (;;) {
          mbar_wait(bP + (pph & 1) * 8, pph >> 1 & 1);
          TM(14);
          TR(2, clk32());
#pragma unroll
          for (int i = 0; i < 4; i++) ldsm4t(&u[4 * i], l16 + (ps + (pph & 1) * 2048) + i * 512);
          pph++;
          uint32_t bad = 0;
#pragma unroll
          for (int i = 0; i < 4; i++) bad = or3(bad, differ(u[4 * i], u[4 * i + 1], want), differ(u[4 * i + 2], u[4 * i + 3], want));
          if (!__any_sync(~0u, bad & chk)) break;
          fetch(pph + 1);
          spin_guard(n);
        }
        float y[4][4] = {};
#pragma unroll
        for (int i = 0; i < 8; i++) mma16(y[i & 3], sel.x, sel.y, sel.z, sel.w, u[2 * i], u[2 * i + 1]);
        TR(1, t0 + (n ? CH_D1 : CH_D0));
        TM(15);
        const uint32_t w = nz(pack2((y[0][0] + y[1][0]) + (y[2][0] + y[3][0]), (y[0][1] + y[1][1]) + (y[2][1] + y[3][1])));
        if (ln < 16) { stg_strong32(mdst, w); stg_strong32(mdst + 4096, w); }
        TMV(12, 32, n);
        TR(3, (clk32() & ~3u) | min(n, 3));
      } else {
        if (CH_RP) refill2();
        if (!NOX) mbar_wait_hot(bXB, (s + 1) & 1);
        stg_strong32(p.pool + ((st == 2 ? 0 : st + 1) * 32768 + rdst + t4 * 4096) + ln * 4, 0u);
        if (t4 == 0 && cta < 40 && s + 4 < NSEG && elect())
          asm volatile("cp.async.bulk.prefetch.L2.global [%0], 1024;" :: "l"(p.xc + (s + 4) * 10240 + cta * 256) : "memory");
        if (t4 == 1 && (s & 3) == 0 && s > 0 && elect()) red_relaxed(p.sync + 2 * s - 4, 1);
        if (t4 == 1 && s == NSEG - 3 && cta == 95 && elect()) red_relaxed(p.sync + 2 * s + 2, 0x10000);
      }
      TM(10);
      bar_arrive(8, 256);
      tokens0(s + 1, Int<CH_R2>());
      TM(2);
      TR(7, clk32());
    } else {
      const uint32_t xo = l4 + (CH_SX - (t4 == 3 ? 128 : 0)), x1 = xo + (r1 + 768 + min(t4, 2) * 256), x2 = xo + (r2 + 1024 + min(t4, 2) * 256);
      if (t4 < 2) {
        float ds[4][4] = {};
        uint32_t q[16];
        asm volatile("bar.sync 1, 256;" ::: "memory");
#pragma unroll
        for (int k = 0; k < 4; k++) ldsm4(&q[4 * k], qa + k * 512);
        pin();
        if (VK < 20) { finish_v(b, dv); pin(); }
#pragma unroll
        for (int k = 0; k < 4; k++) {
          mma16(ds[k & 1], kf[4 * k], kf[4 * k + 1], kf[4 * k + 2], kf[4 * k + 3], q[4 * k], q[4 * k + 1]);
          mma16(ds[2 + (k & 1)], kf[4 * k], kf[4 * k + 1], kf[4 * k + 2], kf[4 * k + 3], q[4 * k + 2], q[4 * k + 3]);
        }
        float t[4];
#pragma unroll
        for (int i = 0; i < 4; i++) t[i] = (ds[0][i] + ds[2][i]) + (ds[1][i] + ds[3][i]);
        const uint32_t w0 = pack2(t[0], t[1]), w1 = pack2(t[2], t[3]);
        st_async32(x1, w0, bX + r1); st_async32(x2, w0, bX + r2);
        st_async32(x1 + 128, w1, bX + r1); st_async32(x2 + 128, w1, bX + r2);
        sts32(xo, w0); sts32(xo + 128, w1);
      } else {
        float ds[4][4] = {};
        uint32_t q0[4], q1[4], a0[4], a1[4];
        asm volatile("bar.sync 1, 256; " ::: "memory");
        ldsm4(a0, ka); ldsm4(q0, qa); ldsm4(a1, ka + 512); ldsm4(q1, qa + 512);
        pin();
        if (VK < 20) { finish_v(b, dv); pin(); }
        mma16(ds[0], a0[0], a0[1], a0[2], a0[3], q0[0], q0[1]);
        mma16(ds[1], a0[0], a0[1], a0[2], a0[3], q0[2], q0[3]);
        mma16(ds[2], a1[0], a1[1], a1[2], a1[3], q1[0], q1[1]);
        mma16(ds[3], a1[0], a1[1], a1[2], a1[3], q1[2], q1[3]);
        float t[2];
#pragma unroll
        for (int i = 0; i < 2; i++)
          t[i] = ((ds[0][i] + ds[0][i + 2]) + (ds[1][i] + ds[1][i + 2])) + ((ds[2][i] + ds[2][i + 2]) + (ds[3][i] + ds[3][i + 2]));
        const uint32_t w0 = pack2(t[0], t[1]);
        st_async32(x1, w0, bX + r1);
        st_async32(x2, w0, bX + r2);
        sts32(xo, w0);
      }
      TM(3);
      const uint4 id = lds128(l16 + CH_ID);
      float sc[3][4] = {};
      uint4 v[2];
      sum_v(dv);
      bar_sync(3, 128);
      uint32_t r[12], wd[12];
      ldsm4(&r[0], l16 + CH_SX); ldsm2(&r[4], l16 + CH_SX + 512);
      pin();
      v[0] = lds128(lw + CH_VT); v[1] = lds128(lw + CH_VT + 512);
#pragma unroll
      for (int u = 0; u < 3; u++) ldsm4t(&wd[4 * u], wo + u * 28672);
      pin();
#pragma unroll
      for (int q = 0; q < 3; q++) mma16(sc[q], id.x, id.y, id.z, id.w, r[2 * q], r[2 * q + 1]);
      uint32_t big = absmax2(absmax2(absmax2(r[0], r[1]), absmax2(r[2], r[3])), absmax2(r[4], r[5]));
      const uint32_t oa1 = l4 + (r1 + CH_O), oa2 = l4 + (r2 + CH_O + 2048), ones = 0x3f803f80u;
      mbar_wait_hot(bX, s & 1);
      TM(4);
      ldsm4(&r[0], l16 + CH_SX + 768); ldsm4(&r[8], l16 + CH_SX + 1792); ldsm4(&r[4], l16 + CH_SX + 1280);
      const uint2 vp = lds64(l8 + CH_VP);
      bar_arrive(10, 256);
      pin();
      {
        float sd[3][4] = {};
#pragma unroll
        for (int i = 0; i < 3; i++) {
          const int q = i == 0 ? 0 : 3 - i;
          mma16(sc[q], id.x, id.y, id.z, id.w, r[4 * q], r[4 * q + 1]);
          mma16(sd[q], id.x, id.y, id.z, id.w, r[4 * q + 2], r[4 * q + 3]);
          big = absmax2(big, absmax2(absmax2(r[4 * q], r[4 * q + 1]), absmax2(r[4 * q + 2], r[4 * q + 3])));
        }
#pragma unroll
        for (int i = 0; i < 12; i++) sc[i >> 2][i & 3] += sd[i >> 2][i & 3];
      }
      const bool redo = __any_sync(~0u, (absmax2(big, big << 16) & 0x7fff0000u) >= 0x41800000u);
      const uint2 vm = memory_v(vp, dv);
      sc[2][0] += sc[2][2]; sc[2][1] += sc[2][3];
      float l[4], o[2][4];
      uint32_t p3, p4;
      auto attend = [&]() {
#pragma unroll
        for (int i = 0; i < 4; i++) l[i] = o[0][i] = o[1][i] = 0.f;
        const uint32_t p1 = pack2(ex2(sc[0][0]), ex2(sc[0][1])), p2 = pack2(ex2(sc[0][2]), ex2(sc[0][3]));
        mma16h(o[0], p1, p2, v[0].x, v[0].y);
        mma16h(o[1], p1, p2, v[0].z, v[0].w);
        mma16h(l, p1, p2, ones, ones);
        const uint32_t p0 = pack2(ex2(sc[2][0]), ex2(sc[2][1]));
        mma8h(o[0], p0, vm.x);
        mma8h(o[1], p0, vm.y);
        mma8h(l, p0, ones);
        p3 = pack2(ex2(sc[1][0]), ex2(sc[1][1])); p4 = pack2(ex2(sc[1][2]), ex2(sc[1][3]));
        mma16h(o[0], p3, p4, v[1].x, v[1].y);
        mma16h(o[1], p3, p4, v[1].z, v[1].w);
      };
      attend();
      if (__builtin_expect(redo, 0)) {
        float mx = fmaxf(sc[2][0], sc[2][1]);
#pragma unroll
        for (int i = 0; i < 4; i++) mx = fmaxf(mx, fmaxf(sc[0][i], sc[1][i]));
        mx = fmaxf(mx, __shfl_xor_sync(~0u, mx, 1));
        mx = fmaxf(mx, __shfl_xor_sync(~0u, mx, 2));
#pragma unroll
        for (int i = 0; i < 4; i++) { sc[0][i] -= mx; sc[1][i] -= mx; }
        sc[2][0] -= mx; sc[2][1] -= mx;
        attend();
      }
      const uint32_t o0 = pack2(o[0][0], o[0][1]), o1 = pack2(o[1][0], o[1][1]);
      st_async32(oa1, o0, bO + r1); st_async32(oa2, o0, bO + r2);
      st_async32(oa1 + 128, o1, bO + r1); st_async32(oa2 + 128, o1, bO + r2);
      sts32(l4 + CH_O + 1024, o0); sts32(l4 + CH_O + 1152, o1);
      bar_arrive(2, 256);
      pin();
      TM(6);
      mma16h(l, p3, p4, ones, ones);
      float inv;
      asm("rcp.approx.ftz.f32 %0, %1;" : "=f"(inv) : "f"(l[0]));
      sts32((l8 & ~0xffu) + (lane & 28) + CH_VP, __float_as_uint(inv));
      __syncwarp();
      if (elect()) mbar_arrive(bO);
      {
        float z[2][4] = {}, y[2][4] = {};
        uint32_t we[12] = {};
        mma16(z[0], wd[0], wd[1], wd[2], wd[3], o0, o1);
        if (j == 0) {
#pragma unroll
          for (int u = 0; u < 3; u++) ldsm4t(&we[4 * u], (wo ^ 32) + u * 28672);
          mma16(y[0], we[0], we[1], we[2], we[3], o0, o1);
        }
        const float2 iv = lds64f((l8 & ~0xe0u) + CH_VP);
        uint8_t* dst = pool(pdst[0]);
        const uint32_t mask = ((l16 ^ tag) & 48) == 0;
        const uint32_t oa = qa + ((tag & 0xfffe) + CH_O - CH_QK + t4 * 256 - (t4 == 3 ? 1024 : 0));
        const uint32_t za = l16 + ((tag & 0xfffe) + (t4 >> 1) * 512 + (t4 & 1) * 8);
        pin();
        mbar_wait(bO, s & 1);
        uint32_t a[4];
        ldsm4(a, oa);
        mma16(z[0], wd[4], wd[5], wd[6], wd[7], a[0], a[1]);
        mma16(z[1], wd[8], wd[9], wd[10], wd[11], a[2], a[3]);
        if (j == 0) {
          mma16(y[0], we[4], we[5], we[6], we[7], a[0], a[1]);
          mma16(y[1], we[8], we[9], we[10], we[11], a[2], a[3]);
          sts128f(lw + CH_VT + 512, y[0][0] + y[1][0], y[0][1] + y[1][1], y[0][2] + y[1][2], y[0][3] + y[1][3]);
        }
        sts128f(lw + CH_VT, z[0][0] + z[1][0], z[0][1] + z[1][1], z[0][2] + z[1][2], z[0][3] + z[1][3]);
        bar_sync(3, 128);
        if (j == 0 || t4 < 2) {
          float2 q[4];
#pragma unroll
          for (int i = 0; i < 4; i++) q[i] = lds64f(za + CH_VT + i * 1024);
          stg_strong32(dst, pack_tag(((q[0].x + q[1].x) + (q[2].x + q[3].x)) * iv.x, ((q[0].y + q[1].y) + (q[2].y + q[3].y)) * iv.y, tag, mask));
        }
      }
      TM(2);
      if (!NOX) mbar_wait_hot(bXA, (s + 1) & 1);
      float dk[16], dw[16];
      bar_sync(5, 256);
      wg_fence();
      pass(dk, ak, Int<0>(), Int<20>());
      pass(dw, av, Int<0>(), Int<20>());
      TM(5);
      pin();
      if (CH_EX == 0) publish_v(s, v, vm);
      if (elect()) {
        mbar_expect(bG + t4 * 8, 2560);
        if (t4 == 1 && s + 2 < NSEG) { mbar_expect(bX, 1536); mbar_expect(bO, 2048); }
      }
      if (CH_KD == 0) { wg_wait<1>(); dump(dk, lw + CH_KT); }
      wg_wait<0>();
      if (CH_KD == 1) dump(dk, lw + CH_KT);
      TM(7);
      dump(dw, lw + CH_VT);
      bar_arrive(9, 256);
      pin();
#pragma unroll
      for (int k = 0; k < CH_RB; k++) ldsm4t(&tw[4 * k], wq + k * 2048);
      if (t4 < 2) {
#pragma unroll
        for (int k = CH_RB; k < CH_RC; k++) ldsm4t(&tw[4 * k], wq + k * 2048);
        const int q = t4 ? 3 : j, o = t4 ? j * 896 : 0;
        const uint8_t* src = p.pool + ((80 + st * 4 + q) * 8192 + (pages >> (st * 4 + q) & 1) * 4096 + o);
        asm volatile("bar.sync 8, 256;" ::: "memory");
        const uint32_t t1 = clk32() + CH_D2;
        if (CH_EX == 1) publish_v(s, v, vm);
        auto fetch = [&](auto n) {
          mbar_wait(bH, s & 1);
          until(t1);
          TR(4, clk32());
          if (elect())
            asm volatile("cp.async.bulk.shared::cluster.global.mbarrier::complete_tx::bytes.multicast::cluster [%0], [%1], %2, [%3], 7;"
                         :: "r"(sb + CH_M + q * 2560 + o), "l"(src), "n"(n.value), "r"(bG + q * 8) : "memory");
        };
        if (!t4) fetch(Int<2560>()); else if (j == 2) fetch(Int<768>()); else fetch(Int<896>());
      } else {
        asm volatile("bar.sync 8, 256; " ::: "memory");
        if (elect()) asm volatile("mbarrier.arrive.relaxed.cluster.shared::cluster.b64 _, [%0];" :: "r"(bH + (t4 == 2 ? r1 : r2)) : "memory");
        pin();
        if (CH_EX == 1) publish_v(s, v, vm);
#pragma unroll
        for (int k = CH_RB; k < CH_RC; k++) ldsm4t(&tw[4 * k], wq + k * 2048);
      }
      TM(9);
      pin();
#pragma unroll
      for (int k = CH_RC; k < CH_TW; k++) ldsm4t(&tw[4 * k], wq + k * 2048);
      TM(10);
    }
    if (++st == 3) st = 0;
    tag ^= 0x10001;
  }
  {
    const int s = NSEG - 1;
    float dv[16] = {};
    uint32_t b[40], kf[16];
    project(s, b, dv, kf);
    finish_v(b, dv);
    sum_v(dv);
    if (WG == 0) {
      sts64(l8 + CH_VP, pack2(dv[0], dv[1]), pack2(dv[2], dv[3]));
      bar_sync(1, 256);
      publish_k(s);
      publish_km(s);
      bulk_wait<0>();
      fence_async_global();
      bar_sync(2, 256);
      if (tid == 0) red_release(g_sync + 15 * 8 + 4, 1);
    } else {
      const uint4 v[2] = {lds128(lw + CH_VT), lds128(lw + CH_VT + 512)};
      bar_sync(1, 256);
      publish_v(s, v, memory_v(lds64(l8 + CH_VP), dv));
      bar_arrive(2, 256);
    }
  }
}

__global__ void __launch_bounds__(256, 1) chain_kernel(const __grid_constant__ ChainParams p) {
  extern __shared__ __align__(1024) uint8_t smem_raw[];
  const uint32_t sb = s2u(smem_raw);
  const int tid = threadIdx.x, warp = __shfl_sync(~0u, tid >> 5, 0), lane = tid & 31;
  const int cta = blockIdx.x, h = cta / 3, j = cta - 3 * h, colbase = cta * 64;
  const uint32_t bWo = sb + CH_BAR, bWq = bWo + 8, bXA = bWo + 24, bWk = bWo + 80, bWv = bWo + 88;
  uint32_t smid; asm("mov.u32 %0, %%smid;" : "=r"(smid));
  PRO(0);
  if (sb != mapa(CH_BASE, j)) __trap();
  uint32_t entry = 0;
  auto place = [&]() {
    const int i = tid - 128;
    if (i >= 0 && i <= NSLOT) {
      const uint32_t side = ldg_strong32(g_smpart + (smid & 255));
      if (i < NSLOT) {
        entry = i * 8192 + (ldg_strong32(g_orient + i) == (i < 80 ? i & 1 : side) ? 0 : 4096);
      } else {
        entry = 2 * (atomicAdd(g_bo + p.layer * 128 + 1, 1 << 8 * side) >> 8 * side & 255) + side;
      }
    }
    __syncwarp();
  };
  if (p.layer) place();
  if (warp == 0 && elect()) {
#pragma unroll 1
    for (int i = 0; i < 17; i++) mbar_init(bWo + 8 * i, i == 2 || i == 5 ? 5 : i == 3 || i == 4 ? 4 : i == 12 ? 2 : 1);
    asm volatile("fence.mbarrier_init.release.cluster;" ::: "memory");
    mbar_expect(bWk, 81920);
    tma_load3<(WEF & 1) != 0>(sb + CH_WQ, &p.wk, colbase, 0, bWk);
    mbar_expect(bWv, 81920);
    tma_load3<(WEF & 1) != 0>(sb + CH_WO, &p.wv, colbase, 0, bWv);
    mbar_expect(bWo + 16, 1536);
    mbar_expect(bWo + 40, 2048);
    mbar_expect(bWo, 86016); mbar_expect(bWq, 81920);
#pragma unroll 1
    for (int i = 0; i < 8; i++) mbar_expect(bXA + 8 * (i & 1), 5120);
  }
  if (warp == 1) {
    const uint32_t id = (lane >> 3) == (lane & 3) ? ((lane & 4) ? 0x3f800000u : 0x00003f80u) : 0u;
    sts128(sb + CH_ID + lane * 16, make_uint4(id, 0, 0, id));
  }
  __syncthreads();
  asm volatile("barrier.cluster.arrive.relaxed.aligned;" ::: "memory");
  uint32_t ak[80], av[80];
  const uint32_t wq = opaque(sb + CH_WQ + ((warp >> 2) * 320 + (lane & 7) + (lane >> 4) * 8) * 128 + (((2 * (warp & 3) + ((lane >> 3) & 1)) ^ (lane & 7)) << 4));
  pdl_wait();
  if (tid == 32) stg_strong32(g_smuse + (smid & 255), p.layer + 1);
  pdl_launch();
  PRO(1);
  if (warp == 0 && elect()) {
    bulk_load(sb + CH_X + 20480, p.xc + 5120, 20480, bXA);
    bulk_load(sb + CH_X, p.xc, 20480, bXA + 8);
  }
  if (!p.layer) place();
  __syncwarp();
  PRO(2);
  mbar_wait(bWk, 0);
  PRO(3);
#pragma unroll
  for (int k = 0; k < 20; k++) ldsm4t(&ak[4 * k], wq + k * 2048);
  bar_sync(6, 256);
  if (warp == 0 && elect()) tma_load3<(WEF & 2) != 0>(sb + CH_WQ, &p.wq, colbase, 0, bWq);
  __syncwarp();
  PRO(4);
  mbar_wait(bWv, 0);
  PRO(5);
#pragma unroll
  for (int k = 0; k < 20; k++) ldsm4t(&av[4 * k], wq + CH_WO + k * 2048);
  bar_sync(6, 256);
  PRO(6);
  if (warp >= 5 && elect()) tma_load3<(WEF & 2) != 0>(sb + CH_WO + (warp - 5) * 28672, &p.wo, j == 0 ? 0 : 32 + j * 192, h * 192 + (j + 8 - warp) % 3 * 64, bWo);
  if (tid == 128 + NSLOT && entry >= 80) {
    uint32_t c;
    int n = 0;
    do { c = ldg_strong32(g_bo + p.layer * 128 + 1); spin_guard(n); } while ((c & 255) + (c >> 8) < 96);
    const uint32_t other = (c >> 8 * (~entry & 1) & 255) + (entry >> 1) - 40;
    entry = other < 40 ? 2 * other + (~entry & 1) : entry % 80;
  }
  if (tid >= 128 && tid <= 128 + NSLOT) sts32(sb + CH_O + (tid - 128) * 4, entry);
  PRO(7);
  __syncthreads();
  if (__shfl_sync(~0u, tid >> 7, 0) == 0) chain_body<0>(p, wq, ak, av); else chain_body<1>(p, wq, ak, av);
}

struct PostParams { CUtensorMap wq, wo, wb, wo2, wb2; int gap, share, layer, look, gap2, pol; };
constexpr int PS = 8, PB = 28672;
constexpr int OP_SMEM = PS * PB + 512 + 2048;
enum { IT_ATT = 0, IT_OP = 1, IT_FIN = 2, IT_BQ = 3, IT_Q = 4 };

__device__ __forceinline__ uint32_t item_count(int type, int b) {
  return type == IT_ATT ? 32 : type == IT_OP ? op_split(b) * (DM / op_width(b)) : type == IT_FIN ? fin_items(b) : 1920 / bq_width(b); }
__device__ __forceinline__ uint32_t item_need(int type, int b) { return type == IT_ATT ? 96 : item_count(type - 1, b); }

struct Ring {
  uint32_t sb, bars; int st; uint32_t ph;
  __device__ __forceinline__ uint32_t wait() const { mbar_wait(bars + 8 * st, ph); return sb + st * PB; }
  __device__ __forceinline__ void next() { if (++st == PS) { st = 0; ph ^= 1; } }
  __device__ __forceinline__ void release(int s) const { if ((threadIdx.x & 31) == 0) mbar_arrive(bars + 8 * (PS + s)); }
  __device__ __forceinline__ void pop() { __syncwarp(); release(st); next(); }
};

template <int N>
__device__ __forceinline__ void gemm_item(Ring& r, float* d, int nst, uint32_t go, int go_at) {
  int prev = 0;
#pragma unroll 1
  for (int kb = 0; kb < nst; kb++) {
    const uint32_t base = r.wait();
    const uint64_t da = mkdesc(base + (threadIdx.x >> 7) * 4096, 128, 512, 0), db = mkdesc(base + 8192, 4096, 1024, 1);
    wg_fence();
#pragma unroll
    for (int kk = 0; kk < 2; kk++) {
      if (N == 80) wg_ss80_01(d, da + kk * 16, db + kk * 128, (kb | kk) != 0);
      if (N == 160) wg_ss160_01(d, da + kk * 16, db + kk * 128, (kb | kk) != 0);
      if (N >= 192) wg_ss192_01(d, da + kk * 16, db + kk * 128, (kb | kk) != 0);
      if (N == 320) wg_ss128_01(d + 96, da + kk * 16, db + kk * 128 + 3 * 256, (kb | kk) != 0);
    }
    wg_commit();
    if (kb == go_at && threadIdx.x == 0) mbar_arrive(go);
    if (kb > 0) { wg_wait<1>(); r.release(prev); }
    prev = r.st;
    r.next();
  }
  wg_wait<0>();
  reg_fence<N / 2>(d);
  r.release(prev);
}

template <int HALF>
__device__ __forceinline__ void attn_a_warp(Ring& r, const uint32_t (&q)[48], int b, int h) {
  constexpr int NT = HALF ? 5 : 3, NF = 8 * NT;
  const int lane = threadIdx.x & 31, g = lane >> 2, c = lane & 3, seg = (threadIdx.x >> 5) & 3;
  uint32_t f[6][NF];
  int slot[6];
  auto fetch = [&](int u) {
    const uint32_t kv = r.wait() + seg * KV_BYTES;
    slot[u] = r.st;
    r.next();
#pragma unroll
    for (int w = 0; w < 4; w++) {
      uint32_t* d = &f[u][2 * NT * w];
#pragma unroll
      for (int t = 0; t <= HALF; t++) {
        if (u < 3) {
          ldsm4(d + 4 * t, kv + w * 1024 + t * 512 + (lane & 8) * 32 + (lane & 16) * 8 + (lane & 7) * 16);
        } else {
          const uint4 v = lds128(kv + w * 1024 + t * 512 + lane * 16);
          d[4 * t] = v.x; d[4 * t + 1] = v.y; d[4 * t + 2] = v.z; d[4 * t + 3] = v.w;
        }
      }
      const uint2 m = lds64(kv + KV_M + w * 256 + lane * 8);
      d[2 * NT - 2] = m.x; d[2 * NT - 1] = m.y;
    }
    pdl_launch();
  };
  float s[NT][4] = {};
  fetch(0);
#pragma unroll
  for (int u = 0; u < 3; u++) {
    fetch(u + 1);
#pragma unroll
    for (int kk = 0; kk < 4; kk++) {
      const uint32_t* a = &q[16 * u + 4 * kk];
#pragma unroll
      for (int n = 0; n < NT; n++) mma16(s[(n + 1) % NT], a[0], a[1], a[2], a[3], f[u][2 * NT * kk + 2 * n], f[u][2 * NT * kk + 2 * n + 1]);
    }
    r.release(slot[u]);
    pdl_launch();
  }
  fetch(4);
  const float k2 = 0.07216878364870322f * 1.44269504089f, NEG = -INFINITY;
  if (2 * c > g) { s[NT - 2][0] = NEG; s[NT - 1][2] = NEG; }
  if (2 * c + 1 > g) { s[NT - 2][1] = NEG; s[NT - 1][3] = NEG; }
  s[NT - 1][0] = s[NT - 1][1] = NEG;
  uint32_t pp[NT][2]; float inv[2];
#pragma unroll
  for (int hh = 0; hh < 2; hh++) {
    float m = NEG, l = 0.f;
#pragma unroll
    for (int n = 0; n < NT; n++) m = fmaxf(m, fmaxf(s[n][2 * hh], s[n][2 * hh + 1]));
    m = fmaxf(m, __shfl_xor_sync(~0u, m, 1)); m = fmaxf(m, __shfl_xor_sync(~0u, m, 2));
#pragma unroll
    for (int n = 0; n < NT; n++) { const float x = ex2((s[n][2 * hh] - m) * k2), y = ex2((s[n][2 * hh + 1] - m) * k2); l += x + y; pp[n][hh] = pack2(x, y); }
    l += __shfl_xor_sync(~0u, l, 1); l += __shfl_xor_sync(~0u, l, 2);
    asm("rcp.approx.ftz.f32 %0, %1;" : "=f"(inv[hh]) : "f"(l));
  }
  uint32_t* dst = g_o + ((b * 192 + h * 6) * 16 + seg * 4 + HALF * 2) * 128 + lane;
#pragma unroll
  for (int u = 3; u < 6; u++) {
    float o[8][4] = {};
#pragma unroll
    for (int n = 0; n < 8; n++) mma8(o[n], pp[0][0], pp[0][1], f[u][2 * NT * (n >> 1) + 2 * NT - 2 + (n & 1)]);
#pragma unroll
    for (int t = 0; t <= HALF; t++)
#pragma unroll
      for (int n = 0; n < 8; n++) {
        const uint32_t* v = &f[u][2 * NT * (n >> 1) + 4 * t + 2 * (n & 1)];
        mma16(o[n], pp[1 + 2 * t][0], pp[1 + 2 * t][1], pp[2 + 2 * t][0], pp[2 + 2 * t][1], v[0], v[1]);
      }
    r.release(slot[u]);
    if (u == 3) fetch(5);
#pragma unroll
    for (int n = 0; n < 8; n++) {
      dst[(u - 3) * 4096 + (n >> 2) * 2048 + (n & 3) * 32] = pack2(o[n][0] * inv[0], o[n][1] * inv[0]);
      dst[(u - 3) * 4096 + (n >> 2) * 2048 + (n & 3) * 32 + 128] = pack2(o[n][2] * inv[1], o[n][3] * inv[1]);
    }
  }
}

template <int NG>
__device__ __forceinline__ void fin_item(Ring& r, uint32_t scratch, int b, int idx) {
  const int warp = threadIdx.x >> 5, lane = threadIdx.x & 31;
  float4* x = g_x + ((b * 16 + idx * NG) * 40 + warp * 5) * 32 + lane;
  float4 v[NG][5];
#pragma unroll
  for (int g = 0; g < NG; g++) {
    const uint32_t base = r.wait();
#pragma unroll
    for (int i = 0; i < 5; i++) v[g][i] = lds128f(base + ((warp * 5 + i) * 32 + lane) * 16);
    r.pop();
  }
#pragma unroll 1
  for (int k = 0; k < op_split(b); k += NG == 1 ? 2 : 1) {
#pragma unroll
    for (int g = 0; g < NG; g += 2) {
      const uint32_t base = r.wait();
#pragma unroll
      for (int i = 0; i < 10; i++) {
        const uint2 q = lds64(base + ((i / 5 * 40 + warp * 5 + i % 5) * 32 + lane) * 8);
        float4& t = v[(g + i / 5) % NG][i % 5];
        t.x += bf_lo(q.x); t.y += bf_hi(q.x); t.z += bf_lo(q.y); t.w += bf_hi(q.y);
      }
      r.pop();
    }
  }
  float mean[NG], rs[NG];
  ln_stats<NG>(v, scratch, mean, rs);
#pragma unroll
  for (int i = 0; i < 5; i++) {
    const int u = warp * 5 + i;
    uint32_t* xn = g_xn + ((b * 20 + (u >> 1)) * 16 + idx * NG) * 128 + (u & 1) * 64 + lane;
#pragma unroll
    for (int g = 0; g < NG; g++) {
      xn[g * 128] = pack2((v[g][i].x - mean[g]) * rs[g], (v[g][i].y - mean[g]) * rs[g]);
      xn[g * 128 + 32] = pack2((v[g][i].z - mean[g]) * rs[g], (v[g][i].w - mean[g]) * rs[g]);
    }
  }
#pragma unroll
  for (int g = 0; g < NG; g++)
#pragma unroll
    for (int i = 0; i < 5; i++) x[(g * 40 + i) * 32] = v[g][i];
}

__global__ void __launch_bounds__(384, 1) post_kernel(const __grid_constant__ PostParams p) {
  extern __shared__ __align__(1024) uint8_t smem_raw[];
  const uint32_t sb = s2u(smem_raw), bars = sb + PS * PB;
  const uint32_t bIF = bars + 128, bIE = bars + 160, done = bars + 192, bGo = bars + 224, slots = bars + 240, scratch = bars + 512;
  const int warp = __shfl_sync(~0u, threadIdx.x >> 5, 0), lane = threadIdx.x & 31;
  TRACE(0);
  pdl_launch();
  if (sb & 1023) __trap();
  if (threadIdx.x < 29) mbar_init(bars + 8 * threadIdx.x, threadIdx.x < 8 ? 1 : threadIdx.x < 16 ? 8 : threadIdx.x < 20 ? 1 : threadIdx.x < 24 ? 2 : threadIdx.x < 28 ? 8 : 1);
  fence_async();
  __syncthreads();
  if (warp >= 8) {
    asm volatile("setmaxnreg.dec.sync.aligned.u32 56;");
    if (warp == 9) {
      const int b = lane & 15;
      bool queries = QA_END < 16 && blockIdx.x < 36;
      for (int n = 0;; n++) {
        if (n > 0) mbar_wait(bGo, (n - 1) & 1);
        mbar_wait(bIE + 8 * (n & 3), ((n >> 2) & 1) ^ 1);
        int code = -1, spin = 0, ticket = 0;
        if (queries) {
          if (lane == 0) ticket = atomicAdd(g_sync + SY_QC, 1);
          ticket = __shfl_sync(~0u, ticket, 0);
          queries = ticket < (16 - QA_END) * 32;
          if (queries) code = IT_Q << 16 | (QA_END + ticket % (16 - QA_END)) << 8 | ticket / (16 - QA_END);
        }
        if (!queries && lane == 0) ticket = atomicAdd(g_sync + SY_T, 1);
        while (!queries) {
          const uint4 hd = ldg_strong128(g_sync + b * 8), pr = ldg_strong128(g_sync + b * 8 + 4);
          const uint32_t hv[4] = {hd.x, hd.y, hd.z, hd.w}, pv[4] = {pr.x, pr.y, pr.z, pr.w};
          const uint32_t chain_done = __ballot_sync(~0u, (pr.x & 0xffff) >= 96) & 0xffff;
          int left[4], avail[4], rdy = 0, claimed = 0, upstream = 0;
#pragma unroll
          for (int t = 0; t < 4; t++) {
            const int cnt = lane < 16 ? item_count(t, b) : 0;
            left[t] = max(cnt - (int)hv[t], 0);
            claimed += cnt - left[t];
            const bool ready = (pv[t] & 0xffff) >= item_need(t, b);
            rdy |= ready << t;
            bool ok = ready || (t == IT_ATT ? pr.x >= 0x10000 : !upstream || (t == IT_OP && (chain_done >> 15 & 1)));
            if (t == IT_BQ && (chain_done >> BQ_HOLD & 1) && !(chain_done >> 15)) ok = false;
            avail[t] = ok ? left[t] : 0;
            upstream |= __any_sync(~0u, left[t] > 0);
          }
          if (!upstream) break;
          int rank = max(__shfl_sync(~0u, ticket, 0) - __reduce_add_sync(~0u, claimed), 0), type = -1, mine = 0;
#pragma unroll
          for (int c = 0; c < 8; c++) {
            const int t = c == 0 || c == 5 ? IT_FIN : c == 1 || c == 7 ? IT_ATT : c == 2 || c == 4 ? IT_OP : IT_BQ;
            int a = c == 1 || ((rdy >> t & 1) == (c < 4)) ? avail[t] : 0;
            if (t == IT_OP && !(p.pol & 1)) a = c == 2 ? avail[t] : 0;
            if (c == 7) a = b < QA_END && !(rdy & 1) && ((chain_done << 1 | 1) >> b & 1) ? left[t] : 0;
            const int tot = __reduce_add_sync(~0u, a);
            if (type < 0) { if (rank < tot) { type = t; mine = a; } else rank -= tot; }
          }
          if (type >= 0) {
#pragma unroll
            for (int o = 1; o < 16; o <<= 1) { const int y = __shfl_up_sync(~0u, mine, o); if (lane >= o) mine += y; }
            const int blk = __ffs(__ballot_sync(~0u, mine > rank)) - 1;
            const int early = !(__shfl_sync(~0u, rdy, blk) >> type & 1);
            uint32_t idx = 0;
            if (lane == 0) { idx = atomicAdd(g_sync + blk * 8 + type, 1); ld_acquire(g_sync + blk * 8 + 4 + type); }
            idx = __shfl_sync(~0u, idx, 0);
            if (idx < item_count(type, blk)) { code = (chain_done >> 15 & 1) << 22 | (chain_done >> p.look & 1) << 21 | early << 20 | type << 16 | blk << 8 | idx; break; }
          } else {
            __nanosleep(50);
          }
          spin_guard(spin);
        }
        if (lane == 0) {
          fence_async_global();
          sts32(slots + 4 * (n & 3), code);
          mbar_arrive(bIF + 8 * (n & 3));
        }
        __syncwarp();
        if (code < 0) break;
      }
    } else if (warp == 8) {
      uint32_t smid, nsm, peers = 0;
      asm("mov.u32 %0, %%smid;" : "=r"(smid)); asm("mov.u32 %0, %%nsmid;" : "=r"(nsm));
      for (uint32_t i = lane; i < min(nsm, 256u); i += 32)
        peers += abs((int)(g_smclk[i] - g_smclk[smid & 255])) < 4000 && ldg_strong32(g_smuse + i) != p.layer + 1;
      const uint32_t gap0 = max(p.gap, (int)min(__reduce_add_sync(~0u, peers), 18u) * p.share >> 3);
      if (elect()) {
        uint32_t dst = sb, bar = bars, ph = 1, next = clk32(), gap = 0;
        auto acquire = [&](uint32_t kb) {
          mbar_wait(bar + 8 * PS, ph);
          mbar_expect(bar, kb * 1024);
          if (gap) {
            uint32_t now;
            do now = clk32(); while ((int)(now - next) < 0);
            next = ((int)(now - next) > 100 ? now - 100 : next) + kb * gap;
          }
        };
        auto advance = [&]() { dst += PB; bar += 8; if (dst == bars) { dst = sb; bar = bars; ph ^= 1; } };
        auto depend = [&](const uint32_t* c, uint32_t need) { wait_count(c, need); fence_async_global(); };
#pragma unroll 1
        for (int n = 0;; n++) {
          mbar_wait(bIF + 8 * (n & 3), (n >> 2) & 1);
          const int code = (int)lds32(slots + 4 * (n & 3));
          if (code < 0) break;
          const int type = (code >> 16) & 15, b = (code >> 8) & 255, idx = code & 255;
          const bool early = code >> 20 & 1, go = !(code >> 21 & 1);
          mbar_arrive(bIE + 8 * (n & 3));
          gap = !(code >> 22 & 1) ? gap0 : type == IT_ATT || type == IT_FIN ? 0 : p.gap2;
          const uint32_t* progress = g_sync + b * 8 + 4 + type;
          if (type == IT_ATT && b >= QA_END) {
            depend(g_sync + SY_Q, (16 - QA_END) * 32);
#pragma unroll 1
            for (int u = 0; u < 2; u++) { acquire(24); bulk_load_last(dst, g_q + (((b - QA_END) * 32 + idx) * 2 + u) * 1536, 24576, bar); advance(); }
          } else if (type == IT_FIN) {
            const int ng = 16 / fin_items(b), lg = ng >> 1;
#pragma unroll 1
            for (int g = 0; g < ng; g++) { acquire(20); bulk_load(dst, g_x + (b * 16 + idx * ng + g) * 1280, 20480, bar); advance(); }
            if (early) depend(progress, item_need(type, b));
            if (go) mbar_arrive(bGo);
#pragma unroll 1
            for (int i = 0; i < op_split(b) * ng; i += 2) {
              const uint2* src = g_part + ((b * 16 + (i >> lg)) * 16 + idx * ng + (i & (ng - 1))) * 1280;
              acquire(20);
              bulk_load_last(dst, src, ng > 1 ? 20480 : 10240, bar);
              if (ng == 1) bulk_load_last(dst + 10240, src + 16 * 1280, 10240, bar);
              advance();
            }
          } else {
            const bool op = type == IT_OP, bq = type == IT_BQ;
            const int width = op ? op_width(b) : bq ? bq_width(b) : 192, nb = (width + 63) >> 6, lt = width == 320 ? 1 : 2;
            const int nst = op ? 192 / op_split(b) : 20, kb0 = op ? (idx >> lt) * nst : 0;
            const int col = (op ? idx & ((1 << lt) - 1) : idx) * width;
            const bool whole = !(width & 63);
            const CUtensorMap* m = op ? (whole ? &p.wo : &p.wo2) : bq ? (whole ? &p.wb : &p.wb2) : &p.wq;
            const uint32_t* a = op ? g_o + (b * 192 + kb0) * 2048 : g_xn + b * 20 * 2048;
            int row = kb0 * 32, pre = early && (op || bq) ? min(nst, PS) : 0;
            auto weights = [&]() {
              acquire(8 + nb * 4);
              if (whole) {
                tma_load3z(dst + 8192, m, row, col >> 6, bar);
              } else {
                tma_load(dst + 8192, m, col, row, bar); tma_load(dst + 12288, m, col + 64, row, bar);
                if (nb == 3) tma_load(dst + 16384, m, col + 128, row, bar);
              }
              row += 32;
            };
            if (pre) {
              uint32_t da = dst, ba = bar;
#pragma unroll 1
              for (int kb = 0; kb < pre; kb++) { weights(); advance(); }
              depend(progress, item_need(type, b));
#pragma unroll 1
              for (int kb = 0; kb < pre; kb++) {
                bulk_load(da, a, 8192, ba);
                a += 2048; da += PB; ba += 8;
                if (da == bars) { da = sb; ba = bars; }
              }
            }
#pragma unroll 1
            for (int kb = pre; kb < nst; kb++) { weights(); if (op && OEF) bulk_load_last(dst, a, 8192, bar); else bulk_load(dst, a, 8192, bar); a += 2048; advance(); }
          }
          if (type == IT_ATT) {
            if (early) depend(progress, 96);
            if (go) mbar_arrive(bGo);
            const uint8_t* src = g_kv + (size_t)(idx * 6 * NSEG + b * 4) * KV_BYTES;
#pragma unroll 1
            for (int u = 0; u < 6; u++) {
              acquire(20);
              bulk_load_last(dst, src, 20480, bar);
              src += u == 2 ? -3 * KV_V : 2 * KV_V;
              advance();
            }
          }
        }
      }
    } else if (warp == 10 && lane == 0) {
      for (int n = 0;; n++) {
        mbar_wait(bIF + 8 * (n & 3), (n >> 2) & 1);
        const int code = (int)lds32(slots + 4 * (n & 3));
        if (code < 0) break;
        const int type = (code >> 16) & 15, b = (code >> 8) & 255;
        mbar_wait(done + 8 * (n & 3), (n >> 2) & 1);
        if (type != IT_BQ) red_release(type == IT_Q ? g_sync + SY_Q : g_sync + b * 8 + 5 + type, 1);
        mbar_arrive(bIE + 8 * (n & 3));
      }
    }
  } else {
    asm volatile("setmaxnreg.inc.sync.aligned.u32 224;");
    const int g = lane >> 2, c = lane & 3;
    Ring r = {sb, bars, 0, 0};
#pragma unroll 1
    for (int n = 0;; n++) {
      mbar_wait(bIF + 8 * (n & 3), (n >> 2) & 1);
      const int code = __shfl_sync(~0u, (int)lds32(slots + 4 * (n & 3)), 0);
      if (code < 0) { TRACE(2); break; }
      const int type = (code >> 16) & 15, b = (code >> 8) & 255, idx = code & 255;
      ITEM(code & 0xfffff, 0);
      if (type == IT_ATT || type == IT_Q) {
        uint32_t q[48];
        if (type == IT_Q || b < QA_END) {
          float d[96] = {};
          reg_fence<96>(d);
          gemm_item<192>(r, d, 20, bGo, type == IT_Q ? 12 : -1);
#pragma unroll
          for (int i = 0; i < 48; i++) q[i] = pack2(d[2 * i], d[2 * i + 1]);
        } else {
#pragma unroll
          for (int u = 0; u < 2; u++) {
            const uint32_t base = r.wait() + threadIdx.x * 16;
#pragma unroll
            for (int i = 0; i < 6; i++) {
              const uint4 v = lds128(base + i * 4096);
              q[24 * u + 4 * i] = v.x; q[24 * u + 4 * i + 1] = v.y; q[24 * u + 4 * i + 2] = v.z; q[24 * u + 4 * i + 3] = v.w;
            }
            r.pop();
          }
        }
        if (type == IT_Q) {
          uint4* dst = g_q + ((b - QA_END) * 32 + idx) * 3072 + threadIdx.x;
#pragma unroll
          for (int i = 0; i < 12; i++) dst[i * 256] = make_uint4(q[4 * i], q[4 * i + 1], q[4 * i + 2], q[4 * i + 3]);
        } else if (warp < 4) {
          attn_a_warp<0>(r, q, b, idx);
        } else {
          attn_a_warp<1>(r, q, b, idx);
        }
      } else if (type == IT_FIN) {
        if (fin_items(b) == 4) fin_item<4>(r, scratch, b, idx);
        else if (fin_items(b) == 8) fin_item<2>(r, scratch, b, idx);
        else fin_item<1>(r, scratch, b, idx);
      } else {
        float d[160] = {};
        reg_fence<160>(d);
        const int width = type == IT_OP ? op_width(b) : bq_width(b), nst = type == IT_OP ? 192 / op_split(b) : 20;
        const int go_at = code >> 21 & 1 ? -1 : max(nst - 6, 0);
        if (width == 320) gemm_item<320>(r, d, nst, bGo, go_at);
        else if (width == 160 || BQ_80 == 16) gemm_item<160>(r, d, nst, bGo, go_at);
        else gemm_item<80>(r, d, nst, bGo, go_at);
        reg_fence<160>(d);
        if (type == IT_OP) {
          const int tiles = DM / width;
          uint2* dst = g_part + (((b * 16 + idx / tiles) * 16 + warp * 2) * 40 + idx % tiles * (width / 16)) * 32 + lane;
#pragma unroll
          for (int u = 0; u < 20; u++) {
            if (u % 5 == 0 && u * 16 >= width) break;
            dst[u * 32] = make_uint2(pack2(d[8 * u], d[8 * u + 1]), pack2(d[8 * u + 4], d[8 * u + 5]));
            dst[(40 + u) * 32] = make_uint2(pack2(d[8 * u + 2], d[8 * u + 3]), pack2(d[8 * u + 6], d[8 * u + 7]));
          }
        } else {
          const int row = b * 128 + warp * 16 + g;
          const int h0 = idx * (width / 20);
          const float sc = h0 < 32 ? 0.22360679775f * 1.44269504089f : 1.f;
          const bool lo = c < 2;
          uint32_t* da = g_bqkv + (h0 * 256 + (row >> 3)) * 96 + lane;
          uint32_t* db = da + 256 * 96 + (lo ? 2 : -2);
          uint32_t pad[2];
#pragma unroll
          for (int rr = 0; rr < 2; rr++) pad[rr] = !(c & 1) && (h0 >= 64 || (h0 >= 32 && (row & 1) && poly_group((row >> 3) + rr))) ? 0x00003f80u : 0u;
#pragma unroll
          for (int q = 0; q < 8; q++) {
            if (!(q & 1) && q * 40 >= width) break;
#pragma unroll
            for (int rr = 0; rr < 2; rr++) {
              uint32_t w[5];
#pragma unroll
              for (int i = 0; i < 5; i++) w[i] = pack2(d[20 * q + 4 * i + 2 * rr] * sc, d[20 * q + 4 * i + 2 * rr + 1] * sc);
              const int o = q * 2 * 256 * 96 + rr * 96;
              da[o] = w[0]; da[o + 32] = w[1]; da[o + 64] = lo ? w[2] : pad[rr];
              db[o] = lo ? w[3] : w[2]; db[o + 32] = lo ? w[4] : w[3]; db[o + 64] = lo ? pad[rr] : w[4];
            }
          }
        }
      }
      __syncwarp();
      if (lane == 0) mbar_arrive(done + 8 * (n & 3));
      if ((code >> 21 & 1) && threadIdx.x == 128) mbar_arrive(bGo);
      ITEM(code & 0xfffff, 1);
    }
  }
}

constexpr int AB_SMEM = 1024 + 98304 + 51200 + 4 * 16384 + 256;
#define AB_N 32
#define AB_WG 4
constexpr int AB_T = AB_WG * 128, AB_PASS = 8 / AB_WG;
__device__ __forceinline__ float ex2_poly(float t) {
  const uint32_t r = __float_as_uint(t) & 0xffff8000u;
  const float f = t - __uint_as_float(r);
  const float p = fmaf(fmaf(fmaf(-5.869912678e-38f, f, -1.700740250e-37f), f, -5.234869734e-37f), f, -7.522601252e-37f);
  uint32_t y;
  asm("mad.lo.u32 %0, %1, 256, %2;" : "=r"(y) : "r"(r), "r"(__float_as_uint(p)));
  return __uint_as_float(y);
}
__device__ __forceinline__ float sq2(uint32_t w) { const float a = bf_lo(w), b = bf_hi(w); return fmaf(a, a, b * b); }

__device__ __forceinline__ void attn_b_store(const float* o, int h, int row0, int lane) {
  const int g = lane >> 2, c = lane & 3;
  const float i0 = 1.f / __shfl_sync(~0u, o[8], (lane & ~3) | 2), i1 = 1.f / __shfl_sync(~0u, o[10], (lane & ~3) | 2);
#pragma unroll
  for (int jj = 0; jj < 3; jj++) {
    if (jj < 2 || c < 2) {
      const int col = h * 20 + 8 * jj + 2 * c;
      uint32_t* dst = g_of + (((row0 >> 7) * 10 + (col >> 6)) * 16 + (row0 >> 3 & 15)) * 256 + (col >> 3 & 7) * 32 + g * 4 + (col >> 1 & 3);
      dst[0] = pack2(o[4 * jj] * i0, o[4 * jj + 1] * i0);
      dst[256] = pack2(o[4 * jj + 2] * i1, o[4 * jj + 3] * i1);
    }
  }
}

__device__ __forceinline__ void attn_b_qk(float* s, uint32_t q0, uint32_t q1, uint32_t q2, uint32_t q3, uint32_t q4, uint32_t q5, uint32_t z0, uint32_t z1,
                                          uint64_t dk, uint64_t dk2) {
  wg_rs32_00(s, q0, q1, q2, q3, dk, 0);
  wg_rs32_00(s, q4, q5, z0, z1, dk2, 1);
}

struct AbParams { Weights next; uint32_t* done; uint32_t* out; };
__global__ void __launch_bounds__(AB_T + 32, 1) attn_b_kernel(const __grid_constant__ AbParams p) {
  extern __shared__ uint8_t smem_raw[];
  const uint32_t sb = (s2u(smem_raw) + 1023) & ~1023u, sK = sb, sV = sb + 98304, bars = sV + 51200 + 4 * 16384;
  const uint32_t bF = bars + 64, bW = bars + 72, bA = bars + 80, bE = bars + 128, smax = bars + 176;
  auto ring = [&](int i) { return i < 2 ? sK + 51200 + i * 16384 : sV + 51200 + (i - 2) * 16384; };
  const int warp = __shfl_sync(~0u, threadIdx.x >> 5, 0), lane = threadIdx.x & 31;
  const int h = blockIdx.x >> 2, quarter = blockIdx.x & 3;
  TRACE(0);
  pdl_launch();
  pdl_wait();
  if (blockIdx.x < NSLOT) for (int i = threadIdx.x; i < 512; i += AB_T + 32) reinterpret_cast<uint4*>(pool_at(blockIdx.x * 8192))[i] = make_uint4(0, 0, 0, 0);
  if (blockIdx.x == 31) for (int i = threadIdx.x; i < SY_N; i += AB_T + 32) g_sync[i] = 0;
  if (threadIdx.x == 0) {
    for (int i = 0; i < 22; i++) mbar_init(bars + 8 * i, i == 8 ? AB_T / 32 : i >= 16 ? 8 : 1);
    sts64(smax, 0, 0);
    fence_async();
    const uint8_t* gk = reinterpret_cast<const uint8_t*>(g_bqkv + (32 + h) * 256 * 96);
    const uint8_t* gv = reinterpret_cast<const uint8_t*>(g_bqkv + (64 + h) * 256 * 96);
    for (int i = 0; i < 8; i++) {
      mbar_expect(bars + 8 * i, 24576);
      bulk_load_last(sK + i * 12288, gk + i * 12288, 12288, bars + 8 * i);
      bulk_load_last(sV + i * 12288, gv + i * 12288, 12288, bars + 8 * i);
    }
  }
  __syncthreads();
  const int blk = quarter * 4 + (h >> 3), cg = h & 7;
  auto unsafe = [&]() { const float2 m = lds64f(smax); return !(m.x * m.y <= 10000.f); };
  if (warp == AB_T / 32) {
    auto load_w = [&]() {
      mbar_expect(bW, 102400);
      for (int i = 0; i < 4; i++) bulk_load((i < 2 ? sK : sV) + (i & 1) * 25600, g_wb + cg * 6400 + i * 1600, 25600, bW);
    };
    if (p.next.w[0] && lane == 0) {
      mbar_wait(bars + 56, 0);
      for (int i = 0; i < AB_PF; i++) { const uint32_t t0 = clk32(); while (clk32() - t0 < (i ? AB_PFD : AB_PF0)) __nanosleep(200); prefetch_weights(p.next, i); }
    }
    __syncwarp();
    mbar_wait(bF, 0);
    const bool redo = unsafe();
    if (!redo && lane == 0) load_w();
    __syncwarp();
    bar_sync(1, AB_T + 32);
    if (lane == 0) {
      ABT(!!p.out, 1);
      red_release(p.done + quarter * 32, 1);
      ABT(!!p.out, 2);
      if (redo) load_w();
      wait_count(p.done + quarter * 32, 32);
      fence_async_global();
      ABT(!!p.out, 3);
      for (int kb = 0; kb < 10; kb++) {
        const int i = kb < 6 ? kb : kb - 6;
        if (kb >= 6) mbar_wait(bE + 8 * i, 0);
        mbar_expect(bA + 8 * i, 16384);
        bulk_load(ring(i), g_of + (blk * 10 + kb) * 4096, 16384, bA + 8 * i);
      }
    }
    return;
  }
  float qmax = 0.f;
  constexpr int NT = SEQ / AB_N, PER = 256 / AB_N;
#pragma unroll 1
  for (int pass = 0; pass < AB_PASS; pass++) {
    const int row0 = quarter * 512 + ((warp >> 2) * AB_PASS + pass) * 64 + (warp & 3) * 16;
    const uint32_t* gq = g_bqkv + (h * 256 + (row0 >> 3)) * 96 + lane;
    const uint32_t q0 = gq[0], q1 = gq[96], q2 = gq[32], q3 = gq[128];
    uint32_t q4 = gq[64], q5 = gq[160];
    const uint32_t z0 = gq[64 + 3 - (lane & 3)], z1 = gq[160 + 3 - (lane & 3)];
    {
      float n0 = sq2(q0) + sq2(q2) + sq2(q4), n1 = sq2(q1) + sq2(q3) + sq2(q5);
      n0 += __shfl_xor_sync(~0u, n0, 1); n1 += __shfl_xor_sync(~0u, n1, 1);
      n0 += __shfl_xor_sync(~0u, n0, 2); n1 += __shfl_xor_sync(~0u, n1, 2);
      qmax = (n0 > qmax || n0 != n0) ? n0 : qmax;
      qmax = (n1 > qmax || n1 != n1) ? n1 : qmax;
    }
    if (pass == AB_PASS - 1) {
      float kmax = 0.f;
#pragma unroll
      for (int i = 0; i < SEQ / AB_T; i++) {
        const int key = threadIdx.x + AB_T * i;
        const uint32_t a = sK + (key >> 3) * 384 + (key & 7) * 16;
        const uint4 x = lds128(a), y = lds128(a + 128);
        const uint2 z = lds64(a + 256);
        const float n = ((sq2(x.x) + sq2(x.y)) + (sq2(x.z) + sq2(x.w))) + ((sq2(y.x) + sq2(y.y)) + (sq2(y.z) + sq2(y.w))) + (sq2(z.x) + sq2(z.y));
        kmax = (n > kmax || n != n) ? n : kmax;
      }
      const uint32_t kb = __reduce_max_sync(~0u, __float_as_uint(kmax) & 0x7fffffffu), qb = __reduce_max_sync(~0u, __float_as_uint(qmax) & 0x7fffffffu);
      if (lane < 2) asm volatile("red.shared.max.u32 [%0], %1;" :: "r"(smax + 4 * lane), "r"(lane ? kb : qb) : "memory");
      __syncwarp();
    }
    if ((lane & 3) == 2) { q4 = 0x43BCu; q5 = 0x43BCu; }
    float o[12];
    uint64_t dk = mkdesc(sK, 128, 384, 0), dk2 = mkdesc(sK + 256, 0, 384, 0), dv = mkdesc(sV, 384, 128, 0);
    float sa[AB_N / 2], sb2[AB_N / 2];
    uint32_t pa[AB_N / 4], pb[AB_N / 4];
    if (pass == 0) mbar_wait(bars, 0);
    wg_fence();
    attn_b_qk(sa, q0, q1, q2, q3, q4, q5, z0, z1, dk, dk2);
    wg_commit();
    attn_b_qk(sb2, q0, q1, q2, q3, q4, q5, z0, z1, dk + AB_N * 3, dk2 + AB_N * 3);
    wg_commit();
#pragma unroll 1
    for (int kt = 0; kt < NT; kt += 2) {
      const int nx = kt + 2 < NT ? kt + 2 : 0;
      if (pass == 0 && (nx & (PER - 1)) == 0) mbar_wait(bars + 8 * (nx / PER), 0);
      const uint64_t nk = dk + nx * (AB_N * 3), nk2 = dk2 + nx * (AB_N * 3);
      wg_wait<1>();
      if (pass == AB_PASS - 1 && kt == NT * 5 / 8 + 2 && lane == 0) mbar_arrive(bF);
      reg_fence<AB_N / 2>(sa);
#pragma unroll
      for (int i = 0; i < AB_N / 4; i++) pa[i] = pack2(ex2(sa[2 * i]), poly_group(i >> 1) ? ex2_poly(sa[2 * i + 1]) : ex2(sa[2 * i + 1]));
      wg_fence();
#pragma unroll
      for (int kk = 0; kk < AB_N / 16; kk++) wg_rs24_01(o, pa[4 * kk], pa[4 * kk + 1], pa[4 * kk + 2], pa[4 * kk + 3], dv + kk * 48, kk | kt);
      attn_b_qk(sa, q0, q1, q2, q3, q4, q5, z0, z1, nk, nk2);
      wg_commit();
      wg_wait<1>();
      reg_fence<AB_N / 2>(sb2);
#pragma unroll
      for (int i = 0; i < AB_N / 4; i++) pb[i] = pack2(ex2(sb2[2 * i]), poly_group((i >> 1) + AB_N / 8) ? ex2_poly(sb2[2 * i + 1]) : ex2(sb2[2 * i + 1]));
      wg_fence();
#pragma unroll
      for (int kk = 0; kk < AB_N / 16; kk++) wg_rs24_01(o, pb[4 * kk], pb[4 * kk + 1], pb[4 * kk + 2], pb[4 * kk + 3], dv + AB_N * 3 + kk * 48, 1);
      attn_b_qk(sb2, q0, q1, q2, q3, q4, q5, z0, z1, nk + AB_N * 3, nk2 + AB_N * 3);
      wg_commit();
      dv += AB_N * 6;
    }
    wg_wait<0>();
    reg_fence<12>(o); reg_fence<AB_N / 2>(sa); reg_fence<AB_N / 2>(sb2);
    attn_b_store(o, h, row0, lane);
  }
  mbar_wait(bF, 0);
  if (unsafe())
#pragma unroll 1
  for (int pass = 0; pass < AB_PASS; pass++) {
    const int row0 = quarter * 512 + ((warp >> 2) * AB_PASS + pass) * 64 + (warp & 3) * 16;
    const uint32_t* gq = g_bqkv + (h * 256 + (row0 >> 3)) * 96 + lane;
    const uint32_t q0 = gq[0], q1 = gq[96], q2 = gq[32], q3 = gq[128], q4 = gq[64], q5 = gq[160];
    float o[12];
#pragma unroll
    for (int i = 0; i < 12; i++) o[i] = 0.f;
    float m0 = -INFINITY, m1 = -INFINITY;
#pragma unroll 1
    for (int kt = 0; kt < 32; kt++) {
      float s[32];
      const uint64_t dk = mkdesc(sK + kt * 3072, 128, 384, 0), dk2 = mkdesc(sK + kt * 3072 + 256, 0, 384, 0);
      wg_fence();
      wg_rs64_00(s, q0, q1, q2, q3, dk, 0);
      wg_rs64_00(s, q4, q5, 0, 0, dk2, 1);
      wg_commit();
      wg_wait<0>();
      reg_fence<32>(s); reg_fence<12>(o);
      float n0 = m0, n1 = m1;
#pragma unroll
      for (int jj = 0; jj < 8; jj++) { n0 = fmaxf(n0, fmaxf(s[4 * jj], s[4 * jj + 1])); n1 = fmaxf(n1, fmaxf(s[4 * jj + 2], s[4 * jj + 3])); }
      n0 = fmaxf(n0, __shfl_xor_sync(~0u, n0, 1)); n0 = fmaxf(n0, __shfl_xor_sync(~0u, n0, 2));
      n1 = fmaxf(n1, __shfl_xor_sync(~0u, n1, 1)); n1 = fmaxf(n1, __shfl_xor_sync(~0u, n1, 2));
      const float r0 = ex2(m0 - n0), r1 = ex2(m1 - n1);
      m0 = n0; m1 = n1;
#pragma unroll
      for (int jj = 0; jj < 3; jj++) { o[4 * jj] *= r0; o[4 * jj + 1] *= r0; o[4 * jj + 2] *= r1; o[4 * jj + 3] *= r1; }
      uint32_t pp[16];
#pragma unroll
      for (int jj = 0; jj < 8; jj++) {
        pp[2 * jj] = pack2(ex2(s[4 * jj] - m0), ex2(s[4 * jj + 1] - m0));
        pp[2 * jj + 1] = pack2(ex2(s[4 * jj + 2] - m1), ex2(s[4 * jj + 3] - m1));
      }
      const uint64_t dv = mkdesc(sV + kt * 3072, 384, 128, 0);
      wg_fence();
#pragma unroll
      for (int kk = 0; kk < 4; kk++) wg_rs24_01(o, pp[4 * kk], pp[4 * kk + 1], pp[4 * kk + 2], pp[4 * kk + 3], dv + kk * 48, 1);
      wg_commit();
    }
    wg_wait<0>();
    reg_fence<12>(o);
    attn_b_store(o, h, row0, lane);
  }
  ABT(!!p.out, 0);
  bar_arrive(1, AB_T + 32);
  if (warp >= 8) return;
  const int g = lane >> 2, c = lane & 3;
  float d[40];
  float4* x = g_x + ((blk * 16 + warp * 2) * 40 + cg * 5) * 32 + lane;
#pragma unroll
  for (int i = 0; i < 10; i++) {
    const int r = i / 5, u = i % 5;
    const float4 t = x[(r * 40 + u) * 32];
    d[8 * u + 2 * r] = t.x; d[8 * u + 2 * r + 1] = t.y; d[8 * u + 4 + 2 * r] = t.z; d[8 * u + 5 + 2 * r] = t.w;
  }
  mbar_wait(bW, 0);
  reg_fence<40>(d);
  ABT(!!p.out, 4);
#pragma unroll 1
  for (int kb = 0; kb < 10; kb++) {
    const int i = kb < 6 ? kb : kb - 6;
    mbar_wait(bA + 8 * i, kb >= 6);
    const uint64_t da = mkdesc(ring(i) + (warp >> 2) * 8192, 128, 1024, 0), db = mkdesc(kb < 5 ? sK + kb * 10240 : sV + (kb - 5) * 10240, 1280, 128, 0);
    wg_fence();
#pragma unroll
    for (int kk = 0; kk < 4; kk++) wg_ss80_01(d, da + kk * 16, db + kk * 160, 1);
    wg_commit();
    if (kb > 0 && kb < 5) { wg_wait<1>(); if (lane == 0) mbar_arrive(bE + 8 * (kb - 1)); }
  }
  wg_wait<0>();
  reg_fence<40>(d);
  ABT(!!p.out, 5);
  if (p.out) {
    uint32_t* out = p.out + (blk * 128 + warp * 16 + g) * (DM / 2) + cg * 40 + c;
#pragma unroll
    for (int i = 0; i < 20; i++) out[(i & 1) * 8 * (DM / 2) + (i >> 1) * 4] = pack2(d[2 * i], d[2 * i + 1]);
  } else {
    float2* stat = g_stat + blk * 1024 + warp * 16 + g;
    float mean[2], rs[2];
#pragma unroll
    for (int r = 0; r < 2; r++) {
      float t = 0.f, q = 0.f;
#pragma unroll
      for (int i = 0; i < 10; i++) t += d[4 * i + 2 * r] + d[4 * i + 2 * r + 1];
      t += __shfl_xor_sync(~0u, t, 1); t += __shfl_xor_sync(~0u, t, 2);
      t *= 1.f / 80;
#pragma unroll
      for (int i = 0; i < 10; i++) { const float a = d[4 * i + 2 * r] - t, b = d[4 * i + 2 * r + 1] - t; q += a * a + b * b; }
      q += __shfl_xor_sync(~0u, q, 1); q += __shfl_xor_sync(~0u, q, 2);
      if (c == r) asm volatile("st.relaxed.gpu.global.v2.b32 [%0], {%1, %2};" :: "l"(stat + cg * 128 + r * 8), "r"(__float_as_uint(t)), "r"(nz(__float_as_uint(q))) : "memory");
    }
#pragma unroll
    for (int i = 0; i < 10; i++) {
      const int r = i / 5, u = i % 5;
      x[(r * 40 + u) * 32] = make_float4(d[8 * u + 2 * r], d[8 * u + 2 * r + 1], d[8 * u + 4 + 2 * r], d[8 * u + 5 + 2 * r]);
    }
    ABT(0, 6);
    uint2 e[4];
    int n = 0;
    do {
#pragma unroll
      for (int i = 0; i < 4; i++)
        asm volatile("ld.relaxed.gpu.global.v2.b32 {%0, %1}, [%2];" : "=r"(e[i].x), "=r"(e[i].y) : "l"(stat + (2 * c + (i & 1)) * 128 + (i >> 1) * 8) : "memory");
      spin_guard(n);
    } while (__any_sync(~0u, min(min(e[0].y, e[1].y), min(e[2].y, e[3].y)) == 0));
#pragma unroll
    for (int r = 0; r < 2; r++) {
      const float m0 = __uint_as_float(e[2 * r].x), m1 = __uint_as_float(e[2 * r + 1].x);
      float t = m0 + m1;
      t += __shfl_xor_sync(~0u, t, 1); t += __shfl_xor_sync(~0u, t, 2);
      t *= 0.125f;
      float q = __uint_as_float(e[2 * r].y) + __uint_as_float(e[2 * r + 1].y) + 80.f * ((m0 - t) * (m0 - t) + (m1 - t) * (m1 - t));
      q += __shfl_xor_sync(~0u, q, 1); q += __shfl_xor_sync(~0u, q, 2);
      mean[r] = t; rs[r] = rsqrtf(q * (1.f / DM) + 1e-5f);
    }
    ABT(0, 7);
    uint32_t w[2][5][2];
#pragma unroll
    for (int i = 0; i < 20; i++) w[i & 1][i >> 2][i >> 1 & 1] = pack2((d[2 * i] - mean[i & 1]) * rs[i & 1], (d[2 * i + 1] - mean[i & 1]) * rs[i & 1]);
    ln_store(w, blk * 8 + warp, cg * 5);
  }
  ABT(!!p.out, 8);
  TRACE(2);
}

typedef CUresult (*EncodeFn)(CUtensorMap*, CUtensorMapDataType, cuuint32_t, void*, const cuuint64_t*, const cuuint64_t*,
                             const cuuint32_t*, const cuuint32_t*, CUtensorMapInterleave, CUtensorMapSwizzle,
                             CUtensorMapL2promotion, CUtensorMapFloatOOBfill);

void make_map(EncodeFn enc, CUtensorMap* m, const void* ptr, int cols, int rows, int nb) {
  const cuuint64_t dims[3] = {(cuuint64_t)(nb ? 64 : cols), (cuuint64_t)rows, (cuuint64_t)cols / 64};
  const cuuint64_t strides[2] = {(cuuint64_t)cols * 2, 128};
  const cuuint32_t box[3] = {64, 32, (cuuint32_t)nb}, es[3] = {1, 1, 1};
  enc(m, CU_TENSOR_MAP_DATA_TYPE_BFLOAT16, nb ? 3 : 2, const_cast<void*>(ptr), dims, strides, box, es, CU_TENSOR_MAP_INTERLEAVE_NONE,
      CU_TENSOR_MAP_SWIZZLE_128B, CU_TENSOR_MAP_L2_PROMOTION_L2_128B, CU_TENSOR_MAP_FLOAT_OOB_FILL_NONE);
}
template <class... KA, class... A>
void launch(void (*kern)(KA...), int grid, int block, int smem, int cluster, bool pdl, A... args) {
  cudaFuncSetAttribute(kern, cudaFuncAttributeMaxDynamicSharedMemorySize, smem);
  cudaLaunchConfig_t cfg = {};
  cfg.gridDim = dim3(grid); cfg.blockDim = dim3(block); cfg.dynamicSmemBytes = smem; cfg.stream = cudaStreamPerThread;
  cudaLaunchAttribute at[2];
  int n = 0;
  if (cluster > 1) { at[n].id = cudaLaunchAttributeClusterDimension; at[n].val.clusterDim.x = cluster; at[n].val.clusterDim.y = 1; at[n].val.clusterDim.z = 1; n++; }
  if (pdl) { at[n].id = cudaLaunchAttributeProgrammaticStreamSerialization; at[n].val.programmaticStreamSerializationAllowed = 1; n++; }
  cfg.attrs = at; cfg.numAttrs = n;
  cudaLaunchKernelEx(&cfg, kern, args...);
}
template <class T> void* sym(T& s) { void* p = nullptr; cudaGetSymbolAddress(&p, s); return p; }

}

#define MODE(b) 0
extern "C" void kernel_launch(void* const* d_in, const int* in_sizes, int n_in, void* d_out, int out_size) {
  const __nv_bfloat16* x = (const __nv_bfloat16*)d_in[0];
  void* fn = nullptr; cudaDriverEntryPointQueryResult qr;
  cudaGetDriverEntryPoint("cuTensorMapEncodeTiled", &fn, cudaEnableDefault, &qr);
  EncodeFn enc = (EncodeFn)fn;

  ChainParams ch = {};
  PostParams op = {};
  for (int i = 0; i < 3; i++) {
    const cuuint64_t dims[3] = {HD, 128, 5}, strides[2] = {HD * 2, HD * 256};
    const cuuint32_t box[3] = {64, 128, 5}, es[3] = {1, 1, 1};
    enc(i == 0 ? &ch.wq : i == 1 ? &ch.wk : &ch.wv, CU_TENSOR_MAP_DATA_TYPE_BFLOAT16, 3, d_in[2 + i], dims, strides, box, es, CU_TENSOR_MAP_INTERLEAVE_NONE,
        CU_TENSOR_MAP_SWIZZLE_128B, W_PROMO, CU_TENSOR_MAP_FLOAT_OOB_FILL_NONE);
  }
  {
    const cuuint64_t dims[3] = {DM, HD, 7}, strides[2] = {DM * 2, 64};
    const cuuint32_t box[3] = {32, 64, 7}, es[3] = {1, 1, 1};
    enc(&ch.wo, CU_TENSOR_MAP_DATA_TYPE_BFLOAT16, 3, d_in[5], dims, strides, box, es, CU_TENSOR_MAP_INTERLEAVE_NONE,
        CU_TENSOR_MAP_SWIZZLE_64B, CU_TENSOR_MAP_L2_PROMOTION_L2_128B, CU_TENSOR_MAP_FLOAT_OOB_FILL_NONE);
  }
  ch.mem0 = (const __nv_bfloat16*)d_in[1];
  ch.pool = (uint8_t*)(((uintptr_t)sym(g_pool) + 8191) & ~(uintptr_t)8191); ch.kv = (uint8_t*)sym(g_kv); ch.xc = (const uint32_t*)sym(g_xc); ch.sync = (uint32_t*)sym(g_sync);
  ch.d1 = 0; ch.d1b = 0; ch.d2 = 0; ch.d2b = 0;
  make_map(enc, &op.wq, d_in[2], HD, DM, 3);
  make_map(enc, &op.wo, d_in[5], DM, HD, 5); make_map(enc, &op.wo2, d_in[5], DM, HD, 0);
  make_map(enc, &op.wb, d_in[8], 1920, DM, 5); make_map(enc, &op.wb2, d_in[8], 1920, DM, 0);
  op.gap = 17; op.share = 20; op.look = 14; op.gap2 = 0; op.pol = 0;

  const Weights wa = {{(const uint8_t*)d_in[3], (const uint8_t*)d_in[4], (const uint8_t*)d_in[2], (const uint8_t*)d_in[5]}}, none = {};
  launch(first_kernel, 132, 256, 128 * 1024, 1, false, x, (const uint4*)d_in[9], wa);
  for (int layer = 0; layer < 2; layer++) {
    ch.layer = ch.d2b = op.layer = layer;
    launch(chain_kernel, 96, 256, CH_SMEM, 3, true, ch);
    launch(post_kernel, MODE(3) ? 36 : 132, 384, OP_SMEM, 1, !MODE(1), op);
    const AbParams ab = {layer == 0 ? wa : none, (uint32_t*)sym(g_bo) + layer * 128, layer == 0 ? nullptr : (uint32_t*)d_out};
    launch(attn_b_kernel, 128, AB_T + 32, AB_SMEM, 1, true, ab);
  }
}
```

```cpp
#include <cuda_runtime.h>
#include <cuda_bf16.h>
#include <cuda.h>
#include <stdint.h>

namespace {

constexpr int SEQ = 2048, DM = 640, HD = 6144, NSEG = 64;
constexpr int SPIN_LIMIT = 1 << 20;

__device__ __align__(128) float4 g_x[SEQ * DM / 4];
__device__ __align__(128) uint32_t g_of[SEQ * DM / 2];
__device__ __align__(128) uint4 g_wb[DM * DM / 8];
__device__ __align__(16) float2 g_stat[16 * 8 * 128];
__device__ uint32_t g_bo[8 * 32];
__device__ __align__(128) uint4 g_q[SEQ * HD / 8];
__device__ __align__(128) uint32_t g_o[SEQ * HD / 2];
constexpr int KV_BYTES = 5120, KV_M = 4096, KV_V = NSEG * KV_BYTES;
__device__ __align__(128) uint8_t g_kv[96 * 2 * NSEG * KV_BYTES];
__device__ __align__(128) uint32_t g_xc[SEQ * DM / 2];
#define OP_B4 0
#define OP_B8 10
#define OP_B16 15
#define QA_END 12
__host__ __device__ constexpr int op_split(int b) { return b < OP_B4 ? 2 : b < OP_B8 ? 4 : b < OP_B16 ? 8 : 16; }
__host__ __device__ constexpr int fin_items(int b) { return b < OP_B8 ? 4 : op_split(b); }
#define AB_PF 2
#define AB_PF0 30000
#define AB_PFD 7000
#define W_PROMO CU_TENSOR_MAP_L2_PROMOTION_L2_128B
#define OEF 0
#define BQ_HOLD 12
#define WEF 1
#define FK_PF 1
#define BQ_160 10
#define BQ_80 16
#define OP_160 16
__host__ __device__ constexpr int op_width(int b) { return b < OP_160 ? 320 : 160; }
__host__ __device__ constexpr int bq_width(int b) { return b < BQ_160 ? 320 : b < BQ_80 ? 160 : 80; }
__device__ __align__(128) uint2 g_part[16 * 16 * 16 * 40 * 32];
__device__ __align__(128) uint32_t g_xn[SEQ * DM / 2];
constexpr int SY_Q = 128, SY_T = 160, SY_QC = 192, SY_N = 193;
__device__ __align__(16) uint32_t g_sync[SY_N];
constexpr int NSLOT = 92;
__device__ uint32_t g_pool[(NSLOT + 2) * 2048];
__device__ int g_smpart[256], g_orient[NSLOT];
__device__ uint32_t g_smclk[256], g_smuse[256];
__device__ uint32_t g_bqkv[3 * 32 * 256 * 96];

#define ABT(L, i)
#define MODE_D(b) 0
#define DELAY(d)
#define XT(i)
#define MISS(k, n)
#define PRO(i)
#define TRACE(w)
#define ITEM(code, w)
#define TR(i, v)
#define TM(i)
#define TM1(i)
#define TMD(i, dep)
#define TMV(i, at, v)

__device__ __forceinline__ uint32_t gtime() { uint32_t c; asm volatile("mov.u32 %0, %%globaltimer_lo;" : "=r"(c) :: "memory"); return c; }
__device__ __forceinline__ uint32_t clk32() { uint32_t c; asm volatile("mov.u32 %0, %%clock;" : "=r"(c) :: "memory"); return c; }
__device__ __forceinline__ uint32_t s2u(const void* p) { return (uint32_t)__cvta_generic_to_shared(p); }
__device__ __forceinline__ uint32_t pack2(float a, float b) {
  uint32_t r; asm("cvt.rn.bf16x2.f32 %0, %1, %2;" : "=r"(r) : "f"(b), "f"(a)); return r; }
__device__ __forceinline__ float bf_lo(uint32_t w) { return __uint_as_float(w << 16); }
__device__ __forceinline__ float bf_hi(uint32_t w) { return __uint_as_float(w & 0xffff0000u); }
__device__ __forceinline__ float ex2(float x) { float y; asm("ex2.approx.ftz.f32 %0, %1;" : "=f"(y) : "f"(x)); return y; }

__device__ __forceinline__ void mbar_init(uint32_t bar, uint32_t n) {
  asm volatile("mbarrier.init.shared::cta.b64 [%0], %1;" :: "r"(bar), "r"(n) : "memory"); }
__device__ __forceinline__ void mbar_expect(uint32_t bar, uint32_t bytes) {
  asm volatile("mbarrier.arrive.expect_tx.shared::cta.b64 _, [%0], %1;" :: "r"(bar), "r"(bytes) : "memory"); }
__device__ __forceinline__ void mbar_arrive(uint32_t bar) {
  asm volatile("mbarrier.arrive.shared::cta.b64 _, [%0];" :: "r"(bar) : "memory"); }
__device__ __forceinline__ void mbar_wait(uint32_t bar, uint32_t ph) {
  asm volatile("{.reg .pred p; .reg .u32 n; mov.u32 n, 0;\n"
               "W: mbarrier.try_wait.parity.shared::cta.b64 p, [%0], %1; @p bra D;\n"
               "add.u32 n, n, 1; setp.gt.u32 p, n, %2; @p trap; bra W;\n"
               "D: }" :: "r"(bar), "r"(ph), "n"(SPIN_LIMIT) : "memory");
}
__device__ __forceinline__ void mbar_wait_cluster(uint32_t bar, uint32_t ph) {
  asm volatile("{.reg .pred p; .reg .u32 n; mov.u32 n, 0;\n"
               "W: mbarrier.try_wait.parity.acquire.cluster.shared::cta.b64 p, [%0], %1; @p bra D;\n"
               "add.u32 n, n, 1; setp.gt.u32 p, n, %2; @p trap; bra W;\n"
               "D: }" :: "r"(bar), "r"(ph), "n"(SPIN_LIMIT) : "memory");
}
__device__ __forceinline__ void spin_guard(int& n) {
  asm volatile("{.reg .pred p; add.s32 %0, %0, 1; setp.gt.s32 p, %0, %1; @p trap;}" : "+r"(n) : "n"(SPIN_LIMIT));
}
__device__ __forceinline__ void pdl_wait() { asm volatile("griddepcontrol.wait;" ::: "memory"); TRACE(1); }
__device__ __forceinline__ void pdl_launch() { asm volatile("griddepcontrol.launch_dependents;" ::: "memory"); }
__device__ __forceinline__ uint32_t ld_acquire(const uint32_t* p) { uint32_t v; asm volatile("ld.acquire.gpu.global.u32 %0, [%1];" : "=r"(v) : "l"(p) : "memory"); return v; }
__device__ __forceinline__ void red_release(uint32_t* p, uint32_t v) { asm volatile("red.release.gpu.global.add.u32 [%0], %1;" :: "l"(p), "r"(v) : "memory"); }
__device__ __forceinline__ void red_relaxed(uint32_t* p, uint32_t v) { asm volatile("red.relaxed.gpu.global.add.u32 [%0], %1;" :: "l"(p), "r"(v) : "memory"); }
__device__ __forceinline__ void fence_async_global() { asm volatile("fence.proxy.async.global;" ::: "memory"); }
__device__ __forceinline__ void fence_async() { asm volatile("fence.proxy.async.shared::cta;" ::: "memory"); }
__device__ __forceinline__ void bar_sync(int id, int n) { asm volatile("bar.sync %0, %1;" :: "r"(id), "r"(n) : "memory"); }
__device__ __forceinline__ void bar_arrive(int id, int n) { asm volatile("bar.arrive %0, %1;" :: "r"(id), "r"(n) : "memory"); }
__device__ __forceinline__ void tma_load(uint32_t dst, const CUtensorMap* m, int c0, int c1, uint32_t bar) {
  asm volatile("cp.async.bulk.tensor.2d.shared::cluster.global.mbarrier::complete_tx::bytes [%0], [%1, {%3, %4}], [%2];"
               :: "r"(dst), "l"(m), "r"(bar), "r"(c0), "r"(c1) : "memory"); }
template <bool STREAM = false>
__device__ __forceinline__ void tma_load3(uint32_t dst, const CUtensorMap* m, int c0, int c1, uint32_t bar) {
  if (STREAM)
    asm volatile("{.reg .b64 pol; createpolicy.fractional.L2::evict_first.b64 pol, 1.0;\n"
                 "cp.async.bulk.tensor.3d.shared::cluster.global.mbarrier::complete_tx::bytes.L2::cache_hint [%0], [%1, {%3, %4, 0}], [%2], pol;}"
                 :: "r"(dst), "l"(m), "r"(bar), "r"(c0), "r"(c1) : "memory");
  else
  asm volatile("cp.async.bulk.tensor.3d.shared::cluster.global.mbarrier::complete_tx::bytes [%0], [%1, {%3, %4, 0}], [%2];"
               :: "r"(dst), "l"(m), "r"(bar), "r"(c0), "r"(c1) : "memory"); }
__device__ __forceinline__ void tma_load3z(uint32_t dst, const CUtensorMap* m, int c1, int c2, uint32_t bar) {
  asm volatile("cp.async.bulk.tensor.3d.shared::cluster.global.mbarrier::complete_tx::bytes [%0], [%1, {0, %3, %4}], [%2];"
               :: "r"(dst), "l"(m), "r"(bar), "r"(c1), "r"(c2) : "memory"); }
__device__ __forceinline__ void tma_store(const CUtensorMap* m, uint32_t src, int c0, int c1) {
  asm volatile("cp.async.bulk.tensor.2d.global.shared::cta.bulk_group [%0, {%2, %3}], [%1];"
               :: "l"(m), "r"(src), "r"(c0), "r"(c1) : "memory"); }
__device__ __forceinline__ void tma_store_stream(const CUtensorMap* m, uint32_t src, int c0, int c1) {
  asm volatile("{.reg .b64 pol; createpolicy.fractional.L2::evict_first.b64 pol, 1.0;\n"
               "cp.async.bulk.tensor.2d.global.shared::cta.bulk_group.L2::cache_hint [%0, {%2, %3}], [%1], pol;}"
               :: "l"(m), "r"(src), "r"(c0), "r"(c1) : "memory"); }
__device__ __forceinline__ void bulk_load(uint32_t dst, const void* src, uint32_t bytes, uint32_t bar) {
  asm volatile("cp.async.bulk.shared::cluster.global.mbarrier::complete_tx::bytes [%0], [%1], %2, [%3];"
               :: "r"(dst), "l"(src), "r"(bytes), "r"(bar) : "memory"); }
__device__ __forceinline__ void bulk_load_last(uint32_t dst, const void* src, uint32_t bytes, uint32_t bar) {
  asm volatile("{.reg .b64 pol; createpolicy.fractional.L2::evict_first.b64 pol, 1.0;\n"
               "cp.async.bulk.shared::cluster.global.mbarrier::complete_tx::bytes.L2::cache_hint [%0], [%1], %2, [%3], pol;}"
               :: "r"(dst), "l"(src), "r"(bytes), "r"(bar) : "memory"); }
__device__ __forceinline__ void tma_load_last(uint32_t dst, const CUtensorMap* m, int c0, int c1, uint32_t bar) {
  asm volatile("{.reg .b64 pol; createpolicy.fractional.L2::evict_first.b64 pol, 1.0;\n"
               "cp.async.bulk.tensor.2d.shared::cluster.global.mbarrier::complete_tx::bytes.L2::cache_hint [%0], [%1, {%3, %4}], [%2], pol;}"
               :: "r"(dst), "l"(m), "r"(bar), "r"(c0), "r"(c1) : "memory"); }
__device__ __forceinline__ void bulk_send(uint32_t dst, uint32_t src, uint32_t bytes, uint32_t bar) {
  asm volatile("cp.async.bulk.shared::cluster.shared::cta.mbarrier::complete_tx::bytes [%0], [%1], %2, [%3];"
               :: "r"(dst), "r"(src), "r"(bytes), "r"(bar) : "memory"); }
__device__ __forceinline__ void bulk_store(void* dst, uint32_t src, uint32_t bytes) {
  asm volatile("cp.async.bulk.global.shared::cta.bulk_group [%0], [%1], %2;" :: "l"(dst), "r"(src), "r"(bytes) : "memory"); }
__device__ __forceinline__ void bulk_commit() { asm volatile("cp.async.bulk.commit_group;" ::: "memory"); }
template <int N> __device__ __forceinline__ void bulk_wait_read() { asm volatile("cp.async.bulk.wait_group.read %0;" :: "n"(N) : "memory"); }
template <int N> __device__ __forceinline__ void bulk_wait() { asm volatile("cp.async.bulk.wait_group %0;" :: "n"(N) : "memory"); }

__device__ __forceinline__ uint64_t mkdesc(uint32_t addr, uint32_t lbo, uint32_t sbo, uint32_t sw) {
  return (uint64_t)((addr & 0x3FFFF) >> 4) | ((uint64_t)(lbo >> 4) << 16) | ((uint64_t)(sbo >> 4) << 32) | ((uint64_t)sw << 62); }
__device__ __forceinline__ void wg_fence() { asm volatile("wgmma.fence.sync.aligned;" ::: "memory"); }
__device__ __forceinline__ void wg_commit() { asm volatile("wgmma.commit_group.sync.aligned;" ::: "memory"); }
template <int N> __device__ __forceinline__ void wg_wait() { asm volatile("wgmma.wait_group.sync.aligned %0;" :: "n"(N) : "memory"); }
template <int N> __device__ __forceinline__ void reg_fence(float* d) {
#pragma unroll
  for (int i = 0; i < N; i++) asm volatile("" : "+f"(d[i]) :: "memory");
}

__device__ __forceinline__ void mma16(float* d, uint32_t a0, uint32_t a1, uint32_t a2, uint32_t a3, uint32_t b0, uint32_t b1) {
  asm volatile("mma.sync.aligned.m16n8k16.row.col.f32.bf16.bf16.f32 {%0,%1,%2,%3},{%4,%5,%6,%7},{%8,%9},{%0,%1,%2,%3};"
               : "+f"(d[0]), "+f"(d[1]), "+f"(d[2]), "+f"(d[3]) : "r"(a0), "r"(a1), "r"(a2), "r"(a3), "r"(b0), "r"(b1)); }
__device__ __forceinline__ void mma8(float* d, uint32_t a0, uint32_t a1, uint32_t b0) {
  asm volatile("mma.sync.aligned.m16n8k8.row.col.f32.bf16.bf16.f32 {%0,%1,%2,%3},{%4,%5},{%6},{%0,%1,%2,%3};"
               : "+f"(d[0]), "+f"(d[1]), "+f"(d[2]), "+f"(d[3]) : "r"(a0), "r"(a1), "r"(b0)); }
__device__ __forceinline__ void ldsm4(uint32_t* r, uint32_t a) {
  asm volatile("ldmatrix.sync.aligned.m8n8.x4.shared.b16 {%0,%1,%2,%3},[%4];" : "=r"(r[0]), "=r"(r[1]), "=r"(r[2]), "=r"(r[3]) : "r"(a) : "memory"); }
__device__ __forceinline__ void ldsm4t(uint32_t* r, uint32_t a) {
  asm volatile("ldmatrix.sync.aligned.m8n8.x4.trans.shared.b16 {%0,%1,%2,%3},[%4];" : "=r"(r[0]), "=r"(r[1]), "=r"(r[2]), "=r"(r[3]) : "r"(a) : "memory"); }
__device__ __forceinline__ void ldsm2(uint32_t* r, uint32_t a) {
  asm volatile("ldmatrix.sync.aligned.m8n8.x2.shared.b16 {%0,%1},[%2];" : "=r"(r[0]), "=r"(r[1]) : "r"(a) : "memory"); }
__device__ __forceinline__ void stsm4(uint32_t a, uint32_t r0, uint32_t r1, uint32_t r2, uint32_t r3) {
  asm volatile("stmatrix.sync.aligned.m8n8.x4.shared.b16 [%0], {%1,%2,%3,%4};" :: "r"(a), "r"(r0), "r"(r1), "r"(r2), "r"(r3) : "memory"); }
__device__ __forceinline__ void stsm2t(uint32_t a, uint32_t r0, uint32_t r1) {
  asm volatile("stmatrix.sync.aligned.m8n8.x2.trans.shared.b16 [%0], {%1,%2};" :: "r"(a), "r"(r0), "r"(r1) : "memory"); }
__device__ __forceinline__ void stsm4t(uint32_t a, uint32_t r0, uint32_t r1, uint32_t r2, uint32_t r3) {
  asm volatile("stmatrix.sync.aligned.m8n8.x4.trans.shared.b16 [%0], {%1,%2,%3,%4};" :: "r"(a), "r"(r0), "r"(r1), "r"(r2), "r"(r3) : "memory"); }
__device__ __forceinline__ void st_async128(uint32_t a, uint4 v, uint32_t bar) {
  asm volatile("st.async.shared::cluster.mbarrier::complete_tx::bytes.v4.b32 [%0], {%1,%2,%3,%4}, [%5];" :: "r"(a), "r"(v.x), "r"(v.y), "r"(v.z), "r"(v.w), "r"(bar) : "memory"); }
__device__ __forceinline__ void sts32(uint32_t a, uint32_t v) { asm volatile("st.shared.b32 [%0], %1;" :: "r"(a), "r"(v) : "memory"); }
__device__ __forceinline__ void sts64f(uint32_t a, float x, float y) { asm volatile("st.shared.v2.f32 [%0], {%1,%2};" :: "r"(a), "f"(x), "f"(y) : "memory"); }
__device__ __forceinline__ void sts128(uint32_t a, uint4 v) {
  asm volatile("st.shared.v4.b32 [%0], {%1,%2,%3,%4};" :: "r"(a), "r"(v.x), "r"(v.y), "r"(v.z), "r"(v.w) : "memory"); }
__device__ __forceinline__ void sts128f(uint32_t a, float x, float y, float z, float w) {
  asm volatile("st.shared.v4.f32 [%0], {%1,%2,%3,%4};" :: "r"(a), "f"(x), "f"(y), "f"(z), "f"(w) : "memory"); }
__device__ __forceinline__ float lds32f(uint32_t a) { float v; asm volatile("ld.shared.f32 %0, [%1];" : "=f"(v) : "r"(a) : "memory"); return v; }
__device__ __forceinline__ float2 lds64f(uint32_t a) { float2 v; asm volatile("ld.shared.v2.f32 {%0,%1}, [%2];" : "=f"(v.x), "=f"(v.y) : "r"(a) : "memory"); return v; }
__device__ __forceinline__ float4 lds128f(uint32_t a) {
  float4 v; asm volatile("ld.shared.v4.f32 {%0,%1,%2,%3}, [%4];" : "=f"(v.x), "=f"(v.y), "=f"(v.z), "=f"(v.w) : "r"(a) : "memory"); return v; }
__device__ __forceinline__ uint4 lds128(uint32_t a) {
  uint4 v; asm volatile("ld.shared.v4.b32 {%0,%1,%2,%3}, [%4];" : "=r"(v.x), "=r"(v.y), "=r"(v.z), "=r"(v.w) : "r"(a) : "memory"); return v; }
__device__ __forceinline__ uint4 ldg_strong128(const void* p) {
  uint4 v; asm volatile("ld.relaxed.gpu.global.v4.u32 {%0,%1,%2,%3}, [%4];" : "=r"(v.x), "=r"(v.y), "=r"(v.z), "=r"(v.w) : "l"(p) : "memory"); return v; }
__device__ __forceinline__ void stg_strong32(void* p, uint32_t v) { asm volatile("st.relaxed.gpu.global.u32 [%0], %1;" :: "l"(p), "r"(v) : "memory"); }
__device__ __forceinline__ void stg_strong16(void* p, uint32_t v) { asm volatile("st.relaxed.gpu.global.u16 [%0], %1;" :: "l"(p), "h"((uint16_t)v) : "memory"); }
__device__ __forceinline__ void stg_strong128(void* p, uint4 v) {
  asm volatile("st.relaxed.gpu.global.v4.u32 [%0], {%1,%2,%3,%4};" :: "l"(p), "r"(v.x), "r"(v.y), "r"(v.z), "r"(v.w) : "memory"); }
__device__ __forceinline__ uint32_t mapa(uint32_t a, uint32_t r) {
  uint32_t o; asm("mapa.shared::cluster.u32 %0, %1, %2;" : "=r"(o) : "r"(a), "r"(r)); return o; }
__device__ __forceinline__ void st_async2f(uint32_t a, float x, float y, uint32_t bar) {
  asm volatile("st.async.shared::cluster.mbarrier::complete_tx::bytes.v2.f32 [%0], {%1,%2}, [%3];" :: "r"(a), "f"(x), "f"(y), "r"(bar) : "memory"); }
__device__ __forceinline__ void st_async32(uint32_t a, uint32_t x, uint32_t bar) {
  asm volatile("st.async.shared::cluster.mbarrier::complete_tx::bytes.b32 [%0], %1, [%2];" :: "r"(a), "r"(x), "r"(bar) : "memory"); }
__device__ __forceinline__ uint32_t lds32(uint32_t a) { uint32_t v; asm volatile("ld.shared.b32 %0, [%1];" : "=r"(v) : "r"(a) : "memory"); return v; }
__device__ __forceinline__ void st_async64(uint32_t a, uint32_t x, uint32_t y, uint32_t bar) {
  asm volatile("st.async.shared::cluster.mbarrier::complete_tx::bytes.v2.b32 [%0], {%1,%2}, [%3];" :: "r"(a), "r"(x), "r"(y), "r"(bar) : "memory"); }
__device__ __forceinline__ uint2 lds64(uint32_t a) { uint2 v; asm volatile("ld.shared.v2.b32 {%0,%1}, [%2];" : "=r"(v.x), "=r"(v.y) : "r"(a) : "memory"); return v; }
__device__ __forceinline__ void sts64(uint32_t a, uint32_t x, uint32_t y) { asm volatile("st.shared.v2.b32 [%0], {%1,%2};" :: "r"(a), "r"(x), "r"(y) : "memory"); }
__device__ __forceinline__ uint32_t ldg_strong32(const void* p) { uint32_t v; asm volatile("ld.relaxed.gpu.global.u32 %0, [%1];" : "=r"(v) : "l"(p) : "memory"); return v; }
__device__ __forceinline__ uint32_t transpose8(uint32_t x) { uint32_t r; asm volatile("movmatrix.sync.aligned.m8n8.trans.b16 %0, %1;" : "=r"(r) : "r"(x)); return r; }
__device__ __forceinline__ uint32_t hadd2(uint32_t a, uint32_t b) { uint32_t r; asm("add.rn.bf16x2 %0, %1, %2;" : "=r"(r) : "r"(a), "r"(b)); return r; }
__device__ __forceinline__ uint32_t min4(uint4 v) { return min(__vimin3_u32(v.x, v.y, v.z), v.w); }

__device__ __forceinline__ void wg_ss192_01(float* d, uint64_t da, uint64_t db, int sd) {
  asm volatile("{.reg .pred p; setp.ne.b32 p, %98, 0;\n"
    "wgmma.mma_async.sync.aligned.m64n192k16.f32.bf16.bf16 {%0,%1,%2,%3,%4,%5,%6,%7,%8,%9,%10,%11,%12,%13,%14,%15,%16,%17,%18,%19,%20,%21,%22,%23,%24,%25,%26,%27,%28,%29,%30,%31,%32,%33,%34,%35,%36,%37,%38,%39,%40,%41,%42,%43,%44,%45,%46,%47,%48,%49,%50,%51,%52,%53,%54,%55,%56,%57,%58,%59,%60,%61,%62,%63,%64,%65,%66,%67,%68,%69,%70,%71,%72,%73,%74,%75,%76,%77,%78,%79,%80,%81,%82,%83,%84,%85,%86,%87,%88,%89,%90,%91,%92,%93,%94,%95}, %96, %97, p, 1, 1, 0, 1;}"
    : "+f"(d[0]),"+f"(d[1]),"+f"(d[2]),"+f"(d[3]),"+f"(d[4]),"+f"(d[5]),"+f"(d[6]),"+f"(d[7]),"+f"(d[8]),"+f"(d[9]),"+f"(d[10]),"+f"(d[11]),"+f"(d[12]),"+f"(d[13]),"+f"(d[14]),"+f"(d[15]),"+f"(d[16]),"+f"(d[17]),"+f"(d[18]),"+f"(d[19]),"+f"(d[20]),"+f"(d[21]),"+f"(d[22]),"+f"(d[23]),"+f"(d[24]),"+f"(d[25]),"+f"(d[26]),"+f"(d[27]),"+f"(d[28]),"+f"(d[29]),"+f"(d[30]),"+f"(d[31]),"+f"(d[32]),"+f"(d[33]),"+f"(d[34]),"+f"(d[35]),"+f"(d[36]),"+f"(d[37]),"+f"(d[38]),"+f"(d[39]),"+f"(d[40]),"+f"(d[41]),"+f"(d[42]),"+f"(d[43]),"+f"(d[44]),"+f"(d[45]),"+f"(d[46]),"+f"(d[47]),"+f"(d[48]),"+f"(d[49]),"+f"(d[50]),"+f"(d[51]),"+f"(d[52]),"+f"(d[53]),"+f"(d[54]),"+f"(d[55]),"+f"(d[56]),"+f"(d[57]),"+f"(d[58]),"+f"(d[59]),"+f"(d[60]),"+f"(d[61]),"+f"(d[62]),"+f"(d[63]),"+f"(d[64]),"+f"(d[65]),"+f"(d[66]),"+f"(d[67]),"+f"(d[68]),"+f"(d[69]),"+f"(d[70]),"+f"(d[71]),"+f"(d[72]),"+f"(d[73]),"+f"(d[74]),"+f"(d[75]),"+f"(d[76]),"+f"(d[77]),"+f"(d[78]),"+f"(d[79]),"+f"(d[80]),"+f"(d[81]),"+f"(d[82]),"+f"(d[83]),"+f"(d[84]),"+f"(d[85]),"+f"(d[86]),"+f"(d[87]),"+f"(d[88]),"+f"(d[89]),"+f"(d[90]),"+f"(d[91]),"+f"(d[92]),"+f"(d[93]),"+f"(d[94]),"+f"(d[95])
    : "l"(da), "l"(db), "r"(sd));
}
__device__ __forceinline__ void wg_ss128_01(float* d, uint64_t da, uint64_t db, int sd) {
  asm volatile("{.reg .pred p; setp.ne.b32 p, %66, 0;\n"
    "wgmma.mma_async.sync.aligned.m64n128k16.f32.bf16.bf16 {%0,%1,%2,%3,%4,%5,%6,%7,%8,%9,%10,%11,%12,%13,%14,%15,%16,%17,%18,%19,%20,%21,%22,%23,%24,%25,%26,%27,%28,%29,%30,%31,%32,%33,%34,%35,%36,%37,%38,%39,%40,%41,%42,%43,%44,%45,%46,%47,%48,%49,%50,%51,%52,%53,%54,%55,%56,%57,%58,%59,%60,%61,%62,%63}, %64, %65, p, 1, 1, 0, 1;}"
    : "+f"(d[0]),"+f"(d[1]),"+f"(d[2]),"+f"(d[3]),"+f"(d[4]),"+f"(d[5]),"+f"(d[6]),"+f"(d[7]),"+f"(d[8]),"+f"(d[9]),"+f"(d[10]),"+f"(d[11]),"+f"(d[12]),"+f"(d[13]),"+f"(d[14]),"+f"(d[15]),"+f"(d[16]),"+f"(d[17]),"+f"(d[18]),"+f"(d[19]),"+f"(d[20]),"+f"(d[21]),"+f"(d[22]),"+f"(d[23]),"+f"(d[24]),"+f"(d[25]),"+f"(d[26]),"+f"(d[27]),"+f"(d[28]),"+f"(d[29]),"+f"(d[30]),"+f"(d[31]),"+f"(d[32]),"+f"(d[33]),"+f"(d[34]),"+f"(d[35]),"+f"(d[36]),"+f"(d[37]),"+f"(d[38]),"+f"(d[39]),"+f"(d[40]),"+f"(d[41]),"+f"(d[42]),"+f"(d[43]),"+f"(d[44]),"+f"(d[45]),"+f"(d[46]),"+f"(d[47]),"+f"(d[48]),"+f"(d[49]),"+f"(d[50]),"+f"(d[51]),"+f"(d[52]),"+f"(d[53]),"+f"(d[54]),"+f"(d[55]),"+f"(d[56]),"+f"(d[57]),"+f"(d[58]),"+f"(d[59]),"+f"(d[60]),"+f"(d[61]),"+f"(d[62]),"+f"(d[63])
    : "l"(da), "l"(db), "r"(sd));
}
__device__ __forceinline__ void wg_ss160_01(float* d, uint64_t da, uint64_t db, int sd) {
  asm volatile("{.reg .pred p; setp.ne.b32 p, %82, 0;\n"
    "wgmma.mma_async.sync.aligned.m64n160k16.f32.bf16.bf16 {%0,%1,%2,%3,%4,%5,%6,%7,%8,%9,%10,%11,%12,%13,%14,%15,%16,%17,%18,%19,%20,%21,%22,%23,%24,%25,%26,%27,%28,%29,%30,%31,%32,%33,%34,%35,%36,%37,%38,%39,%40,%41,%42,%43,%44,%45,%46,%47,%48,%49,%50,%51,%52,%53,%54,%55,%56,%57,%58,%59,%60,%61,%62,%63,%64,%65,%66,%67,%68,%69,%70,%71,%72,%73,%74,%75,%76,%77,%78,%79}, %80, %81, p, 1, 1, 0, 1;}"
    : "+f"(d[0]),"+f"(d[1]),"+f"(d[2]),"+f"(d[3]),"+f"(d[4]),"+f"(d[5]),"+f"(d[6]),"+f"(d[7]),"+f"(d[8]),"+f"(d[9]),"+f"(d[10]),"+f"(d[11]),"+f"(d[12]),"+f"(d[13]),"+f"(d[14]),"+f"(d[15]),"+f"(d[16]),"+f"(d[17]),"+f"(d[18]),"+f"(d[19]),"+f"(d[20]),"+f"(d[21]),"+f"(d[22]),"+f"(d[23]),"+f"(d[24]),"+f"(d[25]),"+f"(d[26]),"+f"(d[27]),"+f"(d[28]),"+f"(d[29]),"+f"(d[30]),"+f"(d[31]),"+f"(d[32]),"+f"(d[33]),"+f"(d[34]),"+f"(d[35]),"+f"(d[36]),"+f"(d[37]),"+f"(d[38]),"+f"(d[39]),"+f"(d[40]),"+f"(d[41]),"+f"(d[42]),"+f"(d[43]),"+f"(d[44]),"+f"(d[45]),"+f"(d[46]),"+f"(d[47]),"+f"(d[48]),"+f"(d[49]),"+f"(d[50]),"+f"(d[51]),"+f"(d[52]),"+f"(d[53]),"+f"(d[54]),"+f"(d[55]),"+f"(d[56]),"+f"(d[57]),"+f"(d[58]),"+f"(d[59]),"+f"(d[60]),"+f"(d[61]),"+f"(d[62]),"+f"(d[63]),"+f"(d[64]),"+f"(d[65]),"+f"(d[66]),"+f"(d[67]),"+f"(d[68]),"+f"(d[69]),"+f"(d[70]),"+f"(d[71]),"+f"(d[72]),"+f"(d[73]),"+f"(d[74]),"+f"(d[75]),"+f"(d[76]),"+f"(d[77]),"+f"(d[78]),"+f"(d[79])
    : "l"(da), "l"(db), "r"(sd));
}
__device__ __forceinline__ void wg_ss80_01(float* d, uint64_t da, uint64_t db, int sd) {
  asm volatile("{.reg .pred p; setp.ne.b32 p, %42, 0;\n"
    "wgmma.mma_async.sync.aligned.m64n80k16.f32.bf16.bf16 {%0,%1,%2,%3,%4,%5,%6,%7,%8,%9,%10,%11,%12,%13,%14,%15,%16,%17,%18,%19,%20,%21,%22,%23,%24,%25,%26,%27,%28,%29,%30,%31,%32,%33,%34,%35,%36,%37,%38,%39}, %40, %41, p, 1, 1, 0, 1;}"
    : "+f"(d[0]),"+f"(d[1]),"+f"(d[2]),"+f"(d[3]),"+f"(d[4]),"+f"(d[5]),"+f"(d[6]),"+f"(d[7]),"+f"(d[8]),"+f"(d[9]),"+f"(d[10]),"+f"(d[11]),"+f"(d[12]),"+f"(d[13]),"+f"(d[14]),"+f"(d[15]),"+f"(d[16]),"+f"(d[17]),"+f"(d[18]),"+f"(d[19]),"+f"(d[20]),"+f"(d[21]),"+f"(d[22]),"+f"(d[23]),"+f"(d[24]),"+f"(d[25]),"+f"(d[26]),"+f"(d[27]),"+f"(d[28]),"+f"(d[29]),"+f"(d[30]),"+f"(d[31]),"+f"(d[32]),"+f"(d[33]),"+f"(d[34]),"+f"(d[35]),"+f"(d[36]),"+f"(d[37]),"+f"(d[38]),"+f"(d[39])
    : "l"(da), "l"(db), "r"(sd));
}
__device__ __forceinline__ void wg_rs32_00(float* d, uint32_t a0, uint32_t a1, uint32_t a2, uint32_t a3, uint64_t db, int sd) {
  asm volatile("{.reg .pred p; setp.ne.b32 p, %21, 0;\n"
    "wgmma.mma_async.sync.aligned.m64n32k16.f32.bf16.bf16 {%0,%1,%2,%3,%4,%5,%6,%7,%8,%9,%10,%11,%12,%13,%14,%15}, {%16,%17,%18,%19}, %20, p, 1, 1, 0;}"
    : "+f"(d[0]),"+f"(d[1]),"+f"(d[2]),"+f"(d[3]),"+f"(d[4]),"+f"(d[5]),"+f"(d[6]),"+f"(d[7]),"+f"(d[8]),"+f"(d[9]),"+f"(d[10]),"+f"(d[11]),"+f"(d[12]),"+f"(d[13]),"+f"(d[14]),"+f"(d[15])
    : "r"(a0), "r"(a1), "r"(a2), "r"(a3), "l"(db), "r"(sd));
}
__device__ __forceinline__ void wg_rs64_00(float* d, uint32_t a0, uint32_t a1, uint32_t a2, uint32_t a3, uint64_t db, int sd) {
  asm volatile("{.reg .pred p; setp.ne.b32 p, %37, 0;\n"
    "wgmma.mma_async.sync.aligned.m64n64k16.f32.bf16.bf16 {%0,%1,%2,%3,%4,%5,%6,%7,%8,%9,%10,%11,%12,%13,%14,%15,%16,%17,%18,%19,%20,%21,%22,%23,%24,%25,%26,%27,%28,%29,%30,%31}, {%32,%33,%34,%35}, %36, p, 1, 1, 0;}"
    : "+f"(d[0]),"+f"(d[1]),"+f"(d[2]),"+f"(d[3]),"+f"(d[4]),"+f"(d[5]),"+f"(d[6]),"+f"(d[7]),"+f"(d[8]),"+f"(d[9]),"+f"(d[10]),"+f"(d[11]),"+f"(d[12]),"+f"(d[13]),"+f"(d[14]),"+f"(d[15]),"+f"(d[16]),"+f"(d[17]),"+f"(d[18]),"+f"(d[19]),"+f"(d[20]),"+f"(d[21]),"+f"(d[22]),"+f"(d[23]),"+f"(d[24]),"+f"(d[25]),"+f"(d[26]),"+f"(d[27]),"+f"(d[28]),"+f"(d[29]),"+f"(d[30]),"+f"(d[31])
    : "r"(a0), "r"(a1), "r"(a2), "r"(a3), "l"(db), "r"(sd));
}
__device__ __forceinline__ void wg_rs128_00(float* d, uint32_t a0, uint32_t a1, uint32_t a2, uint32_t a3, uint64_t db, int sd) {
  asm volatile("{.reg .pred p; setp.ne.b32 p, %69, 0;\n"
    "wgmma.mma_async.sync.aligned.m64n128k16.f32.bf16.bf16 {%0,%1,%2,%3,%4,%5,%6,%7,%8,%9,%10,%11,%12,%13,%14,%15,%16,%17,%18,%19,%20,%21,%22,%23,%24,%25,%26,%27,%28,%29,%30,%31,%32,%33,%34,%35,%36,%37,%38,%39,%40,%41,%42,%43,%44,%45,%46,%47,%48,%49,%50,%51,%52,%53,%54,%55,%56,%57,%58,%59,%60,%61,%62,%63}, {%64,%65,%66,%67}, %68, p, 1, 1, 0;}"
    : "+f"(d[0]),"+f"(d[1]),"+f"(d[2]),"+f"(d[3]),"+f"(d[4]),"+f"(d[5]),"+f"(d[6]),"+f"(d[7]),"+f"(d[8]),"+f"(d[9]),"+f"(d[10]),"+f"(d[11]),"+f"(d[12]),"+f"(d[13]),"+f"(d[14]),"+f"(d[15]),"+f"(d[16]),"+f"(d[17]),"+f"(d[18]),"+f"(d[19]),"+f"(d[20]),"+f"(d[21]),"+f"(d[22]),"+f"(d[23]),"+f"(d[24]),"+f"(d[25]),"+f"(d[26]),"+f"(d[27]),"+f"(d[28]),"+f"(d[29]),"+f"(d[30]),"+f"(d[31]),"+f"(d[32]),"+f"(d[33]),"+f"(d[34]),"+f"(d[35]),"+f"(d[36]),"+f"(d[37]),"+f"(d[38]),"+f"(d[39]),"+f"(d[40]),"+f"(d[41]),"+f"(d[42]),"+f"(d[43]),"+f"(d[44]),"+f"(d[45]),"+f"(d[46]),"+f"(d[47]),"+f"(d[48]),"+f"(d[49]),"+f"(d[50]),"+f"(d[51]),"+f"(d[52]),"+f"(d[53]),"+f"(d[54]),"+f"(d[55]),"+f"(d[56]),"+f"(d[57]),"+f"(d[58]),"+f"(d[59]),"+f"(d[60]),"+f"(d[61]),"+f"(d[62]),"+f"(d[63])
    : "r"(a0), "r"(a1), "r"(a2), "r"(a3), "l"(db), "r"(sd));
}
__device__ __forceinline__ void wg_rs24_01(float* d, uint32_t a0, uint32_t a1, uint32_t a2, uint32_t a3, uint64_t db, int sd) {
  asm volatile("{.reg .pred p; setp.ne.b32 p, %17, 0;\n"
    "wgmma.mma_async.sync.aligned.m64n24k16.f32.bf16.bf16 {%0,%1,%2,%3,%4,%5,%6,%7,%8,%9,%10,%11}, {%12,%13,%14,%15}, %16, p, 1, 1, 1;}"
    : "+f"(d[0]),"+f"(d[1]),"+f"(d[2]),"+f"(d[3]),"+f"(d[4]),"+f"(d[5]),"+f"(d[6]),"+f"(d[7]),"+f"(d[8]),"+f"(d[9]),"+f"(d[10]),"+f"(d[11])
    : "r"(a0), "r"(a1), "r"(a2), "r"(a3), "l"(db), "r"(sd));
}

#define AB_POLY 0x77
__device__ __forceinline__ constexpr bool poly_group(int group) { return (AB_POLY >> (group & 7)) & 1; }

template <int V> struct Int { static constexpr int value = V; };

template <int NG>
__device__ __forceinline__ void ln_stats(const float4 (&v)[NG][5], uint32_t scratch, float (&mean)[NG], float (&rs)[NG]) {
  const int warp = threadIdx.x >> 5, lane = threadIdx.x & 31;
#pragma unroll
  for (int r = 0; r < NG; r++) {
    float s = 0.f, q = 0.f;
#pragma unroll
    for (int i = 0; i < 5; i++) s += (v[r][i].x + v[r][i].y) + (v[r][i].z + v[r][i].w);
    s += __shfl_xor_sync(~0u, s, 1); s += __shfl_xor_sync(~0u, s, 2);
    s *= 1.f / 80;
#pragma unroll
    for (int i = 0; i < 5; i++) {
      const float x = v[r][i].x - s, y = v[r][i].y - s, z = v[r][i].z - s, w = v[r][i].w - s;
      q += (x * x + y * y) + (z * z + w * w);
    }
    q += __shfl_xor_sync(~0u, q, 1); q += __shfl_xor_sync(~0u, q, 2);
    mean[r] = s; rs[r] = q;
  }
  bar_sync(1, 256);
  if ((lane & 3) == 0) {
#pragma unroll
    for (int r = 0; r < NG; r++) sts64f(scratch + r * 512 + lane * 16 + warp * 8, mean[r], rs[r]);
  }
  bar_sync(1, 256);
#pragma unroll
  for (int r = 0; r < NG; r++) {
    const float4 e = lds128f(scratch + r * 512 + lane * 16);
    float t = e.x + e.z;
    t += __shfl_xor_sync(~0u, t, 1); t += __shfl_xor_sync(~0u, t, 2);
    t *= 0.125f;
    float q = e.y + e.w + 80.f * ((e.x - t) * (e.x - t) + (e.z - t) * (e.z - t));
    q += __shfl_xor_sync(~0u, q, 1); q += __shfl_xor_sync(~0u, q, 2);
    mean[r] = t; rs[r] = rsqrtf(q * (1.f / DM) + 1e-5f);
  }
}

__device__ __forceinline__ void ln_store(const uint32_t (&w)[2][5][2], int tile, int u0) {
  const int lane = threadIdx.x & 31;
  uint32_t* xc = g_xc + ((tile >> 1) * 40 + u0) * 256 + (tile & 1) * 64 + lane;
#pragma unroll
  for (int i = 0; i < 20; i++) xc[(i >> 1) * 128 + (i & 1) * 32] = w[i & 1][i >> 2][i >> 1 & 1];
#pragma unroll
  for (int i = 0; i < 5; i++) {
    const int u = u0 + i;
    uint32_t* xn = g_xn + (((tile >> 3) * 20 + (u >> 1)) * 16 + (tile & 1) * 8 + (tile & 6)) * 128 + (u & 1) * 64 + lane;
#pragma unroll
    for (int r = 0; r < 2; r++) { xn[r * 128] = w[r][i][0]; xn[r * 128 + 32] = w[r][i][1]; }
  }
}
__device__ __forceinline__ void wait_count(const uint32_t* c, uint32_t n) {
  int spin = 0;
  while ((ld_acquire(c) & 0xffff) < n) { __nanosleep(32); spin_guard(spin); }
}

__device__ __forceinline__ uint8_t* pool_at(uint32_t off) {
  return reinterpret_cast<uint8_t*>((reinterpret_cast<uintptr_t>(g_pool) + 8191) & ~(uintptr_t)8191) + off; }
struct Weights { const uint8_t* w[4]; };
__device__ __forceinline__ void prefetch_weights(const Weights& p, int i) {
  if (blockIdx.x < 128) asm volatile("cp.async.bulk.prefetch.L2.global [%0], 61440;" :: "l"(p.w[i] + (size_t)blockIdx.x * 61440) : "memory");
}
__global__ void __launch_bounds__(256) first_kernel(const __nv_bfloat16* __restrict__ xin, const uint4* __restrict__ wb, const __grid_constant__ Weights wa) {
  __shared__ __align__(16) float scratch[256];
  __shared__ uint32_t lat[4];
  const int warp = threadIdx.x >> 5, lane = threadIdx.x & 31, cta = blockIdx.x;
  TRACE(0);
  pdl_launch();
  if (warp < 4 && (warp < 2 || cta < NSLOT)) {
    uint32_t* q = reinterpret_cast<uint32_t*>(pool_at((warp < 2 ? NSLOT : cta) * 8192 + (warp & 1) * 4096)) + (warp < 2 ? (cta & 127) * 8 : 0);
    if (lane < 8) stg_strong32(q + lane, 0u);
    uint32_t best = ~0u;
    if (lane == 0)
      for (int r = 0; r < 4; r++) {
        uint32_t t0, t1, v;
        asm volatile("mov.u32 %0, %%clock;" : "=r"(t0) :: "memory");
        asm volatile("atom.relaxed.gpu.global.exch.b32 %0, [%1], 0;" : "=r"(v) : "l"(q) : "memory");
        asm volatile("{.reg .u32 t; add.u32 t, %1, 1; mov.u32 %0, %%clock; sub.u32 %0, %0, %1;}" : "=r"(t1) : "r"(__shfl_sync(1u, v, 0)) : "memory");
        best = min(best, t1 - t0);
      }
    if (lane == 0) lat[warp] = best;
  }
  __syncthreads();
  ABT(2, 0);
  if (threadIdx.x == 0) {
    const int part = lat[0] < lat[1] ? 0 : 1;
    uint32_t smid; asm("mov.u32 %0, %%smid;" : "=r"(smid));
    g_smpart[smid & 255] = part;
    g_smclk[smid & 255] = clk32() - gtime() * 2;
    g_smuse[smid & 255] = 0;
    if (cta < NSLOT) g_orient[cta] = lat[2] < lat[3] ? part : 1 - part;
  }
  if (cta < 128) {
    float4 v[2][5];
#pragma unroll
    for (int r = 0; r < 2; r++)
#pragma unroll
      for (int i = 0; i < 5; i++) {
        const uint32_t* src = reinterpret_cast<const uint32_t*>(xin) + (cta * 16 + r * 8 + (lane >> 2)) * (DM / 2) + warp * 40 + i * 8 + (lane & 3);
        const uint32_t a = src[0], b = src[4];
        v[r][i] = make_float4(bf_lo(a), bf_hi(a), bf_lo(b), bf_hi(b));
      }
    uint4 w8[2];
#pragma unroll
    for (int i = 0; i < 2; i++) w8[i] = wb[cta * 400 + min(i * 256 + threadIdx.x, 399)];
    if (threadIdx.x < 128) g_stat[cta * 128 + threadIdx.x] = make_float2(0.f, 0.f);
#pragma unroll
    for (int i = 0; i < 10; i++) g_x[((cta * 2 + i / 5) * 40 + warp * 5 + i % 5) * 32 + lane] = v[i / 5][i % 5];
    ABT(2, 1);
    if (threadIdx.x == 32) for (int i = 0; i < FK_PF; i++) prefetch_weights(wa, i);
    float mean[2], rs[2];
    ln_stats<2>(v, s2u(scratch), mean, rs);
    ABT(2, 2);
    uint32_t w[2][5][2];
#pragma unroll
    for (int i = 0; i < 10; i++) {
      const float4 t = v[i / 5][i % 5];
      const float m = mean[i / 5], q = rs[i / 5];
      w[i / 5][i % 5][0] = pack2((t.x - m) * q, (t.y - m) * q); w[i / 5][i % 5][1] = pack2((t.z - m) * q, (t.w - m) * q);
    }
    ln_store(w, cta, warp * 5);
    ABT(2, 3);
#pragma unroll
    for (int i = 0; i < 2; i++) {
      const int e = cta * 400 + min(i * 256 + threadIdx.x, 399), k = e / 80, n = e - k * 80, cg = n / 10;
      g_wb[((cg * 80 + (k >> 3)) * 10 + n - cg * 10) * 8 + (k & 7)] = w8[i];
    }
  } else if (cta == 128) {
    g_bo[threadIdx.x] = 0;
  }
  TRACE(2);
}

struct ChainParams {
  CUtensorMap wq, wk, wv, wo;
  const __nv_bfloat16* mem0;
  uint8_t *pool, *kv;
  const uint32_t* xc;
  uint32_t* sync;
  int layer;
  int d0, d3, d1, d1b, d2, d2b, mode;
};
constexpr int CH_WQ = 0, CH_WO = 81920, CH_X = CH_WO + 86016, CH_M = CH_X + 20480, CH_KT = CH_X + 40960, CH_VT = CH_KT + 4096,
              CH_PS = CH_VT + 4096, CH_QK = CH_PS + 4096, CH_VP = CH_QK + 4096, CH_SX = CH_VP + 1024, CH_O = CH_SX + 2304, CH_ID = CH_O + 3072,
              CH_BAR = CH_ID + 512;
constexpr int CH_SMEM = CH_BAR + 256;
constexpr int CH_BASE = 1024;
#define CH_VK0 8
#define CH_VK1 20
#define CH_L0 4
#define CH_LR 4
#define NOX 0
#define CH_XA 1
#define CH_XB 4
#define CH_W1 3
#define CH_W2 17
#define CH_W3 26
#define CH_R2 8
#define CH_VA 16
#define CH_EX 1
#define CH_KD 0
#define CH_RP 1
#define CH_KF 10
#define CH_LO 0
#define CH_LR1 4
#define CH_KP 0
#define CH_KM 0
#define CH_WE 0
#define CH_KW 3
#define CH_RB 0
#define CH_RC 8
#define CH_D0 200
#define CH_D1 450
#define CH_D2 350
#define CH_R1 4
#define CH_TW 12
__device__ __forceinline__ uint32_t opaque(uint32_t x) { return __shfl_sync(~0u, x, threadIdx.x & 31); }
__device__ __forceinline__ uint32_t nz(uint32_t x) { uint32_t r; asm("max.u32 %0, %1, 1;" : "=r"(r) : "r"(x)); return r; }
__device__ __forceinline__ uint32_t pack_tag(float lo, float hi, uint32_t tag, uint32_t mask) {
  uint32_t r;
  asm("lop3.b32 %0, %1, %2, %3, 0xD8;" : "=r"(r) : "r"(pack2(lo, hi)), "r"(tag), "r"(mask));
  return r;
}
__device__ __forceinline__ uint32_t differ(uint32_t a, uint32_t b, uint32_t t) { uint32_t r; asm("lop3.b32 %0, %1, %2, %3, 0x7E;" : "=r"(r) : "r"(a), "r"(b), "r"(t)); return r; }
__device__ __forceinline__ void mbar_wait_hot(uint32_t bar, uint32_t ph) {
  uint32_t ok;
  asm volatile("{.reg .pred p; mbarrier.try_wait.parity.shared::cta.b64 p, [%1], %2; selp.u32 %0, 1, 0, p;}" : "=r"(ok) : "r"(bar), "r"(ph) : "memory");
  if (__builtin_expect(!ok, 0)) mbar_wait(bar, ph);
}
__device__ __forceinline__ bool elect() {
  uint32_t r; asm volatile("{.reg .pred p; elect.sync _|p, 0xffffffff; selp.u32 %0, 1, 0, p;}" : "=r"(r)); return r; }
__device__ __forceinline__ uint32_t or3(uint32_t a, uint32_t b, uint32_t c) { uint32_t r; asm("lop3.b32 %0, %1, %2, %3, 0xFE;" : "=r"(r) : "r"(a), "r"(b), "r"(c)); return r; }
__device__ __forceinline__ void pin() { pdl_launch(); }
__device__ __forceinline__ void mma16h(float* d, uint32_t a0, uint32_t a2, uint32_t b0, uint32_t b1) {
  asm volatile("{.reg .b32 u, v; mma.sync.aligned.m16n8k16.row.col.f32.bf16.bf16.f32 {%0,%1,%2,%3},{%4,u,%5,v},{%6,%7},{%0,%1,%2,%3};}"
               : "+f"(d[0]), "+f"(d[1]), "+f"(d[2]), "+f"(d[3]) : "r"(a0), "r"(a2), "r"(b0), "r"(b1)); }
__device__ __forceinline__ void mma8h(float* d, uint32_t a0, uint32_t b0) {
  asm volatile("{.reg .b32 u; mma.sync.aligned.m16n8k8.row.col.f32.bf16.bf16.f32 {%0,%1,%2,%3},{%4,u},{%5},{%0,%1,%2,%3};}"
               : "+f"(d[0]), "+f"(d[1]), "+f"(d[2]), "+f"(d[3]) : "r"(a0), "r"(b0)); }
__device__ __forceinline__ uint32_t absmax2(uint32_t a, uint32_t b) { uint32_t r; asm("max.xorsign.abs.bf16x2 %0, %1, %2;" : "=r"(r) : "r"(a), "r"(b)); return r; }
__device__ __forceinline__ void until(uint32_t t) { while ((int)(clk32() - t) < 0) {} }
__device__ __forceinline__ uint4 pack8(const float* d) { return make_uint4(pack2(d[0], d[1]), pack2(d[2], d[3]), pack2(d[4], d[5]), pack2(d[6], d[7])); }
__device__ __forceinline__ void add8(float* d, uint4 v) {
  d[0] += bf_lo(v.x); d[1] += bf_hi(v.x); d[2] += bf_lo(v.y); d[3] += bf_hi(v.y);
  d[4] += bf_lo(v.z); d[5] += bf_hi(v.z); d[6] += bf_lo(v.w); d[7] += bf_hi(v.w);
}

template <int WG>
__device__ __forceinline__ void chain_body(const ChainParams& p, const uint32_t wq, const uint32_t (&ak)[80], const uint32_t (&av)[80]) {
  const int tid = threadIdx.x & 127, t4 = __shfl_sync(~0u, tid >> 5, 0), lane = tid & 31;
  const int cta = blockIdx.x, h = cta / 3, j = cta - 3 * h;
  const uint32_t sb = mapa(CH_BASE, j);
  const uint32_t bWo = sb + CH_BAR, bWq = bWo + 8, bX = bWo + 16, bXA = bWo + 24, bXB = bWo + 32, bO = bWo + 40, bG = bWo + 48, bH = bWo + 96;
  uint32_t tw[4 * CH_TW];
  auto refill = [&]() {
#pragma unroll
    for (int k = 0; k < CH_TW; k++) ldsm4t(&tw[4 * k], wq + k * 2048);
  };
  const uint32_t wo = opaque((sb + CH_WO + (WG == 0 ? (t4 + (j == 2)) * 4096 : (j == 2 ? 0 : 24576) + t4 * 1024) + ((lane & 7) + (lane >> 4) * 8) * 64 +
                              ((((lane >> 3) & 1) ^ ((lane >> 1) & 3)) << 4)) ^ (WG == 1 && j == 2 ? 32 : 0));
  const uint32_t wo2 = opaque((wo ^ ((t4 & 1) * 32)) + (4 + (t4 >> 1) - t4) * 4096);
  const uint32_t l16 = opaque(sb + lane * 16);
  const uint32_t l8 = opaque(sb + t4 * 256 + lane * 8);
  const uint32_t lw = opaque(sb + t4 * 1024 + lane * 16);
  const uint32_t qs = opaque(sb + CH_QK + WG * 2048 + t4 * 512 + lane * 16);
  const uint32_t qa = opaque(sb + CH_QK + (lane >> 4) * 2048 + (lane & 15) * 16 + (WG == 0 ? t4 * 512 + 256 : t4 == 3 ? 1024 : 0));
  const uint32_t ka = opaque(t4 < 2 ? sb + CH_KT + t4 * 512 + lane * 16
                                    : sb + CH_QK + 256 + (t4 - 2) * 1024 + ((lane >> 3) & 1) * 2048 + (lane >> 4) * 128 + (lane & 7) * 16);
  const uint32_t l4 = opaque(sb + t4 * 256 + lane * 4);
  uint32_t pdst[1], pages = 0;
  auto line0 = [&](int i) { return 28 * j + (i < 4 ? 4 * t4 + i : 12 + 2 * t4 + i); };
  const uint32_t plane = opaque((lane >> 4) * 2048 + h * 64 + (lane & 15) * 4);
  if (WG == 0) {
    pages = __ballot_sync(~0u, lds32(sb + CH_O + line0(min(lane, 5)) * 4) & 4096);
  } else {
    pages = __ballot_sync(~0u, lds32(sb + CH_O + (80 + min(lane, 11)) * 4) & 4096);
    pdst[0] = opaque(lds32(sb + CH_O + (j == 0 ? 24 + t4 : 50 + 2 * j + (t4 & 1)) * 4) + plane);
  }
  const uint32_t role = lds32(sb + CH_O + NSLOT * 4), rsrc = lds32(sb + CH_O + role * 4), rdst = (80 + role / 20) * 8192 + role % 20 * 128;
  const uint32_t r1 = mapa(CH_BASE, j == 2 ? 0 : j + 1) - sb, r2 = mapa(CH_BASE, j == 0 ? 2 : j - 1) - sb;
  uint32_t tag = opaque(1);
  auto pool = [&](uint32_t off) { return p.pool + ((tag & 0xfffe) + off); };
  auto after = [&](uint32_t x) { return x & tag & 0xfffe; };
  auto kv = [&](int s, uint32_t a) { return p.kv + (a + ((cta * 2 * NSEG + s) * KV_BYTES - sb)); };
  auto pass = [&](float (&d)[16], const uint32_t (&a)[80], auto k0, auto k1) {
    const uint64_t db = mkdesc(CH_BASE + CH_X + WG * 20480, 512, 128, 0);
#pragma unroll
    for (int k = k0.value; k < k1.value; k++) wg_rs32_00(d, a[4 * k], a[4 * k + 1], a[4 * k + 2], a[4 * k + 3], db + k * 64, k);
    wg_commit();
  };
  auto dump = [&](float (&d)[16], uint32_t a) {
    reg_fence<16>(d);
    sts128(a, pack8(d)); sts128(a + 512, pack8(d + 8));
  };
  uint32_t pph = 0;
  auto tokens0 = [&](int s, auto k0) {
    float dk[16], dv[16];
    bar_sync(9, 256);
    wg_fence();
    pass(dk, ak, Int<0>(), Int<4>());
    const uint4 a0 = lds128(lw + CH_KT), a1 = lds128(lw + CH_KT + 512);
    pin();
    pass(dk, ak, Int<4>(), Int<20>());
    pass(dv, av, Int<0>(), Int<CH_VA>());
    pin();
    wg_wait<1>();
    reg_fence<16>(dk);
    add8(dk, a0); add8(dk + 8, a1);
    const uint4 w0 = pack8(dk), w1 = pack8(dk + 8);
    const uint4 b0 = lds128(lw + CH_VT), b1 = lds128(lw + CH_VT + 512);
    stsm4t(lw + CH_KT, w0.x, w0.z, w0.y, w0.w); stsm4t(lw + CH_KT + 512, w1.x, w1.z, w1.y, w1.w);
    if (CH_KP == 2) bar_arrive(7, 160);
    TM1(6);
    pin();
    if (CH_VA < 20) pass(dv, av, Int<CH_VA>(), Int<20>());
    pin();
#pragma unroll
    for (int k = k0.value; k < CH_TW; k++) ldsm4t(&tw[4 * k], wq + k * 2048);
    TM1(9);
    if (k0.value < CH_TW && t4 >= 2) { mbar_wait_hot(bH + t4 * 16 - 24 + (pph & 1) * 8, pph >> 1 & 1); pph++; }
    __syncwarp();
    wg_wait<0>();
    reg_fence<16>(dv);
    add8(dv, b0); add8(dv + 8, b1);
#pragma unroll
    for (int e = 0; e < 2; e++) { const uint4 v = pack8(dv + 8 * e); sts128(lw + CH_VT + e * 512, make_uint4(v.x, v.z, v.y, v.w)); }
  };
  auto publish_k = [&](int s) {
    if (t4 == CH_KW && elect()) { fence_async(); bulk_store(p.kv + (size_t)(cta * 2 * NSEG + s) * KV_BYTES, sb + CH_KT, 4096); bulk_commit(); }
    __syncwarp();
  };
  if (WG == 0) {
    mbar_wait(bXB, 0);
    tokens0(0, Int<CH_TW>());
  } else {
    const uint32_t* m0 = reinterpret_cast<const uint32_t*>(p.mem0) + (lane >> 2) * 320 + t4 * 80 + (lane & 3);
    uint32_t a[20];
#pragma unroll
    for (int i = 0; i < 20; i++) a[i] = m0[4 * i];
    pin();
    float dk[16], dv[16];
    mbar_wait(bXA, 0);
    wg_fence();
    pass(dk, ak, Int<0>(), Int<20>());
    pass(dv, av, Int<0>(), Int<20>());
    wg_wait<0>();
    dump(dk, lw + CH_KT);
    dump(dv, lw + CH_VT);
    bar_sync(9, 256);
    if (CH_KP == 2 && t4 == CH_KW) { bar_sync(7, 160); publish_k(0); }
#pragma unroll
    for (int i = 0; i < 20; i++) sts32(sb + CH_M + (t4 * 20 + i) * 128 + lane * 4, nz(transpose8(a[i])));
    __syncwarp();
    if (elect()) mbar_arrive(bG + t4 * 8);
  }
  PRO(8);
  mbar_wait(bWq, 0);
  refill();
  PRO(9);
  mbar_wait(bWo, 0);
  asm volatile("barrier.cluster.wait.aligned;" ::: "memory");
  PRO(10);
  auto load_x = [&](int s, int k0, int n, uint32_t bar) {
    if (!NOX && elect()) { mbar_expect(bar, n * 1024); bulk_load(sb + CH_X + k0 * 1024, p.xc + (s + 1) * 10240 + k0 * 256, n * 1024, bar); }
  };
  constexpr int VK = WG == 0 ? CH_VK0 : CH_VK1;
  uint32_t gph = 0;
  int st = 0;
  const uint32_t ca = opaque(sb + CH_M + t4 * 2560 + lane * 32 + (lane >> 2) * 4);
  auto project = [&](int s, uint32_t (&b)[40], float (&dv)[16], uint32_t (&kf)[16]) {
    float dq[4] = {}, dk[4] = {};
    uint32_t w[80];
#pragma unroll
    for (int i = 0; i < 4 * CH_TW; i++) w[i] = tw[i];
    constexpr int LR = WG == 1 ? CH_LR1 : CH_LR;
    auto load = [&](int n) {
      int c = 0;
#pragma unroll
      for (int i = 0; i < 10; i++) {
        if (i == CH_KF) {
#pragma unroll
          for (int q = 0; q < 4; q++)
            if (WG == 1 && c++ == n) ldsm4(&kf[4 * q], ka + q * 1024);
        }
        if (c++ == n) ldsm4t(&b[4 * i], l16 + CH_M + WG * 5120 + i * 512);
#pragma unroll
        for (int k = 2 * i; k < 2 * i + 2; k++)
          if (k >= CH_TW && c++ == n) ldsm4t(&w[4 * k], wq + k * 2048);
      }
#pragma unroll
      for (int i = 0; i < 4; i++)
        if (WG == 1 && CH_KF >= 10 && c++ == n) ldsm4(&kf[4 * i], ka + i * 1024);
    };
    if (WG == 1) {
      for (int n = 0;;) {
        mbar_wait(bG + t4 * 8, gph);
        TR(5, (clk32() & ~3u) | min(n, 3));
        gph ^= 1;
        if (__builtin_expect(!__any_sync(~0u, __vimin3_u32(lds32(ca), lds32(ca + 1024), lds32(ca + 1536)) == 0), 1)) break;
        if (elect()) {
          const int q = (st == 0 ? 8 : st * 4 - 4) + t4;
          mbar_expect(bG + t4 * 8, 2560);
          bulk_load(sb + CH_M + t4 * 2560, p.pool + ((80 + q) * 8192 + (pages >> q & 1) * 4096), 2560, bG + t4 * 8);
        }
        spin_guard(n);
      }
    }
    bar_sync(6, 256);
#pragma unroll
    for (int i = 0; i < CH_L0; i++) load(i);
    if (WG == 0 && CH_XB == 4 && s + 1 < NSEG) load_x(s, 5 * t4, 5, bXB);
    TM(0);
    TM1(11);
    if (WG == 1) TR(6, clk32());
#pragma unroll
    for (int k = 0; k < 20; k += 2) {
      if (k > 0) {
#pragma unroll
        for (int n = (k == 18 ? 40 : CH_L0 + k * LR / 4) - 1; n >= CH_L0 + (k - 2) * LR / 4; n--) { load(n); if (CH_LO) __syncwarp(); }
      }
      pin();
#pragma unroll
      for (int kk = k; kk < k + 2; kk++) {
        mma16(dk, ak[4 * kk], ak[4 * kk + 1], ak[4 * kk + 2], ak[4 * kk + 3], b[2 * kk], b[2 * kk + 1]);
        mma16(dq, w[4 * kk], w[4 * kk + 1], w[4 * kk + 2], w[4 * kk + 3], b[2 * kk], b[2 * kk + 1]);
        if (kk < VK) mma16(dv, av[4 * kk], av[4 * kk + 1], av[4 * kk + 2], av[4 * kk + 3], b[2 * kk], b[2 * kk + 1]);
      }
    }
    const float k2 = 0.07216878364870322f * 1.44269504089f;
    stsm4t(qs, pack2(dq[0] * k2, dq[1] * k2), pack2(dq[2] * k2, dq[3] * k2), pack2(dk[0], dk[1]), pack2(dk[2], dk[3]));
    TM(1);
  };
  constexpr int VC = VK == 20 ? 1 : WG == 0 ? 2 : 3;
  auto finish_v = [&](const uint32_t (&b)[40], float (&dv)[16]) {
#pragma unroll
    for (int kk = VK; kk < 20; kk++) mma16(dv + 4 * ((kk - VK) % VC), av[4 * kk], av[4 * kk + 1], av[4 * kk + 2], av[4 * kk + 3], b[2 * kk], b[2 * kk + 1]);
  };
  auto sum_v = [&](float (&dv)[16]) {
#pragma unroll
    for (int i = 4; i < 4 * VC; i++) dv[i & 3] += dv[i];
  };
  auto publish_km = [&](int s) {
    uint32_t a[4];
    ldsm4(a, qa);
    *reinterpret_cast<uint2*>(kv(s, l8) + KV_M) = make_uint2(hadd2(a[0], a[2]), hadd2(a[1], a[3]));
  };
  auto memory_v = [&](uint2 x, const float (&dv)[16]) {
    return make_uint2(pack2(dv[0] + bf_lo(x.x), dv[1] + bf_hi(x.x)), pack2(dv[2] + bf_lo(x.y), dv[3] + bf_hi(x.y)));
  };
  auto publish_v = [&](int s, const uint4 (&v)[2], uint2 vm) {
#pragma unroll
    for (int e = 0; e < 2; e++) reinterpret_cast<uint4*>(kv(s, lw) + KV_V)[e * 32] = v[e];
    *reinterpret_cast<uint2*>(kv(s, l8) + KV_V + KV_M) = vm;
  };
#pragma unroll 1
  for (int s = 0; s < NSEG - 1; s++) {
    float dv[16] = {};
    uint32_t b[40], kf[16];
    project(s, b, dv, kf);
    if (WG == 0) {
      bar_sync(1, 256);
      if (CH_XA == 0) load_x(s, 20 + 5 * t4, 5, bXA);
      if (CH_XB == 0) load_x(s, 5 * t4, 5, bXB);
      pin();
      finish_v(b, dv);
      sum_v(dv);
      sts64(l8 + CH_VP, pack2(dv[0], dv[1]), pack2(dv[2], dv[3]));
      __syncwarp();
      if (elect()) mbar_arrive(bX);
      if (CH_XA == 1) load_x(s, 20 + 5 * t4, 5, bXA);
      if (CH_XB == 1) load_x(s, 5 * t4, 5, bXB);
      uint32_t w[144];
      auto wload = [&](int i) { ldsm4t(&w[4 * i], (i % 3 == 0 ? wo : i % 3 == 1 ? wo ^ 32 : wo2) + i / 12 * 28672 + i / 3 % 4 * 1024); };
      TM(3);
      if (CH_KP == 0) publish_k(s);
#pragma unroll
      for (int i = 0; i < CH_W1; i++) wload(i);
      bar_sync(10, 256);
      uint32_t km[4];
      ldsm4(km, qa);
      pin();
#pragma unroll
      for (int i = CH_W1; i < CH_W2; i++) wload(i);
      pin();
      const uint2 kms = make_uint2(hadd2(km[0], km[2]), hadd2(km[1], km[3]));
      if (CH_KM == 0) *reinterpret_cast<uint2*>(kv(s, l8) + KV_M) = kms;
      if (CH_KP == 0) bulk_wait_read<0>();
      if (CH_XA == 2) load_x(s, 20 + 5 * t4, 5, bXA);
      if (CH_XB == 2) load_x(s, 5 * t4, 5, bXB);
      bar_sync(2, 256);
      {
        float y[3][4] = {};
        uint32_t ob[24];
        ldsm4(&ob[0], l16 + CH_O + 1024); ldsm4(&ob[4], l16 + CH_O + 1536);
        TM(7);
        auto step = [&](int i) {
          const int k = i / 3;
          mma16(y[i % 3], w[4 * i], w[4 * i + 1], w[4 * i + 2], w[4 * i + 3], ob[2 * k], ob[2 * k + 1]);
        };
#pragma unroll
        for (int i = 0; i < 12; i++) {
          step(i);
          if (i >= 12 - (CH_W3 - CH_W2)) wload(CH_W3 - 12 + i);
          if (i % 3 == 2) pin();
        }
        if (CH_XB == 3) load_x(s, 5 * t4, 5, bXB);
        if (CH_KM == 1) *reinterpret_cast<uint2*>(kv(s, l8) + KV_M) = kms;
        pin();
        mbar_wait(bO, s & 1);
        TM(4);
        ldsm4(&ob[8], l16 + CH_O); ldsm4(&ob[12], l16 + CH_O + 512);
        pin();
        float2 inv;
        uint8_t* dst[6];
        uint32_t mask;
#pragma unroll
        for (int i = 12; i < 36; i++) {
          step(i);
          const int n = CH_W3 + i - 13, m = n - (n > 30);
          if (i == 12) ldsm4(&ob[16], l16 + after(w[4 * CH_W3 - 1] | w[4 * CH_W3 - 5] | w[4 * CH_W3 - 9] | ob[8]) + CH_O + 2048);
          else if (n == 30) ldsm4(&ob[20], l16 + CH_O + 2560);
          else if (m < 36) wload(m);
          else if (m == 36) inv = lds64f((l8 & ~0xe0u) + CH_VP);
          if (i == 26) mask = ((l16 ^ tag) & 48) == 0;
          if (i >= 27 && i < 33) dst[i - 27] = pool(line0(i - 27) * 8192 + (pages >> (i - 27) & 1) * 4096) + plane;
          if (i % 3 == 2) pin();
        }
#pragma unroll
        for (int k = 0; k < CH_R1; k++) ldsm4t(&tw[4 * k], wq + k * 2048);
        pin();
#pragma unroll
        for (int i = 0; i < 6; i++) stg_strong32(dst[i], pack_tag(y[i >> 1][2 * (i & 1)] * inv.x, y[i >> 1][2 * (i & 1) + 1] * inv.y, tag, mask));
        TM(8);
        TR(0, clk32());
        bar_arrive(5, 256);
        pin();
      }
      const uint32_t t0 = clk32();
      auto refill2 = [&]() {
#pragma unroll
        for (int k = CH_R1; k < CH_R2; k++) ldsm4t(&tw[4 * k], wq + k * 2048);
      };
      if (CH_RP == 0) refill2();
      const uint32_t ln = (l16 ^ tag) >> 4 & 31;
      if (t4 >= 2) {
        const uint32_t bP = bH + t4 * 16 - 24, ps = CH_PS + (t4 & 1) * 4096;
        auto fetch = [&](uint32_t k) {
          if (elect()) { mbar_expect(bP + (k & 1) * 8, 2048); bulk_load(sb + ps + (k & 1) * 2048, p.pool + (rsrc + (t4 & 1) * 2048), 2048, bP + (k & 1) * 8); }
        };
        until(t0 + CH_D0);
        fetch(pph);
        if (CH_RP == 2) refill2();
        if (!NOX) mbar_wait_hot(bXB, (s + 1) & 1);
        const uint32_t want = (tag & 1) * 0x10001, chk = opaque(ln < 4 ? 0x10001 : 0);
        uint4 sel;
        sel.x = opaque((ln >> 3) != (ln & 1) ? 0 : ln & 4 ? 0x3f800000u : 0x00003f80u);
        sel.z = opaque(sel.x); sel.y = opaque(ln); sel.w = opaque(ln + 1);
        uint8_t* mdst = p.pool + opaque(st * 32768 + rdst + (t4 & 1) * 64 + ln * 4);
        until(t0 + CH_D1);
        fetch(pph + 1);
        TM(5);
        if (CH_RP == 1) refill2();
        int n = 0;
        uint32_t u[16];
        for (;;) {
          mbar_wait(bP + (pph & 1) * 8, pph >> 1 & 1);
          TM(14);
          TR(2, clk32());
#pragma unroll
          for (int i = 0; i < 4; i++) ldsm4t(&u[4 * i], l16 + (ps + (pph & 1) * 2048) + i * 512);
          pph++;
          uint32_t bad = 0;
#pragma unroll
          for (int i = 0; i < 4; i++) bad = or3(bad, differ(u[4 * i], u[4 * i + 1], want), differ(u[4 * i + 2], u[4 * i + 3], want));
          if (!__any_sync(~0u, bad & chk)) break;
          fetch(pph + 1);
          spin_guard(n);
        }
        float y[4][4] = {};
#pragma unroll
        for (int i = 0; i < 8; i++) mma16(y[i & 3], sel.x, sel.y, sel.z, sel.w, u[2 * i], u[2 * i + 1]);
        TR(1, t0 + (n ? CH_D1 : CH_D0));
        TM(15);
        const uint32_t w = nz(pack2((y[0][0] + y[1][0]) + (y[2][0] + y[3][0]), (y[0][1] + y[1][1]) + (y[2][1] + y[3][1])));
        if (ln < 16) { stg_strong32(mdst, w); stg_strong32(mdst + 4096, w); }
        TMV(12, 32, n);
        TR(3, (clk32() & ~3u) | min(n, 3));
      } else {
        if (CH_RP) refill2();
        if (!NOX) mbar_wait_hot(bXB, (s + 1) & 1);
        stg_strong32(p.pool + ((st == 2 ? 0 : st + 1) * 32768 + rdst + t4 * 4096) + ln * 4, 0u);
        if (t4 == 0 && cta < 40 && s + 4 < NSEG && elect())
          asm volatile("cp.async.bulk.prefetch.L2.global [%0], 1024;" :: "l"(p.xc + (s + 4) * 10240 + cta * 256) : "memory");
        if (t4 == 1 && (s & 3) == 0 && s > 0 && elect()) red_relaxed(p.sync + 2 * s - 4, 1);
        if (t4 == 1 && s == NSEG - 3 && cta == 95 && elect()) red_relaxed(p.sync + 2 * s + 2, 0x10000);
      }
      TM(10);
      bar_arrive(8, 256);
      tokens0(s + 1, Int<CH_R2>());
      TM(2);
      TR(7, clk32());
    } else {
      const uint32_t xo = l4 + (CH_SX - (t4 == 3 ? 128 : 0)), x1 = xo + (r1 + 768 + min(t4, 2) * 256), x2 = xo + (r2 + 1024 + min(t4, 2) * 256);
      if (t4 < 2) {
        float ds[4][4] = {};
        uint32_t q[16];
        asm volatile("bar.sync 1, 256;" ::: "memory");
#pragma unroll
        for (int k = 0; k < 4; k++) ldsm4(&q[4 * k], qa + k * 512);
        pin();
        if (VK < 20) { finish_v(b, dv); pin(); }
#pragma unroll
        for (int k = 0; k < 4; k++) {
          mma16(ds[k & 1], kf[4 * k], kf[4 * k + 1], kf[4 * k + 2], kf[4 * k + 3], q[4 * k], q[4 * k + 1]);
          mma16(ds[2 + (k & 1)], kf[4 * k], kf[4 * k + 1], kf[4 * k + 2], kf[4 * k + 3], q[4 * k + 2], q[4 * k + 3]);
        }
        float t[4];
#pragma unroll
        for (int i = 0; i < 4; i++) t[i] = (ds[0][i] + ds[2][i]) + (ds[1][i] + ds[3][i]);
        const uint32_t w0 = pack2(t[0], t[1]), w1 = pack2(t[2], t[3]);
        st_async32(x1, w0, bX + r1); st_async32(x2, w0, bX + r2);
        st_async32(x1 + 128, w1, bX + r1); st_async32(x2 + 128, w1, bX + r2);
        sts32(xo, w0); sts32(xo + 128, w1);
      } else {
        float ds[4][4] = {};
        uint32_t q0[4], q1[4], a0[4], a1[4];
        asm volatile("bar.sync 1, 256; " ::: "memory");
        ldsm4(a0, ka); ldsm4(q0, qa); ldsm4(a1, ka + 512); ldsm4(q1, qa + 512);
        pin();
        if (VK < 20) { finish_v(b, dv); pin(); }
        mma16(ds[0], a0[0], a0[1], a0[2], a0[3], q0[0], q0[1]);
        mma16(ds[1], a0[0], a0[1], a0[2], a0[3], q0[2], q0[3]);
        mma16(ds[2], a1[0], a1[1], a1[2], a1[3], q1[0], q1[1]);
        mma16(ds[3], a1[0], a1[1], a1[2], a1[3], q1[2], q1[3]);
        float t[2];
#pragma unroll
        for (int i = 0; i < 2; i++)
          t[i] = ((ds[0][i] + ds[0][i + 2]) + (ds[1][i] + ds[1][i + 2])) + ((ds[2][i] + ds[2][i + 2]) + (ds[3][i] + ds[3][i + 2]));
        const uint32_t w0 = pack2(t[0], t[1]);
        st_async32(x1, w0, bX + r1);
        st_async32(x2, w0, bX + r2);
        sts32(xo, w0);
      }
      TM(3);
      const uint4 id = lds128(l16 + CH_ID);
      float sc[3][4] = {};
      uint4 v[2];
      sum_v(dv);
      bar_sync(3, 128);
      uint32_t r[12], wd[12], we[12] = {};
      ldsm4(&r[0], l16 + CH_SX); ldsm2(&r[4], l16 + CH_SX + 512);
      pin();
      v[0] = lds128(lw + CH_VT); v[1] = lds128(lw + CH_VT + 512);
#pragma unroll
      for (int u = 0; u < 3; u++) ldsm4t(&wd[4 * u], wo + u * 28672);
      if (CH_WE && j == 0) {
#pragma unroll
        for (int u = 0; u < 3; u++) ldsm4t(&we[4 * u], (wo ^ 32) + u * 28672);
      }
      pin();
#pragma unroll
      for (int q = 0; q < 3; q++) mma16(sc[q], id.x, id.y, id.z, id.w, r[2 * q], r[2 * q + 1]);
      uint32_t big = absmax2(absmax2(absmax2(r[0], r[1]), absmax2(r[2], r[3])), absmax2(r[4], r[5]));
      const uint32_t oa1 = l4 + (r1 + CH_O), oa2 = l4 + (r2 + CH_O + 2048), ones = 0x3f803f80u;
      mbar_wait_hot(bX, s & 1);
      TM(4);
      ldsm4(&r[0], l16 + CH_SX + 768); ldsm4(&r[8], l16 + CH_SX + 1792); ldsm4(&r[4], l16 + CH_SX + 1280);
      const uint2 vp = lds64(l8 + CH_VP);
      bar_arrive(10, 256);
      pin();
      {
        float sd[3][4] = {};
#pragma unroll
        for (int i = 0; i < 3; i++) {
          const int q = i == 0 ? 0 : 3 - i;
          mma16(sc[q], id.x, id.y, id.z, id.w, r[4 * q], r[4 * q + 1]);
          mma16(sd[q], id.x, id.y, id.z, id.w, r[4 * q + 2], r[4 * q + 3]);
          big = absmax2(big, absmax2(absmax2(r[4 * q], r[4 * q + 1]), absmax2(r[4 * q + 2], r[4 * q + 3])));
        }
#pragma unroll
        for (int i = 0; i < 12; i++) sc[i >> 2][i & 3] += sd[i >> 2][i & 3];
      }
      const bool redo = __any_sync(~0u, (absmax2(big, big << 16) & 0x7fff0000u) >= 0x41800000u);
      const uint2 vm = memory_v(vp, dv);
      sc[2][0] += sc[2][2]; sc[2][1] += sc[2][3];
      float l[4], o[2][4];
      uint32_t p3, p4;
      auto attend = [&]() {
#pragma unroll
        for (int i = 0; i < 4; i++) l[i] = o[0][i] = o[1][i] = 0.f;
        const uint32_t p1 = pack2(ex2(sc[0][0]), ex2(sc[0][1])), p2 = pack2(ex2(sc[0][2]), ex2(sc[0][3]));
        mma16h(o[0], p1, p2, v[0].x, v[0].y);
        mma16h(o[1], p1, p2, v[0].z, v[0].w);
        mma16h(l, p1, p2, ones, ones);
        const uint32_t p0 = pack2(ex2(sc[2][0]), ex2(sc[2][1]));
        mma8h(o[0], p0, vm.x);
        mma8h(o[1], p0, vm.y);
        mma8h(l, p0, ones);
        p3 = pack2(ex2(sc[1][0]), ex2(sc[1][1])); p4 = pack2(ex2(sc[1][2]), ex2(sc[1][3]));
        mma16h(o[0], p3, p4, v[1].x, v[1].y);
        mma16h(o[1], p3, p4, v[1].z, v[1].w);
      };
      attend();
      if (__builtin_expect(redo, 0)) {
        float mx = fmaxf(sc[2][0], sc[2][1]);
#pragma unroll
        for (int i = 0; i < 4; i++) mx = fmaxf(mx, fmaxf(sc[0][i], sc[1][i]));
        mx = fmaxf(mx, __shfl_xor_sync(~0u, mx, 1));
        mx = fmaxf(mx, __shfl_xor_sync(~0u, mx, 2));
#pragma unroll
        for (int i = 0; i < 4; i++) { sc[0][i] -= mx; sc[1][i] -= mx; }
        sc[2][0] -= mx; sc[2][1] -= mx;
        attend();
      }
      const uint32_t o0 = pack2(o[0][0], o[0][1]), o1 = pack2(o[1][0], o[1][1]);
      st_async32(oa1, o0, bO + r1); st_async32(oa2, o0, bO + r2);
      st_async32(oa1 + 128, o1, bO + r1); st_async32(oa2 + 128, o1, bO + r2);
      sts32(l4 + CH_O + 1024, o0); sts32(l4 + CH_O + 1152, o1);
      bar_arrive(2, 256);
      pin();
      TM(6);
      mma16h(l, p3, p4, ones, ones);
      float inv;
      asm("rcp.approx.ftz.f32 %0, %1;" : "=f"(inv) : "f"(l[0]));
      sts32((l8 & ~0xffu) + (lane & 28) + CH_VP, __float_as_uint(inv));
      __syncwarp();
      if (elect()) mbar_arrive(bO);
      {
        float z[2][4] = {}, y[2][4] = {};
        mma16(z[0], wd[0], wd[1], wd[2], wd[3], o0, o1);
        if (j == 0) {
#pragma unroll
          for (int u = 0; u < 3; u++) if (!CH_WE) ldsm4t(&we[4 * u], (wo ^ 32) + u * 28672);
          mma16(y[0], we[0], we[1], we[2], we[3], o0, o1);
        }
        const float2 iv = lds64f((l8 & ~0xe0u) + CH_VP);
        uint8_t* dst = pool(pdst[0]);
        const uint32_t mask = ((l16 ^ tag) & 48) == 0;
        const uint32_t oa = qa + ((tag & 0xfffe) + CH_O - CH_QK + t4 * 256 - (t4 == 3 ? 1024 : 0));
        const uint32_t za = l16 + ((tag & 0xfffe) + (t4 >> 1) * 512 + (t4 & 1) * 8);
        pin();
        mbar_wait(bO, s & 1);
        uint32_t a[4];
        ldsm4(a, oa);
        mma16(z[0], wd[4], wd[5], wd[6], wd[7], a[0], a[1]);
        mma16(z[1], wd[8], wd[9], wd[10], wd[11], a[2], a[3]);
        if (j == 0) {
          mma16(y[0], we[4], we[5], we[6], we[7], a[0], a[1]);
          mma16(y[1], we[8], we[9], we[10], we[11], a[2], a[3]);
          sts128f(lw + CH_VT + 512, y[0][0] + y[1][0], y[0][1] + y[1][1], y[0][2] + y[1][2], y[0][3] + y[1][3]);
        }
        sts128f(lw + CH_VT, z[0][0] + z[1][0], z[0][1] + z[1][1], z[0][2] + z[1][2], z[0][3] + z[1][3]);
        bar_sync(3, 128);
        if (j == 0 || t4 < 2) {
          float2 q[4];
#pragma unroll
          for (int i = 0; i < 4; i++) q[i] = lds64f(za + CH_VT + i * 1024);
          stg_strong32(dst, pack_tag(((q[0].x + q[1].x) + (q[2].x + q[3].x)) * iv.x, ((q[0].y + q[1].y) + (q[2].y + q[3].y)) * iv.y, tag, mask));
        }
      }
      TM(2);
      if (!NOX) mbar_wait_hot(bXA, (s + 1) & 1);
      if (CH_KP == 2) bulk_wait_read<0>();
      float dk[16], dw[16];
      bar_sync(5, 256);
      wg_fence();
      pass(dk, ak, Int<0>(), Int<20>());
      pass(dw, av, Int<0>(), Int<20>());
      TM(5);
      pin();
      if (CH_EX == 0) publish_v(s, v, vm);
      if (elect()) {
        mbar_expect(bG + t4 * 8, 2560);
        if (t4 == 1 && s + 2 < NSEG) { mbar_expect(bX, 1536); mbar_expect(bO, 2048); }
      }
      if (CH_KD == 0) { wg_wait<1>(); dump(dk, lw + CH_KT); }
      wg_wait<0>();
      if (CH_KD == 1) dump(dk, lw + CH_KT);
      TM(7);
      dump(dw, lw + CH_VT);
      bar_arrive(9, 256);
      pin();
#pragma unroll
      for (int k = 0; k < CH_RB; k++) ldsm4t(&tw[4 * k], wq + k * 2048);
      if (t4 < 2) {
#pragma unroll
        for (int k = CH_RB; k < CH_RC; k++) ldsm4t(&tw[4 * k], wq + k * 2048);
        const int q = t4 ? 3 : j, o = t4 ? j * 896 : 0;
        const uint8_t* src = p.pool + ((80 + st * 4 + q) * 8192 + (pages >> (st * 4 + q) & 1) * 4096 + o);
        asm volatile("bar.sync 8, 256;" ::: "memory");
        const uint32_t t1 = clk32() + CH_D2;
        if (CH_EX == 1) publish_v(s, v, vm);
        auto fetch = [&](auto n) {
          mbar_wait(bH, s & 1);
          until(t1);
          TR(4, clk32());
          if (elect())
            asm volatile("cp.async.bulk.shared::cluster.global.mbarrier::complete_tx::bytes.multicast::cluster [%0], [%1], %2, [%3], 7;"
                         :: "r"(sb + CH_M + q * 2560 + o), "l"(src), "n"(n.value), "r"(bG + q * 8) : "memory");
        };
        if (!t4) fetch(Int<2560>()); else if (j == 2) fetch(Int<768>()); else fetch(Int<896>());
      } else {
        asm volatile("bar.sync 8, 256; " ::: "memory");
        if (elect()) asm volatile("mbarrier.arrive.relaxed.cluster.shared::cluster.b64 _, [%0];" :: "r"(bH + (t4 == 2 ? r1 : r2)) : "memory");
        pin();
        if (CH_EX == 1) publish_v(s, v, vm);
#pragma unroll
        for (int k = CH_RB; k < CH_RC; k++) ldsm4t(&tw[4 * k], wq + k * 2048);
      }
      TM(9);
      pin();
#pragma unroll
      for (int k = CH_RC; k < CH_TW; k++) ldsm4t(&tw[4 * k], wq + k * 2048);
      if (CH_KP == 2 && t4 == CH_KW) { bar_sync(7, 160); publish_k(s + 1); }
      TM(10);
    }
    if (++st == 3) st = 0;
    tag ^= 0x10001;
  }
  {
    const int s = NSEG - 1;
    float dv[16] = {};
    uint32_t b[40], kf[16];
    project(s, b, dv, kf);
    finish_v(b, dv);
    sum_v(dv);
    if (WG == 0) {
      sts64(l8 + CH_VP, pack2(dv[0], dv[1]), pack2(dv[2], dv[3]));
      bar_sync(1, 256);
      if (CH_KP == 0) publish_k(s);
      publish_km(s);
      bulk_wait<0>();
      fence_async_global();
      bar_sync(2, 256);
      if (tid == 0) red_release(g_sync + 15 * 8 + 4, 1);
    } else {
      const uint4 v[2] = {lds128(lw + CH_VT), lds128(lw + CH_VT + 512)};
      bar_sync(1, 256);
      publish_v(s, v, memory_v(lds64(l8 + CH_VP), dv));
      bulk_wait<0>();
      fence_async_global();
      bar_arrive(2, 256);
    }
  }
}

__global__ void __launch_bounds__(256, 1) chain_kernel(const __grid_constant__ ChainParams p) {
  extern __shared__ __align__(1024) uint8_t smem_raw[];
  const uint32_t sb = s2u(smem_raw);
  const int tid = threadIdx.x, warp = __shfl_sync(~0u, tid >> 5, 0), lane = tid & 31;
  const int cta = blockIdx.x, h = cta / 3, j = cta - 3 * h, colbase = cta * 64;
  const uint32_t bWo = sb + CH_BAR, bWq = bWo + 8, bXA = bWo + 24, bWk = bWo + 80, bWv = bWo + 88;
  uint32_t smid; asm("mov.u32 %0, %%smid;" : "=r"(smid));
  PRO(0);
  if (sb != mapa(CH_BASE, j)) __trap();
  uint32_t entry = 0;
  auto place = [&]() {
    const int i = tid - 128;
    if (i >= 0 && i <= NSLOT) {
      const uint32_t side = ldg_strong32(g_smpart + (smid & 255));
      if (i < NSLOT) {
        entry = i * 8192 + (ldg_strong32(g_orient + i) == (i < 80 ? i & 1 : side) ? 0 : 4096);
      } else {
        entry = 2 * (atomicAdd(g_bo + p.layer * 128 + 1, 1 << 8 * side) >> 8 * side & 255) + side;
      }
    }
    __syncwarp();
  };
  if (p.layer) place();
  if (warp == 0 && elect()) {
#pragma unroll 1
    for (int i = 0; i < 17; i++) mbar_init(bWo + 8 * i, i == 2 || i == 5 ? 5 : i == 3 || i == 4 ? 4 : i == 12 ? 2 : 1);
    asm volatile("fence.mbarrier_init.release.cluster;" ::: "memory");
    mbar_expect(bWk, 81920);
    tma_load3<(WEF & 1) != 0>(sb + CH_WQ, &p.wk, colbase, 0, bWk);
    mbar_expect(bWv, 81920);
    tma_load3<(WEF & 1) != 0>(sb + CH_WO, &p.wv, colbase, 0, bWv);
    mbar_expect(bWo + 16, 1536);
    mbar_expect(bWo + 40, 2048);
    mbar_expect(bWo, 86016); mbar_expect(bWq, 81920);
#pragma unroll 1
    for (int i = 0; i < 8; i++) mbar_expect(bXA + 8 * (i & 1), 5120);
  }
  if (warp == 1) {
    const uint32_t id = (lane >> 3) == (lane & 3) ? ((lane & 4) ? 0x3f800000u : 0x00003f80u) : 0u;
    sts128(sb + CH_ID + lane * 16, make_uint4(id, 0, 0, id));
  }
  __syncthreads();
  asm volatile("barrier.cluster.arrive.relaxed.aligned;" ::: "memory");
  uint32_t ak[80], av[80];
  const uint32_t wq = opaque(sb + CH_WQ + ((warp >> 2) * 320 + (lane & 7) + (lane >> 4) * 8) * 128 + (((2 * (warp & 3) + ((lane >> 3) & 1)) ^ (lane & 7)) << 4));
  pdl_wait();
  if (tid == 32) stg_strong32(g_smuse + (smid & 255), p.layer + 1);
  pdl_launch();
  PRO(1);
  if (warp == 0 && elect()) {
    bulk_load(sb + CH_X + 20480, p.xc + 5120, 20480, bXA);
    bulk_load(sb + CH_X, p.xc, 20480, bXA + 8);
  }
  if (!p.layer) place();
  __syncwarp();
  PRO(2);
  mbar_wait(bWk, 0);
  PRO(3);
#pragma unroll
  for (int k = 0; k < 20; k++) ldsm4t(&ak[4 * k], wq + k * 2048);
  bar_sync(6, 256);
  if (warp == 0 && elect()) tma_load3<(WEF & 2) != 0>(sb + CH_WQ, &p.wq, colbase, 0, bWq);
  __syncwarp();
  PRO(4);
  mbar_wait(bWv, 0);
  PRO(5);
#pragma unroll
  for (int k = 0; k < 20; k++) ldsm4t(&av[4 * k], wq + CH_WO + k * 2048);
  bar_sync(6, 256);
  PRO(6);
  if (warp >= 5 && elect()) tma_load3<(WEF & 2) != 0>(sb + CH_WO + (warp - 5) * 28672, &p.wo, j == 0 ? 0 : 32 + j * 192, h * 192 + (j + 8 - warp) % 3 * 64, bWo);
  if (tid == 128 + NSLOT && entry >= 80) {
    uint32_t c;
    int n = 0;
    do { c = ldg_strong32(g_bo + p.layer * 128 + 1); spin_guard(n); } while ((c & 255) + (c >> 8) < 96);
    const uint32_t other = (c >> 8 * (~entry & 1) & 255) + (entry >> 1) - 40;
    entry = other < 40 ? 2 * other + (~entry & 1) : entry % 80;
  }
  if (tid >= 128 && tid <= 128 + NSLOT) sts32(sb + CH_O + (tid - 128) * 4, entry);
  PRO(7);
  __syncthreads();
  if (__shfl_sync(~0u, tid >> 7, 0) == 0) chain_body<0>(p, wq, ak, av); else chain_body<1>(p, wq, ak, av);
}

struct PostParams { CUtensorMap wq, wo, wb, wo2, wb2; int gap, share, layer, look, gap2, pol; };
constexpr int PS = 8, PB = 28672;
constexpr int OP_SMEM = PS * PB + 512 + 2048;
enum { IT_ATT = 0, IT_OP = 1, IT_FIN = 2, IT_BQ = 3, IT_Q = 4 };

__device__ __forceinline__ uint32_t item_count(int type, int b) {
  return type == IT_ATT ? 32 : type == IT_OP ? op_split(b) * (DM / op_width(b)) : type == IT_FIN ? fin_items(b) : 1920 / bq_width(b); }
__device__ __forceinline__ uint32_t item_need(int type, int b) { return type == IT_ATT ? 96 : item_count(type - 1, b); }

struct Ring {
  uint32_t sb, bars; int st; uint32_t ph;
  __device__ __forceinline__ uint32_t wait() const { mbar_wait(bars + 8 * st, ph); return sb + st * PB; }
  __device__ __forceinline__ void next() { if (++st == PS) { st = 0; ph ^= 1; } }
  __device__ __forceinline__ void release(int s) const { if ((threadIdx.x & 31) == 0) mbar_arrive(bars + 8 * (PS + s)); }
  __device__ __forceinline__ void pop() { __syncwarp(); release(st); next(); }
};

template <int N>
__device__ __forceinline__ void gemm_item(Ring& r, float* d, int nst, uint32_t go, int go_at) {
  int prev = 0;
#pragma unroll 1
  for (int kb = 0; kb < nst; kb++) {
    const uint32_t base = r.wait();
    const uint64_t da = mkdesc(base + (threadIdx.x >> 7) * 4096, 128, 512, 0), db = mkdesc(base + 8192, 4096, 1024, 1);
    wg_fence();
#pragma unroll
    for (int kk = 0; kk < 2; kk++) {
      if (N == 80) wg_ss80_01(d, da + kk * 16, db + kk * 128, (kb | kk) != 0);
      if (N == 160) wg_ss160_01(d, da + kk * 16, db + kk * 128, (kb | kk) != 0);
      if (N >= 192) wg_ss192_01(d, da + kk * 16, db + kk * 128, (kb | kk) != 0);
      if (N == 320) wg_ss128_01(d + 96, da + kk * 16, db + kk * 128 + 3 * 256, (kb | kk) != 0);
    }
    wg_commit();
    if (kb == go_at && threadIdx.x == 0) mbar_arrive(go);
    if (kb > 0) { wg_wait<1>(); r.release(prev); }
    prev = r.st;
    r.next();
  }
  wg_wait<0>();
  reg_fence<N / 2>(d);
  r.release(prev);
}

template <int HALF>
__device__ __forceinline__ void attn_a_warp(Ring& r, const uint32_t (&q)[48], int b, int h) {
  constexpr int NT = HALF ? 5 : 3, NF = 8 * NT;
  const int lane = threadIdx.x & 31, g = lane >> 2, c = lane & 3, seg = (threadIdx.x >> 5) & 3;
  uint32_t f[6][NF];
  int slot[6];
  auto fetch = [&](int u) {
    const uint32_t kv = r.wait() + seg * KV_BYTES;
    slot[u] = r.st;
    r.next();
#pragma unroll
    for (int w = 0; w < 4; w++) {
      uint32_t* d = &f[u][2 * NT * w];
#pragma unroll
      for (int t = 0; t <= HALF; t++) {
        if (u < 3) {
          ldsm4(d + 4 * t, kv + w * 1024 + t * 512 + (lane & 8) * 32 + (lane & 16) * 8 + (lane & 7) * 16);
        } else {
          const uint4 v = lds128(kv + w * 1024 + t * 512 + lane * 16);
          d[4 * t] = v.x; d[4 * t + 1] = v.y; d[4 * t + 2] = v.z; d[4 * t + 3] = v.w;
        }
      }
      const uint2 m = lds64(kv + KV_M + w * 256 + lane * 8);
      d[2 * NT - 2] = m.x; d[2 * NT - 1] = m.y;
    }
    pdl_launch();
  };
  float s[NT][4] = {};
  fetch(0);
#pragma unroll
  for (int u = 0; u < 3; u++) {
    fetch(u + 1);
#pragma unroll
    for (int kk = 0; kk < 4; kk++) {
      const uint32_t* a = &q[16 * u + 4 * kk];
#pragma unroll
      for (int n = 0; n < NT; n++) mma16(s[(n + 1) % NT], a[0], a[1], a[2], a[3], f[u][2 * NT * kk + 2 * n], f[u][2 * NT * kk + 2 * n + 1]);
    }
    r.release(slot[u]);
    pdl_launch();
  }
  fetch(4);
  const float k2 = 0.07216878364870322f * 1.44269504089f, NEG = -INFINITY;
  if (2 * c > g) { s[NT - 2][0] = NEG; s[NT - 1][2] = NEG; }
  if (2 * c + 1 > g) { s[NT - 2][1] = NEG; s[NT - 1][3] = NEG; }
  s[NT - 1][0] = s[NT - 1][1] = NEG;
  uint32_t pp[NT][2]; float inv[2];
#pragma unroll
  for (int hh = 0; hh < 2; hh++) {
    float m = NEG, l = 0.f;
#pragma unroll
    for (int n = 0; n < NT; n++) m = fmaxf(m, fmaxf(s[n][2 * hh], s[n][2 * hh + 1]));
    m = fmaxf(m, __shfl_xor_sync(~0u, m, 1)); m = fmaxf(m, __shfl_xor_sync(~0u, m, 2));
#pragma unroll
    for (int n = 0; n < NT; n++) { const float x = ex2((s[n][2 * hh] - m) * k2), y = ex2((s[n][2 * hh + 1] - m) * k2); l += x + y; pp[n][hh] = pack2(x, y); }
    l += __shfl_xor_sync(~0u, l, 1); l += __shfl_xor_sync(~0u, l, 2);
    asm("rcp.approx.ftz.f32 %0, %1;" : "=f"(inv[hh]) : "f"(l));
  }
  uint32_t* dst = g_o + ((b * 192 + h * 6) * 16 + seg * 4 + HALF * 2) * 128 + lane;
#pragma unroll
  for (int u = 3; u < 6; u++) {
    float o[8][4] = {};
#pragma unroll
    for (int n = 0; n < 8; n++) mma8(o[n], pp[0][0], pp[0][1], f[u][2 * NT * (n >> 1) + 2 * NT - 2 + (n & 1)]);
#pragma unroll
    for (int t = 0; t <= HALF; t++)
#pragma unroll
      for (int n = 0; n < 8; n++) {
        const uint32_t* v = &f[u][2 * NT * (n >> 1) + 4 * t + 2 * (n & 1)];
        mma16(o[n], pp[1 + 2 * t][0], pp[1 + 2 * t][1], pp[2 + 2 * t][0], pp[2 + 2 * t][1], v[0], v[1]);
      }
    r.release(slot[u]);
    if (u == 3) fetch(5);
#pragma unroll
    for (int n = 0; n < 8; n++) {
      dst[(u - 3) * 4096 + (n >> 2) * 2048 + (n & 3) * 32] = pack2(o[n][0] * inv[0], o[n][1] * inv[0]);
      dst[(u - 3) * 4096 + (n >> 2) * 2048 + (n & 3) * 32 + 128] = pack2(o[n][2] * inv[1], o[n][3] * inv[1]);
    }
  }
}

template <int NG>
__device__ __forceinline__ void fin_item(Ring& r, uint32_t scratch, int b, int idx) {
  const int warp = threadIdx.x >> 5, lane = threadIdx.x & 31;
  float4* x = g_x + ((b * 16 + idx * NG) * 40 + warp * 5) * 32 + lane;
  float4 v[NG][5];
#pragma unroll
  for (int g = 0; g < NG; g++) {
    const uint32_t base = r.wait();
#pragma unroll
    for (int i = 0; i < 5; i++) v[g][i] = lds128f(base + ((warp * 5 + i) * 32 + lane) * 16);
    r.pop();
  }
#pragma unroll 1
  for (int k = 0; k < op_split(b); k += NG == 1 ? 2 : 1) {
#pragma unroll
    for (int g = 0; g < NG; g += 2) {
      const uint32_t base = r.wait();
#pragma unroll
      for (int i = 0; i < 10; i++) {
        const uint2 q = lds64(base + ((i / 5 * 40 + warp * 5 + i % 5) * 32 + lane) * 8);
        float4& t = v[(g + i / 5) % NG][i % 5];
        t.x += bf_lo(q.x); t.y += bf_hi(q.x); t.z += bf_lo(q.y); t.w += bf_hi(q.y);
      }
      r.pop();
    }
  }
  float mean[NG], rs[NG];
  ln_stats<NG>(v, scratch, mean, rs);
#pragma unroll
  for (int i = 0; i < 5; i++) {
    const int u = warp * 5 + i;
    uint32_t* xn = g_xn + ((b * 20 + (u >> 1)) * 16 + idx * NG) * 128 + (u & 1) * 64 + lane;
#pragma unroll
    for (int g = 0; g < NG; g++) {
      xn[g * 128] = pack2((v[g][i].x - mean[g]) * rs[g], (v[g][i].y - mean[g]) * rs[g]);
      xn[g * 128 + 32] = pack2((v[g][i].z - mean[g]) * rs[g], (v[g][i].w - mean[g]) * rs[g]);
    }
  }
#pragma unroll
  for (int g = 0; g < NG; g++)
#pragma unroll
    for (int i = 0; i < 5; i++) x[(g * 40 + i) * 32] = v[g][i];
}

__global__ void __launch_bounds__(384, 1) post_kernel(const __grid_constant__ PostParams p) {
  extern __shared__ __align__(1024) uint8_t smem_raw[];
  const uint32_t sb = s2u(smem_raw), bars = sb + PS * PB;
  const uint32_t bIF = bars + 128, bIE = bars + 160, done = bars + 192, bGo = bars + 224, slots = bars + 240, scratch = bars + 512;
  const int warp = __shfl_sync(~0u, threadIdx.x >> 5, 0), lane = threadIdx.x & 31;
  TRACE(0);
  pdl_launch();
  if (sb & 1023) __trap();
  if (threadIdx.x < 29) mbar_init(bars + 8 * threadIdx.x, threadIdx.x < 8 ? 1 : threadIdx.x < 16 ? 8 : threadIdx.x < 20 ? 1 : threadIdx.x < 24 ? 2 : threadIdx.x < 28 ? 8 : 1);
  fence_async();
  __syncthreads();
  if (warp >= 8) {
    asm volatile("setmaxnreg.dec.sync.aligned.u32 56;");
    if (warp == 9) {
      const int b = lane & 15;
      bool queries = QA_END < 16 && blockIdx.x < 36;
      for (int n = 0;; n++) {
        if (n > 0) mbar_wait(bGo, (n - 1) & 1);
        mbar_wait(bIE + 8 * (n & 3), ((n >> 2) & 1) ^ 1);
        int code = -1, spin = 0, ticket = 0;
        if (queries) {
          if (lane == 0) ticket = atomicAdd(g_sync + SY_QC, 1);
          ticket = __shfl_sync(~0u, ticket, 0);
          queries = ticket < (16 - QA_END) * 32;
          if (queries) code = IT_Q << 16 | (QA_END + ticket % (16 - QA_END)) << 8 | ticket / (16 - QA_END);
        }
        if (!queries && lane == 0) ticket = atomicAdd(g_sync + SY_T, 1);
        while (!queries) {
          const uint4 hd = ldg_strong128(g_sync + b * 8), pr = ldg_strong128(g_sync + b * 8 + 4);
          const uint32_t hv[4] = {hd.x, hd.y, hd.z, hd.w}, pv[4] = {pr.x, pr.y, pr.z, pr.w};
          const uint32_t chain_done = __ballot_sync(~0u, (pr.x & 0xffff) >= 96) & 0xffff;
          int left[4], avail[4], rdy = 0, claimed = 0, upstream = 0;
#pragma unroll
          for (int t = 0; t < 4; t++) {
            const int cnt = lane < 16 ? item_count(t, b) : 0;
            left[t] = max(cnt - (int)hv[t], 0);
            claimed += cnt - left[t];
            const bool ready = (pv[t] & 0xffff) >= item_need(t, b);
            rdy |= ready << t;
            bool ok = ready || (t == IT_ATT ? pr.x >= 0x10000 : !upstream || (t == IT_OP && (chain_done >> 15 & 1)));
            if (t == IT_BQ && (chain_done >> BQ_HOLD & 1) && !(chain_done >> 15)) ok = false;
            avail[t] = ok ? left[t] : 0;
            upstream |= __any_sync(~0u, left[t] > 0);
          }
          if (!upstream) break;
          int rank = max(__shfl_sync(~0u, ticket, 0) - __reduce_add_sync(~0u, claimed), 0), type = -1, mine = 0;
#pragma unroll
          for (int c = 0; c < 8; c++) {
            const int t = c == 0 || c == 5 ? IT_FIN : c == 1 || c == 7 ? IT_ATT : c == 2 || c == 4 ? IT_OP : IT_BQ;
            int a = c == 1 || ((rdy >> t & 1) == (c < 4)) ? avail[t] : 0;
            if (t == IT_OP && !(p.pol & 1)) a = c == 2 ? avail[t] : 0;
            if (c == 7) a = b < QA_END && !(rdy & 1) && ((chain_done << 1 | 1) >> b & 1) ? left[t] : 0;
            const int tot = __reduce_add_sync(~0u, a);
            if (type < 0) { if (rank < tot) { type = t; mine = a; } else rank -= tot; }
          }
          if (type >= 0) {
#pragma unroll
            for (int o = 1; o < 16; o <<= 1) { const int y = __shfl_up_sync(~0u, mine, o); if (lane >= o) mine += y; }
            const int blk = __ffs(__ballot_sync(~0u, mine > rank)) - 1;
            const int early = !(__shfl_sync(~0u, rdy, blk) >> type & 1);
            uint32_t idx = 0;
            if (lane == 0) { idx = atomicAdd(g_sync + blk * 8 + type, 1); ld_acquire(g_sync + blk * 8 + 4 + type); }
            idx = __shfl_sync(~0u, idx, 0);
            if (idx < item_count(type, blk)) { code = (chain_done >> 15 & 1) << 22 | (chain_done >> p.look & 1) << 21 | early << 20 | type << 16 | blk << 8 | idx; break; }
          } else {
            __nanosleep(50);
          }
          spin_guard(spin);
        }
        if (lane == 0) {
          fence_async_global();
          sts32(slots + 4 * (n & 3), code);
          mbar_arrive(bIF + 8 * (n & 3));
        }
        __syncwarp();
        if (code < 0) break;
      }
    } else if (warp == 8) {
      uint32_t smid, nsm, peers = 0;
      asm("mov.u32 %0, %%smid;" : "=r"(smid)); asm("mov.u32 %0, %%nsmid;" : "=r"(nsm));
      for (uint32_t i = lane; i < min(nsm, 256u); i += 32)
        peers += abs((int)(g_smclk[i] - g_smclk[smid & 255])) < 4000 && ldg_strong32(g_smuse + i) != p.layer + 1;
      const uint32_t gap0 = max(p.gap, (int)min(__reduce_add_sync(~0u, peers), 18u) * p.share >> 3);
      if (elect()) {
        uint32_t dst = sb, bar = bars, ph = 1, next = clk32(), gap = 0;
        auto acquire = [&](uint32_t kb) {
          mbar_wait(bar + 8 * PS, ph);
          mbar_expect(bar, kb * 1024);
          if (gap) {
            uint32_t now;
            do now = clk32(); while ((int)(now - next) < 0);
            next = ((int)(now - next) > 100 ? now - 100 : next) + kb * gap;
          }
        };
        auto advance = [&]() { dst += PB; bar += 8; if (dst == bars) { dst = sb; bar = bars; ph ^= 1; } };
        auto depend = [&](const uint32_t* c, uint32_t need) { wait_count(c, need); fence_async_global(); };
#pragma unroll 1
        for (int n = 0;; n++) {
          mbar_wait(bIF + 8 * (n & 3), (n >> 2) & 1);
          const int code = (int)lds32(slots + 4 * (n & 3));
          if (code < 0) break;
          const int type = (code >> 16) & 15, b = (code >> 8) & 255, idx = code & 255;
          const bool early = code >> 20 & 1, go = !(code >> 21 & 1);
          mbar_arrive(bIE + 8 * (n & 3));
          gap = !(code >> 22 & 1) ? gap0 : type == IT_ATT || type == IT_FIN ? 0 : p.gap2;
          const uint32_t* progress = g_sync + b * 8 + 4 + type;
          if (type == IT_ATT && b >= QA_END) {
            depend(g_sync + SY_Q, (16 - QA_END) * 32);
#pragma unroll 1
            for (int u = 0; u < 2; u++) { acquire(24); bulk_load_last(dst, g_q + (((b - QA_END) * 32 + idx) * 2 + u) * 1536, 24576, bar); advance(); }
          } else if (type == IT_FIN) {
            const int ng = 16 / fin_items(b), lg = ng >> 1;
#pragma unroll 1
            for (int g = 0; g < ng; g++) { acquire(20); bulk_load(dst, g_x + (b * 16 + idx * ng + g) * 1280, 20480, bar); advance(); }
            if (early) depend(progress, item_need(type, b));
            if (go) mbar_arrive(bGo);
#pragma unroll 1
            for (int i = 0; i < op_split(b) * ng; i += 2) {
              const uint2* src = g_part + ((b * 16 + (i >> lg)) * 16 + idx * ng + (i & (ng - 1))) * 1280;
              acquire(20);
              bulk_load_last(dst, src, ng > 1 ? 20480 : 10240, bar);
              if (ng == 1) bulk_load_last(dst + 10240, src + 16 * 1280, 10240, bar);
              advance();
            }
          } else {
            const bool op = type == IT_OP, bq = type == IT_BQ;
            const int width = op ? op_width(b) : bq ? bq_width(b) : 192, nb = (width + 63) >> 6, lt = width == 320 ? 1 : 2;
            const int nst = op ? 192 / op_split(b) : 20, kb0 = op ? (idx >> lt) * nst : 0;
            const int col = (op ? idx & ((1 << lt) - 1) : idx) * width;
            const bool whole = !(width & 63);
            const CUtensorMap* m = op ? (whole ? &p.wo : &p.wo2) : bq ? (whole ? &p.wb : &p.wb2) : &p.wq;
            const uint32_t* a = op ? g_o + (b * 192 + kb0) * 2048 : g_xn + b * 20 * 2048;
            int row = kb0 * 32, pre = early && (op || bq) ? min(nst, PS) : 0;
            auto weights = [&]() {
              acquire(8 + nb * 4);
              if (whole) {
                tma_load3z(dst + 8192, m, row, col >> 6, bar);
              } else {
                tma_load(dst + 8192, m, col, row, bar); tma_load(dst + 12288, m, col + 64, row, bar);
                if (nb == 3) tma_load(dst + 16384, m, col + 128, row, bar);
              }
              row += 32;
            };
            if (pre) {
              uint32_t da = dst, ba = bar;
#pragma unroll 1
              for (int kb = 0; kb < pre; kb++) { weights(); advance(); }
              depend(progress, item_need(type, b));
#pragma unroll 1
              for (int kb = 0; kb < pre; kb++) {
                bulk_load(da, a, 8192, ba);
                a += 2048; da += PB; ba += 8;
                if (da == bars) { da = sb; ba = bars; }
              }
            }
#pragma unroll 1
            for (int kb = pre; kb < nst; kb++) { weights(); if (op && OEF) bulk_load_last(dst, a, 8192, bar); else bulk_load(dst, a, 8192, bar); a += 2048; advance(); }
          }
          if (type == IT_ATT) {
            if (early) depend(progress, 96);
            if (go) mbar_arrive(bGo);
            const uint8_t* src = g_kv + (size_t)(idx * 6 * NSEG + b * 4) * KV_BYTES;
#pragma unroll 1
            for (int u = 0; u < 6; u++) {
              acquire(20);
              bulk_load_last(dst, src, 20480, bar);
              src += u == 2 ? -3 * KV_V : 2 * KV_V;
              advance();
            }
          }
        }
      }
    } else if (warp == 10 && lane == 0) {
      for (int n = 0;; n++) {
        mbar_wait(bIF + 8 * (n & 3), (n >> 2) & 1);
        const int code = (int)lds32(slots + 4 * (n & 3));
        if (code < 0) break;
        const int type = (code >> 16) & 15, b = (code >> 8) & 255;
        mbar_wait(done + 8 * (n & 3), (n >> 2) & 1);
        if (type != IT_BQ) red_release(type == IT_Q ? g_sync + SY_Q : g_sync + b * 8 + 5 + type, 1);
        mbar_arrive(bIE + 8 * (n & 3));
      }
    }
  } else {
    asm volatile("setmaxnreg.inc.sync.aligned.u32 224;");
    const int g = lane >> 2, c = lane & 3;
    Ring r = {sb, bars, 0, 0};
#pragma unroll 1
    for (int n = 0;; n++) {
      mbar_wait(bIF + 8 * (n & 3), (n >> 2) & 1);
      const int code = __shfl_sync(~0u, (int)lds32(slots + 4 * (n & 3)), 0);
      if (code < 0) { TRACE(2); break; }
      const int type = (code >> 16) & 15, b = (code >> 8) & 255, idx = code & 255;
      ITEM(code & 0xfffff, 0);
      if (type == IT_ATT || type == IT_Q) {
        uint32_t q[48];
        if (type == IT_Q || b < QA_END) {
          float d[96] = {};
          reg_fence<96>(d);
          gemm_item<192>(r, d, 20, bGo, type == IT_Q ? 12 : -1);
#pragma unroll
          for (int i = 0; i < 48; i++) q[i] = pack2(d[2 * i], d[2 * i + 1]);
        } else {
#pragma unroll
          for (int u = 0; u < 2; u++) {
            const uint32_t base = r.wait() + threadIdx.x * 16;
#pragma unroll
            for (int i = 0; i < 6; i++) {
              const uint4 v = lds128(base + i * 4096);
              q[24 * u + 4 * i] = v.x; q[24 * u + 4 * i + 1] = v.y; q[24 * u + 4 * i + 2] = v.z; q[24 * u + 4 * i + 3] = v.w;
            }
            r.pop();
          }
        }
        if (type == IT_Q) {
          uint4* dst = g_q + ((b - QA_END) * 32 + idx) * 3072 + threadIdx.x;
#pragma unroll
          for (int i = 0; i < 12; i++) dst[i * 256] = make_uint4(q[4 * i], q[4 * i + 1], q[4 * i + 2], q[4 * i + 3]);
        } else if (warp < 4) {
          attn_a_warp<0>(r, q, b, idx);
        } else {
          attn_a_warp<1>(r, q, b, idx);
        }
      } else if (type == IT_FIN) {
        if (fin_items(b) == 4) fin_item<4>(r, scratch, b, idx);
        else if (fin_items(b) == 8) fin_item<2>(r, scratch, b, idx);
        else fin_item<1>(r, scratch, b, idx);
      } else {
        float d[160] = {};
        reg_fence<160>(d);
        const int width = type == IT_OP ? op_width(b) : bq_width(b), nst = type == IT_OP ? 192 / op_split(b) : 20;
        const int go_at = code >> 21 & 1 ? -1 : max(nst - 6, 0);
        if (width == 320) gemm_item<320>(r, d, nst, bGo, go_at);
        else if (width == 160 || BQ_80 == 16) gemm_item<160>(r, d, nst, bGo, go_at);
        else gemm_item<80>(r, d, nst, bGo, go_at);
        reg_fence<160>(d);
        if (type == IT_OP) {
          const int tiles = DM / width;
          uint2* dst = g_part + (((b * 16 + idx / tiles) * 16 + warp * 2) * 40 + idx % tiles * (width / 16)) * 32 + lane;
#pragma unroll
          for (int u = 0; u < 20; u++) {
            if (u % 5 == 0 && u * 16 >= width) break;
            dst[u * 32] = make_uint2(pack2(d[8 * u], d[8 * u + 1]), pack2(d[8 * u + 4], d[8 * u + 5]));
            dst[(40 + u) * 32] = make_uint2(pack2(d[8 * u + 2], d[8 * u + 3]), pack2(d[8 * u + 6], d[8 * u + 7]));
          }
        } else {
          const int row = b * 128 + warp * 16 + g;
          const int h0 = idx * (width / 20);
          const float sc = h0 < 32 ? 0.22360679775f * 1.44269504089f : 1.f;
          const bool lo = c < 2;
          uint32_t* da = g_bqkv + (h0 * 256 + (row >> 3)) * 96 + lane;
          uint32_t* db = da + 256 * 96 + (lo ? 2 : -2);
          uint32_t pad[2];
#pragma unroll
          for (int rr = 0; rr < 2; rr++) pad[rr] = !(c & 1) && (h0 >= 64 || (h0 >= 32 && (row & 1) && poly_group((row >> 3) + rr))) ? 0x00003f80u : 0u;
#pragma unroll
          for (int q = 0; q < 8; q++) {
            if (!(q & 1) && q * 40 >= width) break;
#pragma unroll
            for (int rr = 0; rr < 2; rr++) {
              uint32_t w[5];
#pragma unroll
              for (int i = 0; i < 5; i++) w[i] = pack2(d[20 * q + 4 * i + 2 * rr] * sc, d[20 * q + 4 * i + 2 * rr + 1] * sc);
              const int o = q * 2 * 256 * 96 + rr * 96;
              da[o] = w[0]; da[o + 32] = w[1]; da[o + 64] = lo ? w[2] : pad[rr];
              db[o] = lo ? w[3] : w[2]; db[o + 32] = lo ? w[4] : w[3]; db[o + 64] = lo ? pad[rr] : w[4];
            }
          }
        }
      }
      __syncwarp();
      if (lane == 0) mbar_arrive(done + 8 * (n & 3));
      if ((code >> 21 & 1) && threadIdx.x == 128) mbar_arrive(bGo);
      ITEM(code & 0xfffff, 1);
    }
  }
}

constexpr int AB_SMEM = 1024 + 98304 + 51200 + 4 * 16384 + 256;
#define AB_N 32
#define AB_WG 4
constexpr int AB_T = AB_WG * 128, AB_PASS = 8 / AB_WG;
__device__ __forceinline__ float ex2_poly(float t) {
  const uint32_t r = __float_as_uint(t) & 0xffff8000u;
  const float f = t - __uint_as_float(r);
  const float p = fmaf(fmaf(fmaf(-5.869912678e-38f, f, -1.700740250e-37f), f, -5.234869734e-37f), f, -7.522601252e-37f);
  uint32_t y;
  asm("mad.lo.u32 %0, %1, 256, %2;" : "=r"(y) : "r"(r), "r"(__float_as_uint(p)));
  return __uint_as_float(y);
}
__device__ __forceinline__ float sq2(uint32_t w) { const float a = bf_lo(w), b = bf_hi(w); return fmaf(a, a, b * b); }

__device__ __forceinline__ void attn_b_store(const float* o, int h, int row0, int lane) {
  const int g = lane >> 2, c = lane & 3;
  const float i0 = 1.f / __shfl_sync(~0u, o[8], (lane & ~3) | 2), i1 = 1.f / __shfl_sync(~0u, o[10], (lane & ~3) | 2);
#pragma unroll
  for (int jj = 0; jj < 3; jj++) {
    if (jj < 2 || c < 2) {
      const int col = h * 20 + 8 * jj + 2 * c;
      uint32_t* dst = g_of + (((row0 >> 7) * 10 + (col >> 6)) * 16 + (row0 >> 3 & 15)) * 256 + (col >> 3 & 7) * 32 + g * 4 + (col >> 1 & 3);
      dst[0] = pack2(o[4 * jj] * i0, o[4 * jj + 1] * i0);
      dst[256] = pack2(o[4 * jj + 2] * i1, o[4 * jj + 3] * i1);
    }
  }
}

__device__ __forceinline__ void attn_b_qk(float* s, uint32_t q0, uint32_t q1, uint32_t q2, uint32_t q3, uint32_t q4, uint32_t q5, uint32_t z0, uint32_t z1,
                                          uint64_t dk, uint64_t dk2) {
  wg_rs32_00(s, q0, q1, q2, q3, dk, 0);
  wg_rs32_00(s, q4, q5, z0, z1, dk2, 1);
}

struct AbParams { Weights next; uint32_t* done; uint32_t* out; };
__global__ void __launch_bounds__(AB_T + 32, 1) attn_b_kernel(const __grid_constant__ AbParams p) {
  extern __shared__ uint8_t smem_raw[];
  const uint32_t sb = (s2u(smem_raw) + 1023) & ~1023u, sK = sb, sV = sb + 98304, bars = sV + 51200 + 4 * 16384;
  const uint32_t bF = bars + 64, bW = bars + 72, bA = bars + 80, bE = bars + 128, smax = bars + 176;
  auto ring = [&](int i) { return i < 2 ? sK + 51200 + i * 16384 : sV + 51200 + (i - 2) * 16384; };
  const int warp = __shfl_sync(~0u, threadIdx.x >> 5, 0), lane = threadIdx.x & 31;
  const int h = blockIdx.x >> 2, quarter = blockIdx.x & 3;
  TRACE(0);
  pdl_launch();
  pdl_wait();
  if (blockIdx.x < NSLOT) for (int i = threadIdx.x; i < 512; i += AB_T + 32) reinterpret_cast<uint4*>(pool_at(blockIdx.x * 8192))[i] = make_uint4(0, 0, 0, 0);
  if (blockIdx.x == 31) for (int i = threadIdx.x; i < SY_N; i += AB_T + 32) g_sync[i] = 0;
  if (threadIdx.x == 0) {
    for (int i = 0; i < 22; i++) mbar_init(bars + 8 * i, i == 8 ? AB_T / 32 : i >= 16 ? 8 : 1);
    sts64(smax, 0, 0);
    fence_async();
    const uint8_t* gk = reinterpret_cast<const uint8_t*>(g_bqkv + (32 + h) * 256 * 96);
    const uint8_t* gv = reinterpret_cast<const uint8_t*>(g_bqkv + (64 + h) * 256 * 96);
    for (int i = 0; i < 8; i++) {
      mbar_expect(bars + 8 * i, 24576);
      bulk_load_last(sK + i * 12288, gk + i * 12288, 12288, bars + 8 * i);
      bulk_load_last(sV + i * 12288, gv + i * 12288, 12288, bars + 8 * i);
    }
  }
  __syncthreads();
  const int blk = quarter * 4 + (h >> 3), cg = h & 7;
  auto unsafe = [&]() { const float2 m = lds64f(smax); return !(m.x * m.y <= 10000.f); };
  if (warp == AB_T / 32) {
    auto load_w = [&]() {
      mbar_expect(bW, 102400);
      for (int i = 0; i < 4; i++) bulk_load((i < 2 ? sK : sV) + (i & 1) * 25600, g_wb + cg * 6400 + i * 1600, 25600, bW);
    };
    if (p.next.w[0] && lane == 0) {
      mbar_wait(bars + 56, 0);
      for (int i = 0; i < AB_PF; i++) { const uint32_t t0 = clk32(); while (clk32() - t0 < (i ? AB_PFD : AB_PF0)) __nanosleep(200); prefetch_weights(p.next, i); }
    }
    __syncwarp();
    mbar_wait(bF, 0);
    const bool redo = unsafe();
    if (!redo && lane == 0) load_w();
    __syncwarp();
    bar_sync(1, AB_T + 32);
    if (lane == 0) {
      ABT(!!p.out, 1);
      red_release(p.done + quarter * 32, 1);
      ABT(!!p.out, 2);
      if (redo) load_w();
      wait_count(p.done + quarter * 32, 32);
      fence_async_global();
      ABT(!!p.out, 3);
      for (int kb = 0; kb < 10; kb++) {
        const int i = kb < 6 ? kb : kb - 6;
        if (kb >= 6) mbar_wait(bE + 8 * i, 0);
        mbar_expect(bA + 8 * i, 16384);
        bulk_load(ring(i), g_of + (blk * 10 + kb) * 4096, 16384, bA + 8 * i);
      }
    }
    return;
  }
  float qmax = 0.f;
  constexpr int NT = SEQ / AB_N, PER = 256 / AB_N;
#pragma unroll 1
  for (int pass = 0; pass < AB_PASS; pass++) {
    const int row0 = quarter * 512 + ((warp >> 2) * AB_PASS + pass) * 64 + (warp & 3) * 16;
    const uint32_t* gq = g_bqkv + (h * 256 + (row0 >> 3)) * 96 + lane;
    const uint32_t q0 = gq[0], q1 = gq[96], q2 = gq[32], q3 = gq[128];
    uint32_t q4 = gq[64], q5 = gq[160];
    const uint32_t z0 = gq[64 + 3 - (lane & 3)], z1 = gq[160 + 3 - (lane & 3)];
    {
      float n0 = sq2(q0) + sq2(q2) + sq2(q4), n1 = sq2(q1) + sq2(q3) + sq2(q5);
      n0 += __shfl_xor_sync(~0u, n0, 1); n1 += __shfl_xor_sync(~0u, n1, 1);
      n0 += __shfl_xor_sync(~0u, n0, 2); n1 += __shfl_xor_sync(~0u, n1, 2);
      qmax = (n0 > qmax || n0 != n0) ? n0 : qmax;
      qmax = (n1 > qmax || n1 != n1) ? n1 : qmax;
    }
    if (pass == AB_PASS - 1) {
      float kmax = 0.f;
#pragma unroll
      for (int i = 0; i < SEQ / AB_T; i++) {
        const int key = threadIdx.x + AB_T * i;
        const uint32_t a = sK + (key >> 3) * 384 + (key & 7) * 16;
        const uint4 x = lds128(a), y = lds128(a + 128);
        const uint2 z = lds64(a + 256);
        const float n = ((sq2(x.x) + sq2(x.y)) + (sq2(x.z) + sq2(x.w))) + ((sq2(y.x) + sq2(y.y)) + (sq2(y.z) + sq2(y.w))) + (sq2(z.x) + sq2(z.y));
        kmax = (n > kmax || n != n) ? n : kmax;
      }
      const uint32_t kb = __reduce_max_sync(~0u, __float_as_uint(kmax) & 0x7fffffffu), qb = __reduce_max_sync(~0u, __float_as_uint(qmax) & 0x7fffffffu);
      if (lane < 2) asm volatile("red.shared.max.u32 [%0], %1;" :: "r"(smax + 4 * lane), "r"(lane ? kb : qb) : "memory");
      __syncwarp();
    }
    if ((lane & 3) == 2) { q4 = 0x43BCu; q5 = 0x43BCu; }
    float o[12];
    uint64_t dk = mkdesc(sK, 128, 384, 0), dk2 = mkdesc(sK + 256, 0, 384, 0), dv = mkdesc(sV, 384, 128, 0);
    float sa[AB_N / 2], sb2[AB_N / 2];
    uint32_t pa[AB_N / 4], pb[AB_N / 4];
    if (pass == 0) mbar_wait(bars, 0);
    wg_fence();
    attn_b_qk(sa, q0, q1, q2, q3, q4, q5, z0, z1, dk, dk2);
    wg_commit();
    attn_b_qk(sb2, q0, q1, q2, q3, q4, q5, z0, z1, dk + AB_N * 3, dk2 + AB_N * 3);
    wg_commit();
#pragma unroll 1
    for (int kt = 0; kt < NT; kt += 2) {
      const int nx = kt + 2 < NT ? kt + 2 : 0;
      if (pass == 0 && (nx & (PER - 1)) == 0) mbar_wait(bars + 8 * (nx / PER), 0);
      const uint64_t nk = dk + nx * (AB_N * 3), nk2 = dk2 + nx * (AB_N * 3);
      wg_wait<1>();
      if (pass == AB_PASS - 1 && kt == NT * 5 / 8 + 2 && lane == 0) mbar_arrive(bF);
      reg_fence<AB_N / 2>(sa);
#pragma unroll
      for (int i = 0; i < AB_N / 4; i++) pa[i] = pack2(ex2(sa[2 * i]), poly_group(i >> 1) ? ex2_poly(sa[2 * i + 1]) : ex2(sa[2 * i + 1]));
      wg_fence();
#pragma unroll
      for (int kk = 0; kk < AB_N / 16; kk++) wg_rs24_01(o, pa[4 * kk], pa[4 * kk + 1], pa[4 * kk + 2], pa[4 * kk + 3], dv + kk * 48, kk | kt);
      attn_b_qk(sa, q0, q1, q2, q3, q4, q5, z0, z1, nk, nk2);
      wg_commit();
      wg_wait<1>();
      reg_fence<AB_N / 2>(sb2);
#pragma unroll
      for (int i = 0; i < AB_N / 4; i++) pb[i] = pack2(ex2(sb2[2 * i]), poly_group((i >> 1) + AB_N / 8) ? ex2_poly(sb2[2 * i + 1]) : ex2(sb2[2 * i + 1]));
      wg_fence();
#pragma unroll
      for (int kk = 0; kk < AB_N / 16; kk++) wg_rs24_01(o, pb[4 * kk], pb[4 * kk + 1], pb[4 * kk + 2], pb[4 * kk + 3], dv + AB_N * 3 + kk * 48, 1);
      attn_b_qk(sb2, q0, q1, q2, q3, q4, q5, z0, z1, nk + AB_N * 3, nk2 + AB_N * 3);
      wg_commit();
      dv += AB_N * 6;
    }
    wg_wait<0>();
    reg_fence<12>(o); reg_fence<AB_N / 2>(sa); reg_fence<AB_N / 2>(sb2);
    attn_b_store(o, h, row0, lane);
  }
  mbar_wait(bF, 0);
  if (unsafe())
#pragma unroll 1
  for (int pass = 0; pass < AB_PASS; pass++) {
    const int row0 = quarter * 512 + ((warp >> 2) * AB_PASS + pass) * 64 + (warp & 3) * 16;
    const uint32_t* gq = g_bqkv + (h * 256 + (row0 >> 3)) * 96 + lane;
    const uint32_t q0 = gq[0], q1 = gq[96], q2 = gq[32], q3 = gq[128], q4 = gq[64], q5 = gq[160];
    float o[12];
#pragma unroll
    for (int i = 0; i < 12; i++) o[i] = 0.f;
    float m0 = -INFINITY, m1 = -INFINITY;
#pragma unroll 1
    for (int kt = 0; kt < 32; kt++) {
      float s[32];
      const uint64_t dk = mkdesc(sK + kt * 3072, 128, 384, 0), dk2 = mkdesc(sK + kt * 3072 + 256, 0, 384, 0);
      wg_fence();
      wg_rs64_00(s, q0, q1, q2, q3, dk, 0);
      wg_rs64_00(s, q4, q5, 0, 0, dk2, 1);
      wg_commit();
      wg_wait<0>();
      reg_fence<32>(s); reg_fence<12>(o);
      float n0 = m0, n1 = m1;
#pragma unroll
      for (int jj = 0; jj < 8; jj++) { n0 = fmaxf(n0, fmaxf(s[4 * jj], s[4 * jj + 1])); n1 = fmaxf(n1, fmaxf(s[4 * jj + 2], s[4 * jj + 3])); }
      n0 = fmaxf(n0, __shfl_xor_sync(~0u, n0, 1)); n0 = fmaxf(n0, __shfl_xor_sync(~0u, n0, 2));
      n1 = fmaxf(n1, __shfl_xor_sync(~0u, n1, 1)); n1 = fmaxf(n1, __shfl_xor_sync(~0u, n1, 2));
      const float r0 = ex2(m0 - n0), r1 = ex2(m1 - n1);
      m0 = n0; m1 = n1;
#pragma unroll
      for (int jj = 0; jj < 3; jj++) { o[4 * jj] *= r0; o[4 * jj + 1] *= r0; o[4 * jj + 2] *= r1; o[4 * jj + 3] *= r1; }
      uint32_t pp[16];
#pragma unroll
      for (int jj = 0; jj < 8; jj++) {
        pp[2 * jj] = pack2(ex2(s[4 * jj] - m0), ex2(s[4 * jj + 1] - m0));
        pp[2 * jj + 1] = pack2(ex2(s[4 * jj + 2] - m1), ex2(s[4 * jj + 3] - m1));
      }
      const uint64_t dv = mkdesc(sV + kt * 3072, 384, 128, 0);
      wg_fence();
#pragma unroll
      for (int kk = 0; kk < 4; kk++) wg_rs24_01(o, pp[4 * kk], pp[4 * kk + 1], pp[4 * kk + 2], pp[4 * kk + 3], dv + kk * 48, 1);
      wg_commit();
    }
    wg_wait<0>();
    reg_fence<12>(o);
    attn_b_store(o, h, row0, lane);
  }
  ABT(!!p.out, 0);
  bar_arrive(1, AB_T + 32);
  if (warp >= 8) return;
  const int g = lane >> 2, c = lane & 3;
  float d[40];
  float4* x = g_x + ((blk * 16 + warp * 2) * 40 + cg * 5) * 32 + lane;
#pragma unroll
  for (int i = 0; i < 10; i++) {
    const int r = i / 5, u = i % 5;
    const float4 t = x[(r * 40 + u) * 32];
    d[8 * u + 2 * r] = t.x; d[8 * u + 2 * r + 1] = t.y; d[8 * u + 4 + 2 * r] = t.z; d[8 * u + 5 + 2 * r] = t.w;
  }
  mbar_wait(bW, 0);
  reg_fence<40>(d);
  ABT(!!p.out, 4);
#pragma unroll 1
  for (int kb = 0; kb < 10; kb++) {
    const int i = kb < 6 ? kb : kb - 6;
    mbar_wait(bA + 8 * i, kb >= 6);
    const uint64_t da = mkdesc(ring(i) + (warp >> 2) * 8192, 128, 1024, 0), db = mkdesc(kb < 5 ? sK + kb * 10240 : sV + (kb - 5) * 10240, 1280, 128, 0);
    wg_fence();
#pragma unroll
    for (int kk = 0; kk < 4; kk++) wg_ss80_01(d, da + kk * 16, db + kk * 160, 1);
    wg_commit();
    if (kb > 0 && kb < 5) { wg_wait<1>(); if (lane == 0) mbar_arrive(bE + 8 * (kb - 1)); }
  }
  wg_wait<0>();
  reg_fence<40>(d);
  ABT(!!p.out, 5);
  if (p.out) {
    uint32_t* out = p.out + (blk * 128 + warp * 16 + g) * (DM / 2) + cg * 40 + c;
#pragma unroll
    for (int i = 0; i < 20; i++) out[(i & 1) * 8 * (DM / 2) + (i >> 1) * 4] = pack2(d[2 * i], d[2 * i + 1]);
  } else {
    float2* stat = g_stat + blk * 1024 + warp * 16 + g;
    float mean[2], rs[2];
#pragma unroll
    for (int r = 0; r < 2; r++) {
      float t = 0.f, q = 0.f;
#pragma unroll
      for (int i = 0; i < 10; i++) t += d[4 * i + 2 * r] + d[4 * i + 2 * r + 1];
      t += __shfl_xor_sync(~0u, t, 1); t += __shfl_xor_sync(~0u, t, 2);
      t *= 1.f / 80;
#pragma unroll
      for (int i = 0; i < 10; i++) { const float a = d[4 * i + 2 * r] - t, b = d[4 * i + 2 * r + 1] - t; q += a * a + b * b; }
      q += __shfl_xor_sync(~0u, q, 1); q += __shfl_xor_sync(~0u, q, 2);
      if (c == r) asm volatile("st.relaxed.gpu.global.v2.b32 [%0], {%1, %2};" :: "l"(stat + cg * 128 + r * 8), "r"(__float_as_uint(t)), "r"(nz(__float_as_uint(q))) : "memory");
    }
#pragma unroll
    for (int i = 0; i < 10; i++) {
      const int r = i / 5, u = i % 5;
      x[(r * 40 + u) * 32] = make_float4(d[8 * u + 2 * r], d[8 * u + 2 * r + 1], d[8 * u + 4 + 2 * r], d[8 * u + 5 + 2 * r]);
    }
    ABT(0, 6);
    uint2 e[4];
    int n = 0;
    do {
#pragma unroll
      for (int i = 0; i < 4; i++)
        asm volatile("ld.relaxed.gpu.global.v2.b32 {%0, %1}, [%2];" : "=r"(e[i].x), "=r"(e[i].y) : "l"(stat + (2 * c + (i & 1)) * 128 + (i >> 1) * 8) : "memory");
      spin_guard(n);
    } while (__any_sync(~0u, min(min(e[0].y, e[1].y), min(e[2].y, e[3].y)) == 0));
#pragma unroll
    for (int r = 0; r < 2; r++) {
      const float m0 = __uint_as_float(e[2 * r].x), m1 = __uint_as_float(e[2 * r + 1].x);
      float t = m0 + m1;
      t += __shfl_xor_sync(~0u, t, 1); t += __shfl_xor_sync(~0u, t, 2);
      t *= 0.125f;
      float q = __uint_as_float(e[2 * r].y) + __uint_as_float(e[2 * r + 1].y) + 80.f * ((m0 - t) * (m0 - t) + (m1 - t) * (m1 - t));
      q += __shfl_xor_sync(~0u, q, 1); q += __shfl_xor_sync(~0u, q, 2);
      mean[r] = t; rs[r] = rsqrtf(q * (1.f / DM) + 1e-5f);
    }
    ABT(0, 7);
    uint32_t w[2][5][2];
#pragma unroll
    for (int i = 0; i < 20; i++) w[i & 1][i >> 2][i >> 1 & 1] = pack2((d[2 * i] - mean[i & 1]) * rs[i & 1], (d[2 * i + 1] - mean[i & 1]) * rs[i & 1]);
    ln_store(w, blk * 8 + warp, cg * 5);
  }
  ABT(!!p.out, 8);
  TRACE(2);
}

typedef CUresult (*EncodeFn)(CUtensorMap*, CUtensorMapDataType, cuuint32_t, void*, const cuuint64_t*, const cuuint64_t*,
                             const cuuint32_t*, const cuuint32_t*, CUtensorMapInterleave, CUtensorMapSwizzle,
                             CUtensorMapL2promotion, CUtensorMapFloatOOBfill);

void make_map(EncodeFn enc, CUtensorMap* m, const void* ptr, int cols, int rows, int nb) {
  const cuuint64_t dims[3] = {(cuuint64_t)(nb ? 64 : cols), (cuuint64_t)rows, (cuuint64_t)cols / 64};
  const cuuint64_t strides[2] = {(cuuint64_t)cols * 2, 128};
  const cuuint32_t box[3] = {64, 32, (cuuint32_t)nb}, es[3] = {1, 1, 1};
  enc(m, CU_TENSOR_MAP_DATA_TYPE_BFLOAT16, nb ? 3 : 2, const_cast<void*>(ptr), dims, strides, box, es, CU_TENSOR_MAP_INTERLEAVE_NONE,
      CU_TENSOR_MAP_SWIZZLE_128B, CU_TENSOR_MAP_L2_PROMOTION_L2_128B, CU_TENSOR_MAP_FLOAT_OOB_FILL_NONE);
}
template <class... KA, class... A>
void launch(void (*kern)(KA...), int grid, int block, int smem, int cluster, bool pdl, A... args) {
  cudaFuncSetAttribute(kern, cudaFuncAttributeMaxDynamicSharedMemorySize, smem);
  cudaLaunchConfig_t cfg = {};
  cfg.gridDim = dim3(grid); cfg.blockDim = dim3(block); cfg.dynamicSmemBytes = smem; cfg.stream = cudaStreamPerThread;
  cudaLaunchAttribute at[2];
  int n = 0;
  if (cluster > 1) { at[n].id = cudaLaunchAttributeClusterDimension; at[n].val.clusterDim.x = cluster; at[n].val.clusterDim.y = 1; at[n].val.clusterDim.z = 1; n++; }
  if (pdl) { at[n].id = cudaLaunchAttributeProgrammaticStreamSerialization; at[n].val.programmaticStreamSerializationAllowed = 1; n++; }
  cfg.attrs = at; cfg.numAttrs = n;
  cudaLaunchKernelEx(&cfg, kern, args...);
}
template <class T> void* sym(T& s) { void* p = nullptr; cudaGetSymbolAddress(&p, s); return p; }

}

#define MODE(b) 0
extern "C" void kernel_launch(void* const* d_in, const int* in_sizes, int n_in, void* d_out, int out_size) {
  const __nv_bfloat16* x = (const __nv_bfloat16*)d_in[0];
  void* fn = nullptr; cudaDriverEntryPointQueryResult qr;
  cudaGetDriverEntryPoint("cuTensorMapEncodeTiled", &fn, cudaEnableDefault, &qr);
  EncodeFn enc = (EncodeFn)fn;

  ChainParams ch = {};
  PostParams op = {};
  for (int i = 0; i < 3; i++) {
    const cuuint64_t dims[3] = {HD, 128, 5}, strides[2] = {HD * 2, HD * 256};
    const cuuint32_t box[3] = {64, 128, 5}, es[3] = {1, 1, 1};
    enc(i == 0 ? &ch.wq : i == 1 ? &ch.wk : &ch.wv, CU_TENSOR_MAP_DATA_TYPE_BFLOAT16, 3, d_in[2 + i], dims, strides, box, es, CU_TENSOR_MAP_INTERLEAVE_NONE,
        CU_TENSOR_MAP_SWIZZLE_128B, W_PROMO, CU_TENSOR_MAP_FLOAT_OOB_FILL_NONE);
  }
  {
    const cuuint64_t dims[3] = {DM, HD, 7}, strides[2] = {DM * 2, 64};
    const cuuint32_t box[3] = {32, 64, 7}, es[3] = {1, 1, 1};
    enc(&ch.wo, CU_TENSOR_MAP_DATA_TYPE_BFLOAT16, 3, d_in[5], dims, strides, box, es, CU_TENSOR_MAP_INTERLEAVE_NONE,
        CU_TENSOR_MAP_SWIZZLE_64B, CU_TENSOR_MAP_L2_PROMOTION_L2_128B, CU_TENSOR_MAP_FLOAT_OOB_FILL_NONE);
  }
  ch.mem0 = (const __nv_bfloat16*)d_in[1];
  ch.pool = (uint8_t*)(((uintptr_t)sym(g_pool) + 8191) & ~(uintptr_t)8191); ch.kv = (uint8_t*)sym(g_kv); ch.xc = (const uint32_t*)sym(g_xc); ch.sync = (uint32_t*)sym(g_sync);
  ch.d1 = 0; ch.d1b = 0; ch.d2 = 0; ch.d2b = 0;
  make_map(enc, &op.wq, d_in[2], HD, DM, 3);
  make_map(enc, &op.wo, d_in[5], DM, HD, 5); make_map(enc, &op.wo2, d_in[5], DM, HD, 0);
  make_map(enc, &op.wb, d_in[8], 1920, DM, 5); make_map(enc, &op.wb2, d_in[8], 1920, DM, 0);
  op.gap = 17; op.share = 20; op.look = 14; op.gap2 = 0; op.pol = 0;

  const Weights wa = {{(const uint8_t*)d_in[3], (const uint8_t*)d_in[4], (const uint8_t*)d_in[2], (const uint8_t*)d_in[5]}}, none = {};
  launch(first_kernel, 132, 256, 128 * 1024, 1, false, x, (const uint4*)d_in[9], wa);
  for (int layer = 0; layer < 2; layer++) {
    ch.layer = ch.d2b = op.layer = layer;
    launch(chain_kernel, 96, 256, CH_SMEM, 3, true, ch);
    launch(post_kernel, MODE(3) ? 36 : 132, 384, OP_SMEM, 1, !MODE(1), op);
    const AbParams ab = {layer == 0 ? wa : none, (uint32_t*)sym(g_bo) + layer * 128, layer == 0 ? nullptr : (uint32_t*)d_out};
    launch(attn_b_kernel, 128, AB_T + 32, AB_SMEM, 1, true, ab);
  }
}
```

```cpp
#include <cuda_runtime.h>
#include <cuda_bf16.h>
#include <cuda.h>
#include <stdint.h>

namespace {

constexpr int SEQ = 2048, DM = 640, HD = 6144, NSEG = 64;
constexpr int SPIN_LIMIT = 1 << 20;

__device__ __align__(128) float4 g_x[SEQ * DM / 4];
__device__ __align__(128) uint32_t g_of[SEQ * DM / 2];
__device__ __align__(128) uint4 g_wb[DM * DM / 8];
__device__ __align__(16) float2 g_stat[16 * 8 * 128];
__device__ uint32_t g_bo[8 * 32];
__device__ __align__(128) uint4 g_q[SEQ * HD / 8];
__device__ __align__(128) uint32_t g_o[SEQ * HD / 2];
constexpr int KV_BYTES = 5120, KV_M = 4096, KV_V = NSEG * KV_BYTES;
__device__ __align__(128) uint8_t g_kv[96 * 2 * NSEG * KV_BYTES];
__device__ __align__(128) uint32_t g_xc[SEQ * DM / 2];
#define OP_B4 0
#define OP_B8 10
#define OP_B16 15
#define QA_END 12
__host__ __device__ constexpr int op_split(int b) { return b < OP_B4 ? 2 : b < OP_B8 ? 4 : b < OP_B16 ? 8 : 16; }
__host__ __device__ constexpr int fin_items(int b) { return b < OP_B8 ? 4 : op_split(b); }
#define AB_PF 2
#define AB_PF0 10000
#define AB_PFD 8000
#define W_PROMO CU_TENSOR_MAP_L2_PROMOTION_L2_128B
#define OEF 0
#define BQ_HOLD 12
#define WEF 1
#define FK_PF 1
#define BQ_160 10
#define BQ_80 16
#define OP_160 16
__host__ __device__ constexpr int op_width(int b) { return b < OP_160 ? 320 : 160; }
__host__ __device__ constexpr int bq_width(int b) { return b < BQ_160 ? 320 : b < BQ_80 ? 160 : 80; }
__device__ __align__(128) uint2 g_part[16 * 16 * 16 * 40 * 32];
__device__ __align__(128) uint32_t g_xn[SEQ * DM / 2];
constexpr int SY_Q = 128, SY_T = 160, SY_QC = 192, SY_N = 193;
__device__ __align__(16) uint32_t g_sync[SY_N];
constexpr int NSLOT = 92;
__device__ uint32_t g_pool[(NSLOT + 2) * 2048];
__device__ int g_smpart[256], g_orient[NSLOT];
__device__ uint32_t g_smclk[256], g_smuse[256];
__device__ uint32_t g_bqkv[3 * 32 * 256 * 96];

#define ABT(L, i)
#define MODE_D(b) 0
#define DELAY(d)
#define XT(i)
#define MISS(k, n)
#define PRO(i)
#define TRACE(w)
#define ITEM(code, w)
#define TR(i, v)
#define TM(i)
#define TM1(i)
#define TMD(i, dep)
#define TMV(i, at, v)

__device__ __forceinline__ uint32_t gtime() { uint32_t c; asm volatile("mov.u32 %0, %%globaltimer_lo;" : "=r"(c) :: "memory"); return c; }
__device__ __forceinline__ uint32_t clk32() { uint32_t c; asm volatile("mov.u32 %0, %%clock;" : "=r"(c) :: "memory"); return c; }
__device__ __forceinline__ uint32_t s2u(const void* p) { return (uint32_t)__cvta_generic_to_shared(p); }
__device__ __forceinline__ uint32_t pack2(float a, float b) {
  uint32_t r; asm("cvt.rn.bf16x2.f32 %0, %1, %2;" : "=r"(r) : "f"(b), "f"(a)); return r; }
__device__ __forceinline__ float bf_lo(uint32_t w) { return __uint_as_float(w << 16); }
__device__ __forceinline__ float bf_hi(uint32_t w) { return __uint_as_float(w & 0xffff0000u); }
__device__ __forceinline__ float ex2(float x) { float y; asm("ex2.approx.ftz.f32 %0, %1;" : "=f"(y) : "f"(x)); return y; }

__device__ __forceinline__ void mbar_init(uint32_t bar, uint32_t n) {
  asm volatile("mbarrier.init.shared::cta.b64 [%0], %1;" :: "r"(bar), "r"(n) : "memory"); }
__device__ __forceinline__ void mbar_expect(uint32_t bar, uint32_t bytes) {
  asm volatile("mbarrier.arrive.expect_tx.shared::cta.b64 _, [%0], %1;" :: "r"(bar), "r"(bytes) : "memory"); }
__device__ __forceinline__ void mbar_arrive(uint32_t bar) {
  asm volatile("mbarrier.arrive.shared::cta.b64 _, [%0];" :: "r"(bar) : "memory"); }
__device__ __forceinline__ void mbar_wait(uint32_t bar, uint32_t ph) {
  asm volatile("{.reg .pred p; .reg .u32 n; mov.u32 n, 0;\n"
               "W: mbarrier.try_wait.parity.shared::cta.b64 p, [%0], %1; @p bra D;\n"
               "add.u32 n, n, 1; setp.gt.u32 p, n, %2; @p trap; bra W;\n"
               "D: }" :: "r"(bar), "r"(ph), "n"(SPIN_LIMIT) : "memory");
}
__device__ __forceinline__ void mbar_wait_cluster(uint32_t bar, uint32_t ph) {
  asm volatile("{.reg .pred p; .reg .u32 n; mov.u32 n, 0;\n"
               "W: mbarrier.try_wait.parity.acquire.cluster.shared::cta.b64 p, [%0], %1; @p bra D;\n"
               "add.u32 n, n, 1; setp.gt.u32 p, n, %2; @p trap; bra W;\n"
               "D: }" :: "r"(bar), "r"(ph), "n"(SPIN_LIMIT) : "memory");
}
__device__ __forceinline__ void spin_guard(int& n) {
  asm volatile("{.reg .pred p; add.s32 %0, %0, 1; setp.gt.s32 p, %0, %1; @p trap;}" : "+r"(n) : "n"(SPIN_LIMIT));
}
__device__ __forceinline__ void pdl_wait() { asm volatile("griddepcontrol.wait;" ::: "memory"); TRACE(1); }
__device__ __forceinline__ void pdl_launch() { asm volatile("griddepcontrol.launch_dependents;" ::: "memory"); }
__device__ __forceinline__ uint32_t ld_acquire(const uint32_t* p) { uint32_t v; asm volatile("ld.acquire.gpu.global.u32 %0, [%1];" : "=r"(v) : "l"(p) : "memory"); return v; }
__device__ __forceinline__ void red_release(uint32_t* p, uint32_t v) { asm volatile("red.release.gpu.global.add.u32 [%0], %1;" :: "l"(p), "r"(v) : "memory"); }
__device__ __forceinline__ void red_relaxed(uint32_t* p, uint32_t v) { asm volatile("red.relaxed.gpu.global.add.u32 [%0], %1;" :: "l"(p), "r"(v) : "memory"); }
__device__ __forceinline__ void fence_async_global() { asm volatile("fence.proxy.async.global;" ::: "memory"); }
__device__ __forceinline__ void fence_async() { asm volatile("fence.proxy.async.shared::cta;" ::: "memory"); }
__device__ __forceinline__ void bar_sync(int id, int n) { asm volatile("bar.sync %0, %1;" :: "r"(id), "r"(n) : "memory"); }
__device__ __forceinline__ void bar_arrive(int id, int n) { asm volatile("bar.arrive %0, %1;" :: "r"(id), "r"(n) : "memory"); }
__device__ __forceinline__ void tma_load(uint32_t dst, const CUtensorMap* m, int c0, int c1, uint32_t bar) {
  asm volatile("cp.async.bulk.tensor.2d.shared::cluster.global.mbarrier::complete_tx::bytes [%0], [%1, {%3, %4}], [%2];"
               :: "r"(dst), "l"(m), "r"(bar), "r"(c0), "r"(c1) : "memory"); }
template <bool STREAM = false>
__device__ __forceinline__ void tma_load3(uint32_t dst, const CUtensorMap* m, int c0, int c1, uint32_t bar) {
  if (STREAM)
    asm volatile("{.reg .b64 pol; createpolicy.fractional.L2::evict_first.b64 pol, 1.0;\n"
                 "cp.async.bulk.tensor.3d.shared::cluster.global.mbarrier::complete_tx::bytes.L2::cache_hint [%0], [%1, {%3, %4, 0}], [%2], pol;}"
                 :: "r"(dst), "l"(m), "r"(bar), "r"(c0), "r"(c1) : "memory");
  else
  asm volatile("cp.async.bulk.tensor.3d.shared::cluster.global.mbarrier::complete_tx::bytes [%0], [%1, {%3, %4, 0}], [%2];"
               :: "r"(dst), "l"(m), "r"(bar), "r"(c0), "r"(c1) : "memory"); }
__device__ __forceinline__ void tma_load3z(uint32_t dst, const CUtensorMap* m, int c1, int c2, uint32_t bar) {
  asm volatile("cp.async.bulk.tensor.3d.shared::cluster.global.mbarrier::complete_tx::bytes [%0], [%1, {0, %3, %4}], [%2];"
               :: "r"(dst), "l"(m), "r"(bar), "r"(c1), "r"(c2) : "memory"); }
__device__ __forceinline__ void tma_store(const CUtensorMap* m, uint32_t src, int c0, int c1) {
  asm volatile("cp.async.bulk.tensor.2d.global.shared::cta.bulk_group [%0, {%2, %3}], [%1];"
               :: "l"(m), "r"(src), "r"(c0), "r"(c1) : "memory"); }
__device__ __forceinline__ void tma_store_stream(const CUtensorMap* m, uint32_t src, int c0, int c1) {
  asm volatile("{.reg .b64 pol; createpolicy.fractional.L2::evict_first.b64 pol, 1.0;\n"
               "cp.async.bulk.tensor.2d.global.shared::cta.bulk_group.L2::cache_hint [%0, {%2, %3}], [%1], pol;}"
               :: "l"(m), "r"(src), "r"(c0), "r"(c1) : "memory"); }
__device__ __forceinline__ void bulk_load(uint32_t dst, const void* src, uint32_t bytes, uint32_t bar) {
  asm volatile("cp.async.bulk.shared::cluster.global.mbarrier::complete_tx::bytes [%0], [%1], %2, [%3];"
               :: "r"(dst), "l"(src), "r"(bytes), "r"(bar) : "memory"); }
__device__ __forceinline__ void bulk_load_last(uint32_t dst, const void* src, uint32_t bytes, uint32_t bar) {
  asm volatile("{.reg .b64 pol; createpolicy.fractional.L2::evict_first.b64 pol, 1.0;\n"
               "cp.async.bulk.shared::cluster.global.mbarrier::complete_tx::bytes.L2::cache_hint [%0], [%1], %2, [%3], pol;}"
               :: "r"(dst), "l"(src), "r"(bytes), "r"(bar) : "memory"); }
__device__ __forceinline__ void tma_load_last(uint32_t dst, const CUtensorMap* m, int c0, int c1, uint32_t bar) {
  asm volatile("{.reg .b64 pol; createpolicy.fractional.L2::evict_first.b64 pol, 1.0;\n"
               "cp.async.bulk.tensor.2d.shared::cluster.global.mbarrier::complete_tx::bytes.L2::cache_hint [%0], [%1, {%3, %4}], [%2], pol;}"
               :: "r"(dst), "l"(m), "r"(bar), "r"(c0), "r"(c1) : "memory"); }
__device__ __forceinline__ void bulk_send(uint32_t dst, uint32_t src, uint32_t bytes, uint32_t bar) {
  asm volatile("cp.async.bulk.shared::cluster.shared::cta.mbarrier::complete_tx::bytes [%0], [%1], %2, [%3];"
               :: "r"(dst), "r"(src), "r"(bytes), "r"(bar) : "memory"); }
__device__ __forceinline__ void bulk_store(void* dst, uint32_t src, uint32_t bytes) {
  asm volatile("cp.async.bulk.global.shared::cta.bulk_group [%0], [%1], %2;" :: "l"(dst), "r"(src), "r"(bytes) : "memory"); }
__device__ __forceinline__ void bulk_commit() { asm volatile("cp.async.bulk.commit_group;" ::: "memory"); }
template <int N> __device__ __forceinline__ void bulk_wait_read() { asm volatile("cp.async.bulk.wait_group.read %0;" :: "n"(N) : "memory"); }
template <int N> __device__ __forceinline__ void bulk_wait() { asm volatile("cp.async.bulk.wait_group %0;" :: "n"(N) : "memory"); }

__device__ __forceinline__ uint64_t mkdesc(uint32_t addr, uint32_t lbo, uint32_t sbo, uint32_t sw) {
  return (uint64_t)((addr & 0x3FFFF) >> 4) | ((uint64_t)(lbo >> 4) << 16) | ((uint64_t)(sbo >> 4) << 32) | ((uint64_t)sw << 62); }
__device__ __forceinline__ void wg_fence() { asm volatile("wgmma.fence.sync.aligned;" ::: "memory"); }
__device__ __forceinline__ void wg_commit() { asm volatile("wgmma.commit_group.sync.aligned;" ::: "memory"); }
template <int N> __device__ __forceinline__ void wg_wait() { asm volatile("wgmma.wait_group.sync.aligned %0;" :: "n"(N) : "memory"); }
template <int N> __device__ __forceinline__ void reg_fence(float* d) {
#pragma unroll
  for (int i = 0; i < N; i++) asm volatile("" : "+f"(d[i]) :: "memory");
}

__device__ __forceinline__ void mma16(float* d, uint32_t a0, uint32_t a1, uint32_t a2, uint32_t a3, uint32_t b0, uint32_t b1) {
  asm volatile("mma.sync.aligned.m16n8k16.row.col.f32.bf16.bf16.f32 {%0,%1,%2,%3},{%4,%5,%6,%7},{%8,%9},{%0,%1,%2,%3};"
               : "+f"(d[0]), "+f"(d[1]), "+f"(d[2]), "+f"(d[3]) : "r"(a0), "r"(a1), "r"(a2), "r"(a3), "r"(b0), "r"(b1)); }
__device__ __forceinline__ void mma8(float* d, uint32_t a0, uint32_t a1, uint32_t b0) {
  asm volatile("mma.sync.aligned.m16n8k8.row.col.f32.bf16.bf16.f32 {%0,%1,%2,%3},{%4,%5},{%6},{%0,%1,%2,%3};"
               : "+f"(d[0]), "+f"(d[1]), "+f"(d[2]), "+f"(d[3]) : "r"(a0), "r"(a1), "r"(b0)); }
__device__ __forceinline__ void ldsm4(uint32_t* r, uint32_t a) {
  asm volatile("ldmatrix.sync.aligned.m8n8.x4.shared.b16 {%0,%1,%2,%3},[%4];" : "=r"(r[0]), "=r"(r[1]), "=r"(r[2]), "=r"(r[3]) : "r"(a) : "memory"); }
__device__ __forceinline__ void ldsm4t(uint32_t* r, uint32_t a) {
  asm volatile("ldmatrix.sync.aligned.m8n8.x4.trans.shared.b16 {%0,%1,%2,%3},[%4];" : "=r"(r[0]), "=r"(r[1]), "=r"(r[2]), "=r"(r[3]) : "r"(a) : "memory"); }
__device__ __forceinline__ void ldsm2(uint32_t* r, uint32_t a) {
  asm volatile("ldmatrix.sync.aligned.m8n8.x2.shared.b16 {%0,%1},[%2];" : "=r"(r[0]), "=r"(r[1]) : "r"(a) : "memory"); }
__device__ __forceinline__ void stsm4(uint32_t a, uint32_t r0, uint32_t r1, uint32_t r2, uint32_t r3) {
  asm volatile("stmatrix.sync.aligned.m8n8.x4.shared.b16 [%0], {%1,%2,%3,%4};" :: "r"(a), "r"(r0), "r"(r1), "r"(r2), "r"(r3) : "memory"); }
__device__ __forceinline__ void stsm2t(uint32_t a, uint32_t r0, uint32_t r1) {
  asm volatile("stmatrix.sync.aligned.m8n8.x2.trans.shared.b16 [%0], {%1,%2};" :: "r"(a), "r"(r0), "r"(r1) : "memory"); }
__device__ __forceinline__ void stsm4t(uint32_t a, uint32_t r0, uint32_t r1, uint32_t r2, uint32_t r3) {
  asm volatile("stmatrix.sync.aligned.m8n8.x4.trans.shared.b16 [%0], {%1,%2,%3,%4};" :: "r"(a), "r"(r0), "r"(r1), "r"(r2), "r"(r3) : "memory"); }
__device__ __forceinline__ void st_async128(uint32_t a, uint4 v, uint32_t bar) {
  asm volatile("st.async.shared::cluster.mbarrier::complete_tx::bytes.v4.b32 [%0], {%1,%2,%3,%4}, [%5];" :: "r"(a), "r"(v.x), "r"(v.y), "r"(v.z), "r"(v.w), "r"(bar) : "memory"); }
__device__ __forceinline__ void sts32(uint32_t a, uint32_t v) { asm volatile("st.shared.b32 [%0], %1;" :: "r"(a), "r"(v) : "memory"); }
__device__ __forceinline__ void sts64f(uint32_t a, float x, float y) { asm volatile("st.shared.v2.f32 [%0], {%1,%2};" :: "r"(a), "f"(x), "f"(y) : "memory"); }
__device__ __forceinline__ void sts128(uint32_t a, uint4 v) {
  asm volatile("st.shared.v4.b32 [%0], {%1,%2,%3,%4};" :: "r"(a), "r"(v.x), "r"(v.y), "r"(v.z), "r"(v.w) : "memory"); }
__device__ __forceinline__ void sts128f(uint32_t a, float x, float y, float z, float w) {
  asm volatile("st.shared.v4.f32 [%0], {%1,%2,%3,%4};" :: "r"(a), "f"(x), "f"(y), "f"(z), "f"(w) : "memory"); }
__device__ __forceinline__ float lds32f(uint32_t a) { float v; asm volatile("ld.shared.f32 %0, [%1];" : "=f"(v) : "r"(a) : "memory"); return v; }
__device__ __forceinline__ float2 lds64f(uint32_t a) { float2 v; asm volatile("ld.shared.v2.f32 {%0,%1}, [%2];" : "=f"(v.x), "=f"(v.y) : "r"(a) : "memory"); return v; }
__device__ __forceinline__ float4 lds128f(uint32_t a) {
  float4 v; asm volatile("ld.shared.v4.f32 {%0,%1,%2,%3}, [%4];" : "=f"(v.x), "=f"(v.y), "=f"(v.z), "=f"(v.w) : "r"(a) : "memory"); return v; }
__device__ __forceinline__ uint4 lds128(uint32_t a) {
  uint4 v; asm volatile("ld.shared.v4.b32 {%0,%1,%2,%3}, [%4];" : "=r"(v.x), "=r"(v.y), "=r"(v.z), "=r"(v.w) : "r"(a) : "memory"); return v; }
__device__ __forceinline__ uint4 ldg_strong128(const void* p) {
  uint4 v; asm volatile("ld.relaxed.gpu.global.v4.u32 {%0,%1,%2,%3}, [%4];" : "=r"(v.x), "=r"(v.y), "=r"(v.z), "=r"(v.w) : "l"(p) : "memory"); return v; }
__device__ __forceinline__ void stg_strong32(void* p, uint32_t v) { asm volatile("st.relaxed.gpu.global.u32 [%0], %1;" :: "l"(p), "r"(v) : "memory"); }
__device__ __forceinline__ void stg_strong16(void* p, uint32_t v) { asm volatile("st.relaxed.gpu.global.u16 [%0], %1;" :: "l"(p), "h"((uint16_t)v) : "memory"); }
__device__ __forceinline__ void stg_strong128(void* p, uint4 v) {
  asm volatile("st.relaxed.gpu.global.v4.u32 [%0], {%1,%2,%3,%4};" :: "l"(p), "r"(v.x), "r"(v.y), "r"(v.z), "r"(v.w) : "memory"); }
__device__ __forceinline__ uint32_t mapa(uint32_t a, uint32_t r) {
  uint32_t o; asm("mapa.shared::cluster.u32 %0, %1, %2;" : "=r"(o) : "r"(a), "r"(r)); return o; }
__device__ __forceinline__ void st_async2f(uint32_t a, float x, float y, uint32_t bar) {
  asm volatile("st.async.shared::cluster.mbarrier::complete_tx::bytes.v2.f32 [%0], {%1,%2}, [%3];" :: "r"(a), "f"(x), "f"(y), "r"(bar) : "memory"); }
__device__ __forceinline__ void st_async32(uint32_t a, uint32_t x, uint32_t bar) {
  asm volatile("st.async.shared::cluster.mbarrier::complete_tx::bytes.b32 [%0], %1, [%2];" :: "r"(a), "r"(x), "r"(bar) : "memory"); }
__device__ __forceinline__ uint32_t lds32(uint32_t a) { uint32_t v; asm volatile("ld.shared.b32 %0, [%1];" : "=r"(v) : "r"(a) : "memory"); return v; }
__device__ __forceinline__ void st_async64(uint32_t a, uint32_t x, uint32_t y, uint32_t bar) {
  asm volatile("st.async.shared::cluster.mbarrier::complete_tx::bytes.v2.b32 [%0], {%1,%2}, [%3];" :: "r"(a), "r"(x), "r"(y), "r"(bar) : "memory"); }
__device__ __forceinline__ uint2 lds64(uint32_t a) { uint2 v; asm volatile("ld.shared.v2.b32 {%0,%1}, [%2];" : "=r"(v.x), "=r"(v.y) : "r"(a) : "memory"); return v; }
__device__ __forceinline__ void sts64(uint32_t a, uint32_t x, uint32_t y) { asm volatile("st.shared.v2.b32 [%0], {%1,%2};" :: "r"(a), "r"(x), "r"(y) : "memory"); }
__device__ __forceinline__ uint32_t ldg_strong32(const void* p) { uint32_t v; asm volatile("ld.relaxed.gpu.global.u32 %0, [%1];" : "=r"(v) : "l"(p) : "memory"); return v; }
__device__ __forceinline__ uint32_t transpose8(uint32_t x) { uint32_t r; asm volatile("movmatrix.sync.aligned.m8n8.trans.b16 %0, %1;" : "=r"(r) : "r"(x)); return r; }
__device__ __forceinline__ uint32_t hadd2(uint32_t a, uint32_t b) { uint32_t r; asm("add.rn.bf16x2 %0, %1, %2;" : "=r"(r) : "r"(a), "r"(b)); return r; }
__device__ __forceinline__ uint32_t min4(uint4 v) { return min(__vimin3_u32(v.x, v.y, v.z), v.w); }

__device__ __forceinline__ void wg_ss192_01(float* d, uint64_t da, uint64_t db, int sd) {
  asm volatile("{.reg .pred p; setp.ne.b32 p, %98, 0;\n"
    "wgmma.mma_async.sync.aligned.m64n192k16.f32.bf16.bf16 {%0,%1,%2,%3,%4,%5,%6,%7,%8,%9,%10,%11,%12,%13,%14,%15,%16,%17,%18,%19,%20,%21,%22,%23,%24,%25,%26,%27,%28,%29,%30,%31,%32,%33,%34,%35,%36,%37,%38,%39,%40,%41,%42,%43,%44,%45,%46,%47,%48,%49,%50,%51,%52,%53,%54,%55,%56,%57,%58,%59,%60,%61,%62,%63,%64,%65,%66,%67,%68,%69,%70,%71,%72,%73,%74,%75,%76,%77,%78,%79,%80,%81,%82,%83,%84,%85,%86,%87,%88,%89,%90,%91,%92,%93,%94,%95}, %96, %97, p, 1, 1, 0, 1;}"
    : "+f"(d[0]),"+f"(d[1]),"+f"(d[2]),"+f"(d[3]),"+f"(d[4]),"+f"(d[5]),"+f"(d[6]),"+f"(d[7]),"+f"(d[8]),"+f"(d[9]),"+f"(d[10]),"+f"(d[11]),"+f"(d[12]),"+f"(d[13]),"+f"(d[14]),"+f"(d[15]),"+f"(d[16]),"+f"(d[17]),"+f"(d[18]),"+f"(d[19]),"+f"(d[20]),"+f"(d[21]),"+f"(d[22]),"+f"(d[23]),"+f"(d[24]),"+f"(d[25]),"+f"(d[26]),"+f"(d[27]),"+f"(d[28]),"+f"(d[29]),"+f"(d[30]),"+f"(d[31]),"+f"(d[32]),"+f"(d[33]),"+f"(d[34]),"+f"(d[35]),"+f"(d[36]),"+f"(d[37]),"+f"(d[38]),"+f"(d[39]),"+f"(d[40]),"+f"(d[41]),"+f"(d[42]),"+f"(d[43]),"+f"(d[44]),"+f"(d[45]),"+f"(d[46]),"+f"(d[47]),"+f"(d[48]),"+f"(d[49]),"+f"(d[50]),"+f"(d[51]),"+f"(d[52]),"+f"(d[53]),"+f"(d[54]),"+f"(d[55]),"+f"(d[56]),"+f"(d[57]),"+f"(d[58]),"+f"(d[59]),"+f"(d[60]),"+f"(d[61]),"+f"(d[62]),"+f"(d[63]),"+f"(d[64]),"+f"(d[65]),"+f"(d[66]),"+f"(d[67]),"+f"(d[68]),"+f"(d[69]),"+f"(d[70]),"+f"(d[71]),"+f"(d[72]),"+f"(d[73]),"+f"(d[74]),"+f"(d[75]),"+f"(d[76]),"+f"(d[77]),"+f"(d[78]),"+f"(d[79]),"+f"(d[80]),"+f"(d[81]),"+f"(d[82]),"+f"(d[83]),"+f"(d[84]),"+f"(d[85]),"+f"(d[86]),"+f"(d[87]),"+f"(d[88]),"+f"(d[89]),"+f"(d[90]),"+f"(d[91]),"+f"(d[92]),"+f"(d[93]),"+f"(d[94]),"+f"(d[95])
    : "l"(da), "l"(db), "r"(sd));
}
__device__ __forceinline__ void wg_ss128_01(float* d, uint64_t da, uint64_t db, int sd) {
  asm volatile("{.reg .pred p; setp.ne.b32 p, %66, 0;\n"
    "wgmma.mma_async.sync.aligned.m64n128k16.f32.bf16.bf16 {%0,%1,%2,%3,%4,%5,%6,%7,%8,%9,%10,%11,%12,%13,%14,%15,%16,%17,%18,%19,%20,%21,%22,%23,%24,%25,%26,%27,%28,%29,%30,%31,%32,%33,%34,%35,%36,%37,%38,%39,%40,%41,%42,%43,%44,%45,%46,%47,%48,%49,%50,%51,%52,%53,%54,%55,%56,%57,%58,%59,%60,%61,%62,%63}, %64, %65, p, 1, 1, 0, 1;}"
    : "+f"(d[0]),"+f"(d[1]),"+f"(d[2]),"+f"(d[3]),"+f"(d[4]),"+f"(d[5]),"+f"(d[6]),"+f"(d[7]),"+f"(d[8]),"+f"(d[9]),"+f"(d[10]),"+f"(d[11]),"+f"(d[12]),"+f"(d[13]),"+f"(d[14]),"+f"(d[15]),"+f"(d[16]),"+f"(d[17]),"+f"(d[18]),"+f"(d[19]),"+f"(d[20]),"+f"(d[21]),"+f"(d[22]),"+f"(d[23]),"+f"(d[24]),"+f"(d[25]),"+f"(d[26]),"+f"(d[27]),"+f"(d[28]),"+f"(d[29]),"+f"(d[30]),"+f"(d[31]),"+f"(d[32]),"+f"(d[33]),"+f"(d[34]),"+f"(d[35]),"+f"(d[36]),"+f"(d[37]),"+f"(d[38]),"+f"(d[39]),"+f"(d[40]),"+f"(d[41]),"+f"(d[42]),"+f"(d[43]),"+f"(d[44]),"+f"(d[45]),"+f"(d[46]),"+f"(d[47]),"+f"(d[48]),"+f"(d[49]),"+f"(d[50]),"+f"(d[51]),"+f"(d[52]),"+f"(d[53]),"+f"(d[54]),"+f"(d[55]),"+f"(d[56]),"+f"(d[57]),"+f"(d[58]),"+f"(d[59]),"+f"(d[60]),"+f"(d[61]),"+f"(d[62]),"+f"(d[63])
    : "l"(da), "l"(db), "r"(sd));
}
__device__ __forceinline__ void wg_ss160_01(float* d, uint64_t da, uint64_t db, int sd) {
  asm volatile("{.reg .pred p; setp.ne.b32 p, %82, 0;\n"
    "wgmma.mma_async.sync.aligned.m64n160k16.f32.bf16.bf16 {%0,%1,%2,%3,%4,%5,%6,%7,%8,%9,%10,%11,%12,%13,%14,%15,%16,%17,%18,%19,%20,%21,%22,%23,%24,%25,%26,%27,%28,%29,%30,%31,%32,%33,%34,%35,%36,%37,%38,%39,%40,%41,%42,%43,%44,%45,%46,%47,%48,%49,%50,%51,%52,%53,%54,%55,%56,%57,%58,%59,%60,%61,%62,%63,%64,%65,%66,%67,%68,%69,%70,%71,%72,%73,%74,%75,%76,%77,%78,%79}, %80, %81, p, 1, 1, 0, 1;}"
    : "+f"(d[0]),"+f"(d[1]),"+f"(d[2]),"+f"(d[3]),"+f"(d[4]),"+f"(d[5]),"+f"(d[6]),"+f"(d[7]),"+f"(d[8]),"+f"(d[9]),"+f"(d[10]),"+f"(d[11]),"+f"(d[12]),"+f"(d[13]),"+f"(d[14]),"+f"(d[15]),"+f"(d[16]),"+f"(d[17]),"+f"(d[18]),"+f"(d[19]),"+f"(d[20]),"+f"(d[21]),"+f"(d[22]),"+f"(d[23]),"+f"(d[24]),"+f"(d[25]),"+f"(d[26]),"+f"(d[27]),"+f"(d[28]),"+f"(d[29]),"+f"(d[30]),"+f"(d[31]),"+f"(d[32]),"+f"(d[33]),"+f"(d[34]),"+f"(d[35]),"+f"(d[36]),"+f"(d[37]),"+f"(d[38]),"+f"(d[39]),"+f"(d[40]),"+f"(d[41]),"+f"(d[42]),"+f"(d[43]),"+f"(d[44]),"+f"(d[45]),"+f"(d[46]),"+f"(d[47]),"+f"(d[48]),"+f"(d[49]),"+f"(d[50]),"+f"(d[51]),"+f"(d[52]),"+f"(d[53]),"+f"(d[54]),"+f"(d[55]),"+f"(d[56]),"+f"(d[57]),"+f"(d[58]),"+f"(d[59]),"+f"(d[60]),"+f"(d[61]),"+f"(d[62]),"+f"(d[63]),"+f"(d[64]),"+f"(d[65]),"+f"(d[66]),"+f"(d[67]),"+f"(d[68]),"+f"(d[69]),"+f"(d[70]),"+f"(d[71]),"+f"(d[72]),"+f"(d[73]),"+f"(d[74]),"+f"(d[75]),"+f"(d[76]),"+f"(d[77]),"+f"(d[78]),"+f"(d[79])
    : "l"(da), "l"(db), "r"(sd));
}
__device__ __forceinline__ void wg_ss80_01(float* d, uint64_t da, uint64_t db, int sd) {
  asm volatile("{.reg .pred p; setp.ne.b32 p, %42, 0;\n"
    "wgmma.mma_async.sync.aligned.m64n80k16.f32.bf16.bf16 {%0,%1,%2,%3,%4,%5,%6,%7,%8,%9,%10,%11,%12,%13,%14,%15,%16,%17,%18,%19,%20,%21,%22,%23,%24,%25,%26,%27,%28,%29,%30,%31,%32,%33,%34,%35,%36,%37,%38,%39}, %40, %41, p, 1, 1, 0, 1;}"
    : "+f"(d[0]),"+f"(d[1]),"+f"(d[2]),"+f"(d[3]),"+f"(d[4]),"+f"(d[5]),"+f"(d[6]),"+f"(d[7]),"+f"(d[8]),"+f"(d[9]),"+f"(d[10]),"+f"(d[11]),"+f"(d[12]),"+f"(d[13]),"+f"(d[14]),"+f"(d[15]),"+f"(d[16]),"+f"(d[17]),"+f"(d[18]),"+f"(d[19]),"+f"(d[20]),"+f"(d[21]),"+f"(d[22]),"+f"(d[23]),"+f"(d[24]),"+f"(d[25]),"+f"(d[26]),"+f"(d[27]),"+f"(d[28]),"+f"(d[29]),"+f"(d[30]),"+f"(d[31]),"+f"(d[32]),"+f"(d[33]),"+f"(d[34]),"+f"(d[35]),"+f"(d[36]),"+f"(d[37]),"+f"(d[38]),"+f"(d[39])
    : "l"(da), "l"(db), "r"(sd));
}
__device__ __forceinline__ void wg_rs32_00(float* d, uint32_t a0, uint32_t a1, uint32_t a2, uint32_t a3, uint64_t db, int sd) {
  asm volatile("{.reg .pred p; setp.ne.b32 p, %21, 0;\n"
    "wgmma.mma_async.sync.aligned.m64n32k16.f32.bf16.bf16 {%0,%1,%2,%3,%4,%5,%6,%7,%8,%9,%10,%11,%12,%13,%14,%15}, {%16,%17,%18,%19}, %20, p, 1, 1, 0;}"
    : "+f"(d[0]),"+f"(d[1]),"+f"(d[2]),"+f"(d[3]),"+f"(d[4]),"+f"(d[5]),"+f"(d[6]),"+f"(d[7]),"+f"(d[8]),"+f"(d[9]),"+f"(d[10]),"+f"(d[11]),"+f"(d[12]),"+f"(d[13]),"+f"(d[14]),"+f"(d[15])
    : "r"(a0), "r"(a1), "r"(a2), "r"(a3), "l"(db), "r"(sd));
}
__device__ __forceinline__ void wg_rs64_00(float* d, uint32_t a0, uint32_t a1, uint32_t a2, uint32_t a3, uint64_t db, int sd) {
  asm volatile("{.reg .pred p; setp.ne.b32 p, %37, 0;\n"
    "wgmma.mma_async.sync.aligned.m64n64k16.f32.bf16.bf16 {%0,%1,%2,%3,%4,%5,%6,%7,%8,%9,%10,%11,%12,%13,%14,%15,%16,%17,%18,%19,%20,%21,%22,%23,%24,%25,%26,%27,%28,%29,%30,%31}, {%32,%33,%34,%35}, %36, p, 1, 1, 0;}"
    : "+f"(d[0]),"+f"(d[1]),"+f"(d[2]),"+f"(d[3]),"+f"(d[4]),"+f"(d[5]),"+f"(d[6]),"+f"(d[7]),"+f"(d[8]),"+f"(d[9]),"+f"(d[10]),"+f"(d[11]),"+f"(d[12]),"+f"(d[13]),"+f"(d[14]),"+f"(d[15]),"+f"(d[16]),"+f"(d[17]),"+f"(d[18]),"+f"(d[19]),"+f"(d[20]),"+f"(d[21]),"+f"(d[22]),"+f"(d[23]),"+f"(d[24]),"+f"(d[25]),"+f"(d[26]),"+f"(d[27]),"+f"(d[28]),"+f"(d[29]),"+f"(d[30]),"+f"(d[31])
    : "r"(a0), "r"(a1), "r"(a2), "r"(a3), "l"(db), "r"(sd));
}
__device__ __forceinline__ void wg_rs128_00(float* d, uint32_t a0, uint32_t a1, uint32_t a2, uint32_t a3, uint64_t db, int sd) {
  asm volatile("{.reg .pred p; setp.ne.b32 p, %69, 0;\n"
    "wgmma.mma_async.sync.aligned.m64n128k16.f32.bf16.bf16 {%0,%1,%2,%3,%4,%5,%6,%7,%8,%9,%10,%11,%12,%13,%14,%15,%16,%17,%18,%19,%20,%21,%22,%23,%24,%25,%26,%27,%28,%29,%30,%31,%32,%33,%34,%35,%36,%37,%38,%39,%40,%41,%42,%43,%44,%45,%46,%47,%48,%49,%50,%51,%52,%53,%54,%55,%56,%57,%58,%59,%60,%61,%62,%63}, {%64,%65,%66,%67}, %68, p, 1, 1, 0;}"
    : "+f"(d[0]),"+f"(d[1]),"+f"(d[2]),"+f"(d[3]),"+f"(d[4]),"+f"(d[5]),"+f"(d[6]),"+f"(d[7]),"+f"(d[8]),"+f"(d[9]),"+f"(d[10]),"+f"(d[11]),"+f"(d[12]),"+f"(d[13]),"+f"(d[14]),"+f"(d[15]),"+f"(d[16]),"+f"(d[17]),"+f"(d[18]),"+f"(d[19]),"+f"(d[20]),"+f"(d[21]),"+f"(d[22]),"+f"(d[23]),"+f"(d[24]),"+f"(d[25]),"+f"(d[26]),"+f"(d[27]),"+f"(d[28]),"+f"(d[29]),"+f"(d[30]),"+f"(d[31]),"+f"(d[32]),"+f"(d[33]),"+f"(d[34]),"+f"(d[35]),"+f"(d[36]),"+f"(d[37]),"+f"(d[38]),"+f"(d[39]),"+f"(d[40]),"+f"(d[41]),"+f"(d[42]),"+f"(d[43]),"+f"(d[44]),"+f"(d[45]),"+f"(d[46]),"+f"(d[47]),"+f"(d[48]),"+f"(d[49]),"+f"(d[50]),"+f"(d[51]),"+f"(d[52]),"+f"(d[53]),"+f"(d[54]),"+f"(d[55]),"+f"(d[56]),"+f"(d[57]),"+f"(d[58]),"+f"(d[59]),"+f"(d[60]),"+f"(d[61]),"+f"(d[62]),"+f"(d[63])
    : "r"(a0), "r"(a1), "r"(a2), "r"(a3), "l"(db), "r"(sd));
}
__device__ __forceinline__ void wg_rs24_01(float* d, uint32_t a0, uint32_t a1, uint32_t a2, uint32_t a3, uint64_t db, int sd) {
  asm volatile("{.reg .pred p; setp.ne.b32 p, %17, 0;\n"
    "wgmma.mma_async.sync.aligned.m64n24k16.f32.bf16.bf16 {%0,%1,%2,%3,%4,%5,%6,%7,%8,%9,%10,%11}, {%12,%13,%14,%15}, %16, p, 1, 1, 1;}"
    : "+f"(d[0]),"+f"(d[1]),"+f"(d[2]),"+f"(d[3]),"+f"(d[4]),"+f"(d[5]),"+f"(d[6]),"+f"(d[7]),"+f"(d[8]),"+f"(d[9]),"+f"(d[10]),"+f"(d[11])
    : "r"(a0), "r"(a1), "r"(a2), "r"(a3), "l"(db), "r"(sd));
}

#define AB_POLY 0x77
__device__ __forceinline__ constexpr bool poly_group(int group) { return (AB_POLY >> (group & 7)) & 1; }

template <int V> struct Int { static constexpr int value = V; };

template <int NG>
__device__ __forceinline__ void ln_stats(const float4 (&v)[NG][5], uint32_t scratch, float (&mean)[NG], float (&rs)[NG]) {
  const int warp = threadIdx.x >> 5, lane = threadIdx.x & 31;
#pragma unroll
  for (int r = 0; r < NG; r++) {
    float s = 0.f, q = 0.f;
#pragma unroll
    for (int i = 0; i < 5; i++) s += (v[r][i].x + v[r][i].y) + (v[r][i].z + v[r][i].w);
    s += __shfl_xor_sync(~0u, s, 1); s += __shfl_xor_sync(~0u, s, 2);
    s *= 1.f / 80;
#pragma unroll
    for (int i = 0; i < 5; i++) {
      const float x = v[r][i].x - s, y = v[r][i].y - s, z = v[r][i].z - s, w = v[r][i].w - s;
      q += (x * x + y * y) + (z * z + w * w);
    }
    q += __shfl_xor_sync(~0u, q, 1); q += __shfl_xor_sync(~0u, q, 2);
    mean[r] = s; rs[r] = q;
  }
  bar_sync(1, 256);
  if ((lane & 3) == 0) {
#pragma unroll
    for (int r = 0; r < NG; r++) sts64f(scratch + r * 512 + lane * 16 + warp * 8, mean[r], rs[r]);
  }
  bar_sync(1, 256);
#pragma unroll
  for (int r = 0; r < NG; r++) {
    const float4 e = lds128f(scratch + r * 512 + lane * 16);
    float t = e.x + e.z;
    t += __shfl_xor_sync(~0u, t, 1); t += __shfl_xor_sync(~0u, t, 2);
    t *= 0.125f;
    float q = e.y + e.w + 80.f * ((e.x - t) * (e.x - t) + (e.z - t) * (e.z - t));
    q += __shfl_xor_sync(~0u, q, 1); q += __shfl_xor_sync(~0u, q, 2);
    mean[r] = t; rs[r] = rsqrtf(q * (1.f / DM) + 1e-5f);
  }
}

__device__ __forceinline__ void ln_store(const uint32_t (&w)[2][5][2], int tile, int u0) {
  const int lane = threadIdx.x & 31;
  uint32_t* xc = g_xc + ((tile >> 1) * 40 + u0) * 256 + (tile & 1) * 64 + lane;
#pragma unroll
  for (int i = 0; i < 20; i++) xc[(i >> 1) * 128 + (i & 1) * 32] = w[i & 1][i >> 2][i >> 1 & 1];
#pragma unroll
  for (int i = 0; i < 5; i++) {
    const int u = u0 + i;
    uint32_t* xn = g_xn + (((tile >> 3) * 20 + (u >> 1)) * 16 + (tile & 1) * 8 + (tile & 6)) * 128 + (u & 1) * 64 + lane;
#pragma unroll
    for (int r = 0; r < 2; r++) { xn[r * 128] = w[r][i][0]; xn[r * 128 + 32] = w[r][i][1]; }
  }
}
__device__ __forceinline__ void wait_count(const uint32_t* c, uint32_t n) {
  int spin = 0;
  while ((ld_acquire(c) & 0xffff) < n) { __nanosleep(32); spin_guard(spin); }
}

__device__ __forceinline__ uint8_t* pool_at(uint32_t off) {
  return reinterpret_cast<uint8_t*>((reinterpret_cast<uintptr_t>(g_pool) + 8191) & ~(uintptr_t)8191) + off; }
struct Weights { const uint8_t* w[4]; };
__device__ __forceinline__ void prefetch_weights(const Weights& p, int i) {
  if (blockIdx.x < 128) asm volatile("cp.async.bulk.prefetch.L2.global [%0], 61440;" :: "l"(p.w[i] + (size_t)blockIdx.x * 61440) : "memory");
}
__global__ void __launch_bounds__(256) first_kernel(const __nv_bfloat16* __restrict__ xin, const uint4* __restrict__ wb, const __grid_constant__ Weights wa) {
  __shared__ __align__(16) float scratch[256];
  __shared__ uint32_t lat[4];
  const int warp = threadIdx.x >> 5, lane = threadIdx.x & 31, cta = blockIdx.x;
  TRACE(0);
  pdl_launch();
  if (warp < 4 && (warp < 2 || cta < NSLOT)) {
    uint32_t* q = reinterpret_cast<uint32_t*>(pool_at((warp < 2 ? NSLOT : cta) * 8192 + (warp & 1) * 4096)) + (warp < 2 ? (cta & 127) * 8 : 0);
    if (lane < 8) stg_strong32(q + lane, 0u);
    uint32_t best = ~0u;
    if (lane == 0)
      for (int r = 0; r < 4; r++) {
        uint32_t t0, t1, v;
        asm volatile("mov.u32 %0, %%clock;" : "=r"(t0) :: "memory");
        asm volatile("atom.relaxed.gpu.global.exch.b32 %0, [%1], 0;" : "=r"(v) : "l"(q) : "memory");
        asm volatile("{.reg .u32 t; add.u32 t, %1, 1; mov.u32 %0, %%clock; sub.u32 %0, %0, %1;}" : "=r"(t1) : "r"(__shfl_sync(1u, v, 0)) : "memory");
        best = min(best, t1 - t0);
      }
    if (lane == 0) lat[warp] = best;
  }
  __syncthreads();
  ABT(2, 0);
  if (threadIdx.x == 0) {
    const int part = lat[0] < lat[1] ? 0 : 1;
    uint32_t smid; asm("mov.u32 %0, %%smid;" : "=r"(smid));
    g_smpart[smid & 255] = part;
    g_smclk[smid & 255] = clk32() - gtime() * 2;
    g_smuse[smid & 255] = 0;
    if (cta < NSLOT) g_orient[cta] = lat[2] < lat[3] ? part : 1 - part;
  }
  if (cta < 128) {
    float4 v[2][5];
#pragma unroll
    for (int r = 0; r < 2; r++)
#pragma unroll
      for (int i = 0; i < 5; i++) {
        const uint32_t* src = reinterpret_cast<const uint32_t*>(xin) + (cta * 16 + r * 8 + (lane >> 2)) * (DM / 2) + warp * 40 + i * 8 + (lane & 3);
        const uint32_t a = src[0], b = src[4];
        v[r][i] = make_float4(bf_lo(a), bf_hi(a), bf_lo(b), bf_hi(b));
      }
    uint4 w8[2];
#pragma unroll
    for (int i = 0; i < 2; i++) w8[i] = wb[cta * 400 + min(i * 256 + threadIdx.x, 399)];
    if (threadIdx.x < 128) g_stat[cta * 128 + threadIdx.x] = make_float2(0.f, 0.f);
#pragma unroll
    for (int i = 0; i < 10; i++) g_x[((cta * 2 + i / 5) * 40 + warp * 5 + i % 5) * 32 + lane] = v[i / 5][i % 5];
    ABT(2, 1);
    if (threadIdx.x == 32) for (int i = 0; i < FK_PF; i++) prefetch_weights(wa, i);
    float mean[2], rs[2];
    ln_stats<2>(v, s2u(scratch), mean, rs);
    ABT(2, 2);
    uint32_t w[2][5][2];
#pragma unroll
    for (int i = 0; i < 10; i++) {
      const float4 t = v[i / 5][i % 5];
      const float m = mean[i / 5], q = rs[i / 5];
      w[i / 5][i % 5][0] = pack2((t.x - m) * q, (t.y - m) * q); w[i / 5][i % 5][1] = pack2((t.z - m) * q, (t.w - m) * q);
    }
    ln_store(w, cta, warp * 5);
    ABT(2, 3);
#pragma unroll
    for (int i = 0; i < 2; i++) {
      const int e = cta * 400 + min(i * 256 + threadIdx.x, 399), k = e / 80, n = e - k * 80, cg = n / 10;
      g_wb[((cg * 80 + (k >> 3)) * 10 + n - cg * 10) * 8 + (k & 7)] = w8[i];
    }
  } else if (cta == 128) {
    g_bo[threadIdx.x] = 0;
  }
  TRACE(2);
}

struct ChainParams {
  CUtensorMap wq, wk, wv, wo;
  const __nv_bfloat16* mem0;
  uint8_t *pool, *kv;
  const uint32_t* xc;
  uint32_t* sync;
  int layer;
  int d0, d3, d1, d1b, d2, d2b, mode;
};
constexpr int CH_WQ = 0, CH_WO = 81920, CH_X = CH_WO + 86016, CH_M = CH_X + 20480, CH_KT = CH_X + 40960, CH_VT = CH_KT + 4096,
              CH_PS = CH_VT + 4096, CH_QK = CH_PS + 4096, CH_VP = CH_QK + 4096, CH_SX = CH_VP + 1024, CH_O = CH_SX + 2304, CH_ID = CH_O + 3072,
              CH_BAR = CH_ID + 512;
constexpr int CH_SMEM = CH_BAR + 256;
constexpr int CH_BASE = 1024;
#define CH_VK0 8
#define CH_VK1 20
#define CH_L0 4
#define CH_LR 4
#define NOX 0
#define CH_XA 1
#define CH_XB 4
#define CH_W1 3
#define CH_W2 17
#define CH_W3 26
#define CH_R2 8
#define CH_VA 16
#define CH_EX 1
#define CH_KD 0
#define CH_RP 1
#define CH_KF 10
#define CH_LO 0
#define CH_LR1 4
#define CH_KP 0
#define CH_KM 0
#define CH_WE 0
#define CH_KW 3
#define CH_RB 0
#define CH_RC 8
#define CH_D0 200
#define CH_D1 450
#define CH_D2 350
#define CH_R1 4
#define CH_TW 12
__device__ __forceinline__ uint32_t opaque(uint32_t x) { return __shfl_sync(~0u, x, threadIdx.x & 31); }
__device__ __forceinline__ uint32_t nz(uint32_t x) { uint32_t r; asm("max.u32 %0, %1, 1;" : "=r"(r) : "r"(x)); return r; }
__device__ __forceinline__ uint32_t pack_tag(float lo, float hi, uint32_t tag, uint32_t mask) {
  uint32_t r;
  asm("lop3.b32 %0, %1, %2, %3, 0xD8;" : "=r"(r) : "r"(pack2(lo, hi)), "r"(tag), "r"(mask));
  return r;
}
__device__ __forceinline__ uint32_t differ(uint32_t a, uint32_t b, uint32_t t) { uint32_t r; asm("lop3.b32 %0, %1, %2, %3, 0x7E;" : "=r"(r) : "r"(a), "r"(b), "r"(t)); return r; }
__device__ __forceinline__ void mbar_wait_hot(uint32_t bar, uint32_t ph) {
  uint32_t ok;
  asm volatile("{.reg .pred p; mbarrier.try_wait.parity.shared::cta.b64 p, [%1], %2; selp.u32 %0, 1, 0, p;}" : "=r"(ok) : "r"(bar), "r"(ph) : "memory");
  if (__builtin_expect(!ok, 0)) mbar_wait(bar, ph);
}
__device__ __forceinline__ bool elect() {
  uint32_t r; asm volatile("{.reg .pred p; elect.sync _|p, 0xffffffff; selp.u32 %0, 1, 0, p;}" : "=r"(r)); return r; }
__device__ __forceinline__ uint32_t or3(uint32_t a, uint32_t b, uint32_t c) { uint32_t r; asm("lop3.b32 %0, %1, %2, %3, 0xFE;" : "=r"(r) : "r"(a), "r"(b), "r"(c)); return r; }
__device__ __forceinline__ void pin() { pdl_launch(); }
__device__ __forceinline__ void mma16h(float* d, uint32_t a0, uint32_t a2, uint32_t b0, uint32_t b1) {
  asm volatile("{.reg .b32 u, v; mma.sync.aligned.m16n8k16.row.col.f32.bf16.bf16.f32 {%0,%1,%2,%3},{%4,u,%5,v},{%6,%7},{%0,%1,%2,%3};}"
               : "+f"(d[0]), "+f"(d[1]), "+f"(d[2]), "+f"(d[3]) : "r"(a0), "r"(a2), "r"(b0), "r"(b1)); }
__device__ __forceinline__ void mma8h(float* d, uint32_t a0, uint32_t b0) {
  asm volatile("{.reg .b32 u; mma.sync.aligned.m16n8k8.row.col.f32.bf16.bf16.f32 {%0,%1,%2,%3},{%4,u},{%5},{%0,%1,%2,%3};}"
               : "+f"(d[0]), "+f"(d[1]), "+f"(d[2]), "+f"(d[3]) : "r"(a0), "r"(b0)); }
__device__ __forceinline__ uint32_t absmax2(uint32_t a, uint32_t b) { uint32_t r; asm("max.xorsign.abs.bf16x2 %0, %1, %2;" : "=r"(r) : "r"(a), "r"(b)); return r; }
__device__ __forceinline__ void until(uint32_t t) { while ((int)(clk32() - t) < 0) {} }
__device__ __forceinline__ uint4 pack8(const float* d) { return make_uint4(pack2(d[0], d[1]), pack2(d[2], d[3]), pack2(d[4], d[5]), pack2(d[6], d[7])); }
__device__ __forceinline__ void add8(float* d, uint4 v) {
  d[0] += bf_lo(v.x); d[1] += bf_hi(v.x); d[2] += bf_lo(v.y); d[3] += bf_hi(v.y);
  d[4] += bf_lo(v.z); d[5] += bf_hi(v.z); d[6] += bf_lo(v.w); d[7] += bf_hi(v.w);
}

template <int WG>
__device__ __forceinline__ void chain_body(const ChainParams& p, const uint32_t wq, const uint32_t (&ak)[80], const uint32_t (&av)[80]) {
  const int tid = threadIdx.x & 127, t4 = __shfl_sync(~0u, tid >> 5, 0), lane = tid & 31;
  const int cta = blockIdx.x, h = cta / 3, j = cta - 3 * h;
  const uint32_t sb = mapa(CH_BASE, j);
  const uint32_t bWo = sb + CH_BAR, bWq = bWo + 8, bX = bWo + 16, bXA = bWo + 24, bXB = bWo + 32, bO = bWo + 40, bG = bWo + 48, bH = bWo + 96;
  uint32_t tw[4 * CH_TW];
  auto refill = [&]() {
#pragma unroll
    for (int k = 0; k < CH_TW; k++) ldsm4t(&tw[4 * k], wq + k * 2048);
  };
  const uint32_t wo = opaque((sb + CH_WO + (WG == 0 ? (t4 + (j == 2)) * 4096 : (j == 2 ? 0 : 24576) + t4 * 1024) + ((lane & 7) + (lane >> 4) * 8) * 64 +
                              ((((lane >> 3) & 1) ^ ((lane >> 1) & 3)) << 4)) ^ (WG == 1 && j == 2 ? 32 : 0));
  const uint32_t wo2 = opaque((wo ^ ((t4 & 1) * 32)) + (4 + (t4 >> 1) - t4) * 4096);
  const uint32_t l16 = opaque(sb + lane * 16);
  const uint32_t l8 = opaque(sb + t4 * 256 + lane * 8);
  const uint32_t lw = opaque(sb + t4 * 1024 + lane * 16);
  const uint32_t qs = opaque(sb + CH_QK + WG * 2048 + t4 * 512 + lane * 16);
  const uint32_t qa = opaque(sb + CH_QK + (lane >> 4) * 2048 + (lane & 15) * 16 + (WG == 0 ? t4 * 512 + 256 : t4 == 3 ? 1024 : 0));
  const uint32_t ka = opaque(t4 < 2 ? sb + CH_KT + t4 * 512 + lane * 16
                                    : sb + CH_QK + 256 + (t4 - 2) * 1024 + ((lane >> 3) & 1) * 2048 + (lane >> 4) * 128 + (lane & 7) * 16);
  const uint32_t l4 = opaque(sb + t4 * 256 + lane * 4);
  uint32_t pdst[1], pages = 0;
  auto line0 = [&](int i) { return 28 * j + (i < 4 ? 4 * t4 + i : 12 + 2 * t4 + i); };
  const uint32_t plane = opaque((lane >> 4) * 2048 + h * 64 + (lane & 15) * 4);
  if (WG == 0) {
    pages = __ballot_sync(~0u, lds32(sb + CH_O + line0(min(lane, 5)) * 4) & 4096);
  } else {
    pages = __ballot_sync(~0u, lds32(sb + CH_O + (80 + min(lane, 11)) * 4) & 4096);
    pdst[0] = opaque(lds32(sb + CH_O + (j == 0 ? 24 + t4 : 50 + 2 * j + (t4 & 1)) * 4) + plane);
  }
  const uint32_t role = lds32(sb + CH_O + NSLOT * 4), rsrc = lds32(sb + CH_O + role * 4), rdst = (80 + role / 20) * 8192 + role % 20 * 128;
  const uint32_t r1 = mapa(CH_BASE, j == 2 ? 0 : j + 1) - sb, r2 = mapa(CH_BASE, j == 0 ? 2 : j - 1) - sb;
  uint32_t tag = opaque(1);
  auto pool = [&](uint32_t off) { return p.pool + ((tag & 0xfffe) + off); };
  auto after = [&](uint32_t x) { return x & tag & 0xfffe; };
  auto kv = [&](int s, uint32_t a) { return p.kv + (a + ((cta * 2 * NSEG + s) * KV_BYTES - sb)); };
  auto pass = [&](float (&d)[16], const uint32_t (&a)[80], auto k0, auto k1) {
    const uint64_t db = mkdesc(CH_BASE + CH_X + WG * 20480, 512, 128, 0);
#pragma unroll
    for (int k = k0.value; k < k1.value; k++) wg_rs32_00(d, a[4 * k], a[4 * k + 1], a[4 * k + 2], a[4 * k + 3], db + k * 64, k);
    wg_commit();
  };
  auto dump = [&](float (&d)[16], uint32_t a) {
    reg_fence<16>(d);
    sts128(a, pack8(d)); sts128(a + 512, pack8(d + 8));
  };
  uint32_t pph = 0;
  auto tokens0 = [&](int s, auto k0) {
    float dk[16], dv[16];
    bar_sync(9, 256);
    wg_fence();
    pass(dk, ak, Int<0>(), Int<4>());
    const uint4 a0 = lds128(lw + CH_KT), a1 = lds128(lw + CH_KT + 512);
    pin();
    pass(dk, ak, Int<4>(), Int<20>());
    pass(dv, av, Int<0>(), Int<CH_VA>());
    pin();
    wg_wait<1>();
    reg_fence<16>(dk);
    add8(dk, a0); add8(dk + 8, a1);
    const uint4 w0 = pack8(dk), w1 = pack8(dk + 8);
    const uint4 b0 = lds128(lw + CH_VT), b1 = lds128(lw + CH_VT + 512);
    stsm4t(lw + CH_KT, w0.x, w0.z, w0.y, w0.w); stsm4t(lw + CH_KT + 512, w1.x, w1.z, w1.y, w1.w);
    if (CH_KP == 2) bar_arrive(7, 160);
    TM1(6);
    pin();
    if (CH_VA < 20) pass(dv, av, Int<CH_VA>(), Int<20>());
    pin();
#pragma unroll
    for (int k = k0.value; k < CH_TW; k++) ldsm4t(&tw[4 * k], wq + k * 2048);
    TM1(9);
    if (k0.value < CH_TW && t4 >= 2) { mbar_wait_hot(bH + t4 * 16 - 24 + (pph & 1) * 8, pph >> 1 & 1); pph++; }
    __syncwarp();
    wg_wait<0>();
    reg_fence<16>(dv);
    add8(dv, b0); add8(dv + 8, b1);
#pragma unroll
    for (int e = 0; e < 2; e++) { const uint4 v = pack8(dv + 8 * e); sts128(lw + CH_VT + e * 512, make_uint4(v.x, v.z, v.y, v.w)); }
  };
  auto publish_k = [&](int s) {
    if (t4 == CH_KW && elect()) { fence_async(); bulk_store(p.kv + (size_t)(cta * 2 * NSEG + s) * KV_BYTES, sb + CH_KT, 4096); bulk_commit(); }
    __syncwarp();
  };
  if (WG == 0) {
    mbar_wait(bXB, 0);
    tokens0(0, Int<CH_TW>());
  } else {
    const uint32_t* m0 = reinterpret_cast<const uint32_t*>(p.mem0) + (lane >> 2) * 320 + t4 * 80 + (lane & 3);
    uint32_t a[20];
#pragma unroll
    for (int i = 0; i < 20; i++) a[i] = m0[4 * i];
    pin();
    float dk[16], dv[16];
    mbar_wait(bXA, 0);
    wg_fence();
    pass(dk, ak, Int<0>(), Int<20>());
    pass(dv, av, Int<0>(), Int<20>());
    wg_wait<0>();
    dump(dk, lw + CH_KT);
    dump(dv, lw + CH_VT);
    bar_sync(9, 256);
    if (CH_KP == 2 && t4 == CH_KW) { bar_sync(7, 160); publish_k(0); }
#pragma unroll
    for (int i = 0; i < 20; i++) sts32(sb + CH_M + (t4 * 20 + i) * 128 + lane * 4, nz(transpose8(a[i])));
    __syncwarp();
    if (elect()) mbar_arrive(bG + t4 * 8);
  }
  PRO(8);
  mbar_wait(bWq, 0);
  refill();
  PRO(9);
  mbar_wait(bWo, 0);
  asm volatile("barrier.cluster.wait.aligned;" ::: "memory");
  PRO(10);
  auto load_x = [&](int s, int k0, int n, uint32_t bar) {
    if (!NOX && elect()) { mbar_expect(bar, n * 1024); bulk_load(sb + CH_X + k0 * 1024, p.xc + (s + 1) * 10240 + k0 * 256, n * 1024, bar); }
  };
  constexpr int VK = WG == 0 ? CH_VK0 : CH_VK1;
  uint32_t gph = 0;
  int st = 0;
  const uint32_t ca = opaque(sb + CH_M + t4 * 2560 + lane * 32 + (lane >> 2) * 4);
  auto project = [&](int s, uint32_t (&b)[40], float (&dv)[16], uint32_t (&kf)[16]) {
    float dq[4] = {}, dk[4] = {};
    uint32_t w[80];
#pragma unroll
    for (int i = 0; i < 4 * CH_TW; i++) w[i] = tw[i];
    constexpr int LR = WG == 1 ? CH_LR1 : CH_LR;
    auto load = [&](int n) {
      int c = 0;
#pragma unroll
      for (int i = 0; i < 10; i++) {
        if (i == CH_KF) {
#pragma unroll
          for (int q = 0; q < 4; q++)
            if (WG == 1 && c++ == n) ldsm4(&kf[4 * q], ka + q * 1024);
        }
        if (c++ == n) ldsm4t(&b[4 * i], l16 + CH_M + WG * 5120 + i * 512);
#pragma unroll
        for (int k = 2 * i; k < 2 * i + 2; k++)
          if (k >= CH_TW && c++ == n) ldsm4t(&w[4 * k], wq + k * 2048);
      }
#pragma unroll
      for (int i = 0; i < 4; i++)
        if (WG == 1 && CH_KF >= 10 && c++ == n) ldsm4(&kf[4 * i], ka + i * 1024);
    };
    if (WG == 1) {
      for (int n = 0;;) {
        mbar_wait(bG + t4 * 8, gph);
        TR(5, (clk32() & ~3u) | min(n, 3));
        gph ^= 1;
        if (__builtin_expect(!__any_sync(~0u, __vimin3_u32(lds32(ca), lds32(ca + 1024), lds32(ca + 1536)) == 0), 1)) break;
        if (elect()) {
          const int q = (st == 0 ? 8 : st * 4 - 4) + t4;
          mbar_expect(bG + t4 * 8, 2560);
          bulk_load(sb + CH_M + t4 * 2560, p.pool + ((80 + q) * 8192 + (pages >> q & 1) * 4096), 2560, bG + t4 * 8);
        }
        spin_guard(n);
      }
    }
    bar_sync(6, 256);
#pragma unroll
    for (int i = 0; i < CH_L0; i++) load(i);
    if (WG == 0 && CH_XB == 4 && s + 1 < NSEG) load_x(s, 5 * t4, 5, bXB);
    TM(0);
    TM1(11);
    if (WG == 1) TR(6, clk32());
#pragma unroll
    for (int k = 0; k < 20; k += 2) {
      if (k > 0) {
#pragma unroll
        for (int n = (k == 18 ? 40 : CH_L0 + k * LR / 4) - 1; n >= CH_L0 + (k - 2) * LR / 4; n--) { load(n); if (CH_LO) __syncwarp(); }
      }
      pin();
#pragma unroll
      for (int kk = k; kk < k + 2; kk++) {
        mma16(dk, ak[4 * kk], ak[4 * kk + 1], ak[4 * kk + 2], ak[4 * kk + 3], b[2 * kk], b[2 * kk + 1]);
        mma16(dq, w[4 * kk], w[4 * kk + 1], w[4 * kk + 2], w[4 * kk + 3], b[2 * kk], b[2 * kk + 1]);
        if (kk < VK) mma16(dv, av[4 * kk], av[4 * kk + 1], av[4 * kk + 2], av[4 * kk + 3], b[2 * kk], b[2 * kk + 1]);
      }
    }
    const float k2 = 0.07216878364870322f * 1.44269504089f;
    stsm4t(qs, pack2(dq[0] * k2, dq[1] * k2), pack2(dq[2] * k2, dq[3] * k2), pack2(dk[0], dk[1]), pack2(dk[2], dk[3]));
    TM(1);
  };
  constexpr int VC = VK == 20 ? 1 : WG == 0 ? 2 : 3;
  auto finish_v = [&](const uint32_t (&b)[40], float (&dv)[16]) {
#pragma unroll
    for (int kk = VK; kk < 20; kk++) mma16(dv + 4 * ((kk - VK) % VC), av[4 * kk], av[4 * kk + 1], av[4 * kk + 2], av[4 * kk + 3], b[2 * kk], b[2 * kk + 1]);
  };
  auto sum_v = [&](float (&dv)[16]) {
#pragma unroll
    for (int i = 4; i < 4 * VC; i++) dv[i & 3] += dv[i];
  };
  auto publish_km = [&](int s) {
    uint32_t a[4];
    ldsm4(a, qa);
    *reinterpret_cast<uint2*>(kv(s, l8) + KV_M) = make_uint2(hadd2(a[0], a[2]), hadd2(a[1], a[3]));
  };
  auto memory_v = [&](uint2 x, const float (&dv)[16]) {
    return make_uint2(pack2(dv[0] + bf_lo(x.x), dv[1] + bf_hi(x.x)), pack2(dv[2] + bf_lo(x.y), dv[3] + bf_hi(x.y)));
  };
  auto publish_v = [&](int s, const uint4 (&v)[2], uint2 vm) {
#pragma unroll
    for (int e = 0; e < 2; e++) reinterpret_cast<uint4*>(kv(s, lw) + KV_V)[e * 32] = v[e];
    *reinterpret_cast<uint2*>(kv(s, l8) + KV_V + KV_M) = vm;
  };
#pragma unroll 1
  for (int s = 0; s < NSEG - 1; s++) {
    float dv[16] = {};
    uint32_t b[40], kf[16];
    project(s, b, dv, kf);
    if (WG == 0) {
      bar_sync(1, 256);
      if (CH_XA == 0) load_x(s, 20 + 5 * t4, 5, bXA);
      if (CH_XB == 0) load_x(s, 5 * t4, 5, bXB);
      pin();
      finish_v(b, dv);
      sum_v(dv);
      sts64(l8 + CH_VP, pack2(dv[0], dv[1]), pack2(dv[2], dv[3]));
      __syncwarp();
      if (elect()) mbar_arrive(bX);
      if (CH_XA == 1) load_x(s, 20 + 5 * t4, 5, bXA);
      if (CH_XB == 1) load_x(s, 5 * t4, 5, bXB);
      uint32_t w[144];
      auto wload = [&](int i) { ldsm4t(&w[4 * i], (i % 3 == 0 ? wo : i % 3 == 1 ? wo ^ 32 : wo2) + i / 12 * 28672 + i / 3 % 4 * 1024); };
      TM(3);
      if (CH_KP == 0) publish_k(s);
#pragma unroll
      for (int i = 0; i < CH_W1; i++) wload(i);
      bar_sync(10, 256);
      uint32_t km[4];
      ldsm4(km, qa);
      pin();
#pragma unroll
      for (int i = CH_W1; i < CH_W2; i++) wload(i);
      pin();
      const uint2 kms = make_uint2(hadd2(km[0], km[2]), hadd2(km[1], km[3]));
      if (CH_KM == 0) *reinterpret_cast<uint2*>(kv(s, l8) + KV_M) = kms;
      if (CH_KP == 0) bulk_wait_read<0>();
      if (CH_XA == 2) load_x(s, 20 + 5 * t4, 5, bXA);
      if (CH_XB == 2) load_x(s, 5 * t4, 5, bXB);
      bar_sync(2, 256);
      {
        float y[3][4] = {};
        uint32_t ob[24];
        ldsm4(&ob[0], l16 + CH_O + 1024); ldsm4(&ob[4], l16 + CH_O + 1536);
        TM(7);
        auto step = [&](int i) {
          const int k = i / 3;
          mma16(y[i % 3], w[4 * i], w[4 * i + 1], w[4 * i + 2], w[4 * i + 3], ob[2 * k], ob[2 * k + 1]);
        };
#pragma unroll
        for (int i = 0; i < 12; i++) {
          step(i);
          if (i >= 12 - (CH_W3 - CH_W2)) wload(CH_W3 - 12 + i);
          if (i % 3 == 2) pin();
        }
        if (CH_XB == 3) load_x(s, 5 * t4, 5, bXB);
        if (CH_KM == 1) *reinterpret_cast<uint2*>(kv(s, l8) + KV_M) = kms;
        pin();
        mbar_wait(bO, s & 1);
        TM(4);
        ldsm4(&ob[8], l16 + CH_O); ldsm4(&ob[12], l16 + CH_O + 512);
        pin();
        float2 inv;
        uint8_t* dst[6];
        uint32_t mask;
#pragma unroll
        for (int i = 12; i < 36; i++) {
          step(i);
          const int n = CH_W3 + i - 13, m = n - (n > 30);
          if (i == 12) ldsm4(&ob[16], l16 + after(w[4 * CH_W3 - 1] | w[4 * CH_W3 - 5] | w[4 * CH_W3 - 9] | ob[8]) + CH_O + 2048);
          else if (n == 30) ldsm4(&ob[20], l16 + CH_O + 2560);
          else if (m < 36) wload(m);
          else if (m == 36) inv = lds64f((l8 & ~0xe0u) + CH_VP);
          if (i == 26) mask = ((l16 ^ tag) & 48) == 0;
          if (i >= 27 && i < 33) dst[i - 27] = pool(line0(i - 27) * 8192 + (pages >> (i - 27) & 1) * 4096) + plane;
          if (i % 3 == 2) pin();
        }
#pragma unroll
        for (int k = 0; k < CH_R1; k++) ldsm4t(&tw[4 * k], wq + k * 2048);
        pin();
#pragma unroll
        for (int i = 0; i < 6; i++) stg_strong32(dst[i], pack_tag(y[i >> 1][2 * (i & 1)] * inv.x, y[i >> 1][2 * (i & 1) + 1] * inv.y, tag, mask));
        TM(8);
        TR(0, clk32());
        bar_arrive(5, 256);
        pin();
      }
      const uint32_t t0 = clk32();
      auto refill2 = [&]() {
#pragma unroll
        for (int k = CH_R1; k < CH_R2; k++) ldsm4t(&tw[4 * k], wq + k * 2048);
      };
      if (CH_RP == 0) refill2();
      const uint32_t ln = (l16 ^ tag) >> 4 & 31;
      if (t4 >= 2) {
        const uint32_t bP = bH + t4 * 16 - 24, ps = CH_PS + (t4 & 1) * 4096;
        auto fetch = [&](uint32_t k) {
          if (elect()) { mbar_expect(bP + (k & 1) * 8, 2048); bulk_load(sb + ps + (k & 1) * 2048, p.pool + (rsrc + (t4 & 1) * 2048), 2048, bP + (k & 1) * 8); }
        };
        until(t0 + CH_D0);
        fetch(pph);
        if (CH_RP == 2) refill2();
        if (!NOX) mbar_wait_hot(bXB, (s + 1) & 1);
        const uint32_t want = (tag & 1) * 0x10001, chk = opaque(ln < 4 ? 0x10001 : 0);
        uint4 sel;
        sel.x = opaque((ln >> 3) != (ln & 1) ? 0 : ln & 4 ? 0x3f800000u : 0x00003f80u);
        sel.z = opaque(sel.x); sel.y = opaque(ln); sel.w = opaque(ln + 1);
        uint8_t* mdst = p.pool + opaque(st * 32768 + rdst + (t4 & 1) * 64 + ln * 4);
        until(t0 + CH_D1);
        fetch(pph + 1);
        TM(5);
        if (CH_RP == 1) refill2();
        int n = 0;
        uint32_t u[16];
        for (;;) {
          mbar_wait(bP + (pph & 1) * 8, pph >> 1 & 1);
          TM(14);
          TR(2, clk32());
#pragma unroll
          for (int i = 0; i < 4; i++) ldsm4t(&u[4 * i], l16 + (ps + (pph & 1) * 2048) + i * 512);
          pph++;
          uint32_t bad = 0;
#pragma unroll
          for (int i = 0; i < 4; i++) bad = or3(bad, differ(u[4 * i], u[4 * i + 1], want), differ(u[4 * i + 2], u[4 * i + 3], want));
          if (!__any_sync(~0u, bad & chk)) break;
          fetch(pph + 1);
          spin_guard(n);
        }
        float y[4][4] = {};
#pragma unroll
        for (int i = 0; i < 8; i++) mma16(y[i & 3], sel.x, sel.y, sel.z, sel.w, u[2 * i], u[2 * i + 1]);
        TR(1, t0 + (n ? CH_D1 : CH_D0));
        TM(15);
        const uint32_t w = nz(pack2((y[0][0] + y[1][0]) + (y[2][0] + y[3][0]), (y[0][1] + y[1][1]) + (y[2][1] + y[3][1])));
        if (ln < 16) { stg_strong32(mdst, w); stg_strong32(mdst + 4096, w); }
        TMV(12, 32, n);
        TR(3, (clk32() & ~3u) | min(n, 3));
      } else {
        if (CH_RP) refill2();
        if (!NOX) mbar_wait_hot(bXB, (s + 1) & 1);
        stg_strong32(p.pool + ((st == 2 ? 0 : st + 1) * 32768 + rdst + t4 * 4096) + ln * 4, 0u);
        if (t4 == 0 && cta < 40 && s + 4 < NSEG && elect())
          asm volatile("cp.async.bulk.prefetch.L2.global [%0], 1024;" :: "l"(p.xc + (s + 4) * 10240 + cta * 256) : "memory");
        if (t4 == 1 && (s & 3) == 0 && s > 0 && elect()) red_relaxed(p.sync + 2 * s - 4, 1);
        if (t4 == 1 && s == NSEG - 3 && cta == 95 && elect()) red_relaxed(p.sync + 2 * s + 2, 0x10000);
      }
      TM(10);
      bar_arrive(8, 256);
      tokens0(s + 1, Int<CH_R2>());
      TM(2);
      TR(7, clk32());
    } else {
      const uint32_t xo = l4 + (CH_SX - (t4 == 3 ? 128 : 0)), x1 = xo + (r1 + 768 + min(t4, 2) * 256), x2 = xo + (r2 + 1024 + min(t4, 2) * 256);
      if (t4 < 2) {
        float ds[4][4] = {};
        uint32_t q[16];
        asm volatile("bar.sync 1, 256;" ::: "memory");
#pragma unroll
        for (int k = 0; k < 4; k++) ldsm4(&q[4 * k], qa + k * 512);
        pin();
        if (VK < 20) { finish_v(b, dv); pin(); }
#pragma unroll
        for (int k = 0; k < 4; k++) {
          mma16(ds[k & 1], kf[4 * k], kf[4 * k + 1], kf[4 * k + 2], kf[4 * k + 3], q[4 * k], q[4 * k + 1]);
          mma16(ds[2 + (k & 1)], kf[4 * k], kf[4 * k + 1], kf[4 * k + 2], kf[4 * k + 3], q[4 * k + 2], q[4 * k + 3]);
        }
        float t[4];
#pragma unroll
        for (int i = 0; i < 4; i++) t[i] = (ds[0][i] + ds[2][i]) + (ds[1][i] + ds[3][i]);
        const uint32_t w0 = pack2(t[0], t[1]), w1 = pack2(t[2], t[3]);
        st_async32(x1, w0, bX + r1); st_async32(x2, w0, bX + r2);
        st_async32(x1 + 128, w1, bX + r1); st_async32(x2 + 128, w1, bX + r2);
        sts32(xo, w0); sts32(xo + 128, w1);
      } else {
        float ds[4][4] = {};
        uint32_t q0[4], q1[4], a0[4], a1[4];
        asm volatile("bar.sync 1, 256; " ::: "memory");
        ldsm4(a0, ka); ldsm4(q0, qa); ldsm4(a1, ka + 512); ldsm4(q1, qa + 512);
        pin();
        if (VK < 20) { finish_v(b, dv); pin(); }
        mma16(ds[0], a0[0], a0[1], a0[2], a0[3], q0[0], q0[1]);
        mma16(ds[1], a0[0], a0[1], a0[2], a0[3], q0[2], q0[3]);
        mma16(ds[2], a1[0], a1[1], a1[2], a1[3], q1[0], q1[1]);
        mma16(ds[3], a1[0], a1[1], a1[2], a1[3], q1[2], q1[3]);
        float t[2];
#pragma unroll
        for (int i = 0; i < 2; i++)
          t[i] = ((ds[0][i] + ds[0][i + 2]) + (ds[1][i] + ds[1][i + 2])) + ((ds[2][i] + ds[2][i + 2]) + (ds[3][i] + ds[3][i + 2]));
        const uint32_t w0 = pack2(t[0], t[1]);
        st_async32(x1, w0, bX + r1);
        st_async32(x2, w0, bX + r2);
        sts32(xo, w0);
      }
      TM(3);
      const uint4 id = lds128(l16 + CH_ID);
      float sc[3][4] = {};
      uint4 v[2];
      sum_v(dv);
      bar_sync(3, 128);
      uint32_t r[12], wd[12], we[12] = {};
      ldsm4(&r[0], l16 + CH_SX); ldsm2(&r[4], l16 + CH_SX + 512);
      pin();
      v[0] = lds128(lw + CH_VT); v[1] = lds128(lw + CH_VT + 512);
#pragma unroll
      for (int u = 0; u < 3; u++) ldsm4t(&wd[4 * u], wo + u * 28672);
      if (CH_WE && j == 0) {
#pragma unroll
        for (int u = 0; u < 3; u++) ldsm4t(&we[4 * u], (wo ^ 32) + u * 28672);
      }
      pin();
#pragma unroll
      for (int q = 0; q < 3; q++) mma16(sc[q], id.x, id.y, id.z, id.w, r[2 * q], r[2 * q + 1]);
      uint32_t big = absmax2(absmax2(absmax2(r[0], r[1]), absmax2(r[2], r[3])), absmax2(r[4], r[5]));
      const uint32_t oa1 = l4 + (r1 + CH_O), oa2 = l4 + (r2 + CH_O + 2048), ones = 0x3f803f80u;
      mbar_wait_hot(bX, s & 1);
      TM(4);
      ldsm4(&r[0], l16 + CH_SX + 768); ldsm4(&r[8], l16 + CH_SX + 1792); ldsm4(&r[4], l16 + CH_SX + 1280);
      const uint2 vp = lds64(l8 + CH_VP);
      bar_arrive(10, 256);
      pin();
      {
        float sd[3][4] = {};
#pragma unroll
        for (int i = 0; i < 3; i++) {
          const int q = i == 0 ? 0 : 3 - i;
          mma16(sc[q], id.x, id.y, id.z, id.w, r[4 * q], r[4 * q + 1]);
          mma16(sd[q], id.x, id.y, id.z, id.w, r[4 * q + 2], r[4 * q + 3]);
          big = absmax2(big, absmax2(absmax2(r[4 * q], r[4 * q + 1]), absmax2(r[4 * q + 2], r[4 * q + 3])));
        }
#pragma unroll
        for (int i = 0; i < 12; i++) sc[i >> 2][i & 3] += sd[i >> 2][i & 3];
      }
      const bool redo = __any_sync(~0u, (absmax2(big, big << 16) & 0x7fff0000u) >= 0x41800000u);
      const uint2 vm = memory_v(vp, dv);
      sc[2][0] += sc[2][2]; sc[2][1] += sc[2][3];
      float l[4], o[2][4];
      uint32_t p3, p4;
      auto attend = [&]() {
#pragma unroll
        for (int i = 0; i < 4; i++) l[i] = o[0][i] = o[1][i] = 0.f;
        const uint32_t p1 = pack2(ex2(sc[0][0]), ex2(sc[0][1])), p2 = pack2(ex2(sc[0][2]), ex2(sc[0][3]));
        mma16h(o[0], p1, p2, v[0].x, v[0].y);
        mma16h(o[1], p1, p2, v[0].z, v[0].w);
        mma16h(l, p1, p2, ones, ones);
        const uint32_t p0 = pack2(ex2(sc[2][0]), ex2(sc[2][1]));
        mma8h(o[0], p0, vm.x);
        mma8h(o[1], p0, vm.y);
        mma8h(l, p0, ones);
        p3 = pack2(ex2(sc[1][0]), ex2(sc[1][1])); p4 = pack2(ex2(sc[1][2]), ex2(sc[1][3]));
        mma16h(o[0], p3, p4, v[1].x, v[1].y);
        mma16h(o[1], p3, p4, v[1].z, v[1].w);
      };
      attend();
      if (__builtin_expect(redo, 0)) {
        float mx = fmaxf(sc[2][0], sc[2][1]);
#pragma unroll
        for (int i = 0; i < 4; i++) mx = fmaxf(mx, fmaxf(sc[0][i], sc[1][i]));
        mx = fmaxf(mx, __shfl_xor_sync(~0u, mx, 1));
        mx = fmaxf(mx, __shfl_xor_sync(~0u, mx, 2));
#pragma unroll
        for (int i = 0; i < 4; i++) { sc[0][i] -= mx; sc[1][i] -= mx; }
        sc[2][0] -= mx; sc[2][1] -= mx;
        attend();
      }
      const uint32_t o0 = pack2(o[0][0], o[0][1]), o1 = pack2(o[1][0], o[1][1]);
      st_async32(oa1, o0, bO + r1); st_async32(oa2, o0, bO + r2);
      st_async32(oa1 + 128, o1, bO + r1); st_async32(oa2 + 128, o1, bO + r2);
      sts32(l4 + CH_O + 1024, o0); sts32(l4 + CH_O + 1152, o1);
      bar_arrive(2, 256);
      pin();
      TM(6);
      mma16h(l, p3, p4, ones, ones);
      float inv;
      asm("rcp.approx.ftz.f32 %0, %1;" : "=f"(inv) : "f"(l[0]));
      sts32((l8 & ~0xffu) + (lane & 28) + CH_VP, __float_as_uint(inv));
      __syncwarp();
      if (elect()) mbar_arrive(bO);
      {
        float z[2][4] = {}, y[2][4] = {};
        mma16(z[0], wd[0], wd[1], wd[2], wd[3], o0, o1);
        if (j == 0) {
#pragma unroll
          for (int u = 0; u < 3; u++) if (!CH_WE) ldsm4t(&we[4 * u], (wo ^ 32) + u * 28672);
          mma16(y[0], we[0], we[1], we[2], we[3], o0, o1);
        }
        const float2 iv = lds64f((l8 & ~0xe0u) + CH_VP);
        uint8_t* dst = pool(pdst[0]);
        const uint32_t mask = ((l16 ^ tag) & 48) == 0;
        const uint32_t oa = qa + ((tag & 0xfffe) + CH_O - CH_QK + t4 * 256 - (t4 == 3 ? 1024 : 0));
        const uint32_t za = l16 + ((tag & 0xfffe) + (t4 >> 1) * 512 + (t4 & 1) * 8);
        pin();
        mbar_wait(bO, s & 1);
        uint32_t a[4];
        ldsm4(a, oa);
        mma16(z[0], wd[4], wd[5], wd[6], wd[7], a[0], a[1]);
        mma16(z[1], wd[8], wd[9], wd[10], wd[11], a[2], a[3]);
        if (j == 0) {
          mma16(y[0], we[4], we[5], we[6], we[7], a[0], a[1]);
          mma16(y[1], we[8], we[9], we[10], we[11], a[2], a[3]);
          sts128f(lw + CH_VT + 512, y[0][0] + y[1][0], y[0][1] + y[1][1], y[0][2] + y[1][2], y[0][3] + y[1][3]);
        }
        sts128f(lw + CH_VT, z[0][0] + z[1][0], z[0][1] + z[1][1], z[0][2] + z[1][2], z[0][3] + z[1][3]);
        bar_sync(3, 128);
        if (j == 0 || t4 < 2) {
          float2 q[4];
#pragma unroll
          for (int i = 0; i < 4; i++) q[i] = lds64f(za + CH_VT + i * 1024);
          stg_strong32(dst, pack_tag(((q[0].x + q[1].x) + (q[2].x + q[3].x)) * iv.x, ((q[0].y + q[1].y) + (q[2].y + q[3].y)) * iv.y, tag, mask));
        }
      }
      TM(2);
      if (!NOX) mbar_wait_hot(bXA, (s + 1) & 1);
      if (CH_KP == 2) bulk_wait_read<0>();
      float dk[16], dw[16];
      bar_sync(5, 256);
      wg_fence();
      pass(dk, ak, Int<0>(), Int<20>());
      pass(dw, av, Int<0>(), Int<20>());
      TM(5);
      pin();
      if (CH_EX == 0) publish_v(s, v, vm);
      if (elect()) {
        mbar_expect(bG + t4 * 8, 2560);
        if (t4 == 1 && s + 2 < NSEG) { mbar_expect(bX, 1536); mbar_expect(bO, 2048); }
      }
      if (CH_KD == 0) { wg_wait<1>(); dump(dk, lw + CH_KT); }
      wg_wait<0>();
      if (CH_KD == 1) dump(dk, lw + CH_KT);
      TM(7);
      dump(dw, lw + CH_VT);
      bar_arrive(9, 256);
      pin();
#pragma unroll
      for (int k = 0; k < CH_RB; k++) ldsm4t(&tw[4 * k], wq + k * 2048);
      if (t4 < 2) {
#pragma unroll
        for (int k = CH_RB; k < CH_RC; k++) ldsm4t(&tw[4 * k], wq + k * 2048);
        const int q = t4 ? 3 : j, o = t4 ? j * 896 : 0;
        const uint8_t* src = p.pool + ((80 + st * 4 + q) * 8192 + (pages >> (st * 4 + q) & 1) * 4096 + o);
        asm volatile("bar.sync 8, 256;" ::: "memory");
        const uint32_t t1 = clk32() + CH_D2;
        if (CH_EX == 1) publish_v(s, v, vm);
        auto fetch = [&](auto n) {
          mbar_wait(bH, s & 1);
          until(t1);
          TR(4, clk32());
          if (elect())
            asm volatile("cp.async.bulk.shared::cluster.global.mbarrier::complete_tx::bytes.multicast::cluster [%0], [%1], %2, [%3], 7;"
                         :: "r"(sb + CH_M + q * 2560 + o), "l"(src), "n"(n.value), "r"(bG + q * 8) : "memory");
        };
        if (!t4) fetch(Int<2560>()); else if (j == 2) fetch(Int<768>()); else fetch(Int<896>());
      } else {
        asm volatile("bar.sync 8, 256; " ::: "memory");
        if (elect()) asm volatile("mbarrier.arrive.relaxed.cluster.shared::cluster.b64 _, [%0];" :: "r"(bH + (t4 == 2 ? r1 : r2)) : "memory");
        pin();
        if (CH_EX == 1) publish_v(s, v, vm);
#pragma unroll
        for (int k = CH_RB; k < CH_RC; k++) ldsm4t(&tw[4 * k], wq + k * 2048);
      }
      TM(9);
      pin();
#pragma unroll
      for (int k = CH_RC; k < CH_TW; k++) ldsm4t(&tw[4 * k], wq + k * 2048);
      if (CH_KP == 2 && t4 == CH_KW) { bar_sync(7, 160); publish_k(s + 1); }
      TM(10);
    }
    if (++st == 3) st = 0;
    tag ^= 0x10001;
  }
  {
    const int s = NSEG - 1;
    float dv[16] = {};
    uint32_t b[40], kf[16];
    project(s, b, dv, kf);
    finish_v(b, dv);
    sum_v(dv);
    if (WG == 0) {
      sts64(l8 + CH_VP, pack2(dv[0], dv[1]), pack2(dv[2], dv[3]));
      bar_sync(1, 256);
      if (CH_KP == 0) publish_k(s);
      publish_km(s);
      bulk_wait<0>();
      fence_async_global();
      bar_sync(2, 256);
      if (tid == 0) red_release(g_sync + 15 * 8 + 4, 1);
    } else {
      const uint4 v[2] = {lds128(lw + CH_VT), lds128(lw + CH_VT + 512)};
      bar_sync(1, 256);
      publish_v(s, v, memory_v(lds64(l8 + CH_VP), dv));
      bulk_wait<0>();
      fence_async_global();
      bar_arrive(2, 256);
    }
  }
}

__global__ void __launch_bounds__(256, 1) chain_kernel(const __grid_constant__ ChainParams p) {
  extern __shared__ __align__(1024) uint8_t smem_raw[];
  const uint32_t sb = s2u(smem_raw);
  const int tid = threadIdx.x, warp = __shfl_sync(~0u, tid >> 5, 0), lane = tid & 31;
  const int cta = blockIdx.x, h = cta / 3, j = cta - 3 * h, colbase = cta * 64;
  const uint32_t bWo = sb + CH_BAR, bWq = bWo + 8, bXA = bWo + 24, bWk = bWo + 80, bWv = bWo + 88;
  uint32_t smid; asm("mov.u32 %0, %%smid;" : "=r"(smid));
  PRO(0);
  if (sb != mapa(CH_BASE, j)) __trap();
  uint32_t entry = 0;
  auto place = [&]() {
    const int i = tid - 128;
    if (i >= 0 && i <= NSLOT) {
      const uint32_t side = ldg_strong32(g_smpart + (smid & 255));
      if (i < NSLOT) {
        entry = i * 8192 + (ldg_strong32(g_orient + i) == (i < 80 ? i & 1 : side) ? 0 : 4096);
      } else {
        entry = 2 * (atomicAdd(g_bo + p.layer * 128 + 1, 1 << 8 * side) >> 8 * side & 255) + side;
      }
    }
    __syncwarp();
  };
  if (p.layer) place();
  if (warp == 0 && elect()) {
#pragma unroll 1
    for (int i = 0; i < 17; i++) mbar_init(bWo + 8 * i, i == 2 || i == 5 ? 5 : i == 3 || i == 4 ? 4 : i == 12 ? 2 : 1);
    asm volatile("fence.mbarrier_init.release.cluster;" ::: "memory");
    mbar_expect(bWk, 81920);
    tma_load3<(WEF & 1) != 0>(sb + CH_WQ, &p.wk, colbase, 0, bWk);
    mbar_expect(bWv, 81920);
    tma_load3<(WEF & 1) != 0>(sb + CH_WO, &p.wv, colbase, 0, bWv);
    mbar_expect(bWo + 16, 1536);
    mbar_expect(bWo + 40, 2048);
    mbar_expect(bWo, 86016); mbar_expect(bWq, 81920);
#pragma unroll 1
    for (int i = 0; i < 8; i++) mbar_expect(bXA + 8 * (i & 1), 5120);
  }
  if (warp == 1) {
    const uint32_t id = (lane >> 3) == (lane & 3) ? ((lane & 4) ? 0x3f800000u : 0x00003f80u) : 0u;
    sts128(sb + CH_ID + lane * 16, make_uint4(id, 0, 0, id));
  }
  __syncthreads();
  asm volatile("barrier.cluster.arrive.relaxed.aligned;" ::: "memory");
  uint32_t ak[80], av[80];
  const uint32_t wq = opaque(sb + CH_WQ + ((warp >> 2) * 320 + (lane & 7) + (lane >> 4) * 8) * 128 + (((2 * (warp & 3) + ((lane >> 3) & 1)) ^ (lane & 7)) << 4));
  pdl_wait();
  if (tid == 32) stg_strong32(g_smuse + (smid & 255), p.layer + 1);
  pdl_launch();
  PRO(1);
  if (warp == 0 && elect()) {
    bulk_load(sb + CH_X + 20480, p.xc + 5120, 20480, bXA);
    bulk_load(sb + CH_X, p.xc, 20480, bXA + 8);
  }
  if (!p.layer) place();
  __syncwarp();
  PRO(2);
  mbar_wait(bWk, 0);
  PRO(3);
#pragma unroll
  for (int k = 0; k < 20; k++) ldsm4t(&ak[4 * k], wq + k * 2048);
  bar_sync(6, 256);
  if (warp == 0 && elect()) tma_load3<(WEF & 2) != 0>(sb + CH_WQ, &p.wq, colbase, 0, bWq);
  __syncwarp();
  PRO(4);
  mbar_wait(bWv, 0);
  PRO(5);
#pragma unroll
  for (int k = 0; k < 20; k++) ldsm4t(&av[4 * k], wq + CH_WO + k * 2048);
  bar_sync(6, 256);
  PRO(6);
  if (warp >= 5 && elect()) tma_load3<(WEF & 2) != 0>(sb + CH_WO + (warp - 5) * 28672, &p.wo, j == 0 ? 0 : 32 + j * 192, h * 192 + (j + 8 - warp) % 3 * 64, bWo);
  if (tid == 128 + NSLOT && entry >= 80) {
    uint32_t c;
    int n = 0;
    do { c = ldg_strong32(g_bo + p.layer * 128 + 1); spin_guard(n); } while ((c & 255) + (c >> 8) < 96);
    const uint32_t other = (c >> 8 * (~entry & 1) & 255) + (entry >> 1) - 40;
    entry = other < 40 ? 2 * other + (~entry & 1) : entry % 80;
  }
  if (tid >= 128 && tid <= 128 + NSLOT) sts32(sb + CH_O + (tid - 128) * 4, entry);
  PRO(7);
  __syncthreads();
  if (__shfl_sync(~0u, tid >> 7, 0) == 0) chain_body<0>(p, wq, ak, av); else chain_body<1>(p, wq, ak, av);
}

struct PostParams { CUtensorMap wq, wo, wb, wo2, wb2; int gap, share, layer, look, gap2, pol; };
constexpr int PS = 8, PB = 28672;
constexpr int OP_SMEM = PS * PB + 512 + 2048;
enum { IT_ATT = 0, IT_OP = 1, IT_FIN = 2, IT_BQ = 3, IT_Q = 4 };

__device__ __forceinline__ uint32_t item_count(int type, int b) {
  return type == IT_ATT ? 32 : type == IT_OP ? op_split(b) * (DM / op_width(b)) : type == IT_FIN ? fin_items(b) : 1920 / bq_width(b); }
__device__ __forceinline__ uint32_t item_need(int type, int b) { return type == IT_ATT ? 96 : item_count(type - 1, b); }

struct Ring {
  uint32_t sb, bars; int st; uint32_t ph;
  __device__ __forceinline__ uint32_t wait() const { mbar_wait(bars + 8 * st, ph); return sb + st * PB; }
  __device__ __forceinline__ void next() { if (++st == PS) { st = 0; ph ^= 1; } }
  __device__ __forceinline__ void release(int s) const { if ((threadIdx.x & 31) == 0) mbar_arrive(bars + 8 * (PS + s)); }
  __device__ __forceinline__ void pop() { __syncwarp(); release(st); next(); }
};

template <int N>
__device__ __forceinline__ void gemm_item(Ring& r, float* d, int nst, uint32_t go, int go_at) {
  int prev = 0;
#pragma unroll 1
  for (int kb = 0; kb < nst; kb++) {
    const uint32_t base = r.wait();
    const uint64_t da = mkdesc(base + (threadIdx.x >> 7) * 4096, 128, 512, 0), db = mkdesc(base + 8192, 4096, 1024, 1);
    wg_fence();
#pragma unroll
    for (int kk = 0; kk < 2; kk++) {
      if (N == 80) wg_ss80_01(d, da + kk * 16, db + kk * 128, (kb | kk) != 0);
      if (N == 160) wg_ss160_01(d, da + kk * 16, db + kk * 128, (kb | kk) != 0);
      if (N >= 192) wg_ss192_01(d, da + kk * 16, db + kk * 128, (kb | kk) != 0);
      if (N == 320) wg_ss128_01(d + 96, da + kk * 16, db + kk * 128 + 3 * 256, (kb | kk) != 0);
    }
    wg_commit();
    if (kb == go_at && threadIdx.x == 0) mbar_arrive(go);
    if (kb > 0) { wg_wait<1>(); r.release(prev); }
    prev = r.st;
    r.next();
  }
  wg_wait<0>();
  reg_fence<N / 2>(d);
  r.release(prev);
}

template <int HALF>
__device__ __forceinline__ void attn_a_warp(Ring& r, const uint32_t (&q)[48], int b, int h) {
  constexpr int NT = HALF ? 5 : 3, NF = 8 * NT;
  const int lane = threadIdx.x & 31, g = lane >> 2, c = lane & 3, seg = (threadIdx.x >> 5) & 3;
  uint32_t f[6][NF];
  int slot[6];
  auto fetch = [&](int u) {
    const uint32_t kv = r.wait() + seg * KV_BYTES;
    slot[u] = r.st;
    r.next();
#pragma unroll
    for (int w = 0; w < 4; w++) {
      uint32_t* d = &f[u][2 * NT * w];
#pragma unroll
      for (int t = 0; t <= HALF; t++) {
        if (u < 3) {
          ldsm4(d + 4 * t, kv + w * 1024 + t * 512 + (lane & 8) * 32 + (lane & 16) * 8 + (lane & 7) * 16);
        } else {
          const uint4 v = lds128(kv + w * 1024 + t * 512 + lane * 16);
          d[4 * t] = v.x; d[4 * t + 1] = v.y; d[4 * t + 2] = v.z; d[4 * t + 3] = v.w;
        }
      }
      const uint2 m = lds64(kv + KV_M + w * 256 + lane * 8);
      d[2 * NT - 2] = m.x; d[2 * NT - 1] = m.y;
    }
    pdl_launch();
  };
  float s[NT][4] = {};
  fetch(0);
#pragma unroll
  for (int u = 0; u < 3; u++) {
    fetch(u + 1);
#pragma unroll
    for (int kk = 0; kk < 4; kk++) {
      const uint32_t* a = &q[16 * u + 4 * kk];
#pragma unroll
      for (int n = 0; n < NT; n++) mma16(s[(n + 1) % NT], a[0], a[1], a[2], a[3], f[u][2 * NT * kk + 2 * n], f[u][2 * NT * kk + 2 * n + 1]);
    }
    r.release(slot[u]);
    pdl_launch();
  }
  fetch(4);
  const float k2 = 0.07216878364870322f * 1.44269504089f, NEG = -INFINITY;
  if (2 * c > g) { s[NT - 2][0] = NEG; s[NT - 1][2] = NEG; }
  if (2 * c + 1 > g) { s[NT - 2][1] = NEG; s[NT - 1][3] = NEG; }
  s[NT - 1][0] = s[NT - 1][1] = NEG;
  uint32_t pp[NT][2]; float inv[2];
#pragma unroll
  for (int hh = 0; hh < 2; hh++) {
    float m = NEG, l = 0.f;
#pragma unroll
    for (int n = 0; n < NT; n++) m = fmaxf(m, fmaxf(s[n][2 * hh], s[n][2 * hh + 1]));
    m = fmaxf(m, __shfl_xor_sync(~0u, m, 1)); m = fmaxf(m, __shfl_xor_sync(~0u, m, 2));
#pragma unroll
    for (int n = 0; n < NT; n++) { const float x = ex2((s[n][2 * hh] - m) * k2), y = ex2((s[n][2 * hh + 1] - m) * k2); l += x + y; pp[n][hh] = pack2(x, y); }
    l += __shfl_xor_sync(~0u, l, 1); l += __shfl_xor_sync(~0u, l, 2);
    asm("rcp.approx.ftz.f32 %0, %1;" : "=f"(inv[hh]) : "f"(l));
  }
  uint32_t* dst = g_o + ((b * 192 + h * 6) * 16 + seg * 4 + HALF * 2) * 128 + lane;
#pragma unroll
  for (int u = 3; u < 6; u++) {
    float o[8][4] = {};
#pragma unroll
    for (int n = 0; n < 8; n++) mma8(o[n], pp[0][0], pp[0][1], f[u][2 * NT * (n >> 1) + 2 * NT - 2 + (n & 1)]);
#pragma unroll
    for (int t = 0; t <= HALF; t++)
#pragma unroll
      for (int n = 0; n < 8; n++) {
        const uint32_t* v = &f[u][2 * NT * (n >> 1) + 4 * t + 2 * (n & 1)];
        mma16(o[n], pp[1 + 2 * t][0], pp[1 + 2 * t][1], pp[2 + 2 * t][0], pp[2 + 2 * t][1], v[0], v[1]);
      }
    r.release(slot[u]);
    if (u == 3) fetch(5);
#pragma unroll
    for (int n = 0; n < 8; n++) {
      dst[(u - 3) * 4096 + (n >> 2) * 2048 + (n & 3) * 32] = pack2(o[n][0] * inv[0], o[n][1] * inv[0]);
      dst[(u - 3) * 4096 + (n >> 2) * 2048 + (n & 3) * 32 + 128] = pack2(o[n][2] * inv[1], o[n][3] * inv[1]);
    }
  }
}

template <int NG>
__device__ __forceinline__ void fin_item(Ring& r, uint32_t scratch, int b, int idx) {
  const int warp = threadIdx.x >> 5, lane = threadIdx.x & 31;
  float4* x = g_x + ((b * 16 + idx * NG) * 40 + warp * 5) * 32 + lane;
  float4 v[NG][5];
#pragma unroll
  for (int g = 0; g < NG; g++) {
    const uint32_t base = r.wait();
#pragma unroll
    for (int i = 0; i < 5; i++) v[g][i] = lds128f(base + ((warp * 5 + i) * 32 + lane) * 16);
    r.pop();
  }
#pragma unroll 1
  for (int k = 0; k < op_split(b); k += NG == 1 ? 2 : 1) {
#pragma unroll
    for (int g = 0; g < NG; g += 2) {
      const uint32_t base = r.wait();
#pragma unroll
      for (int i = 0; i < 10; i++) {
        const uint2 q = lds64(base + ((i / 5 * 40 + warp * 5 + i % 5) * 32 + lane) * 8);
        float4& t = v[(g + i / 5) % NG][i % 5];
        t.x += bf_lo(q.x); t.y += bf_hi(q.x); t.z += bf_lo(q.y); t.w += bf_hi(q.y);
      }
      r.pop();
    }
  }
  float mean[NG], rs[NG];
  ln_stats<NG>(v, scratch, mean, rs);
#pragma unroll
  for (int i = 0; i < 5; i++) {
    const int u = warp * 5 + i;
    uint32_t* xn = g_xn + ((b * 20 + (u >> 1)) * 16 + idx * NG) * 128 + (u & 1) * 64 + lane;
#pragma unroll
    for (int g = 0; g < NG; g++) {
      xn[g * 128] = pack2((v[g][i].x - mean[g]) * rs[g], (v[g][i].y - mean[g]) * rs[g]);
      xn[g * 128 + 32] = pack2((v[g][i].z - mean[g]) * rs[g], (v[g][i].w - mean[g]) * rs[g]);
    }
  }
#pragma unroll
  for (int g = 0; g < NG; g++)
#pragma unroll
    for (int i = 0; i < 5; i++) x[(g * 40 + i) * 32] = v[g][i];
}

__global__ void __launch_bounds__(384, 1) post_kernel(const __grid_constant__ PostParams p) {
  extern __shared__ __align__(1024) uint8_t smem_raw[];
  const uint32_t sb = s2u(smem_raw), bars = sb + PS * PB;
  const uint32_t bIF = bars + 128, bIE = bars + 160, done = bars + 192, bGo = bars + 224, slots = bars + 240, scratch = bars + 512;
  const int warp = __shfl_sync(~0u, threadIdx.x >> 5, 0), lane = threadIdx.x & 31;
  TRACE(0);
  pdl_launch();
  if (sb & 1023) __trap();
  if (threadIdx.x < 29) mbar_init(bars + 8 * threadIdx.x, threadIdx.x < 8 ? 1 : threadIdx.x < 16 ? 8 : threadIdx.x < 20 ? 1 : threadIdx.x < 24 ? 2 : threadIdx.x < 28 ? 8 : 1);
  if (threadIdx.x == 32) sts32(slots + 16, p.gap);
  fence_async();
  __syncthreads();
  if (warp >= 8) {
    asm volatile("setmaxnreg.dec.sync.aligned.u32 56;");
    if (warp == 9) {
      const int b = lane & 15;
      bool queries = QA_END < 16 && blockIdx.x < 36;
      for (int n = 0;; n++) {
        if (n > 0) mbar_wait(bGo, (n - 1) & 1);
        mbar_wait(bIE + 8 * (n & 3), ((n >> 2) & 1) ^ 1);
        int code = -1, spin = 0, ticket = 0;
        if (queries) {
          if (lane == 0) ticket = atomicAdd(g_sync + SY_QC, 1);
          ticket = __shfl_sync(~0u, ticket, 0);
          queries = ticket < (16 - QA_END) * 32;
          if (queries) code = IT_Q << 16 | (QA_END + ticket % (16 - QA_END)) << 8 | ticket / (16 - QA_END);
        }
        if (!queries && lane == 0) ticket = atomicAdd(g_sync + SY_T, 1);
        while (!queries) {
          const uint4 hd = ldg_strong128(g_sync + b * 8), pr = ldg_strong128(g_sync + b * 8 + 4);
          const uint32_t hv[4] = {hd.x, hd.y, hd.z, hd.w}, pv[4] = {pr.x, pr.y, pr.z, pr.w};
          const uint32_t chain_done = __ballot_sync(~0u, (pr.x & 0xffff) >= 96) & 0xffff;
          int left[4], avail[4], rdy = 0, claimed = 0, upstream = 0;
#pragma unroll
          for (int t = 0; t < 4; t++) {
            const int cnt = lane < 16 ? item_count(t, b) : 0;
            left[t] = max(cnt - (int)hv[t], 0);
            claimed += cnt - left[t];
            const bool ready = (pv[t] & 0xffff) >= item_need(t, b);
            rdy |= ready << t;
            bool ok = ready || (t == IT_ATT ? pr.x >= 0x10000 : !upstream || (t == IT_OP && (chain_done >> 15 & 1)));
            if (t == IT_BQ && (chain_done >> BQ_HOLD & 1) && !(chain_done >> 15)) ok = false;
            avail[t] = ok ? left[t] : 0;
            upstream |= __any_sync(~0u, left[t] > 0);
          }
          if (!upstream) break;
          int rank = max(__shfl_sync(~0u, ticket, 0) - __reduce_add_sync(~0u, claimed), 0), type = -1, mine = 0;
#pragma unroll
          for (int c = 0; c < 8; c++) {
            const int t = c == 0 || c == 5 ? IT_FIN : c == 1 || c == 7 ? IT_ATT : c == 2 || c == 4 ? IT_OP : IT_BQ;
            int a = c == 1 || ((rdy >> t & 1) == (c < 4)) ? avail[t] : 0;
            if (t == IT_OP && !(p.pol & 1)) a = c == 2 ? avail[t] : 0;
            if (c == 7) a = b < QA_END && !(rdy & 1) && ((chain_done << 1 | 1) >> b & 1) ? left[t] : 0;
            const int tot = __reduce_add_sync(~0u, a);
            if (type < 0) { if (rank < tot) { type = t; mine = a; } else rank -= tot; }
          }
          if (type >= 0) {
#pragma unroll
            for (int o = 1; o < 16; o <<= 1) { const int y = __shfl_up_sync(~0u, mine, o); if (lane >= o) mine += y; }
            const int blk = __ffs(__ballot_sync(~0u, mine > rank)) - 1;
            const int early = !(__shfl_sync(~0u, rdy, blk) >> type & 1);
            uint32_t idx = 0;
            if (lane == 0) { idx = atomicAdd(g_sync + blk * 8 + type, 1); ld_acquire(g_sync + blk * 8 + 4 + type); }
            idx = __shfl_sync(~0u, idx, 0);
            if (idx < item_count(type, blk)) { code = (chain_done >> 15 & 1) << 22 | (chain_done >> p.look & 1) << 21 | early << 20 | type << 16 | blk << 8 | idx; break; }
          } else {
            __nanosleep(50);
          }
          spin_guard(spin);
        }
        if (lane == 0) {
          fence_async_global();
          sts32(slots + 4 * (n & 3), code);
          mbar_arrive(bIF + 8 * (n & 3));
        }
        __syncwarp();
        if (code < 0) break;
      }
    } else if (warp == 8) {
      if (elect()) {
        uint32_t dst = sb, bar = bars, ph = 1, next = clk32(), gap = 0;
        auto acquire = [&](uint32_t kb) {
          mbar_wait(bar + 8 * PS, ph);
          mbar_expect(bar, kb * 1024);
          if (gap) {
            uint32_t now;
            do now = clk32(); while ((int)(now - next) < 0);
            next = ((int)(now - next) > 100 ? now - 100 : next) + kb * gap;
          }
        };
        auto advance = [&]() { dst += PB; bar += 8; if (dst == bars) { dst = sb; bar = bars; ph ^= 1; } };
        auto depend = [&](const uint32_t* c, uint32_t need) { wait_count(c, need); fence_async_global(); };
#pragma unroll 1
        for (int n = 0;; n++) {
          mbar_wait(bIF + 8 * (n & 3), (n >> 2) & 1);
          const int code = (int)lds32(slots + 4 * (n & 3));
          if (code < 0) break;
          const int type = (code >> 16) & 15, b = (code >> 8) & 255, idx = code & 255;
          const bool early = code >> 20 & 1, go = !(code >> 21 & 1);
          mbar_arrive(bIE + 8 * (n & 3));
          gap = !(code >> 22 & 1) ? lds32(slots + 16) : type == IT_ATT || type == IT_FIN ? 0 : p.gap2;
          const uint32_t* progress = g_sync + b * 8 + 4 + type;
          if (type == IT_ATT && b >= QA_END) {
            depend(g_sync + SY_Q, (16 - QA_END) * 32);
#pragma unroll 1
            for (int u = 0; u < 2; u++) { acquire(24); bulk_load_last(dst, g_q + (((b - QA_END) * 32 + idx) * 2 + u) * 1536, 24576, bar); advance(); }
          } else if (type == IT_FIN) {
            const int ng = 16 / fin_items(b), lg = ng >> 1;
#pragma unroll 1
            for (int g = 0; g < ng; g++) { acquire(20); bulk_load(dst, g_x + (b * 16 + idx * ng + g) * 1280, 20480, bar); advance(); }
            if (early) depend(progress, item_need(type, b));
            if (go) mbar_arrive(bGo);
#pragma unroll 1
            for (int i = 0; i < op_split(b) * ng; i += 2) {
              const uint2* src = g_part + ((b * 16 + (i >> lg)) * 16 + idx * ng + (i & (ng - 1))) * 1280;
              acquire(20);
              bulk_load_last(dst, src, ng > 1 ? 20480 : 10240, bar);
              if (ng == 1) bulk_load_last(dst + 10240, src + 16 * 1280, 10240, bar);
              advance();
            }
          } else {
            const bool op = type == IT_OP, bq = type == IT_BQ;
            const int width = op ? op_width(b) : bq ? bq_width(b) : 192, nb = (width + 63) >> 6, lt = width == 320 ? 1 : 2;
            const int nst = op ? 192 / op_split(b) : 20, kb0 = op ? (idx >> lt) * nst : 0;
            const int col = (op ? idx & ((1 << lt) - 1) : idx) * width;
            const bool whole = !(width & 63);
            const CUtensorMap* m = op ? (whole ? &p.wo : &p.wo2) : bq ? (whole ? &p.wb : &p.wb2) : &p.wq;
            const uint32_t* a = op ? g_o + (b * 192 + kb0) * 2048 : g_xn + b * 20 * 2048;
            int row = kb0 * 32, pre = early && (op || bq) ? min(nst, PS) : 0;
            auto weights = [&]() {
              acquire(8 + nb * 4);
              if (whole) {
                tma_load3z(dst + 8192, m, row, col >> 6, bar);
              } else {
                tma_load(dst + 8192, m, col, row, bar); tma_load(dst + 12288, m, col + 64, row, bar);
                if (nb == 3) tma_load(dst + 16384, m, col + 128, row, bar);
              }
              row += 32;
            };
            if (pre) {
              uint32_t da = dst, ba = bar;
#pragma unroll 1
              for (int kb = 0; kb < pre; kb++) { weights(); advance(); }
              depend(progress, item_need(type, b));
#pragma unroll 1
              for (int kb = 0; kb < pre; kb++) {
                bulk_load(da, a, 8192, ba);
                a += 2048; da += PB; ba += 8;
                if (da == bars) { da = sb; ba = bars; }
              }
            }
#pragma unroll 1
            for (int kb = pre; kb < nst; kb++) { weights(); if (op && OEF) bulk_load_last(dst, a, 8192, bar); else bulk_load(dst, a, 8192, bar); a += 2048; advance(); }
          }
          if (type == IT_ATT) {
            if (early) depend(progress, 96);
            if (go) mbar_arrive(bGo);
            const uint8_t* src = g_kv + (size_t)(idx * 6 * NSEG + b * 4) * KV_BYTES;
#pragma unroll 1
            for (int u = 0; u < 6; u++) {
              acquire(20);
              bulk_load_last(dst, src, 20480, bar);
              src += u == 2 ? -3 * KV_V : 2 * KV_V;
              advance();
            }
          }
        }
      }
    } else if (warp == 11) {
      uint32_t smid, nsm, used = 0;
      asm("mov.u32 %0, %%smid;" : "=r"(smid)); asm("mov.u32 %0, %%nsmid;" : "=r"(nsm));
      for (int n = 0; n < 64 && used < 96; n++) {
        uint32_t peers = 0;
        used = 0;
        for (uint32_t i = lane; i < min(nsm, 256u); i += 32) {
          const bool taken = ldg_strong32(g_smuse + i) == p.layer + 1;
          used += taken;
          peers += abs((int)(g_smclk[i] - g_smclk[smid & 255])) < 4000 && !taken;
        }
        used = __reduce_add_sync(~0u, used);
        sts32(slots + 16, max(p.gap, (int)min(__reduce_add_sync(~0u, peers), 18u) * p.share >> 3));
      }
    } else if (warp == 10 && lane == 0) {
      for (int n = 0;; n++) {
        mbar_wait(bIF + 8 * (n & 3), (n >> 2) & 1);
        const int code = (int)lds32(slots + 4 * (n & 3));
        if (code < 0) break;
        const int type = (code >> 16) & 15, b = (code >> 8) & 255;
        mbar_wait(done + 8 * (n & 3), (n >> 2) & 1);
        if (type != IT_BQ) red_release(type == IT_Q ? g_sync + SY_Q : g_sync + b * 8 + 5 + type, 1);
        mbar_arrive(bIE + 8 * (n & 3));
      }
    }
  } else {
    asm volatile("setmaxnreg.inc.sync.aligned.u32 224;");
    const int g = lane >> 2, c = lane & 3;
    Ring r = {sb, bars, 0, 0};
#pragma unroll 1
    for (int n = 0;; n++) {
      mbar_wait(bIF + 8 * (n & 3), (n >> 2) & 1);
      const int code = __shfl_sync(~0u, (int)lds32(slots + 4 * (n & 3)), 0);
      if (code < 0) { TRACE(2); break; }
      const int type = (code >> 16) & 15, b = (code >> 8) & 255, idx = code & 255;
      ITEM(code & 0xfffff, 0);
      if (type == IT_ATT || type == IT_Q) {
        uint32_t q[48];
        if (type == IT_Q || b < QA_END) {
          float d[96] = {};
          reg_fence<96>(d);
          gemm_item<192>(r, d, 20, bGo, type == IT_Q ? 12 : -1);
#pragma unroll
          for (int i = 0; i < 48; i++) q[i] = pack2(d[2 * i], d[2 * i + 1]);
        } else {
#pragma unroll
          for (int u = 0; u < 2; u++) {
            const uint32_t base = r.wait() + threadIdx.x * 16;
#pragma unroll
            for (int i = 0; i < 6; i++) {
              const uint4 v = lds128(base + i * 4096);
              q[24 * u + 4 * i] = v.x; q[24 * u + 4 * i + 1] = v.y; q[24 * u + 4 * i + 2] = v.z; q[24 * u + 4 * i + 3] = v.w;
            }
            r.pop();
          }
        }
        if (type == IT_Q) {
          uint4* dst = g_q + ((b - QA_END) * 32 + idx) * 3072 + threadIdx.x;
#pragma unroll
          for (int i = 0; i < 12; i++) dst[i * 256] = make_uint4(q[4 * i], q[4 * i + 1], q[4 * i + 2], q[4 * i + 3]);
        } else if (warp < 4) {
          attn_a_warp<0>(r, q, b, idx);
        } else {
          attn_a_warp<1>(r, q, b, idx);
        }
      } else if (type == IT_FIN) {
        if (fin_items(b) == 4) fin_item<4>(r, scratch, b, idx);
        else if (fin_items(b) == 8) fin_item<2>(r, scratch, b, idx);
        else fin_item<1>(r, scratch, b, idx);
      } else {
        float d[160] = {};
        reg_fence<160>(d);
        const int width = type == IT_OP ? op_width(b) : bq_width(b), nst = type == IT_OP ? 192 / op_split(b) : 20;
        const int go_at = code >> 21 & 1 ? -1 : max(nst - 6, 0);
        if (width == 320) gemm_item<320>(r, d, nst, bGo, go_at);
        else if (width == 160 || BQ_80 == 16) gemm_item<160>(r, d, nst, bGo, go_at);
        else gemm_item<80>(r, d, nst, bGo, go_at);
        reg_fence<160>(d);
        if (type == IT_OP) {
          const int tiles = DM / width;
          uint2* dst = g_part + (((b * 16 + idx / tiles) * 16 + warp * 2) * 40 + idx % tiles * (width / 16)) * 32 + lane;
#pragma unroll
          for (int u = 0; u < 20; u++) {
            if (u % 5 == 0 && u * 16 >= width) break;
            dst[u * 32] = make_uint2(pack2(d[8 * u], d[8 * u + 1]), pack2(d[8 * u + 4], d[8 * u + 5]));
            dst[(40 + u) * 32] = make_uint2(pack2(d[8 * u + 2], d[8 * u + 3]), pack2(d[8 * u + 6], d[8 * u + 7]));
          }
        } else {
          const int row = b * 128 + warp * 16 + g;
          const int h0 = idx * (width / 20);
          const float sc = h0 < 32 ? 0.22360679775f * 1.44269504089f : 1.f;
          const bool lo = c < 2;
          uint32_t* da = g_bqkv + (h0 * 256 + (row >> 3)) * 96 + lane;
          uint32_t* db = da + 256 * 96 + (lo ? 2 : -2);
          uint32_t pad[2];
#pragma unroll
          for (int rr = 0; rr < 2; rr++) pad[rr] = !(c & 1) && (h0 >= 64 || (h0 >= 32 && (row & 1) && poly_group((row >> 3) + rr))) ? 0x00003f80u : 0u;
#pragma unroll
          for (int q = 0; q < 8; q++) {
            if (!(q & 1) && q * 40 >= width) break;
#pragma unroll
            for (int rr = 0; rr < 2; rr++) {
              uint32_t w[5];
#pragma unroll
              for (int i = 0; i < 5; i++) w[i] = pack2(d[20 * q + 4 * i + 2 * rr] * sc, d[20 * q + 4 * i + 2 * rr + 1] * sc);
              const int o = q * 2 * 256 * 96 + rr * 96;
              da[o] = w[0]; da[o + 32] = w[1]; da[o + 64] = lo ? w[2] : pad[rr];
              db[o] = lo ? w[3] : w[2]; db[o + 32] = lo ? w[4] : w[3]; db[o + 64] = lo ? pad[rr] : w[4];
            }
          }
        }
      }
      __syncwarp();
      if (lane == 0) mbar_arrive(done + 8 * (n & 3));
      if ((code >> 21 & 1) && threadIdx.x == 128) mbar_arrive(bGo);
      ITEM(code & 0xfffff, 1);
    }
  }
}

constexpr int AB_SMEM = 1024 + 98304 + 51200 + 4 * 16384 + 256;
#define AB_N 32
#define AB_WG 4
constexpr int AB_T = AB_WG * 128, AB_PASS = 8 / AB_WG;
__device__ __forceinline__ float ex2_poly(float t) {
  const uint32_t r = __float_as_uint(t) & 0xffff8000u;
  const float f = t - __uint_as_float(r);
  const float p = fmaf(fmaf(fmaf(-5.869912678e-38f, f, -1.700740250e-37f), f, -5.234869734e-37f), f, -7.522601252e-37f);
  uint32_t y;
  asm("mad.lo.u32 %0, %1, 256, %2;" : "=r"(y) : "r"(r), "r"(__float_as_uint(p)));
  return __uint_as_float(y);
}
__device__ __forceinline__ float sq2(uint32_t w) { const float a = bf_lo(w), b = bf_hi(w); return fmaf(a, a, b * b); }

__device__ __forceinline__ void attn_b_store(const float* o, int h, int row0, int lane) {
  const int g = lane >> 2, c = lane & 3;
  const float i0 = 1.f / __shfl_sync(~0u, o[8], (lane & ~3) | 2), i1 = 1.f / __shfl_sync(~0u, o[10], (lane & ~3) | 2);
#pragma unroll
  for (int jj = 0; jj < 3; jj++) {
    if (jj < 2 || c < 2) {
      const int col = h * 20 + 8 * jj + 2 * c;
      uint32_t* dst = g_of + (((row0 >> 7) * 10 + (col >> 6)) * 16 + (row0 >> 3 & 15)) * 256 + (col >> 3 & 7) * 32 + g * 4 + (col >> 1 & 3);
      dst[0] = pack2(o[4 * jj] * i0, o[4 * jj + 1] * i0);
      dst[256] = pack2(o[4 * jj + 2] * i1, o[4 * jj + 3] * i1);
    }
  }
}

__device__ __forceinline__ void attn_b_qk(float* s, uint32_t q0, uint32_t q1, uint32_t q2, uint32_t q3, uint32_t q4, uint32_t q5, uint32_t z0, uint32_t z1,
                                          uint64_t dk, uint64_t dk2) {
  wg_rs32_00(s, q0, q1, q2, q3, dk, 0);
  wg_rs32_00(s, q4, q5, z0, z1, dk2, 1);
}

struct AbParams { Weights next; uint32_t* done; uint32_t* out; };
__global__ void __launch_bounds__(AB_T + 32, 1) attn_b_kernel(const __grid_constant__ AbParams p) {
  extern __shared__ uint8_t smem_raw[];
  const uint32_t sb = (s2u(smem_raw) + 1023) & ~1023u, sK = sb, sV = sb + 98304, bars = sV + 51200 + 4 * 16384;
  const uint32_t bF = bars + 64, bW = bars + 72, bA = bars + 80, bE = bars + 128, smax = bars + 176;
  auto ring = [&](int i) { return i < 2 ? sK + 51200 + i * 16384 : sV + 51200 + (i - 2) * 16384; };
  const int warp = __shfl_sync(~0u, threadIdx.x >> 5, 0), lane = threadIdx.x & 31;
  const int h = blockIdx.x >> 2, quarter = blockIdx.x & 3;
  TRACE(0);
  pdl_launch();
  pdl_wait();
  if (blockIdx.x < NSLOT) for (int i = threadIdx.x; i < 512; i += AB_T + 32) reinterpret_cast<uint4*>(pool_at(blockIdx.x * 8192))[i] = make_uint4(0, 0, 0, 0);
  if (blockIdx.x == 31) for (int i = threadIdx.x; i < SY_N; i += AB_T + 32) g_sync[i] = 0;
  if (threadIdx.x == 0) {
    for (int i = 0; i < 22; i++) mbar_init(bars + 8 * i, i == 8 ? AB_T / 32 : i >= 16 ? 8 : 1);
    sts64(smax, 0, 0);
    fence_async();
    const uint8_t* gk = reinterpret_cast<const uint8_t*>(g_bqkv + (32 + h) * 256 * 96);
    const uint8_t* gv = reinterpret_cast<const uint8_t*>(g_bqkv + (64 + h) * 256 * 96);
    for (int i = 0; i < 8; i++) {
      mbar_expect(bars + 8 * i, 24576);
      bulk_load_last(sK + i * 12288, gk + i * 12288, 12288, bars + 8 * i);
      bulk_load_last(sV + i * 12288, gv + i * 12288, 12288, bars + 8 * i);
    }
  }
  __syncthreads();
  const int blk = quarter * 4 + (h >> 3), cg = h & 7;
  auto unsafe = [&]() { const float2 m = lds64f(smax); return !(m.x * m.y <= 10000.f); };
  if (warp == AB_T / 32) {
    auto load_w = [&]() {
      mbar_expect(bW, 102400);
      for (int i = 0; i < 4; i++) bulk_load((i < 2 ? sK : sV) + (i & 1) * 25600, g_wb + cg * 6400 + i * 1600, 25600, bW);
    };
    if (p.next.w[0] && lane == 0) {
      mbar_wait(bars + 56, 0);
      for (int i = 0; i < AB_PF; i++) { const uint32_t t0 = clk32(); while (clk32() - t0 < (i ? AB_PFD : AB_PF0)) __nanosleep(200); prefetch_weights(p.next, i); }
    }
    __syncwarp();
    mbar_wait(bF, 0);
    const bool redo = unsafe();
    if (!redo && lane == 0) load_w();
    __syncwarp();
    bar_sync(1, AB_T + 32);
    if (lane == 0) {
      ABT(!!p.out, 1);
      red_release(p.done + quarter * 32, 1);
      ABT(!!p.out, 2);
      if (redo) load_w();
      wait_count(p.done + quarter * 32, 32);
      fence_async_global();
      ABT(!!p.out, 3);
      for (int kb = 0; kb < 10; kb++) {
        const int i = kb < 6 ? kb : kb - 6;
        if (kb >= 6) mbar_wait(bE + 8 * i, 0);
        mbar_expect(bA + 8 * i, 16384);
        bulk_load(ring(i), g_of + (blk * 10 + kb) * 4096, 16384, bA + 8 * i);
      }
    }
    return;
  }
  float qmax = 0.f;
  constexpr int NT = SEQ / AB_N, PER = 256 / AB_N;
#pragma unroll 1
  for (int pass = 0; pass < AB_PASS; pass++) {
    const int row0 = quarter * 512 + ((warp >> 2) * AB_PASS + pass) * 64 + (warp & 3) * 16;
    const uint32_t* gq = g_bqkv + (h * 256 + (row0 >> 3)) * 96 + lane;
    const uint32_t q0 = gq[0], q1 = gq[96], q2 = gq[32], q3 = gq[128];
    uint32_t q4 = gq[64], q5 = gq[160];
    const uint32_t z0 = gq[64 + 3 - (lane & 3)], z1 = gq[160 + 3 - (lane & 3)];
    {
      float n0 = sq2(q0) + sq2(q2) + sq2(q4), n1 = sq2(q1) + sq2(q3) + sq2(q5);
      n0 += __shfl_xor_sync(~0u, n0, 1); n1 += __shfl_xor_sync(~0u, n1, 1);
      n0 += __shfl_xor_sync(~0u, n0, 2); n1 += __shfl_xor_sync(~0u, n1, 2);
      qmax = (n0 > qmax || n0 != n0) ? n0 : qmax;
      qmax = (n1 > qmax || n1 != n1) ? n1 : qmax;
    }
    if (pass == AB_PASS - 1) {
      float kmax = 0.f;
#pragma unroll
      for (int i = 0; i < SEQ / AB_T; i++) {
        const int key = threadIdx.x + AB_T * i;
        const uint32_t a = sK + (key >> 3) * 384 + (key & 7) * 16;
        const uint4 x = lds128(a), y = lds128(a + 128);
        const uint2 z = lds64(a + 256);
        const float n = ((sq2(x.x) + sq2(x.y)) + (sq2(x.z) + sq2(x.w))) + ((sq2(y.x) + sq2(y.y)) + (sq2(y.z) + sq2(y.w))) + (sq2(z.x) + sq2(z.y));
        kmax = (n > kmax || n != n) ? n : kmax;
      }
      const uint32_t kb = __reduce_max_sync(~0u, __float_as_uint(kmax) & 0x7fffffffu), qb = __reduce_max_sync(~0u, __float_as_uint(qmax) & 0x7fffffffu);
      if (lane < 2) asm volatile("red.shared.max.u32 [%0], %1;" :: "r"(smax + 4 * lane), "r"(lane ? kb : qb) : "memory");
      __syncwarp();
    }
    if ((lane & 3) == 2) { q4 = 0x43BCu; q5 = 0x43BCu; }
    float o[12];
    uint64_t dk = mkdesc(sK, 128, 384, 0), dk2 = mkdesc(sK + 256, 0, 384, 0), dv = mkdesc(sV, 384, 128, 0);
    float sa[AB_N / 2], sb2[AB_N / 2];
    uint32_t pa[AB_N / 4], pb[AB_N / 4];
    if (pass == 0) mbar_wait(bars, 0);
    wg_fence();
    attn_b_qk(sa, q0, q1, q2, q3, q4, q5, z0, z1, dk, dk2);
    wg_commit();
    attn_b_qk(sb2, q0, q1, q2, q3, q4, q5, z0, z1, dk + AB_N * 3, dk2 + AB_N * 3);
    wg_commit();
#pragma unroll 1
    for (int kt = 0; kt < NT; kt += 2) {
      const int nx = kt + 2 < NT ? kt + 2 : 0;
      if (pass == 0 && (nx & (PER - 1)) == 0) mbar_wait(bars + 8 * (nx / PER), 0);
      const uint64_t nk = dk + nx * (AB_N * 3), nk2 = dk2 + nx * (AB_N * 3);
      wg_wait<1>();
      if (pass == AB_PASS - 1 && kt == NT * 5 / 8 + 2 && lane == 0) mbar_arrive(bF);
      reg_fence<AB_N / 2>(sa);
#pragma unroll
      for (int i = 0; i < AB_N / 4; i++) pa[i] = pack2(ex2(sa[2 * i]), poly_group(i >> 1) ? ex2_poly(sa[2 * i + 1]) : ex2(sa[2 * i + 1]));
      wg_fence();
#pragma unroll
      for (int kk = 0; kk < AB_N / 16; kk++) wg_rs24_01(o, pa[4 * kk], pa[4 * kk + 1], pa[4 * kk + 2], pa[4 * kk + 3], dv + kk * 48, kk | kt);
      attn_b_qk(sa, q0, q1, q2, q3, q4, q5, z0, z1, nk, nk2);
      wg_commit();
      wg_wait<1>();
      reg_fence<AB_N / 2>(sb2);
#pragma unroll
      for (int i = 0; i < AB_N / 4; i++) pb[i] = pack2(ex2(sb2[2 * i]), poly_group((i >> 1) + AB_N / 8) ? ex2_poly(sb2[2 * i + 1]) : ex2(sb2[2 * i + 1]));
      wg_fence();
#pragma unroll
      for (int kk = 0; kk < AB_N / 16; kk++) wg_rs24_01(o, pb[4 * kk], pb[4 * kk + 1], pb[4 * kk + 2], pb[4 * kk + 3], dv + AB_N * 3 + kk * 48, 1);
      attn_b_qk(sb2, q0, q1, q2, q3, q4, q5, z0, z1, nk + AB_N * 3, nk2 + AB_N * 3);
      wg_commit();
      dv += AB_N * 6;
    }
    wg_wait<0>();
    reg_fence<12>(o); reg_fence<AB_N / 2>(sa); reg_fence<AB_N / 2>(sb2);
    attn_b_store(o, h, row0, lane);
  }
  mbar_wait(bF, 0);
  if (unsafe())
#pragma unroll 1
  for (int pass = 0; pass < AB_PASS; pass++) {
    const int row0 = quarter * 512 + ((warp >> 2) * AB_PASS + pass) * 64 + (warp & 3) * 16;
    const uint32_t* gq = g_bqkv + (h * 256 + (row0 >> 3)) * 96 + lane;
    const uint32_t q0 = gq[0], q1 = gq[96], q2 = gq[32], q3 = gq[128], q4 = gq[64], q5 = gq[160];
    float o[12];
#pragma unroll
    for (int i = 0; i < 12; i++) o[i] = 0.f;
    float m0 = -INFINITY, m1 = -INFINITY;
#pragma unroll 1
    for (int kt = 0; kt < 32; kt++) {
      float s[32];
      const uint64_t dk = mkdesc(sK + kt * 3072, 128, 384, 0), dk2 = mkdesc(sK + kt * 3072 + 256, 0, 384, 0);
      wg_fence();
      wg_rs64_00(s, q0, q1, q2, q3, dk, 0);
      wg_rs64_00(s, q4, q5, 0, 0, dk2, 1);
      wg_commit();
      wg_wait<0>();
      reg_fence<32>(s); reg_fence<12>(o);
      float n0 = m0, n1 = m1;
#pragma unroll
      for (int jj = 0; jj < 8; jj++) { n0 = fmaxf(n0, fmaxf(s[4 * jj], s[4 * jj + 1])); n1 = fmaxf(n1, fmaxf(s[4 * jj + 2], s[4 * jj + 3])); }
      n0 = fmaxf(n0, __shfl_xor_sync(~0u, n0, 1)); n0 = fmaxf(n0, __shfl_xor_sync(~0u, n0, 2));
      n1 = fmaxf(n1, __shfl_xor_sync(~0u, n1, 1)); n1 = fmaxf(n1, __shfl_xor_sync(~0u, n1, 2));
      const float r0 = ex2(m0 - n0), r1 = ex2(m1 - n1);
      m0 = n0; m1 = n1;
#pragma unroll
      for (int jj = 0; jj < 3; jj++) { o[4 * jj] *= r0; o[4 * jj + 1] *= r0; o[4 * jj + 2] *= r1; o[4 * jj + 3] *= r1; }
      uint32_t pp[16];
#pragma unroll
      for (int jj = 0; jj < 8; jj++) {
        pp[2 * jj] = pack2(ex2(s[4 * jj] - m0), ex2(s[4 * jj + 1] - m0));
        pp[2 * jj + 1] = pack2(ex2(s[4 * jj + 2] - m1), ex2(s[4 * jj + 3] - m1));
      }
      const uint64_t dv = mkdesc(sV + kt * 3072, 384, 128, 0);
      wg_fence();
#pragma unroll
      for (int kk = 0; kk < 4; kk++) wg_rs24_01(o, pp[4 * kk], pp[4 * kk + 1], pp[4 * kk + 2], pp[4 * kk + 3], dv + kk * 48, 1);
      wg_commit();
    }
    wg_wait<0>();
    reg_fence<12>(o);
    attn_b_store(o, h, row0, lane);
  }
  ABT(!!p.out, 0);
  bar_arrive(1, AB_T + 32);
  if (warp >= 8) return;
  const int g = lane >> 2, c = lane & 3;
  float d[40];
  float4* x = g_x + ((blk * 16 + warp * 2) * 40 + cg * 5) * 32 + lane;
#pragma unroll
  for (int i = 0; i < 10; i++) {
    const int r = i / 5, u = i % 5;
    const float4 t = x[(r * 40 + u) * 32];
    d[8 * u + 2 * r] = t.x; d[8 * u + 2 * r + 1] = t.y; d[8 * u + 4 + 2 * r] = t.z; d[8 * u + 5 + 2 * r] = t.w;
  }
  mbar_wait(bW, 0);
  reg_fence<40>(d);
  ABT(!!p.out, 4);
#pragma unroll 1
  for (int kb = 0; kb < 10; kb++) {
    const int i = kb < 6 ? kb : kb - 6;
    mbar_wait(bA + 8 * i, kb >= 6);
    const uint64_t da = mkdesc(ring(i) + (warp >> 2) * 8192, 128, 1024, 0), db = mkdesc(kb < 5 ? sK + kb * 10240 : sV + (kb - 5) * 10240, 1280, 128, 0);
    wg_fence();
#pragma unroll
    for (int kk = 0; kk < 4; kk++) wg_ss80_01(d, da + kk * 16, db + kk * 160, 1);
    wg_commit();
    if (kb > 0 && kb < 5) { wg_wait<1>(); if (lane == 0) mbar_arrive(bE + 8 * (kb - 1)); }
  }
  wg_wait<0>();
  reg_fence<40>(d);
  ABT(!!p.out, 5);
  if (p.out) {
    uint32_t* out = p.out + (blk * 128 + warp * 16 + g) * (DM / 2) + cg * 40 + c;
#pragma unroll
    for (int i = 0; i < 20; i++) out[(i & 1) * 8 * (DM / 2) + (i >> 1) * 4] = pack2(d[2 * i], d[2 * i + 1]);
  } else {
    float2* stat = g_stat + blk * 1024 + warp * 16 + g;
    float mean[2], rs[2];
#pragma unroll
    for (int r = 0; r < 2; r++) {
      float t = 0.f, q = 0.f;
#pragma unroll
      for (int i = 0; i < 10; i++) t += d[4 * i + 2 * r] + d[4 * i + 2 * r + 1];
      t += __shfl_xor_sync(~0u, t, 1); t += __shfl_xor_sync(~0u, t, 2);
      t *= 1.f / 80;
#pragma unroll
      for (int i = 0; i < 10; i++) { const float a = d[4 * i + 2 * r] - t, b = d[4 * i + 2 * r + 1] - t; q += a * a + b * b; }
      q += __shfl_xor_sync(~0u, q, 1); q += __shfl_xor_sync(~0u, q, 2);
      if (c == r) asm volatile("st.relaxed.gpu.global.v2.b32 [%0], {%1, %2};" :: "l"(stat + cg * 128 + r * 8), "r"(__float_as_uint(t)), "r"(nz(__float_as_uint(q))) : "memory");
    }
#pragma unroll
    for (int i = 0; i < 10; i++) {
      const int r = i / 5, u = i % 5;
      x[(r * 40 + u) * 32] = make_float4(d[8 * u + 2 * r], d[8 * u + 2 * r + 1], d[8 * u + 4 + 2 * r], d[8 * u + 5 + 2 * r]);
    }
    ABT(0, 6);
    uint2 e[4];
    int n = 0;
    do {
#pragma unroll
      for (int i = 0; i < 4; i++)
        asm volatile("ld.relaxed.gpu.global.v2.b32 {%0, %1}, [%2];" : "=r"(e[i].x), "=r"(e[i].y) : "l"(stat + (2 * c + (i & 1)) * 128 + (i >> 1) * 8) : "memory");
      spin_guard(n);
    } while (__any_sync(~0u, min(min(e[0].y, e[1].y), min(e[2].y, e[3].y)) == 0));
#pragma unroll
    for (int r = 0; r < 2; r++) {
      const float m0 = __uint_as_float(e[2 * r].x), m1 = __uint_as_float(e[2 * r + 1].x);
      float t = m0 + m1;
      t += __shfl_xor_sync(~0u, t, 1); t += __shfl_xor_sync(~0u, t, 2);
      t *= 0.125f;
      float q = __uint_as_float(e[2 * r].y) + __uint_as_float(e[2 * r + 1].y) + 80.f * ((m0 - t) * (m0 - t) + (m1 - t) * (m1 - t));
      q += __shfl_xor_sync(~0u, q, 1); q += __shfl_xor_sync(~0u, q, 2);
      mean[r] = t; rs[r] = rsqrtf(q * (1.f / DM) + 1e-5f);
    }
    ABT(0, 7);
    uint32_t w[2][5][2];
#pragma unroll
    for (int i = 0; i < 20; i++) w[i & 1][i >> 2][i >> 1 & 1] = pack2((d[2 * i] - mean[i & 1]) * rs[i & 1], (d[2 * i + 1] - mean[i & 1]) * rs[i & 1]);
    ln_store(w, blk * 8 + warp, cg * 5);
  }
  ABT(!!p.out, 8);
  TRACE(2);
}

typedef CUresult (*EncodeFn)(CUtensorMap*, CUtensorMapDataType, cuuint32_t, void*, const cuuint64_t*, const cuuint64_t*,
                             const cuuint32_t*, const cuuint32_t*, CUtensorMapInterleave, CUtensorMapSwizzle,
                             CUtensorMapL2promotion, CUtensorMapFloatOOBfill);

void make_map(EncodeFn enc, CUtensorMap* m, const void* ptr, int cols, int rows, int nb) {
  const cuuint64_t dims[3] = {(cuuint64_t)(nb ? 64 : cols), (cuuint64_t)rows, (cuuint64_t)cols / 64};
  const cuuint64_t strides[2] = {(cuuint64_t)cols * 2, 128};
  const cuuint32_t box[3] = {64, 32, (cuuint32_t)nb}, es[3] = {1, 1, 1};
  enc(m, CU_TENSOR_MAP_DATA_TYPE_BFLOAT16, nb ? 3 : 2, const_cast<void*>(ptr), dims, strides, box, es, CU_TENSOR_MAP_INTERLEAVE_NONE,
      CU_TENSOR_MAP_SWIZZLE_128B, CU_TENSOR_MAP_L2_PROMOTION_L2_128B, CU_TENSOR_MAP_FLOAT_OOB_FILL_NONE);
}
template <class... KA, class... A>
void launch(void (*kern)(KA...), int grid, int block, int smem, int cluster, bool pdl, A... args) {
  cudaFuncSetAttribute(kern, cudaFuncAttributeMaxDynamicSharedMemorySize, smem);
  cudaLaunchConfig_t cfg = {};
  cfg.gridDim = dim3(grid); cfg.blockDim = dim3(block); cfg.dynamicSmemBytes = smem; cfg.stream = cudaStreamPerThread;
  cudaLaunchAttribute at[2];
  int n = 0;
  if (cluster > 1) { at[n].id = cudaLaunchAttributeClusterDimension; at[n].val.clusterDim.x = cluster; at[n].val.clusterDim.y = 1; at[n].val.clusterDim.z = 1; n++; }
  if (pdl) { at[n].id = cudaLaunchAttributeProgrammaticStreamSerialization; at[n].val.programmaticStreamSerializationAllowed = 1; n++; }
  cfg.attrs = at; cfg.numAttrs = n;
  cudaLaunchKernelEx(&cfg, kern, args...);
}
template <class T> void* sym(T& s) { void* p = nullptr; cudaGetSymbolAddress(&p, s); return p; }

}

#define MODE(b) 0
extern "C" void kernel_launch(void* const* d_in, const int* in_sizes, int n_in, void* d_out, int out_size) {
  const __nv_bfloat16* x = (const __nv_bfloat16*)d_in[0];
  void* fn = nullptr; cudaDriverEntryPointQueryResult qr;
  cudaGetDriverEntryPoint("cuTensorMapEncodeTiled", &fn, cudaEnableDefault, &qr);
  EncodeFn enc = (EncodeFn)fn;

  ChainParams ch = {};
  PostParams op = {};
  for (int i = 0; i < 3; i++) {
    const cuuint64_t dims[3] = {HD, 128, 5}, strides[2] = {HD * 2, HD * 256};
    const cuuint32_t box[3] = {64, 128, 5}, es[3] = {1, 1, 1};
    enc(i == 0 ? &ch.wq : i == 1 ? &ch.wk : &ch.wv, CU_TENSOR_MAP_DATA_TYPE_BFLOAT16, 3, d_in[2 + i], dims, strides, box, es, CU_TENSOR_MAP_INTERLEAVE_NONE,
        CU_TENSOR_MAP_SWIZZLE_128B, W_PROMO, CU_TENSOR_MAP_FLOAT_OOB_FILL_NONE);
  }
  {
    const cuuint64_t dims[3] = {DM, HD, 7}, strides[2] = {DM * 2, 64};
    const cuuint32_t box[3] = {32, 64, 7}, es[3] = {1, 1, 1};
    enc(&ch.wo, CU_TENSOR_MAP_DATA_TYPE_BFLOAT16, 3, d_in[5], dims, strides, box, es, CU_TENSOR_MAP_INTERLEAVE_NONE,
        CU_TENSOR_MAP_SWIZZLE_64B, CU_TENSOR_MAP_L2_PROMOTION_L2_128B, CU_TENSOR_MAP_FLOAT_OOB_FILL_NONE);
  }
  ch.mem0 = (const __nv_bfloat16*)d_in[1];
  ch.pool = (uint8_t*)(((uintptr_t)sym(g_pool) + 8191) & ~(uintptr_t)8191); ch.kv = (uint8_t*)sym(g_kv); ch.xc = (const uint32_t*)sym(g_xc); ch.sync = (uint32_t*)sym(g_sync);
  ch.d1 = 0; ch.d1b = 0; ch.d2 = 0; ch.d2b = 0;
  make_map(enc, &op.wq, d_in[2], HD, DM, 3);
  make_map(enc, &op.wo, d_in[5], DM, HD, 5); make_map(enc, &op.wo2, d_in[5], DM, HD, 0);
  make_map(enc, &op.wb, d_in[8], 1920, DM, 5); make_map(enc, &op.wb2, d_in[8], 1920, DM, 0);
  op.gap = 17; op.share = 20; op.look = 14; op.gap2 = 0; op.pol = 0;

  const Weights wa = {{(const uint8_t*)d_in[3], (const uint8_t*)d_in[4], (const uint8_t*)d_in[2], (const uint8_t*)d_in[5]}}, none = {};
  launch(first_kernel, 132, 256, 128 * 1024, 1, false, x, (const uint4*)d_in[9], wa);
  for (int layer = 0; layer < 2; layer++) {
    ch.layer = ch.d2b = op.layer = layer;
    launch(chain_kernel, 96, 256, CH_SMEM, 3, true, ch);
    launch(post_kernel, MODE(3) ? 36 : 132, 384, OP_SMEM, 1, !MODE(1), op);
    const AbParams ab = {layer == 0 ? wa : none, (uint32_t*)sym(g_bo) + layer * 128, layer == 0 ? nullptr : (uint32_t*)d_out};
    launch(attn_b_kernel, 128, AB_T + 32, AB_SMEM, 1, true, ab);
  }
}
```

```cpp
#include <cuda_runtime.h>
#include <cuda_bf16.h>
#include <cuda.h>
#include <stdint.h>

namespace {

constexpr int SEQ = 2048, DM = 640, HD = 6144, NSEG = 64;
constexpr int SPIN_LIMIT = 1 << 20;

__device__ __align__(128) float4 g_x[SEQ * DM / 4];
__device__ __align__(128) uint32_t g_of[SEQ * DM / 2];
__device__ __align__(128) uint4 g_wb[DM * DM / 8];
__device__ __align__(16) float2 g_stat[16 * 8 * 128];
__device__ uint32_t g_bo[8 * 32];
__device__ __align__(128) uint4 g_q[SEQ * HD / 8];
__device__ __align__(128) uint32_t g_o[SEQ * HD / 2];
constexpr int KV_BYTES = 5120, KV_M = 4096, KV_V = NSEG * KV_BYTES;
__device__ __align__(128) uint8_t g_kv[96 * 2 * NSEG * KV_BYTES];
__device__ __align__(128) uint32_t g_xc[SEQ * DM / 2];
#define OP_B4 0
#define OP_B8 10
#define OP_B16 15
#define QA_END 12
__host__ __device__ constexpr int op_split(int b) { return b < OP_B4 ? 2 : b < OP_B8 ? 4 : b < OP_B16 ? 8 : 16; }
__host__ __device__ constexpr int fin_items(int b) { return b < OP_B8 ? 4 : op_split(b); }
#define AB_PF 2
#define AB_PF0 10000
#define AB_PFD 8000
#define W_PROMO CU_TENSOR_MAP_L2_PROMOTION_L2_128B
#define OEF 0
#define BQ_HOLD 12
#define WEF 1
#define FK_PF 1
#define BQ_160 10
#define BQ_80 16
#define OP_160 16
__host__ __device__ constexpr int op_width(int b) { return b < OP_160 ? 320 : 160; }
__host__ __device__ constexpr int bq_width(int b) { return b < BQ_160 ? 320 : b < BQ_80 ? 160 : 80; }
__device__ __align__(128) uint2 g_part[16 * 16 * 16 * 40 * 32];
__device__ __align__(128) uint32_t g_xn[SEQ * DM / 2];
constexpr int SY_Q = 128, SY_T = 160, SY_QC = 192, SY_N = 193;
__device__ __align__(16) uint32_t g_sync[SY_N];
constexpr int NSLOT = 92;
__device__ uint32_t g_pool[(NSLOT + 2) * 2048];
__device__ int g_smpart[256], g_orient[NSLOT];
__device__ uint32_t g_smclk[256], g_smuse[256];
__device__ uint32_t g_bqkv[3 * 32 * 256 * 96];

#define ABT(L, i)
#define MODE_D(b) 0
#define DELAY(d)
#define XT(i)
#define MISS(k, n)
#define PRO(i)
#define TRACE(w)
#define ITEM(code, w)
#define TR(i, v)
#define TM(i)
#define TM1(i)
#define TMD(i, dep)
#define TMV(i, at, v)

__device__ __forceinline__ uint32_t gtime() { uint32_t c; asm volatile("mov.u32 %0, %%globaltimer_lo;" : "=r"(c) :: "memory"); return c; }
__device__ __forceinline__ uint32_t clk32() { uint32_t c; asm volatile("mov.u32 %0, %%clock;" : "=r"(c) :: "memory"); return c; }
__device__ __forceinline__ uint32_t s2u(const void* p) { return (uint32_t)__cvta_generic_to_shared(p); }
__device__ __forceinline__ uint32_t pack2(float a, float b) {
  uint32_t r; asm("cvt.rn.bf16x2.f32 %0, %1, %2;" : "=r"(r) : "f"(b), "f"(a)); return r; }
__device__ __forceinline__ float bf_lo(uint32_t w) { return __uint_as_float(w << 16); }
__device__ __forceinline__ float bf_hi(uint32_t w) { return __uint_as_float(w & 0xffff0000u); }
__device__ __forceinline__ float ex2(float x) { float y; asm("ex2.approx.ftz.f32 %0, %1;" : "=f"(y) : "f"(x)); return y; }

__device__ __forceinline__ void mbar_init(uint32_t bar, uint32_t n) {
  asm volatile("mbarrier.init.shared::cta.b64 [%0], %1;" :: "r"(bar), "r"(n) : "memory"); }
__device__ __forceinline__ void mbar_expect(uint32_t bar, uint32_t bytes) {
  asm volatile("mbarrier.arrive.expect_tx.shared::cta.b64 _, [%0], %1;" :: "r"(bar), "r"(bytes) : "memory"); }
__device__ __forceinline__ void mbar_arrive(uint32_t bar) {
  asm volatile("mbarrier.arrive.shared::cta.b64 _, [%0];" :: "r"(bar) : "memory"); }
__device__ __forceinline__ void mbar_wait(uint32_t bar, uint32_t ph) {
  asm volatile("{.reg .pred p; .reg .u32 n; mov.u32 n, 0;\n"
               "W: mbarrier.try_wait.parity.shared::cta.b64 p, [%0], %1; @p bra D;\n"
               "add.u32 n, n, 1; setp.gt.u32 p, n, %2; @p trap; bra W;\n"
               "D: }" :: "r"(bar), "r"(ph), "n"(SPIN_LIMIT) : "memory");
}
__device__ __forceinline__ void mbar_wait_cluster(uint32_t bar, uint32_t ph) {
  asm volatile("{.reg .pred p; .reg .u32 n; mov.u32 n, 0;\n"
               "W: mbarrier.try_wait.parity.acquire.cluster.shared::cta.b64 p, [%0], %1; @p bra D;\n"
               "add.u32 n, n, 1; setp.gt.u32 p, n, %2; @p trap; bra W;\n"
               "D: }" :: "r"(bar), "r"(ph), "n"(SPIN_LIMIT) : "memory");
}
__device__ __forceinline__ void spin_guard(int& n) {
  asm volatile("{.reg .pred p; add.s32 %0, %0, 1; setp.gt.s32 p, %0, %1; @p trap;}" : "+r"(n) : "n"(SPIN_LIMIT));
}
__device__ __forceinline__ void pdl_wait() { asm volatile("griddepcontrol.wait;" ::: "memory"); TRACE(1); }
__device__ __forceinline__ void pdl_launch() { asm volatile("griddepcontrol.launch_dependents;" ::: "memory"); }
__device__ __forceinline__ uint32_t ld_acquire(const uint32_t* p) { uint32_t v; asm volatile("ld.acquire.gpu.global.u32 %0, [%1];" : "=r"(v) : "l"(p) : "memory"); return v; }
__device__ __forceinline__ void red_release(uint32_t* p, uint32_t v) { asm volatile("red.release.gpu.global.add.u32 [%0], %1;" :: "l"(p), "r"(v) : "memory"); }
__device__ __forceinline__ void red_relaxed(uint32_t* p, uint32_t v) { asm volatile("red.relaxed.gpu.global.add.u32 [%0], %1;" :: "l"(p), "r"(v) : "memory"); }
__device__ __forceinline__ void fence_async_global() { asm volatile("fence.proxy.async.global;" ::: "memory"); }
__device__ __forceinline__ void fence_async() { asm volatile("fence.proxy.async.shared::cta;" ::: "memory"); }
__device__ __forceinline__ void bar_sync(int id, int n) { asm volatile("bar.sync %0, %1;" :: "r"(id), "r"(n) : "memory"); }
__device__ __forceinline__ void bar_arrive(int id, int n) { asm volatile("bar.arrive %0, %1;" :: "r"(id), "r"(n) : "memory"); }
__device__ __forceinline__ void tma_load(uint32_t dst, const CUtensorMap* m, int c0, int c1, uint32_t bar) {
  asm volatile("cp.async.bulk.tensor.2d.shared::cluster.global.mbarrier::complete_tx::bytes [%0], [%1, {%3, %4}], [%2];"
               :: "r"(dst), "l"(m), "r"(bar), "r"(c0), "r"(c1) : "memory"); }
template <bool STREAM = false>
__device__ __forceinline__ void tma_load3(uint32_t dst, const CUtensorMap* m, int c0, int c1, uint32_t bar) {
  if (STREAM)
    asm volatile("{.reg .b64 pol; createpolicy.fractional.L2::evict_first.b64 pol, 1.0;\n"
                 "cp.async.bulk.tensor.3d.shared::cluster.global.mbarrier::complete_tx::bytes.L2::cache_hint [%0], [%1, {%3, %4, 0}], [%2], pol;}"
                 :: "r"(dst), "l"(m), "r"(bar), "r"(c0), "r"(c1) : "memory");
  else
  asm volatile("cp.async.bulk.tensor.3d.shared::cluster.global.mbarrier::complete_tx::bytes [%0], [%1, {%3, %4, 0}], [%2];"
               :: "r"(dst), "l"(m), "r"(bar), "r"(c0), "r"(c1) : "memory"); }
__device__ __forceinline__ void tma_load3z(uint32_t dst, const CUtensorMap* m, int c1, int c2, uint32_t bar) {
  asm volatile("cp.async.bulk.tensor.3d.shared::cluster.global.mbarrier::complete_tx::bytes [%0], [%1, {0, %3, %4}], [%2];"
               :: "r"(dst), "l"(m), "r"(bar), "r"(c1), "r"(c2) : "memory"); }
__device__ __forceinline__ void tma_store(const CUtensorMap* m, uint32_t src, int c0, int c1) {
  asm volatile("cp.async.bulk.tensor.2d.global.shared::cta.bulk_group [%0, {%2, %3}], [%1];"
               :: "l"(m), "r"(src), "r"(c0), "r"(c1) : "memory"); }
__device__ __forceinline__ void tma_store_stream(const CUtensorMap* m, uint32_t src, int c0, int c1) {
  asm volatile("{.reg .b64 pol; createpolicy.fractional.L2::evict_first.b64 pol, 1.0;\n"
               "cp.async.bulk.tensor.2d.global.shared::cta.bulk_group.L2::cache_hint [%0, {%2, %3}], [%1], pol;}"
               :: "l"(m), "r"(src), "r"(c0), "r"(c1) : "memory"); }
__device__ __forceinline__ void bulk_load(uint32_t dst, const void* src, uint32_t bytes, uint32_t bar) {
  asm volatile("cp.async.bulk.shared::cluster.global.mbarrier::complete_tx::bytes [%0], [%1], %2, [%3];"
               :: "r"(dst), "l"(src), "r"(bytes), "r"(bar) : "memory"); }
__device__ __forceinline__ void bulk_load_last(uint32_t dst, const void* src, uint32_t bytes, uint32_t bar) {
  asm volatile("{.reg .b64 pol; createpolicy.fractional.L2::evict_first.b64 pol, 1.0;\n"
               "cp.async.bulk.shared::cluster.global.mbarrier::complete_tx::bytes.L2::cache_hint [%0], [%1], %2, [%3], pol;}"
               :: "r"(dst), "l"(src), "r"(bytes), "r"(bar) : "memory"); }
__device__ __forceinline__ void tma_load_last(uint32_t dst, const CUtensorMap* m, int c0, int c1, uint32_t bar) {
  asm volatile("{.reg .b64 pol; createpolicy.fractional.L2::evict_first.b64 pol, 1.0;\n"
               "cp.async.bulk.tensor.2d.shared::cluster.global.mbarrier::complete_tx::bytes.L2::cache_hint [%0], [%1, {%3, %4}], [%2], pol;}"
               :: "r"(dst), "l"(m), "r"(bar), "r"(c0), "r"(c1) : "memory"); }
__device__ __forceinline__ void bulk_send(uint32_t dst, uint32_t src, uint32_t bytes, uint32_t bar) {
  asm volatile("cp.async.bulk.shared::cluster.shared::cta.mbarrier::complete_tx::bytes [%0], [%1], %2, [%3];"
               :: "r"(dst), "r"(src), "r"(bytes), "r"(bar) : "memory"); }
__device__ __forceinline__ void bulk_store(void* dst, uint32_t src, uint32_t bytes) {
  asm volatile("cp.async.bulk.global.shared::cta.bulk_group [%0], [%1], %2;" :: "l"(dst), "r"(src), "r"(bytes) : "memory"); }
__device__ __forceinline__ void bulk_commit() { asm volatile("cp.async.bulk.commit_group;" ::: "memory"); }
template <int N> __device__ __forceinline__ void bulk_wait_read() { asm volatile("cp.async.bulk.wait_group.read %0;" :: "n"(N) : "memory"); }
template <int N> __device__ __forceinline__ void bulk_wait() { asm volatile("cp.async.bulk.wait_group %0;" :: "n"(N) : "memory"); }

__device__ __forceinline__ uint64_t mkdesc(uint32_t addr, uint32_t lbo, uint32_t sbo, uint32_t sw) {
  return (uint64_t)((addr & 0x3FFFF) >> 4) | ((uint64_t)(lbo >> 4) << 16) | ((uint64_t)(sbo >> 4) << 32) | ((uint64_t)sw << 62); }
__device__ __forceinline__ void wg_fence() { asm volatile("wgmma.fence.sync.aligned;" ::: "memory"); }
__device__ __forceinline__ void wg_commit() { asm volatile("wgmma.commit_group.sync.aligned;" ::: "memory"); }
template <int N> __device__ __forceinline__ void wg_wait() { asm volatile("wgmma.wait_group.sync.aligned %0;" :: "n"(N) : "memory"); }
template <int N> __device__ __forceinline__ void reg_fence(float* d) {
#pragma unroll
  for (int i = 0; i < N; i++) asm volatile("" : "+f"(d[i]) :: "memory");
}

__device__ __forceinline__ void mma16(float* d, uint32_t a0, uint32_t a1, uint32_t a2, uint32_t a3, uint32_t b0, uint32_t b1) {
  asm volatile("mma.sync.aligned.m16n8k16.row.col.f32.bf16.bf16.f32 {%0,%1,%2,%3},{%4,%5,%6,%7},{%8,%9},{%0,%1,%2,%3};"
               : "+f"(d[0]), "+f"(d[1]), "+f"(d[2]), "+f"(d[3]) : "r"(a0), "r"(a1), "r"(a2), "r"(a3), "r"(b0), "r"(b1)); }
__device__ __forceinline__ void mma8(float* d, uint32_t a0, uint32_t a1, uint32_t b0) {
  asm volatile("mma.sync.aligned.m16n8k8.row.col.f32.bf16.bf16.f32 {%0,%1,%2,%3},{%4,%5},{%6},{%0,%1,%2,%3};"
               : "+f"(d[0]), "+f"(d[1]), "+f"(d[2]), "+f"(d[3]) : "r"(a0), "r"(a1), "r"(b0)); }
__device__ __forceinline__ void ldsm4(uint32_t* r, uint32_t a) {
  asm volatile("ldmatrix.sync.aligned.m8n8.x4.shared.b16 {%0,%1,%2,%3},[%4];" : "=r"(r[0]), "=r"(r[1]), "=r"(r[2]), "=r"(r[3]) : "r"(a) : "memory"); }
__device__ __forceinline__ void ldsm4t(uint32_t* r, uint32_t a) {
  asm volatile("ldmatrix.sync.aligned.m8n8.x4.trans.shared.b16 {%0,%1,%2,%3},[%4];" : "=r"(r[0]), "=r"(r[1]), "=r"(r[2]), "=r"(r[3]) : "r"(a) : "memory"); }
__device__ __forceinline__ void ldsm2(uint32_t* r, uint32_t a) {
  asm volatile("ldmatrix.sync.aligned.m8n8.x2.shared.b16 {%0,%1},[%2];" : "=r"(r[0]), "=r"(r[1]) : "r"(a) : "memory"); }
__device__ __forceinline__ void stsm4(uint32_t a, uint32_t r0, uint32_t r1, uint32_t r2, uint32_t r3) {
  asm volatile("stmatrix.sync.aligned.m8n8.x4.shared.b16 [%0], {%1,%2,%3,%4};" :: "r"(a), "r"(r0), "r"(r1), "r"(r2), "r"(r3) : "memory"); }
__device__ __forceinline__ void stsm2t(uint32_t a, uint32_t r0, uint32_t r1) {
  asm volatile("stmatrix.sync.aligned.m8n8.x2.trans.shared.b16 [%0], {%1,%2};" :: "r"(a), "r"(r0), "r"(r1) : "memory"); }
__device__ __forceinline__ void stsm4t(uint32_t a, uint32_t r0, uint32_t r1, uint32_t r2, uint32_t r3) {
  asm volatile("stmatrix.sync.aligned.m8n8.x4.trans.shared.b16 [%0], {%1,%2,%3,%4};" :: "r"(a), "r"(r0), "r"(r1), "r"(r2), "r"(r3) : "memory"); }
__device__ __forceinline__ void st_async128(uint32_t a, uint4 v, uint32_t bar) {
  asm volatile("st.async.shared::cluster.mbarrier::complete_tx::bytes.v4.b32 [%0], {%1,%2,%3,%4}, [%5];" :: "r"(a), "r"(v.x), "r"(v.y), "r"(v.z), "r"(v.w), "r"(bar) : "memory"); }
__device__ __forceinline__ void sts32(uint32_t a, uint32_t v) { asm volatile("st.shared.b32 [%0], %1;" :: "r"(a), "r"(v) : "memory"); }
__device__ __forceinline__ void sts64f(uint32_t a, float x, float y) { asm volatile("st.shared.v2.f32 [%0], {%1,%2};" :: "r"(a), "f"(x), "f"(y) : "memory"); }
__device__ __forceinline__ void sts128(uint32_t a, uint4 v) {
  asm volatile("st.shared.v4.b32 [%0], {%1,%2,%3,%4};" :: "r"(a), "r"(v.x), "r"(v.y), "r"(v.z), "r"(v.w) : "memory"); }
__device__ __forceinline__ void sts128f(uint32_t a, float x, float y, float z, float w) {
  asm volatile("st.shared.v4.f32 [%0], {%1,%2,%3,%4};" :: "r"(a), "f"(x), "f"(y), "f"(z), "f"(w) : "memory"); }
__device__ __forceinline__ float lds32f(uint32_t a) { float v; asm volatile("ld.shared.f32 %0, [%1];" : "=f"(v) : "r"(a) : "memory"); return v; }
__device__ __forceinline__ float2 lds64f(uint32_t a) { float2 v; asm volatile("ld.shared.v2.f32 {%0,%1}, [%2];" : "=f"(v.x), "=f"(v.y) : "r"(a) : "memory"); return v; }
__device__ __forceinline__ float4 lds128f(uint32_t a) {
  float4 v; asm volatile("ld.shared.v4.f32 {%0,%1,%2,%3}, [%4];" : "=f"(v.x), "=f"(v.y), "=f"(v.z), "=f"(v.w) : "r"(a) : "memory"); return v; }
__device__ __forceinline__ uint4 lds128(uint32_t a) {
  uint4 v; asm volatile("ld.shared.v4.b32 {%0,%1,%2,%3}, [%4];" : "=r"(v.x), "=r"(v.y), "=r"(v.z), "=r"(v.w) : "r"(a) : "memory"); return v; }
__device__ __forceinline__ uint4 ldg_strong128(const void* p) {
  uint4 v; asm volatile("ld.relaxed.gpu.global.v4.u32 {%0,%1,%2,%3}, [%4];" : "=r"(v.x), "=r"(v.y), "=r"(v.z), "=r"(v.w) : "l"(p) : "memory"); return v; }
__device__ __forceinline__ void stg_strong32(void* p, uint32_t v) { asm volatile("st.relaxed.gpu.global.u32 [%0], %1;" :: "l"(p), "r"(v) : "memory"); }
__device__ __forceinline__ void stg_strong16(void* p, uint32_t v) { asm volatile("st.relaxed.gpu.global.u16 [%0], %1;" :: "l"(p), "h"((uint16_t)v) : "memory"); }
__device__ __forceinline__ void stg_strong128(void* p, uint4 v) {
  asm volatile("st.relaxed.gpu.global.v4.u32 [%0], {%1,%2,%3,%4};" :: "l"(p), "r"(v.x), "r"(v.y), "r"(v.z), "r"(v.w) : "memory"); }
__device__ __forceinline__ uint32_t mapa(uint32_t a, uint32_t r) {
  uint32_t o; asm("mapa.shared::cluster.u32 %0, %1, %2;" : "=r"(o) : "r"(a), "r"(r)); return o; }
__device__ __forceinline__ void st_async2f(uint32_t a, float x, float y, uint32_t bar) {
  asm volatile("st.async.shared::cluster.mbarrier::complete_tx::bytes.v2.f32 [%0], {%1,%2}, [%3];" :: "r"(a), "f"(x), "f"(y), "r"(bar) : "memory"); }
__device__ __forceinline__ void st_async32(uint32_t a, uint32_t x, uint32_t bar) {
  asm volatile("st.async.shared::cluster.mbarrier::complete_tx::bytes.b32 [%0], %1, [%2];" :: "r"(a), "r"(x), "r"(bar) : "memory"); }
__device__ __forceinline__ uint32_t lds32(uint32_t a) { uint32_t v; asm volatile("ld.shared.b32 %0, [%1];" : "=r"(v) : "r"(a) : "memory"); return v; }
__device__ __forceinline__ void st_async64(uint32_t a, uint32_t x, uint32_t y, uint32_t bar) {
  asm volatile("st.async.shared::cluster.mbarrier::complete_tx::bytes.v2.b32 [%0], {%1,%2}, [%3];" :: "r"(a), "r"(x), "r"(y), "r"(bar) : "memory"); }
__device__ __forceinline__ uint2 lds64(uint32_t a) { uint2 v; asm volatile("ld.shared.v2.b32 {%0,%1}, [%2];" : "=r"(v.x), "=r"(v.y) : "r"(a) : "memory"); return v; }
__device__ __forceinline__ void sts64(uint32_t a, uint32_t x, uint32_t y) { asm volatile("st.shared.v2.b32 [%0], {%1,%2};" :: "r"(a), "r"(x), "r"(y) : "memory"); }
__device__ __forceinline__ uint32_t ldg_strong32(const void* p) { uint32_t v; asm volatile("ld.relaxed.gpu.global.u32 %0, [%1];" : "=r"(v) : "l"(p) : "memory"); return v; }
__device__ __forceinline__ uint32_t transpose8(uint32_t x) { uint32_t r; asm volatile("movmatrix.sync.aligned.m8n8.trans.b16 %0, %1;" : "=r"(r) : "r"(x)); return r; }
__device__ __forceinline__ uint32_t hadd2(uint32_t a, uint32_t b) { uint32_t r; asm("add.rn.bf16x2 %0, %1, %2;" : "=r"(r) : "r"(a), "r"(b)); return r; }
__device__ __forceinline__ uint32_t min4(uint4 v) { return min(__vimin3_u32(v.x, v.y, v.z), v.w); }

__device__ __forceinline__ void wg_ss192_01(float* d, uint64_t da, uint64_t db, int sd) {
  asm volatile("{.reg .pred p; setp.ne.b32 p, %98, 0;\n"
    "wgmma.mma_async.sync.aligned.m64n192k16.f32.bf16.bf16 {%0,%1,%2,%3,%4,%5,%6,%7,%8,%9,%10,%11,%12,%13,%14,%15,%16,%17,%18,%19,%20,%21,%22,%23,%24,%25,%26,%27,%28,%29,%30,%31,%32,%33,%34,%35,%36,%37,%38,%39,%40,%41,%42,%43,%44,%45,%46,%47,%48,%49,%50,%51,%52,%53,%54,%55,%56,%57,%58,%59,%60,%61,%62,%63,%64,%65,%66,%67,%68,%69,%70,%71,%72,%73,%74,%75,%76,%77,%78,%79,%80,%81,%82,%83,%84,%85,%86,%87,%88,%89,%90,%91,%92,%93,%94,%95}, %96, %97, p, 1, 1, 0, 1;}"
    : "+f"(d[0]),"+f"(d[1]),"+f"(d[2]),"+f"(d[3]),"+f"(d[4]),"+f"(d[5]),"+f"(d[6]),"+f"(d[7]),"+f"(d[8]),"+f"(d[9]),"+f"(d[10]),"+f"(d[11]),"+f"(d[12]),"+f"(d[13]),"+f"(d[14]),"+f"(d[15]),"+f"(d[16]),"+f"(d[17]),"+f"(d[18]),"+f"(d[19]),"+f"(d[20]),"+f"(d[21]),"+f"(d[22]),"+f"(d[23]),"+f"(d[24]),"+f"(d[25]),"+f"(d[26]),"+f"(d[27]),"+f"(d[28]),"+f"(d[29]),"+f"(d[30]),"+f"(d[31]),"+f"(d[32]),"+f"(d[33]),"+f"(d[34]),"+f"(d[35]),"+f"(d[36]),"+f"(d[37]),"+f"(d[38]),"+f"(d[39]),"+f"(d[40]),"+f"(d[41]),"+f"(d[42]),"+f"(d[43]),"+f"(d[44]),"+f"(d[45]),"+f"(d[46]),"+f"(d[47]),"+f"(d[48]),"+f"(d[49]),"+f"(d[50]),"+f"(d[51]),"+f"(d[52]),"+f"(d[53]),"+f"(d[54]),"+f"(d[55]),"+f"(d[56]),"+f"(d[57]),"+f"(d[58]),"+f"(d[59]),"+f"(d[60]),"+f"(d[61]),"+f"(d[62]),"+f"(d[63]),"+f"(d[64]),"+f"(d[65]),"+f"(d[66]),"+f"(d[67]),"+f"(d[68]),"+f"(d[69]),"+f"(d[70]),"+f"(d[71]),"+f"(d[72]),"+f"(d[73]),"+f"(d[74]),"+f"(d[75]),"+f"(d[76]),"+f"(d[77]),"+f"(d[78]),"+f"(d[79]),"+f"(d[80]),"+f"(d[81]),"+f"(d[82]),"+f"(d[83]),"+f"(d[84]),"+f"(d[85]),"+f"(d[86]),"+f"(d[87]),"+f"(d[88]),"+f"(d[89]),"+f"(d[90]),"+f"(d[91]),"+f"(d[92]),"+f"(d[93]),"+f"(d[94]),"+f"(d[95])
    : "l"(da), "l"(db), "r"(sd));
}
__device__ __forceinline__ void wg_ss128_01(float* d, uint64_t da, uint64_t db, int sd) {
  asm volatile("{.reg .pred p; setp.ne.b32 p, %66, 0;\n"
    "wgmma.mma_async.sync.aligned.m64n128k16.f32.bf16.bf16 {%0,%1,%2,%3,%4,%5,%6,%7,%8,%9,%10,%11,%12,%13,%14,%15,%16,%17,%18,%19,%20,%21,%22,%23,%24,%25,%26,%27,%28,%29,%30,%31,%32,%33,%34,%35,%36,%37,%38,%39,%40,%41,%42,%43,%44,%45,%46,%47,%48,%49,%50,%51,%52,%53,%54,%55,%56,%57,%58,%59,%60,%61,%62,%63}, %64, %65, p, 1, 1, 0, 1;}"
    : "+f"(d[0]),"+f"(d[1]),"+f"(d[2]),"+f"(d[3]),"+f"(d[4]),"+f"(d[5]),"+f"(d[6]),"+f"(d[7]),"+f"(d[8]),"+f"(d[9]),"+f"(d[10]),"+f"(d[11]),"+f"(d[12]),"+f"(d[13]),"+f"(d[14]),"+f"(d[15]),"+f"(d[16]),"+f"(d[17]),"+f"(d[18]),"+f"(d[19]),"+f"(d[20]),"+f"(d[21]),"+f"(d[22]),"+f"(d[23]),"+f"(d[24]),"+f"(d[25]),"+f"(d[26]),"+f"(d[27]),"+f"(d[28]),"+f"(d[29]),"+f"(d[30]),"+f"(d[31]),"+f"(d[32]),"+f"(d[33]),"+f"(d[34]),"+f"(d[35]),"+f"(d[36]),"+f"(d[37]),"+f"(d[38]),"+f"(d[39]),"+f"(d[40]),"+f"(d[41]),"+f"(d[42]),"+f"(d[43]),"+f"(d[44]),"+f"(d[45]),"+f"(d[46]),"+f"(d[47]),"+f"(d[48]),"+f"(d[49]),"+f"(d[50]),"+f"(d[51]),"+f"(d[52]),"+f"(d[53]),"+f"(d[54]),"+f"(d[55]),"+f"(d[56]),"+f"(d[57]),"+f"(d[58]),"+f"(d[59]),"+f"(d[60]),"+f"(d[61]),"+f"(d[62]),"+f"(d[63])
    : "l"(da), "l"(db), "r"(sd));
}
__device__ __forceinline__ void wg_ss160_01(float* d, uint64_t da, uint64_t db, int sd) {
  asm volatile("{.reg .pred p; setp.ne.b32 p, %82, 0;\n"
    "wgmma.mma_async.sync.aligned.m64n160k16.f32.bf16.bf16 {%0,%1,%2,%3,%4,%5,%6,%7,%8,%9,%10,%11,%12,%13,%14,%15,%16,%17,%18,%19,%20,%21,%22,%23,%24,%25,%26,%27,%28,%29,%30,%31,%32,%33,%34,%35,%36,%37,%38,%39,%40,%41,%42,%43,%44,%45,%46,%47,%48,%49,%50,%51,%52,%53,%54,%55,%56,%57,%58,%59,%60,%61,%62,%63,%64,%65,%66,%67,%68,%69,%70,%71,%72,%73,%74,%75,%76,%77,%78,%79}, %80, %81, p, 1, 1, 0, 1;}"
    : "+f"(d[0]),"+f"(d[1]),"+f"(d[2]),"+f"(d[3]),"+f"(d[4]),"+f"(d[5]),"+f"(d[6]),"+f"(d[7]),"+f"(d[8]),"+f"(d[9]),"+f"(d[10]),"+f"(d[11]),"+f"(d[12]),"+f"(d[13]),"+f"(d[14]),"+f"(d[15]),"+f"(d[16]),"+f"(d[17]),"+f"(d[18]),"+f"(d[19]),"+f"(d[20]),"+f"(d[21]),"+f"(d[22]),"+f"(d[23]),"+f"(d[24]),"+f"(d[25]),"+f"(d[26]),"+f"(d[27]),"+f"(d[28]),"+f"(d[29]),"+f"(d[30]),"+f"(d[31]),"+f"(d[32]),"+f"(d[33]),"+f"(d[34]),"+f"(d[35]),"+f"(d[36]),"+f"(d[37]),"+f"(d[38]),"+f"(d[39]),"+f"(d[40]),"+f"(d[41]),"+f"(d[42]),"+f"(d[43]),"+f"(d[44]),"+f"(d[45]),"+f"(d[46]),"+f"(d[47]),"+f"(d[48]),"+f"(d[49]),"+f"(d[50]),"+f"(d[51]),"+f"(d[52]),"+f"(d[53]),"+f"(d[54]),"+f"(d[55]),"+f"(d[56]),"+f"(d[57]),"+f"(d[58]),"+f"(d[59]),"+f"(d[60]),"+f"(d[61]),"+f"(d[62]),"+f"(d[63]),"+f"(d[64]),"+f"(d[65]),"+f"(d[66]),"+f"(d[67]),"+f"(d[68]),"+f"(d[69]),"+f"(d[70]),"+f"(d[71]),"+f"(d[72]),"+f"(d[73]),"+f"(d[74]),"+f"(d[75]),"+f"(d[76]),"+f"(d[77]),"+f"(d[78]),"+f"(d[79])
    : "l"(da), "l"(db), "r"(sd));
}
__device__ __forceinline__ void wg_ss80_01(float* d, uint64_t da, uint64_t db, int sd) {
  asm volatile("{.reg .pred p; setp.ne.b32 p, %42, 0;\n"
    "wgmma.mma_async.sync.aligned.m64n80k16.f32.bf16.bf16 {%0,%1,%2,%3,%4,%5,%6,%7,%8,%9,%10,%11,%12,%13,%14,%15,%16,%17,%18,%19,%20,%21,%22,%23,%24,%25,%26,%27,%28,%29,%30,%31,%32,%33,%34,%35,%36,%37,%38,%39}, %40, %41, p, 1, 1, 0, 1;}"
    : "+f"(d[0]),"+f"(d[1]),"+f"(d[2]),"+f"(d[3]),"+f"(d[4]),"+f"(d[5]),"+f"(d[6]),"+f"(d[7]),"+f"(d[8]),"+f"(d[9]),"+f"(d[10]),"+f"(d[11]),"+f"(d[12]),"+f"(d[13]),"+f"(d[14]),"+f"(d[15]),"+f"(d[16]),"+f"(d[17]),"+f"(d[18]),"+f"(d[19]),"+f"(d[20]),"+f"(d[21]),"+f"(d[22]),"+f"(d[23]),"+f"(d[24]),"+f"(d[25]),"+f"(d[26]),"+f"(d[27]),"+f"(d[28]),"+f"(d[29]),"+f"(d[30]),"+f"(d[31]),"+f"(d[32]),"+f"(d[33]),"+f"(d[34]),"+f"(d[35]),"+f"(d[36]),"+f"(d[37]),"+f"(d[38]),"+f"(d[39])
    : "l"(da), "l"(db), "r"(sd));
}
__device__ __forceinline__ void wg_rs32_00(float* d, uint32_t a0, uint32_t a1, uint32_t a2, uint32_t a3, uint64_t db, int sd) {
  asm volatile("{.reg .pred p; setp.ne.b32 p, %21, 0;\n"
    "wgmma.mma_async.sync.aligned.m64n32k16.f32.bf16.bf16 {%0,%1,%2,%3,%4,%5,%6,%7,%8,%9,%10,%11,%12,%13,%14,%15}, {%16,%17,%18,%19}, %20, p, 1, 1, 0;}"
    : "+f"(d[0]),"+f"(d[1]),"+f"(d[2]),"+f"(d[3]),"+f"(d[4]),"+f"(d[5]),"+f"(d[6]),"+f"(d[7]),"+f"(d[8]),"+f"(d[9]),"+f"(d[10]),"+f"(d[11]),"+f"(d[12]),"+f"(d[13]),"+f"(d[14]),"+f"(d[15])
    : "r"(a0), "r"(a1), "r"(a2), "r"(a3), "l"(db), "r"(sd));
}
__device__ __forceinline__ void wg_rs64_00(float* d, uint32_t a0, uint32_t a1, uint32_t a2, uint32_t a3, uint64_t db, int sd) {
  asm volatile("{.reg .pred p; setp.ne.b32 p, %37, 0;\n"
    "wgmma.mma_async.sync.aligned.m64n64k16.f32.bf16.bf16 {%0,%1,%2,%3,%4,%5,%6,%7,%8,%9,%10,%11,%12,%13,%14,%15,%16,%17,%18,%19,%20,%21,%22,%23,%24,%25,%26,%27,%28,%29,%30,%31}, {%32,%33,%34,%35}, %36, p, 1, 1, 0;}"
    : "+f"(d[0]),"+f"(d[1]),"+f"(d[2]),"+f"(d[3]),"+f"(d[4]),"+f"(d[5]),"+f"(d[6]),"+f"(d[7]),"+f"(d[8]),"+f"(d[9]),"+f"(d[10]),"+f"(d[11]),"+f"(d[12]),"+f"(d[13]),"+f"(d[14]),"+f"(d[15]),"+f"(d[16]),"+f"(d[17]),"+f"(d[18]),"+f"(d[19]),"+f"(d[20]),"+f"(d[21]),"+f"(d[22]),"+f"(d[23]),"+f"(d[24]),"+f"(d[25]),"+f"(d[26]),"+f"(d[27]),"+f"(d[28]),"+f"(d[29]),"+f"(d[30]),"+f"(d[31])
    : "r"(a0), "r"(a1), "r"(a2), "r"(a3), "l"(db), "r"(sd));
}
__device__ __forceinline__ void wg_rs24_01(float* d, uint32_t a0, uint32_t a1, uint32_t a2, uint32_t a3, uint64_t db, int sd) {
  asm volatile("{.reg .pred p; setp.ne.b32 p, %17, 0;\n"
    "wgmma.mma_async.sync.aligned.m64n24k16.f32.bf16.bf16 {%0,%1,%2,%3,%4,%5,%6,%7,%8,%9,%10,%11}, {%12,%13,%14,%15}, %16, p, 1, 1, 1;}"
    : "+f"(d[0]),"+f"(d[1]),"+f"(d[2]),"+f"(d[3]),"+f"(d[4]),"+f"(d[5]),"+f"(d[6]),"+f"(d[7]),"+f"(d[8]),"+f"(d[9]),"+f"(d[10]),"+f"(d[11])
    : "r"(a0), "r"(a1), "r"(a2), "r"(a3), "l"(db), "r"(sd));
}

#define AB_POLY 0xaa
#define AB_DEG 3
__device__ __forceinline__ constexpr bool poly_group(int group) { return (AB_POLY >> (group & 7)) & 1; }

template <int V> struct Int { static constexpr int value = V; };

template <int NG>
__device__ __forceinline__ void ln_stats(const float4 (&v)[NG][5], uint32_t scratch, float (&mean)[NG], float (&rs)[NG]) {
  const int warp = threadIdx.x >> 5, lane = threadIdx.x & 31;
#pragma unroll
  for (int r = 0; r < NG; r++) {
    float s = 0.f, q = 0.f;
#pragma unroll
    for (int i = 0; i < 5; i++) s += (v[r][i].x + v[r][i].y) + (v[r][i].z + v[r][i].w);
    s += __shfl_xor_sync(~0u, s, 1); s += __shfl_xor_sync(~0u, s, 2);
    s *= 1.f / 80;
#pragma unroll
    for (int i = 0; i < 5; i++) {
      const float x = v[r][i].x - s, y = v[r][i].y - s, z = v[r][i].z - s, w = v[r][i].w - s;
      q += (x * x + y * y) + (z * z + w * w);
    }
    q += __shfl_xor_sync(~0u, q, 1); q += __shfl_xor_sync(~0u, q, 2);
    mean[r] = s; rs[r] = q;
  }
  bar_sync(1, 256);
  if ((lane & 3) == 0) {
#pragma unroll
    for (int r = 0; r < NG; r++) sts64f(scratch + r * 512 + lane * 16 + warp * 8, mean[r], rs[r]);
  }
  bar_sync(1, 256);
#pragma unroll
  for (int r = 0; r < NG; r++) {
    const float4 e = lds128f(scratch + r * 512 + lane * 16);
    float t = e.x + e.z;
    t += __shfl_xor_sync(~0u, t, 1); t += __shfl_xor_sync(~0u, t, 2);
    t *= 0.125f;
    float q = e.y + e.w + 80.f * ((e.x - t) * (e.x - t) + (e.z - t) * (e.z - t));
    q += __shfl_xor_sync(~0u, q, 1); q += __shfl_xor_sync(~0u, q, 2);
    mean[r] = t; rs[r] = rsqrtf(q * (1.f / DM) + 1e-5f);
  }
}

__device__ __forceinline__ void ln_store(const uint32_t (&w)[2][5][2], int tile, int u0) {
  const int lane = threadIdx.x & 31;
  uint32_t* xc = g_xc + ((tile >> 1) * 40 + u0) * 256 + (tile & 1) * 64 + lane;
#pragma unroll
  for (int i = 0; i < 20; i++) xc[(i >> 1) * 128 + (i & 1) * 32] = w[i & 1][i >> 2][i >> 1 & 1];
#pragma unroll
  for (int i = 0; i < 5; i++) {
    const int u = u0 + i;
    uint32_t* xn = g_xn + (((tile >> 3) * 20 + (u >> 1)) * 16 + (tile & 1) * 8 + (tile & 6)) * 128 + (u & 1) * 64 + lane;
#pragma unroll
    for (int r = 0; r < 2; r++) { xn[r * 128] = w[r][i][0]; xn[r * 128 + 32] = w[r][i][1]; }
  }
}
__device__ __forceinline__ void wait_count(const uint32_t* c, uint32_t n) {
  int spin = 0;
  while ((ld_acquire(c) & 0xffff) < n) { __nanosleep(32); spin_guard(spin); }
}

__device__ __forceinline__ uint8_t* pool_at(uint32_t off) {
  return reinterpret_cast<uint8_t*>((reinterpret_cast<uintptr_t>(g_pool) + 8191) & ~(uintptr_t)8191) + off; }
struct Weights { const uint8_t* w[4]; };
__device__ __forceinline__ void prefetch_weights(const Weights& p, int i) {
  if (blockIdx.x < 128) asm volatile("cp.async.bulk.prefetch.L2.global [%0], 61440;" :: "l"(p.w[i] + (size_t)blockIdx.x * 61440) : "memory");
}
__global__ void __launch_bounds__(256) first_kernel(const __nv_bfloat16* __restrict__ xin, const uint4* __restrict__ wb, const __grid_constant__ Weights wa) {
  __shared__ __align__(16) float scratch[256];
  __shared__ uint32_t lat[4];
  const int warp = threadIdx.x >> 5, lane = threadIdx.x & 31, cta = blockIdx.x;
  TRACE(0);
  pdl_launch();
  if (warp < 4 && (warp < 2 || cta < NSLOT)) {
    uint32_t* q = reinterpret_cast<uint32_t*>(pool_at((warp < 2 ? NSLOT : cta) * 8192 + (warp & 1) * 4096)) + (warp < 2 ? (cta & 127) * 8 : 0);
    if (lane < 8) stg_strong32(q + lane, 0u);
    uint32_t best = ~0u;
    if (lane == 0)
      for (int r = 0; r < 4; r++) {
        uint32_t t0, t1, v;
        asm volatile("mov.u32 %0, %%clock;" : "=r"(t0) :: "memory");
        asm volatile("atom.relaxed.gpu.global.exch.b32 %0, [%1], 0;" : "=r"(v) : "l"(q) : "memory");
        asm volatile("{.reg .u32 t; add.u32 t, %1, 1; mov.u32 %0, %%clock; sub.u32 %0, %0, %1;}" : "=r"(t1) : "r"(__shfl_sync(1u, v, 0)) : "memory");
        best = min(best, t1 - t0);
      }
    if (lane == 0) lat[warp] = best;
  }
  __syncthreads();
  ABT(2, 0);
  if (threadIdx.x == 0) {
    const int part = lat[0] < lat[1] ? 0 : 1;
    uint32_t smid; asm("mov.u32 %0, %%smid;" : "=r"(smid));
    g_smpart[smid & 255] = part;
    g_smclk[smid & 255] = clk32() - gtime() * 2;
    g_smuse[smid & 255] = 0;
    if (cta < NSLOT) g_orient[cta] = lat[2] < lat[3] ? part : 1 - part;
  }
  if (cta < 128) {
    float4 v[2][5];
#pragma unroll
    for (int r = 0; r < 2; r++)
#pragma unroll
      for (int i = 0; i < 5; i++) {
        const uint32_t* src = reinterpret_cast<const uint32_t*>(xin) + (cta * 16 + r * 8 + (lane >> 2)) * (DM / 2) + warp * 40 + i * 8 + (lane & 3);
        const uint32_t a = src[0], b = src[4];
        v[r][i] = make_float4(bf_lo(a), bf_hi(a), bf_lo(b), bf_hi(b));
      }
    uint4 w8[2];
#pragma unroll
    for (int i = 0; i < 2; i++) w8[i] = wb[cta * 400 + min(i * 256 + threadIdx.x, 399)];
    if (threadIdx.x < 128) g_stat[cta * 128 + threadIdx.x] = make_float2(0.f, 0.f);
#pragma unroll
    for (int i = 0; i < 10; i++) g_x[((cta * 2 + i / 5) * 40 + warp * 5 + i % 5) * 32 + lane] = v[i / 5][i % 5];
    ABT(2, 1);
    if (threadIdx.x == 32) for (int i = 0; i < FK_PF; i++) prefetch_weights(wa, i);
    float mean[2], rs[2];
    ln_stats<2>(v, s2u(scratch), mean, rs);
    ABT(2, 2);
    uint32_t w[2][5][2];
#pragma unroll
    for (int i = 0; i < 10; i++) {
      const float4 t = v[i / 5][i % 5];
      const float m = mean[i / 5], q = rs[i / 5];
      w[i / 5][i % 5][0] = pack2((t.x - m) * q, (t.y - m) * q); w[i / 5][i % 5][1] = pack2((t.z - m) * q, (t.w - m) * q);
    }
    ln_store(w, cta, warp * 5);
    ABT(2, 3);
#pragma unroll
    for (int i = 0; i < 2; i++) {
      const int e = cta * 400 + min(i * 256 + threadIdx.x, 399), k = e / 80, n = e - k * 80, cg = n / 10;
      g_wb[((cg * 80 + (k >> 3)) * 10 + n - cg * 10) * 8 + (k & 7)] = w8[i];
    }
  } else if (cta == 128) {
    g_bo[threadIdx.x] = 0;
  }
  TRACE(2);
}

struct ChainParams {
  CUtensorMap wq, wk, wv, wo;
  const __nv_bfloat16* mem0;
  uint8_t *pool, *kv;
  const uint32_t* xc;
  uint32_t* sync;
  int layer;
  int d0, d3, d1, d1b, d2, d2b, mode;
};
constexpr int CH_WQ = 0, CH_WO = 81920, CH_X = CH_WO + 86016, CH_M = CH_X + 20480, CH_KT = CH_X + 40960, CH_VT = CH_KT + 4096,
              CH_PS = CH_VT + 4096, CH_QK = CH_PS + 4096, CH_VP = CH_QK + 4096, CH_SX = CH_VP + 1024, CH_O = CH_SX + 2304, CH_ID = CH_O + 3072,
              CH_BAR = CH_ID + 512;
constexpr int CH_SMEM = CH_BAR + 256;
constexpr int CH_BASE = 1024;
#define CH_VK0 8
#define CH_VK1 20
#define CH_L0 4
#define CH_LR 4
#define NOX 0
#define CH_XA 1
#define CH_XB 4
#define CH_W1 3
#define CH_W2 17
#define CH_W3 26
#define CH_R2 8
#define CH_VA 16
#define CH_EX 1
#define CH_KD 0
#define CH_RP 1
#define CH_KF 10
#define CH_LO 0
#define CH_LR1 4
#define CH_KP 0
#define CH_KM 0
#define CH_WE 0
#define CH_KW 3
#define CH_RB 0
#define CH_RC 8
#define CH_D0 200
#define CH_D1 450
#define CH_D2 350
#define CH_R1 4
#define CH_TW 12
__device__ __forceinline__ uint32_t opaque(uint32_t x) { return __shfl_sync(~0u, x, threadIdx.x & 31); }
__device__ __forceinline__ uint32_t nz(uint32_t x) { uint32_t r; asm("max.u32 %0, %1, 1;" : "=r"(r) : "r"(x)); return r; }
__device__ __forceinline__ uint32_t pack_tag(float lo, float hi, uint32_t tag, uint32_t mask) {
  uint32_t r;
  asm("lop3.b32 %0, %1, %2, %3, 0xD8;" : "=r"(r) : "r"(pack2(lo, hi)), "r"(tag), "r"(mask));
  return r;
}
__device__ __forceinline__ uint32_t differ(uint32_t a, uint32_t b, uint32_t t) { uint32_t r; asm("lop3.b32 %0, %1, %2, %3, 0x7E;" : "=r"(r) : "r"(a), "r"(b), "r"(t)); return r; }
__device__ __forceinline__ void mbar_wait_hot(uint32_t bar, uint32_t ph) {
  uint32_t ok;
  asm volatile("{.reg .pred p; mbarrier.try_wait.parity.shared::cta.b64 p, [%1], %2; selp.u32 %0, 1, 0, p;}" : "=r"(ok) : "r"(bar), "r"(ph) : "memory");
  if (__builtin_expect(!ok, 0)) mbar_wait(bar, ph);
}
__device__ __forceinline__ bool elect() {
  uint32_t r; asm volatile("{.reg .pred p; elect.sync _|p, 0xffffffff; selp.u32 %0, 1, 0, p;}" : "=r"(r)); return r; }
__device__ __forceinline__ uint32_t or3(uint32_t a, uint32_t b, uint32_t c) { uint32_t r; asm("lop3.b32 %0, %1, %2, %3, 0xFE;" : "=r"(r) : "r"(a), "r"(b), "r"(c)); return r; }
__device__ __forceinline__ void pin() { pdl_launch(); }
__device__ __forceinline__ void mma16h(float* d, uint32_t a0, uint32_t a2, uint32_t b0, uint32_t b1) {
  asm volatile("{.reg .b32 u, v; mma.sync.aligned.m16n8k16.row.col.f32.bf16.bf16.f32 {%0,%1,%2,%3},{%4,u,%5,v},{%6,%7},{%0,%1,%2,%3};}"
               : "+f"(d[0]), "+f"(d[1]), "+f"(d[2]), "+f"(d[3]) : "r"(a0), "r"(a2), "r"(b0), "r"(b1)); }
__device__ __forceinline__ void mma8h(float* d, uint32_t a0, uint32_t b0) {
  asm volatile("{.reg .b32 u; mma.sync.aligned.m16n8k8.row.col.f32.bf16.bf16.f32 {%0,%1,%2,%3},{%4,u},{%5},{%0,%1,%2,%3};}"
               : "+f"(d[0]), "+f"(d[1]), "+f"(d[2]), "+f"(d[3]) : "r"(a0), "r"(b0)); }
__device__ __forceinline__ uint32_t absmax2(uint32_t a, uint32_t b) { uint32_t r; asm("max.xorsign.abs.bf16x2 %0, %1, %2;" : "=r"(r) : "r"(a), "r"(b)); return r; }
__device__ __forceinline__ void until(uint32_t t) { while ((int)(clk32() - t) < 0) {} }
__device__ __forceinline__ uint4 pack8(const float* d) { return make_uint4(pack2(d[0], d[1]), pack2(d[2], d[3]), pack2(d[4], d[5]), pack2(d[6], d[7])); }
__device__ __forceinline__ void add8(float* d, uint4 v) {
  d[0] += bf_lo(v.x); d[1] += bf_hi(v.x); d[2] += bf_lo(v.y); d[3] += bf_hi(v.y);
  d[4] += bf_lo(v.z); d[5] += bf_hi(v.z); d[6] += bf_lo(v.w); d[7] += bf_hi(v.w);
}

template <int WG>
__device__ __forceinline__ void chain_body(const ChainParams& p, const uint32_t wq, const uint32_t (&ak)[80], const uint32_t (&av)[80]) {
  const int tid = threadIdx.x & 127, t4 = __shfl_sync(~0u, tid >> 5, 0), lane = tid & 31;
  const int cta = blockIdx.x, h = cta / 3, j = cta - 3 * h;
  const uint32_t sb = mapa(CH_BASE, j);
  const uint32_t bWo = sb + CH_BAR, bWq = bWo + 8, bX = bWo + 16, bXA = bWo + 24, bXB = bWo + 32, bO = bWo + 40, bG = bWo + 48, bH = bWo + 96;
  uint32_t tw[4 * CH_TW];
  auto refill = [&]() {
#pragma unroll
    for (int k = 0; k < CH_TW; k++) ldsm4t(&tw[4 * k], wq + k * 2048);
  };
  const uint32_t wo = opaque((sb + CH_WO + (WG == 0 ? (t4 + (j == 2)) * 4096 : (j == 2 ? 0 : 24576) + t4 * 1024) + ((lane & 7) + (lane >> 4) * 8) * 64 +
                              ((((lane >> 3) & 1) ^ ((lane >> 1) & 3)) << 4)) ^ (WG == 1 && j == 2 ? 32 : 0));
  const uint32_t wo2 = opaque((wo ^ ((t4 & 1) * 32)) + (4 + (t4 >> 1) - t4) * 4096);
  const uint32_t l16 = opaque(sb + lane * 16);
  const uint32_t l8 = opaque(sb + t4 * 256 + lane * 8);
  const uint32_t lw = opaque(sb + t4 * 1024 + lane * 16);
  const uint32_t qs = opaque(sb + CH_QK + WG * 2048 + t4 * 512 + lane * 16);
  const uint32_t qa = opaque(sb + CH_QK + (lane >> 4) * 2048 + (lane & 15) * 16 + (WG == 0 ? t4 * 512 + 256 : t4 == 3 ? 1024 : 0));
  const uint32_t ka = opaque(t4 < 2 ? sb + CH_KT + t4 * 512 + lane * 16
                                    : sb + CH_QK + 256 + (t4 - 2) * 1024 + ((lane >> 3) & 1) * 2048 + (lane >> 4) * 128 + (lane & 7) * 16);
  const uint32_t l4 = opaque(sb + t4 * 256 + lane * 4);
  uint32_t pdst[1], pages = 0;
  auto line0 = [&](int i) { return 28 * j + (i < 4 ? 4 * t4 + i : 12 + 2 * t4 + i); };
  const uint32_t plane = opaque((lane >> 4) * 2048 + h * 64 + (lane & 15) * 4);
  if (WG == 0) {
    pages = __ballot_sync(~0u, lds32(sb + CH_O + line0(min(lane, 5)) * 4) & 4096);
  } else {
    pages = __ballot_sync(~0u, lds32(sb + CH_O + (80 + min(lane, 11)) * 4) & 4096);
    pdst[0] = opaque(lds32(sb + CH_O + (j == 0 ? 24 + t4 : 50 + 2 * j + (t4 & 1)) * 4) + plane);
  }
  const uint32_t role = lds32(sb + CH_O + NSLOT * 4), rsrc = lds32(sb + CH_O + role * 4), rdst = (80 + role / 20) * 8192 + role % 20 * 128;
  const uint32_t r1 = mapa(CH_BASE, j == 2 ? 0 : j + 1) - sb, r2 = mapa(CH_BASE, j == 0 ? 2 : j - 1) - sb;
  uint32_t tag = opaque(1);
  auto pool = [&](uint32_t off) { return p.pool + ((tag & 0xfffe) + off); };
  auto after = [&](uint32_t x) { return x & tag & 0xfffe; };
  auto kv = [&](int s, uint32_t a) { return p.kv + (a + ((cta * 2 * NSEG + s) * KV_BYTES - sb)); };
  auto pass = [&](float (&d)[16], const uint32_t (&a)[80], auto k0, auto k1) {
    const uint64_t db = mkdesc(CH_BASE + CH_X + WG * 20480, 512, 128, 0);
#pragma unroll
    for (int k = k0.value; k < k1.value; k++) wg_rs32_00(d, a[4 * k], a[4 * k + 1], a[4 * k + 2], a[4 * k + 3], db + k * 64, k);
    wg_commit();
  };
  auto dump = [&](float (&d)[16], uint32_t a) {
    reg_fence<16>(d);
    sts128(a, pack8(d)); sts128(a + 512, pack8(d + 8));
  };
  uint32_t pph = 0;
  auto tokens0 = [&](int s, auto k0) {
    float dk[16], dv[16];
    bar_sync(9, 256);
    wg_fence();
    pass(dk, ak, Int<0>(), Int<4>());
    const uint4 a0 = lds128(lw + CH_KT), a1 = lds128(lw + CH_KT + 512);
    pin();
    pass(dk, ak, Int<4>(), Int<20>());
    pass(dv, av, Int<0>(), Int<CH_VA>());
    pin();
    wg_wait<1>();
    reg_fence<16>(dk);
    add8(dk, a0); add8(dk + 8, a1);
    const uint4 w0 = pack8(dk), w1 = pack8(dk + 8);
    const uint4 b0 = lds128(lw + CH_VT), b1 = lds128(lw + CH_VT + 512);
    stsm4t(lw + CH_KT, w0.x, w0.z, w0.y, w0.w); stsm4t(lw + CH_KT + 512, w1.x, w1.z, w1.y, w1.w);
    if (CH_KP == 2) bar_arrive(7, 160);
    TM1(6);
    pin();
    if (CH_VA < 20) pass(dv, av, Int<CH_VA>(), Int<20>());
    pin();
#pragma unroll
    for (int k = k0.value; k < CH_TW; k++) ldsm4t(&tw[4 * k], wq + k * 2048);
    TM1(9);
    if (k0.value < CH_TW && t4 >= 2) { mbar_wait_hot(bH + t4 * 16 - 24 + (pph & 1) * 8, pph >> 1 & 1); pph++; }
    __syncwarp();
    wg_wait<0>();
    reg_fence<16>(dv);
    add8(dv, b0); add8(dv + 8, b1);
#pragma unroll
    for (int e = 0; e < 2; e++) { const uint4 v = pack8(dv + 8 * e); sts128(lw + CH_VT + e * 512, make_uint4(v.x, v.z, v.y, v.w)); }
  };
  auto publish_k = [&](int s) {
    if (t4 == CH_KW && elect()) { fence_async(); bulk_store(p.kv + (size_t)(cta * 2 * NSEG + s) * KV_BYTES, sb + CH_KT, 4096); bulk_commit(); }
    __syncwarp();
  };
  if (WG == 0) {
    mbar_wait(bXB, 0);
    tokens0(0, Int<CH_TW>());
  } else {
    const uint32_t* m0 = reinterpret_cast<const uint32_t*>(p.mem0) + (lane >> 2) * 320 + t4 * 80 + (lane & 3);
    uint32_t a[20];
#pragma unroll
    for (int i = 0; i < 20; i++) a[i] = m0[4 * i];
    pin();
    float dk[16], dv[16];
    mbar_wait(bXA, 0);
    wg_fence();
    pass(dk, ak, Int<0>(), Int<20>());
    pass(dv, av, Int<0>(), Int<20>());
    wg_wait<0>();
    dump(dk, lw + CH_KT);
    dump(dv, lw + CH_VT);
    bar_sync(9, 256);
    if (CH_KP == 2 && t4 == CH_KW) { bar_sync(7, 160); publish_k(0); }
#pragma unroll
    for (int i = 0; i < 20; i++) sts32(sb + CH_M + (t4 * 20 + i) * 128 + lane * 4, nz(transpose8(a[i])));
    __syncwarp();
    if (elect()) mbar_arrive(bG + t4 * 8);
  }
  PRO(8);
  mbar_wait(bWq, 0);
  refill();
  PRO(9);
  mbar_wait(bWo, 0);
  asm volatile("barrier.cluster.wait.aligned;" ::: "memory");
  PRO(10);
  auto load_x = [&](int s, int k0, int n, uint32_t bar) {
    if (!NOX && elect()) { mbar_expect(bar, n * 1024); bulk_load(sb + CH_X + k0 * 1024, p.xc + (s + 1) * 10240 + k0 * 256, n * 1024, bar); }
  };
  constexpr int VK = WG == 0 ? CH_VK0 : CH_VK1;
  uint32_t gph = 0;
  int st = 0;
  const uint32_t ca = opaque(sb + CH_M + t4 * 2560 + lane * 32 + (lane >> 2) * 4);
  auto project = [&](int s, uint32_t (&b)[40], float (&dv)[16], uint32_t (&kf)[16]) {
    float dq[4] = {}, dk[4] = {};
    uint32_t w[80];
#pragma unroll
    for (int i = 0; i < 4 * CH_TW; i++) w[i] = tw[i];
    constexpr int LR = WG == 1 ? CH_LR1 : CH_LR;
    auto load = [&](int n) {
      int c = 0;
#pragma unroll
      for (int i = 0; i < 10; i++) {
        if (i == CH_KF) {
#pragma unroll
          for (int q = 0; q < 4; q++)
            if (WG == 1 && c++ == n) ldsm4(&kf[4 * q], ka + q * 1024);
        }
        if (c++ == n) ldsm4t(&b[4 * i], l16 + CH_M + WG * 5120 + i * 512);
#pragma unroll
        for (int k = 2 * i; k < 2 * i + 2; k++)
          if (k >= CH_TW && c++ == n) ldsm4t(&w[4 * k], wq + k * 2048);
      }
#pragma unroll
      for (int i = 0; i < 4; i++)
        if (WG == 1 && CH_KF >= 10 && c++ == n) ldsm4(&kf[4 * i], ka + i * 1024);
    };
    if (WG == 1) {
      for (int n = 0;;) {
        mbar_wait(bG + t4 * 8, gph);
        TR(5, (clk32() & ~3u) | min(n, 3));
        gph ^= 1;
        if (__builtin_expect(!__any_sync(~0u, __vimin3_u32(lds32(ca), lds32(ca + 1024), lds32(ca + 1536)) == 0), 1)) break;
        if (elect()) {
          const int q = (st == 0 ? 8 : st * 4 - 4) + t4;
          mbar_expect(bG + t4 * 8, 2560);
          bulk_load(sb + CH_M + t4 * 2560, p.pool + ((80 + q) * 8192 + (pages >> q & 1) * 4096), 2560, bG + t4 * 8);
        }
        spin_guard(n);
      }
    }
    bar_sync(6, 256);
#pragma unroll
    for (int i = 0; i < CH_L0; i++) load(i);
    if (WG == 0 && CH_XB == 4 && s + 1 < NSEG) load_x(s, 5 * t4, 5, bXB);
    TM(0);
    TM1(11);
    if (WG == 1) TR(6, clk32());
#pragma unroll
    for (int k = 0; k < 20; k += 2) {
      if (k > 0) {
#pragma unroll
        for (int n = (k == 18 ? 40 : CH_L0 + k * LR / 4) - 1; n >= CH_L0 + (k - 2) * LR / 4; n--) { load(n); if (CH_LO) __syncwarp(); }
      }
      pin();
#pragma unroll
      for (int kk = k; kk < k + 2; kk++) {
        mma16(dk, ak[4 * kk], ak[4 * kk + 1], ak[4 * kk + 2], ak[4 * kk + 3], b[2 * kk], b[2 * kk + 1]);
        mma16(dq, w[4 * kk], w[4 * kk + 1], w[4 * kk + 2], w[4 * kk + 3], b[2 * kk], b[2 * kk + 1]);
        if (kk < VK) mma16(dv, av[4 * kk], av[4 * kk + 1], av[4 * kk + 2], av[4 * kk + 3], b[2 * kk], b[2 * kk + 1]);
      }
    }
    const float k2 = 0.07216878364870322f * 1.44269504089f;
    stsm4t(qs, pack2(dq[0] * k2, dq[1] * k2), pack2(dq[2] * k2, dq[3] * k2), pack2(dk[0], dk[1]), pack2(dk[2], dk[3]));
    TM(1);
  };
  constexpr int VC = VK == 20 ? 1 : WG == 0 ? 2 : 3;
  auto finish_v = [&](const uint32_t (&b)[40], float (&dv)[16]) {
#pragma unroll
    for (int kk = VK; kk < 20; kk++) mma16(dv + 4 * ((kk - VK) % VC), av[4 * kk], av[4 * kk + 1], av[4 * kk + 2], av[4 * kk + 3], b[2 * kk], b[2 * kk + 1]);
  };
  auto sum_v = [&](float (&dv)[16]) {
#pragma unroll
    for (int i = 4; i < 4 * VC; i++) dv[i & 3] += dv[i];
  };
  auto publish_km = [&](int s) {
    uint32_t a[4];
    ldsm4(a, qa);
    *reinterpret_cast<uint2*>(kv(s, l8) + KV_M) = make_uint2(hadd2(a[0], a[2]), hadd2(a[1], a[3]));
  };
  auto memory_v = [&](uint2 x, const float (&dv)[16]) {
    return make_uint2(pack2(dv[0] + bf_lo(x.x), dv[1] + bf_hi(x.x)), pack2(dv[2] + bf_lo(x.y), dv[3] + bf_hi(x.y)));
  };
  auto publish_v = [&](int s, const uint4 (&v)[2], uint2 vm) {
#pragma unroll
    for (int e = 0; e < 2; e++) reinterpret_cast<uint4*>(kv(s, lw) + KV_V)[e * 32] = v[e];
    *reinterpret_cast<uint2*>(kv(s, l8) + KV_V + KV_M) = vm;
  };
#pragma unroll 1
  for (int s = 0; s < NSEG - 1; s++) {
    float dv[16] = {};
    uint32_t b[40], kf[16];
    project(s, b, dv, kf);
    if (WG == 0) {
      bar_sync(1, 256);
      if (CH_XA == 0) load_x(s, 20 + 5 * t4, 5, bXA);
      if (CH_XB == 0) load_x(s, 5 * t4, 5, bXB);
      pin();
      finish_v(b, dv);
      sum_v(dv);
      sts64(l8 + CH_VP, pack2(dv[0], dv[1]), pack2(dv[2], dv[3]));
      __syncwarp();
      if (elect()) mbar_arrive(bX);
      if (CH_XA == 1) load_x(s, 20 + 5 * t4, 5, bXA);
      if (CH_XB == 1) load_x(s, 5 * t4, 5, bXB);
      uint32_t w[144];
      auto wload = [&](int i) { ldsm4t(&w[4 * i], (i % 3 == 0 ? wo : i % 3 == 1 ? wo ^ 32 : wo2) + i / 12 * 28672 + i / 3 % 4 * 1024); };
      TM(3);
      if (CH_KP == 0) publish_k(s);
#pragma unroll
      for (int i = 0; i < CH_W1; i++) wload(i);
      bar_sync(10, 256);
      uint32_t km[4];
      ldsm4(km, qa);
      pin();
#pragma unroll
      for (int i = CH_W1; i < CH_W2; i++) wload(i);
      pin();
      const uint2 kms = make_uint2(hadd2(km[0], km[2]), hadd2(km[1], km[3]));
      if (CH_KM == 0) *reinterpret_cast<uint2*>(kv(s, l8) + KV_M) = kms;
      if (CH_KP == 0) bulk_wait_read<0>();
      if (CH_XA == 2) load_x(s, 20 + 5 * t4, 5, bXA);
      if (CH_XB == 2) load_x(s, 5 * t4, 5, bXB);
      bar_sync(2, 256);
      {
        float y[3][4] = {};
        uint32_t ob[24];
        ldsm4(&ob[0], l16 + CH_O + 1024); ldsm4(&ob[4], l16 + CH_O + 1536);
        TM(7);
        auto step = [&](int i) {
          const int k = i / 3;
          mma16(y[i % 3], w[4 * i], w[4 * i + 1], w[4 * i + 2], w[4 * i + 3], ob[2 * k], ob[2 * k + 1]);
        };
#pragma unroll
        for (int i = 0; i < 12; i++) {
          step(i);
          if (i >= 12 - (CH_W3 - CH_W2)) wload(CH_W3 - 12 + i);
          if (i % 3 == 2) pin();
        }
        if (CH_XB == 3) load_x(s, 5 * t4, 5, bXB);
        if (CH_KM == 1) *reinterpret_cast<uint2*>(kv(s, l8) + KV_M) = kms;
        pin();
        mbar_wait(bO, s & 1);
        TM(4);
        ldsm4(&ob[8], l16 + CH_O); ldsm4(&ob[12], l16 + CH_O + 512);
        pin();
        float2 inv;
        uint8_t* dst[6];
        uint32_t mask;
#pragma unroll
        for (int i = 12; i < 36; i++) {
          step(i);
          const int n = CH_W3 + i - 13, m = n - (n > 30);
          if (i == 12) ldsm4(&ob[16], l16 + after(w[4 * CH_W3 - 1] | w[4 * CH_W3 - 5] | w[4 * CH_W3 - 9] | ob[8]) + CH_O + 2048);
          else if (n == 30) ldsm4(&ob[20], l16 + CH_O + 2560);
          else if (m < 36) wload(m);
          else if (m == 36) inv = lds64f((l8 & ~0xe0u) + CH_VP);
          if (i == 26) mask = ((l16 ^ tag) & 48) == 0;
          if (i >= 27 && i < 33) dst[i - 27] = pool(line0(i - 27) * 8192 + (pages >> (i - 27) & 1) * 4096) + plane;
          if (i % 3 == 2) pin();
        }
#pragma unroll
        for (int k = 0; k < CH_R1; k++) ldsm4t(&tw[4 * k], wq + k * 2048);
        pin();
#pragma unroll
        for (int i = 0; i < 6; i++) stg_strong32(dst[i], pack_tag(y[i >> 1][2 * (i & 1)] * inv.x, y[i >> 1][2 * (i & 1) + 1] * inv.y, tag, mask));
        TM(8);
        TR(0, clk32());
        bar_arrive(5, 256);
        pin();
      }
      const uint32_t t0 = clk32();
      auto refill2 = [&]() {
#pragma unroll
        for (int k = CH_R1; k < CH_R2; k++) ldsm4t(&tw[4 * k], wq + k * 2048);
      };
      if (CH_RP == 0) refill2();
      const uint32_t ln = (l16 ^ tag) >> 4 & 31;
      if (t4 >= 2) {
        const uint32_t bP = bH + t4 * 16 - 24, ps = CH_PS + (t4 & 1) * 4096;
        auto fetch = [&](uint32_t k) {
          if (elect()) { mbar_expect(bP + (k & 1) * 8, 2048); bulk_load(sb + ps + (k & 1) * 2048, p.pool + (rsrc + (t4 & 1) * 2048), 2048, bP + (k & 1) * 8); }
        };
        until(t0 + CH_D0);
        fetch(pph);
        if (CH_RP == 2) refill2();
        if (!NOX) mbar_wait_hot(bXB, (s + 1) & 1);
        const uint32_t want = (tag & 1) * 0x10001, chk = opaque(ln < 4 ? 0x10001 : 0);
        uint4 sel;
        sel.x = opaque((ln >> 3) != (ln & 1) ? 0 : ln & 4 ? 0x3f800000u : 0x00003f80u);
        sel.z = opaque(sel.x); sel.y = opaque(ln); sel.w = opaque(ln + 1);
        uint8_t* mdst = p.pool + opaque(st * 32768 + rdst + (t4 & 1) * 64 + ln * 4);
        until(t0 + CH_D1);
        fetch(pph + 1);
        TM(5);
        if (CH_RP == 1) refill2();
        int n = 0;
        uint32_t u[16];
        for (;;) {
          mbar_wait(bP + (pph & 1) * 8, pph >> 1 & 1);
          TM(14);
          TR(2, clk32());
#pragma unroll
          for (int i = 0; i < 4; i++) ldsm4t(&u[4 * i], l16 + (ps + (pph & 1) * 2048) + i * 512);
          pph++;
          uint32_t bad = 0;
#pragma unroll
          for (int i = 0; i < 4; i++) bad = or3(bad, differ(u[4 * i], u[4 * i + 1], want), differ(u[4 * i + 2], u[4 * i + 3], want));
          if (!__any_sync(~0u, bad & chk)) break;
          fetch(pph + 1);
          spin_guard(n);
        }
        float y[4][4] = {};
#pragma unroll
        for (int i = 0; i < 8; i++) mma16(y[i & 3], sel.x, sel.y, sel.z, sel.w, u[2 * i], u[2 * i + 1]);
        TR(1, t0 + (n ? CH_D1 : CH_D0));
        TM(15);
        const uint32_t w = nz(pack2((y[0][0] + y[1][0]) + (y[2][0] + y[3][0]), (y[0][1] + y[1][1]) + (y[2][1] + y[3][1])));
        if (ln < 16) { stg_strong32(mdst, w); stg_strong32(mdst + 4096, w); }
        TMV(12, 32, n);
        TR(3, (clk32() & ~3u) | min(n, 3));
      } else {
        if (CH_RP) refill2();
        if (!NOX) mbar_wait_hot(bXB, (s + 1) & 1);
        stg_strong32(p.pool + ((st == 2 ? 0 : st + 1) * 32768 + rdst + t4 * 4096) + ln * 4, 0u);
        if (t4 == 0 && cta < 40 && s + 4 < NSEG && elect())
          asm volatile("cp.async.bulk.prefetch.L2.global [%0], 1024;" :: "l"(p.xc + (s + 4) * 10240 + cta * 256) : "memory");
        if (t4 == 1 && (s & 3) == 0 && s > 0 && elect()) red_relaxed(p.sync + 2 * s - 4, 1);
        if (t4 == 1 && s == NSEG - 3 && cta == 95 && elect()) red_relaxed(p.sync + 2 * s + 2, 0x10000);
      }
      TM(10);
      bar_arrive(8, 256);
      tokens0(s + 1, Int<CH_R2>());
      TM(2);
      TR(7, clk32());
    } else {
      const uint32_t xo = l4 + (CH_SX - (t4 == 3 ? 128 : 0)), x1 = xo + (r1 + 768 + min(t4, 2) * 256), x2 = xo + (r2 + 1024 + min(t4, 2) * 256);
      if (t4 < 2) {
        float ds[4][4] = {};
        uint32_t q[16];
        asm volatile("bar.sync 1, 256;" ::: "memory");
#pragma unroll
        for (int k = 0; k < 4; k++) ldsm4(&q[4 * k], qa + k * 512);
        pin();
        if (VK < 20) { finish_v(b, dv); pin(); }
#pragma unroll
        for (int k = 0; k < 4; k++) {
          mma16(ds[k & 1], kf[4 * k], kf[4 * k + 1], kf[4 * k + 2], kf[4 * k + 3], q[4 * k], q[4 * k + 1]);
          mma16(ds[2 + (k & 1)], kf[4 * k], kf[4 * k + 1], kf[4 * k + 2], kf[4 * k + 3], q[4 * k + 2], q[4 * k + 3]);
        }
        float t[4];
#pragma unroll
        for (int i = 0; i < 4; i++) t[i] = (ds[0][i] + ds[2][i]) + (ds[1][i] + ds[3][i]);
        const uint32_t w0 = pack2(t[0], t[1]), w1 = pack2(t[2], t[3]);
        st_async32(x1, w0, bX + r1); st_async32(x2, w0, bX + r2);
        st_async32(x1 + 128, w1, bX + r1); st_async32(x2 + 128, w1, bX + r2);
        sts32(xo, w0); sts32(xo + 128, w1);
      } else {
        float ds[4][4] = {};
        uint32_t q0[4], q1[4], a0[4], a1[4];
        asm volatile("bar.sync 1, 256; " ::: "memory");
        ldsm4(a0, ka); ldsm4(q0, qa); ldsm4(a1, ka + 512); ldsm4(q1, qa + 512);
        pin();
        if (VK < 20) { finish_v(b, dv); pin(); }
        mma16(ds[0], a0[0], a0[1], a0[2], a0[3], q0[0], q0[1]);
        mma16(ds[1], a0[0], a0[1], a0[2], a0[3], q0[2], q0[3]);
        mma16(ds[2], a1[0], a1[1], a1[2], a1[3], q1[0], q1[1]);
        mma16(ds[3], a1[0], a1[1], a1[2], a1[3], q1[2], q1[3]);
        float t[2];
#pragma unroll
        for (int i = 0; i < 2; i++)
          t[i] = ((ds[0][i] + ds[0][i + 2]) + (ds[1][i] + ds[1][i + 2])) + ((ds[2][i] + ds[2][i + 2]) + (ds[3][i] + ds[3][i + 2]));
        const uint32_t w0 = pack2(t[0], t[1]);
        st_async32(x1, w0, bX + r1);
        st_async32(x2, w0, bX + r2);
        sts32(xo, w0);
      }
      TM(3);
      const uint4 id = lds128(l16 + CH_ID);
      float sc[3][4] = {};
      uint4 v[2];
      sum_v(dv);
      bar_sync(3, 128);
      uint32_t r[12], wd[12], we[12] = {};
      ldsm4(&r[0], l16 + CH_SX); ldsm2(&r[4], l16 + CH_SX + 512);
      pin();
      v[0] = lds128(lw + CH_VT); v[1] = lds128(lw + CH_VT + 512);
#pragma unroll
      for (int u = 0; u < 3; u++) ldsm4t(&wd[4 * u], wo + u * 28672);
      if (CH_WE && j == 0) {
#pragma unroll
        for (int u = 0; u < 3; u++) ldsm4t(&we[4 * u], (wo ^ 32) + u * 28672);
      }
      pin();
#pragma unroll
      for (int q = 0; q < 3; q++) mma16(sc[q], id.x, id.y, id.z, id.w, r[2 * q], r[2 * q + 1]);
      uint32_t big = absmax2(absmax2(absmax2(r[0], r[1]), absmax2(r[2], r[3])), absmax2(r[4], r[5]));
      const uint32_t oa1 = l4 + (r1 + CH_O), oa2 = l4 + (r2 + CH_O + 2048), ones = 0x3f803f80u;
      mbar_wait_hot(bX, s & 1);
      TM(4);
      ldsm4(&r[0], l16 + CH_SX + 768); ldsm4(&r[8], l16 + CH_SX + 1792); ldsm4(&r[4], l16 + CH_SX + 1280);
      const uint2 vp = lds64(l8 + CH_VP);
      bar_arrive(10, 256);
      pin();
      {
        float sd[3][4] = {};
#pragma unroll
        for (int i = 0; i < 3; i++) {
          const int q = i == 0 ? 0 : 3 - i;
          mma16(sc[q], id.x, id.y, id.z, id.w, r[4 * q], r[4 * q + 1]);
          mma16(sd[q], id.x, id.y, id.z, id.w, r[4 * q + 2], r[4 * q + 3]);
          big = absmax2(big, absmax2(absmax2(r[4 * q], r[4 * q + 1]), absmax2(r[4 * q + 2], r[4 * q + 3])));
        }
#pragma unroll
        for (int i = 0; i < 12; i++) sc[i >> 2][i & 3] += sd[i >> 2][i & 3];
      }
      const bool redo = __any_sync(~0u, (absmax2(big, big << 16) & 0x7fff0000u) >= 0x41800000u);
      const uint2 vm = memory_v(vp, dv);
      sc[2][0] += sc[2][2]; sc[2][1] += sc[2][3];
      float l[4], o[2][4];
      uint32_t p3, p4;
      auto attend = [&]() {
#pragma unroll
        for (int i = 0; i < 4; i++) l[i] = o[0][i] = o[1][i] = 0.f;
        const uint32_t p1 = pack2(ex2(sc[0][0]), ex2(sc[0][1])), p2 = pack2(ex2(sc[0][2]), ex2(sc[0][3]));
        mma16h(o[0], p1, p2, v[0].x, v[0].y);
        mma16h(o[1], p1, p2, v[0].z, v[0].w);
        mma16h(l, p1, p2, ones, ones);
        const uint32_t p0 = pack2(ex2(sc[2][0]), ex2(sc[2][1]));
        mma8h(o[0], p0, vm.x);
        mma8h(o[1], p0, vm.y);
        mma8h(l, p0, ones);
        p3 = pack2(ex2(sc[1][0]), ex2(sc[1][1])); p4 = pack2(ex2(sc[1][2]), ex2(sc[1][3]));
        mma16h(o[0], p3, p4, v[1].x, v[1].y);
        mma16h(o[1], p3, p4, v[1].z, v[1].w);
      };
      attend();
      if (__builtin_expect(redo, 0)) {
        float mx = fmaxf(sc[2][0], sc[2][1]);
#pragma unroll
        for (int i = 0; i < 4; i++) mx = fmaxf(mx, fmaxf(sc[0][i], sc[1][i]));
        mx = fmaxf(mx, __shfl_xor_sync(~0u, mx, 1));
        mx = fmaxf(mx, __shfl_xor_sync(~0u, mx, 2));
#pragma unroll
        for (int i = 0; i < 4; i++) { sc[0][i] -= mx; sc[1][i] -= mx; }
        sc[2][0] -= mx; sc[2][1] -= mx;
        attend();
      }
      const uint32_t o0 = pack2(o[0][0], o[0][1]), o1 = pack2(o[1][0], o[1][1]);
      st_async32(oa1, o0, bO + r1); st_async32(oa2, o0, bO + r2);
      st_async32(oa1 + 128, o1, bO + r1); st_async32(oa2 + 128, o1, bO + r2);
      sts32(l4 + CH_O + 1024, o0); sts32(l4 + CH_O + 1152, o1);
      bar_arrive(2, 256);
      pin();
      TM(6);
      mma16h(l, p3, p4, ones, ones);
      float inv;
      asm("rcp.approx.ftz.f32 %0, %1;" : "=f"(inv) : "f"(l[0]));
      sts32((l8 & ~0xffu) + (lane & 28) + CH_VP, __float_as_uint(inv));
      __syncwarp();
      if (elect()) mbar_arrive(bO);
      {
        float z[2][4] = {}, y[2][4] = {};
        mma16(z[0], wd[0], wd[1], wd[2], wd[3], o0, o1);
        if (j == 0) {
#pragma unroll
          for (int u = 0; u < 3; u++) if (!CH_WE) ldsm4t(&we[4 * u], (wo ^ 32) + u * 28672);
          mma16(y[0], we[0], we[1], we[2], we[3], o0, o1);
        }
        const float2 iv = lds64f((l8 & ~0xe0u) + CH_VP);
        uint8_t* dst = pool(pdst[0]);
        const uint32_t mask = ((l16 ^ tag) & 48) == 0;
        const uint32_t oa = qa + ((tag & 0xfffe) + CH_O - CH_QK + t4 * 256 - (t4 == 3 ? 1024 : 0));
        const uint32_t za = l16 + ((tag & 0xfffe) + (t4 >> 1) * 512 + (t4 & 1) * 8);
        pin();
        mbar_wait(bO, s & 1);
        uint32_t a[4];
        ldsm4(a, oa);
        mma16(z[0], wd[4], wd[5], wd[6], wd[7], a[0], a[1]);
        mma16(z[1], wd[8], wd[9], wd[10], wd[11], a[2], a[3]);
        if (j == 0) {
          mma16(y[0], we[4], we[5], we[6], we[7], a[0], a[1]);
          mma16(y[1], we[8], we[9], we[10], we[11], a[2], a[3]);
          sts128f(lw + CH_VT + 512, y[0][0] + y[1][0], y[0][1] + y[1][1], y[0][2] + y[1][2], y[0][3] + y[1][3]);
        }
        sts128f(lw + CH_VT, z[0][0] + z[1][0], z[0][1] + z[1][1], z[0][2] + z[1][2], z[0][3] + z[1][3]);
        bar_sync(3, 128);
        if (j == 0 || t4 < 2) {
          float2 q[4];
#pragma unroll
          for (int i = 0; i < 4; i++) q[i] = lds64f(za + CH_VT + i * 1024);
          stg_strong32(dst, pack_tag(((q[0].x + q[1].x) + (q[2].x + q[3].x)) * iv.x, ((q[0].y + q[1].y) + (q[2].y + q[3].y)) * iv.y, tag, mask));
        }
      }
      TM(2);
      if (!NOX) mbar_wait_hot(bXA, (s + 1) & 1);
      if (CH_KP == 2) bulk_wait_read<0>();
      float dk[16], dw[16];
      bar_sync(5, 256);
      wg_fence();
      pass(dk, ak, Int<0>(), Int<20>());
      pass(dw, av, Int<0>(), Int<20>());
      TM(5);
      pin();
      if (CH_EX == 0) publish_v(s, v, vm);
      if (elect()) {
        mbar_expect(bG + t4 * 8, 2560);
        if (t4 == 1 && s + 2 < NSEG) { mbar_expect(bX, 1536); mbar_expect(bO, 2048); }
      }
      if (CH_KD == 0) { wg_wait<1>(); dump(dk, lw + CH_KT); }
      wg_wait<0>();
      if (CH_KD == 1) dump(dk, lw + CH_KT);
      TM(7);
      dump(dw, lw + CH_VT);
      bar_arrive(9, 256);
      pin();
#pragma unroll
      for (int k = 0; k < CH_RB; k++) ldsm4t(&tw[4 * k], wq + k * 2048);
      if (t4 < 2) {
#pragma unroll
        for (int k = CH_RB; k < CH_RC; k++) ldsm4t(&tw[4 * k], wq + k * 2048);
        const int q = t4 ? 3 : j, o = t4 ? j * 896 : 0;
        const uint8_t* src = p.pool + ((80 + st * 4 + q) * 8192 + (pages >> (st * 4 + q) & 1) * 4096 + o);
        asm volatile("bar.sync 8, 256;" ::: "memory");
        const uint32_t t1 = clk32() + CH_D2;
        if (CH_EX == 1) publish_v(s, v, vm);
        auto fetch = [&](auto n) {
          mbar_wait(bH, s & 1);
          until(t1);
          TR(4, clk32());
          if (elect())
            asm volatile("cp.async.bulk.shared::cluster.global.mbarrier::complete_tx::bytes.multicast::cluster [%0], [%1], %2, [%3], 7;"
                         :: "r"(sb + CH_M + q * 2560 + o), "l"(src), "n"(n.value), "r"(bG + q * 8) : "memory");
        };
        if (!t4) fetch(Int<2560>()); else if (j == 2) fetch(Int<768>()); else fetch(Int<896>());
      } else {
        asm volatile("bar.sync 8, 256; " ::: "memory");
        if (elect()) asm volatile("mbarrier.arrive.relaxed.cluster.shared::cluster.b64 _, [%0];" :: "r"(bH + (t4 == 2 ? r1 : r2)) : "memory");
        pin();
        if (CH_EX == 1) publish_v(s, v, vm);
#pragma unroll
        for (int k = CH_RB; k < CH_RC; k++) ldsm4t(&tw[4 * k], wq + k * 2048);
      }
      TM(9);
      pin();
#pragma unroll
      for (int k = CH_RC; k < CH_TW; k++) ldsm4t(&tw[4 * k], wq + k * 2048);
      if (CH_KP == 2 && t4 == CH_KW) { bar_sync(7, 160); publish_k(s + 1); }
      TM(10);
    }
    if (++st == 3) st = 0;
    tag ^= 0x10001;
  }
  {
    const int s = NSEG - 1;
    float dv[16] = {};
    uint32_t b[40], kf[16];
    project(s, b, dv, kf);
    finish_v(b, dv);
    sum_v(dv);
    if (WG == 0) {
      sts64(l8 + CH_VP, pack2(dv[0], dv[1]), pack2(dv[2], dv[3]));
      bar_sync(1, 256);
      if (CH_KP == 0) publish_k(s);
      publish_km(s);
      bulk_wait<0>();
      fence_async_global();
      bar_sync(2, 256);
      if (tid == 0) red_release(g_sync + 15 * 8 + 4, 1);
    } else {
      const uint4 v[2] = {lds128(lw + CH_VT), lds128(lw + CH_VT + 512)};
      bar_sync(1, 256);
      publish_v(s, v, memory_v(lds64(l8 + CH_VP), dv));
      bulk_wait<0>();
      fence_async_global();
      bar_arrive(2, 256);
    }
  }
}

__global__ void __launch_bounds__(256, 1) chain_kernel(const __grid_constant__ ChainParams p) {
  extern __shared__ __align__(1024) uint8_t smem_raw[];
  const uint32_t sb = s2u(smem_raw);
  const int tid = threadIdx.x, warp = __shfl_sync(~0u, tid >> 5, 0), lane = tid & 31;
  const int cta = blockIdx.x, h = cta / 3, j = cta - 3 * h, colbase = cta * 64;
  const uint32_t bWo = sb + CH_BAR, bWq = bWo + 8, bXA = bWo + 24, bWk = bWo + 80, bWv = bWo + 88;
  uint32_t smid; asm("mov.u32 %0, %%smid;" : "=r"(smid));
  PRO(0);
  if (sb != mapa(CH_BASE, j)) __trap();
  uint32_t entry = 0;
  auto place = [&]() {
    const int i = tid - 128;
    if (i >= 0 && i <= NSLOT) {
      const uint32_t side = ldg_strong32(g_smpart + (smid & 255));
      if (i < NSLOT) {
        entry = i * 8192 + (ldg_strong32(g_orient + i) == (i < 80 ? i & 1 : side) ? 0 : 4096);
      } else {
        entry = 2 * (atomicAdd(g_bo + p.layer * 128 + 1, 1 << 8 * side) >> 8 * side & 255) + side;
      }
    }
    __syncwarp();
  };
  if (p.layer) place();
  if (warp == 0 && elect()) {
#pragma unroll 1
    for (int i = 0; i < 17; i++) mbar_init(bWo + 8 * i, i == 2 || i == 5 ? 5 : i == 3 || i == 4 ? 4 : i == 12 ? 2 : 1);
    asm volatile("fence.mbarrier_init.release.cluster;" ::: "memory");
    mbar_expect(bWk, 81920);
    tma_load3<(WEF & 1) != 0>(sb + CH_WQ, &p.wk, colbase, 0, bWk);
    mbar_expect(bWv, 81920);
    tma_load3<(WEF & 1) != 0>(sb + CH_WO, &p.wv, colbase, 0, bWv);
    mbar_expect(bWo + 16, 1536);
    mbar_expect(bWo + 40, 2048);
    mbar_expect(bWo, 86016); mbar_expect(bWq, 81920);
#pragma unroll 1
    for (int i = 0; i < 8; i++) mbar_expect(bXA + 8 * (i & 1), 5120);
  }
  if (warp == 1) {
    const uint32_t id = (lane >> 3) == (lane & 3) ? ((lane & 4) ? 0x3f800000u : 0x00003f80u) : 0u;
    sts128(sb + CH_ID + lane * 16, make_uint4(id, 0, 0, id));
  }
  __syncthreads();
  asm volatile("barrier.cluster.arrive.relaxed.aligned;" ::: "memory");
  uint32_t ak[80], av[80];
  const uint32_t wq = opaque(sb + CH_WQ + ((warp >> 2) * 320 + (lane & 7) + (lane >> 4) * 8) * 128 + (((2 * (warp & 3) + ((lane >> 3) & 1)) ^ (lane & 7)) << 4));
  pdl_wait();
  if (tid == 32) stg_strong32(g_smuse + (smid & 255), p.layer + 1);
  pdl_launch();
  PRO(1);
  if (warp == 0 && elect()) {
    bulk_load(sb + CH_X + 20480, p.xc + 5120, 20480, bXA);
    bulk_load(sb + CH_X, p.xc, 20480, bXA + 8);
  }
  if (!p.layer) place();
  __syncwarp();
  PRO(2);
  mbar_wait(bWk, 0);
  PRO(3);
#pragma unroll
  for (int k = 0; k < 20; k++) ldsm4t(&ak[4 * k], wq + k * 2048);
  bar_sync(6, 256);
  if (warp == 0 && elect()) tma_load3<(WEF & 2) != 0>(sb + CH_WQ, &p.wq, colbase, 0, bWq);
  __syncwarp();
  PRO(4);
  mbar_wait(bWv, 0);
  PRO(5);
#pragma unroll
  for (int k = 0; k < 20; k++) ldsm4t(&av[4 * k], wq + CH_WO + k * 2048);
  bar_sync(6, 256);
  PRO(6);
  if (warp >= 5 && elect()) tma_load3<(WEF & 2) != 0>(sb + CH_WO + (warp - 5) * 28672, &p.wo, j == 0 ? 0 : 32 + j * 192, h * 192 + (j + 8 - warp) % 3 * 64, bWo);
  if (tid == 128 + NSLOT && entry >= 80) {
    uint32_t c;
    int n = 0;
    do { c = ldg_strong32(g_bo + p.layer * 128 + 1); spin_guard(n); } while ((c & 255) + (c >> 8) < 96);
    const uint32_t other = (c >> 8 * (~entry & 1) & 255) + (entry >> 1) - 40;
    entry = other < 40 ? 2 * other + (~entry & 1) : entry % 80;
  }
  if (tid >= 128 && tid <= 128 + NSLOT) sts32(sb + CH_O + (tid - 128) * 4, entry);
  PRO(7);
  __syncthreads();
  if (__shfl_sync(~0u, tid >> 7, 0) == 0) chain_body<0>(p, wq, ak, av); else chain_body<1>(p, wq, ak, av);
}

struct PostParams { CUtensorMap wq, wo, wb, wo2, wb2; int gap, share, layer, look, gap2, pol; };
constexpr int PS = 8, PB = 28672;
constexpr int OP_SMEM = PS * PB + 512 + 2048;
enum { IT_ATT = 0, IT_OP = 1, IT_FIN = 2, IT_BQ = 3, IT_Q = 4 };

__device__ __forceinline__ uint32_t item_count(int type, int b) {
  return type == IT_ATT ? 32 : type == IT_OP ? op_split(b) * (DM / op_width(b)) : type == IT_FIN ? fin_items(b) : 1920 / bq_width(b); }
__device__ __forceinline__ uint32_t item_need(int type, int b) { return type == IT_ATT ? 96 : item_count(type - 1, b); }

struct Ring {
  uint32_t sb, bars; int st; uint32_t ph;
  __device__ __forceinline__ uint32_t wait() const { mbar_wait(bars + 8 * st, ph); return sb + st * PB; }
  __device__ __forceinline__ void next() { if (++st == PS) { st = 0; ph ^= 1; } }
  __device__ __forceinline__ void release(int s) const { if ((threadIdx.x & 31) == 0) mbar_arrive(bars + 8 * (PS + s)); }
  __device__ __forceinline__ void pop() { __syncwarp(); release(st); next(); }
};

template <int N>
__device__ __forceinline__ void gemm_item(Ring& r, float* d, int nst, uint32_t go, int go_at) {
  int prev = 0;
#pragma unroll 1
  for (int kb = 0; kb < nst; kb++) {
    const uint32_t base = r.wait();
    const uint64_t da = mkdesc(base + (threadIdx.x >> 7) * 4096, 128, 512, 0), db = mkdesc(base + 8192, 4096, 1024, 1);
    wg_fence();
#pragma unroll
    for (int kk = 0; kk < 2; kk++) {
      if (N == 80) wg_ss80_01(d, da + kk * 16, db + kk * 128, (kb | kk) != 0);
      if (N == 160) wg_ss160_01(d, da + kk * 16, db + kk * 128, (kb | kk) != 0);
      if (N >= 192) wg_ss192_01(d, da + kk * 16, db + kk * 128, (kb | kk) != 0);
      if (N == 320) wg_ss128_01(d + 96, da + kk * 16, db + kk * 128 + 3 * 256, (kb | kk) != 0);
    }
    wg_commit();
    if (kb == go_at && threadIdx.x == 0) mbar_arrive(go);
    if (kb > 0) { wg_wait<1>(); r.release(prev); }
    prev = r.st;
    r.next();
  }
  wg_wait<0>();
  reg_fence<N / 2>(d);
  r.release(prev);
}

template <int HALF>
__device__ __forceinline__ void attn_a_warp(Ring& r, const uint32_t (&q)[48], int b, int h) {
  constexpr int NT = HALF ? 5 : 3, NF = 8 * NT;
  const int lane = threadIdx.x & 31, g = lane >> 2, c = lane & 3, seg = (threadIdx.x >> 5) & 3;
  uint32_t f[6][NF];
  int slot[6];
  auto fetch = [&](int u) {
    const uint32_t kv = r.wait() + seg * KV_BYTES;
    slot[u] = r.st;
    r.next();
#pragma unroll
    for (int w = 0; w < 4; w++) {
      uint32_t* d = &f[u][2 * NT * w];
#pragma unroll
      for (int t = 0; t <= HALF; t++) {
        if (u < 3) {
          ldsm4(d + 4 * t, kv + w * 1024 + t * 512 + (lane & 8) * 32 + (lane & 16) * 8 + (lane & 7) * 16);
        } else {
          const uint4 v = lds128(kv + w * 1024 + t * 512 + lane * 16);
          d[4 * t] = v.x; d[4 * t + 1] = v.y; d[4 * t + 2] = v.z; d[4 * t + 3] = v.w;
        }
      }
      const uint2 m = lds64(kv + KV_M + w * 256 + lane * 8);
      d[2 * NT - 2] = m.x; d[2 * NT - 1] = m.y;
    }
    pdl_launch();
  };
  float s[NT][4] = {};
  fetch(0);
#pragma unroll
  for (int u = 0; u < 3; u++) {
    fetch(u + 1);
#pragma unroll
    for (int kk = 0; kk < 4; kk++) {
      const uint32_t* a = &q[16 * u + 4 * kk];
#pragma unroll
      for (int n = 0; n < NT; n++) mma16(s[(n + 1) % NT], a[0], a[1], a[2], a[3], f[u][2 * NT * kk + 2 * n], f[u][2 * NT * kk + 2 * n + 1]);
    }
    r.release(slot[u]);
    pdl_launch();
  }
  fetch(4);
  const float k2 = 0.07216878364870322f * 1.44269504089f, NEG = -INFINITY;
  if (2 * c > g) { s[NT - 2][0] = NEG; s[NT - 1][2] = NEG; }
  if (2 * c + 1 > g) { s[NT - 2][1] = NEG; s[NT - 1][3] = NEG; }
  s[NT - 1][0] = s[NT - 1][1] = NEG;
  uint32_t pp[NT][2]; float inv[2];
#pragma unroll
  for (int hh = 0; hh < 2; hh++) {
    float m = NEG, l = 0.f;
#pragma unroll
    for (int n = 0; n < NT; n++) m = fmaxf(m, fmaxf(s[n][2 * hh], s[n][2 * hh + 1]));
    m = fmaxf(m, __shfl_xor_sync(~0u, m, 1)); m = fmaxf(m, __shfl_xor_sync(~0u, m, 2));
#pragma unroll
    for (int n = 0; n < NT; n++) { const float x = ex2((s[n][2 * hh] - m) * k2), y = ex2((s[n][2 * hh + 1] - m) * k2); l += x + y; pp[n][hh] = pack2(x, y); }
    l += __shfl_xor_sync(~0u, l, 1); l += __shfl_xor_sync(~0u, l, 2);
    asm("rcp.approx.ftz.f32 %0, %1;" : "=f"(inv[hh]) : "f"(l));
  }
  uint32_t* dst = g_o + ((b * 192 + h * 6) * 16 + seg * 4 + HALF * 2) * 128 + lane;
#pragma unroll
  for (int u = 3; u < 6; u++) {
    float o[8][4] = {};
#pragma unroll
    for (int n = 0; n < 8; n++) mma8(o[n], pp[0][0], pp[0][1], f[u][2 * NT * (n >> 1) + 2 * NT - 2 + (n & 1)]);
#pragma unroll
    for (int t = 0; t <= HALF; t++)
#pragma unroll
      for (int n = 0; n < 8; n++) {
        const uint32_t* v = &f[u][2 * NT * (n >> 1) + 4 * t + 2 * (n & 1)];
        mma16(o[n], pp[1 + 2 * t][0], pp[1 + 2 * t][1], pp[2 + 2 * t][0], pp[2 + 2 * t][1], v[0], v[1]);
      }
    r.release(slot[u]);
    if (u == 3) fetch(5);
#pragma unroll
    for (int n = 0; n < 8; n++) {
      dst[(u - 3) * 4096 + (n >> 2) * 2048 + (n & 3) * 32] = pack2(o[n][0] * inv[0], o[n][1] * inv[0]);
      dst[(u - 3) * 4096 + (n >> 2) * 2048 + (n & 3) * 32 + 128] = pack2(o[n][2] * inv[1], o[n][3] * inv[1]);
    }
  }
}

template <int NG>
__device__ __forceinline__ void fin_item(Ring& r, uint32_t scratch, int b, int idx) {
  const int warp = threadIdx.x >> 5, lane = threadIdx.x & 31;
  float4* x = g_x + ((b * 16 + idx * NG) * 40 + warp * 5) * 32 + lane;
  float4 v[NG][5];
#pragma unroll
  for (int g = 0; g < NG; g++) {
    const uint32_t base = r.wait();
#pragma unroll
    for (int i = 0; i < 5; i++) v[g][i] = lds128f(base + ((warp * 5 + i) * 32 + lane) * 16);
    r.pop();
  }
#pragma unroll 1
  for (int k = 0; k < op_split(b); k += NG == 1 ? 2 : 1) {
#pragma unroll
    for (int g = 0; g < NG; g += 2) {
      const uint32_t base = r.wait();
#pragma unroll
      for (int i = 0; i < 10; i++) {
        const uint2 q = lds64(base + ((i / 5 * 40 + warp * 5 + i % 5) * 32 + lane) * 8);
        float4& t = v[(g + i / 5) % NG][i % 5];
        t.x += bf_lo(q.x); t.y += bf_hi(q.x); t.z += bf_lo(q.y); t.w += bf_hi(q.y);
      }
      r.pop();
    }
  }
  float mean[NG], rs[NG];
  ln_stats<NG>(v, scratch, mean, rs);
#pragma unroll
  for (int i = 0; i < 5; i++) {
    const int u = warp * 5 + i;
    uint32_t* xn = g_xn + ((b * 20 + (u >> 1)) * 16 + idx * NG) * 128 + (u & 1) * 64 + lane;
#pragma unroll
    for (int g = 0; g < NG; g++) {
      xn[g * 128] = pack2((v[g][i].x - mean[g]) * rs[g], (v[g][i].y - mean[g]) * rs[g]);
      xn[g * 128 + 32] = pack2((v[g][i].z - mean[g]) * rs[g], (v[g][i].w - mean[g]) * rs[g]);
    }
  }
#pragma unroll
  for (int g = 0; g < NG; g++)
#pragma unroll
    for (int i = 0; i < 5; i++) x[(g * 40 + i) * 32] = v[g][i];
}

__global__ void __launch_bounds__(384, 1) post_kernel(const __grid_constant__ PostParams p) {
  extern __shared__ __align__(1024) uint8_t smem_raw[];
  const uint32_t sb = s2u(smem_raw), bars = sb + PS * PB;
  const uint32_t bIF = bars + 128, bIE = bars + 160, done = bars + 192, bGo = bars + 224, slots = bars + 240, scratch = bars + 512;
  const int warp = __shfl_sync(~0u, threadIdx.x >> 5, 0), lane = threadIdx.x & 31;
  TRACE(0);
  pdl_launch();
  if (sb & 1023) __trap();
  if (threadIdx.x < 29) mbar_init(bars + 8 * threadIdx.x, threadIdx.x < 8 ? 1 : threadIdx.x < 16 ? 8 : threadIdx.x < 20 ? 1 : threadIdx.x < 24 ? 2 : threadIdx.x < 28 ? 8 : 1);
  if (threadIdx.x == 32) sts32(slots + 16, p.gap);
  fence_async();
  __syncthreads();
  if (warp >= 8) {
    asm volatile("setmaxnreg.dec.sync.aligned.u32 56;");
    if (warp == 9) {
      const int b = lane & 15;
      bool queries = QA_END < 16 && blockIdx.x < 36;
      for (int n = 0;; n++) {
        if (n > 0) mbar_wait(bGo, (n - 1) & 1);
        mbar_wait(bIE + 8 * (n & 3), ((n >> 2) & 1) ^ 1);
        int code = -1, spin = 0, ticket = 0;
        if (queries) {
          if (lane == 0) ticket = atomicAdd(g_sync + SY_QC, 1);
          ticket = __shfl_sync(~0u, ticket, 0);
          queries = ticket < (16 - QA_END) * 32;
          if (queries) code = IT_Q << 16 | (QA_END + ticket % (16 - QA_END)) << 8 | ticket / (16 - QA_END);
        }
        if (!queries && lane == 0) ticket = atomicAdd(g_sync + SY_T, 1);
        while (!queries) {
          const uint4 hd = ldg_strong128(g_sync + b * 8), pr = ldg_strong128(g_sync + b * 8 + 4);
          const uint32_t hv[4] = {hd.x, hd.y, hd.z, hd.w}, pv[4] = {pr.x, pr.y, pr.z, pr.w};
          const uint32_t chain_done = __ballot_sync(~0u, (pr.x & 0xffff) >= 96) & 0xffff;
          int left[4], avail[4], rdy = 0, claimed = 0, upstream = 0;
#pragma unroll
          for (int t = 0; t < 4; t++) {
            const int cnt = lane < 16 ? item_count(t, b) : 0;
            left[t] = max(cnt - (int)hv[t], 0);
            claimed += cnt - left[t];
            const bool ready = (pv[t] & 0xffff) >= item_need(t, b);
            rdy |= ready << t;
            bool ok = ready || (t == IT_ATT ? pr.x >= 0x10000 : !upstream || (t == IT_OP && (chain_done >> 15 & 1)));
            if (t == IT_BQ && (chain_done >> BQ_HOLD & 1) && !(chain_done >> 15)) ok = false;
            avail[t] = ok ? left[t] : 0;
            upstream |= __any_sync(~0u, left[t] > 0);
          }
          if (!upstream) break;
          int rank = max(__shfl_sync(~0u, ticket, 0) - __reduce_add_sync(~0u, claimed), 0), type = -1, mine = 0;
#pragma unroll
          for (int c = 0; c < 8; c++) {
            const int t = c == 0 || c == 5 ? IT_FIN : c == 1 || c == 7 ? IT_ATT : c == 2 || c == 4 ? IT_OP : IT_BQ;
            int a = c == 1 || ((rdy >> t & 1) == (c < 4)) ? avail[t] : 0;
            if (t == IT_OP && !(p.pol & 1)) a = c == 2 ? avail[t] : 0;
            if (c == 7) a = b < QA_END && !(rdy & 1) && ((chain_done << 1 | 1) >> b & 1) ? left[t] : 0;
            const int tot = __reduce_add_sync(~0u, a);
            if (type < 0) { if (rank < tot) { type = t; mine = a; } else rank -= tot; }
          }
          if (type >= 0) {
#pragma unroll
            for (int o = 1; o < 16; o <<= 1) { const int y = __shfl_up_sync(~0u, mine, o); if (lane >= o) mine += y; }
            const int blk = __ffs(__ballot_sync(~0u, mine > rank)) - 1;
            const int early = !(__shfl_sync(~0u, rdy, blk) >> type & 1);
            uint32_t idx = 0;
            if (lane == 0) { idx = atomicAdd(g_sync + blk * 8 + type, 1); ld_acquire(g_sync + blk * 8 + 4 + type); }
            idx = __shfl_sync(~0u, idx, 0);
            if (idx < item_count(type, blk)) { code = (chain_done >> 15 & 1) << 22 | (chain_done >> p.look & 1) << 21 | early << 20 | type << 16 | blk << 8 | idx; break; }
          } else {
            __nanosleep(50);
          }
          spin_guard(spin);
        }
        if (lane == 0) {
          fence_async_global();
          sts32(slots + 4 * (n & 3), code);
          mbar_arrive(bIF + 8 * (n & 3));
        }
        __syncwarp();
        if (code < 0) break;
      }
    } else if (warp == 8) {
      if (elect()) {
        uint32_t dst = sb, bar = bars, ph = 1, next = clk32(), gap = 0;
        auto acquire = [&](uint32_t kb) {
          mbar_wait(bar + 8 * PS, ph);
          mbar_expect(bar, kb * 1024);
          if (gap) {
            uint32_t now;
            do now = clk32(); while ((int)(now - next) < 0);
            next = ((int)(now - next) > 100 ? now - 100 : next) + kb * gap;
          }
        };
        auto advance = [&]() { dst += PB; bar += 8; if (dst == bars) { dst = sb; bar = bars; ph ^= 1; } };
        auto depend = [&](const uint32_t* c, uint32_t need) { wait_count(c, need); fence_async_global(); };
#pragma unroll 1
        for (int n = 0;; n++) {
          mbar_wait(bIF + 8 * (n & 3), (n >> 2) & 1);
          const int code = (int)lds32(slots + 4 * (n & 3));
          if (code < 0) break;
          const int type = (code >> 16) & 15, b = (code >> 8) & 255, idx = code & 255;
          const bool early = code >> 20 & 1, go = !(code >> 21 & 1);
          mbar_arrive(bIE + 8 * (n & 3));
          gap = !(code >> 22 & 1) ? lds32(slots + 16) : type == IT_ATT || type == IT_FIN ? 0 : p.gap2;
          const uint32_t* progress = g_sync + b * 8 + 4 + type;
          if (type == IT_ATT && b >= QA_END) {
            depend(g_sync + SY_Q, (16 - QA_END) * 32);
#pragma unroll 1
            for (int u = 0; u < 2; u++) { acquire(24); bulk_load_last(dst, g_q + (((b - QA_END) * 32 + idx) * 2 + u) * 1536, 24576, bar); advance(); }
          } else if (type == IT_FIN) {
            const int ng = 16 / fin_items(b), lg = ng >> 1;
#pragma unroll 1
            for (int g = 0; g < ng; g++) { acquire(20); bulk_load(dst, g_x + (b * 16 + idx * ng + g) * 1280, 20480, bar); advance(); }
            if (early) depend(progress, item_need(type, b));
            if (go) mbar_arrive(bGo);
#pragma unroll 1
            for (int i = 0; i < op_split(b) * ng; i += 2) {
              const uint2* src = g_part + ((b * 16 + (i >> lg)) * 16 + idx * ng + (i & (ng - 1))) * 1280;
              acquire(20);
              bulk_load_last(dst, src, ng > 1 ? 20480 : 10240, bar);
              if (ng == 1) bulk_load_last(dst + 10240, src + 16 * 1280, 10240, bar);
              advance();
            }
          } else {
            const bool op = type == IT_OP, bq = type == IT_BQ;
            const int width = op ? op_width(b) : bq ? bq_width(b) : 192, nb = (width + 63) >> 6, lt = width == 320 ? 1 : 2;
            const int nst = op ? 192 / op_split(b) : 20, kb0 = op ? (idx >> lt) * nst : 0;
            const int col = (op ? idx & ((1 << lt) - 1) : idx) * width;
            const bool whole = !(width & 63);
            const CUtensorMap* m = op ? (whole ? &p.wo : &p.wo2) : bq ? (whole ? &p.wb : &p.wb2) : &p.wq;
            const uint32_t* a = op ? g_o + (b * 192 + kb0) * 2048 : g_xn + b * 20 * 2048;
            int row = kb0 * 32, pre = early && (op || bq) ? min(nst, PS) : 0;
            auto weights = [&]() {
              acquire(8 + nb * 4);
              if (whole) {
                tma_load3z(dst + 8192, m, row, col >> 6, bar);
              } else {
                tma_load(dst + 8192, m, col, row, bar); tma_load(dst + 12288, m, col + 64, row, bar);
                if (nb == 3) tma_load(dst + 16384, m, col + 128, row, bar);
              }
              row += 32;
            };
            if (pre) {
              uint32_t da = dst, ba = bar;
#pragma unroll 1
              for (int kb = 0; kb < pre; kb++) { weights(); advance(); }
              depend(progress, item_need(type, b));
#pragma unroll 1
              for (int kb = 0; kb < pre; kb++) {
                bulk_load(da, a, 8192, ba);
                a += 2048; da += PB; ba += 8;
                if (da == bars) { da = sb; ba = bars; }
              }
            }
#pragma unroll 1
            for (int kb = pre; kb < nst; kb++) { weights(); if (op && OEF) bulk_load_last(dst, a, 8192, bar); else bulk_load(dst, a, 8192, bar); a += 2048; advance(); }
          }
          if (type == IT_ATT) {
            if (early) depend(progress, 96);
            if (go) mbar_arrive(bGo);
            const uint8_t* src = g_kv + (size_t)(idx * 6 * NSEG + b * 4) * KV_BYTES;
#pragma unroll 1
            for (int u = 0; u < 6; u++) {
              acquire(20);
              bulk_load_last(dst, src, 20480, bar);
              src += u == 2 ? -3 * KV_V : 2 * KV_V;
              advance();
            }
          }
        }
      }
    } else if (warp == 11) {
      uint32_t smid, nsm, used = 0;
      asm("mov.u32 %0, %%smid;" : "=r"(smid)); asm("mov.u32 %0, %%nsmid;" : "=r"(nsm));
      for (int n = 0; n < 64 && used < 96; n++) {
        uint32_t peers = 0;
        used = 0;
        for (uint32_t i = lane; i < min(nsm, 256u); i += 32) {
          const bool taken = ldg_strong32(g_smuse + i) == p.layer + 1;
          used += taken;
          peers += abs((int)(g_smclk[i] - g_smclk[smid & 255])) < 4000 && !taken;
        }
        used = __reduce_add_sync(~0u, used);
        sts32(slots + 16, max(p.gap, (int)min(__reduce_add_sync(~0u, peers), 18u) * p.share >> 3));
      }
    } else if (warp == 10 && lane == 0) {
      for (int n = 0;; n++) {
        mbar_wait(bIF + 8 * (n & 3), (n >> 2) & 1);
        const int code = (int)lds32(slots + 4 * (n & 3));
        if (code < 0) break;
        const int type = (code >> 16) & 15, b = (code >> 8) & 255;
        mbar_wait(done + 8 * (n & 3), (n >> 2) & 1);
        if (type != IT_BQ) red_release(type == IT_Q ? g_sync + SY_Q : g_sync + b * 8 + 5 + type, 1);
        mbar_arrive(bIE + 8 * (n & 3));
      }
    }
  } else {
    asm volatile("setmaxnreg.inc.sync.aligned.u32 224;");
    const int g = lane >> 2, c = lane & 3;
    Ring r = {sb, bars, 0, 0};
#pragma unroll 1
    for (int n = 0;; n++) {
      mbar_wait(bIF + 8 * (n & 3), (n >> 2) & 1);
      const int code = __shfl_sync(~0u, (int)lds32(slots + 4 * (n & 3)), 0);
      if (code < 0) { TRACE(2); break; }
      const int type = (code >> 16) & 15, b = (code >> 8) & 255, idx = code & 255;
      ITEM(code & 0xfffff, 0);
      if (type == IT_ATT || type == IT_Q) {
        uint32_t q[48];
        if (type == IT_Q || b < QA_END) {
          float d[96] = {};
          reg_fence<96>(d);
          gemm_item<192>(r, d, 20, bGo, type == IT_Q ? 12 : -1);
#pragma unroll
          for (int i = 0; i < 48; i++) q[i] = pack2(d[2 * i], d[2 * i + 1]);
        } else {
#pragma unroll
          for (int u = 0; u < 2; u++) {
            const uint32_t base = r.wait() + threadIdx.x * 16;
#pragma unroll
            for (int i = 0; i < 6; i++) {
              const uint4 v = lds128(base + i * 4096);
              q[24 * u + 4 * i] = v.x; q[24 * u + 4 * i + 1] = v.y; q[24 * u + 4 * i + 2] = v.z; q[24 * u + 4 * i + 3] = v.w;
            }
            r.pop();
          }
        }
        if (type == IT_Q) {
          uint4* dst = g_q + ((b - QA_END) * 32 + idx) * 3072 + threadIdx.x;
#pragma unroll
          for (int i = 0; i < 12; i++) dst[i * 256] = make_uint4(q[4 * i], q[4 * i + 1], q[4 * i + 2], q[4 * i + 3]);
        } else if (warp < 4) {
          attn_a_warp<0>(r, q, b, idx);
        } else {
          attn_a_warp<1>(r, q, b, idx);
        }
      } else if (type == IT_FIN) {
        if (fin_items(b) == 4) fin_item<4>(r, scratch, b, idx);
        else if (fin_items(b) == 8) fin_item<2>(r, scratch, b, idx);
        else fin_item<1>(r, scratch, b, idx);
      } else {
        float d[160] = {};
        reg_fence<160>(d);
        const int width = type == IT_OP ? op_width(b) : bq_width(b), nst = type == IT_OP ? 192 / op_split(b) : 20;
        const int go_at = code >> 21 & 1 ? -1 : max(nst - 6, 0);
        if (width == 320) gemm_item<320>(r, d, nst, bGo, go_at);
        else if (width == 160 || BQ_80 == 16) gemm_item<160>(r, d, nst, bGo, go_at);
        else gemm_item<80>(r, d, nst, bGo, go_at);
        reg_fence<160>(d);
        if (type == IT_OP) {
          const int tiles = DM / width;
          uint2* dst = g_part + (((b * 16 + idx / tiles) * 16 + warp * 2) * 40 + idx % tiles * (width / 16)) * 32 + lane;
#pragma unroll
          for (int u = 0; u < 20; u++) {
            if (u % 5 == 0 && u * 16 >= width) break;
            dst[u * 32] = make_uint2(pack2(d[8 * u], d[8 * u + 1]), pack2(d[8 * u + 4], d[8 * u + 5]));
            dst[(40 + u) * 32] = make_uint2(pack2(d[8 * u + 2], d[8 * u + 3]), pack2(d[8 * u + 6], d[8 * u + 7]));
          }
        } else {
          const int row = b * 128 + warp * 16 + g;
          const int h0 = idx * (width / 20);
          const float sc = h0 < 32 ? 0.22360679775f * 1.44269504089f : 1.f;
          const bool lo = c < 2;
          uint32_t* da = g_bqkv + (h0 * 256 + (row >> 3)) * 96 + lane;
          uint32_t* db = da + 256 * 96 + (lo ? 2 : -2);
          uint32_t pad[2];
#pragma unroll
          for (int rr = 0; rr < 2; rr++) pad[rr] = c & 1 || h0 < 32 ? 0u : h0 >= 64 ? 0x00003f80u : poly_group((row >> 3) + rr) ? 0x3f803f80u : 0u;
#pragma unroll
          for (int q = 0; q < 8; q++) {
            if (!(q & 1) && q * 40 >= width) break;
#pragma unroll
            for (int rr = 0; rr < 2; rr++) {
              uint32_t w[5];
#pragma unroll
              for (int i = 0; i < 5; i++) w[i] = pack2(d[20 * q + 4 * i + 2 * rr] * sc, d[20 * q + 4 * i + 2 * rr + 1] * sc);
              const int o = q * 2 * 256 * 96 + rr * 96;
              da[o] = w[0]; da[o + 32] = w[1]; da[o + 64] = lo ? w[2] : pad[rr];
              db[o] = lo ? w[3] : w[2]; db[o + 32] = lo ? w[4] : w[3]; db[o + 64] = lo ? pad[rr] : w[4];
            }
          }
        }
      }
      __syncwarp();
      if (lane == 0) mbar_arrive(done + 8 * (n & 3));
      if ((code >> 21 & 1) && threadIdx.x == 128) mbar_arrive(bGo);
      ITEM(code & 0xfffff, 1);
    }
  }
}

constexpr int AB_SMEM = 1024 + 98304 + 51200 + 4 * 16384 + 256;
#define AB_LW 1
#define AB_U 8
#define AB_WG 4
constexpr int AB_T = AB_WG * 128, AB_PASS = 8 / AB_WG;
__device__ __forceinline__ uint32_t fma2(uint32_t a, uint32_t b, uint32_t c) { uint32_t r; asm("fma.rn.bf16x2 %0, %1, %2, %3;" : "=r"(r) : "r"(a), "r"(b), "r"(c)); return r; }
__device__ __forceinline__ uint32_t ex2_pair(float a, float b, uint32_t one, uint32_t c0) {
  const uint32_t e = __byte_perm(__float_as_uint(a), __float_as_uint(b), 0x6521);
  uint32_t x, r;
  asm("lop3.b32 %0, %1, 0x007f007f, %2, 0xEA;" : "=r"(x) : "r"(e), "r"(one));
  const uint32_t m = AB_DEG == 3 ? fma2(fma2(fma2(c0, x, 0xbbdcbbdcu), x, 0x3ef53ef5u), x, 0x3ee83ee8u) : fma2(fma2(c0, x, 0xbc43bc43u), x, 0x3f2e3f2eu);
  asm("lop3.b32 %0, %1, %2, 0x7f807f80, 0xE4;" : "=r"(r) : "r"(e), "r"(m));
  return r;
}
__device__ __forceinline__ float sq2(uint32_t w) { const float a = bf_lo(w), b = bf_hi(w); return fmaf(a, a, b * b); }

__device__ __forceinline__ void attn_b_store(const float* o, int h, int row0, int lane) {
  const int g = lane >> 2, c = lane & 3;
  const float i0 = __frcp_rn(__shfl_sync(~0u, o[8], (lane & ~3) | 2)), i1 = __frcp_rn(__shfl_sync(~0u, o[10], (lane & ~3) | 2));
#pragma unroll
  for (int jj = 0; jj < 3; jj++) {
    if (jj < 2 || c < 2) {
      const int col = h * 20 + 8 * jj + 2 * c;
      uint32_t* dst = g_of + (((row0 >> 7) * 10 + (col >> 6)) * 16 + (row0 >> 3 & 15)) * 256 + (col >> 3 & 7) * 32 + g * 4 + (col >> 1 & 3);
      dst[0] = pack2(o[4 * jj] * i0, o[4 * jj + 1] * i0);
      dst[256] = pack2(o[4 * jj + 2] * i1, o[4 * jj + 3] * i1);
    }
  }
}

struct AbParams { Weights next; uint32_t* done; uint32_t* out; };
__global__ void __launch_bounds__(AB_T + 32, 1) attn_b_kernel(const __grid_constant__ AbParams p) {
  extern __shared__ uint8_t smem_raw[];
  const uint32_t sb = (s2u(smem_raw) + 1023) & ~1023u, sK = sb, sV = sb + 98304, bars = sV + 51200 + 4 * 16384;
  const uint32_t bF = bars + 64, bW = bars + 72, bA = bars + 80, bE = bars + 128, smax = bars + 176;
  auto ring = [&](int i) { return i < 2 ? sK + 51200 + i * 16384 : sV + 51200 + (i - 2) * 16384; };
  const int warp = __shfl_sync(~0u, threadIdx.x >> 5, 0), lane = threadIdx.x & 31;
  const int h = blockIdx.x >> 2, quarter = blockIdx.x & 3;
  TRACE(0);
  pdl_launch();
  if (threadIdx.x < 22) mbar_init(bars + 8 * threadIdx.x, threadIdx.x == 8 ? AB_T / 32 : threadIdx.x >= 16 ? 8 : 1);
  if (threadIdx.x == 32) sts64(smax, 0, 0);
  fence_async();
  __syncthreads();
  pdl_wait();
  const int blk = quarter * 4 + (h >> 3), cg = h & 7;
  auto unsafe = [&]() { const float2 m = lds64f(smax); return !(m.x * m.y <= 10000.f); };
  if (warp == AB_T / 32) {
    auto load_w = [&]() {
      mbar_expect(bW, 102400);
      for (int i = 0; i < 4; i++) bulk_load((i < 2 ? sK : sV) + (i & 1) * 25600, g_wb + cg * 6400 + i * 1600, 25600, bW);
    };
    if (elect()) {
      const uint32_t* gk = g_bqkv + (32 + h) * 256 * 96;
#pragma unroll 1
      for (int i = 0; i < 8; i++) {
        if (i >= AB_LW) mbar_wait(bars + 8 * (i - AB_LW), 0);
        mbar_expect(bars + 8 * i, 24576);
        bulk_load_last(sK + i * 12288, gk + i * 3072, 12288, bars + 8 * i);
        bulk_load_last(sV + i * 12288, gk + 32 * 256 * 96 + i * 3072, 12288, bars + 8 * i);
      }
    }
    __syncwarp();
    if (blockIdx.x < NSLOT) for (int i = lane; i < 512; i += 32) reinterpret_cast<uint4*>(pool_at(blockIdx.x * 8192))[i] = make_uint4(0, 0, 0, 0);
    if (blockIdx.x == 127) for (int i = lane; i < SY_N; i += 32) g_sync[i] = 0;
    if (p.next.w[0] && lane == 0) {
      for (int i = 0; i < AB_PF; i++) { const uint32_t t0 = clk32(); while (clk32() - t0 < (i ? AB_PFD : AB_PF0)) __nanosleep(200); prefetch_weights(p.next, i); }
    }
    __syncwarp();
    mbar_wait(bF, 0);
    const bool redo = unsafe();
    if (!redo && lane == 0) load_w();
    __syncwarp();
    bar_sync(1, AB_T + 32);
    if (lane == 0) {
      ABT(!!p.out, 1);
      red_release(p.done + quarter * 32, 1);
      ABT(!!p.out, 2);
      if (redo) load_w();
      wait_count(p.done + quarter * 32, 32);
      fence_async_global();
      ABT(!!p.out, 3);
      for (int kb = 0; kb < 10; kb++) {
        const int i = kb < 6 ? kb : kb - 6;
        if (kb >= 6) mbar_wait(bE + 8 * i, 0);
        mbar_expect(bA + 8 * i, 16384);
        bulk_load(ring(i), g_of + (blk * 10 + kb) * 4096, 16384, bA + 8 * i);
      }
    }
    return;
  }
  float qmax = 0.f;
  const uint32_t one = opaque(0x3f803f80u + (threadIdx.x >> 10)), c0 = opaque((AB_DEG == 3 ? 0x3d9f3d9fu : 0x3eac3eacu) + (threadIdx.x >> 10));
#pragma unroll 1
  for (int pass = 0; pass < AB_PASS; pass++) {
    const int row0 = quarter * 512 + ((warp >> 2) * AB_PASS + pass) * 64 + (warp & 3) * 16;
    const uint32_t* gq = g_bqkv + (h * 256 + (row0 >> 3)) * 96 + lane;
    const uint32_t q0 = gq[0], q1 = gq[96], q2 = gq[32], q3 = gq[128];
    uint32_t q4 = gq[64], q5 = gq[160];
    const uint32_t z0 = gq[64 + 3 - (lane & 3)], z1 = gq[160 + 3 - (lane & 3)];
    {
      float n0 = sq2(q0) + sq2(q2) + sq2(q4), n1 = sq2(q1) + sq2(q3) + sq2(q5);
      n0 += __shfl_xor_sync(~0u, n0, 1); n1 += __shfl_xor_sync(~0u, n1, 1);
      n0 += __shfl_xor_sync(~0u, n0, 2); n1 += __shfl_xor_sync(~0u, n1, 2);
      qmax = (n0 > qmax || n0 != n0) ? n0 : qmax;
      qmax = (n1 > qmax || n1 != n1) ? n1 : qmax;
    }
    if (pass == AB_PASS - 1) {
      float kmax = 0.f;
#pragma unroll
      for (int i = 0; i < SEQ / AB_T; i++) {
        const int key = threadIdx.x + AB_T * i;
        const uint32_t a = sK + (key >> 3) * 384 + (key & 7) * 16;
        const uint4 x = lds128(a), y = lds128(a + 128);
        const uint2 z = lds64(a + 256);
        const float n = ((sq2(x.x) + sq2(x.y)) + (sq2(x.z) + sq2(x.w))) + ((sq2(y.x) + sq2(y.y)) + (sq2(y.z) + sq2(y.w))) + (sq2(z.x) + sq2(z.y));
        kmax = (n > kmax || n != n) ? n : kmax;
      }
      const uint32_t kb = __reduce_max_sync(~0u, __float_as_uint(kmax) & 0x7fffffffu), qb = __reduce_max_sync(~0u, __float_as_uint(qmax) & 0x7fffffffu);
      if (lane < 2) asm volatile("red.shared.max.u32 [%0], %1;" :: "r"(smax + 4 * lane), "r"(lane ? kb : qb) : "memory");
      __syncwarp();
    }
    if ((lane & 3) == 2) { q4 = 0xBF8043C0u; q5 = 0xBF8043C0u; }
    float o[12];
    auto desc = [](uint32_t lo, uint32_t hi) { uint64_t d; asm("mov.b64 %0, {%1, %2};" : "=l"(d) : "r"(lo), "r"(hi)); return d; };
    const uint32_t k0 = (uint32_t)mkdesc(sK, 128, 0, 0), k1 = (uint32_t)mkdesc(sK + 256, 0, 0, 0), v0 = (uint32_t)mkdesc(sV, 384, 0, 0);
    float sa[16], sb2[16];
    uint32_t pa[8], pb[8];
    auto qk = [&](float* s, uint32_t t) {
      wg_rs32_00(s, q0, q1, q2, q3, desc(k0 + t, 24), 0);
      wg_rs32_00(s, q4, q5, z0, z1, desc(k1 + t, 24), 1);
      wg_commit();
    };
    auto step = [&](float* s, uint32_t* pp, int g0, uint32_t t, uint32_t nx, int acc) {
      wg_wait<1>();
      reg_fence<16>(s);
#pragma unroll
      for (int i = 0; i < 8; i++) pp[i] = poly_group(g0 + (i >> 1)) ? ex2_pair(s[2 * i], s[2 * i + 1], one, c0) : pack2(ex2(s[2 * i]), ex2(s[2 * i + 1]));
      wg_fence();
      wg_rs24_01(o, pp[0], pp[1], pp[2], pp[3], desc(v0 + t, 8), acc);
      wg_rs24_01(o, pp[4], pp[5], pp[6], pp[7], desc(v0 + t + 48, 8), 1);
      qk(s, nx);
    };
    if (pass == 0) mbar_wait(bars, 0);
    wg_fence();
    qk(sa, 0);
    qk(sb2, 96);
#pragma unroll 1
    for (uint32_t t = 0; t < 64 * 96; t += AB_U * 96) {
      const uint32_t nx = t + AB_U * 96 < 64 * 96 ? t + AB_U * 96 : 0;
      if (pass == AB_PASS - 1 && t == 40 * 96 && lane == 0) mbar_arrive(bF);
#pragma unroll
      for (int u = 0; u < AB_U; u += 2) {
        if (u == AB_U - 2 && pass == 0) mbar_wait(bars + 8 * (nx / 768), 0);
        step(sa, pa, 0, t + u * 96, u + 2 < AB_U ? t + (u + 2) * 96 : nx, u | t);
        step(sb2, pb, 4, t + u * 96 + 96, (u + 2 < AB_U ? t + (u + 2) * 96 : nx) + 96, 1);
      }
    }
    wg_wait<0>();
    reg_fence<12>(o); reg_fence<16>(sa); reg_fence<16>(sb2);
    attn_b_store(o, h, row0, lane);
  }
  mbar_wait(bF, 0);
  if (unsafe())
#pragma unroll 1
  for (int pass = 0; pass < AB_PASS; pass++) {
    const int row0 = quarter * 512 + ((warp >> 2) * AB_PASS + pass) * 64 + (warp & 3) * 16;
    const uint32_t* gq = g_bqkv + (h * 256 + (row0 >> 3)) * 96 + lane;
    const uint32_t q0 = gq[0], q1 = gq[96], q2 = gq[32], q3 = gq[128], q4 = gq[64], q5 = gq[160];
    float o[12];
#pragma unroll
    for (int i = 0; i < 12; i++) o[i] = 0.f;
    float m0 = -INFINITY, m1 = -INFINITY;
#pragma unroll 1
    for (int kt = 0; kt < 32; kt++) {
      float s[32];
      const uint64_t dk = mkdesc(sK + kt * 3072, 128, 384, 0), dk2 = mkdesc(sK + kt * 3072 + 256, 0, 384, 0);
      wg_fence();
      wg_rs64_00(s, q0, q1, q2, q3, dk, 0);
      wg_rs64_00(s, q4, q5, 0, 0, dk2, 1);
      wg_commit();
      wg_wait<0>();
      reg_fence<32>(s); reg_fence<12>(o);
      float n0 = m0, n1 = m1;
#pragma unroll
      for (int jj = 0; jj < 8; jj++) { n0 = fmaxf(n0, fmaxf(s[4 * jj], s[4 * jj + 1])); n1 = fmaxf(n1, fmaxf(s[4 * jj + 2], s[4 * jj + 3])); }
      n0 = fmaxf(n0, __shfl_xor_sync(~0u, n0, 1)); n0 = fmaxf(n0, __shfl_xor_sync(~0u, n0, 2));
      n1 = fmaxf(n1, __shfl_xor_sync(~0u, n1, 1)); n1 = fmaxf(n1, __shfl_xor_sync(~0u, n1, 2));
      const float r0 = ex2(m0 - n0), r1 = ex2(m1 - n1);
      m0 = n0; m1 = n1;
#pragma unroll
      for (int jj = 0; jj < 3; jj++) { o[4 * jj] *= r0; o[4 * jj + 1] *= r0; o[4 * jj + 2] *= r1; o[4 * jj + 3] *= r1; }
      uint32_t pp[16];
#pragma unroll
      for (int jj = 0; jj < 8; jj++) {
        pp[2 * jj] = pack2(ex2(s[4 * jj] - m0), ex2(s[4 * jj + 1] - m0));
        pp[2 * jj + 1] = pack2(ex2(s[4 * jj + 2] - m1), ex2(s[4 * jj + 3] - m1));
      }
      const uint64_t dv = mkdesc(sV + kt * 3072, 384, 128, 0);
      wg_fence();
#pragma unroll
      for (int kk = 0; kk < 4; kk++) wg_rs24_01(o, pp[4 * kk], pp[4 * kk + 1], pp[4 * kk + 2], pp[4 * kk + 3], dv + kk * 48, 1);
      wg_commit();
    }
    wg_wait<0>();
    reg_fence<12>(o);
    attn_b_store(o, h, row0, lane);
  }
  ABT(!!p.out, 0);
  bar_arrive(1, AB_T + 32);
  if (warp >= 8) return;
  const int g = lane >> 2, c = lane & 3;
  float d[40];
  float4* x = g_x + ((blk * 16 + warp * 2) * 40 + cg * 5) * 32 + lane;
#pragma unroll
  for (int i = 0; i < 10; i++) {
    const int r = i / 5, u = i % 5;
    const float4 t = x[(r * 40 + u) * 32];
    d[8 * u + 2 * r] = t.x; d[8 * u + 2 * r + 1] = t.y; d[8 * u + 4 + 2 * r] = t.z; d[8 * u + 5 + 2 * r] = t.w;
  }
  mbar_wait(bW, 0);
  reg_fence<40>(d);
  ABT(!!p.out, 4);
#pragma unroll 1
  for (int kb = 0; kb < 10; kb++) {
    const int i = kb < 6 ? kb : kb - 6;
    mbar_wait(bA + 8 * i, kb >= 6);
    const uint64_t da = mkdesc(ring(i) + (warp >> 2) * 8192, 128, 1024, 0), db = mkdesc(kb < 5 ? sK + kb * 10240 : sV + (kb - 5) * 10240, 1280, 128, 0);
    wg_fence();
#pragma unroll
    for (int kk = 0; kk < 4; kk++) wg_ss80_01(d, da + kk * 16, db + kk * 160, 1);
    wg_commit();
    if (kb > 0 && kb < 5) { wg_wait<1>(); if (lane == 0) mbar_arrive(bE + 8 * (kb - 1)); }
  }
  wg_wait<0>();
  reg_fence<40>(d);
  ABT(!!p.out, 5);
  if (p.out) {
    uint32_t* out = p.out + (blk * 128 + warp * 16 + g) * (DM / 2) + cg * 40 + c;
#pragma unroll
    for (int i = 0; i < 20; i++) out[(i & 1) * 8 * (DM / 2) + (i >> 1) * 4] = pack2(d[2 * i], d[2 * i + 1]);
  } else {
    float2* stat = g_stat + blk * 1024 + warp * 16 + g;
    float mean[2], rs[2];
#pragma unroll
    for (int r = 0; r < 2; r++) {
      float t = 0.f, q = 0.f;
#pragma unroll
      for (int i = 0; i < 10; i++) t += d[4 * i + 2 * r] + d[4 * i + 2 * r + 1];
      t += __shfl_xor_sync(~0u, t, 1); t += __shfl_xor_sync(~0u, t, 2);
      t *= 1.f / 80;
#pragma unroll
      for (int i = 0; i < 10; i++) { const float a = d[4 * i + 2 * r] - t, b = d[4 * i + 2 * r + 1] - t; q += a * a + b * b; }
      q += __shfl_xor_sync(~0u, q, 1); q += __shfl_xor_sync(~0u, q, 2);
      if (c == r) asm volatile("st.relaxed.gpu.global.v2.b32 [%0], {%1, %2};" :: "l"(stat + cg * 128 + r * 8), "r"(__float_as_uint(t)), "r"(nz(__float_as_uint(q))) : "memory");
    }
#pragma unroll
    for (int i = 0; i < 10; i++) {
      const int r = i / 5, u = i % 5;
      x[(r * 40 + u) * 32] = make_float4(d[8 * u + 2 * r], d[8 * u + 2 * r + 1], d[8 * u + 4 + 2 * r], d[8 * u + 5 + 2 * r]);
    }
    ABT(0, 6);
    uint2 e[4];
    int n = 0;
    do {
#pragma unroll
      for (int i = 0; i < 4; i++)
        asm volatile("ld.relaxed.gpu.global.v2.b32 {%0, %1}, [%2];" : "=r"(e[i].x), "=r"(e[i].y) : "l"(stat + (2 * c + (i & 1)) * 128 + (i >> 1) * 8) : "memory");
      spin_guard(n);
    } while (__any_sync(~0u, min(min(e[0].y, e[1].y), min(e[2].y, e[3].y)) == 0));
#pragma unroll
    for (int r = 0; r < 2; r++) {
      const float m0 = __uint_as_float(e[2 * r].x), m1 = __uint_as_float(e[2 * r + 1].x);
      float t = m0 + m1;
      t += __shfl_xor_sync(~0u, t, 1); t += __shfl_xor_sync(~0u, t, 2);
      t *= 0.125f;
      float q = __uint_as_float(e[2 * r].y) + __uint_as_float(e[2 * r + 1].y) + 80.f * ((m0 - t) * (m0 - t) + (m1 - t) * (m1 - t));
      q += __shfl_xor_sync(~0u, q, 1); q += __shfl_xor_sync(~0u, q, 2);
      mean[r] = t; rs[r] = rsqrtf(q * (1.f / DM) + 1e-5f);
    }
    ABT(0, 7);
    uint32_t w[2][5][2];
#pragma unroll
    for (int i = 0; i < 20; i++) w[i & 1][i >> 2][i >> 1 & 1] = pack2((d[2 * i] - mean[i & 1]) * rs[i & 1], (d[2 * i + 1] - mean[i & 1]) * rs[i & 1]);
    ln_store(w, blk * 8 + warp, cg * 5);
  }
  ABT(!!p.out, 8);
  TRACE(2);
}

typedef CUresult (*EncodeFn)(CUtensorMap*, CUtensorMapDataType, cuuint32_t, void*, const cuuint64_t*, const cuuint64_t*,
                             const cuuint32_t*, const cuuint32_t*, CUtensorMapInterleave, CUtensorMapSwizzle,
                             CUtensorMapL2promotion, CUtensorMapFloatOOBfill);

void make_map(EncodeFn enc, CUtensorMap* m, const void* ptr, int cols, int rows, int nb) {
  const cuuint64_t dims[3] = {(cuuint64_t)(nb ? 64 : cols), (cuuint64_t)rows, (cuuint64_t)cols / 64};
  const cuuint64_t strides[2] = {(cuuint64_t)cols * 2, 128};
  const cuuint32_t box[3] = {64, 32, (cuuint32_t)nb}, es[3] = {1, 1, 1};
  enc(m, CU_TENSOR_MAP_DATA_TYPE_BFLOAT16, nb ? 3 : 2, const_cast<void*>(ptr), dims, strides, box, es, CU_TENSOR_MAP_INTERLEAVE_NONE,
      CU_TENSOR_MAP_SWIZZLE_128B, CU_TENSOR_MAP_L2_PROMOTION_L2_128B, CU_TENSOR_MAP_FLOAT_OOB_FILL_NONE);
}
template <class... KA, class... A>
void launch(void (*kern)(KA...), int grid, int block, int smem, int cluster, bool pdl, A... args) {
  cudaFuncSetAttribute(kern, cudaFuncAttributeMaxDynamicSharedMemorySize, smem);
  cudaLaunchConfig_t cfg = {};
  cfg.gridDim = dim3(grid); cfg.blockDim = dim3(block); cfg.dynamicSmemBytes = smem; cfg.stream = cudaStreamPerThread;
  cudaLaunchAttribute at[2];
  int n = 0;
  if (cluster > 1) { at[n].id = cudaLaunchAttributeClusterDimension; at[n].val.clusterDim.x = cluster; at[n].val.clusterDim.y = 1; at[n].val.clusterDim.z = 1; n++; }
  if (pdl) { at[n].id = cudaLaunchAttributeProgrammaticStreamSerialization; at[n].val.programmaticStreamSerializationAllowed = 1; n++; }
  cfg.attrs = at; cfg.numAttrs = n;
  cudaLaunchKernelEx(&cfg, kern, args...);
}
template <class T> void* sym(T& s) { void* p = nullptr; cudaGetSymbolAddress(&p, s); return p; }

}

#define MODE(b) 0
extern "C" void kernel_launch(void* const* d_in, const int* in_sizes, int n_in, void* d_out, int out_size) {
  const __nv_bfloat16* x = (const __nv_bfloat16*)d_in[0];
  void* fn = nullptr; cudaDriverEntryPointQueryResult qr;
  cudaGetDriverEntryPoint("cuTensorMapEncodeTiled", &fn, cudaEnableDefault, &qr);
  EncodeFn enc = (EncodeFn)fn;

  ChainParams ch = {};
  PostParams op = {};
  for (int i = 0; i < 3; i++) {
    const cuuint64_t dims[3] = {HD, 128, 5}, strides[2] = {HD * 2, HD * 256};
    const cuuint32_t box[3] = {64, 128, 5}, es[3] = {1, 1, 1};
    enc(i == 0 ? &ch.wq : i == 1 ? &ch.wk : &ch.wv, CU_TENSOR_MAP_DATA_TYPE_BFLOAT16, 3, d_in[2 + i], dims, strides, box, es, CU_TENSOR_MAP_INTERLEAVE_NONE,
        CU_TENSOR_MAP_SWIZZLE_128B, W_PROMO, CU_TENSOR_MAP_FLOAT_OOB_FILL_NONE);
  }
  {
    const cuuint64_t dims[3] = {DM, HD, 7}, strides[2] = {DM * 2, 64};
    const cuuint32_t box[3] = {32, 64, 7}, es[3] = {1, 1, 1};
    enc(&ch.wo, CU_TENSOR_MAP_DATA_TYPE_BFLOAT16, 3, d_in[5], dims, strides, box, es, CU_TENSOR_MAP_INTERLEAVE_NONE,
        CU_TENSOR_MAP_SWIZZLE_64B, CU_TENSOR_MAP_L2_PROMOTION_L2_128B, CU_TENSOR_MAP_FLOAT_OOB_FILL_NONE);
  }
  ch.mem0 = (const __nv_bfloat16*)d_in[1];
  ch.pool = (uint8_t*)(((uintptr_t)sym(g_pool) + 8191) & ~(uintptr_t)8191); ch.kv = (uint8_t*)sym(g_kv); ch.xc = (const uint32_t*)sym(g_xc); ch.sync = (uint32_t*)sym(g_sync);
  ch.d1 = 0; ch.d1b = 0; ch.d2 = 0; ch.d2b = 0;
  make_map(enc, &op.wq, d_in[2], HD, DM, 3);
  make_map(enc, &op.wo, d_in[5], DM, HD, 5); make_map(enc, &op.wo2, d_in[5], DM, HD, 0);
  make_map(enc, &op.wb, d_in[8], 1920, DM, 5); make_map(enc, &op.wb2, d_in[8], 1920, DM, 0);
  op.gap = 17; op.share = 20; op.look = 14; op.gap2 = 0; op.pol = 0;

  const Weights wa = {{(const uint8_t*)d_in[3], (const uint8_t*)d_in[4], (const uint8_t*)d_in[2], (const uint8_t*)d_in[5]}}, none = {};
  launch(first_kernel, 132, 256, 128 * 1024, 1, false, x, (const uint4*)d_in[9], wa);
  for (int layer = 0; layer < 2; layer++) {
    ch.layer = ch.d2b = op.layer = layer;
    launch(chain_kernel, 96, 256, CH_SMEM, 3, true, ch);
    launch(post_kernel, MODE(3) ? 36 : 132, 384, OP_SMEM, 1, !MODE(1), op);
    const AbParams ab = {layer == 0 ? wa : none, (uint32_t*)sym(g_bo) + layer * 128, layer == 0 ? nullptr : (uint32_t*)d_out};
    launch(attn_b_kernel, 128, AB_T + 32, AB_SMEM, 1, true, ab);
  }
}
```

```cpp
#include <cuda_runtime.h>
#include <cuda_bf16.h>
#include <cuda.h>
#include <stdint.h>

namespace {

constexpr int SEQ = 2048, DM = 640, HD = 6144, NSEG = 64;
constexpr int SPIN_LIMIT = 1 << 20;

__device__ __align__(128) float4 g_x[SEQ * DM / 4];
__device__ __align__(128) uint32_t g_of[SEQ * DM / 2];
__device__ __align__(128) uint4 g_wb[DM * DM / 8];
__device__ __align__(16) float2 g_stat[16 * 8 * 128];
__device__ uint32_t g_bo[8 * 32];
__device__ __align__(128) uint4 g_q[SEQ * HD / 8];
__device__ __align__(128) uint32_t g_o[SEQ * HD / 2];
constexpr int KV_BYTES = 5120, KV_M = 4096, KV_V = NSEG * KV_BYTES;
__device__ __align__(128) uint8_t g_kv[96 * 2 * NSEG * KV_BYTES];
__device__ __align__(128) uint32_t g_xc[SEQ * DM / 2];
#define OP_B4 0
#define OP_B8 10
#define OP_B16 15
#define QA_END 12
__host__ __device__ constexpr int op_split(int b) { return b < OP_B4 ? 2 : b < OP_B8 ? 4 : b < OP_B16 ? 8 : 16; }
__host__ __device__ constexpr int fin_items(int b) { return b < OP_B8 ? 4 : op_split(b); }
#define AB_PF 2
#define AB_PF0 0
#define AB_PFD 6000
#define W_PROMO CU_TENSOR_MAP_L2_PROMOTION_L2_128B
#define OEF 0
#define BQ_HOLD 12
#define WEF 1
#define FK_PF 1
#define BQ_160 10
#define BQ_80 16
#define OP_160 16
__host__ __device__ constexpr int op_width(int b) { return b < OP_160 ? 320 : 160; }
__host__ __device__ constexpr int bq_width(int b) { return b < BQ_160 ? 320 : b < BQ_80 ? 160 : 80; }
__device__ __align__(128) uint2 g_part[16 * 16 * 16 * 40 * 32];
__device__ __align__(128) uint32_t g_xn[SEQ * DM / 2];
constexpr int SY_Q = 128, SY_T = 160, SY_QC = 192, SY_N = 193;
__device__ __align__(16) uint32_t g_sync[SY_N];
constexpr int NSLOT = 92;
__device__ uint32_t g_pool[(NSLOT + 2) * 2048];
__device__ int g_smpart[256], g_orient[NSLOT];
__device__ uint32_t g_smclk[256], g_smuse[256];
__device__ uint32_t g_bqkv[3 * 32 * 256 * 96];

#define ABT(L, i)
#define MODE_D(b) 0
#define DELAY(d)
#define XT(i)
#define MISS(k, n)
#define PRO(i)
#define TRACE(w)
#define ITEM(code, w)
#define TR(i, v)
#define TM(i)
#define TM1(i)
#define TMD(i, dep)
#define TMV(i, at, v)

__device__ __forceinline__ uint32_t gtime() { uint32_t c; asm volatile("mov.u32 %0, %%globaltimer_lo;" : "=r"(c) :: "memory"); return c; }
__device__ __forceinline__ uint32_t clk32() { uint32_t c; asm volatile("mov.u32 %0, %%clock;" : "=r"(c) :: "memory"); return c; }
__device__ __forceinline__ uint32_t s2u(const void* p) { return (uint32_t)__cvta_generic_to_shared(p); }
__device__ __forceinline__ uint32_t pack2(float a, float b) {
  uint32_t r; asm("cvt.rn.bf16x2.f32 %0, %1, %2;" : "=r"(r) : "f"(b), "f"(a)); return r; }
__device__ __forceinline__ float bf_lo(uint32_t w) { return __uint_as_float(w << 16); }
__device__ __forceinline__ float bf_hi(uint32_t w) { return __uint_as_float(w & 0xffff0000u); }
__device__ __forceinline__ float ex2(float x) { float y; asm("ex2.approx.ftz.f32 %0, %1;" : "=f"(y) : "f"(x)); return y; }

__device__ __forceinline__ void mbar_init(uint32_t bar, uint32_t n) {
  asm volatile("mbarrier.init.shared::cta.b64 [%0], %1;" :: "r"(bar), "r"(n) : "memory"); }
__device__ __forceinline__ void mbar_expect(uint32_t bar, uint32_t bytes) {
  asm volatile("mbarrier.arrive.expect_tx.shared::cta.b64 _, [%0], %1;" :: "r"(bar), "r"(bytes) : "memory"); }
__device__ __forceinline__ void mbar_arrive(uint32_t bar) {
  asm volatile("mbarrier.arrive.shared::cta.b64 _, [%0];" :: "r"(bar) : "memory"); }
__device__ __forceinline__ void mbar_wait(uint32_t bar, uint32_t ph) {
  asm volatile("{.reg .pred p; .reg .u32 n; mov.u32 n, 0;\n"
               "W: mbarrier.try_wait.parity.shared::cta.b64 p, [%0], %1; @p bra D;\n"
               "add.u32 n, n, 1; setp.gt.u32 p, n, %2; @p trap; bra W;\n"
               "D: }" :: "r"(bar), "r"(ph), "n"(SPIN_LIMIT) : "memory");
}
__device__ __forceinline__ void mbar_wait_cluster(uint32_t bar, uint32_t ph) {
  asm volatile("{.reg .pred p; .reg .u32 n; mov.u32 n, 0;\n"
               "W: mbarrier.try_wait.parity.acquire.cluster.shared::cta.b64 p, [%0], %1; @p bra D;\n"
               "add.u32 n, n, 1; setp.gt.u32 p, n, %2; @p trap; bra W;\n"
               "D: }" :: "r"(bar), "r"(ph), "n"(SPIN_LIMIT) : "memory");
}
__device__ __forceinline__ void spin_guard(int& n) {
  asm volatile("{.reg .pred p; add.s32 %0, %0, 1; setp.gt.s32 p, %0, %1; @p trap;}" : "+r"(n) : "n"(SPIN_LIMIT));
}
__device__ __forceinline__ void pdl_wait() { asm volatile("griddepcontrol.wait;" ::: "memory"); TRACE(1); }
__device__ __forceinline__ void pdl_launch() { asm volatile("griddepcontrol.launch_dependents;" ::: "memory"); }
__device__ __forceinline__ uint32_t ld_acquire(const uint32_t* p) { uint32_t v; asm volatile("ld.acquire.gpu.global.u32 %0, [%1];" : "=r"(v) : "l"(p) : "memory"); return v; }
__device__ __forceinline__ void red_release(uint32_t* p, uint32_t v) { asm volatile("red.release.gpu.global.add.u32 [%0], %1;" :: "l"(p), "r"(v) : "memory"); }
__device__ __forceinline__ void red_relaxed(uint32_t* p, uint32_t v) { asm volatile("red.relaxed.gpu.global.add.u32 [%0], %1;" :: "l"(p), "r"(v) : "memory"); }
__device__ __forceinline__ void fence_async_global() { asm volatile("fence.proxy.async.global;" ::: "memory"); }
__device__ __forceinline__ void fence_async() { asm volatile("fence.proxy.async.shared::cta;" ::: "memory"); }
__device__ __forceinline__ void bar_sync(int id, int n) { asm volatile("bar.sync %0, %1;" :: "r"(id), "r"(n) : "memory"); }
__device__ __forceinline__ void bar_arrive(int id, int n) { asm volatile("bar.arrive %0, %1;" :: "r"(id), "r"(n) : "memory"); }
__device__ __forceinline__ void tma_load(uint32_t dst, const CUtensorMap* m, int c0, int c1, uint32_t bar) {
  asm volatile("cp.async.bulk.tensor.2d.shared::cluster.global.mbarrier::complete_tx::bytes [%0], [%1, {%3, %4}], [%2];"
               :: "r"(dst), "l"(m), "r"(bar), "r"(c0), "r"(c1) : "memory"); }
template <bool STREAM = false>
__device__ __forceinline__ void tma_load3(uint32_t dst, const CUtensorMap* m, int c0, int c1, uint32_t bar) {
  if (STREAM)
    asm volatile("{.reg .b64 pol; createpolicy.fractional.L2::evict_first.b64 pol, 1.0;\n"
                 "cp.async.bulk.tensor.3d.shared::cluster.global.mbarrier::complete_tx::bytes.L2::cache_hint [%0], [%1, {%3, %4, 0}], [%2], pol;}"
                 :: "r"(dst), "l"(m), "r"(bar), "r"(c0), "r"(c1) : "memory");
  else
  asm volatile("cp.async.bulk.tensor.3d.shared::cluster.global.mbarrier::complete_tx::bytes [%0], [%1, {%3, %4, 0}], [%2];"
               :: "r"(dst), "l"(m), "r"(bar), "r"(c0), "r"(c1) : "memory"); }
__device__ __forceinline__ void tma_load3z(uint32_t dst, const CUtensorMap* m, int c1, int c2, uint32_t bar) {
  asm volatile("cp.async.bulk.tensor.3d.shared::cluster.global.mbarrier::complete_tx::bytes [%0], [%1, {0, %3, %4}], [%2];"
               :: "r"(dst), "l"(m), "r"(bar), "r"(c1), "r"(c2) : "memory"); }
__device__ __forceinline__ void tma_store(const CUtensorMap* m, uint32_t src, int c0, int c1) {
  asm volatile("cp.async.bulk.tensor.2d.global.shared::cta.bulk_group [%0, {%2, %3}], [%1];"
               :: "l"(m), "r"(src), "r"(c0), "r"(c1) : "memory"); }
__device__ __forceinline__ void tma_store_stream(const CUtensorMap* m, uint32_t src, int c0, int c1) {
  asm volatile("{.reg .b64 pol; createpolicy.fractional.L2::evict_first.b64 pol, 1.0;\n"
               "cp.async.bulk.tensor.2d.global.shared::cta.bulk_group.L2::cache_hint [%0, {%2, %3}], [%1], pol;}"
               :: "l"(m), "r"(src), "r"(c0), "r"(c1) : "memory"); }
__device__ __forceinline__ void bulk_load(uint32_t dst, const void* src, uint32_t bytes, uint32_t bar) {
  asm volatile("cp.async.bulk.shared::cluster.global.mbarrier::complete_tx::bytes [%0], [%1], %2, [%3];"
               :: "r"(dst), "l"(src), "r"(bytes), "r"(bar) : "memory"); }
__device__ __forceinline__ void bulk_load_last(uint32_t dst, const void* src, uint32_t bytes, uint32_t bar) {
  asm volatile("{.reg .b64 pol; createpolicy.fractional.L2::evict_first.b64 pol, 1.0;\n"
               "cp.async.bulk.shared::cluster.global.mbarrier::complete_tx::bytes.L2::cache_hint [%0], [%1], %2, [%3], pol;}"
               :: "r"(dst), "l"(src), "r"(bytes), "r"(bar) : "memory"); }
__device__ __forceinline__ void tma_load_last(uint32_t dst, const CUtensorMap* m, int c0, int c1, uint32_t bar) {
  asm volatile("{.reg .b64 pol; createpolicy.fractional.L2::evict_first.b64 pol, 1.0;\n"
               "cp.async.bulk.tensor.2d.shared::cluster.global.mbarrier::complete_tx::bytes.L2::cache_hint [%0], [%1, {%3, %4}], [%2], pol;}"
               :: "r"(dst), "l"(m), "r"(bar), "r"(c0), "r"(c1) : "memory"); }
__device__ __forceinline__ void bulk_send(uint32_t dst, uint32_t src, uint32_t bytes, uint32_t bar) {
  asm volatile("cp.async.bulk.shared::cluster.shared::cta.mbarrier::complete_tx::bytes [%0], [%1], %2, [%3];"
               :: "r"(dst), "r"(src), "r"(bytes), "r"(bar) : "memory"); }
__device__ __forceinline__ void bulk_store(void* dst, uint32_t src, uint32_t bytes) {
  asm volatile("cp.async.bulk.global.shared::cta.bulk_group [%0], [%1], %2;" :: "l"(dst), "r"(src), "r"(bytes) : "memory"); }
__device__ __forceinline__ void bulk_commit() { asm volatile("cp.async.bulk.commit_group;" ::: "memory"); }
template <int N> __device__ __forceinline__ void bulk_wait_read() { asm volatile("cp.async.bulk.wait_group.read %0;" :: "n"(N) : "memory"); }
template <int N> __device__ __forceinline__ void bulk_wait() { asm volatile("cp.async.bulk.wait_group %0;" :: "n"(N) : "memory"); }

__device__ __forceinline__ uint64_t mkdesc(uint32_t addr, uint32_t lbo, uint32_t sbo, uint32_t sw) {
  return (uint64_t)((addr & 0x3FFFF) >> 4) | ((uint64_t)(lbo >> 4) << 16) | ((uint64_t)(sbo >> 4) << 32) | ((uint64_t)sw << 62); }
__device__ __forceinline__ void wg_fence() { asm volatile("wgmma.fence.sync.aligned;" ::: "memory"); }
__device__ __forceinline__ void wg_commit() { asm volatile("wgmma.commit_group.sync.aligned;" ::: "memory"); }
template <int N> __device__ __forceinline__ void wg_wait() { asm volatile("wgmma.wait_group.sync.aligned %0;" :: "n"(N) : "memory"); }
template <int N> __device__ __forceinline__ void reg_fence(float* d) {
#pragma unroll
  for (int i = 0; i < N; i++) asm volatile("" : "+f"(d[i]) :: "memory");
}

__device__ __forceinline__ void mma16(float* d, uint32_t a0, uint32_t a1, uint32_t a2, uint32_t a3, uint32_t b0, uint32_t b1) {
  asm volatile("mma.sync.aligned.m16n8k16.row.col.f32.bf16.bf16.f32 {%0,%1,%2,%3},{%4,%5,%6,%7},{%8,%9},{%0,%1,%2,%3};"
               : "+f"(d[0]), "+f"(d[1]), "+f"(d[2]), "+f"(d[3]) : "r"(a0), "r"(a1), "r"(a2), "r"(a3), "r"(b0), "r"(b1)); }
__device__ __forceinline__ void mma8(float* d, uint32_t a0, uint32_t a1, uint32_t b0) {
  asm volatile("mma.sync.aligned.m16n8k8.row.col.f32.bf16.bf16.f32 {%0,%1,%2,%3},{%4,%5},{%6},{%0,%1,%2,%3};"
               : "+f"(d[0]), "+f"(d[1]), "+f"(d[2]), "+f"(d[3]) : "r"(a0), "r"(a1), "r"(b0)); }
__device__ __forceinline__ void ldsm4(uint32_t* r, uint32_t a) {
  asm volatile("ldmatrix.sync.aligned.m8n8.x4.shared.b16 {%0,%1,%2,%3},[%4];" : "=r"(r[0]), "=r"(r[1]), "=r"(r[2]), "=r"(r[3]) : "r"(a) : "memory"); }
__device__ __forceinline__ void ldsm4t(uint32_t* r, uint32_t a) {
  asm volatile("ldmatrix.sync.aligned.m8n8.x4.trans.shared.b16 {%0,%1,%2,%3},[%4];" : "=r"(r[0]), "=r"(r[1]), "=r"(r[2]), "=r"(r[3]) : "r"(a) : "memory"); }
__device__ __forceinline__ void ldsm2(uint32_t* r, uint32_t a) {
  asm volatile("ldmatrix.sync.aligned.m8n8.x2.shared.b16 {%0,%1},[%2];" : "=r"(r[0]), "=r"(r[1]) : "r"(a) : "memory"); }
__device__ __forceinline__ void stsm4(uint32_t a, uint32_t r0, uint32_t r1, uint32_t r2, uint32_t r3) {
  asm volatile("stmatrix.sync.aligned.m8n8.x4.shared.b16 [%0], {%1,%2,%3,%4};" :: "r"(a), "r"(r0), "r"(r1), "r"(r2), "r"(r3) : "memory"); }
__device__ __forceinline__ void stsm2t(uint32_t a, uint32_t r0, uint32_t r1) {
  asm volatile("stmatrix.sync.aligned.m8n8.x2.trans.shared.b16 [%0], {%1,%2};" :: "r"(a), "r"(r0), "r"(r1) : "memory"); }
__device__ __forceinline__ void stsm4t(uint32_t a, uint32_t r0, uint32_t r1, uint32_t r2, uint32_t r3) {
  asm volatile("stmatrix.sync.aligned.m8n8.x4.trans.shared.b16 [%0], {%1,%2,%3,%4};" :: "r"(a), "r"(r0), "r"(r1), "r"(r2), "r"(r3) : "memory"); }
__device__ __forceinline__ void st_async128(uint32_t a, uint4 v, uint32_t bar) {
  asm volatile("st.async.shared::cluster.mbarrier::complete_tx::bytes.v4.b32 [%0], {%1,%2,%3,%4}, [%5];" :: "r"(a), "r"(v.x), "r"(v.y), "r"(v.z), "r"(v.w), "r"(bar) : "memory"); }
__device__ __forceinline__ void sts32(uint32_t a, uint32_t v) { asm volatile("st.shared.b32 [%0], %1;" :: "r"(a), "r"(v) : "memory"); }
__device__ __forceinline__ void sts64f(uint32_t a, float x, float y) { asm volatile("st.shared.v2.f32 [%0], {%1,%2};" :: "r"(a), "f"(x), "f"(y) : "memory"); }
__device__ __forceinline__ void sts128(uint32_t a, uint4 v) {
  asm volatile("st.shared.v4.b32 [%0], {%1,%2,%3,%4};" :: "r"(a), "r"(v.x), "r"(v.y), "r"(v.z), "r"(v.w) : "memory"); }
__device__ __forceinline__ void sts128f(uint32_t a, float x, float y, float z, float w) {
  asm volatile("st.shared.v4.f32 [%0], {%1,%2,%3,%4};" :: "r"(a), "f"(x), "f"(y), "f"(z), "f"(w) : "memory"); }
__device__ __forceinline__ float lds32f(uint32_t a) { float v; asm volatile("ld.shared.f32 %0, [%1];" : "=f"(v) : "r"(a) : "memory"); return v; }
__device__ __forceinline__ float2 lds64f(uint32_t a) { float2 v; asm volatile("ld.shared.v2.f32 {%0,%1}, [%2];" : "=f"(v.x), "=f"(v.y) : "r"(a) : "memory"); return v; }
__device__ __forceinline__ float4 lds128f(uint32_t a) {
  float4 v; asm volatile("ld.shared.v4.f32 {%0,%1,%2,%3}, [%4];" : "=f"(v.x), "=f"(v.y), "=f"(v.z), "=f"(v.w) : "r"(a) : "memory"); return v; }
__device__ __forceinline__ uint4 lds128(uint32_t a) {
  uint4 v; asm volatile("ld.shared.v4.b32 {%0,%1,%2,%3}, [%4];" : "=r"(v.x), "=r"(v.y), "=r"(v.z), "=r"(v.w) : "r"(a) : "memory"); return v; }
__device__ __forceinline__ uint4 ldg_strong128(const void* p) {
  uint4 v; asm volatile("ld.relaxed.gpu.global.v4.u32 {%0,%1,%2,%3}, [%4];" : "=r"(v.x), "=r"(v.y), "=r"(v.z), "=r"(v.w) : "l"(p) : "memory"); return v; }
__device__ __forceinline__ void stg_strong32(void* p, uint32_t v) { asm volatile("st.relaxed.gpu.global.u32 [%0], %1;" :: "l"(p), "r"(v) : "memory"); }
__device__ __forceinline__ void stg_strong16(void* p, uint32_t v) { asm volatile("st.relaxed.gpu.global.u16 [%0], %1;" :: "l"(p), "h"((uint16_t)v) : "memory"); }
__device__ __forceinline__ void stg_strong128(void* p, uint4 v) {
  asm volatile("st.relaxed.gpu.global.v4.u32 [%0], {%1,%2,%3,%4};" :: "l"(p), "r"(v.x), "r"(v.y), "r"(v.z), "r"(v.w) : "memory"); }
__device__ __forceinline__ uint32_t mapa(uint32_t a, uint32_t r) {
  uint32_t o; asm("mapa.shared::cluster.u32 %0, %1, %2;" : "=r"(o) : "r"(a), "r"(r)); return o; }
__device__ __forceinline__ void st_async2f(uint32_t a, float x, float y, uint32_t bar) {
  asm volatile("st.async.shared::cluster.mbarrier::complete_tx::bytes.v2.f32 [%0], {%1,%2}, [%3];" :: "r"(a), "f"(x), "f"(y), "r"(bar) : "memory"); }
__device__ __forceinline__ void st_async32(uint32_t a, uint32_t x, uint32_t bar) {
  asm volatile("st.async.shared::cluster.mbarrier::complete_tx::bytes.b32 [%0], %1, [%2];" :: "r"(a), "r"(x), "r"(bar) : "memory"); }
__device__ __forceinline__ uint32_t lds32(uint32_t a) { uint32_t v; asm volatile("ld.shared.b32 %0, [%1];" : "=r"(v) : "r"(a) : "memory"); return v; }
__device__ __forceinline__ void st_async64(uint32_t a, uint32_t x, uint32_t y, uint32_t bar) {
  asm volatile("st.async.shared::cluster.mbarrier::complete_tx::bytes.v2.b32 [%0], {%1,%2}, [%3];" :: "r"(a), "r"(x), "r"(y), "r"(bar) : "memory"); }
__device__ __forceinline__ uint2 lds64(uint32_t a) { uint2 v; asm volatile("ld.shared.v2.b32 {%0,%1}, [%2];" : "=r"(v.x), "=r"(v.y) : "r"(a) : "memory"); return v; }
__device__ __forceinline__ void sts64(uint32_t a, uint32_t x, uint32_t y) { asm volatile("st.shared.v2.b32 [%0], {%1,%2};" :: "r"(a), "r"(x), "r"(y) : "memory"); }
__device__ __forceinline__ uint32_t ldg_strong32(const void* p) { uint32_t v; asm volatile("ld.relaxed.gpu.global.u32 %0, [%1];" : "=r"(v) : "l"(p) : "memory"); return v; }
__device__ __forceinline__ uint32_t transpose8(uint32_t x) { uint32_t r; asm volatile("movmatrix.sync.aligned.m8n8.trans.b16 %0, %1;" : "=r"(r) : "r"(x)); return r; }
__device__ __forceinline__ uint32_t hadd2(uint32_t a, uint32_t b) { uint32_t r; asm("add.rn.bf16x2 %0, %1, %2;" : "=r"(r) : "r"(a), "r"(b)); return r; }
__device__ __forceinline__ uint32_t min4(uint4 v) { return min(__vimin3_u32(v.x, v.y, v.z), v.w); }

__device__ __forceinline__ void wg_ss192_01(float* d, uint64_t da, uint64_t db, int sd) {
  asm volatile("{.reg .pred p; setp.ne.b32 p, %98, 0;\n"
    "wgmma.mma_async.sync.aligned.m64n192k16.f32.bf16.bf16 {%0,%1,%2,%3,%4,%5,%6,%7,%8,%9,%10,%11,%12,%13,%14,%15,%16,%17,%18,%19,%20,%21,%22,%23,%24,%25,%26,%27,%28,%29,%30,%31,%32,%33,%34,%35,%36,%37,%38,%39,%40,%41,%42,%43,%44,%45,%46,%47,%48,%49,%50,%51,%52,%53,%54,%55,%56,%57,%58,%59,%60,%61,%62,%63,%64,%65,%66,%67,%68,%69,%70,%71,%72,%73,%74,%75,%76,%77,%78,%79,%80,%81,%82,%83,%84,%85,%86,%87,%88,%89,%90,%91,%92,%93,%94,%95}, %96, %97, p, 1, 1, 0, 1;}"
    : "+f"(d[0]),"+f"(d[1]),"+f"(d[2]),"+f"(d[3]),"+f"(d[4]),"+f"(d[5]),"+f"(d[6]),"+f"(d[7]),"+f"(d[8]),"+f"(d[9]),"+f"(d[10]),"+f"(d[11]),"+f"(d[12]),"+f"(d[13]),"+f"(d[14]),"+f"(d[15]),"+f"(d[16]),"+f"(d[17]),"+f"(d[18]),"+f"(d[19]),"+f"(d[20]),"+f"(d[21]),"+f"(d[22]),"+f"(d[23]),"+f"(d[24]),"+f"(d[25]),"+f"(d[26]),"+f"(d[27]),"+f"(d[28]),"+f"(d[29]),"+f"(d[30]),"+f"(d[31]),"+f"(d[32]),"+f"(d[33]),"+f"(d[34]),"+f"(d[35]),"+f"(d[36]),"+f"(d[37]),"+f"(d[38]),"+f"(d[39]),"+f"(d[40]),"+f"(d[41]),"+f"(d[42]),"+f"(d[43]),"+f"(d[44]),"+f"(d[45]),"+f"(d[46]),"+f"(d[47]),"+f"(d[48]),"+f"(d[49]),"+f"(d[50]),"+f"(d[51]),"+f"(d[52]),"+f"(d[53]),"+f"(d[54]),"+f"(d[55]),"+f"(d[56]),"+f"(d[57]),"+f"(d[58]),"+f"(d[59]),"+f"(d[60]),"+f"(d[61]),"+f"(d[62]),"+f"(d[63]),"+f"(d[64]),"+f"(d[65]),"+f"(d[66]),"+f"(d[67]),"+f"(d[68]),"+f"(d[69]),"+f"(d[70]),"+f"(d[71]),"+f"(d[72]),"+f"(d[73]),"+f"(d[74]),"+f"(d[75]),"+f"(d[76]),"+f"(d[77]),"+f"(d[78]),"+f"(d[79]),"+f"(d[80]),"+f"(d[81]),"+f"(d[82]),"+f"(d[83]),"+f"(d[84]),"+f"(d[85]),"+f"(d[86]),"+f"(d[87]),"+f"(d[88]),"+f"(d[89]),"+f"(d[90]),"+f"(d[91]),"+f"(d[92]),"+f"(d[93]),"+f"(d[94]),"+f"(d[95])
    : "l"(da), "l"(db), "r"(sd));
}
__device__ __forceinline__ void wg_ss128_01(float* d, uint64_t da, uint64_t db, int sd) {
  asm volatile("{.reg .pred p; setp.ne.b32 p, %66, 0;\n"
    "wgmma.mma_async.sync.aligned.m64n128k16.f32.bf16.bf16 {%0,%1,%2,%3,%4,%5,%6,%7,%8,%9,%10,%11,%12,%13,%14,%15,%16,%17,%18,%19,%20,%21,%22,%23,%24,%25,%26,%27,%28,%29,%30,%31,%32,%33,%34,%35,%36,%37,%38,%39,%40,%41,%42,%43,%44,%45,%46,%47,%48,%49,%50,%51,%52,%53,%54,%55,%56,%57,%58,%59,%60,%61,%62,%63}, %64, %65, p, 1, 1, 0, 1;}"
    : "+f"(d[0]),"+f"(d[1]),"+f"(d[2]),"+f"(d[3]),"+f"(d[4]),"+f"(d[5]),"+f"(d[6]),"+f"(d[7]),"+f"(d[8]),"+f"(d[9]),"+f"(d[10]),"+f"(d[11]),"+f"(d[12]),"+f"(d[13]),"+f"(d[14]),"+f"(d[15]),"+f"(d[16]),"+f"(d[17]),"+f"(d[18]),"+f"(d[19]),"+f"(d[20]),"+f"(d[21]),"+f"(d[22]),"+f"(d[23]),"+f"(d[24]),"+f"(d[25]),"+f"(d[26]),"+f"(d[27]),"+f"(d[28]),"+f"(d[29]),"+f"(d[30]),"+f"(d[31]),"+f"(d[32]),"+f"(d[33]),"+f"(d[34]),"+f"(d[35]),"+f"(d[36]),"+f"(d[37]),"+f"(d[38]),"+f"(d[39]),"+f"(d[40]),"+f"(d[41]),"+f"(d[42]),"+f"(d[43]),"+f"(d[44]),"+f"(d[45]),"+f"(d[46]),"+f"(d[47]),"+f"(d[48]),"+f"(d[49]),"+f"(d[50]),"+f"(d[51]),"+f"(d[52]),"+f"(d[53]),"+f"(d[54]),"+f"(d[55]),"+f"(d[56]),"+f"(d[57]),"+f"(d[58]),"+f"(d[59]),"+f"(d[60]),"+f"(d[61]),"+f"(d[62]),"+f"(d[63])
    : "l"(da), "l"(db), "r"(sd));
}
__device__ __forceinline__ void wg_ss160_01(float* d, uint64_t da, uint64_t db, int sd) {
  asm volatile("{.reg .pred p; setp.ne.b32 p, %82, 0;\n"
    "wgmma.mma_async.sync.aligned.m64n160k16.f32.bf16.bf16 {%0,%1,%2,%3,%4,%5,%6,%7,%8,%9,%10,%11,%12,%13,%14,%15,%16,%17,%18,%19,%20,%21,%22,%23,%24,%25,%26,%27,%28,%29,%30,%31,%32,%33,%34,%35,%36,%37,%38,%39,%40,%41,%42,%43,%44,%45,%46,%47,%48,%49,%50,%51,%52,%53,%54,%55,%56,%57,%58,%59,%60,%61,%62,%63,%64,%65,%66,%67,%68,%69,%70,%71,%72,%73,%74,%75,%76,%77,%78,%79}, %80, %81, p, 1, 1, 0, 1;}"
    : "+f"(d[0]),"+f"(d[1]),"+f"(d[2]),"+f"(d[3]),"+f"(d[4]),"+f"(d[5]),"+f"(d[6]),"+f"(d[7]),"+f"(d[8]),"+f"(d[9]),"+f"(d[10]),"+f"(d[11]),"+f"(d[12]),"+f"(d[13]),"+f"(d[14]),"+f"(d[15]),"+f"(d[16]),"+f"(d[17]),"+f"(d[18]),"+f"(d[19]),"+f"(d[20]),"+f"(d[21]),"+f"(d[22]),"+f"(d[23]),"+f"(d[24]),"+f"(d[25]),"+f"(d[26]),"+f"(d[27]),"+f"(d[28]),"+f"(d[29]),"+f"(d[30]),"+f"(d[31]),"+f"(d[32]),"+f"(d[33]),"+f"(d[34]),"+f"(d[35]),"+f"(d[36]),"+f"(d[37]),"+f"(d[38]),"+f"(d[39]),"+f"(d[40]),"+f"(d[41]),"+f"(d[42]),"+f"(d[43]),"+f"(d[44]),"+f"(d[45]),"+f"(d[46]),"+f"(d[47]),"+f"(d[48]),"+f"(d[49]),"+f"(d[50]),"+f"(d[51]),"+f"(d[52]),"+f"(d[53]),"+f"(d[54]),"+f"(d[55]),"+f"(d[56]),"+f"(d[57]),"+f"(d[58]),"+f"(d[59]),"+f"(d[60]),"+f"(d[61]),"+f"(d[62]),"+f"(d[63]),"+f"(d[64]),"+f"(d[65]),"+f"(d[66]),"+f"(d[67]),"+f"(d[68]),"+f"(d[69]),"+f"(d[70]),"+f"(d[71]),"+f"(d[72]),"+f"(d[73]),"+f"(d[74]),"+f"(d[75]),"+f"(d[76]),"+f"(d[77]),"+f"(d[78]),"+f"(d[79])
    : "l"(da), "l"(db), "r"(sd));
}
__device__ __forceinline__ void wg_ss80_01(float* d, uint64_t da, uint64_t db, int sd) {
  asm volatile("{.reg .pred p; setp.ne.b32 p, %42, 0;\n"
    "wgmma.mma_async.sync.aligned.m64n80k16.f32.bf16.bf16 {%0,%1,%2,%3,%4,%5,%6,%7,%8,%9,%10,%11,%12,%13,%14,%15,%16,%17,%18,%19,%20,%21,%22,%23,%24,%25,%26,%27,%28,%29,%30,%31,%32,%33,%34,%35,%36,%37,%38,%39}, %40, %41, p, 1, 1, 0, 1;}"
    : "+f"(d[0]),"+f"(d[1]),"+f"(d[2]),"+f"(d[3]),"+f"(d[4]),"+f"(d[5]),"+f"(d[6]),"+f"(d[7]),"+f"(d[8]),"+f"(d[9]),"+f"(d[10]),"+f"(d[11]),"+f"(d[12]),"+f"(d[13]),"+f"(d[14]),"+f"(d[15]),"+f"(d[16]),"+f"(d[17]),"+f"(d[18]),"+f"(d[19]),"+f"(d[20]),"+f"(d[21]),"+f"(d[22]),"+f"(d[23]),"+f"(d[24]),"+f"(d[25]),"+f"(d[26]),"+f"(d[27]),"+f"(d[28]),"+f"(d[29]),"+f"(d[30]),"+f"(d[31]),"+f"(d[32]),"+f"(d[33]),"+f"(d[34]),"+f"(d[35]),"+f"(d[36]),"+f"(d[37]),"+f"(d[38]),"+f"(d[39])
    : "l"(da), "l"(db), "r"(sd));
}
__device__ __forceinline__ void wg_rs32_00(float* d, uint32_t a0, uint32_t a1, uint32_t a2, uint32_t a3, uint64_t db, int sd) {
  asm volatile("{.reg .pred p; setp.ne.b32 p, %21, 0;\n"
    "wgmma.mma_async.sync.aligned.m64n32k16.f32.bf16.bf16 {%0,%1,%2,%3,%4,%5,%6,%7,%8,%9,%10,%11,%12,%13,%14,%15}, {%16,%17,%18,%19}, %20, p, 1, 1, 0;}"
    : "+f"(d[0]),"+f"(d[1]),"+f"(d[2]),"+f"(d[3]),"+f"(d[4]),"+f"(d[5]),"+f"(d[6]),"+f"(d[7]),"+f"(d[8]),"+f"(d[9]),"+f"(d[10]),"+f"(d[11]),"+f"(d[12]),"+f"(d[13]),"+f"(d[14]),"+f"(d[15])
    : "r"(a0), "r"(a1), "r"(a2), "r"(a3), "l"(db), "r"(sd));
}
__device__ __forceinline__ void wg_rs64_00(float* d, uint32_t a0, uint32_t a1, uint32_t a2, uint32_t a3, uint64_t db, int sd) {
  asm volatile("{.reg .pred p; setp.ne.b32 p, %37, 0;\n"
    "wgmma.mma_async.sync.aligned.m64n64k16.f32.bf16.bf16 {%0,%1,%2,%3,%4,%5,%6,%7,%8,%9,%10,%11,%12,%13,%14,%15,%16,%17,%18,%19,%20,%21,%22,%23,%24,%25,%26,%27,%28,%29,%30,%31}, {%32,%33,%34,%35}, %36, p, 1, 1, 0;}"
    : "+f"(d[0]),"+f"(d[1]),"+f"(d[2]),"+f"(d[3]),"+f"(d[4]),"+f"(d[5]),"+f"(d[6]),"+f"(d[7]),"+f"(d[8]),"+f"(d[9]),"+f"(d[10]),"+f"(d[11]),"+f"(d[12]),"+f"(d[13]),"+f"(d[14]),"+f"(d[15]),"+f"(d[16]),"+f"(d[17]),"+f"(d[18]),"+f"(d[19]),"+f"(d[20]),"+f"(d[21]),"+f"(d[22]),"+f"(d[23]),"+f"(d[24]),"+f"(d[25]),"+f"(d[26]),"+f"(d[27]),"+f"(d[28]),"+f"(d[29]),"+f"(d[30]),"+f"(d[31])
    : "r"(a0), "r"(a1), "r"(a2), "r"(a3), "l"(db), "r"(sd));
}
__device__ __forceinline__ void wg_rs24_01(float* d, uint32_t a0, uint32_t a1, uint32_t a2, uint32_t a3, uint64_t db, int sd) {
  asm volatile("{.reg .pred p; setp.ne.b32 p, %17, 0;\n"
    "wgmma.mma_async.sync.aligned.m64n24k16.f32.bf16.bf16 {%0,%1,%2,%3,%4,%5,%6,%7,%8,%9,%10,%11}, {%12,%13,%14,%15}, %16, p, 1, 1, 1;}"
    : "+f"(d[0]),"+f"(d[1]),"+f"(d[2]),"+f"(d[3]),"+f"(d[4]),"+f"(d[5]),"+f"(d[6]),"+f"(d[7]),"+f"(d[8]),"+f"(d[9]),"+f"(d[10]),"+f"(d[11])
    : "r"(a0), "r"(a1), "r"(a2), "r"(a3), "l"(db), "r"(sd));
}

#define AB_POLY 0xaa
#define AB_DEG 3
__device__ __forceinline__ constexpr bool poly_group(int group) { return (AB_POLY >> (group & 7)) & 1; }

template <int V> struct Int { static constexpr int value = V; };

template <int NG>
__device__ __forceinline__ void ln_stats(const float4 (&v)[NG][5], uint32_t scratch, float (&mean)[NG], float (&rs)[NG]) {
  const int warp = threadIdx.x >> 5, lane = threadIdx.x & 31;
#pragma unroll
  for (int r = 0; r < NG; r++) {
    float s = 0.f, q = 0.f;
#pragma unroll
    for (int i = 0; i < 5; i++) s += (v[r][i].x + v[r][i].y) + (v[r][i].z + v[r][i].w);
    s += __shfl_xor_sync(~0u, s, 1); s += __shfl_xor_sync(~0u, s, 2);
    s *= 1.f / 80;
#pragma unroll
    for (int i = 0; i < 5; i++) {
      const float x = v[r][i].x - s, y = v[r][i].y - s, z = v[r][i].z - s, w = v[r][i].w - s;
      q += (x * x + y * y) + (z * z + w * w);
    }
    q += __shfl_xor_sync(~0u, q, 1); q += __shfl_xor_sync(~0u, q, 2);
    mean[r] = s; rs[r] = q;
  }
  bar_sync(1, 256);
  if ((lane & 3) == 0) {
#pragma unroll
    for (int r = 0; r < NG; r++) sts64f(scratch + r * 512 + lane * 16 + warp * 8, mean[r], rs[r]);
  }
  bar_sync(1, 256);
#pragma unroll
  for (int r = 0; r < NG; r++) {
    const float4 e = lds128f(scratch + r * 512 + lane * 16);
    float t = e.x + e.z;
    t += __shfl_xor_sync(~0u, t, 1); t += __shfl_xor_sync(~0u, t, 2);
    t *= 0.125f;
    float q = e.y + e.w + 80.f * ((e.x - t) * (e.x - t) + (e.z - t) * (e.z - t));
    q += __shfl_xor_sync(~0u, q, 1); q += __shfl_xor_sync(~0u, q, 2);
    mean[r] = t; rs[r] = rsqrtf(q * (1.f / DM) + 1e-5f);
  }
}

__device__ __forceinline__ void ln_store(const uint32_t (&w)[2][5][2], int tile, int u0, bool live = true) {
  const int lane = threadIdx.x & 31;
  uint32_t* xc = g_xc + ((tile >> 1) * 40 + u0) * 256 + (tile & 1) * 64 + lane;
#pragma unroll
  for (int i = 0; i < 20; i++) if (live) xc[(i >> 1) * 128 + (i & 1) * 32] = w[i & 1][i >> 2][i >> 1 & 1];
#pragma unroll
  for (int i = 0; i < 5; i++) {
    const int u = u0 + i;
    uint32_t* xn = g_xn + (((tile >> 3) * 20 + (u >> 1)) * 16 + (tile & 1) * 8 + (tile & 6)) * 128 + (u & 1) * 64 + lane;
#pragma unroll
    for (int r = 0; r < 2; r++) if (live) { xn[r * 128] = w[r][i][0]; xn[r * 128 + 32] = w[r][i][1]; }
  }
}
__device__ __forceinline__ void wait_count(const uint32_t* c, uint32_t n) {
  int spin = 0;
  while ((ld_acquire(c) & 0xffff) < n) { __nanosleep(32); spin_guard(spin); }
}

__device__ __forceinline__ uint8_t* pool_at(uint32_t off) {
  return reinterpret_cast<uint8_t*>((reinterpret_cast<uintptr_t>(g_pool) + 8191) & ~(uintptr_t)8191) + off; }
struct Weights { const uint8_t* w[4]; };
__device__ __forceinline__ void prefetch_weights(const Weights& p, int i) {
  if (blockIdx.x < 128) asm volatile("cp.async.bulk.prefetch.L2.global [%0], 61440;" :: "l"(p.w[i] + (size_t)blockIdx.x * 61440) : "memory");
}
__global__ void __launch_bounds__(256) first_kernel(const __nv_bfloat16* __restrict__ xin, const uint4* __restrict__ wb, const __grid_constant__ Weights wa) {
  __shared__ __align__(16) float scratch[256];
  __shared__ uint32_t lat[4];
  const int warp = threadIdx.x >> 5, lane = threadIdx.x & 31, cta = blockIdx.x;
  TRACE(0);
  pdl_launch();
  if (warp < 4 && (warp < 2 || cta < NSLOT)) {
    uint32_t* q = reinterpret_cast<uint32_t*>(pool_at((warp < 2 ? NSLOT : cta) * 8192 + (warp & 1) * 4096)) + (warp < 2 ? (cta & 127) * 8 : 0);
    if (lane < 8) stg_strong32(q + lane, 0u);
    uint32_t best = ~0u;
    if (lane == 0)
      for (int r = 0; r < 4; r++) {
        uint32_t t0, t1, v;
        asm volatile("mov.u32 %0, %%clock;" : "=r"(t0) :: "memory");
        asm volatile("atom.relaxed.gpu.global.exch.b32 %0, [%1], 0;" : "=r"(v) : "l"(q) : "memory");
        asm volatile("{.reg .u32 t; add.u32 t, %1, 1; mov.u32 %0, %%clock; sub.u32 %0, %0, %1;}" : "=r"(t1) : "r"(__shfl_sync(1u, v, 0)) : "memory");
        best = min(best, t1 - t0);
      }
    if (lane == 0) lat[warp] = best;
  }
  __syncthreads();
  ABT(2, 0);
  if (threadIdx.x == 0) {
    const int part = lat[0] < lat[1] ? 0 : 1;
    uint32_t smid; asm("mov.u32 %0, %%smid;" : "=r"(smid));
    g_smpart[smid & 255] = part;
    g_smclk[smid & 255] = clk32() - gtime() * 2;
    g_smuse[smid & 255] = 0;
    if (cta < NSLOT) g_orient[cta] = lat[2] < lat[3] ? part : 1 - part;
  }
  if (cta < 128) {
    float4 v[2][5];
#pragma unroll
    for (int r = 0; r < 2; r++)
#pragma unroll
      for (int i = 0; i < 5; i++) {
        const uint32_t* src = reinterpret_cast<const uint32_t*>(xin) + (cta * 16 + r * 8 + (lane >> 2)) * (DM / 2) + warp * 40 + i * 8 + (lane & 3);
        const uint32_t a = src[0], b = src[4];
        v[r][i] = make_float4(bf_lo(a), bf_hi(a), bf_lo(b), bf_hi(b));
      }
    uint4 w8[2];
#pragma unroll
    for (int i = 0; i < 2; i++) w8[i] = wb[cta * 400 + min(i * 256 + threadIdx.x, 399)];
    if (threadIdx.x < 128) g_stat[cta * 128 + threadIdx.x] = make_float2(0.f, 0.f);
#pragma unroll
    for (int i = 0; i < 10; i++) g_x[((cta * 2 + i / 5) * 40 + warp * 5 + i % 5) * 32 + lane] = v[i / 5][i % 5];
    ABT(2, 1);
    if (threadIdx.x == 32) for (int i = 0; i < FK_PF; i++) prefetch_weights(wa, i);
    float mean[2], rs[2];
    ln_stats<2>(v, s2u(scratch), mean, rs);
    ABT(2, 2);
    uint32_t w[2][5][2];
#pragma unroll
    for (int i = 0; i < 10; i++) {
      const float4 t = v[i / 5][i % 5];
      const float m = mean[i / 5], q = rs[i / 5];
      w[i / 5][i % 5][0] = pack2((t.x - m) * q, (t.y - m) * q); w[i / 5][i % 5][1] = pack2((t.z - m) * q, (t.w - m) * q);
    }
    ln_store(w, cta, warp * 5);
    ABT(2, 3);
#pragma unroll
    for (int i = 0; i < 2; i++) {
      const int e = cta * 400 + min(i * 256 + threadIdx.x, 399), k = e / 80, n = e - k * 80, cg = n / 10;
      g_wb[((cg * 80 + (k >> 3)) * 10 + n - cg * 10) * 8 + (k & 7)] = w8[i];
    }
  } else if (cta == 128) {
    g_bo[threadIdx.x] = 0;
  }
  TRACE(2);
}

struct ChainParams {
  CUtensorMap wq, wk, wv, wo;
  const __nv_bfloat16* mem0;
  uint8_t *pool, *kv;
  const uint32_t* xc;
  uint32_t* sync;
  int layer;
  int d0, d3, d1, d1b, d2, d2b, mode;
};
constexpr int CH_WQ = 0, CH_WO = 81920, CH_X = CH_WO + 86016, CH_M = CH_X + 20480, CH_KT = CH_X + 40960, CH_VT = CH_KT + 4096,
              CH_PS = CH_VT + 4096, CH_QK = CH_PS + 4096, CH_VP = CH_QK + 4096, CH_SX = CH_VP + 1024, CH_O = CH_SX + 2304, CH_ID = CH_O + 3072,
              CH_BAR = CH_ID + 512;
constexpr int CH_SMEM = CH_BAR + 256;
constexpr int CH_BASE = 1024;
#define CH_VK0 8
#define CH_VK1 20
#define CH_L0 4
#define CH_LR 4
#define NOX 0
#define CH_XA 1
#define CH_XB 4
#define CH_W1 3
#define CH_W2 17
#define CH_W3 26
#define CH_R2 8
#define CH_VA 16
#define CH_EX 1
#define CH_KD 0
#define CH_RP 1
#define CH_KF 10
#define CH_LO 0
#define CH_LR1 4
#define CH_KP 0
#define CH_KM 0
#define CH_WE 0
#define CH_KW 3
#define CH_RB 0
#define CH_RC 8
#define CH_D0 200
#define CH_D1 450
#define CH_D2 350
#define CH_R1 4
#define CH_TW 12
__device__ __forceinline__ uint32_t opaque(uint32_t x) { return __shfl_sync(~0u, x, threadIdx.x & 31); }
__device__ __forceinline__ uint32_t nz(uint32_t x) { uint32_t r; asm("max.u32 %0, %1, 1;" : "=r"(r) : "r"(x)); return r; }
__device__ __forceinline__ uint32_t pack_tag(float lo, float hi, uint32_t tag, uint32_t mask) {
  uint32_t r;
  asm("lop3.b32 %0, %1, %2, %3, 0xD8;" : "=r"(r) : "r"(pack2(lo, hi)), "r"(tag), "r"(mask));
  return r;
}
__device__ __forceinline__ uint32_t differ(uint32_t a, uint32_t b, uint32_t t) { uint32_t r; asm("lop3.b32 %0, %1, %2, %3, 0x7E;" : "=r"(r) : "r"(a), "r"(b), "r"(t)); return r; }
__device__ __forceinline__ void mbar_wait_hot(uint32_t bar, uint32_t ph) {
  uint32_t ok;
  asm volatile("{.reg .pred p; mbarrier.try_wait.parity.shared::cta.b64 p, [%1], %2; selp.u32 %0, 1, 0, p;}" : "=r"(ok) : "r"(bar), "r"(ph) : "memory");
  if (__builtin_expect(!ok, 0)) mbar_wait(bar, ph);
}
__device__ __forceinline__ bool elect() {
  uint32_t r; asm volatile("{.reg .pred p; elect.sync _|p, 0xffffffff; selp.u32 %0, 1, 0, p;}" : "=r"(r)); return r; }
__device__ __forceinline__ uint32_t or3(uint32_t a, uint32_t b, uint32_t c) { uint32_t r; asm("lop3.b32 %0, %1, %2, %3, 0xFE;" : "=r"(r) : "r"(a), "r"(b), "r"(c)); return r; }
__device__ __forceinline__ void pin() { pdl_launch(); }
__device__ __forceinline__ void mma16h(float* d, uint32_t a0, uint32_t a2, uint32_t b0, uint32_t b1) {
  asm volatile("{.reg .b32 u, v; mma.sync.aligned.m16n8k16.row.col.f32.bf16.bf16.f32 {%0,%1,%2,%3},{%4,u,%5,v},{%6,%7},{%0,%1,%2,%3};}"
               : "+f"(d[0]), "+f"(d[1]), "+f"(d[2]), "+f"(d[3]) : "r"(a0), "r"(a2), "r"(b0), "r"(b1)); }
__device__ __forceinline__ void mma8h(float* d, uint32_t a0, uint32_t b0) {
  asm volatile("{.reg .b32 u; mma.sync.aligned.m16n8k8.row.col.f32.bf16.bf16.f32 {%0,%1,%2,%3},{%4,u},{%5},{%0,%1,%2,%3};}"
               : "+f"(d[0]), "+f"(d[1]), "+f"(d[2]), "+f"(d[3]) : "r"(a0), "r"(b0)); }
__device__ __forceinline__ uint32_t absmax2(uint32_t a, uint32_t b) { uint32_t r; asm("max.xorsign.abs.bf16x2 %0, %1, %2;" : "=r"(r) : "r"(a), "r"(b)); return r; }
__device__ __forceinline__ void until(uint32_t t) { while ((int)(clk32() - t) < 0) {} }
__device__ __forceinline__ uint4 pack8(const float* d) { return make_uint4(pack2(d[0], d[1]), pack2(d[2], d[3]), pack2(d[4], d[5]), pack2(d[6], d[7])); }
__device__ __forceinline__ void add8(float* d, uint4 v) {
  d[0] += bf_lo(v.x); d[1] += bf_hi(v.x); d[2] += bf_lo(v.y); d[3] += bf_hi(v.y);
  d[4] += bf_lo(v.z); d[5] += bf_hi(v.z); d[6] += bf_lo(v.w); d[7] += bf_hi(v.w);
}

template <int WG>
__device__ __forceinline__ void chain_body(const ChainParams& p, const uint32_t wq, const uint32_t (&ak)[80], const uint32_t (&av)[80]) {
  const int tid = threadIdx.x & 127, t4 = __shfl_sync(~0u, tid >> 5, 0), lane = tid & 31;
  const int cta = blockIdx.x, h = cta / 3, j = cta - 3 * h;
  const uint32_t sb = mapa(CH_BASE, j);
  const uint32_t bWo = sb + CH_BAR, bWq = bWo + 8, bX = bWo + 16, bXA = bWo + 24, bXB = bWo + 32, bO = bWo + 40, bG = bWo + 48, bH = bWo + 96;
  uint32_t tw[4 * CH_TW];
  auto refill = [&]() {
#pragma unroll
    for (int k = 0; k < CH_TW; k++) ldsm4t(&tw[4 * k], wq + k * 2048);
  };
  const uint32_t wo = opaque((sb + CH_WO + (WG == 0 ? (t4 + (j == 2)) * 4096 : (j == 2 ? 0 : 24576) + t4 * 1024) + ((lane & 7) + (lane >> 4) * 8) * 64 +
                              ((((lane >> 3) & 1) ^ ((lane >> 1) & 3)) << 4)) ^ (WG == 1 && j == 2 ? 32 : 0));
  const uint32_t wo2 = opaque((wo ^ ((t4 & 1) * 32)) + (4 + (t4 >> 1) - t4) * 4096);
  const uint32_t l16 = opaque(sb + lane * 16);
  const uint32_t l8 = opaque(sb + t4 * 256 + lane * 8);
  const uint32_t lw = opaque(sb + t4 * 1024 + lane * 16);
  const uint32_t qs = opaque(sb + CH_QK + WG * 2048 + t4 * 512 + lane * 16);
  const uint32_t qa = opaque(sb + CH_QK + (lane >> 4) * 2048 + (lane & 15) * 16 + (WG == 0 ? t4 * 512 + 256 : t4 == 3 ? 1024 : 0));
  const uint32_t ka = opaque(t4 < 2 ? sb + CH_KT + t4 * 512 + lane * 16
                                    : sb + CH_QK + 256 + (t4 - 2) * 1024 + ((lane >> 3) & 1) * 2048 + (lane >> 4) * 128 + (lane & 7) * 16);
  const uint32_t l4 = opaque(sb + t4 * 256 + lane * 4);
  uint32_t pdst[1], pages = 0;
  auto line0 = [&](int i) { return 28 * j + (i < 4 ? 4 * t4 + i : 12 + 2 * t4 + i); };
  const uint32_t plane = opaque((lane >> 4) * 2048 + h * 64 + (lane & 15) * 4);
  if (WG == 0) {
    pages = __ballot_sync(~0u, lds32(sb + CH_O + line0(min(lane, 5)) * 4) & 4096);
  } else {
    pages = __ballot_sync(~0u, lds32(sb + CH_O + (80 + min(lane, 11)) * 4) & 4096);
    pdst[0] = opaque(lds32(sb + CH_O + (j == 0 ? 24 + t4 : 50 + 2 * j + (t4 & 1)) * 4) + plane);
  }
  const uint32_t role = lds32(sb + CH_O + NSLOT * 4), rsrc = lds32(sb + CH_O + role * 4), rdst = (80 + role / 20) * 8192 + role % 20 * 128;
  const uint32_t r1 = mapa(CH_BASE, j == 2 ? 0 : j + 1) - sb, r2 = mapa(CH_BASE, j == 0 ? 2 : j - 1) - sb;
  uint32_t tag = opaque(1);
  auto pool = [&](uint32_t off) { return p.pool + ((tag & 0xfffe) + off); };
  auto after = [&](uint32_t x) { return x & tag & 0xfffe; };
  auto kv = [&](int s, uint32_t a) { return p.kv + (a + ((cta * 2 * NSEG + s) * KV_BYTES - sb)); };
  auto pass = [&](float (&d)[16], const uint32_t (&a)[80], auto k0, auto k1) {
    const uint64_t db = mkdesc(CH_BASE + CH_X + WG * 20480, 512, 128, 0);
#pragma unroll
    for (int k = k0.value; k < k1.value; k++) wg_rs32_00(d, a[4 * k], a[4 * k + 1], a[4 * k + 2], a[4 * k + 3], db + k * 64, k);
    wg_commit();
  };
  auto dump = [&](float (&d)[16], uint32_t a) {
    reg_fence<16>(d);
    sts128(a, pack8(d)); sts128(a + 512, pack8(d + 8));
  };
  uint32_t pph = 0;
  auto tokens0 = [&](int s, auto k0) {
    float dk[16], dv[16];
    bar_sync(9, 256);
    wg_fence();
    pass(dk, ak, Int<0>(), Int<4>());
    const uint4 a0 = lds128(lw + CH_KT), a1 = lds128(lw + CH_KT + 512);
    pin();
    pass(dk, ak, Int<4>(), Int<20>());
    pass(dv, av, Int<0>(), Int<CH_VA>());
    pin();
    wg_wait<1>();
    reg_fence<16>(dk);
    add8(dk, a0); add8(dk + 8, a1);
    const uint4 w0 = pack8(dk), w1 = pack8(dk + 8);
    const uint4 b0 = lds128(lw + CH_VT), b1 = lds128(lw + CH_VT + 512);
    stsm4t(lw + CH_KT, w0.x, w0.z, w0.y, w0.w); stsm4t(lw + CH_KT + 512, w1.x, w1.z, w1.y, w1.w);
    if (CH_KP == 2) bar_arrive(7, 160);
    TM1(6);
    pin();
    if (CH_VA < 20) pass(dv, av, Int<CH_VA>(), Int<20>());
    pin();
#pragma unroll
    for (int k = k0.value; k < CH_TW; k++) ldsm4t(&tw[4 * k], wq + k * 2048);
    TM1(9);
    if (k0.value < CH_TW && t4 >= 2) { mbar_wait_hot(bH + t4 * 16 - 24 + (pph & 1) * 8, pph >> 1 & 1); pph++; }
    __syncwarp();
    wg_wait<0>();
    reg_fence<16>(dv);
    add8(dv, b0); add8(dv + 8, b1);
#pragma unroll
    for (int e = 0; e < 2; e++) { const uint4 v = pack8(dv + 8 * e); sts128(lw + CH_VT + e * 512, make_uint4(v.x, v.z, v.y, v.w)); }
  };
  auto publish_k = [&](int s) {
    if (t4 == CH_KW && elect()) { fence_async(); bulk_store(p.kv + (size_t)(cta * 2 * NSEG + s) * KV_BYTES, sb + CH_KT, 4096); bulk_commit(); }
    __syncwarp();
  };
  if (WG == 0) {
    mbar_wait(bXB, 0);
    tokens0(0, Int<CH_TW>());
  } else {
    const uint32_t* m0 = reinterpret_cast<const uint32_t*>(p.mem0) + (lane >> 2) * 320 + t4 * 80 + (lane & 3);
    uint32_t a[20];
#pragma unroll
    for (int i = 0; i < 20; i++) a[i] = m0[4 * i];
    pin();
    float dk[16], dv[16];
    mbar_wait(bXA, 0);
    wg_fence();
    pass(dk, ak, Int<0>(), Int<20>());
    pass(dv, av, Int<0>(), Int<20>());
    wg_wait<0>();
    dump(dk, lw + CH_KT);
    dump(dv, lw + CH_VT);
    bar_sync(9, 256);
    if (CH_KP == 2 && t4 == CH_KW) { bar_sync(7, 160); publish_k(0); }
#pragma unroll
    for (int i = 0; i < 20; i++) sts32(sb + CH_M + (t4 * 20 + i) * 128 + lane * 4, nz(transpose8(a[i])));
    __syncwarp();
    if (elect()) mbar_arrive(bG + t4 * 8);
  }
  PRO(8);
  mbar_wait(bWq, 0);
  refill();
  PRO(9);
  mbar_wait(bWo, 0);
  asm volatile("barrier.cluster.wait.aligned;" ::: "memory");
  PRO(10);
  auto load_x = [&](int s, int k0, int n, uint32_t bar) {
    if (!NOX && elect()) { mbar_expect(bar, n * 1024); bulk_load(sb + CH_X + k0 * 1024, p.xc + (s + 1) * 10240 + k0 * 256, n * 1024, bar); }
  };
  constexpr int VK = WG == 0 ? CH_VK0 : CH_VK1;
  uint32_t gph = 0;
  int st = 0;
  const uint32_t ca = opaque(sb + CH_M + t4 * 2560 + lane * 32 + (lane >> 2) * 4);
  auto project = [&](int s, uint32_t (&b)[40], float (&dv)[16], uint32_t (&kf)[16]) {
    float dq[4] = {}, dk[4] = {};
    uint32_t w[80];
#pragma unroll
    for (int i = 0; i < 4 * CH_TW; i++) w[i] = tw[i];
    constexpr int LR = WG == 1 ? CH_LR1 : CH_LR;
    auto load = [&](int n) {
      int c = 0;
#pragma unroll
      for (int i = 0; i < 10; i++) {
        if (i == CH_KF) {
#pragma unroll
          for (int q = 0; q < 4; q++)
            if (WG == 1 && c++ == n) ldsm4(&kf[4 * q], ka + q * 1024);
        }
        if (c++ == n) ldsm4t(&b[4 * i], l16 + CH_M + WG * 5120 + i * 512);
#pragma unroll
        for (int k = 2 * i; k < 2 * i + 2; k++)
          if (k >= CH_TW && c++ == n) ldsm4t(&w[4 * k], wq + k * 2048);
      }
#pragma unroll
      for (int i = 0; i < 4; i++)
        if (WG == 1 && CH_KF >= 10 && c++ == n) ldsm4(&kf[4 * i], ka + i * 1024);
    };
    if (WG == 1) {
      for (int n = 0;;) {
        mbar_wait(bG + t4 * 8, gph);
        TR(5, (clk32() & ~3u) | min(n, 3));
        gph ^= 1;
        if (__builtin_expect(!__any_sync(~0u, __vimin3_u32(lds32(ca), lds32(ca + 1024), lds32(ca + 1536)) == 0), 1)) break;
        if (elect()) {
          const int q = (st == 0 ? 8 : st * 4 - 4) + t4;
          mbar_expect(bG + t4 * 8, 2560);
          bulk_load(sb + CH_M + t4 * 2560, p.pool + ((80 + q) * 8192 + (pages >> q & 1) * 4096), 2560, bG + t4 * 8);
        }
        spin_guard(n);
      }
    }
    bar_sync(6, 256);
#pragma unroll
    for (int i = 0; i < CH_L0; i++) load(i);
    if (WG == 0 && CH_XB == 4 && s + 1 < NSEG) load_x(s, 5 * t4, 5, bXB);
    TM(0);
    TM1(11);
    if (WG == 1) TR(6, clk32());
#pragma unroll
    for (int k = 0; k < 20; k += 2) {
      if (k > 0) {
#pragma unroll
        for (int n = (k == 18 ? 40 : CH_L0 + k * LR / 4) - 1; n >= CH_L0 + (k - 2) * LR / 4; n--) { load(n); if (CH_LO) __syncwarp(); }
      }
      pin();
#pragma unroll
      for (int kk = k; kk < k + 2; kk++) {
        mma16(dk, ak[4 * kk], ak[4 * kk + 1], ak[4 * kk + 2], ak[4 * kk + 3], b[2 * kk], b[2 * kk + 1]);
        mma16(dq, w[4 * kk], w[4 * kk + 1], w[4 * kk + 2], w[4 * kk + 3], b[2 * kk], b[2 * kk + 1]);
        if (kk < VK) mma16(dv, av[4 * kk], av[4 * kk + 1], av[4 * kk + 2], av[4 * kk + 3], b[2 * kk], b[2 * kk + 1]);
      }
    }
    const float k2 = 0.07216878364870322f * 1.44269504089f;
    stsm4t(qs, pack2(dq[0] * k2, dq[1] * k2), pack2(dq[2] * k2, dq[3] * k2), pack2(dk[0], dk[1]), pack2(dk[2], dk[3]));
    TM(1);
  };
  constexpr int VC = VK == 20 ? 1 : WG == 0 ? 2 : 3;
  auto finish_v = [&](const uint32_t (&b)[40], float (&dv)[16]) {
#pragma unroll
    for (int kk = VK; kk < 20; kk++) mma16(dv + 4 * ((kk - VK) % VC), av[4 * kk], av[4 * kk + 1], av[4 * kk + 2], av[4 * kk + 3], b[2 * kk], b[2 * kk + 1]);
  };
  auto sum_v = [&](float (&dv)[16]) {
#pragma unroll
    for (int i = 4; i < 4 * VC; i++) dv[i & 3] += dv[i];
  };
  auto publish_km = [&](int s) {
    uint32_t a[4];
    ldsm4(a, qa);
    *reinterpret_cast<uint2*>(kv(s, l8) + KV_M) = make_uint2(hadd2(a[0], a[2]), hadd2(a[1], a[3]));
  };
  auto memory_v = [&](uint2 x, const float (&dv)[16]) {
    return make_uint2(pack2(dv[0] + bf_lo(x.x), dv[1] + bf_hi(x.x)), pack2(dv[2] + bf_lo(x.y), dv[3] + bf_hi(x.y)));
  };
  auto publish_v = [&](int s, const uint4 (&v)[2], uint2 vm) {
#pragma unroll
    for (int e = 0; e < 2; e++) reinterpret_cast<uint4*>(kv(s, lw) + KV_V)[e * 32] = v[e];
    *reinterpret_cast<uint2*>(kv(s, l8) + KV_V + KV_M) = vm;
  };
#pragma unroll 1
  for (int s = 0; s < NSEG - 1; s++) {
    float dv[16] = {};
    uint32_t b[40], kf[16];
    project(s, b, dv, kf);
    if (WG == 0) {
      bar_sync(1, 256);
      if (CH_XA == 0) load_x(s, 20 + 5 * t4, 5, bXA);
      if (CH_XB == 0) load_x(s, 5 * t4, 5, bXB);
      pin();
      finish_v(b, dv);
      sum_v(dv);
      sts64(l8 + CH_VP, pack2(dv[0], dv[1]), pack2(dv[2], dv[3]));
      __syncwarp();
      if (elect()) mbar_arrive(bX);
      if (CH_XA == 1) load_x(s, 20 + 5 * t4, 5, bXA);
      if (CH_XB == 1) load_x(s, 5 * t4, 5, bXB);
      uint32_t w[144];
      auto wload = [&](int i) { ldsm4t(&w[4 * i], (i % 3 == 0 ? wo : i % 3 == 1 ? wo ^ 32 : wo2) + i / 12 * 28672 + i / 3 % 4 * 1024); };
      TM(3);
      if (CH_KP == 0) publish_k(s);
#pragma unroll
      for (int i = 0; i < CH_W1; i++) wload(i);
      bar_sync(10, 256);
      uint32_t km[4];
      ldsm4(km, qa);
      pin();
#pragma unroll
      for (int i = CH_W1; i < CH_W2; i++) wload(i);
      pin();
      const uint2 kms = make_uint2(hadd2(km[0], km[2]), hadd2(km[1], km[3]));
      if (CH_KM == 0) *reinterpret_cast<uint2*>(kv(s, l8) + KV_M) = kms;
      if (CH_KP == 0) bulk_wait_read<0>();
      if (CH_XA == 2) load_x(s, 20 + 5 * t4, 5, bXA);
      if (CH_XB == 2) load_x(s, 5 * t4, 5, bXB);
      bar_sync(2, 256);
      {
        float y[3][4] = {};
        uint32_t ob[24];
        ldsm4(&ob[0], l16 + CH_O + 1024); ldsm4(&ob[4], l16 + CH_O + 1536);
        TM(7);
        auto step = [&](int i) {
          const int k = i / 3;
          mma16(y[i % 3], w[4 * i], w[4 * i + 1], w[4 * i + 2], w[4 * i + 3], ob[2 * k], ob[2 * k + 1]);
        };
#pragma unroll
        for (int i = 0; i < 12; i++) {
          step(i);
          if (i >= 12 - (CH_W3 - CH_W2)) wload(CH_W3 - 12 + i);
          if (i % 3 == 2) pin();
        }
        if (CH_XB == 3) load_x(s, 5 * t4, 5, bXB);
        if (CH_KM == 1) *reinterpret_cast<uint2*>(kv(s, l8) + KV_M) = kms;
        pin();
        mbar_wait(bO, s & 1);
        TM(4);
        ldsm4(&ob[8], l16 + CH_O); ldsm4(&ob[12], l16 + CH_O + 512);
        pin();
        float2 inv;
        uint8_t* dst[6];
        uint32_t mask;
#pragma unroll
        for (int i = 12; i < 36; i++) {
          step(i);
          const int n = CH_W3 + i - 13, m = n - (n > 30);
          if (i == 12) ldsm4(&ob[16], l16 + after(w[4 * CH_W3 - 1] | w[4 * CH_W3 - 5] | w[4 * CH_W3 - 9] | ob[8]) + CH_O + 2048);
          else if (n == 30) ldsm4(&ob[20], l16 + CH_O + 2560);
          else if (m < 36) wload(m);
          else if (m == 36) inv = lds64f((l8 & ~0xe0u) + CH_VP);
          if (i == 26) mask = ((l16 ^ tag) & 48) == 0;
          if (i >= 27 && i < 33) dst[i - 27] = pool(line0(i - 27) * 8192 + (pages >> (i - 27) & 1) * 4096) + plane;
          if (i % 3 == 2) pin();
        }
#pragma unroll
        for (int k = 0; k < CH_R1; k++) ldsm4t(&tw[4 * k], wq + k * 2048);
        pin();
#pragma unroll
        for (int i = 0; i < 6; i++) stg_strong32(dst[i], pack_tag(y[i >> 1][2 * (i & 1)] * inv.x, y[i >> 1][2 * (i & 1) + 1] * inv.y, tag, mask));
        TM(8);
        TR(0, clk32());
        bar_arrive(5, 256);
        pin();
      }
      const uint32_t t0 = clk32();
      auto refill2 = [&]() {
#pragma unroll
        for (int k = CH_R1; k < CH_R2; k++) ldsm4t(&tw[4 * k], wq + k * 2048);
      };
      if (CH_RP == 0) refill2();
      const uint32_t ln = (l16 ^ tag) >> 4 & 31;
      if (t4 >= 2) {
        const uint32_t bP = bH + t4 * 16 - 24, ps = CH_PS + (t4 & 1) * 4096;
        auto fetch = [&](uint32_t k) {
          if (elect()) { mbar_expect(bP + (k & 1) * 8, 2048); bulk_load(sb + ps + (k & 1) * 2048, p.pool + (rsrc + (t4 & 1) * 2048), 2048, bP + (k & 1) * 8); }
        };
        until(t0 + CH_D0);
        fetch(pph);
        if (CH_RP == 2) refill2();
        if (!NOX) mbar_wait_hot(bXB, (s + 1) & 1);
        const uint32_t want = (tag & 1) * 0x10001, chk = opaque(ln < 4 ? 0x10001 : 0);
        uint4 sel;
        sel.x = opaque((ln >> 3) != (ln & 1) ? 0 : ln & 4 ? 0x3f800000u : 0x00003f80u);
        sel.z = opaque(sel.x); sel.y = opaque(ln); sel.w = opaque(ln + 1);
        uint8_t* mdst = p.pool + opaque(st * 32768 + rdst + (t4 & 1) * 64 + ln * 4);
        until(t0 + CH_D1);
        fetch(pph + 1);
        TM(5);
        if (CH_RP == 1) refill2();
        int n = 0;
        uint32_t u[16];
        for (;;) {
          mbar_wait(bP + (pph & 1) * 8, pph >> 1 & 1);
          TM(14);
          TR(2, clk32());
#pragma unroll
          for (int i = 0; i < 4; i++) ldsm4t(&u[4 * i], l16 + (ps + (pph & 1) * 2048) + i * 512);
          pph++;
          uint32_t bad = 0;
#pragma unroll
          for (int i = 0; i < 4; i++) bad = or3(bad, differ(u[4 * i], u[4 * i + 1], want), differ(u[4 * i + 2], u[4 * i + 3], want));
          if (!__any_sync(~0u, bad & chk)) break;
          fetch(pph + 1);
          spin_guard(n);
        }
        float y[4][4] = {};
#pragma unroll
        for (int i = 0; i < 8; i++) mma16(y[i & 3], sel.x, sel.y, sel.z, sel.w, u[2 * i], u[2 * i + 1]);
        TR(1, t0 + (n ? CH_D1 : CH_D0));
        TM(15);
        const uint32_t w = nz(pack2((y[0][0] + y[1][0]) + (y[2][0] + y[3][0]), (y[0][1] + y[1][1]) + (y[2][1] + y[3][1])));
        if (ln < 16) { stg_strong32(mdst, w); stg_strong32(mdst + 4096, w); }
        TMV(12, 32, n);
        TR(3, (clk32() & ~3u) | min(n, 3));
      } else {
        if (CH_RP) refill2();
        if (!NOX) mbar_wait_hot(bXB, (s + 1) & 1);
        stg_strong32(p.pool + ((st == 2 ? 0 : st + 1) * 32768 + rdst + t4 * 4096) + ln * 4, 0u);
        if (t4 == 0 && cta < 40 && s + 4 < NSEG && elect())
          asm volatile("cp.async.bulk.prefetch.L2.global [%0], 1024;" :: "l"(p.xc + (s + 4) * 10240 + cta * 256) : "memory");
        if (t4 == 1 && (s & 3) == 0 && s > 0 && elect()) red_relaxed(p.sync + 2 * s - 4, 1);
        if (t4 == 1 && s == NSEG - 3 && cta == 95 && elect()) red_relaxed(p.sync + 2 * s + 2, 0x10000);
      }
      TM(10);
      bar_arrive(8, 256);
      tokens0(s + 1, Int<CH_R2>());
      TM(2);
      TR(7, clk32());
    } else {
      const uint32_t xo = l4 + (CH_SX - (t4 == 3 ? 128 : 0)), x1 = xo + (r1 + 768 + min(t4, 2) * 256), x2 = xo + (r2 + 1024 + min(t4, 2) * 256);
      if (t4 < 2) {
        float ds[4][4] = {};
        uint32_t q[16];
        asm volatile("bar.sync 1, 256;" ::: "memory");
#pragma unroll
        for (int k = 0; k < 4; k++) ldsm4(&q[4 * k], qa + k * 512);
        pin();
        if (VK < 20) { finish_v(b, dv); pin(); }
#pragma unroll
        for (int k = 0; k < 4; k++) {
          mma16(ds[k & 1], kf[4 * k], kf[4 * k + 1], kf[4 * k + 2], kf[4 * k + 3], q[4 * k], q[4 * k + 1]);
          mma16(ds[2 + (k & 1)], kf[4 * k], kf[4 * k + 1], kf[4 * k + 2], kf[4 * k + 3], q[4 * k + 2], q[4 * k + 3]);
        }
        float t[4];
#pragma unroll
        for (int i = 0; i < 4; i++) t[i] = (ds[0][i] + ds[2][i]) + (ds[1][i] + ds[3][i]);
        const uint32_t w0 = pack2(t[0], t[1]), w1 = pack2(t[2], t[3]);
        st_async32(x1, w0, bX + r1); st_async32(x2, w0, bX + r2);
        st_async32(x1 + 128, w1, bX + r1); st_async32(x2 + 128, w1, bX + r2);
        sts32(xo, w0); sts32(xo + 128, w1);
      } else {
        float ds[4][4] = {};
        uint32_t q0[4], q1[4], a0[4], a1[4];
        asm volatile("bar.sync 1, 256; " ::: "memory");
        ldsm4(a0, ka); ldsm4(q0, qa); ldsm4(a1, ka + 512); ldsm4(q1, qa + 512);
        pin();
        if (VK < 20) { finish_v(b, dv); pin(); }
        mma16(ds[0], a0[0], a0[1], a0[2], a0[3], q0[0], q0[1]);
        mma16(ds[1], a0[0], a0[1], a0[2], a0[3], q0[2], q0[3]);
        mma16(ds[2], a1[0], a1[1], a1[2], a1[3], q1[0], q1[1]);
        mma16(ds[3], a1[0], a1[1], a1[2], a1[3], q1[2], q1[3]);
        float t[2];
#pragma unroll
        for (int i = 0; i < 2; i++)
          t[i] = ((ds[0][i] + ds[0][i + 2]) + (ds[1][i] + ds[1][i + 2])) + ((ds[2][i] + ds[2][i + 2]) + (ds[3][i] + ds[3][i + 2]));
        const uint32_t w0 = pack2(t[0], t[1]);
        st_async32(x1, w0, bX + r1);
        st_async32(x2, w0, bX + r2);
        sts32(xo, w0);
      }
      TM(3);
      const uint4 id = lds128(l16 + CH_ID);
      float sc[3][4] = {};
      uint4 v[2];
      sum_v(dv);
      bar_sync(3, 128);
      uint32_t r[12], wd[12], we[12] = {};
      ldsm4(&r[0], l16 + CH_SX); ldsm2(&r[4], l16 + CH_SX + 512);
      pin();
      v[0] = lds128(lw + CH_VT); v[1] = lds128(lw + CH_VT + 512);
#pragma unroll
      for (int u = 0; u < 3; u++) ldsm4t(&wd[4 * u], wo + u * 28672);
      if (CH_WE && j == 0) {
#pragma unroll
        for (int u = 0; u < 3; u++) ldsm4t(&we[4 * u], (wo ^ 32) + u * 28672);
      }
      pin();
#pragma unroll
      for (int q = 0; q < 3; q++) mma16(sc[q], id.x, id.y, id.z, id.w, r[2 * q], r[2 * q + 1]);
      uint32_t big = absmax2(absmax2(absmax2(r[0], r[1]), absmax2(r[2], r[3])), absmax2(r[4], r[5]));
      const uint32_t oa1 = l4 + (r1 + CH_O), oa2 = l4 + (r2 + CH_O + 2048), ones = 0x3f803f80u;
      mbar_wait_hot(bX, s & 1);
      TM(4);
      ldsm4(&r[0], l16 + CH_SX + 768); ldsm4(&r[8], l16 + CH_SX + 1792); ldsm4(&r[4], l16 + CH_SX + 1280);
      const uint2 vp = lds64(l8 + CH_VP);
      bar_arrive(10, 256);
      pin();
      {
        float sd[3][4] = {};
#pragma unroll
        for (int i = 0; i < 3; i++) {
          const int q = i == 0 ? 0 : 3 - i;
          mma16(sc[q], id.x, id.y, id.z, id.w, r[4 * q], r[4 * q + 1]);
          mma16(sd[q], id.x, id.y, id.z, id.w, r[4 * q + 2], r[4 * q + 3]);
          big = absmax2(big, absmax2(absmax2(r[4 * q], r[4 * q + 1]), absmax2(r[4 * q + 2], r[4 * q + 3])));
        }
#pragma unroll
        for (int i = 0; i < 12; i++) sc[i >> 2][i & 3] += sd[i >> 2][i & 3];
      }
      const bool redo = __any_sync(~0u, (absmax2(big, big << 16) & 0x7fff0000u) >= 0x41800000u);
      const uint2 vm = memory_v(vp, dv);
      sc[2][0] += sc[2][2]; sc[2][1] += sc[2][3];
      float l[4], o[2][4];
      uint32_t p3, p4;
      auto attend = [&]() {
#pragma unroll
        for (int i = 0; i < 4; i++) l[i] = o[0][i] = o[1][i] = 0.f;
        const uint32_t p1 = pack2(ex2(sc[0][0]), ex2(sc[0][1])), p2 = pack2(ex2(sc[0][2]), ex2(sc[0][3]));
        mma16h(o[0], p1, p2, v[0].x, v[0].y);
        mma16h(o[1], p1, p2, v[0].z, v[0].w);
        mma16h(l, p1, p2, ones, ones);
        const uint32_t p0 = pack2(ex2(sc[2][0]), ex2(sc[2][1]));
        mma8h(o[0], p0, vm.x);
        mma8h(o[1], p0, vm.y);
        mma8h(l, p0, ones);
        p3 = pack2(ex2(sc[1][0]), ex2(sc[1][1])); p4 = pack2(ex2(sc[1][2]), ex2(sc[1][3]));
        mma16h(o[0], p3, p4, v[1].x, v[1].y);
        mma16h(o[1], p3, p4, v[1].z, v[1].w);
      };
      attend();
      if (__builtin_expect(redo, 0)) {
        float mx = fmaxf(sc[2][0], sc[2][1]);
#pragma unroll
        for (int i = 0; i < 4; i++) mx = fmaxf(mx, fmaxf(sc[0][i], sc[1][i]));
        mx = fmaxf(mx, __shfl_xor_sync(~0u, mx, 1));
        mx = fmaxf(mx, __shfl_xor_sync(~0u, mx, 2));
#pragma unroll
        for (int i = 0; i < 4; i++) { sc[0][i] -= mx; sc[1][i] -= mx; }
        sc[2][0] -= mx; sc[2][1] -= mx;
        attend();
      }
      const uint32_t o0 = pack2(o[0][0], o[0][1]), o1 = pack2(o[1][0], o[1][1]);
      st_async32(oa1, o0, bO + r1); st_async32(oa2, o0, bO + r2);
      st_async32(oa1 + 128, o1, bO + r1); st_async32(oa2 + 128, o1, bO + r2);
      sts32(l4 + CH_O + 1024, o0); sts32(l4 + CH_O + 1152, o1);
      bar_arrive(2, 256);
      pin();
      TM(6);
      mma16h(l, p3, p4, ones, ones);
      float inv;
      asm("rcp.approx.ftz.f32 %0, %1;" : "=f"(inv) : "f"(l[0]));
      sts32((l8 & ~0xffu) + (lane & 28) + CH_VP, __float_as_uint(inv));
      __syncwarp();
      if (elect()) mbar_arrive(bO);
      {
        float z[2][4] = {}, y[2][4] = {};
        mma16(z[0], wd[0], wd[1], wd[2], wd[3], o0, o1);
        if (j == 0) {
#pragma unroll
          for (int u = 0; u < 3; u++) if (!CH_WE) ldsm4t(&we[4 * u], (wo ^ 32) + u * 28672);
          mma16(y[0], we[0], we[1], we[2], we[3], o0, o1);
        }
        const float2 iv = lds64f((l8 & ~0xe0u) + CH_VP);
        uint8_t* dst = pool(pdst[0]);
        const uint32_t mask = ((l16 ^ tag) & 48) == 0;
        const uint32_t oa = qa + ((tag & 0xfffe) + CH_O - CH_QK + t4 * 256 - (t4 == 3 ? 1024 : 0));
        const uint32_t za = l16 + ((tag & 0xfffe) + (t4 >> 1) * 512 + (t4 & 1) * 8);
        pin();
        mbar_wait(bO, s & 1);
        uint32_t a[4];
        ldsm4(a, oa);
        mma16(z[0], wd[4], wd[5], wd[6], wd[7], a[0], a[1]);
        mma16(z[1], wd[8], wd[9], wd[10], wd[11], a[2], a[3]);
        if (j == 0) {
          mma16(y[0], we[4], we[5], we[6], we[7], a[0], a[1]);
          mma16(y[1], we[8], we[9], we[10], we[11], a[2], a[3]);
          sts128f(lw + CH_VT + 512, y[0][0] + y[1][0], y[0][1] + y[1][1], y[0][2] + y[1][2], y[0][3] + y[1][3]);
        }
        sts128f(lw + CH_VT, z[0][0] + z[1][0], z[0][1] + z[1][1], z[0][2] + z[1][2], z[0][3] + z[1][3]);
        bar_sync(3, 128);
        if (j == 0 || t4 < 2) {
          float2 q[4];
#pragma unroll
          for (int i = 0; i < 4; i++) q[i] = lds64f(za + CH_VT + i * 1024);
          stg_strong32(dst, pack_tag(((q[0].x + q[1].x) + (q[2].x + q[3].x)) * iv.x, ((q[0].y + q[1].y) + (q[2].y + q[3].y)) * iv.y, tag, mask));
        }
      }
      TM(2);
      if (!NOX) mbar_wait_hot(bXA, (s + 1) & 1);
      if (CH_KP == 2) bulk_wait_read<0>();
      float dk[16], dw[16];
      bar_sync(5, 256);
      wg_fence();
      pass(dk, ak, Int<0>(), Int<20>());
      pass(dw, av, Int<0>(), Int<20>());
      TM(5);
      pin();
      if (CH_EX == 0) publish_v(s, v, vm);
      if (elect()) {
        mbar_expect(bG + t4 * 8, 2560);
        if (t4 == 1 && s + 2 < NSEG) { mbar_expect(bX, 1536); mbar_expect(bO, 2048); }
      }
      if (CH_KD == 0) { wg_wait<1>(); dump(dk, lw + CH_KT); }
      wg_wait<0>();
      if (CH_KD == 1) dump(dk, lw + CH_KT);
      TM(7);
      dump(dw, lw + CH_VT);
      bar_arrive(9, 256);
      pin();
#pragma unroll
      for (int k = 0; k < CH_RB; k++) ldsm4t(&tw[4 * k], wq + k * 2048);
      if (t4 < 2) {
#pragma unroll
        for (int k = CH_RB; k < CH_RC; k++) ldsm4t(&tw[4 * k], wq + k * 2048);
        const int q = t4 ? 3 : j, o = t4 ? j * 896 : 0;
        const uint8_t* src = p.pool + ((80 + st * 4 + q) * 8192 + (pages >> (st * 4 + q) & 1) * 4096 + o);
        asm volatile("bar.sync 8, 256;" ::: "memory");
        const uint32_t t1 = clk32() + CH_D2;
        if (CH_EX == 1) publish_v(s, v, vm);
        auto fetch = [&](auto n) {
          mbar_wait(bH, s & 1);
          until(t1);
          TR(4, clk32());
          if (elect())
            asm volatile("cp.async.bulk.shared::cluster.global.mbarrier::complete_tx::bytes.multicast::cluster [%0], [%1], %2, [%3], 7;"
                         :: "r"(sb + CH_M + q * 2560 + o), "l"(src), "n"(n.value), "r"(bG + q * 8) : "memory");
        };
        if (!t4) fetch(Int<2560>()); else if (j == 2) fetch(Int<768>()); else fetch(Int<896>());
      } else {
        asm volatile("bar.sync 8, 256; " ::: "memory");
        if (elect()) asm volatile("mbarrier.arrive.relaxed.cluster.shared::cluster.b64 _, [%0];" :: "r"(bH + (t4 == 2 ? r1 : r2)) : "memory");
        pin();
        if (CH_EX == 1) publish_v(s, v, vm);
#pragma unroll
        for (int k = CH_RB; k < CH_RC; k++) ldsm4t(&tw[4 * k], wq + k * 2048);
      }
      TM(9);
      pin();
#pragma unroll
      for (int k = CH_RC; k < CH_TW; k++) ldsm4t(&tw[4 * k], wq + k * 2048);
      if (CH_KP == 2 && t4 == CH_KW) { bar_sync(7, 160); publish_k(s + 1); }
      TM(10);
    }
    if (++st == 3) st = 0;
    tag ^= 0x10001;
  }
  {
    const int s = NSEG - 1;
    float dv[16] = {};
    uint32_t b[40], kf[16];
    project(s, b, dv, kf);
    finish_v(b, dv);
    sum_v(dv);
    if (WG == 0) {
      sts64(l8 + CH_VP, pack2(dv[0], dv[1]), pack2(dv[2], dv[3]));
      bar_sync(1, 256);
      if (CH_KP == 0) publish_k(s);
      publish_km(s);
      bulk_wait<0>();
      fence_async_global();
      bar_sync(2, 256);
      if (tid == 0) red_release(g_sync + 15 * 8 + 4, 1);
    } else {
      const uint4 v[2] = {lds128(lw + CH_VT), lds128(lw + CH_VT + 512)};
      bar_sync(1, 256);
      publish_v(s, v, memory_v(lds64(l8 + CH_VP), dv));
      bulk_wait<0>();
      fence_async_global();
      bar_arrive(2, 256);
    }
  }
}

__global__ void __launch_bounds__(256, 1) chain_kernel(const __grid_constant__ ChainParams p) {
  extern __shared__ __align__(1024) uint8_t smem_raw[];
  const uint32_t sb = s2u(smem_raw);
  const int tid = threadIdx.x, warp = __shfl_sync(~0u, tid >> 5, 0), lane = tid & 31;
  const int cta = blockIdx.x, h = cta / 3, j = cta - 3 * h, colbase = cta * 64;
  const uint32_t bWo = sb + CH_BAR, bWq = bWo + 8, bXA = bWo + 24, bWk = bWo + 80, bWv = bWo + 88;
  uint32_t smid; asm("mov.u32 %0, %%smid;" : "=r"(smid));
  PRO(0);
  if (sb != mapa(CH_BASE, j)) __trap();
  uint32_t entry = 0;
  auto place = [&]() {
    const int i = tid - 128;
    if (i >= 0 && i <= NSLOT) {
      const uint32_t side = ldg_strong32(g_smpart + (smid & 255));
      if (i < NSLOT) {
        entry = i * 8192 + (ldg_strong32(g_orient + i) == (i < 80 ? i & 1 : side) ? 0 : 4096);
      } else {
        entry = 2 * (atomicAdd(g_bo + p.layer * 128 + 1, 1 << 8 * side) >> 8 * side & 255) + side;
      }
    }
    __syncwarp();
  };
  if (p.layer) place();
  if (warp == 0 && elect()) {
#pragma unroll 1
    for (int i = 0; i < 17; i++) mbar_init(bWo + 8 * i, i == 2 || i == 5 ? 5 : i == 3 || i == 4 ? 4 : i == 12 ? 2 : 1);
    asm volatile("fence.mbarrier_init.release.cluster;" ::: "memory");
    mbar_expect(bWk, 81920);
    tma_load3<(WEF & 1) != 0>(sb + CH_WQ, &p.wk, colbase, 0, bWk);
    mbar_expect(bWv, 81920);
    tma_load3<(WEF & 1) != 0>(sb + CH_WO, &p.wv, colbase, 0, bWv);
    mbar_expect(bWo + 16, 1536);
    mbar_expect(bWo + 40, 2048);
    mbar_expect(bWo, 86016); mbar_expect(bWq, 81920);
#pragma unroll 1
    for (int i = 0; i < 8; i++) mbar_expect(bXA + 8 * (i & 1), 5120);
  }
  if (warp == 1) {
    const uint32_t id = (lane >> 3) == (lane & 3) ? ((lane & 4) ? 0x3f800000u : 0x00003f80u) : 0u;
    sts128(sb + CH_ID + lane * 16, make_uint4(id, 0, 0, id));
  }
  __syncthreads();
  asm volatile("barrier.cluster.arrive.relaxed.aligned;" ::: "memory");
  uint32_t ak[80], av[80];
  const uint32_t wq = opaque(sb + CH_WQ + ((warp >> 2) * 320 + (lane & 7) + (lane >> 4) * 8) * 128 + (((2 * (warp & 3) + ((lane >> 3) & 1)) ^ (lane & 7)) << 4));
  pdl_wait();
  if (tid == 32) stg_strong32(g_smuse + (smid & 255), p.layer + 1);
  pdl_launch();
  PRO(1);
  if (warp == 0 && elect()) {
    bulk_load(sb + CH_X + 20480, p.xc + 5120, 20480, bXA);
    bulk_load(sb + CH_X, p.xc, 20480, bXA + 8);
  }
  if (!p.layer) place();
  __syncwarp();
  PRO(2);
  mbar_wait(bWk, 0);
  PRO(3);
#pragma unroll
  for (int k = 0; k < 20; k++) ldsm4t(&ak[4 * k], wq + k * 2048);
  bar_sync(6, 256);
  if (warp == 0 && elect()) tma_load3<(WEF & 2) != 0>(sb + CH_WQ, &p.wq, colbase, 0, bWq);
  __syncwarp();
  PRO(4);
  mbar_wait(bWv, 0);
  PRO(5);
#pragma unroll
  for (int k = 0; k < 20; k++) ldsm4t(&av[4 * k], wq + CH_WO + k * 2048);
  bar_sync(6, 256);
  PRO(6);
  if (warp >= 5 && elect()) tma_load3<(WEF & 2) != 0>(sb + CH_WO + (warp - 5) * 28672, &p.wo, j == 0 ? 0 : 32 + j * 192, h * 192 + (j + 8 - warp) % 3 * 64, bWo);
  if (tid == 128 + NSLOT && entry >= 80) {
    uint32_t c;
    int n = 0;
    do { c = ldg_strong32(g_bo + p.layer * 128 + 1); spin_guard(n); } while ((c & 255) + (c >> 8) < 96);
    const uint32_t other = (c >> 8 * (~entry & 1) & 255) + (entry >> 1) - 40;
    entry = other < 40 ? 2 * other + (~entry & 1) : entry % 80;
  }
  if (tid >= 128 && tid <= 128 + NSLOT) sts32(sb + CH_O + (tid - 128) * 4, entry);
  PRO(7);
  __syncthreads();
  if (__shfl_sync(~0u, tid >> 7, 0) == 0) chain_body<0>(p, wq, ak, av); else chain_body<1>(p, wq, ak, av);
}

struct PostParams { CUtensorMap wq, wo, wb, wo2, wb2; int gap, share, layer, look, gap2, pol; };
constexpr int PS = 8, PB = 28672;
constexpr int OP_SMEM = PS * PB + 512 + 2048;
enum { IT_ATT = 0, IT_OP = 1, IT_FIN = 2, IT_BQ = 3, IT_Q = 4 };

__device__ __forceinline__ uint32_t item_count(int type, int b) {
  return type == IT_ATT ? 32 : type == IT_OP ? op_split(b) * (DM / op_width(b)) : type == IT_FIN ? fin_items(b) : 1920 / bq_width(b); }
__device__ __forceinline__ uint32_t item_need(int type, int b) { return type == IT_ATT ? 96 : item_count(type - 1, b); }

struct Ring {
  uint32_t sb, bars; int st; uint32_t ph;
  __device__ __forceinline__ uint32_t wait() const { mbar_wait(bars + 8 * st, ph); return sb + st * PB; }
  __device__ __forceinline__ void next() { if (++st == PS) { st = 0; ph ^= 1; } }
  __device__ __forceinline__ void release(int s) const { if ((threadIdx.x & 31) == 0) mbar_arrive(bars + 8 * (PS + s)); }
  __device__ __forceinline__ void pop() { __syncwarp(); release(st); next(); }
};

template <int N>
__device__ __forceinline__ void gemm_item(Ring& r, float* d, int nst, uint32_t go, int go_at) {
  int prev = 0;
#pragma unroll 1
  for (int kb = 0; kb < nst; kb++) {
    const uint32_t base = r.wait();
    const uint64_t da = mkdesc(base + (threadIdx.x >> 7) * 4096, 128, 512, 0), db = mkdesc(base + 8192, 4096, 1024, 1);
    wg_fence();
#pragma unroll
    for (int kk = 0; kk < 2; kk++) {
      if (N == 80) wg_ss80_01(d, da + kk * 16, db + kk * 128, (kb | kk) != 0);
      if (N == 160) wg_ss160_01(d, da + kk * 16, db + kk * 128, (kb | kk) != 0);
      if (N >= 192) wg_ss192_01(d, da + kk * 16, db + kk * 128, (kb | kk) != 0);
      if (N == 320) wg_ss128_01(d + 96, da + kk * 16, db + kk * 128 + 3 * 256, (kb | kk) != 0);
    }
    wg_commit();
    if (kb == go_at && threadIdx.x == 0) mbar_arrive(go);
    if (kb > 0) { wg_wait<1>(); r.release(prev); }
    prev = r.st;
    r.next();
  }
  wg_wait<0>();
  reg_fence<N / 2>(d);
  r.release(prev);
}

template <int HALF>
__device__ __forceinline__ void attn_a_warp(Ring& r, const uint32_t (&q)[48], int b, int h) {
  constexpr int NT = HALF ? 5 : 3, NF = 8 * NT;
  const int lane = threadIdx.x & 31, g = lane >> 2, c = lane & 3, seg = (threadIdx.x >> 5) & 3;
  uint32_t f[6][NF];
  int slot[6];
  auto fetch = [&](int u) {
    const uint32_t kv = r.wait() + seg * KV_BYTES;
    slot[u] = r.st;
    r.next();
#pragma unroll
    for (int w = 0; w < 4; w++) {
      uint32_t* d = &f[u][2 * NT * w];
#pragma unroll
      for (int t = 0; t <= HALF; t++) {
        if (u < 3) {
          ldsm4(d + 4 * t, kv + w * 1024 + t * 512 + (lane & 8) * 32 + (lane & 16) * 8 + (lane & 7) * 16);
        } else {
          const uint4 v = lds128(kv + w * 1024 + t * 512 + lane * 16);
          d[4 * t] = v.x; d[4 * t + 1] = v.y; d[4 * t + 2] = v.z; d[4 * t + 3] = v.w;
        }
      }
      const uint2 m = lds64(kv + KV_M + w * 256 + lane * 8);
      d[2 * NT - 2] = m.x; d[2 * NT - 1] = m.y;
    }
    pdl_launch();
  };
  float s[NT][4] = {};
  fetch(0);
#pragma unroll
  for (int u = 0; u < 3; u++) {
    fetch(u + 1);
#pragma unroll
    for (int kk = 0; kk < 4; kk++) {
      const uint32_t* a = &q[16 * u + 4 * kk];
#pragma unroll
      for (int n = 0; n < NT; n++) mma16(s[(n + 1) % NT], a[0], a[1], a[2], a[3], f[u][2 * NT * kk + 2 * n], f[u][2 * NT * kk + 2 * n + 1]);
    }
    r.release(slot[u]);
    pdl_launch();
  }
  fetch(4);
  const float k2 = 0.07216878364870322f * 1.44269504089f, NEG = -INFINITY;
  if (2 * c > g) { s[NT - 2][0] = NEG; s[NT - 1][2] = NEG; }
  if (2 * c + 1 > g) { s[NT - 2][1] = NEG; s[NT - 1][3] = NEG; }
  s[NT - 1][0] = s[NT - 1][1] = NEG;
  uint32_t pp[NT][2]; float inv[2];
#pragma unroll
  for (int hh = 0; hh < 2; hh++) {
    float m = NEG, l = 0.f;
#pragma unroll
    for (int n = 0; n < NT; n++) m = fmaxf(m, fmaxf(s[n][2 * hh], s[n][2 * hh + 1]));
    m = fmaxf(m, __shfl_xor_sync(~0u, m, 1)); m = fmaxf(m, __shfl_xor_sync(~0u, m, 2));
#pragma unroll
    for (int n = 0; n < NT; n++) { const float x = ex2((s[n][2 * hh] - m) * k2), y = ex2((s[n][2 * hh + 1] - m) * k2); l += x + y; pp[n][hh] = pack2(x, y); }
    l += __shfl_xor_sync(~0u, l, 1); l += __shfl_xor_sync(~0u, l, 2);
    asm("rcp.approx.ftz.f32 %0, %1;" : "=f"(inv[hh]) : "f"(l));
  }
  uint32_t* dst = g_o + ((b * 192 + h * 6) * 16 + seg * 4 + HALF * 2) * 128 + lane;
#pragma unroll
  for (int u = 3; u < 6; u++) {
    float o[8][4] = {};
#pragma unroll
    for (int n = 0; n < 8; n++) mma8(o[n], pp[0][0], pp[0][1], f[u][2 * NT * (n >> 1) + 2 * NT - 2 + (n & 1)]);
#pragma unroll
    for (int t = 0; t <= HALF; t++)
#pragma unroll
      for (int n = 0; n < 8; n++) {
        const uint32_t* v = &f[u][2 * NT * (n >> 1) + 4 * t + 2 * (n & 1)];
        mma16(o[n], pp[1 + 2 * t][0], pp[1 + 2 * t][1], pp[2 + 2 * t][0], pp[2 + 2 * t][1], v[0], v[1]);
      }
    r.release(slot[u]);
    if (u == 3) fetch(5);
#pragma unroll
    for (int n = 0; n < 8; n++) {
      dst[(u - 3) * 4096 + (n >> 2) * 2048 + (n & 3) * 32] = pack2(o[n][0] * inv[0], o[n][1] * inv[0]);
      dst[(u - 3) * 4096 + (n >> 2) * 2048 + (n & 3) * 32 + 128] = pack2(o[n][2] * inv[1], o[n][3] * inv[1]);
    }
  }
}

template <int NG>
__device__ __forceinline__ void fin_item(Ring& r, uint32_t scratch, int b, int idx) {
  const int warp = threadIdx.x >> 5, lane = threadIdx.x & 31;
  float4* x = g_x + ((b * 16 + idx * NG) * 40 + warp * 5) * 32 + lane;
  float4 v[NG][5];
#pragma unroll
  for (int g = 0; g < NG; g++) {
    const uint32_t base = r.wait();
#pragma unroll
    for (int i = 0; i < 5; i++) v[g][i] = lds128f(base + ((warp * 5 + i) * 32 + lane) * 16);
    r.pop();
  }
#pragma unroll 1
  for (int k = 0; k < op_split(b); k += NG == 1 ? 2 : 1) {
#pragma unroll
    for (int g = 0; g < NG; g += 2) {
      const uint32_t base = r.wait();
#pragma unroll
      for (int i = 0; i < 10; i++) {
        const uint2 q = lds64(base + ((i / 5 * 40 + warp * 5 + i % 5) * 32 + lane) * 8);
        float4& t = v[(g + i / 5) % NG][i % 5];
        t.x += bf_lo(q.x); t.y += bf_hi(q.x); t.z += bf_lo(q.y); t.w += bf_hi(q.y);
      }
      r.pop();
    }
  }
  float mean[NG], rs[NG];
  ln_stats<NG>(v, scratch, mean, rs);
#pragma unroll
  for (int i = 0; i < 5; i++) {
    const int u = warp * 5 + i;
    uint32_t* xn = g_xn + ((b * 20 + (u >> 1)) * 16 + idx * NG) * 128 + (u & 1) * 64 + lane;
#pragma unroll
    for (int g = 0; g < NG; g++) {
      xn[g * 128] = pack2((v[g][i].x - mean[g]) * rs[g], (v[g][i].y - mean[g]) * rs[g]);
      xn[g * 128 + 32] = pack2((v[g][i].z - mean[g]) * rs[g], (v[g][i].w - mean[g]) * rs[g]);
    }
  }
#pragma unroll
  for (int g = 0; g < NG; g++)
#pragma unroll
    for (int i = 0; i < 5; i++) x[(g * 40 + i) * 32] = v[g][i];
}

__global__ void __launch_bounds__(384, 1) post_kernel(const __grid_constant__ PostParams p) {
  extern __shared__ __align__(1024) uint8_t smem_raw[];
  const uint32_t sb = s2u(smem_raw), bars = sb + PS * PB;
  const uint32_t bIF = bars + 128, bIE = bars + 160, done = bars + 192, bGo = bars + 224, slots = bars + 240, scratch = bars + 512;
  const int warp = __shfl_sync(~0u, threadIdx.x >> 5, 0), lane = threadIdx.x & 31;
  TRACE(0);
  pdl_launch();
  if (sb & 1023) __trap();
  if (threadIdx.x < 29) mbar_init(bars + 8 * threadIdx.x, threadIdx.x < 8 ? 1 : threadIdx.x < 16 ? 8 : threadIdx.x < 20 ? 1 : threadIdx.x < 24 ? 2 : threadIdx.x < 28 ? 8 : 1);
  if (threadIdx.x == 32) sts32(slots + 16, p.gap);
  fence_async();
  __syncthreads();
  if (warp >= 8) {
    asm volatile("setmaxnreg.dec.sync.aligned.u32 56;");
    if (warp == 9) {
      const int b = lane & 15;
      bool queries = QA_END < 16 && blockIdx.x < 36;
      for (int n = 0;; n++) {
        if (n > 0) mbar_wait(bGo, (n - 1) & 1);
        mbar_wait(bIE + 8 * (n & 3), ((n >> 2) & 1) ^ 1);
        int code = -1, spin = 0, ticket = 0;
        if (queries) {
          if (lane == 0) ticket = atomicAdd(g_sync + SY_QC, 1);
          ticket = __shfl_sync(~0u, ticket, 0);
          queries = ticket < (16 - QA_END) * 32;
          if (queries) code = IT_Q << 16 | (QA_END + ticket % (16 - QA_END)) << 8 | ticket / (16 - QA_END);
        }
        if (!queries && lane == 0) ticket = atomicAdd(g_sync + SY_T, 1);
        while (!queries) {
          const uint4 hd = ldg_strong128(g_sync + b * 8), pr = ldg_strong128(g_sync + b * 8 + 4);
          const uint32_t hv[4] = {hd.x, hd.y, hd.z, hd.w}, pv[4] = {pr.x, pr.y, pr.z, pr.w};
          const uint32_t chain_done = __ballot_sync(~0u, (pr.x & 0xffff) >= 96) & 0xffff;
          int left[4], avail[4], rdy = 0, claimed = 0, upstream = 0;
#pragma unroll
          for (int t = 0; t < 4; t++) {
            const int cnt = lane < 16 ? item_count(t, b) : 0;
            left[t] = max(cnt - (int)hv[t], 0);
            claimed += cnt - left[t];
            const bool ready = (pv[t] & 0xffff) >= item_need(t, b);
            rdy |= ready << t;
            bool ok = ready || (t == IT_ATT ? pr.x >= 0x10000 : !upstream || (t == IT_OP && (chain_done >> 15 & 1)));
            if (t == IT_BQ && (chain_done >> BQ_HOLD & 1) && !(chain_done >> 15)) ok = false;
            avail[t] = ok ? left[t] : 0;
            upstream |= __any_sync(~0u, left[t] > 0);
          }
          if (!upstream) break;
          int rank = max(__shfl_sync(~0u, ticket, 0) - __reduce_add_sync(~0u, claimed), 0), type = -1, mine = 0;
#pragma unroll
          for (int c = 0; c < 8; c++) {
            const int t = c == 0 || c == 5 ? IT_FIN : c == 1 || c == 7 ? IT_ATT : c == 2 || c == 4 ? IT_OP : IT_BQ;
            int a = c == 1 || ((rdy >> t & 1) == (c < 4)) ? avail[t] : 0;
            if (t == IT_OP && !(p.pol & 1)) a = c == 2 ? avail[t] : 0;
            if (c == 7) a = b < QA_END && !(rdy & 1) && ((chain_done << 1 | 1) >> b & 1) ? left[t] : 0;
            const int tot = __reduce_add_sync(~0u, a);
            if (type < 0) { if (rank < tot) { type = t; mine = a; } else rank -= tot; }
          }
          if (type >= 0) {
#pragma unroll
            for (int o = 1; o < 16; o <<= 1) { const int y = __shfl_up_sync(~0u, mine, o); if (lane >= o) mine += y; }
            const int blk = __ffs(__ballot_sync(~0u, mine > rank)) - 1;
            const int early = !(__shfl_sync(~0u, rdy, blk) >> type & 1);
            uint32_t idx = 0;
            if (lane == 0) { idx = atomicAdd(g_sync + blk * 8 + type, 1); ld_acquire(g_sync + blk * 8 + 4 + type); }
            idx = __shfl_sync(~0u, idx, 0);
            if (idx < item_count(type, blk)) { code = (chain_done >> 15 & 1) << 22 | (chain_done >> p.look & 1) << 21 | early << 20 | type << 16 | blk << 8 | idx; break; }
          } else {
            __nanosleep(50);
          }
          spin_guard(spin);
        }
        if (lane == 0) {
          fence_async_global();
          sts32(slots + 4 * (n & 3), code);
          mbar_arrive(bIF + 8 * (n & 3));
        }
        __syncwarp();
        if (code < 0) break;
      }
    } else if (warp == 8) {
      if (elect()) {
        uint32_t dst = sb, bar = bars, ph = 1, next = clk32(), gap = 0;
        auto acquire = [&](uint32_t kb) {
          mbar_wait(bar + 8 * PS, ph);
          mbar_expect(bar, kb * 1024);
          if (gap) {
            uint32_t now;
            do now = clk32(); while ((int)(now - next) < 0);
            next = ((int)(now - next) > 100 ? now - 100 : next) + kb * gap;
          }
        };
        auto advance = [&]() { dst += PB; bar += 8; if (dst == bars) { dst = sb; bar = bars; ph ^= 1; } };
        auto depend = [&](const uint32_t* c, uint32_t need) { wait_count(c, need); fence_async_global(); };
#pragma unroll 1
        for (int n = 0;; n++) {
          mbar_wait(bIF + 8 * (n & 3), (n >> 2) & 1);
          const int code = (int)lds32(slots + 4 * (n & 3));
          if (code < 0) break;
          const int type = (code >> 16) & 15, b = (code >> 8) & 255, idx = code & 255;
          const bool early = code >> 20 & 1, go = !(code >> 21 & 1);
          mbar_arrive(bIE + 8 * (n & 3));
          gap = !(code >> 22 & 1) ? lds32(slots + 16) : type == IT_ATT || type == IT_FIN ? 0 : p.gap2;
          const uint32_t* progress = g_sync + b * 8 + 4 + type;
          if (type == IT_ATT && b >= QA_END) {
            depend(g_sync + SY_Q, (16 - QA_END) * 32);
#pragma unroll 1
            for (int u = 0; u < 2; u++) { acquire(24); bulk_load_last(dst, g_q + (((b - QA_END) * 32 + idx) * 2 + u) * 1536, 24576, bar); advance(); }
          } else if (type == IT_FIN) {
            const int ng = 16 / fin_items(b), lg = ng >> 1;
#pragma unroll 1
            for (int g = 0; g < ng; g++) { acquire(20); bulk_load(dst, g_x + (b * 16 + idx * ng + g) * 1280, 20480, bar); advance(); }
            if (early) depend(progress, item_need(type, b));
            if (go) mbar_arrive(bGo);
#pragma unroll 1
            for (int i = 0; i < op_split(b) * ng; i += 2) {
              const uint2* src = g_part + ((b * 16 + (i >> lg)) * 16 + idx * ng + (i & (ng - 1))) * 1280;
              acquire(20);
              bulk_load_last(dst, src, ng > 1 ? 20480 : 10240, bar);
              if (ng == 1) bulk_load_last(dst + 10240, src + 16 * 1280, 10240, bar);
              advance();
            }
          } else {
            const bool op = type == IT_OP, bq = type == IT_BQ;
            const int width = op ? op_width(b) : bq ? bq_width(b) : 192, nb = (width + 63) >> 6, lt = width == 320 ? 1 : 2;
            const int nst = op ? 192 / op_split(b) : 20, kb0 = op ? (idx >> lt) * nst : 0;
            const int col = (op ? idx & ((1 << lt) - 1) : idx) * width;
            const bool whole = !(width & 63);
            const CUtensorMap* m = op ? (whole ? &p.wo : &p.wo2) : bq ? (whole ? &p.wb : &p.wb2) : &p.wq;
            const uint32_t* a = op ? g_o + (b * 192 + kb0) * 2048 : g_xn + b * 20 * 2048;
            int row = kb0 * 32, pre = early && (op || bq) ? min(nst, PS) : 0;
            auto weights = [&]() {
              acquire(8 + nb * 4);
              if (whole) {
                tma_load3z(dst + 8192, m, row, col >> 6, bar);
              } else {
                tma_load(dst + 8192, m, col, row, bar); tma_load(dst + 12288, m, col + 64, row, bar);
                if (nb == 3) tma_load(dst + 16384, m, col + 128, row, bar);
              }
              row += 32;
            };
            if (pre) {
              uint32_t da = dst, ba = bar;
#pragma unroll 1
              for (int kb = 0; kb < pre; kb++) { weights(); advance(); }
              depend(progress, item_need(type, b));
#pragma unroll 1
              for (int kb = 0; kb < pre; kb++) {
                bulk_load(da, a, 8192, ba);
                a += 2048; da += PB; ba += 8;
                if (da == bars) { da = sb; ba = bars; }
              }
            }
#pragma unroll 1
            for (int kb = pre; kb < nst; kb++) { weights(); if (op && OEF) bulk_load_last(dst, a, 8192, bar); else bulk_load(dst, a, 8192, bar); a += 2048; advance(); }
          }
          if (type == IT_ATT) {
            if (early) depend(progress, 96);
            if (go) mbar_arrive(bGo);
            const uint8_t* src = g_kv + (size_t)(idx * 6 * NSEG + b * 4) * KV_BYTES;
#pragma unroll 1
            for (int u = 0; u < 6; u++) {
              acquire(20);
              bulk_load_last(dst, src, 20480, bar);
              src += u == 2 ? -3 * KV_V : 2 * KV_V;
              advance();
            }
          }
        }
      }
    } else if (warp == 11) {
      uint32_t smid, nsm, used = 0;
      asm("mov.u32 %0, %%smid;" : "=r"(smid)); asm("mov.u32 %0, %%nsmid;" : "=r"(nsm));
      for (int n = 0; n < 64 && used < 96; n++) {
        uint32_t peers = 0;
        used = 0;
        for (uint32_t i = lane; i < min(nsm, 256u); i += 32) {
          const bool taken = ldg_strong32(g_smuse + i) == p.layer + 1;
          used += taken;
          peers += abs((int)(g_smclk[i] - g_smclk[smid & 255])) < 4000 && !taken;
        }
        used = __reduce_add_sync(~0u, used);
        sts32(slots + 16, max(p.gap, (int)min(__reduce_add_sync(~0u, peers), 18u) * p.share >> 3));
      }
    } else if (warp == 10 && lane == 0) {
      for (int n = 0;; n++) {
        mbar_wait(bIF + 8 * (n & 3), (n >> 2) & 1);
        const int code = (int)lds32(slots + 4 * (n & 3));
        if (code < 0) break;
        const int type = (code >> 16) & 15, b = (code >> 8) & 255;
        mbar_wait(done + 8 * (n & 3), (n >> 2) & 1);
        if (type != IT_BQ) red_release(type == IT_Q ? g_sync + SY_Q : g_sync + b * 8 + 5 + type, 1);
        mbar_arrive(bIE + 8 * (n & 3));
      }
    }
  } else {
    asm volatile("setmaxnreg.inc.sync.aligned.u32 224;");
    const int g = lane >> 2, c = lane & 3;
    Ring r = {sb, bars, 0, 0};
#pragma unroll 1
    for (int n = 0;; n++) {
      mbar_wait(bIF + 8 * (n & 3), (n >> 2) & 1);
      const int code = __shfl_sync(~0u, (int)lds32(slots + 4 * (n & 3)), 0);
      if (code < 0) { TRACE(2); break; }
      const int type = (code >> 16) & 15, b = (code >> 8) & 255, idx = code & 255;
      ITEM(code & 0xfffff, 0);
      if (type == IT_ATT || type == IT_Q) {
        uint32_t q[48];
        if (type == IT_Q || b < QA_END) {
          float d[96] = {};
          reg_fence<96>(d);
          gemm_item<192>(r, d, 20, bGo, type == IT_Q ? 12 : -1);
#pragma unroll
          for (int i = 0; i < 48; i++) q[i] = pack2(d[2 * i], d[2 * i + 1]);
        } else {
#pragma unroll
          for (int u = 0; u < 2; u++) {
            const uint32_t base = r.wait() + threadIdx.x * 16;
#pragma unroll
            for (int i = 0; i < 6; i++) {
              const uint4 v = lds128(base + i * 4096);
              q[24 * u + 4 * i] = v.x; q[24 * u + 4 * i + 1] = v.y; q[24 * u + 4 * i + 2] = v.z; q[24 * u + 4 * i + 3] = v.w;
            }
            r.pop();
          }
        }
        if (type == IT_Q) {
          uint4* dst = g_q + ((b - QA_END) * 32 + idx) * 3072 + threadIdx.x;
#pragma unroll
          for (int i = 0; i < 12; i++) dst[i * 256] = make_uint4(q[4 * i], q[4 * i + 1], q[4 * i + 2], q[4 * i + 3]);
        } else if (warp < 4) {
          attn_a_warp<0>(r, q, b, idx);
        } else {
          attn_a_warp<1>(r, q, b, idx);
        }
      } else if (type == IT_FIN) {
        if (fin_items(b) == 4) fin_item<4>(r, scratch, b, idx);
        else if (fin_items(b) == 8) fin_item<2>(r, scratch, b, idx);
        else fin_item<1>(r, scratch, b, idx);
      } else {
        float d[160] = {};
        reg_fence<160>(d);
        const int width = type == IT_OP ? op_width(b) : bq_width(b), nst = type == IT_OP ? 192 / op_split(b) : 20;
        const int go_at = code >> 21 & 1 ? -1 : max(nst - 6, 0);
        if (width == 320) gemm_item<320>(r, d, nst, bGo, go_at);
        else if (width == 160 || BQ_80 == 16) gemm_item<160>(r, d, nst, bGo, go_at);
        else gemm_item<80>(r, d, nst, bGo, go_at);
        reg_fence<160>(d);
        if (type == IT_OP) {
          const int tiles = DM / width;
          uint2* dst = g_part + (((b * 16 + idx / tiles) * 16 + warp * 2) * 40 + idx % tiles * (width / 16)) * 32 + lane;
#pragma unroll
          for (int u = 0; u < 20; u++) {
            if (u % 5 == 0 && u * 16 >= width) break;
            dst[u * 32] = make_uint2(pack2(d[8 * u], d[8 * u + 1]), pack2(d[8 * u + 4], d[8 * u + 5]));
            dst[(40 + u) * 32] = make_uint2(pack2(d[8 * u + 2], d[8 * u + 3]), pack2(d[8 * u + 6], d[8 * u + 7]));
          }
        } else {
          const int row = b * 128 + warp * 16 + g;
          const int h0 = idx * (width / 20);
          const float sc = h0 < 32 ? 0.22360679775f * 1.44269504089f : 1.f;
          const bool lo = c < 2;
          uint32_t* da = g_bqkv + (h0 * 256 + (row >> 3)) * 96 + lane;
          uint32_t* db = da + 256 * 96 + (lo ? 2 : -2);
          uint32_t pad[2];
#pragma unroll
          for (int rr = 0; rr < 2; rr++) pad[rr] = c & 1 || h0 < 32 ? 0u : h0 >= 64 ? 0x00003f80u : poly_group((row >> 3) + rr) ? 0x3f803f80u : 0u;
#pragma unroll
          for (int q = 0; q < 8; q++) {
            if (!(q & 1) && q * 40 >= width) break;
#pragma unroll
            for (int rr = 0; rr < 2; rr++) {
              uint32_t w[5];
#pragma unroll
              for (int i = 0; i < 5; i++) w[i] = pack2(d[20 * q + 4 * i + 2 * rr] * sc, d[20 * q + 4 * i + 2 * rr + 1] * sc);
              const int o = q * 2 * 256 * 96 + rr * 96;
              da[o] = w[0]; da[o + 32] = w[1]; da[o + 64] = lo ? w[2] : pad[rr];
              db[o] = lo ? w[3] : w[2]; db[o + 32] = lo ? w[4] : w[3]; db[o + 64] = lo ? pad[rr] : w[4];
            }
          }
        }
      }
      __syncwarp();
      if (lane == 0) mbar_arrive(done + 8 * (n & 3));
      if ((code >> 21 & 1) && threadIdx.x == 128) mbar_arrive(bGo);
      ITEM(code & 0xfffff, 1);
    }
  }
}

constexpr int AB_SMEM = 1024 + 98304 + 51200 + 4 * 16384 + 256 + 10240;
#define AB_LW 1
#define AB_U 8
#define AB_WG 4
constexpr int AB_T = AB_WG * 128, AB_PASS = 8 / AB_WG;
__device__ __forceinline__ uint32_t fma2(uint32_t a, uint32_t b, uint32_t c) { uint32_t r; asm("fma.rn.bf16x2 %0, %1, %2, %3;" : "=r"(r) : "r"(a), "r"(b), "r"(c)); return r; }
__device__ __forceinline__ uint32_t ex2_pair(float a, float b, uint32_t one, uint32_t c0) {
  const uint32_t e = __byte_perm(__float_as_uint(a), __float_as_uint(b), 0x6521);
  uint32_t x, r;
  asm("lop3.b32 %0, %1, 0x007f007f, %2, 0xEA;" : "=r"(x) : "r"(e), "r"(one));
  const uint32_t m = AB_DEG == 3 ? fma2(fma2(fma2(c0, x, 0xbbdcbbdcu), x, 0x3ef53ef5u), x, 0x3ee83ee8u) : fma2(fma2(c0, x, 0xbc43bc43u), x, 0x3f2e3f2eu);
  asm("lop3.b32 %0, %1, %2, 0x7f807f80, 0xE4;" : "=r"(r) : "r"(e), "r"(m));
  return r;
}
__device__ __forceinline__ float sq2(uint32_t w) { const float a = bf_lo(w), b = bf_hi(w); return fmaf(a, a, b * b); }

__device__ __forceinline__ void attn_b_store(const float* o, int h, int row0, int lane) {
  const int g = lane >> 2, c = lane & 3;
  const float i0 = __frcp_rn(__shfl_sync(~0u, o[8], (lane & ~3) | 2)), i1 = __frcp_rn(__shfl_sync(~0u, o[10], (lane & ~3) | 2));
#pragma unroll
  for (int jj = 0; jj < 3; jj++) {
    if (jj < 2 || c < 2) {
      const int col = h * 20 + 8 * jj + 2 * c;
      uint32_t* dst = g_of + (((row0 >> 7) * 10 + (col >> 6)) * 16 + (row0 >> 3 & 15)) * 256 + (col >> 3 & 7) * 32 + g * 4 + (col >> 1 & 3);
      dst[0] = pack2(o[4 * jj] * i0, o[4 * jj + 1] * i0);
      dst[256] = pack2(o[4 * jj + 2] * i1, o[4 * jj + 3] * i1);
    }
  }
}

struct AbParams { Weights next; uint32_t* done; uint32_t* out; };
__global__ void __launch_bounds__(AB_T + 32, 1) attn_b_kernel(const __grid_constant__ AbParams p) {
  extern __shared__ uint8_t smem_raw[];
  const uint32_t sb = (s2u(smem_raw) + 1023) & ~1023u, sK = sb, sV = sb + 98304, bars = sV + 51200 + 4 * 16384;
  const uint32_t bF = bars + 64, bW = bars + 72, bA = bars + 80, bE = bars + 128, smax = bars + 176;
  auto ring = [&](int i) { return i < 2 ? sK + 51200 + i * 16384 : sV + 51200 + (i - 2) * 16384; };
  const int warp = __shfl_sync(~0u, threadIdx.x >> 5, 0), lane = threadIdx.x & 31;
  const int h = blockIdx.x >> 2, quarter = blockIdx.x & 3;
  TRACE(0);
  pdl_launch();
  if (threadIdx.x < 22) mbar_init(bars + 8 * threadIdx.x, threadIdx.x == 8 ? AB_T / 32 : threadIdx.x >= 16 ? 8 : 1);
  if (threadIdx.x == 32) sts64(smax, 0, 0);
  fence_async();
  __syncthreads();
  pdl_wait();
  const int blk = quarter * 4 + (h >> 3), cg = h & 7;
  auto unsafe = [&]() { const float2 m = lds64f(smax); return !(m.x * m.y <= 10000.f); };
  if (warp == AB_T / 32) {
    auto load_w = [&]() {
      mbar_expect(bW, 102400);
      for (int i = 0; i < 4; i++) bulk_load((i < 2 ? sK : sV) + (i & 1) * 25600, g_wb + cg * 6400 + i * 1600, 25600, bW);
    };
    if (elect()) {
      const uint32_t* gk = g_bqkv + (32 + h) * 256 * 96;
#pragma unroll 1
      for (int i = 0; i < 8; i++) {
        if (i >= AB_LW) mbar_wait(bars + 8 * (i - AB_LW), 0);
        mbar_expect(bars + 8 * i, 24576);
        bulk_load_last(sK + i * 12288, gk + i * 3072, 12288, bars + 8 * i);
        bulk_load_last(sV + i * 12288, gk + 32 * 256 * 96 + i * 3072, 12288, bars + 8 * i);
      }
    }
    __syncwarp();
    if (blockIdx.x < NSLOT) for (int i = lane; i < 512; i += 32) reinterpret_cast<uint4*>(pool_at(blockIdx.x * 8192))[i] = make_uint4(0, 0, 0, 0);
    if (blockIdx.x == 127) for (int i = lane; i < SY_N; i += 32) g_sync[i] = 0;
    if (p.next.w[0] && lane == 0) {
      for (int i = 0; i < AB_PF; i++) { const uint32_t t0 = clk32(); while (clk32() - t0 < (i ? AB_PFD : AB_PF0)) __nanosleep(200); prefetch_weights(p.next, i); }
    }
    __syncwarp();
    mbar_wait(bF, 0);
    const bool redo = unsafe();
    if (!redo && lane == 0) load_w();
    if (lane < 16) asm volatile("cp.async.bulk.prefetch.L2.global [%0], 2560;" :: "l"(g_x + ((blk * 16 + lane) * 40 + cg * 5) * 32) : "memory");
    __syncwarp();
    bar_sync(1, AB_T + 32);
    if (lane == 0) {
      ABT(!!p.out, 1);
      red_release(p.done + quarter * 32, 1);
      ABT(!!p.out, 2);
      if (redo) load_w();
      wait_count(p.done + quarter * 32, 32);
      fence_async_global();
      ABT(!!p.out, 3);
      for (int kb = 0; kb < 10; kb++) {
        const int i = kb < 6 ? kb : kb - 6;
        if (kb >= 6) mbar_wait(bE + 8 * i, 0);
        mbar_expect(bA + 8 * i, 16384);
        bulk_load(ring(i), g_of + (blk * 10 + kb) * 4096, 16384, bA + 8 * i);
      }
    }
    return;
  }
  float qmax = 0.f;
  const uint32_t one = opaque(0x3f803f80u + (threadIdx.x >> 10)), c0 = opaque((AB_DEG == 3 ? 0x3d9f3d9fu : 0x3eac3eacu) + (threadIdx.x >> 10));
#pragma unroll 1
  for (int pass = 0; pass < AB_PASS; pass++) {
    const int row0 = quarter * 512 + ((warp >> 2) * AB_PASS + pass) * 64 + (warp & 3) * 16;
    const uint32_t* gq = g_bqkv + (h * 256 + (row0 >> 3)) * 96 + lane;
    const uint32_t q0 = gq[0], q1 = gq[96], q2 = gq[32], q3 = gq[128];
    uint32_t q4 = gq[64], q5 = gq[160];
    const uint32_t z0 = gq[64 + 3 - (lane & 3)], z1 = gq[160 + 3 - (lane & 3)];
    {
      float n0 = sq2(q0) + sq2(q2) + sq2(q4), n1 = sq2(q1) + sq2(q3) + sq2(q5);
      n0 += __shfl_xor_sync(~0u, n0, 1); n1 += __shfl_xor_sync(~0u, n1, 1);
      n0 += __shfl_xor_sync(~0u, n0, 2); n1 += __shfl_xor_sync(~0u, n1, 2);
      qmax = (n0 > qmax || n0 != n0) ? n0 : qmax;
      qmax = (n1 > qmax || n1 != n1) ? n1 : qmax;
    }
    if (pass == AB_PASS - 1) {
      float kmax = 0.f;
#pragma unroll
      for (int i = 0; i < SEQ / AB_T; i++) {
        const int key = threadIdx.x + AB_T * i;
        const uint32_t a = sK + (key >> 3) * 384 + (key & 7) * 16;
        const uint4 x = lds128(a), y = lds128(a + 128);
        const uint2 z = lds64(a + 256);
        const float n = ((sq2(x.x) + sq2(x.y)) + (sq2(x.z) + sq2(x.w))) + ((sq2(y.x) + sq2(y.y)) + (sq2(y.z) + sq2(y.w))) + (sq2(z.x) + sq2(z.y));
        kmax = (n > kmax || n != n) ? n : kmax;
      }
      const uint32_t kb = __reduce_max_sync(~0u, __float_as_uint(kmax) & 0x7fffffffu), qb = __reduce_max_sync(~0u, __float_as_uint(qmax) & 0x7fffffffu);
      if (lane < 2) asm volatile("red.shared.max.u32 [%0], %1;" :: "r"(smax + 4 * lane), "r"(lane ? kb : qb) : "memory");
      __syncwarp();
    }
    if ((lane & 3) == 2) { q4 = 0xBF8043C0u; q5 = 0xBF8043C0u; }
    float o[12];
    auto desc = [](uint32_t lo, uint32_t hi) { uint64_t d; asm("mov.b64 %0, {%1, %2};" : "=l"(d) : "r"(lo), "r"(hi)); return d; };
    const uint32_t k0 = (uint32_t)mkdesc(sK, 128, 0, 0), k1 = (uint32_t)mkdesc(sK + 256, 0, 0, 0), v0 = (uint32_t)mkdesc(sV, 384, 0, 0);
    float sa[16], sb2[16];
    uint32_t pa[8], pb[8];
    auto qk = [&](float* s, uint32_t t) {
      wg_rs32_00(s, q0, q1, q2, q3, desc(k0 + t, 24), 0);
      wg_rs32_00(s, q4, q5, z0, z1, desc(k1 + t, 24), 1);
      wg_commit();
    };
    auto step = [&](float* s, uint32_t* pp, int g0, uint32_t t, uint32_t nx, int acc) {
      wg_wait<1>();
      reg_fence<16>(s);
#pragma unroll
      for (int i = 0; i < 8; i++) pp[i] = poly_group(g0 + (i >> 1)) ? ex2_pair(s[2 * i], s[2 * i + 1], one, c0) : pack2(ex2(s[2 * i]), ex2(s[2 * i + 1]));
      wg_fence();
      wg_rs24_01(o, pp[0], pp[1], pp[2], pp[3], desc(v0 + t, 8), acc);
      wg_rs24_01(o, pp[4], pp[5], pp[6], pp[7], desc(v0 + t + 48, 8), 1);
      qk(s, nx);
    };
    if (pass == 0) mbar_wait(bars, 0);
    wg_fence();
    qk(sa, 0);
    qk(sb2, 96);
#pragma unroll 1
    for (uint32_t t = 0; t < 64 * 96; t += AB_U * 96) {
      const uint32_t nx = t + AB_U * 96 < 64 * 96 ? t + AB_U * 96 : 0;
      if (pass == AB_PASS - 1 && t == 40 * 96 && lane == 0) mbar_arrive(bF);
#pragma unroll
      for (int u = 0; u < AB_U; u += 2) {
        if (u == AB_U - 2 && pass == 0) mbar_wait(bars + 8 * (nx / 768), 0);
        step(sa, pa, 0, t + u * 96, u + 2 < AB_U ? t + (u + 2) * 96 : nx, u | t);
        step(sb2, pb, 4, t + u * 96 + 96, (u + 2 < AB_U ? t + (u + 2) * 96 : nx) + 96, 1);
      }
    }
    wg_wait<0>();
    reg_fence<12>(o); reg_fence<16>(sa); reg_fence<16>(sb2);
    attn_b_store(o, h, row0, lane);
  }
  mbar_wait(bF, 0);
  if (unsafe())
#pragma unroll 1
  for (int pass = 0; pass < AB_PASS; pass++) {
    const int row0 = quarter * 512 + ((warp >> 2) * AB_PASS + pass) * 64 + (warp & 3) * 16;
    const uint32_t* gq = g_bqkv + (h * 256 + (row0 >> 3)) * 96 + lane;
    const uint32_t q0 = gq[0], q1 = gq[96], q2 = gq[32], q3 = gq[128], q4 = gq[64], q5 = gq[160];
    float o[12];
#pragma unroll
    for (int i = 0; i < 12; i++) o[i] = 0.f;
    float m0 = -INFINITY, m1 = -INFINITY;
#pragma unroll 1
    for (int kt = 0; kt < 32; kt++) {
      float s[32];
      const uint64_t dk = mkdesc(sK + kt * 3072, 128, 384, 0), dk2 = mkdesc(sK + kt * 3072 + 256, 0, 384, 0);
      wg_fence();
      wg_rs64_00(s, q0, q1, q2, q3, dk, 0);
      wg_rs64_00(s, q4, q5, 0, 0, dk2, 1);
      wg_commit();
      wg_wait<0>();
      reg_fence<32>(s); reg_fence<12>(o);
      float n0 = m0, n1 = m1;
#pragma unroll
      for (int jj = 0; jj < 8; jj++) { n0 = fmaxf(n0, fmaxf(s[4 * jj], s[4 * jj + 1])); n1 = fmaxf(n1, fmaxf(s[4 * jj + 2], s[4 * jj + 3])); }
      n0 = fmaxf(n0, __shfl_xor_sync(~0u, n0, 1)); n0 = fmaxf(n0, __shfl_xor_sync(~0u, n0, 2));
      n1 = fmaxf(n1, __shfl_xor_sync(~0u, n1, 1)); n1 = fmaxf(n1, __shfl_xor_sync(~0u, n1, 2));
      const float r0 = ex2(m0 - n0), r1 = ex2(m1 - n1);
      m0 = n0; m1 = n1;
#pragma unroll
      for (int jj = 0; jj < 3; jj++) { o[4 * jj] *= r0; o[4 * jj + 1] *= r0; o[4 * jj + 2] *= r1; o[4 * jj + 3] *= r1; }
      uint32_t pp[16];
#pragma unroll
      for (int jj = 0; jj < 8; jj++) {
        pp[2 * jj] = pack2(ex2(s[4 * jj] - m0), ex2(s[4 * jj + 1] - m0));
        pp[2 * jj + 1] = pack2(ex2(s[4 * jj + 2] - m1), ex2(s[4 * jj + 3] - m1));
      }
      const uint64_t dv = mkdesc(sV + kt * 3072, 384, 128, 0);
      wg_fence();
#pragma unroll
      for (int kk = 0; kk < 4; kk++) wg_rs24_01(o, pp[4 * kk], pp[4 * kk + 1], pp[4 * kk + 2], pp[4 * kk + 3], dv + kk * 48, 1);
      wg_commit();
    }
    wg_wait<0>();
    reg_fence<12>(o);
    attn_b_store(o, h, row0, lane);
  }
  ABT(!!p.out, 0);
  bar_arrive(1, AB_T + 32);
  if (warp >= 12) return;
  const int g = lane >> 2, c = lane & 3;
  const bool live = opaque(threadIdx.x) < 256;
  float d[40] = {};
  float4* x = g_x + ((blk * 16 + warp * 2) * 40 + cg * 5) * 32 + lane;
  if (warp < 8) {
#pragma unroll
  for (int i = 0; i < 10; i++) {
    const int r = i / 5, u = i % 5;
    const float4 t = x[(r * 40 + u) * 32];
    d[8 * u + 2 * r] = t.x; d[8 * u + 2 * r + 1] = t.y; d[8 * u + 4 + 2 * r] = t.z; d[8 * u + 5 + 2 * r] = t.w;
  }
  mbar_wait(bW, 0);
  reg_fence<40>(d);
  ABT(!!p.out, 4);
#pragma unroll 1
  for (int kb = 0; kb < 10; kb++) {
    const int i = kb < 6 ? kb : kb - 6;
    mbar_wait(bA + 8 * i, kb >= 6);
    const uint64_t da = mkdesc(ring(i) + (warp >> 2) * 8192, 128, 1024, 0), db = mkdesc(kb < 5 ? sK + kb * 10240 : sV + (kb - 5) * 10240, 1280, 128, 0);
    wg_fence();
#pragma unroll
    for (int kk = 0; kk < 4; kk++) wg_ss80_01(d, da + kk * 16, db + kk * 160, 1);
    wg_commit();
    if (kb > 0 && kb < 5) { wg_wait<1>(); if (lane == 0) mbar_arrive(bE + 8 * (kb - 1)); }
  }
  wg_wait<0>();
  reg_fence<40>(d);
  }
  ABT(!!p.out, 5);
  if (p.out) {
    if (warp >= 8) return;
    const uint32_t stage = sK + 83968 + warp * 2560 + (warp < 4 ? 0 : 131328 - 10240);
#pragma unroll
    for (int u = 0; u < 5; u++)
      stsm4(stage + (lane & 15) * 160 + u * 32 + (lane >> 4) * 16, pack2(d[8 * u], d[8 * u + 1]), pack2(d[8 * u + 2], d[8 * u + 3]),
            pack2(d[8 * u + 4], d[8 * u + 5]), pack2(d[8 * u + 6], d[8 * u + 7]));
    __syncwarp();
    uint4* out = reinterpret_cast<uint4*>(p.out + (blk * 128 + warp * 16) * (DM / 2) + cg * 40);
#pragma unroll
    for (int i = 0; i < 5; i++) { const int e = i * 32 + lane, r = e / 10; out[r * (DM / 8) + e - r * 10] = lds128(stage + e * 16); }
  } else {
    float2* stat = g_stat + blk * 1024 + (warp & 7) * 16 + g;
    float mean[2], rs[2];
#pragma unroll
    for (int r = 0; r < 2; r++) {
      float t = 0.f, q = 0.f;
#pragma unroll
      for (int i = 0; i < 10; i++) t += d[4 * i + 2 * r] + d[4 * i + 2 * r + 1];
      t += __shfl_xor_sync(~0u, t, 1); t += __shfl_xor_sync(~0u, t, 2);
      t *= 1.f / 80;
#pragma unroll
      for (int i = 0; i < 10; i++) { const float a = d[4 * i + 2 * r] - t, b = d[4 * i + 2 * r + 1] - t; q += a * a + b * b; }
      q += __shfl_xor_sync(~0u, q, 1); q += __shfl_xor_sync(~0u, q, 2);
      if (c == r && live) asm volatile("st.relaxed.gpu.global.v2.b32 [%0], {%1, %2};" :: "l"(stat + cg * 128 + r * 8), "r"(__float_as_uint(t)), "r"(nz(__float_as_uint(q))) : "memory");
    }
#pragma unroll
    for (int i = 0; i < 10; i++) {
      const int r = i / 5, u = i % 5;
      if (live) x[(r * 40 + u) * 32] = make_float4(d[8 * u + 2 * r], d[8 * u + 2 * r + 1], d[8 * u + 4 + 2 * r], d[8 * u + 5 + 2 * r]);
    }
    ABT(0, 6);
    uint2 e[4];
    int n = 0;
    do {
#pragma unroll
      for (int i = 0; i < 4; i++)
        asm volatile("ld.relaxed.gpu.global.v2.b32 {%0, %1}, [%2];" : "=r"(e[i].x), "=r"(e[i].y) : "l"(stat + (2 * c + (i & 1)) * 128 + (i >> 1) * 8) : "memory");
      spin_guard(n);
    } while (__any_sync(~0u, min(min(e[0].y, e[1].y), min(e[2].y, e[3].y)) == 0 && live));
#pragma unroll
    for (int r = 0; r < 2; r++) {
      const float m0 = __uint_as_float(e[2 * r].x), m1 = __uint_as_float(e[2 * r + 1].x);
      float t = m0 + m1;
      t += __shfl_xor_sync(~0u, t, 1); t += __shfl_xor_sync(~0u, t, 2);
      t *= 0.125f;
      float q = __uint_as_float(e[2 * r].y) + __uint_as_float(e[2 * r + 1].y) + 80.f * ((m0 - t) * (m0 - t) + (m1 - t) * (m1 - t));
      q += __shfl_xor_sync(~0u, q, 1); q += __shfl_xor_sync(~0u, q, 2);
      mean[r] = t; rs[r] = rsqrtf(q * (1.f / DM) + 1e-5f);
    }
    ABT(0, 7);
    uint32_t w[2][5][2];
#pragma unroll
    for (int i = 0; i < 20; i++) w[i & 1][i >> 2][i >> 1 & 1] = pack2((d[2 * i] - mean[i & 1]) * rs[i & 1], (d[2 * i + 1] - mean[i & 1]) * rs[i & 1]);
    ln_store(w, blk * 8 + warp, cg * 5, live);
  }
  ABT(!!p.out, 8);
  TRACE(2);
}

typedef CUresult (*EncodeFn)(CUtensorMap*, CUtensorMapDataType, cuuint32_t, void*, const cuuint64_t*, const cuuint64_t*,
                             const cuuint32_t*, const cuuint32_t*, CUtensorMapInterleave, CUtensorMapSwizzle,
                             CUtensorMapL2promotion, CUtensorMapFloatOOBfill);

void make_map(EncodeFn enc, CUtensorMap* m, const void* ptr, int cols, int rows, int nb) {
  const cuuint64_t dims[3] = {(cuuint64_t)(nb ? 64 : cols), (cuuint64_t)rows, (cuuint64_t)cols / 64};
  const cuuint64_t strides[2] = {(cuuint64_t)cols * 2, 128};
  const cuuint32_t box[3] = {64, 32, (cuuint32_t)nb}, es[3] = {1, 1, 1};
  enc(m, CU_TENSOR_MAP_DATA_TYPE_BFLOAT16, nb ? 3 : 2, const_cast<void*>(ptr), dims, strides, box, es, CU_TENSOR_MAP_INTERLEAVE_NONE,
      CU_TENSOR_MAP_SWIZZLE_128B, CU_TENSOR_MAP_L2_PROMOTION_L2_128B, CU_TENSOR_MAP_FLOAT_OOB_FILL_NONE);
}
template <class... KA, class... A>
void launch(void (*kern)(KA...), int grid, int block, int smem, int cluster, bool pdl, A... args) {
  cudaFuncSetAttribute(kern, cudaFuncAttributeMaxDynamicSharedMemorySize, smem);
  cudaLaunchConfig_t cfg = {};
  cfg.gridDim = dim3(grid); cfg.blockDim = dim3(block); cfg.dynamicSmemBytes = smem; cfg.stream = cudaStreamPerThread;
  cudaLaunchAttribute at[2];
  int n = 0;
  if (cluster > 1) { at[n].id = cudaLaunchAttributeClusterDimension; at[n].val.clusterDim.x = cluster; at[n].val.clusterDim.y = 1; at[n].val.clusterDim.z = 1; n++; }
  if (pdl) { at[n].id = cudaLaunchAttributeProgrammaticStreamSerialization; at[n].val.programmaticStreamSerializationAllowed = 1; n++; }
  cfg.attrs = at; cfg.numAttrs = n;
  cudaLaunchKernelEx(&cfg, kern, args...);
}
template <class T> void* sym(T& s) { void* p = nullptr; cudaGetSymbolAddress(&p, s); return p; }

}

#define MODE(b) 0
extern "C" void kernel_launch(void* const* d_in, const int* in_sizes, int n_in, void* d_out, int out_size) {
  const __nv_bfloat16* x = (const __nv_bfloat16*)d_in[0];
  void* fn = nullptr; cudaDriverEntryPointQueryResult qr;
  cudaGetDriverEntryPoint("cuTensorMapEncodeTiled", &fn, cudaEnableDefault, &qr);
  EncodeFn enc = (EncodeFn)fn;

  ChainParams ch = {};
  PostParams op = {};
  for (int i = 0; i < 3; i++) {
    const cuuint64_t dims[3] = {HD, 128, 5}, strides[2] = {HD * 2, HD * 256};
    const cuuint32_t box[3] = {64, 128, 5}, es[3] = {1, 1, 1};
    enc(i == 0 ? &ch.wq : i == 1 ? &ch.wk : &ch.wv, CU_TENSOR_MAP_DATA_TYPE_BFLOAT16, 3, d_in[2 + i], dims, strides, box, es, CU_TENSOR_MAP_INTERLEAVE_NONE,
        CU_TENSOR_MAP_SWIZZLE_128B, W_PROMO, CU_TENSOR_MAP_FLOAT_OOB_FILL_NONE);
  }
  {
    const cuuint64_t dims[3] = {DM, HD, 7}, strides[2] = {DM * 2, 64};
    const cuuint32_t box[3] = {32, 64, 7}, es[3] = {1, 1, 1};
    enc(&ch.wo, CU_TENSOR_MAP_DATA_TYPE_BFLOAT16, 3, d_in[5], dims, strides, box, es, CU_TENSOR_MAP_INTERLEAVE_NONE,
        CU_TENSOR_MAP_SWIZZLE_64B, CU_TENSOR_MAP_L2_PROMOTION_L2_128B, CU_TENSOR_MAP_FLOAT_OOB_FILL_NONE);
  }
  ch.mem0 = (const __nv_bfloat16*)d_in[1];
  ch.pool = (uint8_t*)(((uintptr_t)sym(g_pool) + 8191) & ~(uintptr_t)8191); ch.kv = (uint8_t*)sym(g_kv); ch.xc = (const uint32_t*)sym(g_xc); ch.sync = (uint32_t*)sym(g_sync);
  ch.d1 = 0; ch.d1b = 0; ch.d2 = 0; ch.d2b = 0;
  make_map(enc, &op.wq, d_in[2], HD, DM, 3);
  make_map(enc, &op.wo, d_in[5], DM, HD, 5); make_map(enc, &op.wo2, d_in[5], DM, HD, 0);
  make_map(enc, &op.wb, d_in[8], 1920, DM, 5); make_map(enc, &op.wb2, d_in[8], 1920, DM, 0);
  op.gap = 17; op.share = 20; op.look = 14; op.gap2 = 0; op.pol = 0;

  const Weights wa = {{(const uint8_t*)d_in[3], (const uint8_t*)d_in[4], (const uint8_t*)d_in[2], (const uint8_t*)d_in[5]}}, none = {};
  launch(first_kernel, 132, 256, 128 * 1024, 1, false, x, (const uint4*)d_in[9], wa);
  for (int layer = 0; layer < 2; layer++) {
    ch.layer = ch.d2b = op.layer = layer;
    launch(chain_kernel, 96, 256, CH_SMEM, 3, true, ch);
    launch(post_kernel, MODE(3) ? 36 : 132, 384, OP_SMEM, 1, !MODE(1), op);
    const AbParams ab = {layer == 0 ? wa : none, (uint32_t*)sym(g_bo) + layer * 128, layer == 0 ? nullptr : (uint32_t*)d_out};
    launch(attn_b_kernel, 128, AB_T + 32, AB_SMEM, 1, true, ab);
  }
}
```

```cpp
#include <cuda_runtime.h>
#include <cuda_bf16.h>
#include <cuda.h>
#include <stdint.h>

namespace {

constexpr int SEQ = 2048, DM = 640, HD = 6144, NSEG = 64;
constexpr int SPIN_LIMIT = 1 << 20;

__device__ __align__(128) float4 g_x[SEQ * DM / 4];
__device__ __align__(128) uint32_t g_of[SEQ * DM / 2];
__device__ __align__(128) uint4 g_wb[DM * DM / 8];
__device__ __align__(16) float2 g_stat[16 * 8 * 128];
__device__ uint32_t g_bo[8 * 32];
__device__ __align__(128) uint4 g_q[SEQ * HD / 8];
__device__ __align__(128) uint32_t g_o[SEQ * HD / 2];
constexpr int KV_BYTES = 5120, KV_M = 4096, KV_V = NSEG * KV_BYTES;
__device__ __align__(128) uint8_t g_kv[96 * 2 * NSEG * KV_BYTES];
__device__ __align__(128) uint32_t g_xc[SEQ * DM / 2];
#define OP_B4 0
#define OP_B8 10
#define OP_B16 15
#define QA_END 12
__host__ __device__ constexpr int op_split(int b) { return b < OP_B4 ? 2 : b < OP_B8 ? 4 : b < OP_B16 ? 8 : 16; }
__host__ __device__ constexpr int fin_items(int b) { return b < OP_B8 ? 4 : op_split(b); }
#define AB_PF 2
#define AB_PF0 0
#define AB_PFD 6000
#define W_PROMO CU_TENSOR_MAP_L2_PROMOTION_L2_128B
#define OEF 0
#define BQ_HOLD 12
#define WEF 1
#define FK_PF 1
#define BQ_160 10
#define BQ_80 16
#define OP_160 16
__host__ __device__ constexpr int op_width(int b) { return b < OP_160 ? 320 : 160; }
__host__ __device__ constexpr int bq_width(int b) { return b < BQ_160 ? 320 : b < BQ_80 ? 160 : 80; }
__device__ __align__(128) uint2 g_part[16 * 16 * 16 * 40 * 32];
__device__ __align__(128) uint32_t g_xn[SEQ * DM / 2];
constexpr int SY_Q = 128, SY_T = 160, SY_QC = 192, SY_N = 193;
__device__ __align__(16) uint32_t g_sync[SY_N];
constexpr int NSLOT = 92;
__device__ uint32_t g_pool[(NSLOT + 2) * 2048];
__device__ int g_smpart[256], g_orient[NSLOT];
__device__ uint32_t g_smclk[256], g_smuse[256];
__device__ uint32_t g_bqkv[3 * 32 * 256 * 96];

#define ABT(L, i)
#define MODE_D(b) 0
#define DELAY(d)
#define XT(i)
#define MISS(k, n)
#define PRO(i)
#define TRACE(w)
#define ITEM(code, w)
#define TR(i, v)
#define TM(i)
#define TM1(i)
#define TMD(i, dep)
#define TMV(i, at, v)

__device__ __forceinline__ uint32_t gtime() { uint32_t c; asm volatile("mov.u32 %0, %%globaltimer_lo;" : "=r"(c) :: "memory"); return c; }
__device__ __forceinline__ uint32_t clk32() { uint32_t c; asm volatile("mov.u32 %0, %%clock;" : "=r"(c) :: "memory"); return c; }
__device__ __forceinline__ uint32_t s2u(const void* p) { return (uint32_t)__cvta_generic_to_shared(p); }
__device__ __forceinline__ uint32_t pack2(float a, float b) {
  uint32_t r; asm("cvt.rn.bf16x2.f32 %0, %1, %2;" : "=r"(r) : "f"(b), "f"(a)); return r; }
__device__ __forceinline__ float bf_lo(uint32_t w) { return __uint_as_float(w << 16); }
__device__ __forceinline__ float bf_hi(uint32_t w) { return __uint_as_float(w & 0xffff0000u); }
__device__ __forceinline__ float ex2(float x) { float y; asm("ex2.approx.ftz.f32 %0, %1;" : "=f"(y) : "f"(x)); return y; }

__device__ __forceinline__ void mbar_init(uint32_t bar, uint32_t n) {
  asm volatile("mbarrier.init.shared::cta.b64 [%0], %1;" :: "r"(bar), "r"(n) : "memory"); }
__device__ __forceinline__ void mbar_expect(uint32_t bar, uint32_t bytes) {
  asm volatile("mbarrier.arrive.expect_tx.shared::cta.b64 _, [%0], %1;" :: "r"(bar), "r"(bytes) : "memory"); }
__device__ __forceinline__ void mbar_arrive(uint32_t bar) {
  asm volatile("mbarrier.arrive.shared::cta.b64 _, [%0];" :: "r"(bar) : "memory"); }
__device__ __forceinline__ void mbar_wait(uint32_t bar, uint32_t ph) {
  asm volatile("{.reg .pred p; .reg .u32 n; mov.u32 n, 0;\n"
               "W: mbarrier.try_wait.parity.shared::cta.b64 p, [%0], %1; @p bra D;\n"
               "add.u32 n, n, 1; setp.gt.u32 p, n, %2; @p trap; bra W;\n"
               "D: }" :: "r"(bar), "r"(ph), "n"(SPIN_LIMIT) : "memory");
}
__device__ __forceinline__ void mbar_wait_cluster(uint32_t bar, uint32_t ph) {
  asm volatile("{.reg .pred p; .reg .u32 n; mov.u32 n, 0;\n"
               "W: mbarrier.try_wait.parity.acquire.cluster.shared::cta.b64 p, [%0], %1; @p bra D;\n"
               "add.u32 n, n, 1; setp.gt.u32 p, n, %2; @p trap; bra W;\n"
               "D: }" :: "r"(bar), "r"(ph), "n"(SPIN_LIMIT) : "memory");
}
__device__ __forceinline__ void spin_guard(int& n) {
  asm volatile("{.reg .pred p; add.s32 %0, %0, 1; setp.gt.s32 p, %0, %1; @p trap;}" : "+r"(n) : "n"(SPIN_LIMIT));
}
__device__ __forceinline__ void pdl_wait() { asm volatile("griddepcontrol.wait;" ::: "memory"); TRACE(1); }
__device__ __forceinline__ void pdl_launch() { asm volatile("griddepcontrol.launch_dependents;" ::: "memory"); }
__device__ __forceinline__ uint32_t ld_acquire(const uint32_t* p) { uint32_t v; asm volatile("ld.acquire.gpu.global.u32 %0, [%1];" : "=r"(v) : "l"(p) : "memory"); return v; }
__device__ __forceinline__ void red_release(uint32_t* p, uint32_t v) { asm volatile("red.release.gpu.global.add.u32 [%0], %1;" :: "l"(p), "r"(v) : "memory"); }
__device__ __forceinline__ void red_relaxed(uint32_t* p, uint32_t v) { asm volatile("red.relaxed.gpu.global.add.u32 [%0], %1;" :: "l"(p), "r"(v) : "memory"); }
__device__ __forceinline__ void fence_async_global() { asm volatile("fence.proxy.async.global;" ::: "memory"); }
__device__ __forceinline__ void fence_async() { asm volatile("fence.proxy.async.shared::cta;" ::: "memory"); }
__device__ __forceinline__ void bar_sync(int id, int n) { asm volatile("bar.sync %0, %1;" :: "r"(id), "r"(n) : "memory"); }
__device__ __forceinline__ void bar_arrive(int id, int n) { asm volatile("bar.arrive %0, %1;" :: "r"(id), "r"(n) : "memory"); }
__device__ __forceinline__ void tma_load(uint32_t dst, const CUtensorMap* m, int c0, int c1, uint32_t bar) {
  asm volatile("cp.async.bulk.tensor.2d.shared::cluster.global.mbarrier::complete_tx::bytes [%0], [%1, {%3, %4}], [%2];"
               :: "r"(dst), "l"(m), "r"(bar), "r"(c0), "r"(c1) : "memory"); }
template <bool STREAM = false>
__device__ __forceinline__ void tma_load3(uint32_t dst, const CUtensorMap* m, int c0, int c1, uint32_t bar) {
  if (STREAM)
    asm volatile("{.reg .b64 pol; createpolicy.fractional.L2::evict_first.b64 pol, 1.0;\n"
                 "cp.async.bulk.tensor.3d.shared::cluster.global.mbarrier::complete_tx::bytes.L2::cache_hint [%0], [%1, {%3, %4, 0}], [%2], pol;}"
                 :: "r"(dst), "l"(m), "r"(bar), "r"(c0), "r"(c1) : "memory");
  else
  asm volatile("cp.async.bulk.tensor.3d.shared::cluster.global.mbarrier::complete_tx::bytes [%0], [%1, {%3, %4, 0}], [%2];"
               :: "r"(dst), "l"(m), "r"(bar), "r"(c0), "r"(c1) : "memory"); }
__device__ __forceinline__ void tma_load3z(uint32_t dst, const CUtensorMap* m, int c1, int c2, uint32_t bar) {
  asm volatile("cp.async.bulk.tensor.3d.shared::cluster.global.mbarrier::complete_tx::bytes [%0], [%1, {0, %3, %4}], [%2];"
               :: "r"(dst), "l"(m), "r"(bar), "r"(c1), "r"(c2) : "memory"); }
__device__ __forceinline__ void tma_store(const CUtensorMap* m, uint32_t src, int c0, int c1) {
  asm volatile("cp.async.bulk.tensor.2d.global.shared::cta.bulk_group [%0, {%2, %3}], [%1];"
               :: "l"(m), "r"(src), "r"(c0), "r"(c1) : "memory"); }
__device__ __forceinline__ void tma_store_stream(const CUtensorMap* m, uint32_t src, int c0, int c1) {
  asm volatile("{.reg .b64 pol; createpolicy.fractional.L2::evict_first.b64 pol, 1.0;\n"
               "cp.async.bulk.tensor.2d.global.shared::cta.bulk_group.L2::cache_hint [%0, {%2, %3}], [%1], pol;}"
               :: "l"(m), "r"(src), "r"(c0), "r"(c1) : "memory"); }
__device__ __forceinline__ void bulk_load(uint32_t dst, const void* src, uint32_t bytes, uint32_t bar) {
  asm volatile("cp.async.bulk.shared::cluster.global.mbarrier::complete_tx::bytes [%0], [%1], %2, [%3];"
               :: "r"(dst), "l"(src), "r"(bytes), "r"(bar) : "memory"); }
__device__ __forceinline__ void bulk_load_last(uint32_t dst, const void* src, uint32_t bytes, uint32_t bar) {
  asm volatile("{.reg .b64 pol; createpolicy.fractional.L2::evict_first.b64 pol, 1.0;\n"
               "cp.async.bulk.shared::cluster.global.mbarrier::complete_tx::bytes.L2::cache_hint [%0], [%1], %2, [%3], pol;}"
               :: "r"(dst), "l"(src), "r"(bytes), "r"(bar) : "memory"); }
__device__ __forceinline__ void tma_load_last(uint32_t dst, const CUtensorMap* m, int c0, int c1, uint32_t bar) {
  asm volatile("{.reg .b64 pol; createpolicy.fractional.L2::evict_first.b64 pol, 1.0;\n"
               "cp.async.bulk.tensor.2d.shared::cluster.global.mbarrier::complete_tx::bytes.L2::cache_hint [%0], [%1, {%3, %4}], [%2], pol;}"
               :: "r"(dst), "l"(m), "r"(bar), "r"(c0), "r"(c1) : "memory"); }
__device__ __forceinline__ void bulk_send(uint32_t dst, uint32_t src, uint32_t bytes, uint32_t bar) {
  asm volatile("cp.async.bulk.shared::cluster.shared::cta.mbarrier::complete_tx::bytes [%0], [%1], %2, [%3];"
               :: "r"(dst), "r"(src), "r"(bytes), "r"(bar) : "memory"); }
__device__ __forceinline__ void bulk_store(void* dst, uint32_t src, uint32_t bytes) {
  asm volatile("cp.async.bulk.global.shared::cta.bulk_group [%0], [%1], %2;" :: "l"(dst), "r"(src), "r"(bytes) : "memory"); }
__device__ __forceinline__ void bulk_commit() { asm volatile("cp.async.bulk.commit_group;" ::: "memory"); }
template <int N> __device__ __forceinline__ void bulk_wait_read() { asm volatile("cp.async.bulk.wait_group.read %0;" :: "n"(N) : "memory"); }
template <int N> __device__ __forceinline__ void bulk_wait() { asm volatile("cp.async.bulk.wait_group %0;" :: "n"(N) : "memory"); }

__device__ __forceinline__ uint64_t mkdesc(uint32_t addr, uint32_t lbo, uint32_t sbo, uint32_t sw) {
  return (uint64_t)((addr & 0x3FFFF) >> 4) | ((uint64_t)(lbo >> 4) << 16) | ((uint64_t)(sbo >> 4) << 32) | ((uint64_t)sw << 62); }
__device__ __forceinline__ void wg_fence() { asm volatile("wgmma.fence.sync.aligned;" ::: "memory"); }
__device__ __forceinline__ void wg_commit() { asm volatile("wgmma.commit_group.sync.aligned;" ::: "memory"); }
template <int N> __device__ __forceinline__ void wg_wait() { asm volatile("wgmma.wait_group.sync.aligned %0;" :: "n"(N) : "memory"); }
template <int N> __device__ __forceinline__ void reg_fence(float* d) {
#pragma unroll
  for (int i = 0; i < N; i++) asm volatile("" : "+f"(d[i]) :: "memory");
}

__device__ __forceinline__ void mma16(float* d, uint32_t a0, uint32_t a1, uint32_t a2, uint32_t a3, uint32_t b0, uint32_t b1) {
  asm volatile("mma.sync.aligned.m16n8k16.row.col.f32.bf16.bf16.f32 {%0,%1,%2,%3},{%4,%5,%6,%7},{%8,%9},{%0,%1,%2,%3};"
               : "+f"(d[0]), "+f"(d[1]), "+f"(d[2]), "+f"(d[3]) : "r"(a0), "r"(a1), "r"(a2), "r"(a3), "r"(b0), "r"(b1)); }
__device__ __forceinline__ void mma8(float* d, uint32_t a0, uint32_t a1, uint32_t b0) {
  asm volatile("mma.sync.aligned.m16n8k8.row.col.f32.bf16.bf16.f32 {%0,%1,%2,%3},{%4,%5},{%6},{%0,%1,%2,%3};"
               : "+f"(d[0]), "+f"(d[1]), "+f"(d[2]), "+f"(d[3]) : "r"(a0), "r"(a1), "r"(b0)); }
__device__ __forceinline__ void ldsm4(uint32_t* r, uint32_t a) {
  asm volatile("ldmatrix.sync.aligned.m8n8.x4.shared.b16 {%0,%1,%2,%3},[%4];" : "=r"(r[0]), "=r"(r[1]), "=r"(r[2]), "=r"(r[3]) : "r"(a) : "memory"); }
__device__ __forceinline__ void ldsm4t(uint32_t* r, uint32_t a) {
  asm volatile("ldmatrix.sync.aligned.m8n8.x4.trans.shared.b16 {%0,%1,%2,%3},[%4];" : "=r"(r[0]), "=r"(r[1]), "=r"(r[2]), "=r"(r[3]) : "r"(a) : "memory"); }
__device__ __forceinline__ void ldsm2(uint32_t* r, uint32_t a) {
  asm volatile("ldmatrix.sync.aligned.m8n8.x2.shared.b16 {%0,%1},[%2];" : "=r"(r[0]), "=r"(r[1]) : "r"(a) : "memory"); }
__device__ __forceinline__ void stsm4(uint32_t a, uint32_t r0, uint32_t r1, uint32_t r2, uint32_t r3) {
  asm volatile("stmatrix.sync.aligned.m8n8.x4.shared.b16 [%0], {%1,%2,%3,%4};" :: "r"(a), "r"(r0), "r"(r1), "r"(r2), "r"(r3) : "memory"); }
__device__ __forceinline__ void stsm2t(uint32_t a, uint32_t r0, uint32_t r1) {
  asm volatile("stmatrix.sync.aligned.m8n8.x2.trans.shared.b16 [%0], {%1,%2};" :: "r"(a), "r"(r0), "r"(r1) : "memory"); }
__device__ __forceinline__ void stsm4t(uint32_t a, uint32_t r0, uint32_t r1, uint32_t r2, uint32_t r3) {
  asm volatile("stmatrix.sync.aligned.m8n8.x4.trans.shared.b16 [%0], {%1,%2,%3,%4};" :: "r"(a), "r"(r0), "r"(r1), "r"(r2), "r"(r3) : "memory"); }
__device__ __forceinline__ void st_async128(uint32_t a, uint4 v, uint32_t bar) {
  asm volatile("st.async.shared::cluster.mbarrier::complete_tx::bytes.v4.b32 [%0], {%1,%2,%3,%4}, [%5];" :: "r"(a), "r"(v.x), "r"(v.y), "r"(v.z), "r"(v.w), "r"(bar) : "memory"); }
__device__ __forceinline__ void sts32(uint32_t a, uint32_t v) { asm volatile("st.shared.b32 [%0], %1;" :: "r"(a), "r"(v) : "memory"); }
__device__ __forceinline__ void sts64f(uint32_t a, float x, float y) { asm volatile("st.shared.v2.f32 [%0], {%1,%2};" :: "r"(a), "f"(x), "f"(y) : "memory"); }
__device__ __forceinline__ void sts128(uint32_t a, uint4 v) {
  asm volatile("st.shared.v4.b32 [%0], {%1,%2,%3,%4};" :: "r"(a), "r"(v.x), "r"(v.y), "r"(v.z), "r"(v.w) : "memory"); }
__device__ __forceinline__ void sts128f(uint32_t a, float x, float y, float z, float w) {
  asm volatile("st.shared.v4.f32 [%0], {%1,%2,%3,%4};" :: "r"(a), "f"(x), "f"(y), "f"(z), "f"(w) : "memory"); }
__device__ __forceinline__ float lds32f(uint32_t a) { float v; asm volatile("ld.shared.f32 %0, [%1];" : "=f"(v) : "r"(a) : "memory"); return v; }
__device__ __forceinline__ float2 lds64f(uint32_t a) { float2 v; asm volatile("ld.shared.v2.f32 {%0,%1}, [%2];" : "=f"(v.x), "=f"(v.y) : "r"(a) : "memory"); return v; }
__device__ __forceinline__ float4 lds128f(uint32_t a) {
  float4 v; asm volatile("ld.shared.v4.f32 {%0,%1,%2,%3}, [%4];" : "=f"(v.x), "=f"(v.y), "=f"(v.z), "=f"(v.w) : "r"(a) : "memory"); return v; }
__device__ __forceinline__ uint4 lds128(uint32_t a) {
  uint4 v; asm volatile("ld.shared.v4.b32 {%0,%1,%2,%3}, [%4];" : "=r"(v.x), "=r"(v.y), "=r"(v.z), "=r"(v.w) : "r"(a) : "memory"); return v; }
__device__ __forceinline__ uint4 ldg_strong128(const void* p) {
  uint4 v; asm volatile("ld.relaxed.gpu.global.v4.u32 {%0,%1,%2,%3}, [%4];" : "=r"(v.x), "=r"(v.y), "=r"(v.z), "=r"(v.w) : "l"(p) : "memory"); return v; }
__device__ __forceinline__ void stg_strong32(void* p, uint32_t v) { asm volatile("st.relaxed.gpu.global.u32 [%0], %1;" :: "l"(p), "r"(v) : "memory"); }
__device__ __forceinline__ void stg_strong16(void* p, uint32_t v) { asm volatile("st.relaxed.gpu.global.u16 [%0], %1;" :: "l"(p), "h"((uint16_t)v) : "memory"); }
__device__ __forceinline__ void stg_strong128(void* p, uint4 v) {
  asm volatile("st.relaxed.gpu.global.v4.u32 [%0], {%1,%2,%3,%4};" :: "l"(p), "r"(v.x), "r"(v.y), "r"(v.z), "r"(v.w) : "memory"); }
__device__ __forceinline__ uint32_t mapa(uint32_t a, uint32_t r) {
  uint32_t o; asm("mapa.shared::cluster.u32 %0, %1, %2;" : "=r"(o) : "r"(a), "r"(r)); return o; }
__device__ __forceinline__ void st_async2f(uint32_t a, float x, float y, uint32_t bar) {
  asm volatile("st.async.shared::cluster.mbarrier::complete_tx::bytes.v2.f32 [%0], {%1,%2}, [%3];" :: "r"(a), "f"(x), "f"(y), "r"(bar) : "memory"); }
__device__ __forceinline__ void st_async32(uint32_t a, uint32_t x, uint32_t bar) {
  asm volatile("st.async.shared::cluster.mbarrier::complete_tx::bytes.b32 [%0], %1, [%2];" :: "r"(a), "r"(x), "r"(bar) : "memory"); }
__device__ __forceinline__ uint32_t lds32(uint32_t a) { uint32_t v; asm volatile("ld.shared.b32 %0, [%1];" : "=r"(v) : "r"(a) : "memory"); return v; }
__device__ __forceinline__ void st_async64(uint32_t a, uint32_t x, uint32_t y, uint32_t bar) {
  asm volatile("st.async.shared::cluster.mbarrier::complete_tx::bytes.v2.b32 [%0], {%1,%2}, [%3];" :: "r"(a), "r"(x), "r"(y), "r"(bar) : "memory"); }
__device__ __forceinline__ uint2 lds64(uint32_t a) { uint2 v; asm volatile("ld.shared.v2.b32 {%0,%1}, [%2];" : "=r"(v.x), "=r"(v.y) : "r"(a) : "memory"); return v; }
__device__ __forceinline__ void sts64(uint32_t a, uint32_t x, uint32_t y) { asm volatile("st.shared.v2.b32 [%0], {%1,%2};" :: "r"(a), "r"(x), "r"(y) : "memory"); }
__device__ __forceinline__ uint32_t ldg_strong32(const void* p) { uint32_t v; asm volatile("ld.relaxed.gpu.global.u32 %0, [%1];" : "=r"(v) : "l"(p) : "memory"); return v; }
__device__ __forceinline__ uint32_t transpose8(uint32_t x) { uint32_t r; asm volatile("movmatrix.sync.aligned.m8n8.trans.b16 %0, %1;" : "=r"(r) : "r"(x)); return r; }
__device__ __forceinline__ uint32_t hadd2(uint32_t a, uint32_t b) { uint32_t r; asm("add.rn.bf16x2 %0, %1, %2;" : "=r"(r) : "r"(a), "r"(b)); return r; }
__device__ __forceinline__ uint32_t min4(uint4 v) { return min(__vimin3_u32(v.x, v.y, v.z), v.w); }

__device__ __forceinline__ void wg_ss192_01(float* d, uint64_t da, uint64_t db, int sd) {
  asm volatile("{.reg .pred p; setp.ne.b32 p, %98, 0;\n"
    "wgmma.mma_async.sync.aligned.m64n192k16.f32.bf16.bf16 {%0,%1,%2,%3,%4,%5,%6,%7,%8,%9,%10,%11,%12,%13,%14,%15,%16,%17,%18,%19,%20,%21,%22,%23,%24,%25,%26,%27,%28,%29,%30,%31,%32,%33,%34,%35,%36,%37,%38,%39,%40,%41,%42,%43,%44,%45,%46,%47,%48,%49,%50,%51,%52,%53,%54,%55,%56,%57,%58,%59,%60,%61,%62,%63,%64,%65,%66,%67,%68,%69,%70,%71,%72,%73,%74,%75,%76,%77,%78,%79,%80,%81,%82,%83,%84,%85,%86,%87,%88,%89,%90,%91,%92,%93,%94,%95}, %96, %97, p, 1, 1, 0, 1;}"
    : "+f"(d[0]),"+f"(d[1]),"+f"(d[2]),"+f"(d[3]),"+f"(d[4]),"+f"(d[5]),"+f"(d[6]),"+f"(d[7]),"+f"(d[8]),"+f"(d[9]),"+f"(d[10]),"+f"(d[11]),"+f"(d[12]),"+f"(d[13]),"+f"(d[14]),"+f"(d[15]),"+f"(d[16]),"+f"(d[17]),"+f"(d[18]),"+f"(d[19]),"+f"(d[20]),"+f"(d[21]),"+f"(d[22]),"+f"(d[23]),"+f"(d[24]),"+f"(d[25]),"+f"(d[26]),"+f"(d[27]),"+f"(d[28]),"+f"(d[29]),"+f"(d[30]),"+f"(d[31]),"+f"(d[32]),"+f"(d[33]),"+f"(d[34]),"+f"(d[35]),"+f"(d[36]),"+f"(d[37]),"+f"(d[38]),"+f"(d[39]),"+f"(d[40]),"+f"(d[41]),"+f"(d[42]),"+f"(d[43]),"+f"(d[44]),"+f"(d[45]),"+f"(d[46]),"+f"(d[47]),"+f"(d[48]),"+f"(d[49]),"+f"(d[50]),"+f"(d[51]),"+f"(d[52]),"+f"(d[53]),"+f"(d[54]),"+f"(d[55]),"+f"(d[56]),"+f"(d[57]),"+f"(d[58]),"+f"(d[59]),"+f"(d[60]),"+f"(d[61]),"+f"(d[62]),"+f"(d[63]),"+f"(d[64]),"+f"(d[65]),"+f"(d[66]),"+f"(d[67]),"+f"(d[68]),"+f"(d[69]),"+f"(d[70]),"+f"(d[71]),"+f"(d[72]),"+f"(d[73]),"+f"(d[74]),"+f"(d[75]),"+f"(d[76]),"+f"(d[77]),"+f"(d[78]),"+f"(d[79]),"+f"(d[80]),"+f"(d[81]),"+f"(d[82]),"+f"(d[83]),"+f"(d[84]),"+f"(d[85]),"+f"(d[86]),"+f"(d[87]),"+f"(d[88]),"+f"(d[89]),"+f"(d[90]),"+f"(d[91]),"+f"(d[92]),"+f"(d[93]),"+f"(d[94]),"+f"(d[95])
    : "l"(da), "l"(db), "r"(sd));
}
__device__ __forceinline__ void wg_ss128_01(float* d, uint64_t da, uint64_t db, int sd) {
  asm volatile("{.reg .pred p; setp.ne.b32 p, %66, 0;\n"
    "wgmma.mma_async.sync.aligned.m64n128k16.f32.bf16.bf16 {%0,%1,%2,%3,%4,%5,%6,%7,%8,%9,%10,%11,%12,%13,%14,%15,%16,%17,%18,%19,%20,%21,%22,%23,%24,%25,%26,%27,%28,%29,%30,%31,%32,%33,%34,%35,%36,%37,%38,%39,%40,%41,%42,%43,%44,%45,%46,%47,%48,%49,%50,%51,%52,%53,%54,%55,%56,%57,%58,%59,%60,%61,%62,%63}, %64, %65, p, 1, 1, 0, 1;}"
    : "+f"(d[0]),"+f"(d[1]),"+f"(d[2]),"+f"(d[3]),"+f"(d[4]),"+f"(d[5]),"+f"(d[6]),"+f"(d[7]),"+f"(d[8]),"+f"(d[9]),"+f"(d[10]),"+f"(d[11]),"+f"(d[12]),"+f"(d[13]),"+f"(d[14]),"+f"(d[15]),"+f"(d[16]),"+f"(d[17]),"+f"(d[18]),"+f"(d[19]),"+f"(d[20]),"+f"(d[21]),"+f"(d[22]),"+f"(d[23]),"+f"(d[24]),"+f"(d[25]),"+f"(d[26]),"+f"(d[27]),"+f"(d[28]),"+f"(d[29]),"+f"(d[30]),"+f"(d[31]),"+f"(d[32]),"+f"(d[33]),"+f"(d[34]),"+f"(d[35]),"+f"(d[36]),"+f"(d[37]),"+f"(d[38]),"+f"(d[39]),"+f"(d[40]),"+f"(d[41]),"+f"(d[42]),"+f"(d[43]),"+f"(d[44]),"+f"(d[45]),"+f"(d[46]),"+f"(d[47]),"+f"(d[48]),"+f"(d[49]),"+f"(d[50]),"+f"(d[51]),"+f"(d[52]),"+f"(d[53]),"+f"(d[54]),"+f"(d[55]),"+f"(d[56]),"+f"(d[57]),"+f"(d[58]),"+f"(d[59]),"+f"(d[60]),"+f"(d[61]),"+f"(d[62]),"+f"(d[63])
    : "l"(da), "l"(db), "r"(sd));
}
__device__ __forceinline__ void wg_ss160_01(float* d, uint64_t da, uint64_t db, int sd) {
  asm volatile("{.reg .pred p; setp.ne.b32 p, %82, 0;\n"
    "wgmma.mma_async.sync.aligned.m64n160k16.f32.bf16.bf16 {%0,%1,%2,%3,%4,%5,%6,%7,%8,%9,%10,%11,%12,%13,%14,%15,%16,%17,%18,%19,%20,%21,%22,%23,%24,%25,%26,%27,%28,%29,%30,%31,%32,%33,%34,%35,%36,%37,%38,%39,%40,%41,%42,%43,%44,%45,%46,%47,%48,%49,%50,%51,%52,%53,%54,%55,%56,%57,%58,%59,%60,%61,%62,%63,%64,%65,%66,%67,%68,%69,%70,%71,%72,%73,%74,%75,%76,%77,%78,%79}, %80, %81, p, 1, 1, 0, 1;}"
    : "+f"(d[0]),"+f"(d[1]),"+f"(d[2]),"+f"(d[3]),"+f"(d[4]),"+f"(d[5]),"+f"(d[6]),"+f"(d[7]),"+f"(d[8]),"+f"(d[9]),"+f"(d[10]),"+f"(d[11]),"+f"(d[12]),"+f"(d[13]),"+f"(d[14]),"+f"(d[15]),"+f"(d[16]),"+f"(d[17]),"+f"(d[18]),"+f"(d[19]),"+f"(d[20]),"+f"(d[21]),"+f"(d[22]),"+f"(d[23]),"+f"(d[24]),"+f"(d[25]),"+f"(d[26]),"+f"(d[27]),"+f"(d[28]),"+f"(d[29]),"+f"(d[30]),"+f"(d[31]),"+f"(d[32]),"+f"(d[33]),"+f"(d[34]),"+f"(d[35]),"+f"(d[36]),"+f"(d[37]),"+f"(d[38]),"+f"(d[39]),"+f"(d[40]),"+f"(d[41]),"+f"(d[42]),"+f"(d[43]),"+f"(d[44]),"+f"(d[45]),"+f"(d[46]),"+f"(d[47]),"+f"(d[48]),"+f"(d[49]),"+f"(d[50]),"+f"(d[51]),"+f"(d[52]),"+f"(d[53]),"+f"(d[54]),"+f"(d[55]),"+f"(d[56]),"+f"(d[57]),"+f"(d[58]),"+f"(d[59]),"+f"(d[60]),"+f"(d[61]),"+f"(d[62]),"+f"(d[63]),"+f"(d[64]),"+f"(d[65]),"+f"(d[66]),"+f"(d[67]),"+f"(d[68]),"+f"(d[69]),"+f"(d[70]),"+f"(d[71]),"+f"(d[72]),"+f"(d[73]),"+f"(d[74]),"+f"(d[75]),"+f"(d[76]),"+f"(d[77]),"+f"(d[78]),"+f"(d[79])
    : "l"(da), "l"(db), "r"(sd));
}
__device__ __forceinline__ void wg_ss80_01(float* d, uint64_t da, uint64_t db, int sd) {
  asm volatile("{.reg .pred p; setp.ne.b32 p, %42, 0;\n"
    "wgmma.mma_async.sync.aligned.m64n80k16.f32.bf16.bf16 {%0,%1,%2,%3,%4,%5,%6,%7,%8,%9,%10,%11,%12,%13,%14,%15,%16,%17,%18,%19,%20,%21,%22,%23,%24,%25,%26,%27,%28,%29,%30,%31,%32,%33,%34,%35,%36,%37,%38,%39}, %40, %41, p, 1, 1, 0, 1;}"
    : "+f"(d[0]),"+f"(d[1]),"+f"(d[2]),"+f"(d[3]),"+f"(d[4]),"+f"(d[5]),"+f"(d[6]),"+f"(d[7]),"+f"(d[8]),"+f"(d[9]),"+f"(d[10]),"+f"(d[11]),"+f"(d[12]),"+f"(d[13]),"+f"(d[14]),"+f"(d[15]),"+f"(d[16]),"+f"(d[17]),"+f"(d[18]),"+f"(d[19]),"+f"(d[20]),"+f"(d[21]),"+f"(d[22]),"+f"(d[23]),"+f"(d[24]),"+f"(d[25]),"+f"(d[26]),"+f"(d[27]),"+f"(d[28]),"+f"(d[29]),"+f"(d[30]),"+f"(d[31]),"+f"(d[32]),"+f"(d[33]),"+f"(d[34]),"+f"(d[35]),"+f"(d[36]),"+f"(d[37]),"+f"(d[38]),"+f"(d[39])
    : "l"(da), "l"(db), "r"(sd));
}
__device__ __forceinline__ void wg_rs32_00(float* d, uint32_t a0, uint32_t a1, uint32_t a2, uint32_t a3, uint64_t db, int sd) {
  asm volatile("{.reg .pred p; setp.ne.b32 p, %21, 0;\n"
    "wgmma.mma_async.sync.aligned.m64n32k16.f32.bf16.bf16 {%0,%1,%2,%3,%4,%5,%6,%7,%8,%9,%10,%11,%12,%13,%14,%15}, {%16,%17,%18,%19}, %20, p, 1, 1, 0;}"
    : "+f"(d[0]),"+f"(d[1]),"+f"(d[2]),"+f"(d[3]),"+f"(d[4]),"+f"(d[5]),"+f"(d[6]),"+f"(d[7]),"+f"(d[8]),"+f"(d[9]),"+f"(d[10]),"+f"(d[11]),"+f"(d[12]),"+f"(d[13]),"+f"(d[14]),"+f"(d[15])
    : "r"(a0), "r"(a1), "r"(a2), "r"(a3), "l"(db), "r"(sd));
}
__device__ __forceinline__ void wg_rs64_00(float* d, uint32_t a0, uint32_t a1, uint32_t a2, uint32_t a3, uint64_t db, int sd) {
  asm volatile("{.reg .pred p; setp.ne.b32 p, %37, 0;\n"
    "wgmma.mma_async.sync.aligned.m64n64k16.f32.bf16.bf16 {%0,%1,%2,%3,%4,%5,%6,%7,%8,%9,%10,%11,%12,%13,%14,%15,%16,%17,%18,%19,%20,%21,%22,%23,%24,%25,%26,%27,%28,%29,%30,%31}, {%32,%33,%34,%35}, %36, p, 1, 1, 0;}"
    : "+f"(d[0]),"+f"(d[1]),"+f"(d[2]),"+f"(d[3]),"+f"(d[4]),"+f"(d[5]),"+f"(d[6]),"+f"(d[7]),"+f"(d[8]),"+f"(d[9]),"+f"(d[10]),"+f"(d[11]),"+f"(d[12]),"+f"(d[13]),"+f"(d[14]),"+f"(d[15]),"+f"(d[16]),"+f"(d[17]),"+f"(d[18]),"+f"(d[19]),"+f"(d[20]),"+f"(d[21]),"+f"(d[22]),"+f"(d[23]),"+f"(d[24]),"+f"(d[25]),"+f"(d[26]),"+f"(d[27]),"+f"(d[28]),"+f"(d[29]),"+f"(d[30]),"+f"(d[31])
    : "r"(a0), "r"(a1), "r"(a2), "r"(a3), "l"(db), "r"(sd));
}
__device__ __forceinline__ void wg_rs24_01(float* d, uint32_t a0, uint32_t a1, uint32_t a2, uint32_t a3, uint64_t db, int sd) {
  asm volatile("{.reg .pred p; setp.ne.b32 p, %17, 0;\n"
    "wgmma.mma_async.sync.aligned.m64n24k16.f32.bf16.bf16 {%0,%1,%2,%3,%4,%5,%6,%7,%8,%9,%10,%11}, {%12,%13,%14,%15}, %16, p, 1, 1, 1;}"
    : "+f"(d[0]),"+f"(d[1]),"+f"(d[2]),"+f"(d[3]),"+f"(d[4]),"+f"(d[5]),"+f"(d[6]),"+f"(d[7]),"+f"(d[8]),"+f"(d[9]),"+f"(d[10]),"+f"(d[11])
    : "r"(a0), "r"(a1), "r"(a2), "r"(a3), "l"(db), "r"(sd));
}

#define AB_POLY 0xaa
#define AB_DEG 3
__device__ __forceinline__ constexpr bool poly_group(int group) { return (AB_POLY >> (group & 7)) & 1; }

template <int V> struct Int { static constexpr int value = V; };

template <int NG>
__device__ __forceinline__ void ln_stats(const float4 (&v)[NG][5], uint32_t scratch, float (&mean)[NG], float (&rs)[NG]) {
  const int warp = threadIdx.x >> 5, lane = threadIdx.x & 31;
#pragma unroll
  for (int r = 0; r < NG; r++) {
    float s = 0.f, q = 0.f;
#pragma unroll
    for (int i = 0; i < 5; i++) s += (v[r][i].x + v[r][i].y) + (v[r][i].z + v[r][i].w);
    s += __shfl_xor_sync(~0u, s, 1); s += __shfl_xor_sync(~0u, s, 2);
    s *= 1.f / 80;
#pragma unroll
    for (int i = 0; i < 5; i++) {
      const float x = v[r][i].x - s, y = v[r][i].y - s, z = v[r][i].z - s, w = v[r][i].w - s;
      q += (x * x + y * y) + (z * z + w * w);
    }
    q += __shfl_xor_sync(~0u, q, 1); q += __shfl_xor_sync(~0u, q, 2);
    mean[r] = s; rs[r] = q;
  }
  bar_sync(1, 256);
  if ((lane & 3) == 0) {
#pragma unroll
    for (int r = 0; r < NG; r++) sts64f(scratch + r * 512 + lane * 16 + warp * 8, mean[r], rs[r]);
  }
  bar_sync(1, 256);
#pragma unroll
  for (int r = 0; r < NG; r++) {
    const float4 e = lds128f(scratch + r * 512 + lane * 16);
    float t = e.x + e.z;
    t += __shfl_xor_sync(~0u, t, 1); t += __shfl_xor_sync(~0u, t, 2);
    t *= 0.125f;
    float q = e.y + e.w + 80.f * ((e.x - t) * (e.x - t) + (e.z - t) * (e.z - t));
    q += __shfl_xor_sync(~0u, q, 1); q += __shfl_xor_sync(~0u, q, 2);
    mean[r] = t; rs[r] = rsqrtf(q * (1.f / DM) + 1e-5f);
  }
}

__device__ __forceinline__ void ln_store(const uint32_t (&w)[2][5][2], int tile, int u0, bool live = true) {
  const int lane = threadIdx.x & 31;
  uint32_t* xc = g_xc + ((tile >> 1) * 40 + u0) * 256 + (tile & 1) * 64 + lane;
#pragma unroll
  for (int i = 0; i < 20; i++) if (live) xc[(i >> 1) * 128 + (i & 1) * 32] = w[i & 1][i >> 2][i >> 1 & 1];
#pragma unroll
  for (int i = 0; i < 5; i++) {
    const int u = u0 + i;
    uint32_t* xn = g_xn + (((tile >> 3) * 20 + (u >> 1)) * 16 + (tile & 1) * 8 + (tile & 6)) * 128 + (u & 1) * 64 + lane;
#pragma unroll
    for (int r = 0; r < 2; r++) if (live) { xn[r * 128] = w[r][i][0]; xn[r * 128 + 32] = w[r][i][1]; }
  }
}
__device__ __forceinline__ void wait_count(const uint32_t* c, uint32_t n) {
  int spin = 0;
  while ((ld_acquire(c) & 0xffff) < n) { __nanosleep(32); spin_guard(spin); }
}

__device__ __forceinline__ uint8_t* pool_at(uint32_t off) {
  return reinterpret_cast<uint8_t*>((reinterpret_cast<uintptr_t>(g_pool) + 8191) & ~(uintptr_t)8191) + off; }
struct Weights { const uint8_t* w[4]; };
__device__ __forceinline__ void prefetch_weights(const Weights& p, int i) {
  if (blockIdx.x < 128) asm volatile("cp.async.bulk.prefetch.L2.global [%0], 61440;" :: "l"(p.w[i] + (size_t)blockIdx.x * 61440) : "memory");
}
__global__ void __launch_bounds__(256) first_kernel(const __nv_bfloat16* __restrict__ xin, const uint4* __restrict__ wb, const __grid_constant__ Weights wa) {
  __shared__ __align__(16) float scratch[256];
  __shared__ uint32_t lat[4];
  const int warp = threadIdx.x >> 5, lane = threadIdx.x & 31, cta = blockIdx.x;
  TRACE(0);
  pdl_launch();
  if (warp < 4 && (warp < 2 || cta < NSLOT)) {
    uint32_t* q = reinterpret_cast<uint32_t*>(pool_at((warp < 2 ? NSLOT : cta) * 8192 + (warp & 1) * 4096)) + (warp < 2 ? (cta & 127) * 8 : 0);
    if (lane < 8) stg_strong32(q + lane, 0u);
    uint32_t best = ~0u;
    if (lane == 0)
      for (int r = 0; r < 4; r++) {
        uint32_t t0, t1, v;
        asm volatile("mov.u32 %0, %%clock;" : "=r"(t0) :: "memory");
        asm volatile("atom.relaxed.gpu.global.exch.b32 %0, [%1], 0;" : "=r"(v) : "l"(q) : "memory");
        asm volatile("{.reg .u32 t; add.u32 t, %1, 1; mov.u32 %0, %%clock; sub.u32 %0, %0, %1;}" : "=r"(t1) : "r"(__shfl_sync(1u, v, 0)) : "memory");
        best = min(best, t1 - t0);
      }
    if (lane == 0) lat[warp] = best;
  }
  __syncthreads();
  ABT(2, 0);
  if (threadIdx.x == 0) {
    const int part = lat[0] < lat[1] ? 0 : 1;
    uint32_t smid; asm("mov.u32 %0, %%smid;" : "=r"(smid));
    g_smpart[smid & 255] = part;
    g_smclk[smid & 255] = clk32() - gtime() * 2;
    g_smuse[smid & 255] = 0;
    if (cta < NSLOT) g_orient[cta] = lat[2] < lat[3] ? part : 1 - part;
  }
  if (cta < 128) {
    float4 v[2][5];
#pragma unroll
    for (int r = 0; r < 2; r++)
#pragma unroll
      for (int i = 0; i < 5; i++) {
        const uint32_t* src = reinterpret_cast<const uint32_t*>(xin) + (cta * 16 + r * 8 + (lane >> 2)) * (DM / 2) + warp * 40 + i * 8 + (lane & 3);
        const uint32_t a = src[0], b = src[4];
        v[r][i] = make_float4(bf_lo(a), bf_hi(a), bf_lo(b), bf_hi(b));
      }
    uint4 w8[2];
#pragma unroll
    for (int i = 0; i < 2; i++) w8[i] = wb[cta * 400 + min(i * 256 + threadIdx.x, 399)];
    if (threadIdx.x < 128) g_stat[cta * 128 + threadIdx.x] = make_float2(0.f, 0.f);
#pragma unroll
    for (int i = 0; i < 10; i++) g_x[((cta * 2 + i / 5) * 40 + warp * 5 + i % 5) * 32 + lane] = v[i / 5][i % 5];
    ABT(2, 1);
    if (threadIdx.x == 32) for (int i = 0; i < FK_PF; i++) prefetch_weights(wa, i);
    float mean[2], rs[2];
    ln_stats<2>(v, s2u(scratch), mean, rs);
    ABT(2, 2);
    uint32_t w[2][5][2];
#pragma unroll
    for (int i = 0; i < 10; i++) {
      const float4 t = v[i / 5][i % 5];
      const float m = mean[i / 5], q = rs[i / 5];
      w[i / 5][i % 5][0] = pack2((t.x - m) * q, (t.y - m) * q); w[i / 5][i % 5][1] = pack2((t.z - m) * q, (t.w - m) * q);
    }
    ln_store(w, cta, warp * 5);
    ABT(2, 3);
#pragma unroll
    for (int i = 0; i < 2; i++) {
      const int e = cta * 400 + min(i * 256 + threadIdx.x, 399), k = e / 80, n = e - k * 80, cg = n / 10;
      g_wb[((cg * 80 + (k >> 3)) * 10 + n - cg * 10) * 8 + (k & 7)] = w8[i];
    }
  } else if (cta == 128) {
    g_bo[threadIdx.x] = 0;
  }
  TRACE(2);
}

struct ChainParams {
  CUtensorMap wq, wk, wv, wo;
  const __nv_bfloat16* mem0;
  uint8_t *pool, *kv;
  const uint32_t* xc;
  uint32_t* sync;
  int layer;
  int d0, d3, d1, d1b, d2, d2b, mode;
};
constexpr int CH_WQ = 0, CH_WO = 81920, CH_X = CH_WO + 86016, CH_M = CH_X + 20480, CH_KT = CH_X + 40960, CH_VT = CH_KT + 4096,
              CH_PS = CH_VT + 4096, CH_QK = CH_PS + 4096, CH_VP = CH_QK + 4096, CH_SX = CH_VP + 1024, CH_O = CH_SX + 2304, CH_ID = CH_O + 3072,
              CH_BAR = CH_ID + 512;
constexpr int CH_SMEM = CH_BAR + 256;
constexpr int CH_BASE = 1024;
#define CH_VK0 8
#define CH_VK1 20
#define CH_L0 4
#define CH_LR 4
#define NOX 0
#define CH_XA 1
#define CH_XB 4
#define CH_W1 3
#define CH_W2 17
#define CH_W3 26
#define CH_R2 8
#define CH_VA 16
#define CH_EX 1
#define CH_KD 0
#define CH_RP 1
#define CH_KF 10
#define CH_LO 0
#define CH_LR1 4
#define CH_KP 0
#define CH_KM 0
#define CH_WE 0
#define CH_KW 3
#define CH_RB 0
#define CH_RC 8
#define CH_D0 200
#define CH_D1 450
#define CH_D2 350
#define CH_R1 4
#define CH_TW 12
__device__ __forceinline__ uint32_t opaque(uint32_t x) { return __shfl_sync(~0u, x, threadIdx.x & 31); }
__device__ __forceinline__ uint32_t nz(uint32_t x) { uint32_t r; asm("max.u32 %0, %1, 1;" : "=r"(r) : "r"(x)); return r; }
__device__ __forceinline__ uint32_t pack_tag(float lo, float hi, uint32_t tag, uint32_t mask) {
  uint32_t r;
  asm("lop3.b32 %0, %1, %2, %3, 0xD8;" : "=r"(r) : "r"(pack2(lo, hi)), "r"(tag), "r"(mask));
  return r;
}
__device__ __forceinline__ uint32_t differ(uint32_t a, uint32_t b, uint32_t t) { uint32_t r; asm("lop3.b32 %0, %1, %2, %3, 0x7E;" : "=r"(r) : "r"(a), "r"(b), "r"(t)); return r; }
__device__ __forceinline__ void mbar_wait_hot(uint32_t bar, uint32_t ph) {
  uint32_t ok;
  asm volatile("{.reg .pred p; mbarrier.try_wait.parity.shared::cta.b64 p, [%1], %2; selp.u32 %0, 1, 0, p;}" : "=r"(ok) : "r"(bar), "r"(ph) : "memory");
  if (__builtin_expect(!ok, 0)) mbar_wait(bar, ph);
}
__device__ __forceinline__ bool elect() {
  uint32_t r; asm volatile("{.reg .pred p; elect.sync _|p, 0xffffffff; selp.u32 %0, 1, 0, p;}" : "=r"(r)); return r; }
__device__ __forceinline__ uint32_t or3(uint32_t a, uint32_t b, uint32_t c) { uint32_t r; asm("lop3.b32 %0, %1, %2, %3, 0xFE;" : "=r"(r) : "r"(a), "r"(b), "r"(c)); return r; }
__device__ __forceinline__ void pin() { pdl_launch(); }
__device__ __forceinline__ void mma16h(float* d, uint32_t a0, uint32_t a2, uint32_t b0, uint32_t b1) {
  asm volatile("{.reg .b32 u, v; mma.sync.aligned.m16n8k16.row.col.f32.bf16.bf16.f32 {%0,%1,%2,%3},{%4,u,%5,v},{%6,%7},{%0,%1,%2,%3};}"
               : "+f"(d[0]), "+f"(d[1]), "+f"(d[2]), "+f"(d[3]) : "r"(a0), "r"(a2), "r"(b0), "r"(b1)); }
__device__ __forceinline__ void mma8h(float* d, uint32_t a0, uint32_t b0) {
  asm volatile("{.reg .b32 u; mma.sync.aligned.m16n8k8.row.col.f32.bf16.bf16.f32 {%0,%1,%2,%3},{%4,u},{%5},{%0,%1,%2,%3};}"
               : "+f"(d[0]), "+f"(d[1]), "+f"(d[2]), "+f"(d[3]) : "r"(a0), "r"(b0)); }
__device__ __forceinline__ uint32_t absmax2(uint32_t a, uint32_t b) { uint32_t r; asm("max.xorsign.abs.bf16x2 %0, %1, %2;" : "=r"(r) : "r"(a), "r"(b)); return r; }
__device__ __forceinline__ void until(uint32_t t) { while ((int)(clk32() - t) < 0) {} }
__device__ __forceinline__ uint4 pack8(const float* d) { return make_uint4(pack2(d[0], d[1]), pack2(d[2], d[3]), pack2(d[4], d[5]), pack2(d[6], d[7])); }
__device__ __forceinline__ void add8(float* d, uint4 v) {
  d[0] += bf_lo(v.x); d[1] += bf_hi(v.x); d[2] += bf_lo(v.y); d[3] += bf_hi(v.y);
  d[4] += bf_lo(v.z); d[5] += bf_hi(v.z); d[6] += bf_lo(v.w); d[7] += bf_hi(v.w);
}

template <int WG>
__device__ __forceinline__ void chain_body(const ChainParams& p, const uint32_t wq, const uint32_t (&ak)[80], const uint32_t (&av)[80]) {
  const int tid = threadIdx.x & 127, t4 = __shfl_sync(~0u, tid >> 5, 0), lane = tid & 31;
  const int cta = blockIdx.x, h = cta / 3, j = cta - 3 * h;
  const uint32_t sb = mapa(CH_BASE, j);
  const uint32_t bWo = sb + CH_BAR, bWq = bWo + 8, bX = bWo + 16, bXA = bWo + 24, bXB = bWo + 32, bO = bWo + 40, bG = bWo + 48, bH = bWo + 96;
  uint32_t tw[4 * CH_TW];
  auto refill = [&]() {
#pragma unroll
    for (int k = 0; k < CH_TW; k++) ldsm4t(&tw[4 * k], wq + k * 2048);
  };
  const uint32_t wo = opaque((sb + CH_WO + (WG == 0 ? (t4 + (j == 2)) * 4096 : (j == 2 ? 0 : 24576) + t4 * 1024) + ((lane & 7) + (lane >> 4) * 8) * 64 +
                              ((((lane >> 3) & 1) ^ ((lane >> 1) & 3)) << 4)) ^ (WG == 1 && j == 2 ? 32 : 0));
  const uint32_t wo2 = opaque((wo ^ ((t4 & 1) * 32)) + (4 + (t4 >> 1) - t4) * 4096);
  const uint32_t l16 = opaque(sb + lane * 16);
  const uint32_t l8 = opaque(sb + t4 * 256 + lane * 8);
  const uint32_t lw = opaque(sb + t4 * 1024 + lane * 16);
  const uint32_t qs = opaque(sb + CH_QK + WG * 2048 + t4 * 512 + lane * 16);
  const uint32_t qa = opaque(sb + CH_QK + (lane >> 4) * 2048 + (lane & 15) * 16 + (WG == 0 ? t4 * 512 + 256 : t4 == 3 ? 1024 : 0));
  const uint32_t ka = opaque(t4 < 2 ? sb + CH_KT + t4 * 512 + lane * 16
                                    : sb + CH_QK + 256 + (t4 - 2) * 1024 + ((lane >> 3) & 1) * 2048 + (lane >> 4) * 128 + (lane & 7) * 16);
  const uint32_t l4 = opaque(sb + t4 * 256 + lane * 4);
  uint32_t pdst[1], pages = 0;
  auto line0 = [&](int i) { return 28 * j + (i < 4 ? 4 * t4 + i : 12 + 2 * t4 + i); };
  const uint32_t plane = opaque((lane >> 4) * 2048 + h * 64 + (lane & 15) * 4);
  if (WG == 0) {
    pages = __ballot_sync(~0u, lds32(sb + CH_O + line0(min(lane, 5)) * 4) & 4096);
  } else {
    pages = __ballot_sync(~0u, lds32(sb + CH_O + (80 + min(lane, 11)) * 4) & 4096);
    pdst[0] = opaque(lds32(sb + CH_O + (j == 0 ? 24 + t4 : 50 + 2 * j + (t4 & 1)) * 4) + plane);
  }
  const uint32_t role = lds32(sb + CH_O + NSLOT * 4), rsrc = lds32(sb + CH_O + role * 4), rdst = (80 + role / 20) * 8192 + role % 20 * 128;
  const uint32_t r1 = mapa(CH_BASE, j == 2 ? 0 : j + 1) - sb, r2 = mapa(CH_BASE, j == 0 ? 2 : j - 1) - sb;
  uint32_t tag = opaque(1);
  auto pool = [&](uint32_t off) { return p.pool + ((tag & 0xfffe) + off); };
  auto after = [&](uint32_t x) { return x & tag & 0xfffe; };
  auto kv = [&](int s, uint32_t a) { return p.kv + (a + ((cta * 2 * NSEG + s) * KV_BYTES - sb)); };
  auto pass = [&](float (&d)[16], const uint32_t (&a)[80], auto k0, auto k1) {
    const uint64_t db = mkdesc(CH_BASE + CH_X + WG * 20480, 512, 128, 0);
#pragma unroll
    for (int k = k0.value; k < k1.value; k++) wg_rs32_00(d, a[4 * k], a[4 * k + 1], a[4 * k + 2], a[4 * k + 3], db + k * 64, k);
    wg_commit();
  };
  auto dump = [&](float (&d)[16], uint32_t a) {
    reg_fence<16>(d);
    sts128(a, pack8(d)); sts128(a + 512, pack8(d + 8));
  };
  uint32_t pph = 0;
  auto tokens0 = [&](int s, auto k0) {
    float dk[16], dv[16];
    bar_sync(9, 256);
    wg_fence();
    pass(dk, ak, Int<0>(), Int<4>());
    const uint4 a0 = lds128(lw + CH_KT), a1 = lds128(lw + CH_KT + 512);
    pin();
    pass(dk, ak, Int<4>(), Int<20>());
    pass(dv, av, Int<0>(), Int<CH_VA>());
    pin();
    wg_wait<1>();
    reg_fence<16>(dk);
    add8(dk, a0); add8(dk + 8, a1);
    const uint4 w0 = pack8(dk), w1 = pack8(dk + 8);
    const uint4 b0 = lds128(lw + CH_VT), b1 = lds128(lw + CH_VT + 512);
    stsm4t(lw + CH_KT, w0.x, w0.z, w0.y, w0.w); stsm4t(lw + CH_KT + 512, w1.x, w1.z, w1.y, w1.w);
    if (CH_KP == 2) bar_arrive(7, 160);
    TM1(6);
    pin();
    if (CH_VA < 20) pass(dv, av, Int<CH_VA>(), Int<20>());
    pin();
#pragma unroll
    for (int k = k0.value; k < CH_TW; k++) ldsm4t(&tw[4 * k], wq + k * 2048);
    TM1(9);
    if (k0.value < CH_TW && t4 >= 2) { mbar_wait_hot(bH + t4 * 16 - 24 + (pph & 1) * 8, pph >> 1 & 1); pph++; }
    __syncwarp();
    wg_wait<0>();
    reg_fence<16>(dv);
    add8(dv, b0); add8(dv + 8, b1);
#pragma unroll
    for (int e = 0; e < 2; e++) { const uint4 v = pack8(dv + 8 * e); sts128(lw + CH_VT + e * 512, make_uint4(v.x, v.z, v.y, v.w)); }
  };
  auto publish_k = [&](int s) {
    if (t4 == CH_KW && elect()) { fence_async(); bulk_store(p.kv + (size_t)(cta * 2 * NSEG + s) * KV_BYTES, sb + CH_KT, 4096); bulk_commit(); }
    __syncwarp();
  };
  if (WG == 0) {
    mbar_wait(bXB, 0);
    tokens0(0, Int<CH_TW>());
  } else {
    const uint32_t* m0 = reinterpret_cast<const uint32_t*>(p.mem0) + (lane >> 2) * 320 + t4 * 80 + (lane & 3);
    uint32_t a[20];
#pragma unroll
    for (int i = 0; i < 20; i++) a[i] = m0[4 * i];
    pin();
    float dk[16], dv[16];
    mbar_wait(bXA, 0);
    wg_fence();
    pass(dk, ak, Int<0>(), Int<20>());
    pass(dv, av, Int<0>(), Int<20>());
    wg_wait<0>();
    dump(dk, lw + CH_KT);
    dump(dv, lw + CH_VT);
    bar_sync(9, 256);
    if (CH_KP == 2 && t4 == CH_KW) { bar_sync(7, 160); publish_k(0); }
#pragma unroll
    for (int i = 0; i < 20; i++) sts32(sb + CH_M + (t4 * 20 + i) * 128 + lane * 4, nz(transpose8(a[i])));
    __syncwarp();
    if (elect()) mbar_arrive(bG + t4 * 8);
  }
  PRO(8);
  mbar_wait(bWq, 0);
  refill();
  PRO(9);
  mbar_wait(bWo, 0);
  asm volatile("barrier.cluster.wait.aligned;" ::: "memory");
  PRO(10);
  auto load_x = [&](int s, int k0, int n, uint32_t bar) {
    if (!NOX && elect()) { mbar_expect(bar, n * 1024); bulk_load(sb + CH_X + k0 * 1024, p.xc + (s + 1) * 10240 + k0 * 256, n * 1024, bar); }
  };
  constexpr int VK = WG == 0 ? CH_VK0 : CH_VK1;
  uint32_t gph = 0;
  int st = 0;
  const uint32_t ca = opaque(sb + CH_M + t4 * 2560 + lane * 32 + (lane >> 2) * 4);
  auto project = [&](int s, uint32_t (&b)[40], float (&dv)[16], uint32_t (&kf)[16]) {
    float dq[4] = {}, dk[4] = {};
    uint32_t w[80];
#pragma unroll
    for (int i = 0; i < 4 * CH_TW; i++) w[i] = tw[i];
    constexpr int LR = WG == 1 ? CH_LR1 : CH_LR;
    auto load = [&](int n) {
      int c = 0;
#pragma unroll
      for (int i = 0; i < 10; i++) {
        if (i == CH_KF) {
#pragma unroll
          for (int q = 0; q < 4; q++)
            if (WG == 1 && c++ == n) ldsm4(&kf[4 * q], ka + q * 1024);
        }
        if (c++ == n) ldsm4t(&b[4 * i], l16 + CH_M + WG * 5120 + i * 512);
#pragma unroll
        for (int k = 2 * i; k < 2 * i + 2; k++)
          if (k >= CH_TW && c++ == n) ldsm4t(&w[4 * k], wq + k * 2048);
      }
#pragma unroll
      for (int i = 0; i < 4; i++)
        if (WG == 1 && CH_KF >= 10 && c++ == n) ldsm4(&kf[4 * i], ka + i * 1024);
    };
    if (WG == 1) {
      for (int n = 0;;) {
        mbar_wait(bG + t4 * 8, gph);
        TR(5, (clk32() & ~3u) | min(n, 3));
        gph ^= 1;
        if (__builtin_expect(!__any_sync(~0u, __vimin3_u32(lds32(ca), lds32(ca + 1024), lds32(ca + 1536)) == 0), 1)) break;
        if (elect()) {
          const int q = (st == 0 ? 8 : st * 4 - 4) + t4;
          mbar_expect(bG + t4 * 8, 2560);
          bulk_load(sb + CH_M + t4 * 2560, p.pool + ((80 + q) * 8192 + (pages >> q & 1) * 4096), 2560, bG + t4 * 8);
        }
        spin_guard(n);
      }
    }
    bar_sync(6, 256);
#pragma unroll
    for (int i = 0; i < CH_L0; i++) load(i);
    if (WG == 0 && CH_XB == 4 && s + 1 < NSEG) load_x(s, 5 * t4, 5, bXB);
    TM(0);
    TM1(11);
    if (WG == 1) TR(6, clk32());
#pragma unroll
    for (int k = 0; k < 20; k += 2) {
      if (k > 0) {
#pragma unroll
        for (int n = (k == 18 ? 40 : CH_L0 + k * LR / 4) - 1; n >= CH_L0 + (k - 2) * LR / 4; n--) { load(n); if (CH_LO) __syncwarp(); }
      }
      pin();
#pragma unroll
      for (int kk = k; kk < k + 2; kk++) {
        mma16(dk, ak[4 * kk], ak[4 * kk + 1], ak[4 * kk + 2], ak[4 * kk + 3], b[2 * kk], b[2 * kk + 1]);
        mma16(dq, w[4 * kk], w[4 * kk + 1], w[4 * kk + 2], w[4 * kk + 3], b[2 * kk], b[2 * kk + 1]);
        if (kk < VK) mma16(dv, av[4 * kk], av[4 * kk + 1], av[4 * kk + 2], av[4 * kk + 3], b[2 * kk], b[2 * kk + 1]);
      }
    }
    const float k2 = 0.07216878364870322f * 1.44269504089f;
    stsm4t(qs, pack2(dq[0] * k2, dq[1] * k2), pack2(dq[2] * k2, dq[3] * k2), pack2(dk[0], dk[1]), pack2(dk[2], dk[3]));
    TM(1);
  };
  static_assert(CH_VK1 == 20 && CH_KP == 0 && CH_XA > 0 && CH_XB > 0, "last step");
  constexpr int VC = VK == 20 ? 1 : WG == 0 ? 2 : 3;
  auto finish_v = [&](const uint32_t (&b)[40], float (&dv)[16]) {
#pragma unroll
    for (int kk = VK; kk < 20; kk++) mma16(dv + 4 * ((kk - VK) % VC), av[4 * kk], av[4 * kk + 1], av[4 * kk + 2], av[4 * kk + 3], b[2 * kk], b[2 * kk + 1]);
  };
  auto sum_v = [&](float (&dv)[16]) {
#pragma unroll
    for (int i = 4; i < 4 * VC; i++) dv[i & 3] += dv[i];
  };
  auto publish_km = [&](int s) {
    uint32_t a[4];
    ldsm4(a, qa);
    *reinterpret_cast<uint2*>(kv(s, l8) + KV_M) = make_uint2(hadd2(a[0], a[2]), hadd2(a[1], a[3]));
  };
  auto memory_v = [&](uint2 x, const float (&dv)[16]) {
    return make_uint2(pack2(dv[0] + bf_lo(x.x), dv[1] + bf_hi(x.x)), pack2(dv[2] + bf_lo(x.y), dv[3] + bf_hi(x.y)));
  };
  auto publish_v = [&](int s, const uint4 (&v)[2], uint2 vm) {
#pragma unroll
    for (int e = 0; e < 2; e++) reinterpret_cast<uint4*>(kv(s, lw) + KV_V)[e * 32] = v[e];
    *reinterpret_cast<uint2*>(kv(s, l8) + KV_V + KV_M) = vm;
  };
#pragma unroll 1
  for (int s = 0;; s++) {
    float dv[16] = {};
    uint32_t b[40], kf[16];
    project(s, b, dv, kf);
    if (WG == 0) {
      bar_sync(1, 256);
      if (CH_XA == 0) load_x(s, 20 + 5 * t4, 5, bXA);
      if (CH_XB == 0) load_x(s, 5 * t4, 5, bXB);
      pin();
      finish_v(b, dv);
      sum_v(dv);
      sts64(l8 + CH_VP, pack2(dv[0], dv[1]), pack2(dv[2], dv[3]));
      if (s == NSEG - 1) {
        bar_arrive(10, 256);
        publish_k(s);
        publish_km(s);
        bulk_wait<0>();
        fence_async_global();
        bar_sync(2, 256);
        if (tid == 0) red_release(p.sync + 15 * 8 + 4, 1);
        break;
      }
      __syncwarp();
      if (elect()) mbar_arrive(bX);
      if (CH_XA == 1) load_x(s, 20 + 5 * t4, 5, bXA);
      if (CH_XB == 1) load_x(s, 5 * t4, 5, bXB);
      uint32_t w[144];
      auto wload = [&](int i) { ldsm4t(&w[4 * i], (i % 3 == 0 ? wo : i % 3 == 1 ? wo ^ 32 : wo2) + i / 12 * 28672 + i / 3 % 4 * 1024); };
      TM(3);
      if (CH_KP == 0) publish_k(s);
#pragma unroll
      for (int i = 0; i < CH_W1; i++) wload(i);
      bar_sync(10, 256);
      uint32_t km[4];
      ldsm4(km, qa);
      pin();
#pragma unroll
      for (int i = CH_W1; i < CH_W2; i++) wload(i);
      pin();
      const uint2 kms = make_uint2(hadd2(km[0], km[2]), hadd2(km[1], km[3]));
      if (CH_KM == 0) *reinterpret_cast<uint2*>(kv(s, l8) + KV_M) = kms;
      if (CH_KP == 0) bulk_wait_read<0>();
      if (CH_XA == 2) load_x(s, 20 + 5 * t4, 5, bXA);
      if (CH_XB == 2) load_x(s, 5 * t4, 5, bXB);
      bar_sync(2, 256);
      {
        float y[3][4] = {};
        uint32_t ob[24];
        ldsm4(&ob[0], l16 + CH_O + 1024); ldsm4(&ob[4], l16 + CH_O + 1536);
        TM(7);
        auto step = [&](int i) {
          const int k = i / 3;
          mma16(y[i % 3], w[4 * i], w[4 * i + 1], w[4 * i + 2], w[4 * i + 3], ob[2 * k], ob[2 * k + 1]);
        };
#pragma unroll
        for (int i = 0; i < 12; i++) {
          step(i);
          if (i >= 12 - (CH_W3 - CH_W2)) wload(CH_W3 - 12 + i);
          if (i % 3 == 2) pin();
        }
        if (CH_XB == 3) load_x(s, 5 * t4, 5, bXB);
        if (CH_KM == 1) *reinterpret_cast<uint2*>(kv(s, l8) + KV_M) = kms;
        pin();
        mbar_wait(bO, s & 1);
        TM(4);
        ldsm4(&ob[8], l16 + CH_O); ldsm4(&ob[12], l16 + CH_O + 512);
        pin();
        float2 inv;
        uint8_t* dst[6];
        uint32_t mask;
#pragma unroll
        for (int i = 12; i < 36; i++) {
          step(i);
          const int n = CH_W3 + i - 13, m = n - (n > 30);
          if (i == 12) ldsm4(&ob[16], l16 + after(w[4 * CH_W3 - 1] | w[4 * CH_W3 - 5] | w[4 * CH_W3 - 9] | ob[8]) + CH_O + 2048);
          else if (n == 30) ldsm4(&ob[20], l16 + CH_O + 2560);
          else if (m < 36) wload(m);
          else if (m == 36) inv = lds64f((l8 & ~0xe0u) + CH_VP);
          if (i == 26) mask = ((l16 ^ tag) & 48) == 0;
          if (i >= 27 && i < 33) dst[i - 27] = pool(line0(i - 27) * 8192 + (pages >> (i - 27) & 1) * 4096) + plane;
          if (i % 3 == 2) pin();
        }
#pragma unroll
        for (int k = 0; k < CH_R1; k++) ldsm4t(&tw[4 * k], wq + k * 2048);
        pin();
#pragma unroll
        for (int i = 0; i < 6; i++) stg_strong32(dst[i], pack_tag(y[i >> 1][2 * (i & 1)] * inv.x, y[i >> 1][2 * (i & 1) + 1] * inv.y, tag, mask));
        TM(8);
        TR(0, clk32());
        bar_arrive(5, 256);
        pin();
      }
      const uint32_t t0 = clk32();
      auto refill2 = [&]() {
#pragma unroll
        for (int k = CH_R1; k < CH_R2; k++) ldsm4t(&tw[4 * k], wq + k * 2048);
      };
      if (CH_RP == 0) refill2();
      const uint32_t ln = (l16 ^ tag) >> 4 & 31;
      if (t4 >= 2) {
        const uint32_t bP = bH + t4 * 16 - 24, ps = CH_PS + (t4 & 1) * 4096;
        auto fetch = [&](uint32_t k) {
          if (elect()) { mbar_expect(bP + (k & 1) * 8, 2048); bulk_load(sb + ps + (k & 1) * 2048, p.pool + (rsrc + (t4 & 1) * 2048), 2048, bP + (k & 1) * 8); }
        };
        until(t0 + CH_D0);
        fetch(pph);
        if (CH_RP == 2) refill2();
        if (!NOX) mbar_wait_hot(bXB, (s + 1) & 1);
        const uint32_t want = (tag & 1) * 0x10001, chk = opaque(ln < 4 ? 0x10001 : 0);
        uint4 sel;
        sel.x = opaque((ln >> 3) != (ln & 1) ? 0 : ln & 4 ? 0x3f800000u : 0x00003f80u);
        sel.z = opaque(sel.x); sel.y = opaque(ln); sel.w = opaque(ln + 1);
        uint8_t* mdst = p.pool + opaque(st * 32768 + rdst + (t4 & 1) * 64 + ln * 4);
        until(t0 + CH_D1);
        fetch(pph + 1);
        TM(5);
        if (CH_RP == 1) refill2();
        int n = 0;
        uint32_t u[16];
        for (;;) {
          mbar_wait(bP + (pph & 1) * 8, pph >> 1 & 1);
          TM(14);
          TR(2, clk32());
#pragma unroll
          for (int i = 0; i < 4; i++) ldsm4t(&u[4 * i], l16 + (ps + (pph & 1) * 2048) + i * 512);
          pph++;
          uint32_t bad = 0;
#pragma unroll
          for (int i = 0; i < 4; i++) bad = or3(bad, differ(u[4 * i], u[4 * i + 1], want), differ(u[4 * i + 2], u[4 * i + 3], want));
          if (!__any_sync(~0u, bad & chk)) break;
          fetch(pph + 1);
          spin_guard(n);
        }
        float y[4][4] = {};
#pragma unroll
        for (int i = 0; i < 8; i++) mma16(y[i & 3], sel.x, sel.y, sel.z, sel.w, u[2 * i], u[2 * i + 1]);
        TR(1, t0 + (n ? CH_D1 : CH_D0));
        TM(15);
        const uint32_t w = nz(pack2((y[0][0] + y[1][0]) + (y[2][0] + y[3][0]), (y[0][1] + y[1][1]) + (y[2][1] + y[3][1])));
        if (ln < 16) { stg_strong32(mdst, w); stg_strong32(mdst + 4096, w); }
        TMV(12, 32, n);
        TR(3, (clk32() & ~3u) | min(n, 3));
      } else {
        if (CH_RP) refill2();
        if (!NOX) mbar_wait_hot(bXB, (s + 1) & 1);
        stg_strong32(p.pool + ((st == 2 ? 0 : st + 1) * 32768 + rdst + t4 * 4096) + ln * 4, 0u);
        if (t4 == 0 && cta < 40 && s + 4 < NSEG && elect())
          asm volatile("cp.async.bulk.prefetch.L2.global [%0], 1024;" :: "l"(p.xc + (s + 4) * 10240 + cta * 256) : "memory");
        if (t4 == 1 && (s & 3) == 0 && s > 0 && elect()) red_relaxed(p.sync + 2 * s - 4, 1);
        if (t4 == 1 && s == NSEG - 3 && cta == 95 && elect()) red_relaxed(p.sync + 2 * s + 2, 0x10000);
      }
      TM(10);
      bar_arrive(8, 256);
      tokens0(s + 1, Int<CH_R2>());
      TM(2);
      TR(7, clk32());
    } else {
      if (s == NSEG - 1) {
        bar_arrive(1, 256);
        const uint4 v[2] = {lds128(lw + CH_VT), lds128(lw + CH_VT + 512)};
        bar_sync(10, 256);
        publish_v(s, v, memory_v(lds64(l8 + CH_VP), dv));
        bar_arrive(2, 256);
        break;
      }
      const uint32_t xo = l4 + (CH_SX - (t4 == 3 ? 128 : 0)), x1 = xo + (r1 + 768 + min(t4, 2) * 256), x2 = xo + (r2 + 1024 + min(t4, 2) * 256);
      if (t4 < 2) {
        float ds[4][4] = {};
        uint32_t q[16];
        asm volatile("bar.sync 1, 256;" ::: "memory");
#pragma unroll
        for (int k = 0; k < 4; k++) ldsm4(&q[4 * k], qa + k * 512);
        pin();
        if (VK < 20) { finish_v(b, dv); pin(); }
#pragma unroll
        for (int k = 0; k < 4; k++) {
          mma16(ds[k & 1], kf[4 * k], kf[4 * k + 1], kf[4 * k + 2], kf[4 * k + 3], q[4 * k], q[4 * k + 1]);
          mma16(ds[2 + (k & 1)], kf[4 * k], kf[4 * k + 1], kf[4 * k + 2], kf[4 * k + 3], q[4 * k + 2], q[4 * k + 3]);
        }
        float t[4];
#pragma unroll
        for (int i = 0; i < 4; i++) t[i] = (ds[0][i] + ds[2][i]) + (ds[1][i] + ds[3][i]);
        const uint32_t w0 = pack2(t[0], t[1]), w1 = pack2(t[2], t[3]);
        st_async32(x1, w0, bX + r1); st_async32(x2, w0, bX + r2);
        st_async32(x1 + 128, w1, bX + r1); st_async32(x2 + 128, w1, bX + r2);
        sts32(xo, w0); sts32(xo + 128, w1);
      } else {
        float ds[4][4] = {};
        uint32_t q0[4], q1[4], a0[4], a1[4];
        asm volatile("bar.sync 1, 256; " ::: "memory");
        ldsm4(a0, ka); ldsm4(q0, qa); ldsm4(a1, ka + 512); ldsm4(q1, qa + 512);
        pin();
        if (VK < 20) { finish_v(b, dv); pin(); }
        mma16(ds[0], a0[0], a0[1], a0[2], a0[3], q0[0], q0[1]);
        mma16(ds[1], a0[0], a0[1], a0[2], a0[3], q0[2], q0[3]);
        mma16(ds[2], a1[0], a1[1], a1[2], a1[3], q1[0], q1[1]);
        mma16(ds[3], a1[0], a1[1], a1[2], a1[3], q1[2], q1[3]);
        float t[2];
#pragma unroll
        for (int i = 0; i < 2; i++)
          t[i] = ((ds[0][i] + ds[0][i + 2]) + (ds[1][i] + ds[1][i + 2])) + ((ds[2][i] + ds[2][i + 2]) + (ds[3][i] + ds[3][i + 2]));
        const uint32_t w0 = pack2(t[0], t[1]);
        st_async32(x1, w0, bX + r1);
        st_async32(x2, w0, bX + r2);
        sts32(xo, w0);
      }
      TM(3);
      const uint4 id = lds128(l16 + CH_ID);
      float sc[3][4] = {};
      uint4 v[2];
      sum_v(dv);
      bar_sync(3, 128);
      uint32_t r[12], wd[12], we[12] = {};
      ldsm4(&r[0], l16 + CH_SX); ldsm2(&r[4], l16 + CH_SX + 512);
      pin();
      v[0] = lds128(lw + CH_VT); v[1] = lds128(lw + CH_VT + 512);
#pragma unroll
      for (int u = 0; u < 3; u++) ldsm4t(&wd[4 * u], wo + u * 28672);
      if (CH_WE && j == 0) {
#pragma unroll
        for (int u = 0; u < 3; u++) ldsm4t(&we[4 * u], (wo ^ 32) + u * 28672);
      }
      pin();
#pragma unroll
      for (int q = 0; q < 3; q++) mma16(sc[q], id.x, id.y, id.z, id.w, r[2 * q], r[2 * q + 1]);
      uint32_t big = absmax2(absmax2(absmax2(r[0], r[1]), absmax2(r[2], r[3])), absmax2(r[4], r[5]));
      const uint32_t oa1 = l4 + (r1 + CH_O), oa2 = l4 + (r2 + CH_O + 2048), ones = 0x3f803f80u;
      mbar_wait_hot(bX, s & 1);
      TM(4);
      ldsm4(&r[0], l16 + CH_SX + 768); ldsm4(&r[8], l16 + CH_SX + 1792); ldsm4(&r[4], l16 + CH_SX + 1280);
      const uint2 vp = lds64(l8 + CH_VP);
      bar_arrive(10, 256);
      pin();
      {
        float sd[3][4] = {};
#pragma unroll
        for (int i = 0; i < 3; i++) {
          const int q = i == 0 ? 0 : 3 - i;
          mma16(sc[q], id.x, id.y, id.z, id.w, r[4 * q], r[4 * q + 1]);
          mma16(sd[q], id.x, id.y, id.z, id.w, r[4 * q + 2], r[4 * q + 3]);
          big = absmax2(big, absmax2(absmax2(r[4 * q], r[4 * q + 1]), absmax2(r[4 * q + 2], r[4 * q + 3])));
        }
#pragma unroll
        for (int i = 0; i < 12; i++) sc[i >> 2][i & 3] += sd[i >> 2][i & 3];
      }
      const bool redo = __any_sync(~0u, (absmax2(big, big << 16) & 0x7fff0000u) >= 0x41800000u);
      const uint2 vm = memory_v(vp, dv);
      sc[2][0] += sc[2][2]; sc[2][1] += sc[2][3];
      float l[4], o[2][4];
      uint32_t p3, p4;
      auto attend = [&]() {
#pragma unroll
        for (int i = 0; i < 4; i++) l[i] = o[0][i] = o[1][i] = 0.f;
        const uint32_t p1 = pack2(ex2(sc[0][0]), ex2(sc[0][1])), p2 = pack2(ex2(sc[0][2]), ex2(sc[0][3]));
        mma16h(o[0], p1, p2, v[0].x, v[0].y);
        mma16h(o[1], p1, p2, v[0].z, v[0].w);
        mma16h(l, p1, p2, ones, ones);
        const uint32_t p0 = pack2(ex2(sc[2][0]), ex2(sc[2][1]));
        mma8h(o[0], p0, vm.x);
        mma8h(o[1], p0, vm.y);
        mma8h(l, p0, ones);
        p3 = pack2(ex2(sc[1][0]), ex2(sc[1][1])); p4 = pack2(ex2(sc[1][2]), ex2(sc[1][3]));
        mma16h(o[0], p3, p4, v[1].x, v[1].y);
        mma16h(o[1], p3, p4, v[1].z, v[1].w);
      };
      attend();
      if (__builtin_expect(redo, 0)) {
        float mx = fmaxf(sc[2][0], sc[2][1]);
#pragma unroll
        for (int i = 0; i < 4; i++) mx = fmaxf(mx, fmaxf(sc[0][i], sc[1][i]));
        mx = fmaxf(mx, __shfl_xor_sync(~0u, mx, 1));
        mx = fmaxf(mx, __shfl_xor_sync(~0u, mx, 2));
#pragma unroll
        for (int i = 0; i < 4; i++) { sc[0][i] -= mx; sc[1][i] -= mx; }
        sc[2][0] -= mx; sc[2][1] -= mx;
        attend();
      }
      const uint32_t o0 = pack2(o[0][0], o[0][1]), o1 = pack2(o[1][0], o[1][1]);
      st_async32(oa1, o0, bO + r1); st_async32(oa2, o0, bO + r2);
      st_async32(oa1 + 128, o1, bO + r1); st_async32(oa2 + 128, o1, bO + r2);
      sts32(l4 + CH_O + 1024, o0); sts32(l4 + CH_O + 1152, o1);
      bar_arrive(2, 256);
      pin();
      TM(6);
      mma16h(l, p3, p4, ones, ones);
      float inv;
      asm("rcp.approx.ftz.f32 %0, %1;" : "=f"(inv) : "f"(l[0]));
      sts32((l8 & ~0xffu) + (lane & 28) + CH_VP, __float_as_uint(inv));
      __syncwarp();
      if (elect()) mbar_arrive(bO);
      {
        float z[2][4] = {}, y[2][4] = {};
        mma16(z[0], wd[0], wd[1], wd[2], wd[3], o0, o1);
        if (j == 0) {
#pragma unroll
          for (int u = 0; u < 3; u++) if (!CH_WE) ldsm4t(&we[4 * u], (wo ^ 32) + u * 28672);
          mma16(y[0], we[0], we[1], we[2], we[3], o0, o1);
        }
        const float2 iv = lds64f((l8 & ~0xe0u) + CH_VP);
        uint8_t* dst = pool(pdst[0]);
        const uint32_t mask = ((l16 ^ tag) & 48) == 0;
        const uint32_t oa = qa + ((tag & 0xfffe) + CH_O - CH_QK + t4 * 256 - (t4 == 3 ? 1024 : 0));
        const uint32_t za = l16 + ((tag & 0xfffe) + (t4 >> 1) * 512 + (t4 & 1) * 8);
        pin();
        mbar_wait(bO, s & 1);
        uint32_t a[4];
        ldsm4(a, oa);
        mma16(z[0], wd[4], wd[5], wd[6], wd[7], a[0], a[1]);
        mma16(z[1], wd[8], wd[9], wd[10], wd[11], a[2], a[3]);
        if (j == 0) {
          mma16(y[0], we[4], we[5], we[6], we[7], a[0], a[1]);
          mma16(y[1], we[8], we[9], we[10], we[11], a[2], a[3]);
          sts128f(lw + CH_VT + 512, y[0][0] + y[1][0], y[0][1] + y[1][1], y[0][2] + y[1][2], y[0][3] + y[1][3]);
        }
        sts128f(lw + CH_VT, z[0][0] + z[1][0], z[0][1] + z[1][1], z[0][2] + z[1][2], z[0][3] + z[1][3]);
        bar_sync(3, 128);
        if (j == 0 || t4 < 2) {
          float2 q[4];
#pragma unroll
          for (int i = 0; i < 4; i++) q[i] = lds64f(za + CH_VT + i * 1024);
          stg_strong32(dst, pack_tag(((q[0].x + q[1].x) + (q[2].x + q[3].x)) * iv.x, ((q[0].y + q[1].y) + (q[2].y + q[3].y)) * iv.y, tag, mask));
        }
      }
      TM(2);
      if (!NOX) mbar_wait_hot(bXA, (s + 1) & 1);
      if (CH_KP == 2) bulk_wait_read<0>();
      float dk[16], dw[16];
      bar_sync(5, 256);
      wg_fence();
      pass(dk, ak, Int<0>(), Int<20>());
      pass(dw, av, Int<0>(), Int<20>());
      TM(5);
      pin();
      if (CH_EX == 0) publish_v(s, v, vm);
      if (elect()) {
        mbar_expect(bG + t4 * 8, 2560);
        if (t4 == 1 && s + 2 < NSEG) { mbar_expect(bX, 1536); mbar_expect(bO, 2048); }
      }
      if (CH_KD == 0) { wg_wait<1>(); dump(dk, lw + CH_KT); }
      wg_wait<0>();
      if (CH_KD == 1) dump(dk, lw + CH_KT);
      TM(7);
      dump(dw, lw + CH_VT);
      bar_arrive(9, 256);
      pin();
#pragma unroll
      for (int k = 0; k < CH_RB; k++) ldsm4t(&tw[4 * k], wq + k * 2048);
      if (t4 < 2) {
#pragma unroll
        for (int k = CH_RB; k < CH_RC; k++) ldsm4t(&tw[4 * k], wq + k * 2048);
        const int q = t4 ? 3 : j, o = t4 ? j * 896 : 0;
        const uint8_t* src = p.pool + ((80 + st * 4 + q) * 8192 + (pages >> (st * 4 + q) & 1) * 4096 + o);
        asm volatile("bar.sync 8, 256;" ::: "memory");
        const uint32_t t1 = clk32() + CH_D2;
        if (CH_EX == 1) publish_v(s, v, vm);
        auto fetch = [&](auto n) {
          mbar_wait(bH, s & 1);
          until(t1);
          TR(4, clk32());
          if (elect())
            asm volatile("cp.async.bulk.shared::cluster.global.mbarrier::complete_tx::bytes.multicast::cluster [%0], [%1], %2, [%3], 7;"
                         :: "r"(sb + CH_M + q * 2560 + o), "l"(src), "n"(n.value), "r"(bG + q * 8) : "memory");
        };
        if (!t4) fetch(Int<2560>()); else if (j == 2) fetch(Int<768>()); else fetch(Int<896>());
      } else {
        asm volatile("bar.sync 8, 256; " ::: "memory");
        if (elect()) asm volatile("mbarrier.arrive.relaxed.cluster.shared::cluster.b64 _, [%0];" :: "r"(bH + (t4 == 2 ? r1 : r2)) : "memory");
        pin();
        if (CH_EX == 1) publish_v(s, v, vm);
#pragma unroll
        for (int k = CH_RB; k < CH_RC; k++) ldsm4t(&tw[4 * k], wq + k * 2048);
      }
      TM(9);
      pin();
#pragma unroll
      for (int k = CH_RC; k < CH_TW; k++) ldsm4t(&tw[4 * k], wq + k * 2048);
      if (CH_KP == 2 && t4 == CH_KW) { bar_sync(7, 160); publish_k(s + 1); }
      TM(10);
    }
    if (++st == 3) st = 0;
    tag ^= 0x10001;
  }
}

__global__ void __launch_bounds__(256, 1) chain_kernel(const __grid_constant__ ChainParams p) {
  extern __shared__ __align__(1024) uint8_t smem_raw[];
  const uint32_t sb = s2u(smem_raw);
  const int tid = threadIdx.x, warp = __shfl_sync(~0u, tid >> 5, 0), lane = tid & 31;
  const int cta = blockIdx.x, h = cta / 3, j = cta - 3 * h, colbase = cta * 64;
  const uint32_t bWo = sb + CH_BAR, bWq = bWo + 8, bXA = bWo + 24, bWk = bWo + 80, bWv = bWo + 88;
  uint32_t smid; asm("mov.u32 %0, %%smid;" : "=r"(smid));
  PRO(0);
  if (sb != mapa(CH_BASE, j)) __trap();
  uint32_t entry = 0;
  auto place = [&]() {
    const int i = tid - 128;
    if (i >= 0 && i <= NSLOT) {
      const uint32_t side = ldg_strong32(g_smpart + (smid & 255));
      if (i < NSLOT) {
        entry = i * 8192 + (ldg_strong32(g_orient + i) == (i < 80 ? i & 1 : side) ? 0 : 4096);
      } else {
        entry = 2 * (atomicAdd(g_bo + p.layer * 128 + 1, 1 << 8 * side) >> 8 * side & 255) + side;
      }
    }
    __syncwarp();
  };
  if (p.layer) place();
  if (warp == 0 && elect()) {
#pragma unroll 1
    for (int i = 0; i < 17; i++) mbar_init(bWo + 8 * i, i == 2 || i == 5 ? 5 : i == 3 || i == 4 ? 4 : i == 12 ? 2 : 1);
    asm volatile("fence.mbarrier_init.release.cluster;" ::: "memory");
    mbar_expect(bWk, 81920);
    tma_load3<(WEF & 1) != 0>(sb + CH_WQ, &p.wk, colbase, 0, bWk);
    mbar_expect(bWv, 81920);
    tma_load3<(WEF & 1) != 0>(sb + CH_WO, &p.wv, colbase, 0, bWv);
    mbar_expect(bWo + 16, 1536);
    mbar_expect(bWo + 40, 2048);
    mbar_expect(bWo, 86016); mbar_expect(bWq, 81920);
#pragma unroll 1
    for (int i = 0; i < 8; i++) mbar_expect(bXA + 8 * (i & 1), 5120);
  }
  if (warp == 1) {
    const uint32_t id = (lane >> 3) == (lane & 3) ? ((lane & 4) ? 0x3f800000u : 0x00003f80u) : 0u;
    sts128(sb + CH_ID + lane * 16, make_uint4(id, 0, 0, id));
  }
  __syncthreads();
  asm volatile("barrier.cluster.arrive.relaxed.aligned;" ::: "memory");
  uint32_t ak[80], av[80];
  const uint32_t wq = opaque(sb + CH_WQ + ((warp >> 2) * 320 + (lane & 7) + (lane >> 4) * 8) * 128 + (((2 * (warp & 3) + ((lane >> 3) & 1)) ^ (lane & 7)) << 4));
  pdl_wait();
  if (tid == 32) stg_strong32(g_smuse + (smid & 255), p.layer + 1);
  pdl_launch();
  PRO(1);
  if (warp == 0 && elect()) {
    bulk_load(sb + CH_X + 20480, p.xc + 5120, 20480, bXA);
    bulk_load(sb + CH_X, p.xc, 20480, bXA + 8);
  }
  if (!p.layer) place();
  __syncwarp();
  PRO(2);
  mbar_wait(bWk, 0);
  PRO(3);
#pragma unroll
  for (int k = 0; k < 20; k++) ldsm4t(&ak[4 * k], wq + k * 2048);
  bar_sync(6, 256);
  if (warp == 0 && elect()) tma_load3<(WEF & 2) != 0>(sb + CH_WQ, &p.wq, colbase, 0, bWq);
  __syncwarp();
  PRO(4);
  mbar_wait(bWv, 0);
  PRO(5);
#pragma unroll
  for (int k = 0; k < 20; k++) ldsm4t(&av[4 * k], wq + CH_WO + k * 2048);
  bar_sync(6, 256);
  PRO(6);
  if (warp >= 5 && elect()) tma_load3<(WEF & 2) != 0>(sb + CH_WO + (warp - 5) * 28672, &p.wo, j == 0 ? 0 : 32 + j * 192, h * 192 + (j + 8 - warp) % 3 * 64, bWo);
  if (tid == 128 + NSLOT && entry >= 80) {
    uint32_t c;
    int n = 0;
    do { c = ldg_strong32(g_bo + p.layer * 128 + 1); spin_guard(n); } while ((c & 255) + (c >> 8) < 96);
    const uint32_t other = (c >> 8 * (~entry & 1) & 255) + (entry >> 1) - 40;
    entry = other < 40 ? 2 * other + (~entry & 1) : entry % 80;
  }
  if (tid >= 128 && tid <= 128 + NSLOT) sts32(sb + CH_O + (tid - 128) * 4, entry);
  PRO(7);
  __syncthreads();
  if (__shfl_sync(~0u, tid >> 7, 0) == 0) chain_body<0>(p, wq, ak, av); else chain_body<1>(p, wq, ak, av);
}

struct PostParams { CUtensorMap wq, wo, wb, wo2, wb2; int gap, share, layer, look, gap2, pol; };
constexpr int PS = 8, PB = 28672;
constexpr int OP_SMEM = PS * PB + 512 + 2048;
enum { IT_ATT = 0, IT_OP = 1, IT_FIN = 2, IT_BQ = 3, IT_Q = 4 };

__device__ __forceinline__ uint32_t item_count(int type, int b) {
  return type == IT_ATT ? 32 : type == IT_OP ? op_split(b) * (DM / op_width(b)) : type == IT_FIN ? fin_items(b) : 1920 / bq_width(b); }
__device__ __forceinline__ uint32_t item_need(int type, int b) { return type == IT_ATT ? 96 : item_count(type - 1, b); }

struct Ring {
  uint32_t sb, bars; int st; uint32_t ph;
  __device__ __forceinline__ uint32_t wait() const { mbar_wait(bars + 8 * st, ph); return sb + st * PB; }
  __device__ __forceinline__ void next() { if (++st == PS) { st = 0; ph ^= 1; } }
  __device__ __forceinline__ void release(int s) const { if ((threadIdx.x & 31) == 0) mbar_arrive(bars + 8 * (PS + s)); }
  __device__ __forceinline__ void pop() { __syncwarp(); release(st); next(); }
};

template <int N>
__device__ __forceinline__ void gemm_item(Ring& r, float* d, int nst, uint32_t go, int go_at) {
  int prev = 0;
#pragma unroll 1
  for (int kb = 0; kb < nst; kb++) {
    const uint32_t base = r.wait();
    const uint64_t da = mkdesc(base + (threadIdx.x >> 7) * 4096, 128, 512, 0), db = mkdesc(base + 8192, 4096, 1024, 1);
    wg_fence();
#pragma unroll
    for (int kk = 0; kk < 2; kk++) {
      if (N == 80) wg_ss80_01(d, da + kk * 16, db + kk * 128, (kb | kk) != 0);
      if (N == 160) wg_ss160_01(d, da + kk * 16, db + kk * 128, (kb | kk) != 0);
      if (N >= 192) wg_ss192_01(d, da + kk * 16, db + kk * 128, (kb | kk) != 0);
      if (N == 320) wg_ss128_01(d + 96, da + kk * 16, db + kk * 128 + 3 * 256, (kb | kk) != 0);
    }
    wg_commit();
    if (kb == go_at && threadIdx.x == 0) mbar_arrive(go);
    if (kb > 0) { wg_wait<1>(); r.release(prev); }
    prev = r.st;
    r.next();
  }
  wg_wait<0>();
  reg_fence<N / 2>(d);
  r.release(prev);
}

template <int HALF>
__device__ __forceinline__ void attn_a_warp(Ring& r, const uint32_t (&q)[48], int b, int h) {
  constexpr int NT = HALF ? 5 : 3, NF = 8 * NT;
  const int lane = threadIdx.x & 31, g = lane >> 2, c = lane & 3, seg = (threadIdx.x >> 5) & 3;
  uint32_t f[6][NF];
  int slot[6];
  auto fetch = [&](int u) {
    const uint32_t kv = r.wait() + seg * KV_BYTES;
    slot[u] = r.st;
    r.next();
#pragma unroll
    for (int w = 0; w < 4; w++) {
      uint32_t* d = &f[u][2 * NT * w];
#pragma unroll
      for (int t = 0; t <= HALF; t++) {
        if (u < 3) {
          ldsm4(d + 4 * t, kv + w * 1024 + t * 512 + (lane & 8) * 32 + (lane & 16) * 8 + (lane & 7) * 16);
        } else {
          const uint4 v = lds128(kv + w * 1024 + t * 512 + lane * 16);
          d[4 * t] = v.x; d[4 * t + 1] = v.y; d[4 * t + 2] = v.z; d[4 * t + 3] = v.w;
        }
      }
      const uint2 m = lds64(kv + KV_M + w * 256 + lane * 8);
      d[2 * NT - 2] = m.x; d[2 * NT - 1] = m.y;
    }
    pdl_launch();
  };
  float s[NT][4] = {};
  fetch(0);
#pragma unroll
  for (int u = 0; u < 3; u++) {
    fetch(u + 1);
#pragma unroll
    for (int kk = 0; kk < 4; kk++) {
      const uint32_t* a = &q[16 * u + 4 * kk];
#pragma unroll
      for (int n = 0; n < NT; n++) mma16(s[(n + 1) % NT], a[0], a[1], a[2], a[3], f[u][2 * NT * kk + 2 * n], f[u][2 * NT * kk + 2 * n + 1]);
    }
    r.release(slot[u]);
    pdl_launch();
  }
  fetch(4);
  const float k2 = 0.07216878364870322f * 1.44269504089f, NEG = -INFINITY;
  if (2 * c > g) { s[NT - 2][0] = NEG; s[NT - 1][2] = NEG; }
  if (2 * c + 1 > g) { s[NT - 2][1] = NEG; s[NT - 1][3] = NEG; }
  s[NT - 1][0] = s[NT - 1][1] = NEG;
  uint32_t pp[NT][2]; float inv[2];
#pragma unroll
  for (int hh = 0; hh < 2; hh++) {
    float m = NEG, l = 0.f;
#pragma unroll
    for (int n = 0; n < NT; n++) m = fmaxf(m, fmaxf(s[n][2 * hh], s[n][2 * hh + 1]));
    m = fmaxf(m, __shfl_xor_sync(~0u, m, 1)); m = fmaxf(m, __shfl_xor_sync(~0u, m, 2));
#pragma unroll
    for (int n = 0; n < NT; n++) { const float x = ex2((s[n][2 * hh] - m) * k2), y = ex2((s[n][2 * hh + 1] - m) * k2); l += x + y; pp[n][hh] = pack2(x, y); }
    l += __shfl_xor_sync(~0u, l, 1); l += __shfl_xor_sync(~0u, l, 2);
    asm("rcp.approx.ftz.f32 %0, %1;" : "=f"(inv[hh]) : "f"(l));
  }
  uint32_t* dst = g_o + ((b * 192 + h * 6) * 16 + seg * 4 + HALF * 2) * 128 + lane;
#pragma unroll
  for (int u = 3; u < 6; u++) {
    float o[8][4] = {};
#pragma unroll
    for (int n = 0; n < 8; n++) mma8(o[n], pp[0][0], pp[0][1], f[u][2 * NT * (n >> 1) + 2 * NT - 2 + (n & 1)]);
#pragma unroll
    for (int t = 0; t <= HALF; t++)
#pragma unroll
      for (int n = 0; n < 8; n++) {
        const uint32_t* v = &f[u][2 * NT * (n >> 1) + 4 * t + 2 * (n & 1)];
        mma16(o[n], pp[1 + 2 * t][0], pp[1 + 2 * t][1], pp[2 + 2 * t][0], pp[2 + 2 * t][1], v[0], v[1]);
      }
    r.release(slot[u]);
    if (u == 3) fetch(5);
#pragma unroll
    for (int n = 0; n < 8; n++) {
      dst[(u - 3) * 4096 + (n >> 2) * 2048 + (n & 3) * 32] = pack2(o[n][0] * inv[0], o[n][1] * inv[0]);
      dst[(u - 3) * 4096 + (n >> 2) * 2048 + (n & 3) * 32 + 128] = pack2(o[n][2] * inv[1], o[n][3] * inv[1]);
    }
  }
}

template <int NG>
__device__ __forceinline__ void fin_item(Ring& r, uint32_t scratch, int b, int idx) {
  const int warp = threadIdx.x >> 5, lane = threadIdx.x & 31;
  float4* x = g_x + ((b * 16 + idx * NG) * 40 + warp * 5) * 32 + lane;
  float4 v[NG][5];
#pragma unroll
  for (int g = 0; g < NG; g++) {
    const uint32_t base = r.wait();
#pragma unroll
    for (int i = 0; i < 5; i++) v[g][i] = lds128f(base + ((warp * 5 + i) * 32 + lane) * 16);
    r.pop();
  }
#pragma unroll 1
  for (int k = 0; k < op_split(b); k += NG == 1 ? 2 : 1) {
#pragma unroll
    for (int g = 0; g < NG; g += 2) {
      const uint32_t base = r.wait();
#pragma unroll
      for (int i = 0; i < 10; i++) {
        const uint2 q = lds64(base + ((i / 5 * 40 + warp * 5 + i % 5) * 32 + lane) * 8);
        float4& t = v[(g + i / 5) % NG][i % 5];
        t.x += bf_lo(q.x); t.y += bf_hi(q.x); t.z += bf_lo(q.y); t.w += bf_hi(q.y);
      }
      r.pop();
    }
  }
  float mean[NG], rs[NG];
  ln_stats<NG>(v, scratch, mean, rs);
#pragma unroll
  for (int i = 0; i < 5; i++) {
    const int u = warp * 5 + i;
    uint32_t* xn = g_xn + ((b * 20 + (u >> 1)) * 16 + idx * NG) * 128 + (u & 1) * 64 + lane;
#pragma unroll
    for (int g = 0; g < NG; g++) {
      xn[g * 128] = pack2((v[g][i].x - mean[g]) * rs[g], (v[g][i].y - mean[g]) * rs[g]);
      xn[g * 128 + 32] = pack2((v[g][i].z - mean[g]) * rs[g], (v[g][i].w - mean[g]) * rs[g]);
    }
  }
#pragma unroll
  for (int g = 0; g < NG; g++)
#pragma unroll
    for (int i = 0; i < 5; i++) x[(g * 40 + i) * 32] = v[g][i];
}

__global__ void __launch_bounds__(384, 1) post_kernel(const __grid_constant__ PostParams p) {
  extern __shared__ __align__(1024) uint8_t smem_raw[];
  const uint32_t sb = s2u(smem_raw), bars = sb + PS * PB;
  const uint32_t bIF = bars + 128, bIE = bars + 160, done = bars + 192, bGo = bars + 224, slots = bars + 240, scratch = bars + 512;
  const int warp = __shfl_sync(~0u, threadIdx.x >> 5, 0), lane = threadIdx.x & 31;
  TRACE(0);
  pdl_launch();
  if (sb & 1023) __trap();
  if (threadIdx.x < 29) mbar_init(bars + 8 * threadIdx.x, threadIdx.x < 8 ? 1 : threadIdx.x < 16 ? 8 : threadIdx.x < 20 ? 1 : threadIdx.x < 24 ? 2 : threadIdx.x < 28 ? 8 : 1);
  if (threadIdx.x == 32) sts32(slots + 16, p.gap);
  fence_async();
  __syncthreads();
  if (warp >= 8) {
    asm volatile("setmaxnreg.dec.sync.aligned.u32 56;");
    if (warp == 9) {
      const int b = lane & 15;
      bool queries = QA_END < 16 && blockIdx.x < 36;
      for (int n = 0;; n++) {
        if (n > 0) mbar_wait(bGo, (n - 1) & 1);
        mbar_wait(bIE + 8 * (n & 3), ((n >> 2) & 1) ^ 1);
        int code = -1, spin = 0, ticket = 0;
        if (queries) {
          if (lane == 0) ticket = atomicAdd(g_sync + SY_QC, 1);
          ticket = __shfl_sync(~0u, ticket, 0);
          queries = ticket < (16 - QA_END) * 32;
          if (queries) code = IT_Q << 16 | (QA_END + ticket % (16 - QA_END)) << 8 | ticket / (16 - QA_END);
        }
        if (!queries && lane == 0) ticket = atomicAdd(g_sync + SY_T, 1);
        while (!queries) {
          const uint4 hd = ldg_strong128(g_sync + b * 8), pr = ldg_strong128(g_sync + b * 8 + 4);
          const uint32_t hv[4] = {hd.x, hd.y, hd.z, hd.w}, pv[4] = {pr.x, pr.y, pr.z, pr.w};
          const uint32_t chain_done = __ballot_sync(~0u, (pr.x & 0xffff) >= 96) & 0xffff;
          int left[4], avail[4], rdy = 0, claimed = 0, upstream = 0;
#pragma unroll
          for (int t = 0; t < 4; t++) {
            const int cnt = lane < 16 ? item_count(t, b) : 0;
            left[t] = max(cnt - (int)hv[t], 0);
            claimed += cnt - left[t];
            const bool ready = (pv[t] & 0xffff) >= item_need(t, b);
            rdy |= ready << t;
            bool ok = ready || (t == IT_ATT ? pr.x >= 0x10000 : !upstream || (t == IT_OP && (chain_done >> 15 & 1)));
            if (t == IT_BQ && (chain_done >> BQ_HOLD & 1) && !(chain_done >> 15)) ok = false;
            avail[t] = ok ? left[t] : 0;
            upstream |= __any_sync(~0u, left[t] > 0);
          }
          if (!upstream) break;
          int rank = max(__shfl_sync(~0u, ticket, 0) - __reduce_add_sync(~0u, claimed), 0), type = -1, mine = 0;
#pragma unroll
          for (int c = 0; c < 8; c++) {
            const int t = c == 0 || c == 5 ? IT_FIN : c == 1 || c == 7 ? IT_ATT : c == 2 || c == 4 ? IT_OP : IT_BQ;
            int a = c == 1 || ((rdy >> t & 1) == (c < 4)) ? avail[t] : 0;
            if (t == IT_OP && !(p.pol & 1)) a = c == 2 ? avail[t] : 0;
            if (c == 7) a = b < QA_END && !(rdy & 1) && ((chain_done << 1 | 1) >> b & 1) ? left[t] : 0;
            const int tot = __reduce_add_sync(~0u, a);
            if (type < 0) { if (rank < tot) { type = t; mine = a; } else rank -= tot; }
          }
          if (type >= 0) {
#pragma unroll
            for (int o = 1; o < 16; o <<= 1) { const int y = __shfl_up_sync(~0u, mine, o); if (lane >= o) mine += y; }
            const int blk = __ffs(__ballot_sync(~0u, mine > rank)) - 1;
            const int early = !(__shfl_sync(~0u, rdy, blk) >> type & 1);
            uint32_t idx = 0;
            if (lane == 0) { idx = atomicAdd(g_sync + blk * 8 + type, 1); ld_acquire(g_sync + blk * 8 + 4 + type); }
            idx = __shfl_sync(~0u, idx, 0);
            if (idx < item_count(type, blk)) { code = (chain_done >> 15 & 1) << 22 | (chain_done >> p.look & 1) << 21 | early << 20 | type << 16 | blk << 8 | idx; break; }
          } else {
            __nanosleep(50);
          }
          spin_guard(spin);
        }
        if (lane == 0) {
          fence_async_global();
          sts32(slots + 4 * (n & 3), code);
          mbar_arrive(bIF + 8 * (n & 3));
        }
        __syncwarp();
        if (code < 0) break;
      }
    } else if (warp == 8) {
      if (elect()) {
        uint32_t dst = sb, bar = bars, ph = 1, next = clk32(), gap = 0;
        auto acquire = [&](uint32_t kb) {
          mbar_wait(bar + 8 * PS, ph);
          mbar_expect(bar, kb * 1024);
          if (gap) {
            uint32_t now;
            do now = clk32(); while ((int)(now - next) < 0);
            next = ((int)(now - next) > 100 ? now - 100 : next) + kb * gap;
          }
        };
        auto advance = [&]() { dst += PB; bar += 8; if (dst == bars) { dst = sb; bar = bars; ph ^= 1; } };
        auto depend = [&](const uint32_t* c, uint32_t need) { wait_count(c, need); fence_async_global(); };
#pragma unroll 1
        for (int n = 0;; n++) {
          mbar_wait(bIF + 8 * (n & 3), (n >> 2) & 1);
          const int code = (int)lds32(slots + 4 * (n & 3));
          if (code < 0) break;
          const int type = (code >> 16) & 15, b = (code >> 8) & 255, idx = code & 255;
          const bool early = code >> 20 & 1, go = !(code >> 21 & 1);
          mbar_arrive(bIE + 8 * (n & 3));
          gap = !(code >> 22 & 1) ? lds32(slots + 16) : type == IT_ATT || type == IT_FIN ? 0 : p.gap2;
          const uint32_t* progress = g_sync + b * 8 + 4 + type;
          if (type == IT_ATT && b >= QA_END) {
            depend(g_sync + SY_Q, (16 - QA_END) * 32);
#pragma unroll 1
            for (int u = 0; u < 2; u++) { acquire(24); bulk_load_last(dst, g_q + (((b - QA_END) * 32 + idx) * 2 + u) * 1536, 24576, bar); advance(); }
          } else if (type == IT_FIN) {
            const int ng = 16 / fin_items(b), lg = ng >> 1;
#pragma unroll 1
            for (int g = 0; g < ng; g++) { acquire(20); bulk_load(dst, g_x + (b * 16 + idx * ng + g) * 1280, 20480, bar); advance(); }
            if (early) depend(progress, item_need(type, b));
            if (go) mbar_arrive(bGo);
#pragma unroll 1
            for (int i = 0; i < op_split(b) * ng; i += 2) {
              const uint2* src = g_part + ((b * 16 + (i >> lg)) * 16 + idx * ng + (i & (ng - 1))) * 1280;
              acquire(20);
              bulk_load_last(dst, src, ng > 1 ? 20480 : 10240, bar);
              if (ng == 1) bulk_load_last(dst + 10240, src + 16 * 1280, 10240, bar);
              advance();
            }
          } else {
            const bool op = type == IT_OP, bq = type == IT_BQ;
            const int width = op ? op_width(b) : bq ? bq_width(b) : 192, nb = (width + 63) >> 6, lt = width == 320 ? 1 : 2;
            const int nst = op ? 192 / op_split(b) : 20, kb0 = op ? (idx >> lt) * nst : 0;
            const int col = (op ? idx & ((1 << lt) - 1) : idx) * width;
            const bool whole = !(width & 63);
            const CUtensorMap* m = op ? (whole ? &p.wo : &p.wo2) : bq ? (whole ? &p.wb : &p.wb2) : &p.wq;
            const uint32_t* a = op ? g_o + (b * 192 + kb0) * 2048 : g_xn + b * 20 * 2048;
            int row = kb0 * 32, pre = early && (op || bq) ? min(nst, PS) : 0;
            auto weights = [&]() {
              acquire(8 + nb * 4);
              if (whole) {
                tma_load3z(dst + 8192, m, row, col >> 6, bar);
              } else {
                tma_load(dst + 8192, m, col, row, bar); tma_load(dst + 12288, m, col + 64, row, bar);
                if (nb == 3) tma_load(dst + 16384, m, col + 128, row, bar);
              }
              row += 32;
            };
            if (pre) {
              uint32_t da = dst, ba = bar;
#pragma unroll 1
              for (int kb = 0; kb < pre; kb++) { weights(); advance(); }
              depend(progress, item_need(type, b));
#pragma unroll 1
              for (int kb = 0; kb < pre; kb++) {
                bulk_load(da, a, 8192, ba);
                a += 2048; da += PB; ba += 8;
                if (da == bars) { da = sb; ba = bars; }
              }
            }
#pragma unroll 1
            for (int kb = pre; kb < nst; kb++) { weights(); if (op && OEF) bulk_load_last(dst, a, 8192, bar); else bulk_load(dst, a, 8192, bar); a += 2048; advance(); }
          }
          if (type == IT_ATT) {
            if (early) depend(progress, 96);
            if (go) mbar_arrive(bGo);
            const uint8_t* src = g_kv + (size_t)(idx * 6 * NSEG + b * 4) * KV_BYTES;
#pragma unroll 1
            for (int u = 0; u < 6; u++) {
              acquire(20);
              bulk_load_last(dst, src, 20480, bar);
              src += u == 2 ? -3 * KV_V : 2 * KV_V;
              advance();
            }
          }
        }
      }
    } else if (warp == 11) {
      uint32_t smid, nsm, used = 0;
      asm("mov.u32 %0, %%smid;" : "=r"(smid)); asm("mov.u32 %0, %%nsmid;" : "=r"(nsm));
      for (int n = 0; n < 64 && used < 96; n++) {
        uint32_t peers = 0;
        used = 0;
        for (uint32_t i = lane; i < min(nsm, 256u); i += 32) {
          const bool taken = ldg_strong32(g_smuse + i) == p.layer + 1;
          used += taken;
          peers += abs((int)(g_smclk[i] - g_smclk[smid & 255])) < 4000 && !taken;
        }
        used = __reduce_add_sync(~0u, used);
        sts32(slots + 16, max(p.gap, (int)min(__reduce_add_sync(~0u, peers), 18u) * p.share >> 3));
      }
    } else if (warp == 10 && lane == 0) {
      for (int n = 0;; n++) {
        mbar_wait(bIF + 8 * (n & 3), (n >> 2) & 1);
        const int code = (int)lds32(slots + 4 * (n & 3));
        if (code < 0) break;
        const int type = (code >> 16) & 15, b = (code >> 8) & 255;
        mbar_wait(done + 8 * (n & 3), (n >> 2) & 1);
        if (type != IT_BQ) red_release(type == IT_Q ? g_sync + SY_Q : g_sync + b * 8 + 5 + type, 1);
        mbar_arrive(bIE + 8 * (n & 3));
      }
    }
  } else {
    asm volatile("setmaxnreg.inc.sync.aligned.u32 224;");
    const int g = lane >> 2, c = lane & 3;
    Ring r = {sb, bars, 0, 0};
#pragma unroll 1
    for (int n = 0;; n++) {
      mbar_wait(bIF + 8 * (n & 3), (n >> 2) & 1);
      const int code = __shfl_sync(~0u, (int)lds32(slots + 4 * (n & 3)), 0);
      if (code < 0) { TRACE(2); break; }
      const int type = (code >> 16) & 15, b = (code >> 8) & 255, idx = code & 255;
      ITEM(code & 0xfffff, 0);
      if (type == IT_ATT || type == IT_Q) {
        uint32_t q[48];
        if (type == IT_Q || b < QA_END) {
          float d[96] = {};
          reg_fence<96>(d);
          gemm_item<192>(r, d, 20, bGo, type == IT_Q ? 12 : -1);
#pragma unroll
          for (int i = 0; i < 48; i++) q[i] = pack2(d[2 * i], d[2 * i + 1]);
        } else {
#pragma unroll
          for (int u = 0; u < 2; u++) {
            const uint32_t base = r.wait() + threadIdx.x * 16;
#pragma unroll
            for (int i = 0; i < 6; i++) {
              const uint4 v = lds128(base + i * 4096);
              q[24 * u + 4 * i] = v.x; q[24 * u + 4 * i + 1] = v.y; q[24 * u + 4 * i + 2] = v.z; q[24 * u + 4 * i + 3] = v.w;
            }
            r.pop();
          }
        }
        if (type == IT_Q) {
          uint4* dst = g_q + ((b - QA_END) * 32 + idx) * 3072 + threadIdx.x;
#pragma unroll
          for (int i = 0; i < 12; i++) dst[i * 256] = make_uint4(q[4 * i], q[4 * i + 1], q[4 * i + 2], q[4 * i + 3]);
        } else if (warp < 4) {
          attn_a_warp<0>(r, q, b, idx);
        } else {
          attn_a_warp<1>(r, q, b, idx);
        }
      } else if (type == IT_FIN) {
        if (fin_items(b) == 4) fin_item<4>(r, scratch, b, idx);
        else if (fin_items(b) == 8) fin_item<2>(r, scratch, b, idx);
        else fin_item<1>(r, scratch, b, idx);
      } else {
        float d[160] = {};
        reg_fence<160>(d);
        const int width = type == IT_OP ? op_width(b) : bq_width(b), nst = type == IT_OP ? 192 / op_split(b) : 20;
        const int go_at = code >> 21 & 1 ? -1 : max(nst - 6, 0);
        if (width == 320) gemm_item<320>(r, d, nst, bGo, go_at);
        else if (width == 160 || BQ_80 == 16) gemm_item<160>(r, d, nst, bGo, go_at);
        else gemm_item<80>(r, d, nst, bGo, go_at);
        reg_fence<160>(d);
        if (type == IT_OP) {
          const int tiles = DM / width;
          uint2* dst = g_part + (((b * 16 + idx / tiles) * 16 + warp * 2) * 40 + idx % tiles * (width / 16)) * 32 + lane;
#pragma unroll
          for (int u = 0; u < 20; u++) {
            if (u % 5 == 0 && u * 16 >= width) break;
            dst[u * 32] = make_uint2(pack2(d[8 * u], d[8 * u + 1]), pack2(d[8 * u + 4], d[8 * u + 5]));
            dst[(40 + u) * 32] = make_uint2(pack2(d[8 * u + 2], d[8 * u + 3]), pack2(d[8 * u + 6], d[8 * u + 7]));
          }
        } else {
          const int row = b * 128 + warp * 16 + g;
          const int h0 = idx * (width / 20);
          const float sc = h0 < 32 ? 0.22360679775f * 1.44269504089f : 1.f;
          const bool lo = c < 2;
          uint32_t* da = g_bqkv + (h0 * 256 + (row >> 3)) * 96 + lane;
          uint32_t* db = da + 256 * 96 + (lo ? 2 : -2);
          uint32_t pad[2];
#pragma unroll
          for (int rr = 0; rr < 2; rr++) pad[rr] = c & 1 || h0 < 32 ? 0u : h0 >= 64 ? 0x00003f80u : poly_group((row >> 3) + rr) ? 0x3f803f80u : 0u;
#pragma unroll
          for (int q = 0; q < 8; q++) {
            if (!(q & 1) && q * 40 >= width) break;
#pragma unroll
            for (int rr = 0; rr < 2; rr++) {
              uint32_t w[5];
#pragma unroll
              for (int i = 0; i < 5; i++) w[i] = pack2(d[20 * q + 4 * i + 2 * rr] * sc, d[20 * q + 4 * i + 2 * rr + 1] * sc);
              const int o = q * 2 * 256 * 96 + rr * 96;
              da[o] = w[0]; da[o + 32] = w[1]; da[o + 64] = lo ? w[2] : pad[rr];
              db[o] = lo ? w[3] : w[2]; db[o + 32] = lo ? w[4] : w[3]; db[o + 64] = lo ? pad[rr] : w[4];
            }
          }
        }
      }
      __syncwarp();
      if (lane == 0) mbar_arrive(done + 8 * (n & 3));
      if ((code >> 21 & 1) && threadIdx.x == 128) mbar_arrive(bGo);
      ITEM(code & 0xfffff, 1);
    }
  }
}

constexpr int AB_SMEM = 1024 + 98304 + 51200 + 4 * 16384 + 256 + 10240;
#define AB_LW 1
#define AB_U 8
#define AB_WG 4
constexpr int AB_T = AB_WG * 128, AB_PASS = 8 / AB_WG;
__device__ __forceinline__ uint32_t fma2(uint32_t a, uint32_t b, uint32_t c) { uint32_t r; asm("fma.rn.bf16x2 %0, %1, %2, %3;" : "=r"(r) : "r"(a), "r"(b), "r"(c)); return r; }
__device__ __forceinline__ uint32_t ex2_pair(float a, float b, uint32_t one, uint32_t c0) {
  const uint32_t e = __byte_perm(__float_as_uint(a), __float_as_uint(b), 0x6521);
  uint32_t x, r;
  asm("lop3.b32 %0, %1, 0x007f007f, %2, 0xEA;" : "=r"(x) : "r"(e), "r"(one));
  const uint32_t m = AB_DEG == 3 ? fma2(fma2(fma2(c0, x, 0xbbdcbbdcu), x, 0x3ef53ef5u), x, 0x3ee83ee8u) : fma2(fma2(c0, x, 0xbc43bc43u), x, 0x3f2e3f2eu);
  asm("lop3.b32 %0, %1, %2, 0x7f807f80, 0xE4;" : "=r"(r) : "r"(e), "r"(m));
  return r;
}
__device__ __forceinline__ float sq2(uint32_t w) { const float a = bf_lo(w), b = bf_hi(w); return fmaf(a, a, b * b); }

__device__ __forceinline__ void attn_b_store(const float* o, int h, int row0, int lane) {
  const int g = lane >> 2, c = lane & 3;
  const float i0 = __frcp_rn(__shfl_sync(~0u, o[8], (lane & ~3) | 2)), i1 = __frcp_rn(__shfl_sync(~0u, o[10], (lane & ~3) | 2));
#pragma unroll
  for (int jj = 0; jj < 3; jj++) {
    if (jj < 2 || c < 2) {
      const int col = h * 20 + 8 * jj + 2 * c;
      uint32_t* dst = g_of + (((row0 >> 7) * 10 + (col >> 6)) * 16 + (row0 >> 3 & 15)) * 256 + (col >> 3 & 7) * 32 + g * 4 + (col >> 1 & 3);
      dst[0] = pack2(o[4 * jj] * i0, o[4 * jj + 1] * i0);
      dst[256] = pack2(o[4 * jj + 2] * i1, o[4 * jj + 3] * i1);
    }
  }
}

struct AbParams { Weights next; uint32_t* done; uint32_t* out; };
__global__ void __launch_bounds__(AB_T + 32, 1) attn_b_kernel(const __grid_constant__ AbParams p) {
  extern __shared__ uint8_t smem_raw[];
  const uint32_t sb = (s2u(smem_raw) + 1023) & ~1023u, sK = sb, sV = sb + 98304, bars = sV + 51200 + 4 * 16384;
  const uint32_t bF = bars + 64, bW = bars + 72, bA = bars + 80, bE = bars + 128, smax = bars + 176;
  auto ring = [&](int i) { return i < 2 ? sK + 51200 + i * 16384 : sV + 51200 + (i - 2) * 16384; };
  const int warp = __shfl_sync(~0u, threadIdx.x >> 5, 0), lane = threadIdx.x & 31;
  const int h = blockIdx.x >> 2, quarter = blockIdx.x & 3;
  TRACE(0);
  pdl_launch();
  if (threadIdx.x < 22) mbar_init(bars + 8 * threadIdx.x, threadIdx.x == 8 ? AB_T / 32 : threadIdx.x >= 16 ? 8 : 1);
  if (threadIdx.x == 32) sts64(smax, 0, 0);
  fence_async();
  __syncthreads();
  pdl_wait();
  const int blk = quarter * 4 + (h >> 3), cg = h & 7;
  auto unsafe = [&]() { const float2 m = lds64f(smax); return !(m.x * m.y <= 10000.f); };
  if (warp == AB_T / 32) {
    auto load_w = [&]() {
      mbar_expect(bW, 102400);
      for (int i = 0; i < 4; i++) bulk_load((i < 2 ? sK : sV) + (i & 1) * 25600, g_wb + cg * 6400 + i * 1600, 25600, bW);
    };
    if (elect()) {
      const uint32_t* gk = g_bqkv + (32 + h) * 256 * 96;
#pragma unroll 1
      for (int i = 0; i < 8; i++) {
        if (i >= AB_LW) mbar_wait(bars + 8 * (i - AB_LW), 0);
        mbar_expect(bars + 8 * i, 24576);
        bulk_load_last(sK + i * 12288, gk + i * 3072, 12288, bars + 8 * i);
        bulk_load_last(sV + i * 12288, gk + 32 * 256 * 96 + i * 3072, 12288, bars + 8 * i);
      }
    }
    __syncwarp();
    if (blockIdx.x < NSLOT) for (int i = lane; i < 512; i += 32) reinterpret_cast<uint4*>(pool_at(blockIdx.x * 8192))[i] = make_uint4(0, 0, 0, 0);
    if (blockIdx.x == 127) for (int i = lane; i < SY_N; i += 32) g_sync[i] = 0;
    if (p.next.w[0] && lane == 0) {
      for (int i = 0; i < AB_PF; i++) { const uint32_t t0 = clk32(); while (clk32() - t0 < (i ? AB_PFD : AB_PF0)) __nanosleep(200); prefetch_weights(p.next, i); }
    }
    __syncwarp();
    mbar_wait(bF, 0);
    const bool redo = unsafe();
    if (!redo && lane == 0) load_w();
    if (lane < 16) asm volatile("cp.async.bulk.prefetch.L2.global [%0], 2560;" :: "l"(g_x + ((blk * 16 + lane) * 40 + cg * 5) * 32) : "memory");
    __syncwarp();
    bar_sync(1, AB_T + 32);
    if (lane == 0) {
      ABT(!!p.out, 1);
      red_release(p.done + quarter * 32, 1);
      ABT(!!p.out, 2);
      if (redo) load_w();
      wait_count(p.done + quarter * 32, 32);
      fence_async_global();
      ABT(!!p.out, 3);
      for (int kb = 0; kb < 10; kb++) {
        const int i = kb < 6 ? kb : kb - 6;
        if (kb >= 6) mbar_wait(bE + 8 * i, 0);
        mbar_expect(bA + 8 * i, 16384);
        bulk_load(ring(i), g_of + (blk * 10 + kb) * 4096, 16384, bA + 8 * i);
      }
    }
    return;
  }
  float qmax = 0.f;
  const uint32_t one = opaque(0x3f803f80u + (threadIdx.x >> 10)), c0 = opaque((AB_DEG == 3 ? 0x3d9f3d9fu : 0x3eac3eacu) + (threadIdx.x >> 10));
#pragma unroll 1
  for (int pass = 0; pass < AB_PASS; pass++) {
    const int row0 = quarter * 512 + ((warp >> 2) * AB_PASS + pass) * 64 + (warp & 3) * 16;
    const uint32_t* gq = g_bqkv + (h * 256 + (row0 >> 3)) * 96 + lane;
    const uint32_t q0 = gq[0], q1 = gq[96], q2 = gq[32], q3 = gq[128];
    uint32_t q4 = gq[64], q5 = gq[160];
    const uint32_t z0 = gq[64 + 3 - (lane & 3)], z1 = gq[160 + 3 - (lane & 3)];
    {
      float n0 = sq2(q0) + sq2(q2) + sq2(q4), n1 = sq2(q1) + sq2(q3) + sq2(q5);
      n0 += __shfl_xor_sync(~0u, n0, 1); n1 += __shfl_xor_sync(~0u, n1, 1);
      n0 += __shfl_xor_sync(~0u, n0, 2); n1 += __shfl_xor_sync(~0u, n1, 2);
      qmax = (n0 > qmax || n0 != n0) ? n0 : qmax;
      qmax = (n1 > qmax || n1 != n1) ? n1 : qmax;
    }
    if (pass == AB_PASS - 1) {
      float kmax = 0.f;
#pragma unroll
      for (int i = 0; i < SEQ / AB_T; i++) {
        const int key = threadIdx.x + AB_T * i;
        const uint32_t a = sK + (key >> 3) * 384 + (key & 7) * 16;
        const uint4 x = lds128(a), y = lds128(a + 128);
        const uint2 z = lds64(a + 256);
        const float n = ((sq2(x.x) + sq2(x.y)) + (sq2(x.z) + sq2(x.w))) + ((sq2(y.x) + sq2(y.y)) + (sq2(y.z) + sq2(y.w))) + (sq2(z.x) + sq2(z.y));
        kmax = (n > kmax || n != n) ? n : kmax;
      }
      const uint32_t kb = __reduce_max_sync(~0u, __float_as_uint(kmax) & 0x7fffffffu), qb = __reduce_max_sync(~0u, __float_as_uint(qmax) & 0x7fffffffu);
      if (lane < 2) asm volatile("red.shared.max.u32 [%0], %1;" :: "r"(smax + 4 * lane), "r"(lane ? kb : qb) : "memory");
      __syncwarp();
    }
    if ((lane & 3) == 2) { q4 = 0xBF8043C0u; q5 = 0xBF8043C0u; }
    float o[12];
    auto desc = [](uint32_t lo, uint32_t hi) { uint64_t d; asm("mov.b64 %0, {%1, %2};" : "=l"(d) : "r"(lo), "r"(hi)); return d; };
    const uint32_t k0 = (uint32_t)mkdesc(sK, 128, 0, 0), k1 = (uint32_t)mkdesc(sK + 256, 0, 0, 0), v0 = (uint32_t)mkdesc(sV, 384, 0, 0);
    float sa[16], sb2[16];
    uint32_t pa[8], pb[8];
    auto qk = [&](float* s, uint32_t t) {
      wg_rs32_00(s, q0, q1, q2, q3, desc(k0 + t, 24), 0);
      wg_rs32_00(s, q4, q5, z0, z1, desc(k1 + t, 24), 1);
      wg_commit();
    };
    auto step = [&](float* s, uint32_t* pp, int g0, uint32_t t, uint32_t nx, int acc) {
      wg_wait<1>();
      reg_fence<16>(s);
#pragma unroll
      for (int i = 0; i < 8; i++) pp[i] = poly_group(g0 + (i >> 1)) ? ex2_pair(s[2 * i], s[2 * i + 1], one, c0) : pack2(ex2(s[2 * i]), ex2(s[2 * i + 1]));
      wg_fence();
      wg_rs24_01(o, pp[0], pp[1], pp[2], pp[3], desc(v0 + t, 8), acc);
      wg_rs24_01(o, pp[4], pp[5], pp[6], pp[7], desc(v0 + t + 48, 8), 1);
      qk(s, nx);
    };
    if (pass == 0) mbar_wait(bars, 0);
    wg_fence();
    qk(sa, 0);
    qk(sb2, 96);
#pragma unroll 1
    for (uint32_t t = 0; t < 64 * 96; t += AB_U * 96) {
      const uint32_t nx = t + AB_U * 96 < 64 * 96 ? t + AB_U * 96 : 0;
      if (pass == AB_PASS - 1 && t == 40 * 96 && lane == 0) mbar_arrive(bF);
#pragma unroll
      for (int u = 0; u < AB_U; u += 2) {
        if (u == AB_U - 2 && pass == 0) mbar_wait(bars + 8 * (nx / 768), 0);
        step(sa, pa, 0, t + u * 96, u + 2 < AB_U ? t + (u + 2) * 96 : nx, u | t);
        step(sb2, pb, 4, t + u * 96 + 96, (u + 2 < AB_U ? t + (u + 2) * 96 : nx) + 96, 1);
      }
    }
    wg_wait<0>();
    reg_fence<12>(o); reg_fence<16>(sa); reg_fence<16>(sb2);
    attn_b_store(o, h, row0, lane);
  }
  mbar_wait(bF, 0);
  if (unsafe())
#pragma unroll 1
  for (int pass = 0; pass < AB_PASS; pass++) {
    const int row0 = quarter * 512 + ((warp >> 2) * AB_PASS + pass) * 64 + (warp & 3) * 16;
    const uint32_t* gq = g_bqkv + (h * 256 + (row0 >> 3)) * 96 + lane;
    const uint32_t q0 = gq[0], q1 = gq[96], q2 = gq[32], q3 = gq[128], q4 = gq[64], q5 = gq[160];
    float o[12];
#pragma unroll
    for (int i = 0; i < 12; i++) o[i] = 0.f;
    float m0 = -INFINITY, m1 = -INFINITY;
#pragma unroll 1
    for (int kt = 0; kt < 32; kt++) {
      float s[32];
      const uint64_t dk = mkdesc(sK + kt * 3072, 128, 384, 0), dk2 = mkdesc(sK + kt * 3072 + 256, 0, 384, 0);
      wg_fence();
      wg_rs64_00(s, q0, q1, q2, q3, dk, 0);
      wg_rs64_00(s, q4, q5, 0, 0, dk2, 1);
      wg_commit();
      wg_wait<0>();
      reg_fence<32>(s); reg_fence<12>(o);
      float n0 = m0, n1 = m1;
#pragma unroll
      for (int jj = 0; jj < 8; jj++) { n0 = fmaxf(n0, fmaxf(s[4 * jj], s[4 * jj + 1])); n1 = fmaxf(n1, fmaxf(s[4 * jj + 2], s[4 * jj + 3])); }
      n0 = fmaxf(n0, __shfl_xor_sync(~0u, n0, 1)); n0 = fmaxf(n0, __shfl_xor_sync(~0u, n0, 2));
      n1 = fmaxf(n1, __shfl_xor_sync(~0u, n1, 1)); n1 = fmaxf(n1, __shfl_xor_sync(~0u, n1, 2));
      const float r0 = ex2(m0 - n0), r1 = ex2(m1 - n1);
      m0 = n0; m1 = n1;
#pragma unroll
      for (int jj = 0; jj < 3; jj++) { o[4 * jj] *= r0; o[4 * jj + 1] *= r0; o[4 * jj + 2] *= r1; o[4 * jj + 3] *= r1; }
      uint32_t pp[16];
#pragma unroll
      for (int jj = 0; jj < 8; jj++) {
        pp[2 * jj] = pack2(ex2(s[4 * jj] - m0), ex2(s[4 * jj + 1] - m0));
        pp[2 * jj + 1] = pack2(ex2(s[4 * jj + 2] - m1), ex2(s[4 * jj + 3] - m1));
      }
      const uint64_t dv = mkdesc(sV + kt * 3072, 384, 128, 0);
      wg_fence();
#pragma unroll
      for (int kk = 0; kk < 4; kk++) wg_rs24_01(o, pp[4 * kk], pp[4 * kk + 1], pp[4 * kk + 2], pp[4 * kk + 3], dv + kk * 48, 1);
      wg_commit();
    }
    wg_wait<0>();
    reg_fence<12>(o);
    attn_b_store(o, h, row0, lane);
  }
  ABT(!!p.out, 0);
  bar_arrive(1, AB_T + 32);
  if (warp >= 12) return;
  const int g = lane >> 2, c = lane & 3;
  const bool live = opaque(threadIdx.x) < 256;
  float d[40] = {};
  float4* x = g_x + ((blk * 16 + warp * 2) * 40 + cg * 5) * 32 + lane;
  if (warp < 8) {
#pragma unroll
  for (int i = 0; i < 10; i++) {
    const int r = i / 5, u = i % 5;
    const float4 t = x[(r * 40 + u) * 32];
    d[8 * u + 2 * r] = t.x; d[8 * u + 2 * r + 1] = t.y; d[8 * u + 4 + 2 * r] = t.z; d[8 * u + 5 + 2 * r] = t.w;
  }
  mbar_wait(bW, 0);
  reg_fence<40>(d);
  ABT(!!p.out, 4);
#pragma unroll 1
  for (int kb = 0; kb < 10; kb++) {
    const int i = kb < 6 ? kb : kb - 6;
    mbar_wait(bA + 8 * i, kb >= 6);
    const uint64_t da = mkdesc(ring(i) + (warp >> 2) * 8192, 128, 1024, 0), db = mkdesc(kb < 5 ? sK + kb * 10240 : sV + (kb - 5) * 10240, 1280, 128, 0);
    wg_fence();
#pragma unroll
    for (int kk = 0; kk < 4; kk++) wg_ss80_01(d, da + kk * 16, db + kk * 160, 1);
    wg_commit();
    if (kb > 0 && kb < 5) { wg_wait<1>(); if (lane == 0) mbar_arrive(bE + 8 * (kb - 1)); }
  }
  wg_wait<0>();
  reg_fence<40>(d);
  }
  ABT(!!p.out, 5);
  if (p.out) {
    if (warp >= 8) return;
    const uint32_t stage = sK + 83968 + warp * 2560 + (warp < 4 ? 0 : 131328 - 10240);
#pragma unroll
    for (int u = 0; u < 5; u++)
      stsm4(stage + (lane & 15) * 160 + u * 32 + (lane >> 4) * 16, pack2(d[8 * u], d[8 * u + 1]), pack2(d[8 * u + 2], d[8 * u + 3]),
            pack2(d[8 * u + 4], d[8 * u + 5]), pack2(d[8 * u + 6], d[8 * u + 7]));
    __syncwarp();
    uint4* out = reinterpret_cast<uint4*>(p.out + (blk * 128 + warp * 16) * (DM / 2) + cg * 40);
#pragma unroll
    for (int i = 0; i < 5; i++) { const int e = i * 32 + lane, r = e / 10; out[r * (DM / 8) + e - r * 10] = lds128(stage + e * 16); }
  } else {
    float2* stat = g_stat + blk * 1024 + (warp & 7) * 16 + g;
    float mean[2], rs[2];
#pragma unroll
    for (int r = 0; r < 2; r++) {
      float t = 0.f, q = 0.f;
#pragma unroll
      for (int i = 0; i < 10; i++) t += d[4 * i + 2 * r] + d[4 * i + 2 * r + 1];
      t += __shfl_xor_sync(~0u, t, 1); t += __shfl_xor_sync(~0u, t, 2);
      t *= 1.f / 80;
#pragma unroll
      for (int i = 0; i < 10; i++) { const float a = d[4 * i + 2 * r] - t, b = d[4 * i + 2 * r + 1] - t; q += a * a + b * b; }
      q += __shfl_xor_sync(~0u, q, 1); q += __shfl_xor_sync(~0u, q, 2);
      if (c == r && live) asm volatile("st.relaxed.gpu.global.v2.b32 [%0], {%1, %2};" :: "l"(stat + cg * 128 + r * 8), "r"(__float_as_uint(t)), "r"(nz(__float_as_uint(q))) : "memory");
    }
#pragma unroll
    for (int i = 0; i < 10; i++) {
      const int r = i / 5, u = i % 5;
      if (live) x[(r * 40 + u) * 32] = make_float4(d[8 * u + 2 * r], d[8 * u + 2 * r + 1], d[8 * u + 4 + 2 * r], d[8 * u + 5 + 2 * r]);
    }
    ABT(0, 6);
    uint2 e[4];
    int n = 0;
    do {
#pragma unroll
      for (int i = 0; i < 4; i++)
        asm volatile("ld.relaxed.gpu.global.v2.b32 {%0, %1}, [%2];" : "=r"(e[i].x), "=r"(e[i].y) : "l"(stat + (2 * c + (i & 1)) * 128 + (i >> 1) * 8) : "memory");
      spin_guard(n);
    } while (__any_sync(~0u, min(min(e[0].y, e[1].y), min(e[2].y, e[3].y)) == 0 && live));
#pragma unroll
    for (int r = 0; r < 2; r++) {
      const float m0 = __uint_as_float(e[2 * r].x), m1 = __uint_as_float(e[2 * r + 1].x);
      float t = m0 + m1;
      t += __shfl_xor_sync(~0u, t, 1); t += __shfl_xor_sync(~0u, t, 2);
      t *= 0.125f;
      float q = __uint_as_float(e[2 * r].y) + __uint_as_float(e[2 * r + 1].y) + 80.f * ((m0 - t) * (m0 - t) + (m1 - t) * (m1 - t));
      q += __shfl_xor_sync(~0u, q, 1); q += __shfl_xor_sync(~0u, q, 2);
      mean[r] = t; rs[r] = rsqrtf(q * (1.f / DM) + 1e-5f);
    }
    ABT(0, 7);
    uint32_t w[2][5][2];
#pragma unroll
    for (int i = 0; i < 20; i++) w[i & 1][i >> 2][i >> 1 & 1] = pack2((d[2 * i] - mean[i & 1]) * rs[i & 1], (d[2 * i + 1] - mean[i & 1]) * rs[i & 1]);
    ln_store(w, blk * 8 + warp, cg * 5, live);
  }
  ABT(!!p.out, 8);
  TRACE(2);
}

typedef CUresult (*EncodeFn)(CUtensorMap*, CUtensorMapDataType, cuuint32_t, void*, const cuuint64_t*, const cuuint64_t*,
                             const cuuint32_t*, const cuuint32_t*, CUtensorMapInterleave, CUtensorMapSwizzle,
                             CUtensorMapL2promotion, CUtensorMapFloatOOBfill);

void make_map(EncodeFn enc, CUtensorMap* m, const void* ptr, int cols, int rows, int nb) {
  const cuuint64_t dims[3] = {(cuuint64_t)(nb ? 64 : cols), (cuuint64_t)rows, (cuuint64_t)cols / 64};
  const cuuint64_t strides[2] = {(cuuint64_t)cols * 2, 128};
  const cuuint32_t box[3] = {64, 32, (cuuint32_t)nb}, es[3] = {1, 1, 1};
  enc(m, CU_TENSOR_MAP_DATA_TYPE_BFLOAT16, nb ? 3 : 2, const_cast<void*>(ptr), dims, strides, box, es, CU_TENSOR_MAP_INTERLEAVE_NONE,
      CU_TENSOR_MAP_SWIZZLE_128B, CU_TENSOR_MAP_L2_PROMOTION_L2_128B, CU_TENSOR_MAP_FLOAT_OOB_FILL_NONE);
}
template <class... KA, class... A>
void launch(void (*kern)(KA...), int grid, int block, int smem, int cluster, bool pdl, A... args) {
  cudaFuncSetAttribute(kern, cudaFuncAttributeMaxDynamicSharedMemorySize, smem);
  cudaLaunchConfig_t cfg = {};
  cfg.gridDim = dim3(grid); cfg.blockDim = dim3(block); cfg.dynamicSmemBytes = smem; cfg.stream = cudaStreamPerThread;
  cudaLaunchAttribute at[2];
  int n = 0;
  if (cluster > 1) { at[n].id = cudaLaunchAttributeClusterDimension; at[n].val.clusterDim.x = cluster; at[n].val.clusterDim.y = 1; at[n].val.clusterDim.z = 1; n++; }
  if (pdl) { at[n].id = cudaLaunchAttributeProgrammaticStreamSerialization; at[n].val.programmaticStreamSerializationAllowed = 1; n++; }
  cfg.attrs = at; cfg.numAttrs = n;
  cudaLaunchKernelEx(&cfg, kern, args...);
}
template <class T> void* sym(T& s) { void* p = nullptr; cudaGetSymbolAddress(&p, s); return p; }

}

#define MODE(b) 0
extern "C" void kernel_launch(void* const* d_in, const int* in_sizes, int n_in, void* d_out, int out_size) {
  const __nv_bfloat16* x = (const __nv_bfloat16*)d_in[0];
  void* fn = nullptr; cudaDriverEntryPointQueryResult qr;
  cudaGetDriverEntryPoint("cuTensorMapEncodeTiled", &fn, cudaEnableDefault, &qr);
  EncodeFn enc = (EncodeFn)fn;

  ChainParams ch = {};
  PostParams op = {};
  for (int i = 0; i < 3; i++) {
    const cuuint64_t dims[3] = {HD, 128, 5}, strides[2] = {HD * 2, HD * 256};
    const cuuint32_t box[3] = {64, 128, 5}, es[3] = {1, 1, 1};
    enc(i == 0 ? &ch.wq : i == 1 ? &ch.wk : &ch.wv, CU_TENSOR_MAP_DATA_TYPE_BFLOAT16, 3, d_in[2 + i], dims, strides, box, es, CU_TENSOR_MAP_INTERLEAVE_NONE,
        CU_TENSOR_MAP_SWIZZLE_128B, W_PROMO, CU_TENSOR_MAP_FLOAT_OOB_FILL_NONE);
  }
  {
    const cuuint64_t dims[3] = {DM, HD, 7}, strides[2] = {DM * 2, 64};
    const cuuint32_t box[3] = {32, 64, 7}, es[3] = {1, 1, 1};
    enc(&ch.wo, CU_TENSOR_MAP_DATA_TYPE_BFLOAT16, 3, d_in[5], dims, strides, box, es, CU_TENSOR_MAP_INTERLEAVE_NONE,
        CU_TENSOR_MAP_SWIZZLE_64B, CU_TENSOR_MAP_L2_PROMOTION_L2_128B, CU_TENSOR_MAP_FLOAT_OOB_FILL_NONE);
  }
  ch.mem0 = (const __nv_bfloat16*)d_in[1];
  ch.pool = (uint8_t*)(((uintptr_t)sym(g_pool) + 8191) & ~(uintptr_t)8191); ch.kv = (uint8_t*)sym(g_kv); ch.xc = (const uint32_t*)sym(g_xc); ch.sync = (uint32_t*)sym(g_sync);
  ch.d1 = 0; ch.d1b = 0; ch.d2 = 0; ch.d2b = 0;
  make_map(enc, &op.wq, d_in[2], HD, DM, 3);
  make_map(enc, &op.wo, d_in[5], DM, HD, 5); make_map(enc, &op.wo2, d_in[5], DM, HD, 0);
  make_map(enc, &op.wb, d_in[8], 1920, DM, 5); make_map(enc, &op.wb2, d_in[8], 1920, DM, 0);
  op.gap = 17; op.share = 20; op.look = 14; op.gap2 = 0; op.pol = 0;

  const Weights wa = {{(const uint8_t*)d_in[3], (const uint8_t*)d_in[4], (const uint8_t*)d_in[2], (const uint8_t*)d_in[5]}}, none = {};
  launch(first_kernel, 132, 256, 128 * 1024, 1, false, x, (const uint4*)d_in[9], wa);
  for (int layer = 0; layer < 2; layer++) {
    ch.layer = ch.d2b = op.layer = layer;
    launch(chain_kernel, 96, 256, CH_SMEM, 3, true, ch);
    launch(post_kernel, MODE(3) ? 36 : 132, 384, OP_SMEM, 1, !MODE(1), op);
    const AbParams ab = {layer == 0 ? wa : none, (uint32_t*)sym(g_bo) + layer * 128, layer == 0 ? nullptr : (uint32_t*)d_out};
    launch(attn_b_kernel, 128, AB_T + 32, AB_SMEM, 1, true, ab);
  }
}
```

```cpp
#include <cuda_runtime.h>
#include <cuda_bf16.h>
#include <cuda.h>
#include <stdint.h>

namespace {

constexpr int SEQ = 2048, DM = 640, HD = 6144, NSEG = 64;
constexpr int SPIN_LIMIT = 1 << 20;

__device__ __align__(128) float4 g_x[SEQ * DM / 4];
__device__ __align__(128) uint32_t g_of[SEQ * DM / 2];
__device__ __align__(128) uint4 g_wb[DM * DM / 8];
__device__ __align__(16) float2 g_stat[16 * 8 * 128];
__device__ uint32_t g_bo[8 * 32];
__device__ __align__(128) uint4 g_q[SEQ * HD / 8];
__device__ __align__(128) uint32_t g_o[SEQ * HD / 2];
constexpr int KV_BYTES = 5120, KV_M = 4096, KV_V = NSEG * KV_BYTES;
__device__ __align__(128) uint8_t g_kv[96 * 2 * NSEG * KV_BYTES];
__device__ __align__(128) uint32_t g_xc[SEQ * DM / 2];
#define OP_B4 0
#define OP_B8 10
#define OP_B16 15
#define QA_END 12
__host__ __device__ constexpr int op_split(int b) { return b < OP_B4 ? 2 : b < OP_B8 ? 4 : b < OP_B16 ? 8 : 16; }
#define AB_PF 2
#define AB_PF0 0
#define AB_PFD 6000
#define W_PROMO CU_TENSOR_MAP_L2_PROMOTION_L2_128B
#define OP_EARLY 1
#define FIN_8 0
#define FIN_16 0
#define OEF 0
#define BQ_HOLD 12
#define WEF 1
#define FK_PF 1
#define BQ_160 10
#define BQ_80 16
#define OP_160 16
__host__ __device__ constexpr int fin_items(int b) { return b < FIN_8 ? 4 : b < FIN_16 ? 8 : 16; }
__host__ __device__ constexpr int op_width(int b) { return b < OP_160 ? 320 : 160; }
__host__ __device__ constexpr int bq_width(int b) { return b < BQ_160 ? 320 : b < BQ_80 ? 160 : 80; }
__device__ __align__(128) uint2 g_part[16 * 16 * 16 * 40 * 32];
__device__ __align__(128) uint32_t g_xn[SEQ * DM / 2];
constexpr int SY_Q = 128, SY_T = 160, SY_QC = 192, SY_N = 193;
__device__ __align__(16) uint32_t g_sync[SY_N];
constexpr int NSLOT = 92;
__device__ uint32_t g_pool[(NSLOT + 2) * 2048];
__device__ int g_smpart[256], g_orient[NSLOT];
__device__ uint32_t g_smclk[256], g_smuse[256];
__device__ uint32_t g_bqkv[3 * 32 * 256 * 96];

#define ABT(L, i)
#define MODE_D(b) 0
#define DELAY(d)
#define XT(i)
#define MISS(k, n)
#define PRO(i)
#define TRACE(w)
#define ITEM(code, w)
#define TR(i, v)
#define TM(i)
#define TM1(i)
#define TMD(i, dep)
#define TMV(i, at, v)

__device__ __forceinline__ uint32_t gtime() { uint32_t c; asm volatile("mov.u32 %0, %%globaltimer_lo;" : "=r"(c) :: "memory"); return c; }
__device__ __forceinline__ uint32_t clk32() { uint32_t c; asm volatile("mov.u32 %0, %%clock;" : "=r"(c) :: "memory"); return c; }
__device__ __forceinline__ uint32_t s2u(const void* p) { return (uint32_t)__cvta_generic_to_shared(p); }
__device__ __forceinline__ uint32_t pack2(float a, float b) {
  uint32_t r; asm("cvt.rn.bf16x2.f32 %0, %1, %2;" : "=r"(r) : "f"(b), "f"(a)); return r; }
__device__ __forceinline__ float bf_lo(uint32_t w) { return __uint_as_float(w << 16); }
__device__ __forceinline__ float bf_hi(uint32_t w) { return __uint_as_float(w & 0xffff0000u); }
__device__ __forceinline__ float ex2(float x) { float y; asm("ex2.approx.ftz.f32 %0, %1;" : "=f"(y) : "f"(x)); return y; }

__device__ __forceinline__ void mbar_init(uint32_t bar, uint32_t n) {
  asm volatile("mbarrier.init.shared::cta.b64 [%0], %1;" :: "r"(bar), "r"(n) : "memory"); }
__device__ __forceinline__ void mbar_expect(uint32_t bar, uint32_t bytes) {
  asm volatile("mbarrier.arrive.expect_tx.shared::cta.b64 _, [%0], %1;" :: "r"(bar), "r"(bytes) : "memory"); }
__device__ __forceinline__ void mbar_arrive(uint32_t bar) {
  asm volatile("mbarrier.arrive.shared::cta.b64 _, [%0];" :: "r"(bar) : "memory"); }
__device__ __forceinline__ void mbar_wait(uint32_t bar, uint32_t ph) {
  asm volatile("{.reg .pred p; .reg .u32 n; mov.u32 n, 0;\n"
               "W: mbarrier.try_wait.parity.shared::cta.b64 p, [%0], %1; @p bra D;\n"
               "add.u32 n, n, 1; setp.gt.u32 p, n, %2; @p trap; bra W;\n"
               "D: }" :: "r"(bar), "r"(ph), "n"(SPIN_LIMIT) : "memory");
}
__device__ __forceinline__ void mbar_wait_cluster(uint32_t bar, uint32_t ph) {
  asm volatile("{.reg .pred p; .reg .u32 n; mov.u32 n, 0;\n"
               "W: mbarrier.try_wait.parity.acquire.cluster.shared::cta.b64 p, [%0], %1; @p bra D;\n"
               "add.u32 n, n, 1; setp.gt.u32 p, n, %2; @p trap; bra W;\n"
               "D: }" :: "r"(bar), "r"(ph), "n"(SPIN_LIMIT) : "memory");
}
__device__ __forceinline__ void spin_guard(int& n) {
  asm volatile("{.reg .pred p; add.s32 %0, %0, 1; setp.gt.s32 p, %0, %1; @p trap;}" : "+r"(n) : "n"(SPIN_LIMIT));
}
__device__ __forceinline__ void pdl_wait() { asm volatile("griddepcontrol.wait;" ::: "memory"); TRACE(1); }
__device__ __forceinline__ void pdl_launch() { asm volatile("griddepcontrol.launch_dependents;" ::: "memory"); }
__device__ __forceinline__ uint32_t ld_acquire(const uint32_t* p) { uint32_t v; asm volatile("ld.acquire.gpu.global.u32 %0, [%1];" : "=r"(v) : "l"(p) : "memory"); return v; }
__device__ __forceinline__ void red_release(uint32_t* p, uint32_t v) { asm volatile("red.release.gpu.global.add.u32 [%0], %1;" :: "l"(p), "r"(v) : "memory"); }
__device__ __forceinline__ void red_relaxed(uint32_t* p, uint32_t v) { asm volatile("red.relaxed.gpu.global.add.u32 [%0], %1;" :: "l"(p), "r"(v) : "memory"); }
__device__ __forceinline__ void fence_async_global() { asm volatile("fence.proxy.async.global;" ::: "memory"); }
__device__ __forceinline__ void fence_async() { asm volatile("fence.proxy.async.shared::cta;" ::: "memory"); }
__device__ __forceinline__ void bar_sync(int id, int n) { asm volatile("bar.sync %0, %1;" :: "r"(id), "r"(n) : "memory"); }
__device__ __forceinline__ void bar_arrive(int id, int n) { asm volatile("bar.arrive %0, %1;" :: "r"(id), "r"(n) : "memory"); }
__device__ __forceinline__ void tma_load(uint32_t dst, const CUtensorMap* m, int c0, int c1, uint32_t bar) {
  asm volatile("cp.async.bulk.tensor.2d.shared::cluster.global.mbarrier::complete_tx::bytes [%0], [%1, {%3, %4}], [%2];"
               :: "r"(dst), "l"(m), "r"(bar), "r"(c0), "r"(c1) : "memory"); }
template <bool STREAM = false>
__device__ __forceinline__ void tma_load3(uint32_t dst, const CUtensorMap* m, int c0, int c1, uint32_t bar) {
  if (STREAM)
    asm volatile("{.reg .b64 pol; createpolicy.fractional.L2::evict_first.b64 pol, 1.0;\n"
                 "cp.async.bulk.tensor.3d.shared::cluster.global.mbarrier::complete_tx::bytes.L2::cache_hint [%0], [%1, {%3, %4, 0}], [%2], pol;}"
                 :: "r"(dst), "l"(m), "r"(bar), "r"(c0), "r"(c1) : "memory");
  else
  asm volatile("cp.async.bulk.tensor.3d.shared::cluster.global.mbarrier::complete_tx::bytes [%0], [%1, {%3, %4, 0}], [%2];"
               :: "r"(dst), "l"(m), "r"(bar), "r"(c0), "r"(c1) : "memory"); }
__device__ __forceinline__ void tma_load3z(uint32_t dst, const CUtensorMap* m, int c1, int c2, uint32_t bar) {
  asm volatile("cp.async.bulk.tensor.3d.shared::cluster.global.mbarrier::complete_tx::bytes [%0], [%1, {0, %3, %4}], [%2];"
               :: "r"(dst), "l"(m), "r"(bar), "r"(c1), "r"(c2) : "memory"); }
__device__ __forceinline__ void tma_store(const CUtensorMap* m, uint32_t src, int c0, int c1) {
  asm volatile("cp.async.bulk.tensor.2d.global.shared::cta.bulk_group [%0, {%2, %3}], [%1];"
               :: "l"(m), "r"(src), "r"(c0), "r"(c1) : "memory"); }
__device__ __forceinline__ void tma_store_stream(const CUtensorMap* m, uint32_t src, int c0, int c1) {
  asm volatile("{.reg .b64 pol; createpolicy.fractional.L2::evict_first.b64 pol, 1.0;\n"
               "cp.async.bulk.tensor.2d.global.shared::cta.bulk_group.L2::cache_hint [%0, {%2, %3}], [%1], pol;}"
               :: "l"(m), "r"(src), "r"(c0), "r"(c1) : "memory"); }
__device__ __forceinline__ void bulk_load(uint32_t dst, const void* src, uint32_t bytes, uint32_t bar) {
  asm volatile("cp.async.bulk.shared::cluster.global.mbarrier::complete_tx::bytes [%0], [%1], %2, [%3];"
               :: "r"(dst), "l"(src), "r"(bytes), "r"(bar) : "memory"); }
__device__ __forceinline__ void bulk_load_last(uint32_t dst, const void* src, uint32_t bytes, uint32_t bar) {
  asm volatile("{.reg .b64 pol; createpolicy.fractional.L2::evict_first.b64 pol, 1.0;\n"
               "cp.async.bulk.shared::cluster.global.mbarrier::complete_tx::bytes.L2::cache_hint [%0], [%1], %2, [%3], pol;}"
               :: "r"(dst), "l"(src), "r"(bytes), "r"(bar) : "memory"); }
__device__ __forceinline__ void tma_load_last(uint32_t dst, const CUtensorMap* m, int c0, int c1, uint32_t bar) {
  asm volatile("{.reg .b64 pol; createpolicy.fractional.L2::evict_first.b64 pol, 1.0;\n"
               "cp.async.bulk.tensor.2d.shared::cluster.global.mbarrier::complete_tx::bytes.L2::cache_hint [%0], [%1, {%3, %4}], [%2], pol;}"
               :: "r"(dst), "l"(m), "r"(bar), "r"(c0), "r"(c1) : "memory"); }
__device__ __forceinline__ void bulk_send(uint32_t dst, uint32_t src, uint32_t bytes, uint32_t bar) {
  asm volatile("cp.async.bulk.shared::cluster.shared::cta.mbarrier::complete_tx::bytes [%0], [%1], %2, [%3];"
               :: "r"(dst), "r"(src), "r"(bytes), "r"(bar) : "memory"); }
__device__ __forceinline__ void bulk_store(void* dst, uint32_t src, uint32_t bytes) {
  asm volatile("cp.async.bulk.global.shared::cta.bulk_group [%0], [%1], %2;" :: "l"(dst), "r"(src), "r"(bytes) : "memory"); }
__device__ __forceinline__ void bulk_commit() { asm volatile("cp.async.bulk.commit_group;" ::: "memory"); }
template <int N> __device__ __forceinline__ void bulk_wait_read() { asm volatile("cp.async.bulk.wait_group.read %0;" :: "n"(N) : "memory"); }
template <int N> __device__ __forceinline__ void bulk_wait() { asm volatile("cp.async.bulk.wait_group %0;" :: "n"(N) : "memory"); }

__device__ __forceinline__ uint64_t mkdesc(uint32_t addr, uint32_t lbo, uint32_t sbo, uint32_t sw) {
  return (uint64_t)((addr & 0x3FFFF) >> 4) | ((uint64_t)(lbo >> 4) << 16) | ((uint64_t)(sbo >> 4) << 32) | ((uint64_t)sw << 62); }
__device__ __forceinline__ void wg_fence() { asm volatile("wgmma.fence.sync.aligned;" ::: "memory"); }
__device__ __forceinline__ void wg_commit() { asm volatile("wgmma.commit_group.sync.aligned;" ::: "memory"); }
template <int N> __device__ __forceinline__ void wg_wait() { asm volatile("wgmma.wait_group.sync.aligned %0;" :: "n"(N) : "memory"); }
template <int N> __device__ __forceinline__ void reg_fence(float* d) {
#pragma unroll
  for (int i = 0; i < N; i++) asm volatile("" : "+f"(d[i]) :: "memory");
}

__device__ __forceinline__ void mma16(float* d, uint32_t a0, uint32_t a1, uint32_t a2, uint32_t a3, uint32_t b0, uint32_t b1) {
  asm volatile("mma.sync.aligned.m16n8k16.row.col.f32.bf16.bf16.f32 {%0,%1,%2,%3},{%4,%5,%6,%7},{%8,%9},{%0,%1,%2,%3};"
               : "+f"(d[0]), "+f"(d[1]), "+f"(d[2]), "+f"(d[3]) : "r"(a0), "r"(a1), "r"(a2), "r"(a3), "r"(b0), "r"(b1)); }
__device__ __forceinline__ void mma8(float* d, uint32_t a0, uint32_t a1, uint32_t b0) {
  asm volatile("mma.sync.aligned.m16n8k8.row.col.f32.bf16.bf16.f32 {%0,%1,%2,%3},{%4,%5},{%6},{%0,%1,%2,%3};"
               : "+f"(d[0]), "+f"(d[1]), "+f"(d[2]), "+f"(d[3]) : "r"(a0), "r"(a1), "r"(b0)); }
__device__ __forceinline__ void ldsm4(uint32_t* r, uint32_t a) {
  asm volatile("ldmatrix.sync.aligned.m8n8.x4.shared.b16 {%0,%1,%2,%3},[%4];" : "=r"(r[0]), "=r"(r[1]), "=r"(r[2]), "=r"(r[3]) : "r"(a) : "memory"); }
__device__ __forceinline__ void ldsm4t(uint32_t* r, uint32_t a) {
  asm volatile("ldmatrix.sync.aligned.m8n8.x4.trans.shared.b16 {%0,%1,%2,%3},[%4];" : "=r"(r[0]), "=r"(r[1]), "=r"(r[2]), "=r"(r[3]) : "r"(a) : "memory"); }
__device__ __forceinline__ void ldsm2(uint32_t* r, uint32_t a) {
  asm volatile("ldmatrix.sync.aligned.m8n8.x2.shared.b16 {%0,%1},[%2];" : "=r"(r[0]), "=r"(r[1]) : "r"(a) : "memory"); }
__device__ __forceinline__ void stsm4(uint32_t a, uint32_t r0, uint32_t r1, uint32_t r2, uint32_t r3) {
  asm volatile("stmatrix.sync.aligned.m8n8.x4.shared.b16 [%0], {%1,%2,%3,%4};" :: "r"(a), "r"(r0), "r"(r1), "r"(r2), "r"(r3) : "memory"); }
__device__ __forceinline__ void stsm2t(uint32_t a, uint32_t r0, uint32_t r1) {
  asm volatile("stmatrix.sync.aligned.m8n8.x2.trans.shared.b16 [%0], {%1,%2};" :: "r"(a), "r"(r0), "r"(r1) : "memory"); }
__device__ __forceinline__ void stsm4t(uint32_t a, uint32_t r0, uint32_t r1, uint32_t r2, uint32_t r3) {
  asm volatile("stmatrix.sync.aligned.m8n8.x4.trans.shared.b16 [%0], {%1,%2,%3,%4};" :: "r"(a), "r"(r0), "r"(r1), "r"(r2), "r"(r3) : "memory"); }
__device__ __forceinline__ void st_async128(uint32_t a, uint4 v, uint32_t bar) {
  asm volatile("st.async.shared::cluster.mbarrier::complete_tx::bytes.v4.b32 [%0], {%1,%2,%3,%4}, [%5];" :: "r"(a), "r"(v.x), "r"(v.y), "r"(v.z), "r"(v.w), "r"(bar) : "memory"); }
__device__ __forceinline__ void sts32(uint32_t a, uint32_t v) { asm volatile("st.shared.b32 [%0], %1;" :: "r"(a), "r"(v) : "memory"); }
__device__ __forceinline__ void sts64f(uint32_t a, float x, float y) { asm volatile("st.shared.v2.f32 [%0], {%1,%2};" :: "r"(a), "f"(x), "f"(y) : "memory"); }
__device__ __forceinline__ void sts128(uint32_t a, uint4 v) {
  asm volatile("st.shared.v4.b32 [%0], {%1,%2,%3,%4};" :: "r"(a), "r"(v.x), "r"(v.y), "r"(v.z), "r"(v.w) : "memory"); }
__device__ __forceinline__ void sts128f(uint32_t a, float x, float y, float z, float w) {
  asm volatile("st.shared.v4.f32 [%0], {%1,%2,%3,%4};" :: "r"(a), "f"(x), "f"(y), "f"(z), "f"(w) : "memory"); }
__device__ __forceinline__ float lds32f(uint32_t a) { float v; asm volatile("ld.shared.f32 %0, [%1];" : "=f"(v) : "r"(a) : "memory"); return v; }
__device__ __forceinline__ float2 lds64f(uint32_t a) { float2 v; asm volatile("ld.shared.v2.f32 {%0,%1}, [%2];" : "=f"(v.x), "=f"(v.y) : "r"(a) : "memory"); return v; }
__device__ __forceinline__ float4 lds128f(uint32_t a) {
  float4 v; asm volatile("ld.shared.v4.f32 {%0,%1,%2,%3}, [%4];" : "=f"(v.x), "=f"(v.y), "=f"(v.z), "=f"(v.w) : "r"(a) : "memory"); return v; }
__device__ __forceinline__ uint4 lds128(uint32_t a) {
  uint4 v; asm volatile("ld.shared.v4.b32 {%0,%1,%2,%3}, [%4];" : "=r"(v.x), "=r"(v.y), "=r"(v.z), "=r"(v.w) : "r"(a) : "memory"); return v; }
__device__ __forceinline__ uint4 ldg_strong128(const void* p) {
  uint4 v; asm volatile("ld.relaxed.gpu.global.v4.u32 {%0,%1,%2,%3}, [%4];" : "=r"(v.x), "=r"(v.y), "=r"(v.z), "=r"(v.w) : "l"(p) : "memory"); return v; }
__device__ __forceinline__ void stg_strong32(void* p, uint32_t v) { asm volatile("st.relaxed.gpu.global.u32 [%0], %1;" :: "l"(p), "r"(v) : "memory"); }
__device__ __forceinline__ void stg_strong16(void* p, uint32_t v) { asm volatile("st.relaxed.gpu.global.u16 [%0], %1;" :: "l"(p), "h"((uint16_t)v) : "memory"); }
__device__ __forceinline__ void stg_strong128(void* p, uint4 v) {
  asm volatile("st.relaxed.gpu.global.v4.u32 [%0], {%1,%2,%3,%4};" :: "l"(p), "r"(v.x), "r"(v.y), "r"(v.z), "r"(v.w) : "memory"); }
__device__ __forceinline__ uint32_t mapa(uint32_t a, uint32_t r) {
  uint32_t o; asm("mapa.shared::cluster.u32 %0, %1, %2;" : "=r"(o) : "r"(a), "r"(r)); return o; }
__device__ __forceinline__ void st_async2f(uint32_t a, float x, float y, uint32_t bar) {
  asm volatile("st.async.shared::cluster.mbarrier::complete_tx::bytes.v2.f32 [%0], {%1,%2}, [%3];" :: "r"(a), "f"(x), "f"(y), "r"(bar) : "memory"); }
__device__ __forceinline__ void st_async32(uint32_t a, uint32_t x, uint32_t bar) {
  asm volatile("st.async.shared::cluster.mbarrier::complete_tx::bytes.b32 [%0], %1, [%2];" :: "r"(a), "r"(x), "r"(bar) : "memory"); }
__device__ __forceinline__ uint32_t lds32(uint32_t a) { uint32_t v; asm volatile("ld.shared.b32 %0, [%1];" : "=r"(v) : "r"(a) : "memory"); return v; }
__device__ __forceinline__ void st_async64(uint32_t a, uint32_t x, uint32_t y, uint32_t bar) {
  asm volatile("st.async.shared::cluster.mbarrier::complete_tx::bytes.v2.b32 [%0], {%1,%2}, [%3];" :: "r"(a), "r"(x), "r"(y), "r"(bar) : "memory"); }
__device__ __forceinline__ uint2 lds64(uint32_t a) { uint2 v; asm volatile("ld.shared.v2.b32 {%0,%1}, [%2];" : "=r"(v.x), "=r"(v.y) : "r"(a) : "memory"); return v; }
__device__ __forceinline__ void sts64(uint32_t a, uint32_t x, uint32_t y) { asm volatile("st.shared.v2.b32 [%0], {%1,%2};" :: "r"(a), "r"(x), "r"(y) : "memory"); }
__device__ __forceinline__ uint32_t ldg_strong32(const void* p) { uint32_t v; asm volatile("ld.relaxed.gpu.global.u32 %0, [%1];" : "=r"(v) : "l"(p) : "memory"); return v; }
__device__ __forceinline__ uint32_t transpose8(uint32_t x) { uint32_t r; asm volatile("movmatrix.sync.aligned.m8n8.trans.b16 %0, %1;" : "=r"(r) : "r"(x)); return r; }
__device__ __forceinline__ uint32_t hadd2(uint32_t a, uint32_t b) { uint32_t r; asm("add.rn.bf16x2 %0, %1, %2;" : "=r"(r) : "r"(a), "r"(b)); return r; }
__device__ __forceinline__ uint32_t min4(uint4 v) { return min(__vimin3_u32(v.x, v.y, v.z), v.w); }

__device__ __forceinline__ void wg_ss192_01(float* d, uint64_t da, uint64_t db, int sd) {
  asm volatile("{.reg .pred p; setp.ne.b32 p, %98, 0;\n"
    "wgmma.mma_async.sync.aligned.m64n192k16.f32.bf16.bf16 {%0,%1,%2,%3,%4,%5,%6,%7,%8,%9,%10,%11,%12,%13,%14,%15,%16,%17,%18,%19,%20,%21,%22,%23,%24,%25,%26,%27,%28,%29,%30,%31,%32,%33,%34,%35,%36,%37,%38,%39,%40,%41,%42,%43,%44,%45,%46,%47,%48,%49,%50,%51,%52,%53,%54,%55,%56,%57,%58,%59,%60,%61,%62,%63,%64,%65,%66,%67,%68,%69,%70,%71,%72,%73,%74,%75,%76,%77,%78,%79,%80,%81,%82,%83,%84,%85,%86,%87,%88,%89,%90,%91,%92,%93,%94,%95}, %96, %97, p, 1, 1, 0, 1;}"
    : "+f"(d[0]),"+f"(d[1]),"+f"(d[2]),"+f"(d[3]),"+f"(d[4]),"+f"(d[5]),"+f"(d[6]),"+f"(d[7]),"+f"(d[8]),"+f"(d[9]),"+f"(d[10]),"+f"(d[11]),"+f"(d[12]),"+f"(d[13]),"+f"(d[14]),"+f"(d[15]),"+f"(d[16]),"+f"(d[17]),"+f"(d[18]),"+f"(d[19]),"+f"(d[20]),"+f"(d[21]),"+f"(d[22]),"+f"(d[23]),"+f"(d[24]),"+f"(d[25]),"+f"(d[26]),"+f"(d[27]),"+f"(d[28]),"+f"(d[29]),"+f"(d[30]),"+f"(d[31]),"+f"(d[32]),"+f"(d[33]),"+f"(d[34]),"+f"(d[35]),"+f"(d[36]),"+f"(d[37]),"+f"(d[38]),"+f"(d[39]),"+f"(d[40]),"+f"(d[41]),"+f"(d[42]),"+f"(d[43]),"+f"(d[44]),"+f"(d[45]),"+f"(d[46]),"+f"(d[47]),"+f"(d[48]),"+f"(d[49]),"+f"(d[50]),"+f"(d[51]),"+f"(d[52]),"+f"(d[53]),"+f"(d[54]),"+f"(d[55]),"+f"(d[56]),"+f"(d[57]),"+f"(d[58]),"+f"(d[59]),"+f"(d[60]),"+f"(d[61]),"+f"(d[62]),"+f"(d[63]),"+f"(d[64]),"+f"(d[65]),"+f"(d[66]),"+f"(d[67]),"+f"(d[68]),"+f"(d[69]),"+f"(d[70]),"+f"(d[71]),"+f"(d[72]),"+f"(d[73]),"+f"(d[74]),"+f"(d[75]),"+f"(d[76]),"+f"(d[77]),"+f"(d[78]),"+f"(d[79]),"+f"(d[80]),"+f"(d[81]),"+f"(d[82]),"+f"(d[83]),"+f"(d[84]),"+f"(d[85]),"+f"(d[86]),"+f"(d[87]),"+f"(d[88]),"+f"(d[89]),"+f"(d[90]),"+f"(d[91]),"+f"(d[92]),"+f"(d[93]),"+f"(d[94]),"+f"(d[95])
    : "l"(da), "l"(db), "r"(sd));
}
__device__ __forceinline__ void wg_ss128_01(float* d, uint64_t da, uint64_t db, int sd) {
  asm volatile("{.reg .pred p; setp.ne.b32 p, %66, 0;\n"
    "wgmma.mma_async.sync.aligned.m64n128k16.f32.bf16.bf16 {%0,%1,%2,%3,%4,%5,%6,%7,%8,%9,%10,%11,%12,%13,%14,%15,%16,%17,%18,%19,%20,%21,%22,%23,%24,%25,%26,%27,%28,%29,%30,%31,%32,%33,%34,%35,%36,%37,%38,%39,%40,%41,%42,%43,%44,%45,%46,%47,%48,%49,%50,%51,%52,%53,%54,%55,%56,%57,%58,%59,%60,%61,%62,%63}, %64, %65, p, 1, 1, 0, 1;}"
    : "+f"(d[0]),"+f"(d[1]),"+f"(d[2]),"+f"(d[3]),"+f"(d[4]),"+f"(d[5]),"+f"(d[6]),"+f"(d[7]),"+f"(d[8]),"+f"(d[9]),"+f"(d[10]),"+f"(d[11]),"+f"(d[12]),"+f"(d[13]),"+f"(d[14]),"+f"(d[15]),"+f"(d[16]),"+f"(d[17]),"+f"(d[18]),"+f"(d[19]),"+f"(d[20]),"+f"(d[21]),"+f"(d[22]),"+f"(d[23]),"+f"(d[24]),"+f"(d[25]),"+f"(d[26]),"+f"(d[27]),"+f"(d[28]),"+f"(d[29]),"+f"(d[30]),"+f"(d[31]),"+f"(d[32]),"+f"(d[33]),"+f"(d[34]),"+f"(d[35]),"+f"(d[36]),"+f"(d[37]),"+f"(d[38]),"+f"(d[39]),"+f"(d[40]),"+f"(d[41]),"+f"(d[42]),"+f"(d[43]),"+f"(d[44]),"+f"(d[45]),"+f"(d[46]),"+f"(d[47]),"+f"(d[48]),"+f"(d[49]),"+f"(d[50]),"+f"(d[51]),"+f"(d[52]),"+f"(d[53]),"+f"(d[54]),"+f"(d[55]),"+f"(d[56]),"+f"(d[57]),"+f"(d[58]),"+f"(d[59]),"+f"(d[60]),"+f"(d[61]),"+f"(d[62]),"+f"(d[63])
    : "l"(da), "l"(db), "r"(sd));
}
__device__ __forceinline__ void wg_ss160_01(float* d, uint64_t da, uint64_t db, int sd) {
  asm volatile("{.reg .pred p; setp.ne.b32 p, %82, 0;\n"
    "wgmma.mma_async.sync.aligned.m64n160k16.f32.bf16.bf16 {%0,%1,%2,%3,%4,%5,%6,%7,%8,%9,%10,%11,%12,%13,%14,%15,%16,%17,%18,%19,%20,%21,%22,%23,%24,%25,%26,%27,%28,%29,%30,%31,%32,%33,%34,%35,%36,%37,%38,%39,%40,%41,%42,%43,%44,%45,%46,%47,%48,%49,%50,%51,%52,%53,%54,%55,%56,%57,%58,%59,%60,%61,%62,%63,%64,%65,%66,%67,%68,%69,%70,%71,%72,%73,%74,%75,%76,%77,%78,%79}, %80, %81, p, 1, 1, 0, 1;}"
    : "+f"(d[0]),"+f"(d[1]),"+f"(d[2]),"+f"(d[3]),"+f"(d[4]),"+f"(d[5]),"+f"(d[6]),"+f"(d[7]),"+f"(d[8]),"+f"(d[9]),"+f"(d[10]),"+f"(d[11]),"+f"(d[12]),"+f"(d[13]),"+f"(d[14]),"+f"(d[15]),"+f"(d[16]),"+f"(d[17]),"+f"(d[18]),"+f"(d[19]),"+f"(d[20]),"+f"(d[21]),"+f"(d[22]),"+f"(d[23]),"+f"(d[24]),"+f"(d[25]),"+f"(d[26]),"+f"(d[27]),"+f"(d[28]),"+f"(d[29]),"+f"(d[30]),"+f"(d[31]),"+f"(d[32]),"+f"(d[33]),"+f"(d[34]),"+f"(d[35]),"+f"(d[36]),"+f"(d[37]),"+f"(d[38]),"+f"(d[39]),"+f"(d[40]),"+f"(d[41]),"+f"(d[42]),"+f"(d[43]),"+f"(d[44]),"+f"(d[45]),"+f"(d[46]),"+f"(d[47]),"+f"(d[48]),"+f"(d[49]),"+f"(d[50]),"+f"(d[51]),"+f"(d[52]),"+f"(d[53]),"+f"(d[54]),"+f"(d[55]),"+f"(d[56]),"+f"(d[57]),"+f"(d[58]),"+f"(d[59]),"+f"(d[60]),"+f"(d[61]),"+f"(d[62]),"+f"(d[63]),"+f"(d[64]),"+f"(d[65]),"+f"(d[66]),"+f"(d[67]),"+f"(d[68]),"+f"(d[69]),"+f"(d[70]),"+f"(d[71]),"+f"(d[72]),"+f"(d[73]),"+f"(d[74]),"+f"(d[75]),"+f"(d[76]),"+f"(d[77]),"+f"(d[78]),"+f"(d[79])
    : "l"(da), "l"(db), "r"(sd));
}
__device__ __forceinline__ void wg_ss80_01(float* d, uint64_t da, uint64_t db, int sd) {
  asm volatile("{.reg .pred p; setp.ne.b32 p, %42, 0;\n"
    "wgmma.mma_async.sync.aligned.m64n80k16.f32.bf16.bf16 {%0,%1,%2,%3,%4,%5,%6,%7,%8,%9,%10,%11,%12,%13,%14,%15,%16,%17,%18,%19,%20,%21,%22,%23,%24,%25,%26,%27,%28,%29,%30,%31,%32,%33,%34,%35,%36,%37,%38,%39}, %40, %41, p, 1, 1, 0, 1;}"
    : "+f"(d[0]),"+f"(d[1]),"+f"(d[2]),"+f"(d[3]),"+f"(d[4]),"+f"(d[5]),"+f"(d[6]),"+f"(d[7]),"+f"(d[8]),"+f"(d[9]),"+f"(d[10]),"+f"(d[11]),"+f"(d[12]),"+f"(d[13]),"+f"(d[14]),"+f"(d[15]),"+f"(d[16]),"+f"(d[17]),"+f"(d[18]),"+f"(d[19]),"+f"(d[20]),"+f"(d[21]),"+f"(d[22]),"+f"(d[23]),"+f"(d[24]),"+f"(d[25]),"+f"(d[26]),"+f"(d[27]),"+f"(d[28]),"+f"(d[29]),"+f"(d[30]),"+f"(d[31]),"+f"(d[32]),"+f"(d[33]),"+f"(d[34]),"+f"(d[35]),"+f"(d[36]),"+f"(d[37]),"+f"(d[38]),"+f"(d[39])
    : "l"(da), "l"(db), "r"(sd));
}
__device__ __forceinline__ void wg_rs32_00(float* d, uint32_t a0, uint32_t a1, uint32_t a2, uint32_t a3, uint64_t db, int sd) {
  asm volatile("{.reg .pred p; setp.ne.b32 p, %21, 0;\n"
    "wgmma.mma_async.sync.aligned.m64n32k16.f32.bf16.bf16 {%0,%1,%2,%3,%4,%5,%6,%7,%8,%9,%10,%11,%12,%13,%14,%15}, {%16,%17,%18,%19}, %20, p, 1, 1, 0;}"
    : "+f"(d[0]),"+f"(d[1]),"+f"(d[2]),"+f"(d[3]),"+f"(d[4]),"+f"(d[5]),"+f"(d[6]),"+f"(d[7]),"+f"(d[8]),"+f"(d[9]),"+f"(d[10]),"+f"(d[11]),"+f"(d[12]),"+f"(d[13]),"+f"(d[14]),"+f"(d[15])
    : "r"(a0), "r"(a1), "r"(a2), "r"(a3), "l"(db), "r"(sd));
}
__device__ __forceinline__ void wg_rs64_00(float* d, uint32_t a0, uint32_t a1, uint32_t a2, uint32_t a3, uint64_t db, int sd) {
  asm volatile("{.reg .pred p; setp.ne.b32 p, %37, 0;\n"
    "wgmma.mma_async.sync.aligned.m64n64k16.f32.bf16.bf16 {%0,%1,%2,%3,%4,%5,%6,%7,%8,%9,%10,%11,%12,%13,%14,%15,%16,%17,%18,%19,%20,%21,%22,%23,%24,%25,%26,%27,%28,%29,%30,%31}, {%32,%33,%34,%35}, %36, p, 1, 1, 0;}"
    : "+f"(d[0]),"+f"(d[1]),"+f"(d[2]),"+f"(d[3]),"+f"(d[4]),"+f"(d[5]),"+f"(d[6]),"+f"(d[7]),"+f"(d[8]),"+f"(d[9]),"+f"(d[10]),"+f"(d[11]),"+f"(d[12]),"+f"(d[13]),"+f"(d[14]),"+f"(d[15]),"+f"(d[16]),"+f"(d[17]),"+f"(d[18]),"+f"(d[19]),"+f"(d[20]),"+f"(d[21]),"+f"(d[22]),"+f"(d[23]),"+f"(d[24]),"+f"(d[25]),"+f"(d[26]),"+f"(d[27]),"+f"(d[28]),"+f"(d[29]),"+f"(d[30]),"+f"(d[31])
    : "r"(a0), "r"(a1), "r"(a2), "r"(a3), "l"(db), "r"(sd));
}
__device__ __forceinline__ void wg_rs24_01(float* d, uint32_t a0, uint32_t a1, uint32_t a2, uint32_t a3, uint64_t db, int sd) {
  asm volatile("{.reg .pred p; setp.ne.b32 p, %17, 0;\n"
    "wgmma.mma_async.sync.aligned.m64n24k16.f32.bf16.bf16 {%0,%1,%2,%3,%4,%5,%6,%7,%8,%9,%10,%11}, {%12,%13,%14,%15}, %16, p, 1, 1, 1;}"
    : "+f"(d[0]),"+f"(d[1]),"+f"(d[2]),"+f"(d[3]),"+f"(d[4]),"+f"(d[5]),"+f"(d[6]),"+f"(d[7]),"+f"(d[8]),"+f"(d[9]),"+f"(d[10]),"+f"(d[11])
    : "r"(a0), "r"(a1), "r"(a2), "r"(a3), "l"(db), "r"(sd));
}

#define AB_POLY 0xaa
#define AB_DEG 3
__device__ __forceinline__ constexpr bool poly_group(int group) { return (AB_POLY >> (group & 7)) & 1; }

template <int V> struct Int { static constexpr int value = V; };

template <int NG>
__device__ __forceinline__ void ln_stats(const float4 (&v)[NG][5], uint32_t scratch, float (&mean)[NG], float (&rs)[NG]) {
  const int warp = threadIdx.x >> 5, lane = threadIdx.x & 31;
#pragma unroll
  for (int r = 0; r < NG; r++) {
    float s = 0.f, q = 0.f;
#pragma unroll
    for (int i = 0; i < 5; i++) s += (v[r][i].x + v[r][i].y) + (v[r][i].z + v[r][i].w);
    s += __shfl_xor_sync(~0u, s, 1); s += __shfl_xor_sync(~0u, s, 2);
    s *= 1.f / 80;
#pragma unroll
    for (int i = 0; i < 5; i++) {
      const float x = v[r][i].x - s, y = v[r][i].y - s, z = v[r][i].z - s, w = v[r][i].w - s;
      q += (x * x + y * y) + (z * z + w * w);
    }
    q += __shfl_xor_sync(~0u, q, 1); q += __shfl_xor_sync(~0u, q, 2);
    mean[r] = s; rs[r] = q;
  }
  bar_sync(1, 256);
  if ((lane & 3) == 0) {
#pragma unroll
    for (int r = 0; r < NG; r++) sts64f(scratch + r * 512 + lane * 16 + warp * 8, mean[r], rs[r]);
  }
  bar_sync(1, 256);
#pragma unroll
  for (int r = 0; r < NG; r++) {
    const float4 e = lds128f(scratch + r * 512 + lane * 16);
    float t = e.x + e.z;
    t += __shfl_xor_sync(~0u, t, 1); t += __shfl_xor_sync(~0u, t, 2);
    t *= 0.125f;
    float q = e.y + e.w + 80.f * ((e.x - t) * (e.x - t) + (e.z - t) * (e.z - t));
    q += __shfl_xor_sync(~0u, q, 1); q += __shfl_xor_sync(~0u, q, 2);
    mean[r] = t; rs[r] = rsqrtf(q * (1.f / DM) + 1e-5f);
  }
}

__device__ __forceinline__ void ln_store(const uint32_t (&w)[2][5][2], int tile, int u0, bool live = true) {
  const int lane = threadIdx.x & 31;
  uint32_t* xc = g_xc + ((tile >> 1) * 40 + u0) * 256 + (tile & 1) * 64 + lane;
#pragma unroll
  for (int i = 0; i < 20; i++) if (live) xc[(i >> 1) * 128 + (i & 1) * 32] = w[i & 1][i >> 2][i >> 1 & 1];
#pragma unroll
  for (int i = 0; i < 5; i++) {
    const int u = u0 + i;
    uint32_t* xn = g_xn + (((tile >> 3) * 20 + (u >> 1)) * 16 + (tile & 1) * 8 + (tile & 6)) * 128 + (u & 1) * 64 + lane;
#pragma unroll
    for (int r = 0; r < 2; r++) if (live) { xn[r * 128] = w[r][i][0]; xn[r * 128 + 32] = w[r][i][1]; }
  }
}
__device__ __forceinline__ void wait_count(const uint32_t* c, uint32_t n) {
  int spin = 0;
  while ((ld_acquire(c) & 0xffff) < n) { __nanosleep(32); spin_guard(spin); }
}

__device__ __forceinline__ uint8_t* pool_at(uint32_t off) {
  return reinterpret_cast<uint8_t*>((reinterpret_cast<uintptr_t>(g_pool) + 8191) & ~(uintptr_t)8191) + off; }
struct Weights { const uint8_t* w[4]; };
__device__ __forceinline__ void prefetch_weights(const Weights& p, int i) {
  if (blockIdx.x < 128) asm volatile("cp.async.bulk.prefetch.L2.global [%0], 61440;" :: "l"(p.w[i] + (size_t)blockIdx.x * 61440) : "memory");
}
__global__ void __launch_bounds__(256) first_kernel(const __nv_bfloat16* __restrict__ xin, const uint4* __restrict__ wb, const __grid_constant__ Weights wa) {
  __shared__ __align__(16) float scratch[256];
  __shared__ uint32_t lat[4];
  const int warp = threadIdx.x >> 5, lane = threadIdx.x & 31, cta = blockIdx.x;
  TRACE(0);
  pdl_launch();
  if (warp < 4 && (warp < 2 || cta < NSLOT)) {
    uint32_t* q = reinterpret_cast<uint32_t*>(pool_at((warp < 2 ? NSLOT : cta) * 8192 + (warp & 1) * 4096)) + (warp < 2 ? (cta & 127) * 8 : 0);
    if (lane < 8) stg_strong32(q + lane, 0u);
    uint32_t best = ~0u;
    if (lane == 0)
      for (int r = 0; r < 4; r++) {
        uint32_t t0, t1, v;
        asm volatile("mov.u32 %0, %%clock;" : "=r"(t0) :: "memory");
        asm volatile("atom.relaxed.gpu.global.exch.b32 %0, [%1], 0;" : "=r"(v) : "l"(q) : "memory");
        asm volatile("{.reg .u32 t; add.u32 t, %1, 1; mov.u32 %0, %%clock; sub.u32 %0, %0, %1;}" : "=r"(t1) : "r"(__shfl_sync(1u, v, 0)) : "memory");
        best = min(best, t1 - t0);
      }
    if (lane == 0) lat[warp] = best;
  }
  __syncthreads();
  ABT(2, 0);
  if (threadIdx.x == 0) {
    const int part = lat[0] < lat[1] ? 0 : 1;
    uint32_t smid; asm("mov.u32 %0, %%smid;" : "=r"(smid));
    g_smpart[smid & 255] = part;
    g_smclk[smid & 255] = clk32() - gtime() * 2;
    g_smuse[smid & 255] = 0;
    if (cta < NSLOT) g_orient[cta] = lat[2] < lat[3] ? part : 1 - part;
  }
  if (cta < 128) {
    float4 v[2][5];
#pragma unroll
    for (int r = 0; r < 2; r++)
#pragma unroll
      for (int i = 0; i < 5; i++) {
        const uint32_t* src = reinterpret_cast<const uint32_t*>(xin) + (cta * 16 + r * 8 + (lane >> 2)) * (DM / 2) + warp * 40 + i * 8 + (lane & 3);
        const uint32_t a = src[0], b = src[4];
        v[r][i] = make_float4(bf_lo(a), bf_hi(a), bf_lo(b), bf_hi(b));
      }
    uint4 w8[2];
#pragma unroll
    for (int i = 0; i < 2; i++) w8[i] = wb[cta * 400 + min(i * 256 + threadIdx.x, 399)];
    if (threadIdx.x < 128) g_stat[cta * 128 + threadIdx.x] = make_float2(0.f, 0.f);
#pragma unroll
    for (int i = 0; i < 10; i++) g_x[((cta * 2 + i / 5) * 40 + warp * 5 + i % 5) * 32 + lane] = v[i / 5][i % 5];
    ABT(2, 1);
    if (threadIdx.x == 32) for (int i = 0; i < FK_PF; i++) prefetch_weights(wa, i);
    float mean[2], rs[2];
    ln_stats<2>(v, s2u(scratch), mean, rs);
    ABT(2, 2);
    uint32_t w[2][5][2];
#pragma unroll
    for (int i = 0; i < 10; i++) {
      const float4 t = v[i / 5][i % 5];
      const float m = mean[i / 5], q = rs[i / 5];
      w[i / 5][i % 5][0] = pack2((t.x - m) * q, (t.y - m) * q); w[i / 5][i % 5][1] = pack2((t.z - m) * q, (t.w - m) * q);
    }
    ln_store(w, cta, warp * 5);
    ABT(2, 3);
#pragma unroll
    for (int i = 0; i < 2; i++) {
      const int e = cta * 400 + min(i * 256 + threadIdx.x, 399), k = e / 80, n = e - k * 80, cg = n / 10;
      g_wb[((cg * 80 + (k >> 3)) * 10 + n - cg * 10) * 8 + (k & 7)] = w8[i];
    }
  } else if (cta == 128) {
    g_bo[threadIdx.x] = 0;
  }
  TRACE(2);
}

struct ChainParams {
  CUtensorMap wq, wk, wv, wo;
  const __nv_bfloat16* mem0;
  uint8_t *pool, *kv;
  const uint32_t* xc;
  uint32_t* sync;
  int layer;
  int d0, d3, d1, d1b, d2, d2b, mode;
};
constexpr int CH_WQ = 0, CH_WO = 81920, CH_X = CH_WO + 86016, CH_M = CH_X + 20480, CH_KT = CH_X + 40960, CH_VT = CH_KT + 4096,
              CH_PS = CH_VT + 4096, CH_QK = CH_PS + 4096, CH_VP = CH_QK + 4096, CH_SX = CH_VP + 1024, CH_O = CH_SX + 2304, CH_ID = CH_O + 3072,
              CH_BAR = CH_ID + 512;
constexpr int CH_SMEM = CH_BAR + 256;
constexpr int CH_BASE = 1024;
#define CH_VK0 8
#define CH_VK1 20
#define CH_L0 4
#define CH_LR 4
#define NOX 0
#define CH_XA 1
#define CH_XB 4
#define CH_W1 3
#define CH_W2 17
#define CH_W3 26
#define CH_R2 8
#define CH_VA 16
#define CH_EX 1
#define CH_KD 0
#define CH_RP 1
#define CH_KF 10
#define CH_LO 0
#define CH_LR1 4
#define CH_KP 0
#define CH_KM 0
#define CH_WE 0
#define CH_KW 3
#define CH_RB 0
#define CH_RC 8
#define CH_D0 200
#define CH_D1 450
#define CH_D2 350
#define CH_R1 4
#define CH_TW 12
__device__ __forceinline__ uint32_t opaque(uint32_t x) { return __shfl_sync(~0u, x, threadIdx.x & 31); }
__device__ __forceinline__ uint32_t nz(uint32_t x) { uint32_t r; asm("max.u32 %0, %1, 1;" : "=r"(r) : "r"(x)); return r; }
__device__ __forceinline__ uint32_t pack_tag(float lo, float hi, uint32_t tag, uint32_t mask) {
  uint32_t r;
  asm("lop3.b32 %0, %1, %2, %3, 0xD8;" : "=r"(r) : "r"(pack2(lo, hi)), "r"(tag), "r"(mask));
  return r;
}
__device__ __forceinline__ uint32_t differ(uint32_t a, uint32_t b, uint32_t t) { uint32_t r; asm("lop3.b32 %0, %1, %2, %3, 0x7E;" : "=r"(r) : "r"(a), "r"(b), "r"(t)); return r; }
__device__ __forceinline__ void mbar_wait_hot(uint32_t bar, uint32_t ph) {
  uint32_t ok;
  asm volatile("{.reg .pred p; mbarrier.try_wait.parity.shared::cta.b64 p, [%1], %2; selp.u32 %0, 1, 0, p;}" : "=r"(ok) : "r"(bar), "r"(ph) : "memory");
  if (__builtin_expect(!ok, 0)) mbar_wait(bar, ph);
}
__device__ __forceinline__ bool elect() {
  uint32_t r; asm volatile("{.reg .pred p; elect.sync _|p, 0xffffffff; selp.u32 %0, 1, 0, p;}" : "=r"(r)); return r; }
__device__ __forceinline__ uint32_t or3(uint32_t a, uint32_t b, uint32_t c) { uint32_t r; asm("lop3.b32 %0, %1, %2, %3, 0xFE;" : "=r"(r) : "r"(a), "r"(b), "r"(c)); return r; }
__device__ __forceinline__ void pin() { pdl_launch(); }
__device__ __forceinline__ void mma16h(float* d, uint32_t a0, uint32_t a2, uint32_t b0, uint32_t b1) {
  asm volatile("{.reg .b32 u, v; mma.sync.aligned.m16n8k16.row.col.f32.bf16.bf16.f32 {%0,%1,%2,%3},{%4,u,%5,v},{%6,%7},{%0,%1,%2,%3};}"
               : "+f"(d[0]), "+f"(d[1]), "+f"(d[2]), "+f"(d[3]) : "r"(a0), "r"(a2), "r"(b0), "r"(b1)); }
__device__ __forceinline__ void mma8h(float* d, uint32_t a0, uint32_t b0) {
  asm volatile("{.reg .b32 u; mma.sync.aligned.m16n8k8.row.col.f32.bf16.bf16.f32 {%0,%1,%2,%3},{%4,u},{%5},{%0,%1,%2,%3};}"
               : "+f"(d[0]), "+f"(d[1]), "+f"(d[2]), "+f"(d[3]) : "r"(a0), "r"(b0)); }
__device__ __forceinline__ uint32_t absmax2(uint32_t a, uint32_t b) { uint32_t r; asm("max.xorsign.abs.bf16x2 %0, %1, %2;" : "=r"(r) : "r"(a), "r"(b)); return r; }
__device__ __forceinline__ void until(uint32_t t) { while ((int)(clk32() - t) < 0) {} }
__device__ __forceinline__ uint4 pack8(const float* d) { return make_uint4(pack2(d[0], d[1]), pack2(d[2], d[3]), pack2(d[4], d[5]), pack2(d[6], d[7])); }
__device__ __forceinline__ void add8(float* d, uint4 v) {
  d[0] += bf_lo(v.x); d[1] += bf_hi(v.x); d[2] += bf_lo(v.y); d[3] += bf_hi(v.y);
  d[4] += bf_lo(v.z); d[5] += bf_hi(v.z); d[6] += bf_lo(v.w); d[7] += bf_hi(v.w);
}

template <int WG>
__device__ __forceinline__ void chain_body(const ChainParams& p, const uint32_t wq, const uint32_t (&ak)[80], const uint32_t (&av)[80]) {
  const int tid = threadIdx.x & 127, t4 = __shfl_sync(~0u, tid >> 5, 0), lane = tid & 31;
  const int cta = blockIdx.x, h = cta / 3, j = cta - 3 * h;
  const uint32_t sb = mapa(CH_BASE, j);
  const uint32_t bWo = sb + CH_BAR, bWq = bWo + 8, bX = bWo + 16, bXA = bWo + 24, bXB = bWo + 32, bO = bWo + 40, bG = bWo + 48, bH = bWo + 96;
  uint32_t tw[4 * CH_TW];
  auto refill = [&]() {
#pragma unroll
    for (int k = 0; k < CH_TW; k++) ldsm4t(&tw[4 * k], wq + k * 2048);
  };
  const uint32_t wo = opaque((sb + CH_WO + (WG == 0 ? (t4 + (j == 2)) * 4096 : (j == 2 ? 0 : 24576) + t4 * 1024) + ((lane & 7) + (lane >> 4) * 8) * 64 +
                              ((((lane >> 3) & 1) ^ ((lane >> 1) & 3)) << 4)) ^ (WG == 1 && j == 2 ? 32 : 0));
  const uint32_t wo2 = opaque((wo ^ ((t4 & 1) * 32)) + (4 + (t4 >> 1) - t4) * 4096);
  const uint32_t l16 = opaque(sb + lane * 16);
  const uint32_t l8 = opaque(sb + t4 * 256 + lane * 8);
  const uint32_t lw = opaque(sb + t4 * 1024 + lane * 16);
  const uint32_t qs = opaque(sb + CH_QK + WG * 2048 + t4 * 512 + lane * 16);
  const uint32_t qa = opaque(sb + CH_QK + (lane >> 4) * 2048 + (lane & 15) * 16 + (WG == 0 ? t4 * 512 + 256 : t4 == 3 ? 1024 : 0));
  const uint32_t ka = opaque(t4 < 2 ? sb + CH_KT + t4 * 512 + lane * 16
                                    : sb + CH_QK + 256 + (t4 - 2) * 1024 + ((lane >> 3) & 1) * 2048 + (lane >> 4) * 128 + (lane & 7) * 16);
  const uint32_t l4 = opaque(sb + t4 * 256 + lane * 4);
  uint32_t pdst[1], pages = 0;
  auto line0 = [&](int i) { return 28 * j + (i < 4 ? 4 * t4 + i : 12 + 2 * t4 + i); };
  const uint32_t plane = opaque((lane >> 4) * 2048 + h * 64 + (lane & 15) * 4);
  if (WG == 0) {
    pages = __ballot_sync(~0u, lds32(sb + CH_O + line0(min(lane, 5)) * 4) & 4096);
  } else {
    pages = __ballot_sync(~0u, lds32(sb + CH_O + (80 + min(lane, 11)) * 4) & 4096);
    pdst[0] = opaque(lds32(sb + CH_O + (j == 0 ? 24 + t4 : 50 + 2 * j + (t4 & 1)) * 4) + plane);
  }
  const uint32_t role = lds32(sb + CH_O + NSLOT * 4), rsrc = lds32(sb + CH_O + role * 4), rdst = (80 + role / 20) * 8192 + role % 20 * 128;
  const uint32_t r1 = mapa(CH_BASE, j == 2 ? 0 : j + 1) - sb, r2 = mapa(CH_BASE, j == 0 ? 2 : j - 1) - sb;
  uint32_t tag = opaque(1);
  auto pool = [&](uint32_t off) { return p.pool + ((tag & 0xfffe) + off); };
  auto after = [&](uint32_t x) { return x & tag & 0xfffe; };
  auto kv = [&](int s, uint32_t a) { return p.kv + (a + ((cta * 2 * NSEG + s) * KV_BYTES - sb)); };
  auto pass = [&](float (&d)[16], const uint32_t (&a)[80], auto k0, auto k1) {
    const uint64_t db = mkdesc(CH_BASE + CH_X + WG * 20480, 512, 128, 0);
#pragma unroll
    for (int k = k0.value; k < k1.value; k++) wg_rs32_00(d, a[4 * k], a[4 * k + 1], a[4 * k + 2], a[4 * k + 3], db + k * 64, k);
    wg_commit();
  };
  auto dump = [&](float (&d)[16], uint32_t a) {
    reg_fence<16>(d);
    sts128(a, pack8(d)); sts128(a + 512, pack8(d + 8));
  };
  uint32_t pph = 0;
  auto tokens0 = [&](int s, auto k0) {
    float dk[16], dv[16];
    bar_sync(9, 256);
    wg_fence();
    pass(dk, ak, Int<0>(), Int<4>());
    const uint4 a0 = lds128(lw + CH_KT), a1 = lds128(lw + CH_KT + 512);
    pin();
    pass(dk, ak, Int<4>(), Int<20>());
    pass(dv, av, Int<0>(), Int<CH_VA>());
    pin();
    wg_wait<1>();
    reg_fence<16>(dk);
    add8(dk, a0); add8(dk + 8, a1);
    const uint4 w0 = pack8(dk), w1 = pack8(dk + 8);
    const uint4 b0 = lds128(lw + CH_VT), b1 = lds128(lw + CH_VT + 512);
    stsm4t(lw + CH_KT, w0.x, w0.z, w0.y, w0.w); stsm4t(lw + CH_KT + 512, w1.x, w1.z, w1.y, w1.w);
    if (CH_KP == 2) bar_arrive(7, 160);
    TM1(6);
    pin();
    if (CH_VA < 20) pass(dv, av, Int<CH_VA>(), Int<20>());
    pin();
#pragma unroll
    for (int k = k0.value; k < CH_TW; k++) ldsm4t(&tw[4 * k], wq + k * 2048);
    TM1(9);
    if (k0.value < CH_TW && t4 >= 2) { mbar_wait_hot(bH + t4 * 16 - 24 + (pph & 1) * 8, pph >> 1 & 1); pph++; }
    __syncwarp();
    wg_wait<0>();
    reg_fence<16>(dv);
    add8(dv, b0); add8(dv + 8, b1);
#pragma unroll
    for (int e = 0; e < 2; e++) { const uint4 v = pack8(dv + 8 * e); sts128(lw + CH_VT + e * 512, make_uint4(v.x, v.z, v.y, v.w)); }
  };
  auto publish_k = [&](int s) {
    if (t4 == CH_KW && elect()) { fence_async(); bulk_store(p.kv + (size_t)(cta * 2 * NSEG + s) * KV_BYTES, sb + CH_KT, 4096); bulk_commit(); }
    __syncwarp();
  };
  if (WG == 0) {
    mbar_wait(bXB, 0);
    tokens0(0, Int<CH_TW>());
  } else {
    const uint32_t* m0 = reinterpret_cast<const uint32_t*>(p.mem0) + (lane >> 2) * 320 + t4 * 80 + (lane & 3);
    uint32_t a[20];
#pragma unroll
    for (int i = 0; i < 20; i++) a[i] = m0[4 * i];
    pin();
    float dk[16], dv[16];
    mbar_wait(bXA, 0);
    wg_fence();
    pass(dk, ak, Int<0>(), Int<20>());
    pass(dv, av, Int<0>(), Int<20>());
    wg_wait<0>();
    dump(dk, lw + CH_KT);
    dump(dv, lw + CH_VT);
    bar_sync(9, 256);
    if (CH_KP == 2 && t4 == CH_KW) { bar_sync(7, 160); publish_k(0); }
#pragma unroll
    for (int i = 0; i < 20; i++) sts32(sb + CH_M + (t4 * 20 + i) * 128 + lane * 4, nz(transpose8(a[i])));
    __syncwarp();
    if (elect()) mbar_arrive(bG + t4 * 8);
  }
  PRO(8);
  mbar_wait(bWq, 0);
  refill();
  PRO(9);
  mbar_wait(bWo, 0);
  asm volatile("barrier.cluster.wait.aligned;" ::: "memory");
  PRO(10);
  auto load_x = [&](int s, int k0, int n, uint32_t bar) {
    if (!NOX && elect()) { mbar_expect(bar, n * 1024); bulk_load(sb + CH_X + k0 * 1024, p.xc + (s + 1) * 10240 + k0 * 256, n * 1024, bar); }
  };
  constexpr int VK = WG == 0 ? CH_VK0 : CH_VK1;
  uint32_t gph = 0;
  int st = 0;
  const uint32_t ca = opaque(sb + CH_M + t4 * 2560 + lane * 32 + (lane >> 2) * 4);
  auto project = [&](int s, uint32_t (&b)[40], float (&dv)[16], uint32_t (&kf)[16]) {
    float dq[4] = {}, dk[4] = {};
    uint32_t w[80];
#pragma unroll
    for (int i = 0; i < 4 * CH_TW; i++) w[i] = tw[i];
    constexpr int LR = WG == 1 ? CH_LR1 : CH_LR;
    auto load = [&](int n) {
      int c = 0;
#pragma unroll
      for (int i = 0; i < 10; i++) {
        if (i == CH_KF) {
#pragma unroll
          for (int q = 0; q < 4; q++)
            if (WG == 1 && c++ == n) ldsm4(&kf[4 * q], ka + q * 1024);
        }
        if (c++ == n) ldsm4t(&b[4 * i], l16 + CH_M + WG * 5120 + i * 512);
#pragma unroll
        for (int k = 2 * i; k < 2 * i + 2; k++)
          if (k >= CH_TW && c++ == n) ldsm4t(&w[4 * k], wq + k * 2048);
      }
#pragma unroll
      for (int i = 0; i < 4; i++)
        if (WG == 1 && CH_KF >= 10 && c++ == n) ldsm4(&kf[4 * i], ka + i * 1024);
    };
    if (WG == 1) {
      for (int n = 0;;) {
        mbar_wait(bG + t4 * 8, gph);
        TR(5, (clk32() & ~3u) | min(n, 3));
        gph ^= 1;
        if (__builtin_expect(!__any_sync(~0u, __vimin3_u32(lds32(ca), lds32(ca + 1024), lds32(ca + 1536)) == 0), 1)) break;
        if (elect()) {
          const int q = (st == 0 ? 8 : st * 4 - 4) + t4;
          mbar_expect(bG + t4 * 8, 2560);
          bulk_load(sb + CH_M + t4 * 2560, p.pool + ((80 + q) * 8192 + (pages >> q & 1) * 4096), 2560, bG + t4 * 8);
        }
        spin_guard(n);
      }
    }
    bar_sync(6, 256);
#pragma unroll
    for (int i = 0; i < CH_L0; i++) load(i);
    if (WG == 0 && CH_XB == 4 && s + 1 < NSEG) load_x(s, 5 * t4, 5, bXB);
    TM(0);
    TM1(11);
    if (WG == 1) TR(6, clk32());
#pragma unroll
    for (int k = 0; k < 20; k += 2) {
      if (k > 0) {
#pragma unroll
        for (int n = (k == 18 ? 40 : CH_L0 + k * LR / 4) - 1; n >= CH_L0 + (k - 2) * LR / 4; n--) { load(n); if (CH_LO) __syncwarp(); }
      }
      pin();
#pragma unroll
      for (int kk = k; kk < k + 2; kk++) {
        mma16(dk, ak[4 * kk], ak[4 * kk + 1], ak[4 * kk + 2], ak[4 * kk + 3], b[2 * kk], b[2 * kk + 1]);
        mma16(dq, w[4 * kk], w[4 * kk + 1], w[4 * kk + 2], w[4 * kk + 3], b[2 * kk], b[2 * kk + 1]);
        if (kk < VK) mma16(dv, av[4 * kk], av[4 * kk + 1], av[4 * kk + 2], av[4 * kk + 3], b[2 * kk], b[2 * kk + 1]);
      }
    }
    const float k2 = 0.07216878364870322f * 1.44269504089f;
    stsm4t(qs, pack2(dq[0] * k2, dq[1] * k2), pack2(dq[2] * k2, dq[3] * k2), pack2(dk[0], dk[1]), pack2(dk[2], dk[3]));
    TM(1);
  };
  static_assert(CH_VK1 == 20 && CH_KP == 0 && CH_XA > 0 && CH_XB > 0, "last step");
  constexpr int VC = VK == 20 ? 1 : WG == 0 ? 2 : 3;
  auto finish_v = [&](const uint32_t (&b)[40], float (&dv)[16]) {
#pragma unroll
    for (int kk = VK; kk < 20; kk++) mma16(dv + 4 * ((kk - VK) % VC), av[4 * kk], av[4 * kk + 1], av[4 * kk + 2], av[4 * kk + 3], b[2 * kk], b[2 * kk + 1]);
  };
  auto sum_v = [&](float (&dv)[16]) {
#pragma unroll
    for (int i = 4; i < 4 * VC; i++) dv[i & 3] += dv[i];
  };
  auto publish_km = [&](int s) {
    uint32_t a[4];
    ldsm4(a, qa);
    *reinterpret_cast<uint2*>(kv(s, l8) + KV_M) = make_uint2(hadd2(a[0], a[2]), hadd2(a[1], a[3]));
  };
  auto memory_v = [&](uint2 x, const float (&dv)[16]) {
    return make_uint2(pack2(dv[0] + bf_lo(x.x), dv[1] + bf_hi(x.x)), pack2(dv[2] + bf_lo(x.y), dv[3] + bf_hi(x.y)));
  };
  auto publish_v = [&](int s, const uint4 (&v)[2], uint2 vm) {
#pragma unroll
    for (int e = 0; e < 2; e++) reinterpret_cast<uint4*>(kv(s, lw) + KV_V)[e * 32] = v[e];
    *reinterpret_cast<uint2*>(kv(s, l8) + KV_V + KV_M) = vm;
  };
#pragma unroll 1
  for (int s = 0;; s++) {
    float dv[16] = {};
    uint32_t b[40], kf[16];
    project(s, b, dv, kf);
    if (WG == 0) {
      bar_sync(1, 256);
      if (CH_XA == 0) load_x(s, 20 + 5 * t4, 5, bXA);
      if (CH_XB == 0) load_x(s, 5 * t4, 5, bXB);
      pin();
      finish_v(b, dv);
      sum_v(dv);
      sts64(l8 + CH_VP, pack2(dv[0], dv[1]), pack2(dv[2], dv[3]));
      if (s == NSEG - 1) {
        bar_arrive(10, 256);
        publish_k(s);
        publish_km(s);
        bulk_wait<0>();
        fence_async_global();
        bar_sync(2, 256);
        if (tid == 0) red_release(p.sync + 15 * 8 + 4, 1);
        break;
      }
      __syncwarp();
      if (elect()) mbar_arrive(bX);
      if (CH_XA == 1) load_x(s, 20 + 5 * t4, 5, bXA);
      if (CH_XB == 1) load_x(s, 5 * t4, 5, bXB);
      uint32_t w[144];
      auto wload = [&](int i) { ldsm4t(&w[4 * i], (i % 3 == 0 ? wo : i % 3 == 1 ? wo ^ 32 : wo2) + i / 12 * 28672 + i / 3 % 4 * 1024); };
      TM(3);
      if (CH_KP == 0) publish_k(s);
#pragma unroll
      for (int i = 0; i < CH_W1; i++) wload(i);
      bar_sync(10, 256);
      uint32_t km[4];
      ldsm4(km, qa);
      pin();
#pragma unroll
      for (int i = CH_W1; i < CH_W2; i++) wload(i);
      pin();
      const uint2 kms = make_uint2(hadd2(km[0], km[2]), hadd2(km[1], km[3]));
      if (CH_KM == 0) *reinterpret_cast<uint2*>(kv(s, l8) + KV_M) = kms;
      if (CH_KP == 0) bulk_wait_read<0>();
      if (CH_XA == 2) load_x(s, 20 + 5 * t4, 5, bXA);
      if (CH_XB == 2) load_x(s, 5 * t4, 5, bXB);
      bar_sync(2, 256);
      {
        float y[3][4] = {};
        uint32_t ob[24];
        ldsm4(&ob[0], l16 + CH_O + 1024); ldsm4(&ob[4], l16 + CH_O + 1536);
        TM(7);
        auto step = [&](int i) {
          const int k = i / 3;
          mma16(y[i % 3], w[4 * i], w[4 * i + 1], w[4 * i + 2], w[4 * i + 3], ob[2 * k], ob[2 * k + 1]);
        };
#pragma unroll
        for (int i = 0; i < 12; i++) {
          step(i);
          if (i >= 12 - (CH_W3 - CH_W2)) wload(CH_W3 - 12 + i);
          if (i % 3 == 2) pin();
        }
        if (CH_XB == 3) load_x(s, 5 * t4, 5, bXB);
        if (CH_KM == 1) *reinterpret_cast<uint2*>(kv(s, l8) + KV_M) = kms;
        pin();
        mbar_wait(bO, s & 1);
        TM(4);
        ldsm4(&ob[8], l16 + CH_O); ldsm4(&ob[12], l16 + CH_O + 512);
        pin();
        float2 inv;
        uint8_t* dst[6];
        uint32_t mask;
#pragma unroll
        for (int i = 12; i < 36; i++) {
          step(i);
          const int n = CH_W3 + i - 13, m = n - (n > 30);
          if (i == 12) ldsm4(&ob[16], l16 + after(w[4 * CH_W3 - 1] | w[4 * CH_W3 - 5] | w[4 * CH_W3 - 9] | ob[8]) + CH_O + 2048);
          else if (n == 30) ldsm4(&ob[20], l16 + CH_O + 2560);
          else if (m < 36) wload(m);
          else if (m == 36) inv = lds64f((l8 & ~0xe0u) + CH_VP);
          if (i == 26) mask = ((l16 ^ tag) & 48) == 0;
          if (i >= 27 && i < 33) dst[i - 27] = pool(line0(i - 27) * 8192 + (pages >> (i - 27) & 1) * 4096) + plane;
          if (i % 3 == 2) pin();
        }
#pragma unroll
        for (int k = 0; k < CH_R1; k++) ldsm4t(&tw[4 * k], wq + k * 2048);
        pin();
#pragma unroll
        for (int i = 0; i < 6; i++) stg_strong32(dst[i], pack_tag(y[i >> 1][2 * (i & 1)] * inv.x, y[i >> 1][2 * (i & 1) + 1] * inv.y, tag, mask));
        TM(8);
        TR(0, clk32());
        bar_arrive(5, 256);
        pin();
      }
      const uint32_t t0 = clk32();
      auto refill2 = [&]() {
#pragma unroll
        for (int k = CH_R1; k < CH_R2; k++) ldsm4t(&tw[4 * k], wq + k * 2048);
      };
      if (CH_RP == 0) refill2();
      const uint32_t ln = (l16 ^ tag) >> 4 & 31;
      if (t4 >= 2) {
        const uint32_t bP = bH + t4 * 16 - 24, ps = CH_PS + (t4 & 1) * 4096;
        auto fetch = [&](uint32_t k) {
          if (elect()) { mbar_expect(bP + (k & 1) * 8, 2048); bulk_load(sb + ps + (k & 1) * 2048, p.pool + (rsrc + (t4 & 1) * 2048), 2048, bP + (k & 1) * 8); }
        };
        until(t0 + CH_D0);
        fetch(pph);
        if (CH_RP == 2) refill2();
        if (!NOX) mbar_wait_hot(bXB, (s + 1) & 1);
        const uint32_t want = (tag & 1) * 0x10001, chk = opaque(ln < 4 ? 0x10001 : 0);
        uint4 sel;
        sel.x = opaque((ln >> 3) != (ln & 1) ? 0 : ln & 4 ? 0x3f800000u : 0x00003f80u);
        sel.z = opaque(sel.x); sel.y = opaque(ln); sel.w = opaque(ln + 1);
        uint8_t* mdst = p.pool + opaque(st * 32768 + rdst + (t4 & 1) * 64 + ln * 4);
        until(t0 + CH_D1);
        fetch(pph + 1);
        TM(5);
        if (CH_RP == 1) refill2();
        int n = 0;
        uint32_t u[16];
        for (;;) {
          mbar_wait(bP + (pph & 1) * 8, pph >> 1 & 1);
          TM(14);
          TR(2, clk32());
#pragma unroll
          for (int i = 0; i < 4; i++) ldsm4t(&u[4 * i], l16 + (ps + (pph & 1) * 2048) + i * 512);
          pph++;
          uint32_t bad = 0;
#pragma unroll
          for (int i = 0; i < 4; i++) bad = or3(bad, differ(u[4 * i], u[4 * i + 1], want), differ(u[4 * i + 2], u[4 * i + 3], want));
          if (!__any_sync(~0u, bad & chk)) break;
          fetch(pph + 1);
          spin_guard(n);
        }
        float y[4][4] = {};
#pragma unroll
        for (int i = 0; i < 8; i++) mma16(y[i & 3], sel.x, sel.y, sel.z, sel.w, u[2 * i], u[2 * i + 1]);
        TR(1, t0 + (n ? CH_D1 : CH_D0));
        TM(15);
        const uint32_t w = nz(pack2((y[0][0] + y[1][0]) + (y[2][0] + y[3][0]), (y[0][1] + y[1][1]) + (y[2][1] + y[3][1])));
        if (ln < 16) { stg_strong32(mdst, w); stg_strong32(mdst + 4096, w); }
        TMV(12, 32, n);
        TR(3, (clk32() & ~3u) | min(n, 3));
      } else {
        if (CH_RP) refill2();
        if (!NOX) mbar_wait_hot(bXB, (s + 1) & 1);
        stg_strong32(p.pool + ((st == 2 ? 0 : st + 1) * 32768 + rdst + t4 * 4096) + ln * 4, 0u);
        if (t4 == 0 && cta < 40 && s + 4 < NSEG && elect())
          asm volatile("cp.async.bulk.prefetch.L2.global [%0], 1024;" :: "l"(p.xc + (s + 4) * 10240 + cta * 256) : "memory");
        if (t4 == 1 && (s & 3) == 0 && s > 0 && elect()) red_relaxed(p.sync + 2 * s - 4, 1);
        if (t4 == 1 && s == NSEG - 3 && cta == 95 && elect()) red_relaxed(p.sync + 2 * s + 2, 0x10000);
      }
      TM(10);
      bar_arrive(8, 256);
      tokens0(s + 1, Int<CH_R2>());
      TM(2);
      TR(7, clk32());
    } else {
      if (s == NSEG - 1) {
        bar_arrive(1, 256);
        const uint4 v[2] = {lds128(lw + CH_VT), lds128(lw + CH_VT + 512)};
        bar_sync(10, 256);
        publish_v(s, v, memory_v(lds64(l8 + CH_VP), dv));
        bar_arrive(2, 256);
        break;
      }
      const uint32_t xo = l4 + (CH_SX - (t4 == 3 ? 128 : 0)), x1 = xo + (r1 + 768 + min(t4, 2) * 256), x2 = xo + (r2 + 1024 + min(t4, 2) * 256);
      if (t4 < 2) {
        float ds[4][4] = {};
        uint32_t q[16];
        asm volatile("bar.sync 1, 256;" ::: "memory");
#pragma unroll
        for (int k = 0; k < 4; k++) ldsm4(&q[4 * k], qa + k * 512);
        pin();
        if (VK < 20) { finish_v(b, dv); pin(); }
#pragma unroll
        for (int k = 0; k < 4; k++) {
          mma16(ds[k & 1], kf[4 * k], kf[4 * k + 1], kf[4 * k + 2], kf[4 * k + 3], q[4 * k], q[4 * k + 1]);
          mma16(ds[2 + (k & 1)], kf[4 * k], kf[4 * k + 1], kf[4 * k + 2], kf[4 * k + 3], q[4 * k + 2], q[4 * k + 3]);
        }
        float t[4];
#pragma unroll
        for (int i = 0; i < 4; i++) t[i] = (ds[0][i] + ds[2][i]) + (ds[1][i] + ds[3][i]);
        const uint32_t w0 = pack2(t[0], t[1]), w1 = pack2(t[2], t[3]);
        st_async32(x1, w0, bX + r1); st_async32(x2, w0, bX + r2);
        st_async32(x1 + 128, w1, bX + r1); st_async32(x2 + 128, w1, bX + r2);
        sts32(xo, w0); sts32(xo + 128, w1);
      } else {
        float ds[4][4] = {};
        uint32_t q0[4], q1[4], a0[4], a1[4];
        asm volatile("bar.sync 1, 256; " ::: "memory");
        ldsm4(a0, ka); ldsm4(q0, qa); ldsm4(a1, ka + 512); ldsm4(q1, qa + 512);
        pin();
        if (VK < 20) { finish_v(b, dv); pin(); }
        mma16(ds[0], a0[0], a0[1], a0[2], a0[3], q0[0], q0[1]);
        mma16(ds[1], a0[0], a0[1], a0[2], a0[3], q0[2], q0[3]);
        mma16(ds[2], a1[0], a1[1], a1[2], a1[3], q1[0], q1[1]);
        mma16(ds[3], a1[0], a1[1], a1[2], a1[3], q1[2], q1[3]);
        float t[2];
#pragma unroll
        for (int i = 0; i < 2; i++)
          t[i] = ((ds[0][i] + ds[0][i + 2]) + (ds[1][i] + ds[1][i + 2])) + ((ds[2][i] + ds[2][i + 2]) + (ds[3][i] + ds[3][i + 2]));
        const uint32_t w0 = pack2(t[0], t[1]);
        st_async32(x1, w0, bX + r1);
        st_async32(x2, w0, bX + r2);
        sts32(xo, w0);
      }
      TM(3);
      const uint4 id = lds128(l16 + CH_ID);
      float sc[3][4] = {};
      uint4 v[2];
      sum_v(dv);
      bar_sync(3, 128);
      uint32_t r[12], wd[12], we[12] = {};
      ldsm4(&r[0], l16 + CH_SX); ldsm2(&r[4], l16 + CH_SX + 512);
      pin();
      v[0] = lds128(lw + CH_VT); v[1] = lds128(lw + CH_VT + 512);
#pragma unroll
      for (int u = 0; u < 3; u++) ldsm4t(&wd[4 * u], wo + u * 28672);
      if (CH_WE && j == 0) {
#pragma unroll
        for (int u = 0; u < 3; u++) ldsm4t(&we[4 * u], (wo ^ 32) + u * 28672);
      }
      pin();
#pragma unroll
      for (int q = 0; q < 3; q++) mma16(sc[q], id.x, id.y, id.z, id.w, r[2 * q], r[2 * q + 1]);
      uint32_t big = absmax2(absmax2(absmax2(r[0], r[1]), absmax2(r[2], r[3])), absmax2(r[4], r[5]));
      const uint32_t oa1 = l4 + (r1 + CH_O), oa2 = l4 + (r2 + CH_O + 2048), ones = 0x3f803f80u;
      mbar_wait_hot(bX, s & 1);
      TM(4);
      ldsm4(&r[0], l16 + CH_SX + 768); ldsm4(&r[8], l16 + CH_SX + 1792); ldsm4(&r[4], l16 + CH_SX + 1280);
      const uint2 vp = lds64(l8 + CH_VP);
      bar_arrive(10, 256);
      pin();
      {
        float sd[3][4] = {};
#pragma unroll
        for (int i = 0; i < 3; i++) {
          const int q = i == 0 ? 0 : 3 - i;
          mma16(sc[q], id.x, id.y, id.z, id.w, r[4 * q], r[4 * q + 1]);
          mma16(sd[q], id.x, id.y, id.z, id.w, r[4 * q + 2], r[4 * q + 3]);
          big = absmax2(big, absmax2(absmax2(r[4 * q], r[4 * q + 1]), absmax2(r[4 * q + 2], r[4 * q + 3])));
        }
#pragma unroll
        for (int i = 0; i < 12; i++) sc[i >> 2][i & 3] += sd[i >> 2][i & 3];
      }
      const bool redo = __any_sync(~0u, (absmax2(big, big << 16) & 0x7fff0000u) >= 0x41800000u);
      const uint2 vm = memory_v(vp, dv);
      sc[2][0] += sc[2][2]; sc[2][1] += sc[2][3];
      float l[4], o[2][4];
      uint32_t p3, p4;
      auto attend = [&]() {
#pragma unroll
        for (int i = 0; i < 4; i++) l[i] = o[0][i] = o[1][i] = 0.f;
        const uint32_t p1 = pack2(ex2(sc[0][0]), ex2(sc[0][1])), p2 = pack2(ex2(sc[0][2]), ex2(sc[0][3]));
        mma16h(o[0], p1, p2, v[0].x, v[0].y);
        mma16h(o[1], p1, p2, v[0].z, v[0].w);
        mma16h(l, p1, p2, ones, ones);
        const uint32_t p0 = pack2(ex2(sc[2][0]), ex2(sc[2][1]));
        mma8h(o[0], p0, vm.x);
        mma8h(o[1], p0, vm.y);
        mma8h(l, p0, ones);
        p3 = pack2(ex2(sc[1][0]), ex2(sc[1][1])); p4 = pack2(ex2(sc[1][2]), ex2(sc[1][3]));
        mma16h(o[0], p3, p4, v[1].x, v[1].y);
        mma16h(o[1], p3, p4, v[1].z, v[1].w);
      };
      attend();
      if (__builtin_expect(redo, 0)) {
        float mx = fmaxf(sc[2][0], sc[2][1]);
#pragma unroll
        for (int i = 0; i < 4; i++) mx = fmaxf(mx, fmaxf(sc[0][i], sc[1][i]));
        mx = fmaxf(mx, __shfl_xor_sync(~0u, mx, 1));
        mx = fmaxf(mx, __shfl_xor_sync(~0u, mx, 2));
#pragma unroll
        for (int i = 0; i < 4; i++) { sc[0][i] -= mx; sc[1][i] -= mx; }
        sc[2][0] -= mx; sc[2][1] -= mx;
        attend();
      }
      const uint32_t o0 = pack2(o[0][0], o[0][1]), o1 = pack2(o[1][0], o[1][1]);
      st_async32(oa1, o0, bO + r1); st_async32(oa2, o0, bO + r2);
      st_async32(oa1 + 128, o1, bO + r1); st_async32(oa2 + 128, o1, bO + r2);
      sts32(l4 + CH_O + 1024, o0); sts32(l4 + CH_O + 1152, o1);
      bar_arrive(2, 256);
      pin();
      TM(6);
      mma16h(l, p3, p4, ones, ones);
      float inv;
      asm("rcp.approx.ftz.f32 %0, %1;" : "=f"(inv) : "f"(l[0]));
      sts32((l8 & ~0xffu) + (lane & 28) + CH_VP, __float_as_uint(inv));
      __syncwarp();
      if (elect()) mbar_arrive(bO);
      {
        float z[2][4] = {}, y[2][4] = {};
        mma16(z[0], wd[0], wd[1], wd[2], wd[3], o0, o1);
        if (j == 0) {
#pragma unroll
          for (int u = 0; u < 3; u++) if (!CH_WE) ldsm4t(&we[4 * u], (wo ^ 32) + u * 28672);
          mma16(y[0], we[0], we[1], we[2], we[3], o0, o1);
        }
        const float2 iv = lds64f((l8 & ~0xe0u) + CH_VP);
        uint8_t* dst = pool(pdst[0]);
        const uint32_t mask = ((l16 ^ tag) & 48) == 0;
        const uint32_t oa = qa + ((tag & 0xfffe) + CH_O - CH_QK + t4 * 256 - (t4 == 3 ? 1024 : 0));
        const uint32_t za = l16 + ((tag & 0xfffe) + (t4 >> 1) * 512 + (t4 & 1) * 8);
        pin();
        mbar_wait(bO, s & 1);
        uint32_t a[4];
        ldsm4(a, oa);
        mma16(z[0], wd[4], wd[5], wd[6], wd[7], a[0], a[1]);
        mma16(z[1], wd[8], wd[9], wd[10], wd[11], a[2], a[3]);
        if (j == 0) {
          mma16(y[0], we[4], we[5], we[6], we[7], a[0], a[1]);
          mma16(y[1], we[8], we[9], we[10], we[11], a[2], a[3]);
          sts128f(lw + CH_VT + 512, y[0][0] + y[1][0], y[0][1] + y[1][1], y[0][2] + y[1][2], y[0][3] + y[1][3]);
        }
        sts128f(lw + CH_VT, z[0][0] + z[1][0], z[0][1] + z[1][1], z[0][2] + z[1][2], z[0][3] + z[1][3]);
        bar_sync(3, 128);
        if (j == 0 || t4 < 2) {
          float2 q[4];
#pragma unroll
          for (int i = 0; i < 4; i++) q[i] = lds64f(za + CH_VT + i * 1024);
          stg_strong32(dst, pack_tag(((q[0].x + q[1].x) + (q[2].x + q[3].x)) * iv.x, ((q[0].y + q[1].y) + (q[2].y + q[3].y)) * iv.y, tag, mask));
        }
      }
      TM(2);
      if (!NOX) mbar_wait_hot(bXA, (s + 1) & 1);
      if (CH_KP == 2) bulk_wait_read<0>();
      float dk[16], dw[16];
      bar_sync(5, 256);
      wg_fence();
      pass(dk, ak, Int<0>(), Int<20>());
      pass(dw, av, Int<0>(), Int<20>());
      TM(5);
      pin();
      if (CH_EX == 0) publish_v(s, v, vm);
      if (elect()) {
        mbar_expect(bG + t4 * 8, 2560);
        if (t4 == 1 && s + 2 < NSEG) { mbar_expect(bX, 1536); mbar_expect(bO, 2048); }
      }
      if (CH_KD == 0) { wg_wait<1>(); dump(dk, lw + CH_KT); }
      wg_wait<0>();
      if (CH_KD == 1) dump(dk, lw + CH_KT);
      TM(7);
      dump(dw, lw + CH_VT);
      bar_arrive(9, 256);
      pin();
#pragma unroll
      for (int k = 0; k < CH_RB; k++) ldsm4t(&tw[4 * k], wq + k * 2048);
      if (t4 < 2) {
#pragma unroll
        for (int k = CH_RB; k < CH_RC; k++) ldsm4t(&tw[4 * k], wq + k * 2048);
        const int q = t4 ? 3 : j, o = t4 ? j * 896 : 0;
        const uint8_t* src = p.pool + ((80 + st * 4 + q) * 8192 + (pages >> (st * 4 + q) & 1) * 4096 + o);
        asm volatile("bar.sync 8, 256;" ::: "memory");
        const uint32_t t1 = clk32() + CH_D2;
        if (CH_EX == 1) publish_v(s, v, vm);
        auto fetch = [&](auto n) {
          mbar_wait(bH, s & 1);
          until(t1);
          TR(4, clk32());
          if (elect())
            asm volatile("cp.async.bulk.shared::cluster.global.mbarrier::complete_tx::bytes.multicast::cluster [%0], [%1], %2, [%3], 7;"
                         :: "r"(sb + CH_M + q * 2560 + o), "l"(src), "n"(n.value), "r"(bG + q * 8) : "memory");
        };
        if (!t4) fetch(Int<2560>()); else if (j == 2) fetch(Int<768>()); else fetch(Int<896>());
      } else {
        asm volatile("bar.sync 8, 256; " ::: "memory");
        if (elect()) asm volatile("mbarrier.arrive.relaxed.cluster.shared::cluster.b64 _, [%0];" :: "r"(bH + (t4 == 2 ? r1 : r2)) : "memory");
        pin();
        if (CH_EX == 1) publish_v(s, v, vm);
#pragma unroll
        for (int k = CH_RB; k < CH_RC; k++) ldsm4t(&tw[4 * k], wq + k * 2048);
      }
      TM(9);
      pin();
#pragma unroll
      for (int k = CH_RC; k < CH_TW; k++) ldsm4t(&tw[4 * k], wq + k * 2048);
      if (CH_KP == 2 && t4 == CH_KW) { bar_sync(7, 160); publish_k(s + 1); }
      TM(10);
    }
    if (++st == 3) st = 0;
    tag ^= 0x10001;
  }
}

__global__ void __launch_bounds__(256, 1) chain_kernel(const __grid_constant__ ChainParams p) {
  extern __shared__ __align__(1024) uint8_t smem_raw[];
  const uint32_t sb = s2u(smem_raw);
  const int tid = threadIdx.x, warp = __shfl_sync(~0u, tid >> 5, 0), lane = tid & 31;
  const int cta = blockIdx.x, h = cta / 3, j = cta - 3 * h, colbase = cta * 64;
  const uint32_t bWo = sb + CH_BAR, bWq = bWo + 8, bXA = bWo + 24, bWk = bWo + 80, bWv = bWo + 88;
  uint32_t smid; asm("mov.u32 %0, %%smid;" : "=r"(smid));
  PRO(0);
  if (sb != mapa(CH_BASE, j)) __trap();
  uint32_t entry = 0;
  auto place = [&]() {
    const int i = tid - 128;
    if (i >= 0 && i <= NSLOT) {
      const uint32_t side = ldg_strong32(g_smpart + (smid & 255));
      if (i < NSLOT) {
        entry = i * 8192 + (ldg_strong32(g_orient + i) == (i < 80 ? i & 1 : side) ? 0 : 4096);
      } else {
        entry = 2 * (atomicAdd(g_bo + p.layer * 128 + 1, 1 << 8 * side) >> 8 * side & 255) + side;
      }
    }
    __syncwarp();
  };
  if (p.layer) place();
  if (warp == 0 && elect()) {
#pragma unroll 1
    for (int i = 0; i < 17; i++) mbar_init(bWo + 8 * i, i == 2 || i == 5 ? 5 : i == 3 || i == 4 ? 4 : i == 12 ? 2 : 1);
    asm volatile("fence.mbarrier_init.release.cluster;" ::: "memory");
    mbar_expect(bWk, 81920);
    tma_load3<(WEF & 1) != 0>(sb + CH_WQ, &p.wk, colbase, 0, bWk);
    mbar_expect(bWv, 81920);
    tma_load3<(WEF & 1) != 0>(sb + CH_WO, &p.wv, colbase, 0, bWv);
    mbar_expect(bWo + 16, 1536);
    mbar_expect(bWo + 40, 2048);
    mbar_expect(bWo, 86016); mbar_expect(bWq, 81920);
#pragma unroll 1
    for (int i = 0; i < 8; i++) mbar_expect(bXA + 8 * (i & 1), 5120);
  }
  if (warp == 1) {
    const uint32_t id = (lane >> 3) == (lane & 3) ? ((lane & 4) ? 0x3f800000u : 0x00003f80u) : 0u;
    sts128(sb + CH_ID + lane * 16, make_uint4(id, 0, 0, id));
  }
  __syncthreads();
  asm volatile("barrier.cluster.arrive.relaxed.aligned;" ::: "memory");
  uint32_t ak[80], av[80];
  const uint32_t wq = opaque(sb + CH_WQ + ((warp >> 2) * 320 + (lane & 7) + (lane >> 4) * 8) * 128 + (((2 * (warp & 3) + ((lane >> 3) & 1)) ^ (lane & 7)) << 4));
  pdl_wait();
  if (tid == 32) stg_strong32(g_smuse + (smid & 255), p.layer + 1);
  pdl_launch();
  PRO(1);
  if (warp == 0 && elect()) {
    bulk_load(sb + CH_X + 20480, p.xc + 5120, 20480, bXA);
    bulk_load(sb + CH_X, p.xc, 20480, bXA + 8);
  }
  if (!p.layer) place();
  __syncwarp();
  PRO(2);
  mbar_wait(bWk, 0);
  PRO(3);
#pragma unroll
  for (int k = 0; k < 20; k++) ldsm4t(&ak[4 * k], wq + k * 2048);
  bar_sync(6, 256);
  if (warp == 0 && elect()) tma_load3<(WEF & 2) != 0>(sb + CH_WQ, &p.wq, colbase, 0, bWq);
  __syncwarp();
  PRO(4);
  mbar_wait(bWv, 0);
  PRO(5);
#pragma unroll
  for (int k = 0; k < 20; k++) ldsm4t(&av[4 * k], wq + CH_WO + k * 2048);
  bar_sync(6, 256);
  PRO(6);
  if (warp >= 5 && elect()) tma_load3<(WEF & 2) != 0>(sb + CH_WO + (warp - 5) * 28672, &p.wo, j == 0 ? 0 : 32 + j * 192, h * 192 + (j + 8 - warp) % 3 * 64, bWo);
  if (tid == 128 + NSLOT && entry >= 80) {
    uint32_t c;
    int n = 0;
    do { c = ldg_strong32(g_bo + p.layer * 128 + 1); spin_guard(n); } while ((c & 255) + (c >> 8) < 96);
    const uint32_t other = (c >> 8 * (~entry & 1) & 255) + (entry >> 1) - 40;
    entry = other < 40 ? 2 * other + (~entry & 1) : entry % 80;
  }
  if (tid >= 128 && tid <= 128 + NSLOT) sts32(sb + CH_O + (tid - 128) * 4, entry);
  PRO(7);
  __syncthreads();
  if (__shfl_sync(~0u, tid >> 7, 0) == 0) chain_body<0>(p, wq, ak, av); else chain_body<1>(p, wq, ak, av);
}

struct PostParams { CUtensorMap wq, wo, wb, wo2, wb2; int gap, share, layer, look, gap2, pol; };
constexpr int PS = 8, PB = 28672;
constexpr int OP_SMEM = PS * PB + 512 + 2048;
enum { IT_ATT = 0, IT_OP = 1, IT_FIN = 2, IT_BQ = 3, IT_Q = 4 };

__device__ __forceinline__ uint32_t item_count(int type, int b) {
  return type == IT_ATT ? 32 : type == IT_OP ? op_split(b) * (b < OP_160 ? 2 : 4) : type == IT_FIN ? fin_items(b) : b < BQ_160 ? 6 : b < BQ_80 ? 12 : 24; }
__device__ __forceinline__ uint32_t item_need(int type, int b) { return type == IT_ATT ? 96 : item_count(type - 1, b); }

struct Ring {
  uint32_t sb, bars; int st; uint32_t ph;
  __device__ __forceinline__ uint32_t wait() const { mbar_wait(bars + 8 * st, ph); return sb + st * PB; }
  __device__ __forceinline__ void next() { if (++st == PS) { st = 0; ph ^= 1; } }
  __device__ __forceinline__ void release(int s) const { if ((threadIdx.x & 31) == 0) mbar_arrive(bars + 8 * (PS + s)); }
  __device__ __forceinline__ void pop() { __syncwarp(); release(st); next(); }
};

template <int N>
__device__ __forceinline__ void gemm_item(Ring& r, float* d, int nst, uint32_t go, int go_at) {
  int prev = 0;
#pragma unroll 1
  for (int kb = 0; kb < nst; kb++) {
    const uint32_t base = r.wait();
    const uint64_t da = mkdesc(base + (threadIdx.x >> 7) * 4096, 128, 512, 0), db = mkdesc(base + 8192, 4096, 1024, 1);
    wg_fence();
#pragma unroll
    for (int kk = 0; kk < 2; kk++) {
      if (N == 80) wg_ss80_01(d, da + kk * 16, db + kk * 128, (kb | kk) != 0);
      if (N == 160) wg_ss160_01(d, da + kk * 16, db + kk * 128, (kb | kk) != 0);
      if (N >= 192) wg_ss192_01(d, da + kk * 16, db + kk * 128, (kb | kk) != 0);
      if (N == 320) wg_ss128_01(d + 96, da + kk * 16, db + kk * 128 + 3 * 256, (kb | kk) != 0);
    }
    wg_commit();
    if (kb == go_at && threadIdx.x == 0) mbar_arrive(go);
    if (kb > 0) { wg_wait<1>(); r.release(prev); }
    prev = r.st;
    r.next();
  }
  wg_wait<0>();
  reg_fence<N / 2>(d);
  r.release(prev);
}

template <int HALF>
__device__ __forceinline__ void attn_a_warp(Ring& r, const uint32_t (&q)[48], int b, int h) {
  constexpr int NT = HALF ? 5 : 3, NF = 8 * NT;
  const int lane = threadIdx.x & 31, g = lane >> 2, c = lane & 3, seg = (threadIdx.x >> 5) & 3;
  uint32_t f[6][NF];
  int slot[6];
  auto fetch = [&](int u) {
    const uint32_t kv = r.wait() + seg * KV_BYTES;
    slot[u] = r.st;
    r.next();
#pragma unroll
    for (int w = 0; w < 4; w++) {
      uint32_t* d = &f[u][2 * NT * w];
#pragma unroll
      for (int t = 0; t <= HALF; t++) {
        if (u < 3) {
          ldsm4(d + 4 * t, kv + w * 1024 + t * 512 + (lane & 8) * 32 + (lane & 16) * 8 + (lane & 7) * 16);
        } else {
          const uint4 v = lds128(kv + w * 1024 + t * 512 + lane * 16);
          d[4 * t] = v.x; d[4 * t + 1] = v.y; d[4 * t + 2] = v.z; d[4 * t + 3] = v.w;
        }
      }
      const uint2 m = lds64(kv + KV_M + w * 256 + lane * 8);
      d[2 * NT - 2] = m.x; d[2 * NT - 1] = m.y;
    }
    pdl_launch();
  };
  float s[NT][4] = {};
  fetch(0);
#pragma unroll
  for (int u = 0; u < 3; u++) {
    fetch(u + 1);
#pragma unroll
    for (int kk = 0; kk < 4; kk++) {
      const uint32_t* a = &q[16 * u + 4 * kk];
#pragma unroll
      for (int n = 0; n < NT; n++) mma16(s[(n + 1) % NT], a[0], a[1], a[2], a[3], f[u][2 * NT * kk + 2 * n], f[u][2 * NT * kk + 2 * n + 1]);
    }
    r.release(slot[u]);
    pdl_launch();
  }
  fetch(4);
  const float k2 = 0.07216878364870322f * 1.44269504089f, NEG = -INFINITY;
  if (2 * c > g) { s[NT - 2][0] = NEG; s[NT - 1][2] = NEG; }
  if (2 * c + 1 > g) { s[NT - 2][1] = NEG; s[NT - 1][3] = NEG; }
  s[NT - 1][0] = s[NT - 1][1] = NEG;
  uint32_t pp[NT][2]; float inv[2];
#pragma unroll
  for (int hh = 0; hh < 2; hh++) {
    float m = NEG, l = 0.f;
#pragma unroll
    for (int n = 0; n < NT; n++) m = fmaxf(m, fmaxf(s[n][2 * hh], s[n][2 * hh + 1]));
    m = fmaxf(m, __shfl_xor_sync(~0u, m, 1)); m = fmaxf(m, __shfl_xor_sync(~0u, m, 2));
#pragma unroll
    for (int n = 0; n < NT; n++) { const float x = ex2((s[n][2 * hh] - m) * k2), y = ex2((s[n][2 * hh + 1] - m) * k2); l += x + y; pp[n][hh] = pack2(x, y); }
    l += __shfl_xor_sync(~0u, l, 1); l += __shfl_xor_sync(~0u, l, 2);
    asm("rcp.approx.ftz.f32 %0, %1;" : "=f"(inv[hh]) : "f"(l));
  }
  uint32_t* dst = g_o + ((b * 192 + h * 6) * 16 + seg * 4 + HALF * 2) * 128 + lane;
#pragma unroll
  for (int u = 3; u < 6; u++) {
    float o[8][4] = {};
#pragma unroll
    for (int n = 0; n < 8; n++) mma8(o[n], pp[0][0], pp[0][1], f[u][2 * NT * (n >> 1) + 2 * NT - 2 + (n & 1)]);
#pragma unroll
    for (int t = 0; t <= HALF; t++)
#pragma unroll
      for (int n = 0; n < 8; n++) {
        const uint32_t* v = &f[u][2 * NT * (n >> 1) + 4 * t + 2 * (n & 1)];
        mma16(o[n], pp[1 + 2 * t][0], pp[1 + 2 * t][1], pp[2 + 2 * t][0], pp[2 + 2 * t][1], v[0], v[1]);
      }
    r.release(slot[u]);
    if (u == 3) fetch(5);
#pragma unroll
    for (int n = 0; n < 8; n++) {
      dst[(u - 3) * 4096 + (n >> 2) * 2048 + (n & 3) * 32] = pack2(o[n][0] * inv[0], o[n][1] * inv[0]);
      dst[(u - 3) * 4096 + (n >> 2) * 2048 + (n & 3) * 32 + 128] = pack2(o[n][2] * inv[1], o[n][3] * inv[1]);
    }
  }
}

template <int NG>
__device__ __forceinline__ void fin_item(Ring& r, uint32_t scratch, int b, int idx) {
  const int warp = threadIdx.x >> 5, lane = threadIdx.x & 31;
  float4* x = g_x + ((b * 16 + idx * NG) * 40 + warp * 5) * 32 + lane;
  float4 v[NG][5];
#pragma unroll
  for (int g = 0; g < NG; g++) {
    const uint32_t base = r.wait();
#pragma unroll
    for (int i = 0; i < 5; i++) v[g][i] = lds128f(base + ((warp * 5 + i) * 32 + lane) * 16);
    r.pop();
  }
#pragma unroll 1
  for (int k = 0; k < op_split(b); k += NG == 1 ? 2 : 1) {
#pragma unroll
    for (int g = 0; g < NG; g += 2) {
      const uint32_t base = r.wait();
#pragma unroll
      for (int i = 0; i < 10; i++) {
        const uint2 q = lds64(base + ((i / 5 * 40 + warp * 5 + i % 5) * 32 + lane) * 8);
        float4& t = v[(g + i / 5) % NG][i % 5];
        t.x += bf_lo(q.x); t.y += bf_hi(q.x); t.z += bf_lo(q.y); t.w += bf_hi(q.y);
      }
      r.pop();
    }
  }
  float mean[NG], rs[NG];
  ln_stats<NG>(v, scratch, mean, rs);
#pragma unroll
  for (int i = 0; i < 5; i++) {
    const int u = warp * 5 + i;
    uint32_t* xn = g_xn + ((b * 20 + (u >> 1)) * 16 + idx * NG) * 128 + (u & 1) * 64 + lane;
#pragma unroll
    for (int g = 0; g < NG; g++) {
      xn[g * 128] = pack2((v[g][i].x - mean[g]) * rs[g], (v[g][i].y - mean[g]) * rs[g]);
      xn[g * 128 + 32] = pack2((v[g][i].z - mean[g]) * rs[g], (v[g][i].w - mean[g]) * rs[g]);
    }
  }
#pragma unroll
  for (int g = 0; g < NG; g++)
#pragma unroll
    for (int i = 0; i < 5; i++) x[(g * 40 + i) * 32] = v[g][i];
}

__global__ void __launch_bounds__(384, 1) post_kernel(const __grid_constant__ PostParams p) {
  extern __shared__ __align__(1024) uint8_t smem_raw[];
  const uint32_t sb = s2u(smem_raw), bars = sb + PS * PB;
  const uint32_t bIF = bars + 128, bIE = bars + 160, done = bars + 192, bGo = bars + 224, slots = bars + 240, scratch = bars + 512;
  const int warp = __shfl_sync(~0u, threadIdx.x >> 5, 0), lane = threadIdx.x & 31;
  TRACE(0);
  pdl_launch();
  if (sb & 1023) __trap();
  if (threadIdx.x < 29) mbar_init(bars + 8 * threadIdx.x, threadIdx.x < 8 ? 1 : threadIdx.x < 16 ? 8 : threadIdx.x < 20 ? 1 : threadIdx.x < 24 ? 2 : threadIdx.x < 28 ? 8 : 1);
  if (threadIdx.x == 32) sts32(slots + 16, p.gap);
  fence_async();
  __syncthreads();
  if (warp >= 8) {
    asm volatile("setmaxnreg.dec.sync.aligned.u32 56;");
    if (warp == 9) {
      const int b = lane & 15;
      bool queries = QA_END < 16 && blockIdx.x < 36;
      for (int n = 0;; n++) {
        if (n > 0) mbar_wait(bGo, (n - 1) & 1);
        mbar_wait(bIE + 8 * (n & 3), ((n >> 2) & 1) ^ 1);
        int code = -1, spin = 0, ticket = 0;
        if (queries) {
          if (lane == 0) ticket = n == 0 ? blockIdx.x : 36 + atomicAdd(g_sync + SY_QC, 1);
          ticket = __shfl_sync(~0u, ticket, 0);
          queries = ticket < (16 - QA_END) * 32;
          if (queries) code = IT_Q << 16 | (QA_END + ticket % (16 - QA_END)) << 8 | ticket / (16 - QA_END);
        }
        if (!queries && lane == 0) asm volatile("atom.relaxed.gpu.global.add.u32 %0, [%1], 1;" : "=r"(ticket) : "l"(g_sync + SY_T) : "memory");
        while (!queries) {
          const uint4 hd = ldg_strong128(g_sync + b * 8), pr = ldg_strong128(g_sync + b * 8 + 4);
          const uint32_t hv[4] = {hd.x, hd.y, hd.z, hd.w}, pv[4] = {pr.x, pr.y, pr.z, pr.w};
          const uint32_t chain_done = __ballot_sync(~0u, (pr.x & 0xffff) >= 96) & 0xffff;
          int left[4], avail[4], rdy = 0, claimed = 0, upstream = 0;
#pragma unroll
          for (int t = 0; t < 4; t++) {
            const int cnt = lane < 16 ? item_count(t, b) : 0;
            left[t] = max(cnt - (int)hv[t], 0);
            claimed += cnt - left[t];
            const bool ready = (pv[t] & 0xffff) >= item_need(t, b);
            rdy |= ready << t;
            bool ok = ready || (t == IT_ATT ? pr.x >= 0x10000 : !upstream || (t == IT_OP && (chain_done >> 15 & 1)));
            if (t == IT_BQ && (chain_done >> BQ_HOLD & 1) && !(chain_done >> 15)) ok = false;
            avail[t] = ok ? left[t] : 0;
            upstream |= __any_sync(~0u, left[t] > 0);
          }
          if (!upstream) break;
          int rank = max(__shfl_sync(~0u, ticket, 0) - __reduce_add_sync(~0u, claimed), 0), type = -1, mine = 0;
#pragma unroll
          for (int c = 0; c < 8; c++) {
            const int t = c == 0 || c == 5 ? IT_FIN : c == 1 || c == 7 ? IT_ATT : c == 2 || c == 4 ? IT_OP : IT_BQ;
            int a = c == 1 || ((rdy >> t & 1) == (c < 4)) ? avail[t] : 0;
            if (t == IT_OP && OP_EARLY) a = c == 2 ? avail[t] : 0;
            if (c == 7) a = b < QA_END && !(rdy & 1) && ((chain_done << 1 | 1) >> b & 1) ? left[t] : 0;
            const int tot = __reduce_add_sync(~0u, a);
            if (type < 0) { if (rank < tot) { type = t; mine = a; } else rank -= tot; }
          }
          if (type >= 0) {
#pragma unroll
            for (int o = 1; o < 16; o <<= 1) { const int y = __shfl_up_sync(~0u, mine, o); if (lane >= o) mine += y; }
            const int blk = __ffs(__ballot_sync(~0u, mine > rank)) - 1;
            const int early = !(__shfl_sync(~0u, rdy, blk) >> type & 1);
            uint32_t idx = 0;
            if (lane == 0) asm volatile("atom.relaxed.gpu.global.add.u32 %0, [%1], 1;" : "=r"(idx) : "l"(g_sync + blk * 8 + type) : "memory");
            ld_acquire(g_sync + blk * 8 + 4 + type);
            idx = __shfl_sync(~0u, idx, 0);
            if (idx < item_count(type, blk)) { code = (chain_done >> 15 & 1) << 22 | (chain_done >> p.look & 1) << 21 | early << 20 | type << 16 | blk << 8 | idx; break; }
          } else {
            __nanosleep(50);
          }
          spin_guard(spin);
        }
        if (lane == 0) {
          fence_async_global();
          sts32(slots + 4 * (n & 3), code);
          mbar_arrive(bIF + 8 * (n & 3));
        }
        __syncwarp();
        if (code < 0) break;
      }
    } else if (warp == 8) {
      if (elect()) {
        uint32_t dst = sb, bar = bars, ph = 1, next = clk32(), gap = 0;
        auto acquire = [&](uint32_t kb) {
          mbar_wait(bar + 8 * PS, ph);
          mbar_expect(bar, kb * 1024);
          if (gap) {
            uint32_t now;
            do now = clk32(); while ((int)(now - next) < 0);
            next = ((int)(now - next) > 100 ? now - 100 : next) + kb * gap;
          }
        };
        auto advance = [&]() { dst += PB; bar += 8; if (dst == bars) { dst = sb; bar = bars; ph ^= 1; } };
        auto depend = [&](const uint32_t* c, uint32_t need) { wait_count(c, need); fence_async_global(); };
#pragma unroll 1
        for (int n = 0;; n++) {
          mbar_wait(bIF + 8 * (n & 3), (n >> 2) & 1);
          const int code = (int)lds32(slots + 4 * (n & 3));
          if (code < 0) break;
          const int type = (code >> 16) & 15, b = (code >> 8) & 255, idx = code & 255;
          const bool early = code >> 20 & 1, go = !(code >> 21 & 1);
          mbar_arrive(bIE + 8 * (n & 3));
          gap = !(code >> 22 & 1) ? lds32(slots + 16) : type == IT_ATT || type == IT_FIN ? 0 : p.gap2;
          const uint32_t* progress = g_sync + b * 8 + 4 + type;
          if (type == IT_ATT && b >= QA_END) {
            depend(g_sync + SY_Q, (16 - QA_END) * 32);
#pragma unroll 1
            for (int u = 0; u < 2; u++) { acquire(24); bulk_load_last(dst, g_q + (((b - QA_END) * 32 + idx) * 2 + u) * 1536, 24576, bar); advance(); }
          } else if (type == IT_FIN) {
            const int ng = 16 / fin_items(b), lg = ng >> 1;
#pragma unroll 1
            for (int g = 0; g < ng; g++) { acquire(20); bulk_load(dst, g_x + (b * 16 + idx * ng + g) * 1280, 20480, bar); advance(); }
            if (early) depend(progress, item_need(type, b));
            if (go) mbar_arrive(bGo);
#pragma unroll 1
            for (int i = 0; i < op_split(b) * ng; i += 2) {
              const uint2* src = g_part + ((b * 16 + (i >> lg)) * 16 + idx * ng + (i & (ng - 1))) * 1280;
              acquire(20);
              bulk_load_last(dst, src, ng > 1 ? 20480 : 10240, bar);
              if (ng == 1) bulk_load_last(dst + 10240, src + 16 * 1280, 10240, bar);
              advance();
            }
            if (!go && p.pol) mbar_arrive(bGo);
          } else {
            const bool op = type == IT_OP, bq = type == IT_BQ;
            const int width = op ? op_width(b) : bq ? bq_width(b) : 192, nb = (width + 63) >> 6, lt = width == 320 ? 1 : 2;
            const int nst = op ? 192 / op_split(b) : 20, kb0 = op ? (idx >> lt) * nst : 0;
            const int col = (op ? idx & ((1 << lt) - 1) : idx) * width;
            const bool whole = !(width & 63);
            const CUtensorMap* m = op ? (whole ? &p.wo : &p.wo2) : bq ? (whole ? &p.wb : &p.wb2) : &p.wq;
            const uint32_t* a = op ? g_o + (b * 192 + kb0) * 2048 : g_xn + b * 20 * 2048;
            int row = kb0 * 32, pre = early && (op || bq) ? min(nst, PS) : 0;
            auto weights = [&]() {
              acquire(8 + nb * 4);
              if (whole) {
                tma_load3z(dst + 8192, m, row, col >> 6, bar);
              } else {
                tma_load(dst + 8192, m, col, row, bar); tma_load(dst + 12288, m, col + 64, row, bar);
                if (nb == 3) tma_load(dst + 16384, m, col + 128, row, bar);
              }
              row += 32;
            };
            if (pre) {
              uint32_t da = dst, ba = bar;
#pragma unroll 1
              for (int kb = 0; kb < pre; kb++) { weights(); advance(); }
              depend(progress, item_need(type, b));
#pragma unroll 1
              for (int kb = 0; kb < pre; kb++) {
                bulk_load(da, a, 8192, ba);
                a += 2048; da += PB; ba += 8;
                if (da == bars) { da = sb; ba = bars; }
              }
            }
#pragma unroll 1
            for (int kb = pre; kb < nst; kb++) { weights(); if (op && OEF) bulk_load_last(dst, a, 8192, bar); else bulk_load(dst, a, 8192, bar); a += 2048; advance(); }
          }
          if (type == IT_ATT) {
            if (early) depend(progress, 96);
            if (go) mbar_arrive(bGo);
            const uint8_t* src = g_kv + (size_t)(idx * 6 * NSEG + b * 4) * KV_BYTES;
#pragma unroll 1
            for (int u = 0; u < 6; u++) {
              acquire(20);
              bulk_load_last(dst, src, 20480, bar);
              src += u == 2 ? -3 * KV_V : 2 * KV_V;
              advance();
            }
            if (!go && p.pol) mbar_arrive(bGo);
          }
        }
      }
    } else if (warp == 11) {
      uint32_t smid, nsm, used = 0;
      asm("mov.u32 %0, %%smid;" : "=r"(smid)); asm("mov.u32 %0, %%nsmid;" : "=r"(nsm));
      for (int n = 0; n < 64 && used < 96; n++) {
        uint32_t peers = 0;
        used = 0;
        for (uint32_t i = lane; i < min(nsm, 256u); i += 32) {
          const bool taken = ldg_strong32(g_smuse + i) == p.layer + 1;
          used += taken;
          peers += abs((int)(g_smclk[i] - g_smclk[smid & 255])) < 4000 && !taken;
        }
        used = __reduce_add_sync(~0u, used);
        sts32(slots + 16, max(p.gap, (int)min(__reduce_add_sync(~0u, peers), 18u) * p.share >> 3));
      }
    } else if (warp == 10 && lane == 0) {
      for (int n = 0;; n++) {
        mbar_wait(bIF + 8 * (n & 3), (n >> 2) & 1);
        const int code = (int)lds32(slots + 4 * (n & 3));
        if (code < 0) break;
        const int type = (code >> 16) & 15, b = (code >> 8) & 255;
        mbar_wait(done + 8 * (n & 3), (n >> 2) & 1);
        if (type != IT_BQ) red_release(type == IT_Q ? g_sync + SY_Q : g_sync + b * 8 + 5 + type, 1);
        mbar_arrive(bIE + 8 * (n & 3));
      }
    }
  } else {
    asm volatile("setmaxnreg.inc.sync.aligned.u32 224;");
    const int g = lane >> 2, c = lane & 3;
    Ring r = {sb, bars, 0, 0};
#pragma unroll 1
    for (int n = 0;; n++) {
      mbar_wait(bIF + 8 * (n & 3), (n >> 2) & 1);
      const int code = __shfl_sync(~0u, (int)lds32(slots + 4 * (n & 3)), 0);
      if (code < 0) { TRACE(2); break; }
      const int type = (code >> 16) & 15, b = (code >> 8) & 255, idx = code & 255;
      ITEM(code & 0xfffff, 0);
      if (type == IT_ATT || type == IT_Q) {
        uint32_t q[48];
        if (type == IT_Q || b < QA_END) {
          float d[96] = {};
          reg_fence<96>(d);
          gemm_item<192>(r, d, 20, bGo, type == IT_Q ? 12 : -1);
#pragma unroll
          for (int i = 0; i < 48; i++) q[i] = pack2(d[2 * i], d[2 * i + 1]);
        } else {
#pragma unroll
          for (int u = 0; u < 2; u++) {
            const uint32_t base = r.wait() + threadIdx.x * 16;
#pragma unroll
            for (int i = 0; i < 6; i++) {
              const uint4 v = lds128(base + i * 4096);
              q[24 * u + 4 * i] = v.x; q[24 * u + 4 * i + 1] = v.y; q[24 * u + 4 * i + 2] = v.z; q[24 * u + 4 * i + 3] = v.w;
            }
            r.pop();
          }
        }
        if (type == IT_Q) {
          uint4* dst = g_q + ((b - QA_END) * 32 + idx) * 3072 + threadIdx.x;
#pragma unroll
          for (int i = 0; i < 12; i++) dst[i * 256] = make_uint4(q[4 * i], q[4 * i + 1], q[4 * i + 2], q[4 * i + 3]);
        } else if (warp < 4) {
          attn_a_warp<0>(r, q, b, idx);
        } else {
          attn_a_warp<1>(r, q, b, idx);
        }
      } else if (type == IT_FIN) {
        if (FIN_8 > 0 && fin_items(b) == 4) fin_item<4>(r, scratch, b, idx);
        else if (FIN_16 > FIN_8 && (FIN_16 == 16 || fin_items(b) == 8)) fin_item<2>(r, scratch, b, idx);
        else fin_item<1>(r, scratch, b, idx);
      } else {
        float d[160] = {};
        reg_fence<160>(d);
        const int width = type == IT_OP ? op_width(b) : bq_width(b), nst = type == IT_OP ? 192 / op_split(b) : 20;
        const int go_at = max(nst - (code >> 21 & 1 ? p.pol : 6), 0);
        if (width == 320) gemm_item<320>(r, d, nst, bGo, go_at);
        else if (width == 160 || BQ_80 == 16) gemm_item<160>(r, d, nst, bGo, go_at);
        else gemm_item<80>(r, d, nst, bGo, go_at);
        reg_fence<160>(d);
        if (type == IT_OP) {
          const int tiles = DM / width;
          uint2* dst = g_part + (((b * 16 + idx / tiles) * 16 + warp * 2) * 40 + idx % tiles * (width / 16)) * 32 + lane;
#pragma unroll
          for (int u = 0; u < 20; u++) {
            if (u % 5 == 0 && u * 16 >= width) break;
            dst[u * 32] = make_uint2(pack2(d[8 * u], d[8 * u + 1]), pack2(d[8 * u + 4], d[8 * u + 5]));
            dst[(40 + u) * 32] = make_uint2(pack2(d[8 * u + 2], d[8 * u + 3]), pack2(d[8 * u + 6], d[8 * u + 7]));
          }
        } else {
          const int row = b * 128 + warp * 16 + g;
          const int h0 = idx * (width / 20);
          const float sc = h0 < 32 ? 0.22360679775f * 1.44269504089f : 1.f;
          const bool lo = c < 2;
          uint32_t* da = g_bqkv + (h0 * 256 + (row >> 3)) * 96 + lane;
          uint32_t* db = da + 256 * 96 + (lo ? 2 : -2);
          uint32_t pad[2];
#pragma unroll
          for (int rr = 0; rr < 2; rr++) pad[rr] = c & 1 || h0 < 32 ? 0u : h0 >= 64 ? 0x00003f80u : poly_group((row >> 3) + rr) ? 0x3f803f80u : 0u;
#pragma unroll
          for (int q = 0; q < 8; q++) {
            if (!(q & 1) && q * 40 >= width) break;
#pragma unroll
            for (int rr = 0; rr < 2; rr++) {
              uint32_t w[5];
#pragma unroll
              for (int i = 0; i < 5; i++) w[i] = pack2(d[20 * q + 4 * i + 2 * rr] * sc, d[20 * q + 4 * i + 2 * rr + 1] * sc);
              const int o = q * 2 * 256 * 96 + rr * 96;
              da[o] = w[0]; da[o + 32] = w[1]; da[o + 64] = lo ? w[2] : pad[rr];
              db[o] = lo ? w[3] : w[2]; db[o + 32] = lo ? w[4] : w[3]; db[o + 64] = lo ? pad[rr] : w[4];
            }
          }
        }
      }
      __syncwarp();
      if (lane == 0) mbar_arrive(done + 8 * (n & 3));
      if ((code >> 21 & 1) && p.pol == 0 && threadIdx.x == 128) mbar_arrive(bGo);
      ITEM(code & 0xfffff, 1);
    }
  }
}

constexpr int AB_SMEM = 1024 + 98304 + 51200 + 4 * 16384 + 256 + 10240;
#define AB_LW 1
#define AB_U 8
#define AB_WG 4
constexpr int AB_T = AB_WG * 128, AB_PASS = 8 / AB_WG;
__device__ __forceinline__ uint32_t fma2(uint32_t a, uint32_t b, uint32_t c) { uint32_t r; asm("fma.rn.bf16x2 %0, %1, %2, %3;" : "=r"(r) : "r"(a), "r"(b), "r"(c)); return r; }
__device__ __forceinline__ uint32_t ex2_pair(float a, float b, uint32_t one, uint32_t c0) {
  const uint32_t e = __byte_perm(__float_as_uint(a), __float_as_uint(b), 0x6521);
  uint32_t x, r;
  asm("lop3.b32 %0, %1, 0x007f007f, %2, 0xEA;" : "=r"(x) : "r"(e), "r"(one));
  const uint32_t m = AB_DEG == 3 ? fma2(fma2(fma2(c0, x, 0xbbdcbbdcu), x, 0x3ef53ef5u), x, 0x3ee83ee8u) : fma2(fma2(c0, x, 0xbc43bc43u), x, 0x3f2e3f2eu);
  asm("lop3.b32 %0, %1, %2, 0x7f807f80, 0xE4;" : "=r"(r) : "r"(e), "r"(m));
  return r;
}
__device__ __forceinline__ float sq2(uint32_t w) { const float a = bf_lo(w), b = bf_hi(w); return fmaf(a, a, b * b); }

__device__ __forceinline__ void attn_b_store(const float* o, int h, int row0, int lane) {
  const int g = lane >> 2, c = lane & 3;
  const float i0 = __frcp_rn(__shfl_sync(~0u, o[8], (lane & ~3) | 2)), i1 = __frcp_rn(__shfl_sync(~0u, o[10], (lane & ~3) | 2));
#pragma unroll
  for (int jj = 0; jj < 3; jj++) {
    if (jj < 2 || c < 2) {
      const int col = h * 20 + 8 * jj + 2 * c;
      uint32_t* dst = g_of + (((row0 >> 7) * 10 + (col >> 6)) * 16 + (row0 >> 3 & 15)) * 256 + (col >> 3 & 7) * 32 + g * 4 + (col >> 1 & 3);
      dst[0] = pack2(o[4 * jj] * i0, o[4 * jj + 1] * i0);
      dst[256] = pack2(o[4 * jj + 2] * i1, o[4 * jj + 3] * i1);
    }
  }
}

struct AbParams { Weights next; uint32_t* done; uint32_t* out; };
__global__ void __launch_bounds__(AB_T + 32, 1) attn_b_kernel(const __grid_constant__ AbParams p) {
  extern __shared__ uint8_t smem_raw[];
  const uint32_t sb = (s2u(smem_raw) + 1023) & ~1023u, sK = sb, sV = sb + 98304, bars = sV + 51200 + 4 * 16384;
  const uint32_t bF = bars + 64, bW = bars + 72, bA = bars + 80, bE = bars + 128, smax = bars + 176;
  auto ring = [&](int i) { return i < 2 ? sK + 51200 + i * 16384 : sV + 51200 + (i - 2) * 16384; };
  const int warp = __shfl_sync(~0u, threadIdx.x >> 5, 0), lane = threadIdx.x & 31;
  const int h = blockIdx.x >> 2, quarter = blockIdx.x & 3;
  TRACE(0);
  pdl_launch();
  if (threadIdx.x < 22) mbar_init(bars + 8 * threadIdx.x, threadIdx.x == 8 ? AB_T / 32 : threadIdx.x >= 16 ? 8 : 1);
  if (threadIdx.x == 32) sts64(smax, 0, 0);
  fence_async();
  __syncthreads();
  pdl_wait();
  const int blk = quarter * 4 + (h >> 3), cg = h & 7;
  auto unsafe = [&]() { const float2 m = lds64f(smax); return !(m.x * m.y <= 10000.f); };
  if (warp == AB_T / 32) {
    auto load_w = [&]() {
      mbar_expect(bW, 102400);
      for (int i = 0; i < 4; i++) bulk_load((i < 2 ? sK : sV) + (i & 1) * 25600, g_wb + cg * 6400 + i * 1600, 25600, bW);
    };
    if (elect()) {
      const uint32_t* gk = g_bqkv + (32 + h) * 256 * 96;
#pragma unroll 1
      for (int i = 0; i < 8; i++) {
        if (i >= AB_LW) mbar_wait(bars + 8 * (i - AB_LW), 0);
        mbar_expect(bars + 8 * i, 24576);
        bulk_load_last(sK + i * 12288, gk + i * 3072, 12288, bars + 8 * i);
        bulk_load_last(sV + i * 12288, gk + 32 * 256 * 96 + i * 3072, 12288, bars + 8 * i);
      }
    }
    __syncwarp();
    if (blockIdx.x < NSLOT) for (int i = lane; i < 512; i += 32) reinterpret_cast<uint4*>(pool_at(blockIdx.x * 8192))[i] = make_uint4(0, 0, 0, 0);
    if (blockIdx.x == 127) for (int i = lane; i < SY_N; i += 32) g_sync[i] = 0;
    if (p.next.w[0] && lane == 0) {
      for (int i = 0; i < AB_PF; i++) { const uint32_t t0 = clk32(); while (clk32() - t0 < (i ? AB_PFD : AB_PF0)) __nanosleep(200); prefetch_weights(p.next, i); }
    }
    __syncwarp();
    mbar_wait(bF, 0);
    const bool redo = unsafe();
    if (!redo && lane == 0) load_w();
    if (lane < 16) asm volatile("cp.async.bulk.prefetch.L2.global [%0], 2560;" :: "l"(g_x + ((blk * 16 + lane) * 40 + cg * 5) * 32) : "memory");
    __syncwarp();
    bar_sync(1, AB_T + 32);
    if (lane == 0) {
      ABT(!!p.out, 1);
      red_release(p.done + quarter * 32, 1);
      ABT(!!p.out, 2);
      if (redo) load_w();
      wait_count(p.done + quarter * 32, 32);
      fence_async_global();
      ABT(!!p.out, 3);
      for (int kb = 0; kb < 10; kb++) {
        const int i = kb < 6 ? kb : kb - 6;
        if (kb >= 6) mbar_wait(bE + 8 * i, 0);
        mbar_expect(bA + 8 * i, 16384);
        bulk_load(ring(i), g_of + (blk * 10 + kb) * 4096, 16384, bA + 8 * i);
      }
    }
    return;
  }
  float qmax = 0.f;
  const uint32_t one = opaque(0x3f803f80u + (threadIdx.x >> 10)), c0 = opaque((AB_DEG == 3 ? 0x3d9f3d9fu : 0x3eac3eacu) + (threadIdx.x >> 10));
#pragma unroll 1
  for (int pass = 0; pass < AB_PASS; pass++) {
    const int row0 = quarter * 512 + ((warp >> 2) * AB_PASS + pass) * 64 + (warp & 3) * 16;
    const uint32_t* gq = g_bqkv + (h * 256 + (row0 >> 3)) * 96 + lane;
    const uint32_t q0 = gq[0], q1 = gq[96], q2 = gq[32], q3 = gq[128];
    uint32_t q4 = gq[64], q5 = gq[160];
    const uint32_t z0 = gq[64 + 3 - (lane & 3)], z1 = gq[160 + 3 - (lane & 3)];
    {
      float n0 = sq2(q0) + sq2(q2) + sq2(q4), n1 = sq2(q1) + sq2(q3) + sq2(q5);
      n0 += __shfl_xor_sync(~0u, n0, 1); n1 += __shfl_xor_sync(~0u, n1, 1);
      n0 += __shfl_xor_sync(~0u, n0, 2); n1 += __shfl_xor_sync(~0u, n1, 2);
      qmax = (n0 > qmax || n0 != n0) ? n0 : qmax;
      qmax = (n1 > qmax || n1 != n1) ? n1 : qmax;
    }
    if (pass == AB_PASS - 1) {
      float kmax = 0.f;
#pragma unroll
      for (int i = 0; i < SEQ / AB_T; i++) {
        const int key = threadIdx.x + AB_T * i;
        const uint32_t a = sK + (key >> 3) * 384 + (key & 7) * 16;
        const uint4 x = lds128(a), y = lds128(a + 128);
        const uint2 z = lds64(a + 256);
        const float n = ((sq2(x.x) + sq2(x.y)) + (sq2(x.z) + sq2(x.w))) + ((sq2(y.x) + sq2(y.y)) + (sq2(y.z) + sq2(y.w))) + (sq2(z.x) + sq2(z.y));
        kmax = (n > kmax || n != n) ? n : kmax;
      }
      const uint32_t kb = __reduce_max_sync(~0u, __float_as_uint(kmax) & 0x7fffffffu), qb = __reduce_max_sync(~0u, __float_as_uint(qmax) & 0x7fffffffu);
      if (lane < 2) asm volatile("red.shared.max.u32 [%0], %1;" :: "r"(smax + 4 * lane), "r"(lane ? kb : qb) : "memory");
      __syncwarp();
    }
    if ((lane & 3) == 2) { q4 = 0xBF8043C0u; q5 = 0xBF8043C0u; }
    float o[12];
    auto desc = [](uint32_t lo, uint32_t hi) { uint64_t d; asm("mov.b64 %0, {%1, %2};" : "=l"(d) : "r"(lo), "r"(hi)); return d; };
    const uint32_t k0 = (uint32_t)mkdesc(sK, 128, 0, 0), k1 = (uint32_t)mkdesc(sK + 256, 0, 0, 0), v0 = (uint32_t)mkdesc(sV, 384, 0, 0);
    float sa[16], sb2[16];
    uint32_t pa[8], pb[8];
    auto qk = [&](float* s, uint32_t t) {
      wg_rs32_00(s, q0, q1, q2, q3, desc(k0 + t, 24), 0);
      wg_rs32_00(s, q4, q5, z0, z1, desc(k1 + t, 24), 1);
      wg_commit();
    };
    auto step = [&](float* s, uint32_t* pp, int g0, uint32_t t, uint32_t nx, int acc) {
      wg_wait<1>();
      reg_fence<16>(s);
#pragma unroll
      for (int i = 0; i < 8; i++) pp[i] = poly_group(g0 + (i >> 1)) ? ex2_pair(s[2 * i], s[2 * i + 1], one, c0) : pack2(ex2(s[2 * i]), ex2(s[2 * i + 1]));
      wg_fence();
      wg_rs24_01(o, pp[0], pp[1], pp[2], pp[3], desc(v0 + t, 8), acc);
      wg_rs24_01(o, pp[4], pp[5], pp[6], pp[7], desc(v0 + t + 48, 8), 1);
      qk(s, nx);
    };
    if (pass == 0) mbar_wait(bars, 0);
    wg_fence();
    qk(sa, 0);
    qk(sb2, 96);
#pragma unroll 1
    for (uint32_t t = 0; t < 64 * 96; t += AB_U * 96) {
      const uint32_t nx = t + AB_U * 96 < 64 * 96 ? t + AB_U * 96 : 0;
      if (pass == AB_PASS - 1 && t == 40 * 96 && lane == 0) mbar_arrive(bF);
#pragma unroll
      for (int u = 0; u < AB_U; u += 2) {
        if (u == AB_U - 2 && pass == 0) mbar_wait(bars + 8 * (nx / 768), 0);
        step(sa, pa, 0, t + u * 96, u + 2 < AB_U ? t + (u + 2) * 96 : nx, u | t);
        step(sb2, pb, 4, t + u * 96 + 96, (u + 2 < AB_U ? t + (u + 2) * 96 : nx) + 96, 1);
      }
    }
    wg_wait<0>();
    reg_fence<12>(o); reg_fence<16>(sa); reg_fence<16>(sb2);
    attn_b_store(o, h, row0, lane);
  }
  mbar_wait(bF, 0);
  if (unsafe())
#pragma unroll 1
  for (int pass = 0; pass < AB_PASS; pass++) {
    const int row0 = quarter * 512 + ((warp >> 2) * AB_PASS + pass) * 64 + (warp & 3) * 16;
    const uint32_t* gq = g_bqkv + (h * 256 + (row0 >> 3)) * 96 + lane;
    const uint32_t q0 = gq[0], q1 = gq[96], q2 = gq[32], q3 = gq[128], q4 = gq[64], q5 = gq[160];
    float o[12];
#pragma unroll
    for (int i = 0; i < 12; i++) o[i] = 0.f;
    float m0 = -INFINITY, m1 = -INFINITY;
#pragma unroll 1
    for (int kt = 0; kt < 32; kt++) {
      float s[32];
      const uint64_t dk = mkdesc(sK + kt * 3072, 128, 384, 0), dk2 = mkdesc(sK + kt * 3072 + 256, 0, 384, 0);
      wg_fence();
      wg_rs64_00(s, q0, q1, q2, q3, dk, 0);
      wg_rs64_00(s, q4, q5, 0, 0, dk2, 1);
      wg_commit();
      wg_wait<0>();
      reg_fence<32>(s); reg_fence<12>(o);
      float n0 = m0, n1 = m1;
#pragma unroll
      for (int jj = 0; jj < 8; jj++) { n0 = fmaxf(n0, fmaxf(s[4 * jj], s[4 * jj + 1])); n1 = fmaxf(n1, fmaxf(s[4 * jj + 2], s[4 * jj + 3])); }
      n0 = fmaxf(n0, __shfl_xor_sync(~0u, n0, 1)); n0 = fmaxf(n0, __shfl_xor_sync(~0u, n0, 2));
      n1 = fmaxf(n1, __shfl_xor_sync(~0u, n1, 1)); n1 = fmaxf(n1, __shfl_xor_sync(~0u, n1, 2));
      const float r0 = ex2(m0 - n0), r1 = ex2(m1 - n1);
      m0 = n0; m1 = n1;
#pragma unroll
      for (int jj = 0; jj < 3; jj++) { o[4 * jj] *= r0; o[4 * jj + 1] *= r0; o[4 * jj + 2] *= r1; o[4 * jj + 3] *= r1; }
      uint32_t pp[16];
#pragma unroll
      for (int jj = 0; jj < 8; jj++) {
        pp[2 * jj] = pack2(ex2(s[4 * jj] - m0), ex2(s[4 * jj + 1] - m0));
        pp[2 * jj + 1] = pack2(ex2(s[4 * jj + 2] - m1), ex2(s[4 * jj + 3] - m1));
      }
      const uint64_t dv = mkdesc(sV + kt * 3072, 384, 128, 0);
      wg_fence();
#pragma unroll
      for (int kk = 0; kk < 4; kk++) wg_rs24_01(o, pp[4 * kk], pp[4 * kk + 1], pp[4 * kk + 2], pp[4 * kk + 3], dv + kk * 48, 1);
      wg_commit();
    }
    wg_wait<0>();
    reg_fence<12>(o);
    attn_b_store(o, h, row0, lane);
  }
  ABT(!!p.out, 0);
  bar_arrive(1, AB_T + 32);
  if (warp >= 12) return;
  const int g = lane >> 2, c = lane & 3;
  const bool live = opaque(threadIdx.x) < 256;
  float d[40] = {};
  float4* x = g_x + ((blk * 16 + warp * 2) * 40 + cg * 5) * 32 + lane;
  if (warp < 8) {
#pragma unroll
  for (int i = 0; i < 10; i++) {
    const int r = i / 5, u = i % 5;
    const float4 t = x[(r * 40 + u) * 32];
    d[8 * u + 2 * r] = t.x; d[8 * u + 2 * r + 1] = t.y; d[8 * u + 4 + 2 * r] = t.z; d[8 * u + 5 + 2 * r] = t.w;
  }
  mbar_wait(bW, 0);
  reg_fence<40>(d);
  ABT(!!p.out, 4);
#pragma unroll 1
  for (int kb = 0; kb < 10; kb++) {
    const int i = kb < 6 ? kb : kb - 6;
    mbar_wait(bA + 8 * i, kb >= 6);
    const uint64_t da = mkdesc(ring(i) + (warp >> 2) * 8192, 128, 1024, 0), db = mkdesc(kb < 5 ? sK + kb * 10240 : sV + (kb - 5) * 10240, 1280, 128, 0);
    wg_fence();
#pragma unroll
    for (int kk = 0; kk < 4; kk++) wg_ss80_01(d, da + kk * 16, db + kk * 160, 1);
    wg_commit();
    if (kb > 0 && kb < 5) { wg_wait<1>(); if (lane == 0) mbar_arrive(bE + 8 * (kb - 1)); }
  }
  wg_wait<0>();
  reg_fence<40>(d);
  }
  ABT(!!p.out, 5);
  if (p.out) {
    if (warp >= 8) return;
    const uint32_t stage = sK + 83968 + warp * 2560 + (warp < 4 ? 0 : 131328 - 10240);
#pragma unroll
    for (int u = 0; u < 5; u++)
      stsm4(stage + (lane & 15) * 160 + u * 32 + (lane >> 4) * 16, pack2(d[8 * u], d[8 * u + 1]), pack2(d[8 * u + 2], d[8 * u + 3]),
            pack2(d[8 * u + 4], d[8 * u + 5]), pack2(d[8 * u + 6], d[8 * u + 7]));
    __syncwarp();
    uint4* out = reinterpret_cast<uint4*>(p.out + (blk * 128 + warp * 16) * (DM / 2) + cg * 40);
#pragma unroll
    for (int i = 0; i < 5; i++) { const int e = i * 32 + lane, r = e / 10; out[r * (DM / 8) + e - r * 10] = lds128(stage + e * 16); }
  } else {
    float2* stat = g_stat + blk * 1024 + (warp & 7) * 16 + g;
    float mean[2], rs[2];
#pragma unroll
    for (int r = 0; r < 2; r++) {
      float t = 0.f, q = 0.f;
#pragma unroll
      for (int i = 0; i < 10; i++) t += d[4 * i + 2 * r] + d[4 * i + 2 * r + 1];
      t += __shfl_xor_sync(~0u, t, 1); t += __shfl_xor_sync(~0u, t, 2);
      t *= 1.f / 80;
#pragma unroll
      for (int i = 0; i < 10; i++) { const float a = d[4 * i + 2 * r] - t, b = d[4 * i + 2 * r + 1] - t; q += a * a + b * b; }
      q += __shfl_xor_sync(~0u, q, 1); q += __shfl_xor_sync(~0u, q, 2);
      if (c == r && live) asm volatile("st.relaxed.gpu.global.v2.b32 [%0], {%1, %2};" :: "l"(stat + cg * 128 + r * 8), "r"(__float_as_uint(t)), "r"(nz(__float_as_uint(q))) : "memory");
    }
#pragma unroll
    for (int i = 0; i < 10; i++) {
      const int r = i / 5, u = i % 5;
      if (live) x[(r * 40 + u) * 32] = make_float4(d[8 * u + 2 * r], d[8 * u + 2 * r + 1], d[8 * u + 4 + 2 * r], d[8 * u + 5 + 2 * r]);
    }
    ABT(0, 6);
    uint2 e[4];
    int n = 0;
    do {
#pragma unroll
      for (int i = 0; i < 4; i++)
        asm volatile("ld.relaxed.gpu.global.v2.b32 {%0, %1}, [%2];" : "=r"(e[i].x), "=r"(e[i].y) : "l"(stat + (2 * c + (i & 1)) * 128 + (i >> 1) * 8) : "memory");
      spin_guard(n);
    } while (__any_sync(~0u, min(min(e[0].y, e[1].y), min(e[2].y, e[3].y)) == 0 && live));
#pragma unroll
    for (int r = 0; r < 2; r++) {
      const float m0 = __uint_as_float(e[2 * r].x), m1 = __uint_as_float(e[2 * r + 1].x);
      float t = m0 + m1;
      t += __shfl_xor_sync(~0u, t, 1); t += __shfl_xor_sync(~0u, t, 2);
      t *= 0.125f;
      float q = __uint_as_float(e[2 * r].y) + __uint_as_float(e[2 * r + 1].y) + 80.f * ((m0 - t) * (m0 - t) + (m1 - t) * (m1 - t));
      q += __shfl_xor_sync(~0u, q, 1); q += __shfl_xor_sync(~0u, q, 2);
      mean[r] = t; rs[r] = rsqrtf(q * (1.f / DM) + 1e-5f);
    }
    ABT(0, 7);
    uint32_t w[2][5][2];
#pragma unroll
    for (int i = 0; i < 20; i++) w[i & 1][i >> 2][i >> 1 & 1] = pack2((d[2 * i] - mean[i & 1]) * rs[i & 1], (d[2 * i + 1] - mean[i & 1]) * rs[i & 1]);
    ln_store(w, blk * 8 + warp, cg * 5, live);
  }
  ABT(!!p.out, 8);
  TRACE(2);
}

typedef CUresult (*EncodeFn)(CUtensorMap*, CUtensorMapDataType, cuuint32_t, void*, const cuuint64_t*, const cuuint64_t*,
                             const cuuint32_t*, const cuuint32_t*, CUtensorMapInterleave, CUtensorMapSwizzle,
                             CUtensorMapL2promotion, CUtensorMapFloatOOBfill);

void make_map(EncodeFn enc, CUtensorMap* m, const void* ptr, int cols, int rows, int nb) {
  const cuuint64_t dims[3] = {(cuuint64_t)(nb ? 64 : cols), (cuuint64_t)rows, (cuuint64_t)cols / 64};
  const cuuint64_t strides[2] = {(cuuint64_t)cols * 2, 128};
  const cuuint32_t box[3] = {64, 32, (cuuint32_t)nb}, es[3] = {1, 1, 1};
  enc(m, CU_TENSOR_MAP_DATA_TYPE_BFLOAT16, nb ? 3 : 2, const_cast<void*>(ptr), dims, strides, box, es, CU_TENSOR_MAP_INTERLEAVE_NONE,
      CU_TENSOR_MAP_SWIZZLE_128B, CU_TENSOR_MAP_L2_PROMOTION_L2_128B, CU_TENSOR_MAP_FLOAT_OOB_FILL_NONE);
}
template <class... KA, class... A>
void launch(void (*kern)(KA...), int grid, int block, int smem, int cluster, bool pdl, A... args) {
  cudaFuncSetAttribute(kern, cudaFuncAttributeMaxDynamicSharedMemorySize, smem);
  cudaLaunchConfig_t cfg = {};
  cfg.gridDim = dim3(grid); cfg.blockDim = dim3(block); cfg.dynamicSmemBytes = smem; cfg.stream = cudaStreamPerThread;
  cudaLaunchAttribute at[2];
  int n = 0;
  if (cluster > 1) { at[n].id = cudaLaunchAttributeClusterDimension; at[n].val.clusterDim.x = cluster; at[n].val.clusterDim.y = 1; at[n].val.clusterDim.z = 1; n++; }
  if (pdl) { at[n].id = cudaLaunchAttributeProgrammaticStreamSerialization; at[n].val.programmaticStreamSerializationAllowed = 1; n++; }
  cfg.attrs = at; cfg.numAttrs = n;
  cudaLaunchKernelEx(&cfg, kern, args...);
}
template <class T> void* sym(T& s) { void* p = nullptr; cudaGetSymbolAddress(&p, s); return p; }

}

#define MODE(b) 0
extern "C" void kernel_launch(void* const* d_in, const int* in_sizes, int n_in, void* d_out, int out_size) {
  const __nv_bfloat16* x = (const __nv_bfloat16*)d_in[0];
  void* fn = nullptr; cudaDriverEntryPointQueryResult qr;
  cudaGetDriverEntryPoint("cuTensorMapEncodeTiled", &fn, cudaEnableDefault, &qr);
  EncodeFn enc = (EncodeFn)fn;

  ChainParams ch = {};
  PostParams op = {};
  for (int i = 0; i < 3; i++) {
    const cuuint64_t dims[3] = {HD, 128, 5}, strides[2] = {HD * 2, HD * 256};
    const cuuint32_t box[3] = {64, 128, 5}, es[3] = {1, 1, 1};
    enc(i == 0 ? &ch.wq : i == 1 ? &ch.wk : &ch.wv, CU_TENSOR_MAP_DATA_TYPE_BFLOAT16, 3, d_in[2 + i], dims, strides, box, es, CU_TENSOR_MAP_INTERLEAVE_NONE,
        CU_TENSOR_MAP_SWIZZLE_128B, W_PROMO, CU_TENSOR_MAP_FLOAT_OOB_FILL_NONE);
  }
  {
    const cuuint64_t dims[3] = {DM, HD, 7}, strides[2] = {DM * 2, 64};
    const cuuint32_t box[3] = {32, 64, 7}, es[3] = {1, 1, 1};
    enc(&ch.wo, CU_TENSOR_MAP_DATA_TYPE_BFLOAT16, 3, d_in[5], dims, strides, box, es, CU_TENSOR_MAP_INTERLEAVE_NONE,
        CU_TENSOR_MAP_SWIZZLE_64B, CU_TENSOR_MAP_L2_PROMOTION_L2_128B, CU_TENSOR_MAP_FLOAT_OOB_FILL_NONE);
  }
  ch.mem0 = (const __nv_bfloat16*)d_in[1];
  ch.pool = (uint8_t*)(((uintptr_t)sym(g_pool) + 8191) & ~(uintptr_t)8191); ch.kv = (uint8_t*)sym(g_kv); ch.xc = (const uint32_t*)sym(g_xc); ch.sync = (uint32_t*)sym(g_sync);
  ch.d1 = 0; ch.d1b = 0; ch.d2 = 0; ch.d2b = 0;
  make_map(enc, &op.wq, d_in[2], HD, DM, 3);
  make_map(enc, &op.wo, d_in[5], DM, HD, 5); make_map(enc, &op.wo2, d_in[5], DM, HD, 0);
  make_map(enc, &op.wb, d_in[8], 1920, DM, 5); make_map(enc, &op.wb2, d_in[8], 1920, DM, 0);
  op.gap = 17; op.share = 20; op.look = 14; op.gap2 = 0; op.pol = 1;

  const Weights wa = {{(const uint8_t*)d_in[3], (const uint8_t*)d_in[4], (const uint8_t*)d_in[2], (const uint8_t*)d_in[5]}}, none = {};
  launch(first_kernel, 132, 256, 128 * 1024, 1, false, x, (const uint4*)d_in[9], wa);
  for (int layer = 0; layer < 2; layer++) {
    ch.layer = ch.d2b = op.layer = layer;
    launch(chain_kernel, 96, 256, CH_SMEM, 3, true, ch);
    launch(post_kernel, MODE(3) ? 36 : 132, 384, OP_SMEM, 1, !MODE(1), op);
    const AbParams ab = {layer == 0 ? wa : none, (uint32_t*)sym(g_bo) + layer * 128, layer == 0 ? nullptr : (uint32_t*)d_out};
    launch(attn_b_kernel, 128, AB_T + 32, AB_SMEM, 1, true, ab);
  }
}
```

```cpp
#include <cuda_runtime.h>
#include <cuda_bf16.h>
#include <cuda.h>
#include <stdint.h>

namespace {

constexpr int SEQ = 2048, DM = 640, HD = 6144, NSEG = 64;
constexpr int SPIN_LIMIT = 1 << 20;

__device__ __align__(128) float4 g_x[SEQ * DM / 4];
__device__ __align__(128) uint32_t g_of[SEQ * DM / 2];
__device__ __align__(128) uint4 g_wb[DM * DM / 8];
__device__ __align__(16) float2 g_stat[16 * 8 * 128];
__device__ uint32_t g_bo[8 * 32];
__device__ __align__(128) uint4 g_q[SEQ * HD / 8];
__device__ __align__(128) uint32_t g_o[SEQ * HD / 2];
constexpr int KV_BYTES = 5120, KV_M = 4096, KV_V = NSEG * KV_BYTES;
__device__ __align__(128) uint8_t g_kv[96 * 2 * NSEG * KV_BYTES];
__device__ __align__(128) uint32_t g_xc[SEQ * DM / 2];
#define OP_B4 5
#define OP_B8 9
#define OP_B16 13
#define QA_END 12
__host__ __device__ constexpr int op_split(int b) { return b < OP_B4 ? 2 : b < OP_B8 ? 4 : b < OP_B16 ? 8 : 16; }
#define AB_PF 2
#define AB_PF0 0
#define AB_PFD 6000
#define W_PROMO CU_TENSOR_MAP_L2_PROMOTION_L2_128B
#define OP_EARLY 1
#define FIN_8 0
#define FIN_16 0
#define ATT_LOOK 1
#define PR_FIN 1
#define PR_ATT 0
#define PR_OP 2
#define PRE_MAX PS
#define PRE_GAP 0u
#define Q_PF 0
#define OEF 0
#define BQ_HOLD 6
#define WEF 1
#define FK_REP 4
#define FK_PF 1
#define BQ_160 10
#define BQ_80 16
#define OP_160 16
__host__ __device__ constexpr int fin_items(int b) { return b < FIN_8 ? 4 : b < FIN_16 ? 8 : 16; }
__host__ __device__ constexpr int op_width(int b) { return b < OP_160 ? 320 : 160; }
__host__ __device__ constexpr int bq_width(int b) { return b < BQ_160 ? 320 : b < BQ_80 ? 160 : 80; }
__device__ __align__(128) uint2 g_part[16 * 16 * 16 * 40 * 32];
__device__ __align__(128) uint32_t g_xn[SEQ * DM / 2];
constexpr int SY_Q = 128, SY_T = 160, SY_QC = 192, SY_N = 193;
__device__ __align__(16) uint32_t g_sync[SY_N];
constexpr int NSLOT = 92;
__device__ uint32_t g_pool[(NSLOT + 2) * 2048];
__device__ int g_smpart[256], g_orient[NSLOT];
__device__ uint32_t g_smclk[256], g_smuse[256];
__device__ uint32_t g_bqkv[3 * 32 * 256 * 96];

#define ABT(L, i)
#define MODE_D(b) 0
#define DELAY(d)
#define XT(i)
#define MISS(k, n)
#define PRO(i)
#define TRACE(w)
#define ITEM(code, w)
#define TR(i, v)
#define TM(i)
#define TM1(i)
#define TMD(i, dep)
#define TMV(i, at, v)

__device__ __forceinline__ uint32_t gtime() { uint32_t c; asm volatile("mov.u32 %0, %%globaltimer_lo;" : "=r"(c) :: "memory"); return c; }
__device__ __forceinline__ uint32_t clk32() { uint32_t c; asm volatile("mov.u32 %0, %%clock;" : "=r"(c) :: "memory"); return c; }
__device__ __forceinline__ uint32_t s2u(const void* p) { return (uint32_t)__cvta_generic_to_shared(p); }
__device__ __forceinline__ uint32_t pack2(float a, float b) {
  uint32_t r; asm("cvt.rn.bf16x2.f32 %0, %1, %2;" : "=r"(r) : "f"(b), "f"(a)); return r; }
__device__ __forceinline__ float bf_lo(uint32_t w) { return __uint_as_float(w << 16); }
__device__ __forceinline__ float bf_hi(uint32_t w) { return __uint_as_float(w & 0xffff0000u); }
__device__ __forceinline__ float ex2(float x) { float y; asm("ex2.approx.ftz.f32 %0, %1;" : "=f"(y) : "f"(x)); return y; }

__device__ __forceinline__ void mbar_init(uint32_t bar, uint32_t n) {
  asm volatile("mbarrier.init.shared::cta.b64 [%0], %1;" :: "r"(bar), "r"(n) : "memory"); }
__device__ __forceinline__ void mbar_expect(uint32_t bar, uint32_t bytes) {
  asm volatile("mbarrier.arrive.expect_tx.shared::cta.b64 _, [%0], %1;" :: "r"(bar), "r"(bytes) : "memory"); }
__device__ __forceinline__ void mbar_arrive(uint32_t bar) {
  asm volatile("mbarrier.arrive.shared::cta.b64 _, [%0];" :: "r"(bar) : "memory"); }
__device__ __forceinline__ void mbar_wait(uint32_t bar, uint32_t ph) {
  asm volatile("{.reg .pred p; .reg .u32 n; mov.u32 n, 0;\n"
               "W: mbarrier.try_wait.parity.shared::cta.b64 p, [%0], %1; @p bra D;\n"
               "add.u32 n, n, 1; setp.gt.u32 p, n, %2; @p trap; bra W;\n"
               "D: }" :: "r"(bar), "r"(ph), "n"(SPIN_LIMIT) : "memory");
}
__device__ __forceinline__ void mbar_wait_cluster(uint32_t bar, uint32_t ph) {
  asm volatile("{.reg .pred p; .reg .u32 n; mov.u32 n, 0;\n"
               "W: mbarrier.try_wait.parity.acquire.cluster.shared::cta.b64 p, [%0], %1; @p bra D;\n"
               "add.u32 n, n, 1; setp.gt.u32 p, n, %2; @p trap; bra W;\n"
               "D: }" :: "r"(bar), "r"(ph), "n"(SPIN_LIMIT) : "memory");
}
__device__ __forceinline__ void spin_guard(int& n) {
  asm volatile("{.reg .pred p; add.s32 %0, %0, 1; setp.gt.s32 p, %0, %1; @p trap;}" : "+r"(n) : "n"(SPIN_LIMIT));
}
__device__ __forceinline__ void pdl_wait() { asm volatile("griddepcontrol.wait;" ::: "memory"); TRACE(1); }
__device__ __forceinline__ void pdl_launch() { asm volatile("griddepcontrol.launch_dependents;" ::: "memory"); }
__device__ __forceinline__ uint32_t ld_acquire(const uint32_t* p) { uint32_t v; asm volatile("ld.acquire.gpu.global.u32 %0, [%1];" : "=r"(v) : "l"(p) : "memory"); return v; }
__device__ __forceinline__ void red_release(uint32_t* p, uint32_t v) { asm volatile("red.release.gpu.global.add.u32 [%0], %1;" :: "l"(p), "r"(v) : "memory"); }
__device__ __forceinline__ void red_relaxed(uint32_t* p, uint32_t v) { asm volatile("red.relaxed.gpu.global.add.u32 [%0], %1;" :: "l"(p), "r"(v) : "memory"); }
__device__ __forceinline__ void fence_async_global() { asm volatile("fence.proxy.async.global;" ::: "memory"); }
__device__ __forceinline__ void fence_async() { asm volatile("fence.proxy.async.shared::cta;" ::: "memory"); }
__device__ __forceinline__ void bar_sync(int id, int n) { asm volatile("bar.sync %0, %1;" :: "r"(id), "r"(n) : "memory"); }
__device__ __forceinline__ void bar_arrive(int id, int n) { asm volatile("bar.arrive %0, %1;" :: "r"(id), "r"(n) : "memory"); }
__device__ __forceinline__ void tma_load(uint32_t dst, const CUtensorMap* m, int c0, int c1, uint32_t bar) {
  asm volatile("cp.async.bulk.tensor.2d.shared::cluster.global.mbarrier::complete_tx::bytes [%0], [%1, {%3, %4}], [%2];"
               :: "r"(dst), "l"(m), "r"(bar), "r"(c0), "r"(c1) : "memory"); }
template <bool STREAM = false>
__device__ __forceinline__ void tma_load3(uint32_t dst, const CUtensorMap* m, int c0, int c1, uint32_t bar) {
  if (STREAM)
    asm volatile("{.reg .b64 pol; createpolicy.fractional.L2::evict_first.b64 pol, 1.0;\n"
                 "cp.async.bulk.tensor.3d.shared::cluster.global.mbarrier::complete_tx::bytes.L2::cache_hint [%0], [%1, {%3, %4, 0}], [%2], pol;}"
                 :: "r"(dst), "l"(m), "r"(bar), "r"(c0), "r"(c1) : "memory");
  else
  asm volatile("cp.async.bulk.tensor.3d.shared::cluster.global.mbarrier::complete_tx::bytes [%0], [%1, {%3, %4, 0}], [%2];"
               :: "r"(dst), "l"(m), "r"(bar), "r"(c0), "r"(c1) : "memory"); }
__device__ __forceinline__ void tma_load3z(uint32_t dst, const CUtensorMap* m, int c1, int c2, uint32_t bar) {
  asm volatile("cp.async.bulk.tensor.3d.shared::cluster.global.mbarrier::complete_tx::bytes [%0], [%1, {0, %3, %4}], [%2];"
               :: "r"(dst), "l"(m), "r"(bar), "r"(c1), "r"(c2) : "memory"); }
__device__ __forceinline__ void tma_store(const CUtensorMap* m, uint32_t src, int c0, int c1) {
  asm volatile("cp.async.bulk.tensor.2d.global.shared::cta.bulk_group [%0, {%2, %3}], [%1];"
               :: "l"(m), "r"(src), "r"(c0), "r"(c1) : "memory"); }
__device__ __forceinline__ void tma_store_stream(const CUtensorMap* m, uint32_t src, int c0, int c1) {
  asm volatile("{.reg .b64 pol; createpolicy.fractional.L2::evict_first.b64 pol, 1.0;\n"
               "cp.async.bulk.tensor.2d.global.shared::cta.bulk_group.L2::cache_hint [%0, {%2, %3}], [%1], pol;}"
               :: "l"(m), "r"(src), "r"(c0), "r"(c1) : "memory"); }
__device__ __forceinline__ void bulk_load(uint32_t dst, const void* src, uint32_t bytes, uint32_t bar) {
  asm volatile("cp.async.bulk.shared::cluster.global.mbarrier::complete_tx::bytes [%0], [%1], %2, [%3];"
               :: "r"(dst), "l"(src), "r"(bytes), "r"(bar) : "memory"); }
__device__ __forceinline__ void bulk_load_last(uint32_t dst, const void* src, uint32_t bytes, uint32_t bar) {
  asm volatile("{.reg .b64 pol; createpolicy.fractional.L2::evict_first.b64 pol, 1.0;\n"
               "cp.async.bulk.shared::cluster.global.mbarrier::complete_tx::bytes.L2::cache_hint [%0], [%1], %2, [%3], pol;}"
               :: "r"(dst), "l"(src), "r"(bytes), "r"(bar) : "memory"); }
__device__ __forceinline__ void tma_load_last(uint32_t dst, const CUtensorMap* m, int c0, int c1, uint32_t bar) {
  asm volatile("{.reg .b64 pol; createpolicy.fractional.L2::evict_first.b64 pol, 1.0;\n"
               "cp.async.bulk.tensor.2d.shared::cluster.global.mbarrier::complete_tx::bytes.L2::cache_hint [%0], [%1, {%3, %4}], [%2], pol;}"
               :: "r"(dst), "l"(m), "r"(bar), "r"(c0), "r"(c1) : "memory"); }
__device__ __forceinline__ void bulk_send(uint32_t dst, uint32_t src, uint32_t bytes, uint32_t bar) {
  asm volatile("cp.async.bulk.shared::cluster.shared::cta.mbarrier::complete_tx::bytes [%0], [%1], %2, [%3];"
               :: "r"(dst), "r"(src), "r"(bytes), "r"(bar) : "memory"); }
__device__ __forceinline__ void bulk_store(void* dst, uint32_t src, uint32_t bytes) {
  asm volatile("cp.async.bulk.global.shared::cta.bulk_group [%0], [%1], %2;" :: "l"(dst), "r"(src), "r"(bytes) : "memory"); }
__device__ __forceinline__ void bulk_commit() { asm volatile("cp.async.bulk.commit_group;" ::: "memory"); }
template <int N> __device__ __forceinline__ void bulk_wait_read() { asm volatile("cp.async.bulk.wait_group.read %0;" :: "n"(N) : "memory"); }
template <int N> __device__ __forceinline__ void bulk_wait() { asm volatile("cp.async.bulk.wait_group %0;" :: "n"(N) : "memory"); }

__device__ __forceinline__ uint64_t mkdesc(uint32_t addr, uint32_t lbo, uint32_t sbo, uint32_t sw) {
  return (uint64_t)((addr & 0x3FFFF) >> 4) | ((uint64_t)(lbo >> 4) << 16) | ((uint64_t)(sbo >> 4) << 32) | ((uint64_t)sw << 62); }
__device__ __forceinline__ void wg_fence() { asm volatile("wgmma.fence.sync.aligned;" ::: "memory"); }
__device__ __forceinline__ void wg_commit() { asm volatile("wgmma.commit_group.sync.aligned;" ::: "memory"); }
template <int N> __device__ __forceinline__ void wg_wait() { asm volatile("wgmma.wait_group.sync.aligned %0;" :: "n"(N) : "memory"); }
template <int N> __device__ __forceinline__ void reg_fence(float* d) {
#pragma unroll
  for (int i = 0; i < N; i++) asm volatile("" : "+f"(d[i]) :: "memory");
}

__device__ __forceinline__ void mma16(float* d, uint32_t a0, uint32_t a1, uint32_t a2, uint32_t a3, uint32_t b0, uint32_t b1) {
  asm volatile("mma.sync.aligned.m16n8k16.row.col.f32.bf16.bf16.f32 {%0,%1,%2,%3},{%4,%5,%6,%7},{%8,%9},{%0,%1,%2,%3};"
               : "+f"(d[0]), "+f"(d[1]), "+f"(d[2]), "+f"(d[3]) : "r"(a0), "r"(a1), "r"(a2), "r"(a3), "r"(b0), "r"(b1)); }
__device__ __forceinline__ void mma8(float* d, uint32_t a0, uint32_t a1, uint32_t b0) {
  asm volatile("mma.sync.aligned.m16n8k8.row.col.f32.bf16.bf16.f32 {%0,%1,%2,%3},{%4,%5},{%6},{%0,%1,%2,%3};"
               : "+f"(d[0]), "+f"(d[1]), "+f"(d[2]), "+f"(d[3]) : "r"(a0), "r"(a1), "r"(b0)); }
__device__ __forceinline__ void ldsm4(uint32_t* r, uint32_t a) {
  asm volatile("ldmatrix.sync.aligned.m8n8.x4.shared.b16 {%0,%1,%2,%3},[%4];" : "=r"(r[0]), "=r"(r[1]), "=r"(r[2]), "=r"(r[3]) : "r"(a) : "memory"); }
__device__ __forceinline__ void ldsm4t(uint32_t* r, uint32_t a) {
  asm volatile("ldmatrix.sync.aligned.m8n8.x4.trans.shared.b16 {%0,%1,%2,%3},[%4];" : "=r"(r[0]), "=r"(r[1]), "=r"(r[2]), "=r"(r[3]) : "r"(a) : "memory"); }
__device__ __forceinline__ void ldsm2(uint32_t* r, uint32_t a) {
  asm volatile("ldmatrix.sync.aligned.m8n8.x2.shared.b16 {%0,%1},[%2];" : "=r"(r[0]), "=r"(r[1]) : "r"(a) : "memory"); }
__device__ __forceinline__ void stsm4(uint32_t a, uint32_t r0, uint32_t r1, uint32_t r2, uint32_t r3) {
  asm volatile("stmatrix.sync.aligned.m8n8.x4.shared.b16 [%0], {%1,%2,%3,%4};" :: "r"(a), "r"(r0), "r"(r1), "r"(r2), "r"(r3) : "memory"); }
__device__ __forceinline__ void stsm2t(uint32_t a, uint32_t r0, uint32_t r1) {
  asm volatile("stmatrix.sync.aligned.m8n8.x2.trans.shared.b16 [%0], {%1,%2};" :: "r"(a), "r"(r0), "r"(r1) : "memory"); }
__device__ __forceinline__ void stsm4t(uint32_t a, uint32_t r0, uint32_t r1, uint32_t r2, uint32_t r3) {
  asm volatile("stmatrix.sync.aligned.m8n8.x4.trans.shared.b16 [%0], {%1,%2,%3,%4};" :: "r"(a), "r"(r0), "r"(r1), "r"(r2), "r"(r3) : "memory"); }
__device__ __forceinline__ void st_async128(uint32_t a, uint4 v, uint32_t bar) {
  asm volatile("st.async.shared::cluster.mbarrier::complete_tx::bytes.v4.b32 [%0], {%1,%2,%3,%4}, [%5];" :: "r"(a), "r"(v.x), "r"(v.y), "r"(v.z), "r"(v.w), "r"(bar) : "memory"); }
__device__ __forceinline__ void sts32(uint32_t a, uint32_t v) { asm volatile("st.shared.b32 [%0], %1;" :: "r"(a), "r"(v) : "memory"); }
__device__ __forceinline__ void sts64f(uint32_t a, float x, float y) { asm volatile("st.shared.v2.f32 [%0], {%1,%2};" :: "r"(a), "f"(x), "f"(y) : "memory"); }
__device__ __forceinline__ void sts128(uint32_t a, uint4 v) {
  asm volatile("st.shared.v4.b32 [%0], {%1,%2,%3,%4};" :: "r"(a), "r"(v.x), "r"(v.y), "r"(v.z), "r"(v.w) : "memory"); }
__device__ __forceinline__ void sts128f(uint32_t a, float x, float y, float z, float w) {
  asm volatile("st.shared.v4.f32 [%0], {%1,%2,%3,%4};" :: "r"(a), "f"(x), "f"(y), "f"(z), "f"(w) : "memory"); }
__device__ __forceinline__ float lds32f(uint32_t a) { float v; asm volatile("ld.shared.f32 %0, [%1];" : "=f"(v) : "r"(a) : "memory"); return v; }
__device__ __forceinline__ float2 lds64f(uint32_t a) { float2 v; asm volatile("ld.shared.v2.f32 {%0,%1}, [%2];" : "=f"(v.x), "=f"(v.y) : "r"(a) : "memory"); return v; }
__device__ __forceinline__ float4 lds128f(uint32_t a) {
  float4 v; asm volatile("ld.shared.v4.f32 {%0,%1,%2,%3}, [%4];" : "=f"(v.x), "=f"(v.y), "=f"(v.z), "=f"(v.w) : "r"(a) : "memory"); return v; }
__device__ __forceinline__ uint4 lds128(uint32_t a) {
  uint4 v; asm volatile("ld.shared.v4.b32 {%0,%1,%2,%3}, [%4];" : "=r"(v.x), "=r"(v.y), "=r"(v.z), "=r"(v.w) : "r"(a) : "memory"); return v; }
__device__ __forceinline__ uint4 ldg_strong128(const void* p) {
  uint4 v; asm volatile("ld.relaxed.gpu.global.v4.u32 {%0,%1,%2,%3}, [%4];" : "=r"(v.x), "=r"(v.y), "=r"(v.z), "=r"(v.w) : "l"(p) : "memory"); return v; }
__device__ __forceinline__ void stg_strong32(void* p, uint32_t v) { asm volatile("st.relaxed.gpu.global.u32 [%0], %1;" :: "l"(p), "r"(v) : "memory"); }
__device__ __forceinline__ void stg_strong16(void* p, uint32_t v) { asm volatile("st.relaxed.gpu.global.u16 [%0], %1;" :: "l"(p), "h"((uint16_t)v) : "memory"); }
__device__ __forceinline__ void stg_strong128(void* p, uint4 v) {
  asm volatile("st.relaxed.gpu.global.v4.u32 [%0], {%1,%2,%3,%4};" :: "l"(p), "r"(v.x), "r"(v.y), "r"(v.z), "r"(v.w) : "memory"); }
__device__ __forceinline__ uint32_t mapa(uint32_t a, uint32_t r) {
  uint32_t o; asm("mapa.shared::cluster.u32 %0, %1, %2;" : "=r"(o) : "r"(a), "r"(r)); return o; }
__device__ __forceinline__ void st_async2f(uint32_t a, float x, float y, uint32_t bar) {
  asm volatile("st.async.shared::cluster.mbarrier::complete_tx::bytes.v2.f32 [%0], {%1,%2}, [%3];" :: "r"(a), "f"(x), "f"(y), "r"(bar) : "memory"); }
__device__ __forceinline__ void st_async32(uint32_t a, uint32_t x, uint32_t bar) {
  asm volatile("st.async.shared::cluster.mbarrier::complete_tx::bytes.b32 [%0], %1, [%2];" :: "r"(a), "r"(x), "r"(bar) : "memory"); }
__device__ __forceinline__ uint32_t lds32(uint32_t a) { uint32_t v; asm volatile("ld.shared.b32 %0, [%1];" : "=r"(v) : "r"(a) : "memory"); return v; }
__device__ __forceinline__ void st_async64(uint32_t a, uint32_t x, uint32_t y, uint32_t bar) {
  asm volatile("st.async.shared::cluster.mbarrier::complete_tx::bytes.v2.b32 [%0], {%1,%2}, [%3];" :: "r"(a), "r"(x), "r"(y), "r"(bar) : "memory"); }
__device__ __forceinline__ uint2 lds64(uint32_t a) { uint2 v; asm volatile("ld.shared.v2.b32 {%0,%1}, [%2];" : "=r"(v.x), "=r"(v.y) : "r"(a) : "memory"); return v; }
__device__ __forceinline__ void sts64(uint32_t a, uint32_t x, uint32_t y) { asm volatile("st.shared.v2.b32 [%0], {%1,%2};" :: "r"(a), "r"(x), "r"(y) : "memory"); }
__device__ __forceinline__ uint32_t ldg_strong32(const void* p) { uint32_t v; asm volatile("ld.relaxed.gpu.global.u32 %0, [%1];" : "=r"(v) : "l"(p) : "memory"); return v; }
__device__ __forceinline__ uint32_t transpose8(uint32_t x) { uint32_t r; asm volatile("movmatrix.sync.aligned.m8n8.trans.b16 %0, %1;" : "=r"(r) : "r"(x)); return r; }
__device__ __forceinline__ uint32_t hadd2(uint32_t a, uint32_t b) { uint32_t r; asm("add.rn.bf16x2 %0, %1, %2;" : "=r"(r) : "r"(a), "r"(b)); return r; }
__device__ __forceinline__ uint32_t min4(uint4 v) { return min(__vimin3_u32(v.x, v.y, v.z), v.w); }

__device__ __forceinline__ void wg_ss192_01(float* d, uint64_t da, uint64_t db, int sd) {
  asm volatile("{.reg .pred p; setp.ne.b32 p, %98, 0;\n"
    "wgmma.mma_async.sync.aligned.m64n192k16.f32.bf16.bf16 {%0,%1,%2,%3,%4,%5,%6,%7,%8,%9,%10,%11,%12,%13,%14,%15,%16,%17,%18,%19,%20,%21,%22,%23,%24,%25,%26,%27,%28,%29,%30,%31,%32,%33,%34,%35,%36,%37,%38,%39,%40,%41,%42,%43,%44,%45,%46,%47,%48,%49,%50,%51,%52,%53,%54,%55,%56,%57,%58,%59,%60,%61,%62,%63,%64,%65,%66,%67,%68,%69,%70,%71,%72,%73,%74,%75,%76,%77,%78,%79,%80,%81,%82,%83,%84,%85,%86,%87,%88,%89,%90,%91,%92,%93,%94,%95}, %96, %97, p, 1, 1, 0, 1;}"
    : "+f"(d[0]),"+f"(d[1]),"+f"(d[2]),"+f"(d[3]),"+f"(d[4]),"+f"(d[5]),"+f"(d[6]),"+f"(d[7]),"+f"(d[8]),"+f"(d[9]),"+f"(d[10]),"+f"(d[11]),"+f"(d[12]),"+f"(d[13]),"+f"(d[14]),"+f"(d[15]),"+f"(d[16]),"+f"(d[17]),"+f"(d[18]),"+f"(d[19]),"+f"(d[20]),"+f"(d[21]),"+f"(d[22]),"+f"(d[23]),"+f"(d[24]),"+f"(d[25]),"+f"(d[26]),"+f"(d[27]),"+f"(d[28]),"+f"(d[29]),"+f"(d[30]),"+f"(d[31]),"+f"(d[32]),"+f"(d[33]),"+f"(d[34]),"+f"(d[35]),"+f"(d[36]),"+f"(d[37]),"+f"(d[38]),"+f"(d[39]),"+f"(d[40]),"+f"(d[41]),"+f"(d[42]),"+f"(d[43]),"+f"(d[44]),"+f"(d[45]),"+f"(d[46]),"+f"(d[47]),"+f"(d[48]),"+f"(d[49]),"+f"(d[50]),"+f"(d[51]),"+f"(d[52]),"+f"(d[53]),"+f"(d[54]),"+f"(d[55]),"+f"(d[56]),"+f"(d[57]),"+f"(d[58]),"+f"(d[59]),"+f"(d[60]),"+f"(d[61]),"+f"(d[62]),"+f"(d[63]),"+f"(d[64]),"+f"(d[65]),"+f"(d[66]),"+f"(d[67]),"+f"(d[68]),"+f"(d[69]),"+f"(d[70]),"+f"(d[71]),"+f"(d[72]),"+f"(d[73]),"+f"(d[74]),"+f"(d[75]),"+f"(d[76]),"+f"(d[77]),"+f"(d[78]),"+f"(d[79]),"+f"(d[80]),"+f"(d[81]),"+f"(d[82]),"+f"(d[83]),"+f"(d[84]),"+f"(d[85]),"+f"(d[86]),"+f"(d[87]),"+f"(d[88]),"+f"(d[89]),"+f"(d[90]),"+f"(d[91]),"+f"(d[92]),"+f"(d[93]),"+f"(d[94]),"+f"(d[95])
    : "l"(da), "l"(db), "r"(sd));
}
__device__ __forceinline__ void wg_ss128_01(float* d, uint64_t da, uint64_t db, int sd) {
  asm volatile("{.reg .pred p; setp.ne.b32 p, %66, 0;\n"
    "wgmma.mma_async.sync.aligned.m64n128k16.f32.bf16.bf16 {%0,%1,%2,%3,%4,%5,%6,%7,%8,%9,%10,%11,%12,%13,%14,%15,%16,%17,%18,%19,%20,%21,%22,%23,%24,%25,%26,%27,%28,%29,%30,%31,%32,%33,%34,%35,%36,%37,%38,%39,%40,%41,%42,%43,%44,%45,%46,%47,%48,%49,%50,%51,%52,%53,%54,%55,%56,%57,%58,%59,%60,%61,%62,%63}, %64, %65, p, 1, 1, 0, 1;}"
    : "+f"(d[0]),"+f"(d[1]),"+f"(d[2]),"+f"(d[3]),"+f"(d[4]),"+f"(d[5]),"+f"(d[6]),"+f"(d[7]),"+f"(d[8]),"+f"(d[9]),"+f"(d[10]),"+f"(d[11]),"+f"(d[12]),"+f"(d[13]),"+f"(d[14]),"+f"(d[15]),"+f"(d[16]),"+f"(d[17]),"+f"(d[18]),"+f"(d[19]),"+f"(d[20]),"+f"(d[21]),"+f"(d[22]),"+f"(d[23]),"+f"(d[24]),"+f"(d[25]),"+f"(d[26]),"+f"(d[27]),"+f"(d[28]),"+f"(d[29]),"+f"(d[30]),"+f"(d[31]),"+f"(d[32]),"+f"(d[33]),"+f"(d[34]),"+f"(d[35]),"+f"(d[36]),"+f"(d[37]),"+f"(d[38]),"+f"(d[39]),"+f"(d[40]),"+f"(d[41]),"+f"(d[42]),"+f"(d[43]),"+f"(d[44]),"+f"(d[45]),"+f"(d[46]),"+f"(d[47]),"+f"(d[48]),"+f"(d[49]),"+f"(d[50]),"+f"(d[51]),"+f"(d[52]),"+f"(d[53]),"+f"(d[54]),"+f"(d[55]),"+f"(d[56]),"+f"(d[57]),"+f"(d[58]),"+f"(d[59]),"+f"(d[60]),"+f"(d[61]),"+f"(d[62]),"+f"(d[63])
    : "l"(da), "l"(db), "r"(sd));
}
__device__ __forceinline__ void wg_ss160_01(float* d, uint64_t da, uint64_t db, int sd) {
  asm volatile("{.reg .pred p; setp.ne.b32 p, %82, 0;\n"
    "wgmma.mma_async.sync.aligned.m64n160k16.f32.bf16.bf16 {%0,%1,%2,%3,%4,%5,%6,%7,%8,%9,%10,%11,%12,%13,%14,%15,%16,%17,%18,%19,%20,%21,%22,%23,%24,%25,%26,%27,%28,%29,%30,%31,%32,%33,%34,%35,%36,%37,%38,%39,%40,%41,%42,%43,%44,%45,%46,%47,%48,%49,%50,%51,%52,%53,%54,%55,%56,%57,%58,%59,%60,%61,%62,%63,%64,%65,%66,%67,%68,%69,%70,%71,%72,%73,%74,%75,%76,%77,%78,%79}, %80, %81, p, 1, 1, 0, 1;}"
    : "+f"(d[0]),"+f"(d[1]),"+f"(d[2]),"+f"(d[3]),"+f"(d[4]),"+f"(d[5]),"+f"(d[6]),"+f"(d[7]),"+f"(d[8]),"+f"(d[9]),"+f"(d[10]),"+f"(d[11]),"+f"(d[12]),"+f"(d[13]),"+f"(d[14]),"+f"(d[15]),"+f"(d[16]),"+f"(d[17]),"+f"(d[18]),"+f"(d[19]),"+f"(d[20]),"+f"(d[21]),"+f"(d[22]),"+f"(d[23]),"+f"(d[24]),"+f"(d[25]),"+f"(d[26]),"+f"(d[27]),"+f"(d[28]),"+f"(d[29]),"+f"(d[30]),"+f"(d[31]),"+f"(d[32]),"+f"(d[33]),"+f"(d[34]),"+f"(d[35]),"+f"(d[36]),"+f"(d[37]),"+f"(d[38]),"+f"(d[39]),"+f"(d[40]),"+f"(d[41]),"+f"(d[42]),"+f"(d[43]),"+f"(d[44]),"+f"(d[45]),"+f"(d[46]),"+f"(d[47]),"+f"(d[48]),"+f"(d[49]),"+f"(d[50]),"+f"(d[51]),"+f"(d[52]),"+f"(d[53]),"+f"(d[54]),"+f"(d[55]),"+f"(d[56]),"+f"(d[57]),"+f"(d[58]),"+f"(d[59]),"+f"(d[60]),"+f"(d[61]),"+f"(d[62]),"+f"(d[63]),"+f"(d[64]),"+f"(d[65]),"+f"(d[66]),"+f"(d[67]),"+f"(d[68]),"+f"(d[69]),"+f"(d[70]),"+f"(d[71]),"+f"(d[72]),"+f"(d[73]),"+f"(d[74]),"+f"(d[75]),"+f"(d[76]),"+f"(d[77]),"+f"(d[78]),"+f"(d[79])
    : "l"(da), "l"(db), "r"(sd));
}
__device__ __forceinline__ void wg_ss80_01(float* d, uint64_t da, uint64_t db, int sd) {
  asm volatile("{.reg .pred p; setp.ne.b32 p, %42, 0;\n"
    "wgmma.mma_async.sync.aligned.m64n80k16.f32.bf16.bf16 {%0,%1,%2,%3,%4,%5,%6,%7,%8,%9,%10,%11,%12,%13,%14,%15,%16,%17,%18,%19,%20,%21,%22,%23,%24,%25,%26,%27,%28,%29,%30,%31,%32,%33,%34,%35,%36,%37,%38,%39}, %40, %41, p, 1, 1, 0, 1;}"
    : "+f"(d[0]),"+f"(d[1]),"+f"(d[2]),"+f"(d[3]),"+f"(d[4]),"+f"(d[5]),"+f"(d[6]),"+f"(d[7]),"+f"(d[8]),"+f"(d[9]),"+f"(d[10]),"+f"(d[11]),"+f"(d[12]),"+f"(d[13]),"+f"(d[14]),"+f"(d[15]),"+f"(d[16]),"+f"(d[17]),"+f"(d[18]),"+f"(d[19]),"+f"(d[20]),"+f"(d[21]),"+f"(d[22]),"+f"(d[23]),"+f"(d[24]),"+f"(d[25]),"+f"(d[26]),"+f"(d[27]),"+f"(d[28]),"+f"(d[29]),"+f"(d[30]),"+f"(d[31]),"+f"(d[32]),"+f"(d[33]),"+f"(d[34]),"+f"(d[35]),"+f"(d[36]),"+f"(d[37]),"+f"(d[38]),"+f"(d[39])
    : "l"(da), "l"(db), "r"(sd));
}
__device__ __forceinline__ void wg_rs32_00(float* d, uint32_t a0, uint32_t a1, uint32_t a2, uint32_t a3, uint64_t db, int sd) {
  asm volatile("{.reg .pred p; setp.ne.b32 p, %21, 0;\n"
    "wgmma.mma_async.sync.aligned.m64n32k16.f32.bf16.bf16 {%0,%1,%2,%3,%4,%5,%6,%7,%8,%9,%10,%11,%12,%13,%14,%15}, {%16,%17,%18,%19}, %20, p, 1, 1, 0;}"
    : "+f"(d[0]),"+f"(d[1]),"+f"(d[2]),"+f"(d[3]),"+f"(d[4]),"+f"(d[5]),"+f"(d[6]),"+f"(d[7]),"+f"(d[8]),"+f"(d[9]),"+f"(d[10]),"+f"(d[11]),"+f"(d[12]),"+f"(d[13]),"+f"(d[14]),"+f"(d[15])
    : "r"(a0), "r"(a1), "r"(a2), "r"(a3), "l"(db), "r"(sd));
}
__device__ __forceinline__ void wg_rs64_00(float* d, uint32_t a0, uint32_t a1, uint32_t a2, uint32_t a3, uint64_t db, int sd) {
  asm volatile("{.reg .pred p; setp.ne.b32 p, %37, 0;\n"
    "wgmma.mma_async.sync.aligned.m64n64k16.f32.bf16.bf16 {%0,%1,%2,%3,%4,%5,%6,%7,%8,%9,%10,%11,%12,%13,%14,%15,%16,%17,%18,%19,%20,%21,%22,%23,%24,%25,%26,%27,%28,%29,%30,%31}, {%32,%33,%34,%35}, %36, p, 1, 1, 0;}"
    : "+f"(d[0]),"+f"(d[1]),"+f"(d[2]),"+f"(d[3]),"+f"(d[4]),"+f"(d[5]),"+f"(d[6]),"+f"(d[7]),"+f"(d[8]),"+f"(d[9]),"+f"(d[10]),"+f"(d[11]),"+f"(d[12]),"+f"(d[13]),"+f"(d[14]),"+f"(d[15]),"+f"(d[16]),"+f"(d[17]),"+f"(d[18]),"+f"(d[19]),"+f"(d[20]),"+f"(d[21]),"+f"(d[22]),"+f"(d[23]),"+f"(d[24]),"+f"(d[25]),"+f"(d[26]),"+f"(d[27]),"+f"(d[28]),"+f"(d[29]),"+f"(d[30]),"+f"(d[31])
    : "r"(a0), "r"(a1), "r"(a2), "r"(a3), "l"(db), "r"(sd));
}
__device__ __forceinline__ void wg_rs24_01(float* d, uint32_t a0, uint32_t a1, uint32_t a2, uint32_t a3, uint64_t db, int sd) {
  asm volatile("{.reg .pred p; setp.ne.b32 p, %17, 0;\n"
    "wgmma.mma_async.sync.aligned.m64n24k16.f32.bf16.bf16 {%0,%1,%2,%3,%4,%5,%6,%7,%8,%9,%10,%11}, {%12,%13,%14,%15}, %16, p, 1, 1, 1;}"
    : "+f"(d[0]),"+f"(d[1]),"+f"(d[2]),"+f"(d[3]),"+f"(d[4]),"+f"(d[5]),"+f"(d[6]),"+f"(d[7]),"+f"(d[8]),"+f"(d[9]),"+f"(d[10]),"+f"(d[11])
    : "r"(a0), "r"(a1), "r"(a2), "r"(a3), "l"(db), "r"(sd));
}

#define AB_POLY 0xaa
#define AB_DEG 3
__device__ __forceinline__ constexpr bool poly_group(int group) { return (AB_POLY >> (group & 7)) & 1; }

template <int V> struct Int { static constexpr int value = V; };

template <int NG>
__device__ __forceinline__ void ln_stats(const float4 (&v)[NG][5], uint32_t scratch, float (&mean)[NG], float (&rs)[NG]) {
  const int warp = threadIdx.x >> 5, lane = threadIdx.x & 31;
#pragma unroll
  for (int r = 0; r < NG; r++) {
    float s = 0.f, q = 0.f;
#pragma unroll
    for (int i = 0; i < 5; i++) s += (v[r][i].x + v[r][i].y) + (v[r][i].z + v[r][i].w);
    s += __shfl_xor_sync(~0u, s, 1); s += __shfl_xor_sync(~0u, s, 2);
    s *= 1.f / 80;
#pragma unroll
    for (int i = 0; i < 5; i++) {
      const float x = v[r][i].x - s, y = v[r][i].y - s, z = v[r][i].z - s, w = v[r][i].w - s;
      q += (x * x + y * y) + (z * z + w * w);
    }
    q += __shfl_xor_sync(~0u, q, 1); q += __shfl_xor_sync(~0u, q, 2);
    mean[r] = s; rs[r] = q;
  }
  bar_sync(1, 256);
  if ((lane & 3) == 0) {
#pragma unroll
    for (int r = 0; r < NG; r++) sts64f(scratch + r * 512 + lane * 16 + warp * 8, mean[r], rs[r]);
  }
  bar_sync(1, 256);
#pragma unroll
  for (int r = 0; r < NG; r++) {
    const float4 e = lds128f(scratch + r * 512 + lane * 16);
    float t = e.x + e.z;
    t += __shfl_xor_sync(~0u, t, 1); t += __shfl_xor_sync(~0u, t, 2);
    t *= 0.125f;
    float q = e.y + e.w + 80.f * ((e.x - t) * (e.x - t) + (e.z - t) * (e.z - t));
    q += __shfl_xor_sync(~0u, q, 1); q += __shfl_xor_sync(~0u, q, 2);
    mean[r] = t; rs[r] = rsqrtf(q * (1.f / DM) + 1e-5f);
  }
}

__device__ __forceinline__ void ln_store(const uint32_t (&w)[2][5][2], int tile, int u0, bool live = true) {
  const int lane = threadIdx.x & 31;
  uint32_t* xc = g_xc + ((tile >> 1) * 40 + u0) * 256 + (tile & 1) * 64 + lane;
#pragma unroll
  for (int i = 0; i < 20; i++) if (live) xc[(i >> 1) * 128 + (i & 1) * 32] = w[i & 1][i >> 2][i >> 1 & 1];
#pragma unroll
  for (int i = 0; i < 5; i++) {
    const int u = u0 + i;
    uint32_t* xn = g_xn + (((tile >> 3) * 20 + (u >> 1)) * 16 + (tile & 1) * 8 + (tile & 6)) * 128 + (u & 1) * 64 + lane;
#pragma unroll
    for (int r = 0; r < 2; r++) if (live) { xn[r * 128] = w[r][i][0]; xn[r * 128 + 32] = w[r][i][1]; }
  }
}
__device__ __forceinline__ void wait_count(const uint32_t* c, uint32_t n) {
  int spin = 0;
  while ((ld_acquire(c) & 0xffff) < n) { __nanosleep(32); spin_guard(spin); }
}

__device__ __forceinline__ uint8_t* pool_at(uint32_t off) {
  return reinterpret_cast<uint8_t*>((reinterpret_cast<uintptr_t>(g_pool) + 8191) & ~(uintptr_t)8191) + off; }
struct Weights { const uint8_t* w[4]; };
__device__ __forceinline__ void prefetch_weights(const Weights& p, int i) {
  if (blockIdx.x < 128) asm volatile("cp.async.bulk.prefetch.L2.global [%0], 61440;" :: "l"(p.w[i] + (size_t)blockIdx.x * 61440) : "memory");
}
__global__ void __launch_bounds__(384) first_kernel(const __nv_bfloat16* __restrict__ xin, const uint4* __restrict__ wb, const __grid_constant__ Weights wa) {
  __shared__ __align__(16) float scratch[256];
  __shared__ uint32_t lat[4];
  const int warp = threadIdx.x >> 5, lane = threadIdx.x & 31, cta = blockIdx.x;
  TRACE(0);
  pdl_launch();
  if (warp >= 8) {
    if (warp < 10 || cta < NSLOT) {
      uint32_t* q = reinterpret_cast<uint32_t*>(pool_at((warp < 10 ? NSLOT : cta) * 8192 + (warp & 1) * 4096)) + (warp < 10 ? (cta & 127) * 8 : 0);
      if (lane < 8) stg_strong32(q + lane, 0u);
      uint32_t best = ~0u;
      if (lane == 0) {
        for (int r = 0; r < FK_REP; r++) {
          uint32_t t0, t1, v;
          asm volatile("mov.u32 %0, %%clock;" : "=r"(t0) :: "memory");
          asm volatile("atom.relaxed.gpu.global.exch.b32 %0, [%1], 0;" : "=r"(v) : "l"(q) : "memory");
          asm volatile("{.reg .u32 t; add.u32 t, %1, 1; mov.u32 %0, %%clock; sub.u32 %0, %0, %1;}" : "=r"(t1) : "r"(__shfl_sync(1u, v, 0)) : "memory");
          best = min(best, t1 - t0);
        }
        lat[warp - 8] = best;
      }
    }
    __syncwarp();
    bar_sync(2, cta < 128 ? 384 : 128);
    if (threadIdx.x == 288) for (int i = 0; i < FK_PF; i++) prefetch_weights(wa, i);
    if (threadIdx.x == 256) {
      const int part = lat[0] < lat[1] ? 0 : 1;
      uint32_t smid; asm("mov.u32 %0, %%smid;" : "=r"(smid));
      g_smpart[smid & 255] = part;
      g_smclk[smid & 255] = clk32() - gtime() * 2;
      g_smuse[smid & 255] = 0;
      if (cta < NSLOT) g_orient[cta] = lat[2] < lat[3] ? part : 1 - part;
    }
  } else if (cta < 128) {
    float4 v[2][5];
#pragma unroll
    for (int r = 0; r < 2; r++)
#pragma unroll
      for (int i = 0; i < 5; i++) {
        const uint32_t* src = reinterpret_cast<const uint32_t*>(xin) + (cta * 16 + r * 8 + (lane >> 2)) * (DM / 2) + warp * 40 + i * 8 + (lane & 3);
        const uint32_t a = src[0], b = src[4];
        v[r][i] = make_float4(bf_lo(a), bf_hi(a), bf_lo(b), bf_hi(b));
      }
    uint4 w8[2];
#pragma unroll
    for (int i = 0; i < 2; i++) w8[i] = wb[cta * 400 + min(i * 256 + threadIdx.x, 399)];
    float mean[2], rs[2];
    ln_stats<2>(v, s2u(scratch), mean, rs);
    bar_sync(2, 384);
    ABT(2, 2);
    if (threadIdx.x < 128) g_stat[cta * 128 + threadIdx.x] = make_float2(0.f, 0.f);
#pragma unroll
    for (int i = 0; i < 10; i++) g_x[((cta * 2 + i / 5) * 40 + warp * 5 + i % 5) * 32 + lane] = v[i / 5][i % 5];
    uint32_t w[2][5][2];
#pragma unroll
    for (int i = 0; i < 10; i++) {
      const float4 t = v[i / 5][i % 5];
      const float m = mean[i / 5], q = rs[i / 5];
      w[i / 5][i % 5][0] = pack2((t.x - m) * q, (t.y - m) * q); w[i / 5][i % 5][1] = pack2((t.z - m) * q, (t.w - m) * q);
    }
    ln_store(w, cta, warp * 5);
    ABT(2, 3);
#pragma unroll
    for (int i = 0; i < 2; i++) {
      const int e = cta * 400 + min(i * 256 + threadIdx.x, 399), k = e / 80, n = e - k * 80, cg = n / 10;
      g_wb[((cg * 80 + (k >> 3)) * 10 + n - cg * 10) * 8 + (k & 7)] = w8[i];
    }
  } else if (cta == 128) {
    g_bo[threadIdx.x] = 0;
  }
  TRACE(2);
}

struct ChainParams {
  CUtensorMap wq, wk, wv, wo;
  const __nv_bfloat16* mem0;
  uint8_t *pool, *kv;
  const uint32_t* xc;
  uint32_t* sync;
  int layer;
  int d0, d3, d1, d1b, d2, d2b, mode;
};
constexpr int CH_WQ = 0, CH_WO = 81920, CH_X = CH_WO + 86016, CH_M = CH_X + 20480, CH_KT = CH_X + 40960, CH_VT = CH_KT + 4096,
              CH_PS = CH_VT + 4096, CH_QK = CH_PS + 4096, CH_VP = CH_QK + 4096, CH_SX = CH_VP + 1024, CH_O = CH_SX + 2304, CH_ID = CH_O + 3072,
              CH_BAR = CH_ID + 512;
constexpr int CH_SMEM = CH_BAR + 256;
constexpr int CH_BASE = 1024;
#define CH_VK0 8
#define CH_VK1 20
#define CH_L0 4
#define CH_LR 4
#define NOX 0
#define CH_XA 1
#define CH_XB 4
#define CH_W1 3
#define CH_W2 17
#define CH_W3 26
#define CH_R2 8
#define CH_VA 16
#define CH_EX 1
#define CH_KD 0
#define CH_RP 1
#define CH_KF 10
#define CH_LO 0
#define CH_LR1 4
#define CH_KP 0
#define CH_KM 0
#define CH_WE 0
#define CH_KW 3
#define CH_RB 0
#define CH_RC 8
#define CH_D0 200
#define CH_D1 450
#define CH_D2 350
#define CH_R1 4
#define CH_TW 12
__device__ __forceinline__ uint32_t opaque(uint32_t x) { return __shfl_sync(~0u, x, threadIdx.x & 31); }
__device__ __forceinline__ uint32_t nz(uint32_t x) { uint32_t r; asm("max.u32 %0, %1, 1;" : "=r"(r) : "r"(x)); return r; }
__device__ __forceinline__ uint32_t pack_tag(float lo, float hi, uint32_t tag, uint32_t mask) {
  uint32_t r;
  asm("lop3.b32 %0, %1, %2, %3, 0xD8;" : "=r"(r) : "r"(pack2(lo, hi)), "r"(tag), "r"(mask));
  return r;
}
__device__ __forceinline__ uint32_t differ(uint32_t a, uint32_t b, uint32_t t) { uint32_t r; asm("lop3.b32 %0, %1, %2, %3, 0x7E;" : "=r"(r) : "r"(a), "r"(b), "r"(t)); return r; }
__device__ __forceinline__ void mbar_wait_hot(uint32_t bar, uint32_t ph) {
  uint32_t ok;
  asm volatile("{.reg .pred p; mbarrier.try_wait.parity.shared::cta.b64 p, [%1], %2; selp.u32 %0, 1, 0, p;}" : "=r"(ok) : "r"(bar), "r"(ph) : "memory");
  if (__builtin_expect(!ok, 0)) mbar_wait(bar, ph);
}
__device__ __forceinline__ bool elect() {
  uint32_t r; asm volatile("{.reg .pred p; elect.sync _|p, 0xffffffff; selp.u32 %0, 1, 0, p;}" : "=r"(r)); return r; }
__device__ __forceinline__ uint32_t or3(uint32_t a, uint32_t b, uint32_t c) { uint32_t r; asm("lop3.b32 %0, %1, %2, %3, 0xFE;" : "=r"(r) : "r"(a), "r"(b), "r"(c)); return r; }
__device__ __forceinline__ void pin() { pdl_launch(); }
__device__ __forceinline__ void mma16h(float* d, uint32_t a0, uint32_t a2, uint32_t b0, uint32_t b1) {
  asm volatile("{.reg .b32 u, v; mma.sync.aligned.m16n8k16.row.col.f32.bf16.bf16.f32 {%0,%1,%2,%3},{%4,u,%5,v},{%6,%7},{%0,%1,%2,%3};}"
               : "+f"(d[0]), "+f"(d[1]), "+f"(d[2]), "+f"(d[3]) : "r"(a0), "r"(a2), "r"(b0), "r"(b1)); }
__device__ __forceinline__ void mma8h(float* d, uint32_t a0, uint32_t b0) {
  asm volatile("{.reg .b32 u; mma.sync.aligned.m16n8k8.row.col.f32.bf16.bf16.f32 {%0,%1,%2,%3},{%4,u},{%5},{%0,%1,%2,%3};}"
               : "+f"(d[0]), "+f"(d[1]), "+f"(d[2]), "+f"(d[3]) : "r"(a0), "r"(b0)); }
__device__ __forceinline__ uint32_t absmax2(uint32_t a, uint32_t b) { uint32_t r; asm("max.xorsign.abs.bf16x2 %0, %1, %2;" : "=r"(r) : "r"(a), "r"(b)); return r; }
__device__ __forceinline__ void until(uint32_t t) { while ((int)(clk32() - t) < 0) {} }
__device__ __forceinline__ uint4 pack8(const float* d) { return make_uint4(pack2(d[0], d[1]), pack2(d[2], d[3]), pack2(d[4], d[5]), pack2(d[6], d[7])); }
__device__ __forceinline__ void add8(float* d, uint4 v) {
  d[0] += bf_lo(v.x); d[1] += bf_hi(v.x); d[2] += bf_lo(v.y); d[3] += bf_hi(v.y);
  d[4] += bf_lo(v.z); d[5] += bf_hi(v.z); d[6] += bf_lo(v.w); d[7] += bf_hi(v.w);
}

template <int WG>
__device__ __forceinline__ void chain_body(const ChainParams& p, const uint32_t wq, const uint32_t (&ak)[80], const uint32_t (&av)[80]) {
  const int tid = threadIdx.x & 127, t4 = __shfl_sync(~0u, tid >> 5, 0), lane = tid & 31;
  const int cta = blockIdx.x, h = cta / 3, j = cta - 3 * h;
  const uint32_t sb = mapa(CH_BASE, j);
  const uint32_t bWo = sb + CH_BAR, bWq = bWo + 8, bX = bWo + 16, bXA = bWo + 24, bXB = bWo + 32, bO = bWo + 40, bG = bWo + 48, bH = bWo + 96;
  uint32_t tw[4 * CH_TW];
  auto refill = [&]() {
#pragma unroll
    for (int k = 0; k < CH_TW; k++) ldsm4t(&tw[4 * k], wq + k * 2048);
  };
  const uint32_t wo = opaque((sb + CH_WO + (WG == 0 ? (t4 + (j == 2)) * 4096 : (j == 2 ? 0 : 24576) + t4 * 1024) + ((lane & 7) + (lane >> 4) * 8) * 64 +
                              ((((lane >> 3) & 1) ^ ((lane >> 1) & 3)) << 4)) ^ (WG == 1 && j == 2 ? 32 : 0));
  const uint32_t wo2 = opaque((wo ^ ((t4 & 1) * 32)) + (4 + (t4 >> 1) - t4) * 4096);
  const uint32_t l16 = opaque(sb + lane * 16);
  const uint32_t l8 = opaque(sb + t4 * 256 + lane * 8);
  const uint32_t lw = opaque(sb + t4 * 1024 + lane * 16);
  const uint32_t qs = opaque(sb + CH_QK + WG * 2048 + t4 * 512 + lane * 16);
  const uint32_t qa = opaque(sb + CH_QK + (lane >> 4) * 2048 + (lane & 15) * 16 + (WG == 0 ? t4 * 512 + 256 : t4 == 3 ? 1024 : 0));
  const uint32_t ka = opaque(t4 < 2 ? sb + CH_KT + t4 * 512 + lane * 16
                                    : sb + CH_QK + 256 + (t4 - 2) * 1024 + ((lane >> 3) & 1) * 2048 + (lane >> 4) * 128 + (lane & 7) * 16);
  const uint32_t l4 = opaque(sb + t4 * 256 + lane * 4);
  uint32_t pdst[1], pages = 0;
  auto line0 = [&](int i) { return 28 * j + (i < 4 ? 4 * t4 + i : 12 + 2 * t4 + i); };
  const uint32_t plane = opaque((lane >> 4) * 2048 + h * 64 + (lane & 15) * 4);
  if (WG == 0) {
    pages = __ballot_sync(~0u, lds32(sb + CH_O + line0(min(lane, 5)) * 4) & 4096);
  } else {
    pages = __ballot_sync(~0u, lds32(sb + CH_O + (80 + min(lane, 11)) * 4) & 4096);
    pdst[0] = opaque(lds32(sb + CH_O + (j == 0 ? 24 + t4 : 50 + 2 * j + (t4 & 1)) * 4) + plane);
  }
  const uint32_t role = lds32(sb + CH_O + NSLOT * 4), rsrc = lds32(sb + CH_O + role * 4), rdst = (80 + role / 20) * 8192 + role % 20 * 128;
  const uint32_t r1 = mapa(CH_BASE, j == 2 ? 0 : j + 1) - sb, r2 = mapa(CH_BASE, j == 0 ? 2 : j - 1) - sb;
  uint32_t tag = opaque(1);
  auto pool = [&](uint32_t off) { return p.pool + ((tag & 0xfffe) + off); };
  auto after = [&](uint32_t x) { return x & tag & 0xfffe; };
  auto kv = [&](int s, uint32_t a) { return p.kv + (a + ((cta * 2 * NSEG + s) * KV_BYTES - sb)); };
  auto pass = [&](float (&d)[16], const uint32_t (&a)[80], auto k0, auto k1) {
    const uint64_t db = mkdesc(CH_BASE + CH_X + WG * 20480, 512, 128, 0);
#pragma unroll
    for (int k = k0.value; k < k1.value; k++) wg_rs32_00(d, a[4 * k], a[4 * k + 1], a[4 * k + 2], a[4 * k + 3], db + k * 64, k);
    wg_commit();
  };
  auto dump = [&](float (&d)[16], uint32_t a) {
    reg_fence<16>(d);
    sts128(a, pack8(d)); sts128(a + 512, pack8(d + 8));
  };
  uint32_t pph = 0;
  auto tokens0 = [&](int s, auto k0) {
    float dk[16], dv[16];
    bar_sync(9, 256);
    wg_fence();
    pass(dk, ak, Int<0>(), Int<4>());
    const uint4 a0 = lds128(lw + CH_KT), a1 = lds128(lw + CH_KT + 512);
    pin();
    pass(dk, ak, Int<4>(), Int<20>());
    pass(dv, av, Int<0>(), Int<CH_VA>());
    pin();
    wg_wait<1>();
    reg_fence<16>(dk);
    add8(dk, a0); add8(dk + 8, a1);
    const uint4 w0 = pack8(dk), w1 = pack8(dk + 8);
    const uint4 b0 = lds128(lw + CH_VT), b1 = lds128(lw + CH_VT + 512);
    stsm4t(lw + CH_KT, w0.x, w0.z, w0.y, w0.w); stsm4t(lw + CH_KT + 512, w1.x, w1.z, w1.y, w1.w);
    if (CH_KP == 2) bar_arrive(7, 160);
    TM1(6);
    pin();
    if (CH_VA < 20) pass(dv, av, Int<CH_VA>(), Int<20>());
    pin();
#pragma unroll
    for (int k = k0.value; k < CH_TW; k++) ldsm4t(&tw[4 * k], wq + k * 2048);
    TM1(9);
    if (k0.value < CH_TW && t4 >= 2) { mbar_wait_hot(bH + t4 * 16 - 24 + (pph & 1) * 8, pph >> 1 & 1); pph++; }
    __syncwarp();
    wg_wait<0>();
    reg_fence<16>(dv);
    add8(dv, b0); add8(dv + 8, b1);
#pragma unroll
    for (int e = 0; e < 2; e++) { const uint4 v = pack8(dv + 8 * e); sts128(lw + CH_VT + e * 512, make_uint4(v.x, v.z, v.y, v.w)); }
  };
  auto publish_k = [&](int s) {
    if (t4 == CH_KW && elect()) { fence_async(); bulk_store(p.kv + (size_t)(cta * 2 * NSEG + s) * KV_BYTES, sb + CH_KT, 4096); bulk_commit(); }
    __syncwarp();
  };
  if (WG == 0) {
    mbar_wait(bXB, 0);
    tokens0(0, Int<CH_TW>());
  } else {
    const uint32_t* m0 = reinterpret_cast<const uint32_t*>(p.mem0) + (lane >> 2) * 320 + t4 * 80 + (lane & 3);
    uint32_t a[20];
#pragma unroll
    for (int i = 0; i < 20; i++) a[i] = m0[4 * i];
    pin();
    float dk[16], dv[16];
    mbar_wait(bXA, 0);
    wg_fence();
    pass(dk, ak, Int<0>(), Int<20>());
    pass(dv, av, Int<0>(), Int<20>());
    wg_wait<0>();
    dump(dk, lw + CH_KT);
    dump(dv, lw + CH_VT);
    bar_sync(9, 256);
    if (CH_KP == 2 && t4 == CH_KW) { bar_sync(7, 160); publish_k(0); }
#pragma unroll
    for (int i = 0; i < 20; i++) sts32(sb + CH_M + (t4 * 20 + i) * 128 + lane * 4, nz(transpose8(a[i])));
    __syncwarp();
    if (elect()) mbar_arrive(bG + t4 * 8);
  }
  PRO(8);
  mbar_wait(bWq, 0);
  refill();
  PRO(9);
  mbar_wait(bWo, 0);
  asm volatile("barrier.cluster.wait.aligned;" ::: "memory");
  PRO(10);
  auto load_x = [&](int s, int k0, int n, uint32_t bar) {
    if (!NOX && elect()) { mbar_expect(bar, n * 1024); bulk_load(sb + CH_X + k0 * 1024, p.xc + (s + 1) * 10240 + k0 * 256, n * 1024, bar); }
  };
  constexpr int VK = WG == 0 ? CH_VK0 : CH_VK1;
  uint32_t gph = 0;
  int st = 0;
  const uint32_t ca = opaque(sb + CH_M + t4 * 2560 + lane * 32 + (lane >> 2) * 4);
  auto project = [&](int s, uint32_t (&b)[40], float (&dv)[16], uint32_t (&kf)[16]) {
    float dq[4] = {}, dk[4] = {};
    uint32_t w[80];
#pragma unroll
    for (int i = 0; i < 4 * CH_TW; i++) w[i] = tw[i];
    constexpr int LR = WG == 1 ? CH_LR1 : CH_LR;
    auto load = [&](int n) {
      int c = 0;
#pragma unroll
      for (int i = 0; i < 10; i++) {
        if (i == CH_KF) {
#pragma unroll
          for (int q = 0; q < 4; q++)
            if (WG == 1 && c++ == n) ldsm4(&kf[4 * q], ka + q * 1024);
        }
        if (c++ == n) ldsm4t(&b[4 * i], l16 + CH_M + WG * 5120 + i * 512);
#pragma unroll
        for (int k = 2 * i; k < 2 * i + 2; k++)
          if (k >= CH_TW && c++ == n) ldsm4t(&w[4 * k], wq + k * 2048);
      }
#pragma unroll
      for (int i = 0; i < 4; i++)
        if (WG == 1 && CH_KF >= 10 && c++ == n) ldsm4(&kf[4 * i], ka + i * 1024);
    };
    if (WG == 1) {
      for (int n = 0;;) {
        mbar_wait(bG + t4 * 8, gph);
        TR(5, (clk32() & ~3u) | min(n, 3));
        gph ^= 1;
        if (__builtin_expect(!__any_sync(~0u, __vimin3_u32(lds32(ca), lds32(ca + 1024), lds32(ca + 1536)) == 0), 1)) break;
        if (elect()) {
          const int q = (st == 0 ? 8 : st * 4 - 4) + t4;
          mbar_expect(bG + t4 * 8, 2560);
          bulk_load(sb + CH_M + t4 * 2560, p.pool + ((80 + q) * 8192 + (pages >> q & 1) * 4096), 2560, bG + t4 * 8);
        }
        spin_guard(n);
      }
    }
    bar_sync(6, 256);
#pragma unroll
    for (int i = 0; i < CH_L0; i++) load(i);
    if (WG == 0 && CH_XB == 4 && s + 1 < NSEG) load_x(s, 5 * t4, 5, bXB);
    TM(0);
    TM1(11);
    if (WG == 1) TR(6, clk32());
#pragma unroll
    for (int k = 0; k < 20; k += 2) {
      if (k > 0) {
#pragma unroll
        for (int n = (k == 18 ? 40 : CH_L0 + k * LR / 4) - 1; n >= CH_L0 + (k - 2) * LR / 4; n--) { load(n); if (CH_LO) __syncwarp(); }
      }
      pin();
#pragma unroll
      for (int kk = k; kk < k + 2; kk++) {
        mma16(dk, ak[4 * kk], ak[4 * kk + 1], ak[4 * kk + 2], ak[4 * kk + 3], b[2 * kk], b[2 * kk + 1]);
        mma16(dq, w[4 * kk], w[4 * kk + 1], w[4 * kk + 2], w[4 * kk + 3], b[2 * kk], b[2 * kk + 1]);
        if (kk < VK) mma16(dv, av[4 * kk], av[4 * kk + 1], av[4 * kk + 2], av[4 * kk + 3], b[2 * kk], b[2 * kk + 1]);
      }
    }
    const float k2 = 0.07216878364870322f * 1.44269504089f;
    stsm4t(qs, pack2(dq[0] * k2, dq[1] * k2), pack2(dq[2] * k2, dq[3] * k2), pack2(dk[0], dk[1]), pack2(dk[2], dk[3]));
    TM(1);
  };
  static_assert(CH_VK1 == 20 && CH_KP == 0 && CH_XA > 0 && CH_XB > 0, "last step");
  constexpr int VC = VK == 20 ? 1 : WG == 0 ? 2 : 3;
  auto finish_v = [&](const uint32_t (&b)[40], float (&dv)[16]) {
#pragma unroll
    for (int kk = VK; kk < 20; kk++) mma16(dv + 4 * ((kk - VK) % VC), av[4 * kk], av[4 * kk + 1], av[4 * kk + 2], av[4 * kk + 3], b[2 * kk], b[2 * kk + 1]);
  };
  auto sum_v = [&](float (&dv)[16]) {
#pragma unroll
    for (int i = 4; i < 4 * VC; i++) dv[i & 3] += dv[i];
  };
  auto publish_km = [&](int s) {
    uint32_t a[4];
    ldsm4(a, qa);
    *reinterpret_cast<uint2*>(kv(s, l8) + KV_M) = make_uint2(hadd2(a[0], a[2]), hadd2(a[1], a[3]));
  };
  auto memory_v = [&](uint2 x, const float (&dv)[16]) {
    return make_uint2(pack2(dv[0] + bf_lo(x.x), dv[1] + bf_hi(x.x)), pack2(dv[2] + bf_lo(x.y), dv[3] + bf_hi(x.y)));
  };
  auto publish_v = [&](int s, const uint4 (&v)[2], uint2 vm) {
#pragma unroll
    for (int e = 0; e < 2; e++) reinterpret_cast<uint4*>(kv(s, lw) + KV_V)[e * 32] = v[e];
    *reinterpret_cast<uint2*>(kv(s, l8) + KV_V + KV_M) = vm;
  };
#pragma unroll 1
  for (int s = 0;; s++) {
    float dv[16] = {};
    uint32_t b[40], kf[16];
    project(s, b, dv, kf);
    if (WG == 0) {
      bar_sync(1, 256);
      if (CH_XA == 0) load_x(s, 20 + 5 * t4, 5, bXA);
      if (CH_XB == 0) load_x(s, 5 * t4, 5, bXB);
      pin();
      finish_v(b, dv);
      sum_v(dv);
      sts64(l8 + CH_VP, pack2(dv[0], dv[1]), pack2(dv[2], dv[3]));
      if (s == NSEG - 1) {
        bar_arrive(10, 256);
        publish_k(s);
        publish_km(s);
        bulk_wait<0>();
        fence_async_global();
        bar_sync(2, 256);
        if (tid == 0) red_release(p.sync + 15 * 8 + 4, 1);
        break;
      }
      __syncwarp();
      if (elect()) mbar_arrive(bX);
      if (CH_XA == 1) load_x(s, 20 + 5 * t4, 5, bXA);
      if (CH_XB == 1) load_x(s, 5 * t4, 5, bXB);
      uint32_t w[144];
      auto wload = [&](int i) { ldsm4t(&w[4 * i], (i % 3 == 0 ? wo : i % 3 == 1 ? wo ^ 32 : wo2) + i / 12 * 28672 + i / 3 % 4 * 1024); };
      TM(3);
      if (CH_KP == 0) publish_k(s);
#pragma unroll
      for (int i = 0; i < CH_W1; i++) wload(i);
      bar_sync(10, 256);
      uint32_t km[4];
      ldsm4(km, qa);
      pin();
#pragma unroll
      for (int i = CH_W1; i < CH_W2; i++) wload(i);
      pin();
      const uint2 kms = make_uint2(hadd2(km[0], km[2]), hadd2(km[1], km[3]));
      if (CH_KM == 0) *reinterpret_cast<uint2*>(kv(s, l8) + KV_M) = kms;
      if (CH_KP == 0) bulk_wait_read<0>();
      if (CH_XA == 2) load_x(s, 20 + 5 * t4, 5, bXA);
      if (CH_XB == 2) load_x(s, 5 * t4, 5, bXB);
      bar_sync(2, 256);
      {
        float y[3][4] = {};
        uint32_t ob[24];
        ldsm4(&ob[0], l16 + CH_O + 1024); ldsm4(&ob[4], l16 + CH_O + 1536);
        TM(7);
        auto step = [&](int i) {
          const int k = i / 3;
          mma16(y[i % 3], w[4 * i], w[4 * i + 1], w[4 * i + 2], w[4 * i + 3], ob[2 * k], ob[2 * k + 1]);
        };
#pragma unroll
        for (int i = 0; i < 12; i++) {
          step(i);
          if (i >= 12 - (CH_W3 - CH_W2)) wload(CH_W3 - 12 + i);
          if (i % 3 == 2) pin();
        }
        if (CH_XB == 3) load_x(s, 5 * t4, 5, bXB);
        if (CH_KM == 1) *reinterpret_cast<uint2*>(kv(s, l8) + KV_M) = kms;
        pin();
        mbar_wait(bO, s & 1);
        TM(4);
        ldsm4(&ob[8], l16 + CH_O); ldsm4(&ob[12], l16 + CH_O + 512);
        pin();
        float2 inv;
        uint8_t* dst[6];
        uint32_t mask;
#pragma unroll
        for (int i = 12; i < 36; i++) {
          step(i);
          const int n = CH_W3 + i - 13, m = n - (n > 30);
          if (i == 12) ldsm4(&ob[16], l16 + after(w[4 * CH_W3 - 1] | w[4 * CH_W3 - 5] | w[4 * CH_W3 - 9] | ob[8]) + CH_O + 2048);
          else if (n == 30) ldsm4(&ob[20], l16 + CH_O + 2560);
          else if (m < 36) wload(m);
          else if (m == 36) inv = lds64f((l8 & ~0xe0u) + CH_VP);
          if (i == 26) mask = ((l16 ^ tag) & 48) == 0;
          if (i >= 27 && i < 33) dst[i - 27] = pool(line0(i - 27) * 8192 + (pages >> (i - 27) & 1) * 4096) + plane;
          if (i % 3 == 2) pin();
        }
#pragma unroll
        for (int k = 0; k < CH_R1; k++) ldsm4t(&tw[4 * k], wq + k * 2048);
        pin();
#pragma unroll
        for (int i = 0; i < 6; i++) stg_strong32(dst[i], pack_tag(y[i >> 1][2 * (i & 1)] * inv.x, y[i >> 1][2 * (i & 1) + 1] * inv.y, tag, mask));
        TM(8);
        TR(0, clk32());
        bar_arrive(5, 256);
        pin();
      }
      const uint32_t t0 = clk32();
      auto refill2 = [&]() {
#pragma unroll
        for (int k = CH_R1; k < CH_R2; k++) ldsm4t(&tw[4 * k], wq + k * 2048);
      };
      if (CH_RP == 0) refill2();
      const uint32_t ln = (l16 ^ tag) >> 4 & 31;
      if (t4 >= 2) {
        const uint32_t bP = bH + t4 * 16 - 24, ps = CH_PS + (t4 & 1) * 4096;
        auto fetch = [&](uint32_t k) {
          if (elect()) { mbar_expect(bP + (k & 1) * 8, 2048); bulk_load(sb + ps + (k & 1) * 2048, p.pool + (rsrc + (t4 & 1) * 2048), 2048, bP + (k & 1) * 8); }
        };
        until(t0 + CH_D0);
        fetch(pph);
        if (CH_RP == 2) refill2();
        if (!NOX) mbar_wait_hot(bXB, (s + 1) & 1);
        const uint32_t want = (tag & 1) * 0x10001, chk = opaque(ln < 4 ? 0x10001 : 0);
        uint4 sel;
        sel.x = opaque((ln >> 3) != (ln & 1) ? 0 : ln & 4 ? 0x3f800000u : 0x00003f80u);
        sel.z = opaque(sel.x); sel.y = opaque(ln); sel.w = opaque(ln + 1);
        uint8_t* mdst = p.pool + opaque(st * 32768 + rdst + (t4 & 1) * 64 + ln * 4);
        until(t0 + CH_D1);
        fetch(pph + 1);
        TM(5);
        if (CH_RP == 1) refill2();
        int n = 0;
        uint32_t u[16];
        for (;;) {
          mbar_wait(bP + (pph & 1) * 8, pph >> 1 & 1);
          TM(14);
          TR(2, clk32());
#pragma unroll
          for (int i = 0; i < 4; i++) ldsm4t(&u[4 * i], l16 + (ps + (pph & 1) * 2048) + i * 512);
          pph++;
          uint32_t bad = 0;
#pragma unroll
          for (int i = 0; i < 4; i++) bad = or3(bad, differ(u[4 * i], u[4 * i + 1], want), differ(u[4 * i + 2], u[4 * i + 3], want));
          if (!__any_sync(~0u, bad & chk)) break;
          fetch(pph + 1);
          spin_guard(n);
        }
        float y[4][4] = {};
#pragma unroll
        for (int i = 0; i < 8; i++) mma16(y[i & 3], sel.x, sel.y, sel.z, sel.w, u[2 * i], u[2 * i + 1]);
        TR(1, t0 + (n ? CH_D1 : CH_D0));
        TM(15);
        const uint32_t w = nz(pack2((y[0][0] + y[1][0]) + (y[2][0] + y[3][0]), (y[0][1] + y[1][1]) + (y[2][1] + y[3][1])));
        if (ln < 16) { stg_strong32(mdst, w); stg_strong32(mdst + 4096, w); }
        TMV(12, 32, n);
        TR(3, (clk32() & ~3u) | min(n, 3));
      } else {
        if (CH_RP) refill2();
        if (!NOX) mbar_wait_hot(bXB, (s + 1) & 1);
        stg_strong32(p.pool + ((st == 2 ? 0 : st + 1) * 32768 + rdst + t4 * 4096) + ln * 4, 0u);
        if (t4 == 0 && cta < 40 && s + 4 < NSEG && elect())
          asm volatile("cp.async.bulk.prefetch.L2.global [%0], 1024;" :: "l"(p.xc + (s + 4) * 10240 + cta * 256) : "memory");
        if (t4 == 1 && (s & 3) == 0 && s > 0 && elect()) red_relaxed(p.sync + 2 * s - 4, 1);
        if (t4 == 1 && s == NSEG - 3 && cta == 95 && elect()) red_relaxed(p.sync + 2 * s + 2, 0x10000);
      }
      TM(10);
      bar_arrive(8, 256);
      tokens0(s + 1, Int<CH_R2>());
      TM(2);
      TR(7, clk32());
    } else {
      if (s == NSEG - 1) {
        bar_arrive(1, 256);
        const uint4 v[2] = {lds128(lw + CH_VT), lds128(lw + CH_VT + 512)};
        bar_sync(10, 256);
        publish_v(s, v, memory_v(lds64(l8 + CH_VP), dv));
        bar_arrive(2, 256);
        break;
      }
      const uint32_t xo = l4 + (CH_SX - (t4 == 3 ? 128 : 0)), x1 = xo + (r1 + 768 + min(t4, 2) * 256), x2 = xo + (r2 + 1024 + min(t4, 2) * 256);
      if (t4 < 2) {
        float ds[4][4] = {};
        uint32_t q[16];
        asm volatile("bar.sync 1, 256;" ::: "memory");
#pragma unroll
        for (int k = 0; k < 4; k++) ldsm4(&q[4 * k], qa + k * 512);
        pin();
        if (VK < 20) { finish_v(b, dv); pin(); }
#pragma unroll
        for (int k = 0; k < 4; k++) {
          mma16(ds[k & 1], kf[4 * k], kf[4 * k + 1], kf[4 * k + 2], kf[4 * k + 3], q[4 * k], q[4 * k + 1]);
          mma16(ds[2 + (k & 1)], kf[4 * k], kf[4 * k + 1], kf[4 * k + 2], kf[4 * k + 3], q[4 * k + 2], q[4 * k + 3]);
        }
        float t[4];
#pragma unroll
        for (int i = 0; i < 4; i++) t[i] = (ds[0][i] + ds[2][i]) + (ds[1][i] + ds[3][i]);
        const uint32_t w0 = pack2(t[0], t[1]), w1 = pack2(t[2], t[3]);
        st_async32(x1, w0, bX + r1); st_async32(x2, w0, bX + r2);
        st_async32(x1 + 128, w1, bX + r1); st_async32(x2 + 128, w1, bX + r2);
        sts32(xo, w0); sts32(xo + 128, w1);
      } else {
        float ds[4][4] = {};
        uint32_t q0[4], q1[4], a0[4], a1[4];
        asm volatile("bar.sync 1, 256; " ::: "memory");
        ldsm4(a0, ka); ldsm4(q0, qa); ldsm4(a1, ka + 512); ldsm4(q1, qa + 512);
        pin();
        if (VK < 20) { finish_v(b, dv); pin(); }
        mma16(ds[0], a0[0], a0[1], a0[2], a0[3], q0[0], q0[1]);
        mma16(ds[1], a0[0], a0[1], a0[2], a0[3], q0[2], q0[3]);
        mma16(ds[2], a1[0], a1[1], a1[2], a1[3], q1[0], q1[1]);
        mma16(ds[3], a1[0], a1[1], a1[2], a1[3], q1[2], q1[3]);
        float t[2];
#pragma unroll
        for (int i = 0; i < 2; i++)
          t[i] = ((ds[0][i] + ds[0][i + 2]) + (ds[1][i] + ds[1][i + 2])) + ((ds[2][i] + ds[2][i + 2]) + (ds[3][i] + ds[3][i + 2]));
        const uint32_t w0 = pack2(t[0], t[1]);
        st_async32(x1, w0, bX + r1);
        st_async32(x2, w0, bX + r2);
        sts32(xo, w0);
      }
      TM(3);
      const uint4 id = lds128(l16 + CH_ID);
      float sc[3][4] = {};
      uint4 v[2];
      sum_v(dv);
      bar_sync(3, 128);
      uint32_t r[12], wd[12], we[12] = {};
      ldsm4(&r[0], l16 + CH_SX); ldsm2(&r[4], l16 + CH_SX + 512);
      pin();
      v[0] = lds128(lw + CH_VT); v[1] = lds128(lw + CH_VT + 512);
#pragma unroll
      for (int u = 0; u < 3; u++) ldsm4t(&wd[4 * u], wo + u * 28672);
      if (CH_WE && j == 0) {
#pragma unroll
        for (int u = 0; u < 3; u++) ldsm4t(&we[4 * u], (wo ^ 32) + u * 28672);
      }
      pin();
#pragma unroll
      for (int q = 0; q < 3; q++) mma16(sc[q], id.x, id.y, id.z, id.w, r[2 * q], r[2 * q + 1]);
      uint32_t big = absmax2(absmax2(absmax2(r[0], r[1]), absmax2(r[2], r[3])), absmax2(r[4], r[5]));
      const uint32_t oa1 = l4 + (r1 + CH_O), oa2 = l4 + (r2 + CH_O + 2048), ones = 0x3f803f80u;
      mbar_wait_hot(bX, s & 1);
      TM(4);
      ldsm4(&r[0], l16 + CH_SX + 768); ldsm4(&r[8], l16 + CH_SX + 1792); ldsm4(&r[4], l16 + CH_SX + 1280);
      const uint2 vp = lds64(l8 + CH_VP);
      bar_arrive(10, 256);
      pin();
      {
        float sd[3][4] = {};
#pragma unroll
        for (int i = 0; i < 3; i++) {
          const int q = i == 0 ? 0 : 3 - i;
          mma16(sc[q], id.x, id.y, id.z, id.w, r[4 * q], r[4 * q + 1]);
          mma16(sd[q], id.x, id.y, id.z, id.w, r[4 * q + 2], r[4 * q + 3]);
          big = absmax2(big, absmax2(absmax2(r[4 * q], r[4 * q + 1]), absmax2(r[4 * q + 2], r[4 * q + 3])));
        }
#pragma unroll
        for (int i = 0; i < 12; i++) sc[i >> 2][i & 3] += sd[i >> 2][i & 3];
      }
      const bool redo = __any_sync(~0u, (absmax2(big, big << 16) & 0x7fff0000u) >= 0x41800000u);
      const uint2 vm = memory_v(vp, dv);
      sc[2][0] += sc[2][2]; sc[2][1] += sc[2][3];
      float l[4], o[2][4];
      uint32_t p3, p4;
      auto attend = [&]() {
#pragma unroll
        for (int i = 0; i < 4; i++) l[i] = o[0][i] = o[1][i] = 0.f;
        const uint32_t p1 = pack2(ex2(sc[0][0]), ex2(sc[0][1])), p2 = pack2(ex2(sc[0][2]), ex2(sc[0][3]));
        mma16h(o[0], p1, p2, v[0].x, v[0].y);
        mma16h(o[1], p1, p2, v[0].z, v[0].w);
        mma16h(l, p1, p2, ones, ones);
        const uint32_t p0 = pack2(ex2(sc[2][0]), ex2(sc[2][1]));
        mma8h(o[0], p0, vm.x);
        mma8h(o[1], p0, vm.y);
        mma8h(l, p0, ones);
        p3 = pack2(ex2(sc[1][0]), ex2(sc[1][1])); p4 = pack2(ex2(sc[1][2]), ex2(sc[1][3]));
        mma16h(o[0], p3, p4, v[1].x, v[1].y);
        mma16h(o[1], p3, p4, v[1].z, v[1].w);
      };
      attend();
      if (__builtin_expect(redo, 0)) {
        float mx = fmaxf(sc[2][0], sc[2][1]);
#pragma unroll
        for (int i = 0; i < 4; i++) mx = fmaxf(mx, fmaxf(sc[0][i], sc[1][i]));
        mx = fmaxf(mx, __shfl_xor_sync(~0u, mx, 1));
        mx = fmaxf(mx, __shfl_xor_sync(~0u, mx, 2));
#pragma unroll
        for (int i = 0; i < 4; i++) { sc[0][i] -= mx; sc[1][i] -= mx; }
        sc[2][0] -= mx; sc[2][1] -= mx;
        attend();
      }
      const uint32_t o0 = pack2(o[0][0], o[0][1]), o1 = pack2(o[1][0], o[1][1]);
      st_async32(oa1, o0, bO + r1); st_async32(oa2, o0, bO + r2);
      st_async32(oa1 + 128, o1, bO + r1); st_async32(oa2 + 128, o1, bO + r2);
      sts32(l4 + CH_O + 1024, o0); sts32(l4 + CH_O + 1152, o1);
      bar_arrive(2, 256);
      pin();
      TM(6);
      mma16h(l, p3, p4, ones, ones);
      float inv;
      asm("rcp.approx.ftz.f32 %0, %1;" : "=f"(inv) : "f"(l[0]));
      sts32((l8 & ~0xffu) + (lane & 28) + CH_VP, __float_as_uint(inv));
      __syncwarp();
      if (elect()) mbar_arrive(bO);
      {
        float z[2][4] = {}, y[2][4] = {};
        mma16(z[0], wd[0], wd[1], wd[2], wd[3], o0, o1);
        if (j == 0) {
#pragma unroll
          for (int u = 0; u < 3; u++) if (!CH_WE) ldsm4t(&we[4 * u], (wo ^ 32) + u * 28672);
          mma16(y[0], we[0], we[1], we[2], we[3], o0, o1);
        }
        const float2 iv = lds64f((l8 & ~0xe0u) + CH_VP);
        uint8_t* dst = pool(pdst[0]);
        const uint32_t mask = ((l16 ^ tag) & 48) == 0;
        const uint32_t oa = qa + ((tag & 0xfffe) + CH_O - CH_QK + t4 * 256 - (t4 == 3 ? 1024 : 0));
        const uint32_t za = l16 + ((tag & 0xfffe) + (t4 >> 1) * 512 + (t4 & 1) * 8);
        pin();
        mbar_wait(bO, s & 1);
        uint32_t a[4];
        ldsm4(a, oa);
        mma16(z[0], wd[4], wd[5], wd[6], wd[7], a[0], a[1]);
        mma16(z[1], wd[8], wd[9], wd[10], wd[11], a[2], a[3]);
        if (j == 0) {
          mma16(y[0], we[4], we[5], we[6], we[7], a[0], a[1]);
          mma16(y[1], we[8], we[9], we[10], we[11], a[2], a[3]);
          sts128f(lw + CH_VT + 512, y[0][0] + y[1][0], y[0][1] + y[1][1], y[0][2] + y[1][2], y[0][3] + y[1][3]);
        }
        sts128f(lw + CH_VT, z[0][0] + z[1][0], z[0][1] + z[1][1], z[0][2] + z[1][2], z[0][3] + z[1][3]);
        bar_sync(3, 128);
        if (j == 0 || t4 < 2) {
          float2 q[4];
#pragma unroll
          for (int i = 0; i < 4; i++) q[i] = lds64f(za + CH_VT + i * 1024);
          stg_strong32(dst, pack_tag(((q[0].x + q[1].x) + (q[2].x + q[3].x)) * iv.x, ((q[0].y + q[1].y) + (q[2].y + q[3].y)) * iv.y, tag, mask));
        }
      }
      TM(2);
      if (!NOX) mbar_wait_hot(bXA, (s + 1) & 1);
      if (CH_KP == 2) bulk_wait_read<0>();
      float dk[16], dw[16];
      bar_sync(5, 256);
      wg_fence();
      pass(dk, ak, Int<0>(), Int<20>());
      pass(dw, av, Int<0>(), Int<20>());
      TM(5);
      pin();
      if (CH_EX == 0) publish_v(s, v, vm);
      if (elect()) {
        mbar_expect(bG + t4 * 8, 2560);
        if (t4 == 1 && s + 2 < NSEG) { mbar_expect(bX, 1536); mbar_expect(bO, 2048); }
      }
      if (CH_KD == 0) { wg_wait<1>(); dump(dk, lw + CH_KT); }
      wg_wait<0>();
      if (CH_KD == 1) dump(dk, lw + CH_KT);
      TM(7);
      dump(dw, lw + CH_VT);
      bar_arrive(9, 256);
      pin();
#pragma unroll
      for (int k = 0; k < CH_RB; k++) ldsm4t(&tw[4 * k], wq + k * 2048);
      if (t4 < 2) {
#pragma unroll
        for (int k = CH_RB; k < CH_RC; k++) ldsm4t(&tw[4 * k], wq + k * 2048);
        const int q = t4 ? 3 : j, o = t4 ? j * 896 : 0;
        const uint8_t* src = p.pool + ((80 + st * 4 + q) * 8192 + (pages >> (st * 4 + q) & 1) * 4096 + o);
        asm volatile("bar.sync 8, 256;" ::: "memory");
        const uint32_t t1 = clk32() + CH_D2;
        if (CH_EX == 1) publish_v(s, v, vm);
        auto fetch = [&](auto n) {
          mbar_wait(bH, s & 1);
          until(t1);
          TR(4, clk32());
          if (elect())
            asm volatile("cp.async.bulk.shared::cluster.global.mbarrier::complete_tx::bytes.multicast::cluster [%0], [%1], %2, [%3], 7;"
                         :: "r"(sb + CH_M + q * 2560 + o), "l"(src), "n"(n.value), "r"(bG + q * 8) : "memory");
        };
        if (!t4) fetch(Int<2560>()); else if (j == 2) fetch(Int<768>()); else fetch(Int<896>());
      } else {
        asm volatile("bar.sync 8, 256; " ::: "memory");
        if (elect()) asm volatile("mbarrier.arrive.relaxed.cluster.shared::cluster.b64 _, [%0];" :: "r"(bH + (t4 == 2 ? r1 : r2)) : "memory");
        pin();
        if (CH_EX == 1) publish_v(s, v, vm);
#pragma unroll
        for (int k = CH_RB; k < CH_RC; k++) ldsm4t(&tw[4 * k], wq + k * 2048);
      }
      TM(9);
      pin();
#pragma unroll
      for (int k = CH_RC; k < CH_TW; k++) ldsm4t(&tw[4 * k], wq + k * 2048);
      if (CH_KP == 2 && t4 == CH_KW) { bar_sync(7, 160); publish_k(s + 1); }
      TM(10);
    }
    if (++st == 3) st = 0;
    tag ^= 0x10001;
  }
}

__global__ void __launch_bounds__(256, 1) chain_kernel(const __grid_constant__ ChainParams p) {
  extern __shared__ __align__(1024) uint8_t smem_raw[];
  const uint32_t sb = s2u(smem_raw);
  const int tid = threadIdx.x, warp = __shfl_sync(~0u, tid >> 5, 0), lane = tid & 31;
  const int cta = blockIdx.x, h = cta / 3, j = cta - 3 * h, colbase = cta * 64;
  const uint32_t bWo = sb + CH_BAR, bWq = bWo + 8, bXA = bWo + 24, bWk = bWo + 80, bWv = bWo + 88;
  uint32_t smid; asm("mov.u32 %0, %%smid;" : "=r"(smid));
  PRO(0);
  if (sb != mapa(CH_BASE, j)) __trap();
  uint32_t entry = 0;
  auto place = [&]() {
    const int i = tid - 128;
    if (i >= 0 && i <= NSLOT) {
      const uint32_t side = ldg_strong32(g_smpart + (smid & 255));
      if (i < NSLOT) {
        entry = i * 8192 + (ldg_strong32(g_orient + i) == (i < 80 ? i & 1 : side) ? 0 : 4096);
      } else {
        entry = 2 * (atomicAdd(g_bo + p.layer * 128 + 1, 1 << 8 * side) >> 8 * side & 255) + side;
      }
    }
    __syncwarp();
  };
  if (p.layer) place();
  if (warp == 0 && elect()) {
#pragma unroll 1
    for (int i = 0; i < 17; i++) mbar_init(bWo + 8 * i, i == 2 || i == 5 ? 5 : i == 3 || i == 4 ? 4 : i == 12 ? 2 : 1);
    asm volatile("fence.mbarrier_init.release.cluster;" ::: "memory");
    mbar_expect(bWk, 81920);
    tma_load3<(WEF & 1) != 0>(sb + CH_WQ, &p.wk, colbase, 0, bWk);
    mbar_expect(bWv, 81920);
    tma_load3<(WEF & 1) != 0>(sb + CH_WO, &p.wv, colbase, 0, bWv);
    mbar_expect(bWo + 16, 1536);
    mbar_expect(bWo + 40, 2048);
    mbar_expect(bWo, 86016); mbar_expect(bWq, 81920);
#pragma unroll 1
    for (int i = 0; i < 8; i++) mbar_expect(bXA + 8 * (i & 1), 5120);
  }
  if (warp == 1) {
    const uint32_t id = (lane >> 3) == (lane & 3) ? ((lane & 4) ? 0x3f800000u : 0x00003f80u) : 0u;
    sts128(sb + CH_ID + lane * 16, make_uint4(id, 0, 0, id));
  }
  __syncthreads();
  asm volatile("barrier.cluster.arrive.relaxed.aligned;" ::: "memory");
  uint32_t ak[80], av[80];
  const uint32_t wq = opaque(sb + CH_WQ + ((warp >> 2) * 320 + (lane & 7) + (lane >> 4) * 8) * 128 + (((2 * (warp & 3) + ((lane >> 3) & 1)) ^ (lane & 7)) << 4));
  pdl_wait();
  if (tid == 32) stg_strong32(g_smuse + (smid & 255), p.layer + 1);
  pdl_launch();
  PRO(1);
  if (warp == 0 && elect()) {
    bulk_load(sb + CH_X + 20480, p.xc + 5120, 20480, bXA);
    bulk_load(sb + CH_X, p.xc, 20480, bXA + 8);
  }
  if (!p.layer) place();
  __syncwarp();
  PRO(2);
  mbar_wait(bWk, 0);
  PRO(3);
#pragma unroll
  for (int k = 0; k < 20; k++) ldsm4t(&ak[4 * k], wq + k * 2048);
  bar_sync(6, 256);
  if (warp == 0 && elect()) tma_load3<(WEF & 2) != 0>(sb + CH_WQ, &p.wq, colbase, 0, bWq);
  __syncwarp();
  PRO(4);
  mbar_wait(bWv, 0);
  PRO(5);
#pragma unroll
  for (int k = 0; k < 20; k++) ldsm4t(&av[4 * k], wq + CH_WO + k * 2048);
  bar_sync(6, 256);
  PRO(6);
  if (warp >= 5 && elect()) tma_load3<(WEF & 2) != 0>(sb + CH_WO + (warp - 5) * 28672, &p.wo, j == 0 ? 0 : 32 + j * 192, h * 192 + (j + 8 - warp) % 3 * 64, bWo);
  if (tid == 128 + NSLOT && entry >= 80) {
    uint32_t c;
    int n = 0;
    do { c = ldg_strong32(g_bo + p.layer * 128 + 1); spin_guard(n); } while ((c & 255) + (c >> 8) < 96);
    const uint32_t other = (c >> 8 * (~entry & 1) & 255) + (entry >> 1) - 40;
    entry = other < 40 ? 2 * other + (~entry & 1) : entry % 80;
  }
  if (tid >= 128 && tid <= 128 + NSLOT) sts32(sb + CH_O + (tid - 128) * 4, entry);
  PRO(7);
  __syncthreads();
  if (__shfl_sync(~0u, tid >> 7, 0) == 0) chain_body<0>(p, wq, ak, av); else chain_body<1>(p, wq, ak, av);
}

struct PostParams { CUtensorMap wq, wo, wb, wo2, wb2; int gap, share, layer, look, gap2, pol; };
constexpr int PS = 8, PB = 28672;
constexpr int OP_SMEM = PS * PB + 512 + 2048;
enum { IT_ATT = 0, IT_OP = 1, IT_FIN = 2, IT_BQ = 3, IT_Q = 4 };

__device__ __forceinline__ uint32_t item_count(int type, int b) {
  return type == IT_ATT ? 32 : type == IT_OP ? op_split(b) * (b < OP_160 ? 2 : 4) : type == IT_FIN ? fin_items(b) : b < BQ_160 ? 6 : b < BQ_80 ? 12 : 24; }
__device__ __forceinline__ uint32_t item_need(int type, int b) { return type == IT_ATT ? 96 : item_count(type - 1, b); }

struct Ring {
  uint32_t sb, bars; int st; uint32_t ph;
  __device__ __forceinline__ uint32_t wait() const { mbar_wait(bars + 8 * st, ph); return sb + st * PB; }
  __device__ __forceinline__ void next() { if (++st == PS) { st = 0; ph ^= 1; } }
  __device__ __forceinline__ void release(int s) const { if ((threadIdx.x & 31) == 0) mbar_arrive(bars + 8 * (PS + s)); }
  __device__ __forceinline__ void pop() { __syncwarp(); release(st); next(); }
};

template <int N>
__device__ __forceinline__ void gemm_item(Ring& r, float* d, int nst, uint32_t go, int go_at) {
  int prev = 0;
#pragma unroll 1
  for (int kb = 0; kb < nst; kb++) {
    const uint32_t base = r.wait();
    const uint64_t da = mkdesc(base + (threadIdx.x >> 7) * 4096, 128, 512, 0), db = mkdesc(base + 8192, 4096, 1024, 1);
    wg_fence();
#pragma unroll
    for (int kk = 0; kk < 2; kk++) {
      if (N == 80) wg_ss80_01(d, da + kk * 16, db + kk * 128, (kb | kk) != 0);
      if (N == 160) wg_ss160_01(d, da + kk * 16, db + kk * 128, (kb | kk) != 0);
      if (N >= 192) wg_ss192_01(d, da + kk * 16, db + kk * 128, (kb | kk) != 0);
      if (N == 320) wg_ss128_01(d + 96, da + kk * 16, db + kk * 128 + 3 * 256, (kb | kk) != 0);
    }
    wg_commit();
    if (kb == go_at && threadIdx.x == 0) mbar_arrive(go);
    if (kb > 0) { wg_wait<1>(); r.release(prev); }
    prev = r.st;
    r.next();
  }
  wg_wait<0>();
  reg_fence<N / 2>(d);
  r.release(prev);
}

template <int HALF>
__device__ __forceinline__ void attn_a_warp(Ring& r, const uint32_t (&q)[48], int b, int h) {
  constexpr int NT = HALF ? 5 : 3, NF = 8 * NT;
  const int lane = threadIdx.x & 31, g = lane >> 2, c = lane & 3, seg = (threadIdx.x >> 5) & 3;
  uint32_t f[6][NF];
  int slot[6];
  auto fetch = [&](int u) {
    const uint32_t kv = r.wait() + seg * KV_BYTES;
    slot[u] = r.st;
    r.next();
#pragma unroll
    for (int w = 0; w < 4; w++) {
      uint32_t* d = &f[u][2 * NT * w];
#pragma unroll
      for (int t = 0; t <= HALF; t++) {
        if (u < 3) {
          ldsm4(d + 4 * t, kv + w * 1024 + t * 512 + (lane & 8) * 32 + (lane & 16) * 8 + (lane & 7) * 16);
        } else {
          const uint4 v = lds128(kv + w * 1024 + t * 512 + lane * 16);
          d[4 * t] = v.x; d[4 * t + 1] = v.y; d[4 * t + 2] = v.z; d[4 * t + 3] = v.w;
        }
      }
      const uint2 m = lds64(kv + KV_M + w * 256 + lane * 8);
      d[2 * NT - 2] = m.x; d[2 * NT - 1] = m.y;
    }
    pdl_launch();
  };
  float s[NT][4] = {};
  fetch(0);
#pragma unroll
  for (int u = 0; u < 3; u++) {
    fetch(u + 1);
#pragma unroll
    for (int kk = 0; kk < 4; kk++) {
      const uint32_t* a = &q[16 * u + 4 * kk];
#pragma unroll
      for (int n = 0; n < NT; n++) mma16(s[(n + 1) % NT], a[0], a[1], a[2], a[3], f[u][2 * NT * kk + 2 * n], f[u][2 * NT * kk + 2 * n + 1]);
    }
    r.release(slot[u]);
    pdl_launch();
  }
  fetch(4);
  const float k2 = 0.07216878364870322f * 1.44269504089f, NEG = -INFINITY;
  if (2 * c > g) { s[NT - 2][0] = NEG; s[NT - 1][2] = NEG; }
  if (2 * c + 1 > g) { s[NT - 2][1] = NEG; s[NT - 1][3] = NEG; }
  s[NT - 1][0] = s[NT - 1][1] = NEG;
  uint32_t pp[NT][2]; float inv[2];
#pragma unroll
  for (int hh = 0; hh < 2; hh++) {
    float m = NEG, l = 0.f;
#pragma unroll
    for (int n = 0; n < NT; n++) m = fmaxf(m, fmaxf(s[n][2 * hh], s[n][2 * hh + 1]));
    m = fmaxf(m, __shfl_xor_sync(~0u, m, 1)); m = fmaxf(m, __shfl_xor_sync(~0u, m, 2));
#pragma unroll
    for (int n = 0; n < NT; n++) { const float x = ex2((s[n][2 * hh] - m) * k2), y = ex2((s[n][2 * hh + 1] - m) * k2); l += x + y; pp[n][hh] = pack2(x, y); }
    l += __shfl_xor_sync(~0u, l, 1); l += __shfl_xor_sync(~0u, l, 2);
    asm("rcp.approx.ftz.f32 %0, %1;" : "=f"(inv[hh]) : "f"(l));
  }
  uint32_t* dst = g_o + ((b * 192 + h * 6) * 16 + seg * 4 + HALF * 2) * 128 + lane;
#pragma unroll
  for (int u = 3; u < 6; u++) {
    float o[8][4] = {};
#pragma unroll
    for (int n = 0; n < 8; n++) mma8(o[n], pp[0][0], pp[0][1], f[u][2 * NT * (n >> 1) + 2 * NT - 2 + (n & 1)]);
#pragma unroll
    for (int t = 0; t <= HALF; t++)
#pragma unroll
      for (int n = 0; n < 8; n++) {
        const uint32_t* v = &f[u][2 * NT * (n >> 1) + 4 * t + 2 * (n & 1)];
        mma16(o[n], pp[1 + 2 * t][0], pp[1 + 2 * t][1], pp[2 + 2 * t][0], pp[2 + 2 * t][1], v[0], v[1]);
      }
    r.release(slot[u]);
    if (u == 3) fetch(5);
#pragma unroll
    for (int n = 0; n < 8; n++) {
      dst[(u - 3) * 4096 + (n >> 2) * 2048 + (n & 3) * 32] = pack2(o[n][0] * inv[0], o[n][1] * inv[0]);
      dst[(u - 3) * 4096 + (n >> 2) * 2048 + (n & 3) * 32 + 128] = pack2(o[n][2] * inv[1], o[n][3] * inv[1]);
    }
  }
}

template <int NG>
__device__ __forceinline__ void fin_item(Ring& r, uint32_t scratch, int b, int idx) {
  const int warp = threadIdx.x >> 5, lane = threadIdx.x & 31;
  float4* x = g_x + ((b * 16 + idx * NG) * 40 + warp * 5) * 32 + lane;
  float4 v[NG][5];
#pragma unroll
  for (int g = 0; g < NG; g++) {
    const uint32_t base = r.wait();
#pragma unroll
    for (int i = 0; i < 5; i++) v[g][i] = lds128f(base + ((warp * 5 + i) * 32 + lane) * 16);
    r.pop();
  }
#pragma unroll 1
  for (int k = 0; k < op_split(b); k += NG == 1 ? 2 : 1) {
#pragma unroll
    for (int g = 0; g < NG; g += 2) {
      const uint32_t base = r.wait();
#pragma unroll
      for (int i = 0; i < 10; i++) {
        const uint2 q = lds64(base + ((i / 5 * 40 + warp * 5 + i % 5) * 32 + lane) * 8);
        float4& t = v[(g + i / 5) % NG][i % 5];
        t.x += bf_lo(q.x); t.y += bf_hi(q.x); t.z += bf_lo(q.y); t.w += bf_hi(q.y);
      }
      r.pop();
    }
  }
  float mean[NG], rs[NG];
  ln_stats<NG>(v, scratch, mean, rs);
#pragma unroll
  for (int i = 0; i < 5; i++) {
    const int u = warp * 5 + i;
    uint32_t* xn = g_xn + ((b * 20 + (u >> 1)) * 16 + idx * NG) * 128 + (u & 1) * 64 + lane;
#pragma unroll
    for (int g = 0; g < NG; g++) {
      xn[g * 128] = pack2((v[g][i].x - mean[g]) * rs[g], (v[g][i].y - mean[g]) * rs[g]);
      xn[g * 128 + 32] = pack2((v[g][i].z - mean[g]) * rs[g], (v[g][i].w - mean[g]) * rs[g]);
    }
  }
#pragma unroll
  for (int g = 0; g < NG; g++)
#pragma unroll
    for (int i = 0; i < 5; i++) x[(g * 40 + i) * 32] = v[g][i];
}

__global__ void __launch_bounds__(384, 1) post_kernel(const __grid_constant__ PostParams p) {
  extern __shared__ __align__(1024) uint8_t smem_raw[];
  const uint32_t sb = s2u(smem_raw), bars = sb + PS * PB;
  const uint32_t bIF = bars + 128, bIE = bars + 160, done = bars + 192, bGo = bars + 224, slots = bars + 240, scratch = bars + 512;
  const int warp = __shfl_sync(~0u, threadIdx.x >> 5, 0), lane = threadIdx.x & 31;
  TRACE(0);
  pdl_launch();
  if (sb & 1023) __trap();
  if (threadIdx.x < 29) mbar_init(bars + 8 * threadIdx.x, threadIdx.x < 8 ? 1 : threadIdx.x < 16 ? 8 : threadIdx.x < 20 ? 1 : threadIdx.x < 24 ? 2 : threadIdx.x < 28 ? 8 : 1);
  if (threadIdx.x == 32) sts32(slots + 16, p.gap);
  fence_async();
  __syncthreads();
  if (warp >= 8) {
    asm volatile("setmaxnreg.dec.sync.aligned.u32 56;");
    if (warp == 9) {
      const int b = lane & 15;
      bool queries = QA_END < 16 && blockIdx.x < 36;
      for (int n = 0;; n++) {
        if (n > 0) mbar_wait(bGo, (n - 1) & 1);
        mbar_wait(bIE + 8 * (n & 3), ((n >> 2) & 1) ^ 1);
        int code = -1, spin = 0, ticket = 0;
        if (queries) {
          if (lane == 0) ticket = n == 0 ? blockIdx.x : 36 + atomicAdd(g_sync + SY_QC, 1);
          ticket = __shfl_sync(~0u, ticket, 0);
          queries = ticket < (16 - QA_END) * 32;
          if (queries) code = IT_Q << 16 | (QA_END + ticket % (16 - QA_END)) << 8 | ticket / (16 - QA_END);
        }
        if (!queries && lane == 0) asm volatile("atom.relaxed.gpu.global.add.u32 %0, [%1], 1;" : "=r"(ticket) : "l"(g_sync + SY_T) : "memory");
        while (!queries) {
          const uint4 hd = ldg_strong128(g_sync + b * 8), pr = ldg_strong128(g_sync + b * 8 + 4);
          const uint32_t hv[4] = {hd.x, hd.y, hd.z, hd.w}, pv[4] = {pr.x, pr.y, pr.z, pr.w};
          const uint32_t chain_done = __ballot_sync(~0u, (pr.x & 0xffff) >= 96) & 0xffff;
          int left[4], avail[4], rdy = 0, claimed = 0, upstream = 0;
#pragma unroll
          for (int t = 0; t < 4; t++) {
            const int cnt = lane < 16 ? item_count(t, b) : 0;
            left[t] = max(cnt - (int)hv[t], 0);
            claimed += cnt - left[t];
            const bool ready = (pv[t] & 0xffff) >= item_need(t, b);
            rdy |= ready << t;
            bool ok = ready || (t == IT_ATT ? pr.x >= 0x10000 : !upstream || (t == IT_OP && (chain_done >> 15 & 1)));
            if (t == IT_BQ && (chain_done >> BQ_HOLD & 1) && !(chain_done >> 15)) ok = false;
            avail[t] = ok ? left[t] : 0;
            upstream |= __any_sync(~0u, left[t] > 0);
          }
          if (!upstream) break;
          int rank = max(__shfl_sync(~0u, ticket, 0) - __reduce_add_sync(~0u, claimed), 0), type = -1, mine = 0;
#pragma unroll
          for (int c = 0; c < 8; c++) {
            const int t = c == PR_FIN || c == 5 ? IT_FIN : c == PR_ATT || c == 7 ? IT_ATT : c == PR_OP || c == 4 ? IT_OP : IT_BQ;
            int a = c == PR_ATT || ((rdy >> t & 1) == (c < 4)) ? avail[t] : 0;
            if (t == IT_OP && OP_EARLY) a = c == PR_OP ? avail[t] : 0;
            if (c == 7) a = b < QA_END && !(rdy & 1) && ((chain_done << 1 | 1) >> b & 1) ? left[t] : 0;
            const int tot = __reduce_add_sync(~0u, a);
            if (type < 0) { if (rank < tot) { type = t; mine = a; } else rank -= tot; }
          }
          if (type >= 0) {
#pragma unroll
            for (int o = 1; o < 16; o <<= 1) { const int y = __shfl_up_sync(~0u, mine, o); if (lane >= o) mine += y; }
            const int blk = __ffs(__ballot_sync(~0u, mine > rank)) - 1;
            const int early = !(__shfl_sync(~0u, rdy, blk) >> type & 1);
            uint32_t idx = 0;
            if (lane == 0) asm volatile("atom.relaxed.gpu.global.add.u32 %0, [%1], 1;" : "=r"(idx) : "l"(g_sync + blk * 8 + type) : "memory");
            ld_acquire(g_sync + blk * 8 + 4 + type);
            idx = __shfl_sync(~0u, idx, 0);
            if (idx < item_count(type, blk)) { code = (chain_done >> 15 & 1) << 22 | (chain_done >> p.look & 1) << 21 | early << 20 | type << 16 | blk << 8 | idx; break; }
          } else {
            __nanosleep(50);
          }
          spin_guard(spin);
        }
        if (lane == 0) {
          fence_async_global();
          sts32(slots + 4 * (n & 3), code);
          mbar_arrive(bIF + 8 * (n & 3));
        }
        __syncwarp();
        if (code < 0) break;
      }
    } else if (warp == 8) {
      if (elect()) {
        uint32_t dst = sb, bar = bars, ph = 1, next = clk32(), gap = 0;
        auto acquire = [&](uint32_t kb) {
          mbar_wait(bar + 8 * PS, ph);
          mbar_expect(bar, kb * 1024);
          if (gap) {
            uint32_t now;
            do now = clk32(); while ((int)(now - next) < 0);
            next = ((int)(now - next) > 100 ? now - 100 : next) + kb * gap;
          }
        };
        auto advance = [&]() { dst += PB; bar += 8; if (dst == bars) { dst = sb; bar = bars; ph ^= 1; } };
        auto depend = [&](const uint32_t* c, uint32_t need) { wait_count(c, need); fence_async_global(); };
#pragma unroll 1
        for (int n = 0;; n++) {
          mbar_wait(bIF + 8 * (n & 3), (n >> 2) & 1);
          const int code = (int)lds32(slots + 4 * (n & 3));
          if (code < 0) break;
          const int type = (code >> 16) & 15, b = (code >> 8) & 255, idx = code & 255;
          const bool early = code >> 20 & 1, go = !(code >> 21 & 1);
          mbar_arrive(bIE + 8 * (n & 3));
          gap = !(code >> 22 & 1) ? lds32(slots + 16) : type == IT_ATT || type == IT_FIN ? 0 : p.gap2;
          const uint32_t* progress = g_sync + b * 8 + 4 + type;
          if (type == IT_ATT && b >= QA_END) {
            depend(g_sync + SY_Q, (16 - QA_END) * 32);
#pragma unroll 1
            for (int u = 0; u < 2; u++) { acquire(24); bulk_load_last(dst, g_q + (((b - QA_END) * 32 + idx) * 2 + u) * 1536, 24576, bar); advance(); }
          } else if (type == IT_FIN) {
            const int ng = 16 / fin_items(b), lg = ng >> 1;
#pragma unroll 1
            for (int g = 0; g < ng; g++) { acquire(20); bulk_load(dst, g_x + (b * 16 + idx * ng + g) * 1280, 20480, bar); advance(); }
            if (early) depend(progress, item_need(type, b));
            if (go) mbar_arrive(bGo);
#pragma unroll 1
            for (int i = 0; i < op_split(b) * ng; i += 2) {
              const uint2* src = g_part + ((b * 16 + (i >> lg)) * 16 + idx * ng + (i & (ng - 1))) * 1280;
              acquire(20);
              bulk_load_last(dst, src, ng > 1 ? 20480 : 10240, bar);
              if (ng == 1) bulk_load_last(dst + 10240, src + 16 * 1280, 10240, bar);
              advance();
            }
            if (!go && p.pol) mbar_arrive(bGo);
          } else {
            const bool op = type == IT_OP, bq = type == IT_BQ;
            const int width = op ? op_width(b) : bq ? bq_width(b) : 192, nb = (width + 63) >> 6, lt = width == 320 ? 1 : 2;
            const int nst = op ? 192 / op_split(b) : 20, kb0 = op ? (idx >> lt) * nst : 0;
            const int col = (op ? idx & ((1 << lt) - 1) : idx) * width;
            const bool whole = !(width & 63);
            const CUtensorMap* m = op ? (whole ? &p.wo : &p.wo2) : bq ? (whole ? &p.wb : &p.wb2) : &p.wq;
            const uint32_t* a = op ? g_o + (b * 192 + kb0) * 2048 : g_xn + b * 20 * 2048;
            int row = kb0 * 32, pre = early && (op || bq) ? min(nst, PRE_MAX) : 0;
            auto weights = [&]() {
              acquire(8 + nb * 4);
              if (whole) {
                tma_load3z(dst + 8192, m, row, col >> 6, bar);
              } else {
                tma_load(dst + 8192, m, col, row, bar); tma_load(dst + 12288, m, col + 64, row, bar);
                if (nb == 3) tma_load(dst + 16384, m, col + 128, row, bar);
              }
              row += 32;
            };
            if (pre) {
              uint32_t da = dst, ba = bar;
              const uint32_t g0 = gap;
              gap = max(gap, PRE_GAP);
#pragma unroll 1
              for (int kb = 0; kb < pre; kb++) { weights(); advance(); }
              gap = g0;
              depend(progress, item_need(type, b));
#pragma unroll 1
              for (int kb = 0; kb < pre; kb++) {
                bulk_load(da, a, 8192, ba);
                a += 2048; da += PB; ba += 8;
                if (da == bars) { da = sb; ba = bars; }
              }
            }
#pragma unroll 1
            for (int kb = pre; kb < nst; kb++) { weights(); if (op && OEF) bulk_load_last(dst, a, 8192, bar); else bulk_load(dst, a, 8192, bar); a += 2048; advance(); }
          }
          if (type == IT_ATT) {
            if (early) depend(progress, 96);
            if (go) mbar_arrive(bGo);
            const uint8_t* src = g_kv + (size_t)(idx * 6 * NSEG + b * 4) * KV_BYTES;
#pragma unroll 1
            for (int u = 0; u < 6; u++) {
              acquire(20);
              bulk_load_last(dst, src, 20480, bar);
              src += u == 2 ? -3 * KV_V : 2 * KV_V;
              advance();
            }
            if (!go && p.pol && ATT_LOOK) mbar_arrive(bGo);
            if (Q_PF && b + Q_PF >= QA_END && b + Q_PF < 16)
              asm volatile("cp.async.bulk.prefetch.L2.global [%0], 49152;" :: "l"(g_q + ((b + Q_PF - QA_END) * 32 + idx) * 3072) : "memory");
          }
        }
      }
    } else if (warp == 11) {
      uint32_t smid, nsm, used = 0;
      asm("mov.u32 %0, %%smid;" : "=r"(smid)); asm("mov.u32 %0, %%nsmid;" : "=r"(nsm));
      for (int n = 0; n < 64 && used < 96; n++) {
        uint32_t peers = 0;
        used = 0;
        for (uint32_t i = lane; i < min(nsm, 256u); i += 32) {
          const bool taken = ldg_strong32(g_smuse + i) == p.layer + 1;
          used += taken;
          peers += abs((int)(g_smclk[i] - g_smclk[smid & 255])) < 4000 && !taken;
        }
        used = __reduce_add_sync(~0u, used);
        sts32(slots + 16, max(p.gap, (int)min(__reduce_add_sync(~0u, peers), 18u) * p.share >> 3));
      }
    } else if (warp == 10 && lane == 0) {
      for (int n = 0;; n++) {
        mbar_wait(bIF + 8 * (n & 3), (n >> 2) & 1);
        const int code = (int)lds32(slots + 4 * (n & 3));
        if (code < 0) break;
        const int type = (code >> 16) & 15, b = (code >> 8) & 255;
        mbar_wait(done + 8 * (n & 3), (n >> 2) & 1);
        if (type != IT_BQ) red_release(type == IT_Q ? g_sync + SY_Q : g_sync + b * 8 + 5 + type, 1);
        mbar_arrive(bIE + 8 * (n & 3));
      }
    }
  } else {
    asm volatile("setmaxnreg.inc.sync.aligned.u32 224;");
    const int g = lane >> 2, c = lane & 3;
    Ring r = {sb, bars, 0, 0};
#pragma unroll 1
    for (int n = 0;; n++) {
      mbar_wait(bIF + 8 * (n & 3), (n >> 2) & 1);
      const int code = __shfl_sync(~0u, (int)lds32(slots + 4 * (n & 3)), 0);
      if (code < 0) { TRACE(2); break; }
      const int type = (code >> 16) & 15, b = (code >> 8) & 255, idx = code & 255;
      ITEM(code & 0xfffff, 0);
      if (type == IT_ATT || type == IT_Q) {
        uint32_t q[48];
        if (type == IT_Q || b < QA_END) {
          float d[96] = {};
          reg_fence<96>(d);
          gemm_item<192>(r, d, 20, bGo, type == IT_Q ? 12 : -1);
#pragma unroll
          for (int i = 0; i < 48; i++) q[i] = pack2(d[2 * i], d[2 * i + 1]);
        } else {
#pragma unroll
          for (int u = 0; u < 2; u++) {
            const uint32_t base = r.wait() + threadIdx.x * 16;
#pragma unroll
            for (int i = 0; i < 6; i++) {
              const uint4 v = lds128(base + i * 4096);
              q[24 * u + 4 * i] = v.x; q[24 * u + 4 * i + 1] = v.y; q[24 * u + 4 * i + 2] = v.z; q[24 * u + 4 * i + 3] = v.w;
            }
            r.pop();
          }
        }
        if (type == IT_Q) {
          uint4* dst = g_q + ((b - QA_END) * 32 + idx) * 3072 + threadIdx.x;
#pragma unroll
          for (int i = 0; i < 12; i++) dst[i * 256] = make_uint4(q[4 * i], q[4 * i + 1], q[4 * i + 2], q[4 * i + 3]);
        } else if (warp < 4) {
          attn_a_warp<0>(r, q, b, idx);
        } else {
          attn_a_warp<1>(r, q, b, idx);
        }
      } else if (type == IT_FIN) {
        if (FIN_8 > 0 && fin_items(b) == 4) fin_item<4>(r, scratch, b, idx);
        else if (FIN_16 > FIN_8 && (FIN_16 == 16 || fin_items(b) == 8)) fin_item<2>(r, scratch, b, idx);
        else fin_item<1>(r, scratch, b, idx);
      } else {
        float d[160] = {};
        reg_fence<160>(d);
        const int width = type == IT_OP ? op_width(b) : bq_width(b), nst = type == IT_OP ? 192 / op_split(b) : 20;
        const int go_at = max(nst - (code >> 21 & 1 ? p.pol : 6), 0);
        if (width == 320) gemm_item<320>(r, d, nst, bGo, go_at);
        else if (width == 160 || BQ_80 == 16) gemm_item<160>(r, d, nst, bGo, go_at);
        else gemm_item<80>(r, d, nst, bGo, go_at);
        reg_fence<160>(d);
        if (type == IT_OP) {
          const int tiles = DM / width;
          uint2* dst = g_part + (((b * 16 + idx / tiles) * 16 + warp * 2) * 40 + idx % tiles * (width / 16)) * 32 + lane;
#pragma unroll
          for (int u = 0; u < 20; u++) {
            if (u % 5 == 0 && u * 16 >= width) break;
            dst[u * 32] = make_uint2(pack2(d[8 * u], d[8 * u + 1]), pack2(d[8 * u + 4], d[8 * u + 5]));
            dst[(40 + u) * 32] = make_uint2(pack2(d[8 * u + 2], d[8 * u + 3]), pack2(d[8 * u + 6], d[8 * u + 7]));
          }
        } else {
          const int row = b * 128 + warp * 16 + g;
          const int h0 = idx * (width / 20);
          const float sc = h0 < 32 ? 0.22360679775f * 1.44269504089f : 1.f;
          const bool lo = c < 2;
          uint32_t* da = g_bqkv + (h0 * 256 + (row >> 3)) * 96 + lane;
          uint32_t* db = da + 256 * 96 + (lo ? 2 : -2);
          uint32_t pad[2];
#pragma unroll
          for (int rr = 0; rr < 2; rr++) pad[rr] = c & 1 || h0 < 32 ? 0u : h0 >= 64 ? 0x00003f80u : poly_group((row >> 3) + rr) ? 0x3f803f80u : 0u;
#pragma unroll
          for (int q = 0; q < 8; q++) {
            if (!(q & 1) && q * 40 >= width) break;
#pragma unroll
            for (int rr = 0; rr < 2; rr++) {
              uint32_t w[5];
#pragma unroll
              for (int i = 0; i < 5; i++) w[i] = pack2(d[20 * q + 4 * i + 2 * rr] * sc, d[20 * q + 4 * i + 2 * rr + 1] * sc);
              const int o = q * 2 * 256 * 96 + rr * 96;
              da[o] = w[0]; da[o + 32] = w[1]; da[o + 64] = lo ? w[2] : pad[rr];
              db[o] = lo ? w[3] : w[2]; db[o + 32] = lo ? w[4] : w[3]; db[o + 64] = lo ? pad[rr] : w[4];
            }
          }
        }
      }
      __syncwarp();
      if (lane == 0) mbar_arrive(done + 8 * (n & 3));
      if ((code >> 21 & 1) && (p.pol == 0 || (type == IT_ATT && !ATT_LOOK)) && threadIdx.x == 128) mbar_arrive(bGo);
      ITEM(code & 0xfffff, 1);
    }
  }
}

constexpr int AB_SMEM = 1024 + 98304 + 51200 + 4 * 16384 + 256 + 10240;
#define AB_LW 1
#define AB_U 8
#define AB_WG 4
constexpr int AB_T = AB_WG * 128, AB_PASS = 8 / AB_WG;
__device__ __forceinline__ uint32_t fma2(uint32_t a, uint32_t b, uint32_t c) { uint32_t r; asm("fma.rn.bf16x2 %0, %1, %2, %3;" : "=r"(r) : "r"(a), "r"(b), "r"(c)); return r; }
__device__ __forceinline__ uint32_t ex2_pair(float a, float b, uint32_t one, uint32_t c0) {
  const uint32_t e = __byte_perm(__float_as_uint(a), __float_as_uint(b), 0x6521);
  uint32_t x, r;
  asm("lop3.b32 %0, %1, 0x007f007f, %2, 0xEA;" : "=r"(x) : "r"(e), "r"(one));
  const uint32_t m = AB_DEG == 3 ? fma2(fma2(fma2(c0, x, 0xbbdcbbdcu), x, 0x3ef53ef5u), x, 0x3ee83ee8u) : fma2(fma2(c0, x, 0xbc43bc43u), x, 0x3f2e3f2eu);
  asm("lop3.b32 %0, %1, %2, 0x7f807f80, 0xE4;" : "=r"(r) : "r"(e), "r"(m));
  return r;
}
__device__ __forceinline__ float sq2(uint32_t w) { const float a = bf_lo(w), b = bf_hi(w); return fmaf(a, a, b * b); }

__device__ __forceinline__ void attn_b_store(const float* o, int h, int row0, int lane) {
  const int g = lane >> 2, c = lane & 3;
  const float i0 = __frcp_rn(__shfl_sync(~0u, o[8], (lane & ~3) | 2)), i1 = __frcp_rn(__shfl_sync(~0u, o[10], (lane & ~3) | 2));
#pragma unroll
  for (int jj = 0; jj < 3; jj++) {
    if (jj < 2 || c < 2) {
      const int col = h * 20 + 8 * jj + 2 * c;
      uint32_t* dst = g_of + (((row0 >> 7) * 10 + (col >> 6)) * 16 + (row0 >> 3 & 15)) * 256 + (col >> 3 & 7) * 32 + g * 4 + (col >> 1 & 3);
      dst[0] = pack2(o[4 * jj] * i0, o[4 * jj + 1] * i0);
      dst[256] = pack2(o[4 * jj + 2] * i1, o[4 * jj + 3] * i1);
    }
  }
}

struct AbParams { Weights next; uint32_t* done; uint32_t* out; };
__global__ void __launch_bounds__(AB_T + 32, 1) attn_b_kernel(const __grid_constant__ AbParams p) {
  extern __shared__ uint8_t smem_raw[];
  const uint32_t sb = (s2u(smem_raw) + 1023) & ~1023u, sK = sb, sV = sb + 98304, bars = sV + 51200 + 4 * 16384;
  const uint32_t bF = bars + 64, bW = bars + 72, bA = bars + 80, bE = bars + 128, smax = bars + 176;
  auto ring = [&](int i) { return i < 2 ? sK + 51200 + i * 16384 : sV + 51200 + (i - 2) * 16384; };
  const int warp = __shfl_sync(~0u, threadIdx.x >> 5, 0), lane = threadIdx.x & 31;
  const int h = blockIdx.x >> 2, quarter = blockIdx.x & 3;
  TRACE(0);
  pdl_launch();
  if (threadIdx.x < 22) mbar_init(bars + 8 * threadIdx.x, threadIdx.x == 8 ? AB_T / 32 : threadIdx.x >= 16 ? 8 : 1);
  if (threadIdx.x == 32) sts64(smax, 0, 0);
  fence_async();
  __syncthreads();
  pdl_wait();
  const int blk = quarter * 4 + (h >> 3), cg = h & 7;
  auto unsafe = [&]() { const float2 m = lds64f(smax); return !(m.x * m.y <= 10000.f); };
  if (warp == AB_T / 32) {
    auto load_w = [&]() {
      mbar_expect(bW, 102400);
      for (int i = 0; i < 4; i++) bulk_load((i < 2 ? sK : sV) + (i & 1) * 25600, g_wb + cg * 6400 + i * 1600, 25600, bW);
    };
    if (elect()) {
      const uint32_t* gk = g_bqkv + (32 + h) * 256 * 96;
#pragma unroll 1
      for (int i = 0; i < 8; i++) {
        if (i >= AB_LW) mbar_wait(bars + 8 * (i - AB_LW), 0);
        mbar_expect(bars + 8 * i, 24576);
        bulk_load_last(sK + i * 12288, gk + i * 3072, 12288, bars + 8 * i);
        bulk_load_last(sV + i * 12288, gk + 32 * 256 * 96 + i * 3072, 12288, bars + 8 * i);
      }
    }
    __syncwarp();
    if (blockIdx.x < NSLOT) for (int i = lane; i < 512; i += 32) reinterpret_cast<uint4*>(pool_at(blockIdx.x * 8192))[i] = make_uint4(0, 0, 0, 0);
    if (blockIdx.x == 127) for (int i = lane; i < SY_N; i += 32) g_sync[i] = 0;
    if (p.next.w[0] && lane == 0) {
      for (int i = 0; i < AB_PF; i++) { const uint32_t t0 = clk32(); while (clk32() - t0 < (i ? AB_PFD : AB_PF0)) __nanosleep(200); prefetch_weights(p.next, i); }
    }
    __syncwarp();
    mbar_wait(bF, 0);
    const bool redo = unsafe();
    if (!redo && lane == 0) load_w();
    if (lane < 16) asm volatile("cp.async.bulk.prefetch.L2.global [%0], 2560;" :: "l"(g_x + ((blk * 16 + lane) * 40 + cg * 5) * 32) : "memory");
    __syncwarp();
    bar_sync(1, AB_T + 32);
    if (lane == 0) {
      ABT(!!p.out, 1);
      red_release(p.done + quarter * 32, 1);
      ABT(!!p.out, 2);
      if (redo) load_w();
      wait_count(p.done + quarter * 32, 32);
      fence_async_global();
      ABT(!!p.out, 3);
      for (int kb = 0; kb < 10; kb++) {
        const int i = kb < 6 ? kb : kb - 6;
        if (kb >= 6) mbar_wait(bE + 8 * i, 0);
        mbar_expect(bA + 8 * i, 16384);
        bulk_load(ring(i), g_of + (blk * 10 + kb) * 4096, 16384, bA + 8 * i);
      }
    }
    return;
  }
  float qmax = 0.f;
  const uint32_t one = opaque(0x3f803f80u + (threadIdx.x >> 10)), c0 = opaque((AB_DEG == 3 ? 0x3d9f3d9fu : 0x3eac3eacu) + (threadIdx.x >> 10));
#pragma unroll 1
  for (int pass = 0; pass < AB_PASS; pass++) {
    const int row0 = quarter * 512 + ((warp >> 2) * AB_PASS + pass) * 64 + (warp & 3) * 16;
    const uint32_t* gq = g_bqkv + (h * 256 + (row0 >> 3)) * 96 + lane;
    const uint32_t q0 = gq[0], q1 = gq[96], q2 = gq[32], q3 = gq[128];
    uint32_t q4 = gq[64], q5 = gq[160];
    const uint32_t z0 = gq[64 + 3 - (lane & 3)], z1 = gq[160 + 3 - (lane & 3)];
    {
      float n0 = sq2(q0) + sq2(q2) + sq2(q4), n1 = sq2(q1) + sq2(q3) + sq2(q5);
      n0 += __shfl_xor_sync(~0u, n0, 1); n1 += __shfl_xor_sync(~0u, n1, 1);
      n0 += __shfl_xor_sync(~0u, n0, 2); n1 += __shfl_xor_sync(~0u, n1, 2);
      qmax = (n0 > qmax || n0 != n0) ? n0 : qmax;
      qmax = (n1 > qmax || n1 != n1) ? n1 : qmax;
    }
    if (pass == AB_PASS - 1) {
      float kmax = 0.f;
#pragma unroll
      for (int i = 0; i < SEQ / AB_T; i++) {
        const int key = threadIdx.x + AB_T * i;
        const uint32_t a = sK + (key >> 3) * 384 + (key & 7) * 16;
        const uint4 x = lds128(a), y = lds128(a + 128);
        const uint2 z = lds64(a + 256);
        const float n = ((sq2(x.x) + sq2(x.y)) + (sq2(x.z) + sq2(x.w))) + ((sq2(y.x) + sq2(y.y)) + (sq2(y.z) + sq2(y.w))) + (sq2(z.x) + sq2(z.y));
        kmax = (n > kmax || n != n) ? n : kmax;
      }
      const uint32_t kb = __reduce_max_sync(~0u, __float_as_uint(kmax) & 0x7fffffffu), qb = __reduce_max_sync(~0u, __float_as_uint(qmax) & 0x7fffffffu);
      if (lane < 2) asm volatile("red.shared.max.u32 [%0], %1;" :: "r"(smax + 4 * lane), "r"(lane ? kb : qb) : "memory");
      __syncwarp();
    }
    if ((lane & 3) == 2) { q4 = 0xBF8043C0u; q5 = 0xBF8043C0u; }
    float o[12];
    auto desc = [](uint32_t lo, uint32_t hi) { uint64_t d; asm("mov.b64 %0, {%1, %2};" : "=l"(d) : "r"(lo), "r"(hi)); return d; };
    const uint32_t k0 = (uint32_t)mkdesc(sK, 128, 0, 0), k1 = (uint32_t)mkdesc(sK + 256, 0, 0, 0), v0 = (uint32_t)mkdesc(sV, 384, 0, 0);
    float sa[16], sb2[16];
    uint32_t pa[8], pb[8];
    auto qk = [&](float* s, uint32_t t) {
      wg_rs32_00(s, q0, q1, q2, q3, desc(k0 + t, 24), 0);
      wg_rs32_00(s, q4, q5, z0, z1, desc(k1 + t, 24), 1);
      wg_commit();
    };
    auto step = [&](float* s, uint32_t* pp, int g0, uint32_t t, uint32_t nx, int acc) {
      wg_wait<1>();
      reg_fence<16>(s);
#pragma unroll
      for (int i = 0; i < 8; i++) pp[i] = poly_group(g0 + (i >> 1)) ? ex2_pair(s[2 * i], s[2 * i + 1], one, c0) : pack2(ex2(s[2 * i]), ex2(s[2 * i + 1]));
      wg_fence();
      wg_rs24_01(o, pp[0], pp[1], pp[2], pp[3], desc(v0 + t, 8), acc);
      wg_rs24_01(o, pp[4], pp[5], pp[6], pp[7], desc(v0 + t + 48, 8), 1);
      qk(s, nx);
    };
    if (pass == 0) mbar_wait(bars, 0);
    wg_fence();
    qk(sa, 0);
    qk(sb2, 96);
#pragma unroll 1
    for (uint32_t t = 0; t < 64 * 96; t += AB_U * 96) {
      const uint32_t nx = t + AB_U * 96 < 64 * 96 ? t + AB_U * 96 : 0;
      if (pass == AB_PASS - 1 && t == 40 * 96 && lane == 0) mbar_arrive(bF);
#pragma unroll
      for (int u = 0; u < AB_U; u += 2) {
        if (u == AB_U - 2 && pass == 0) mbar_wait(bars + 8 * (nx / 768), 0);
        step(sa, pa, 0, t + u * 96, u + 2 < AB_U ? t + (u + 2) * 96 : nx, u | t);
        step(sb2, pb, 4, t + u * 96 + 96, (u + 2 < AB_U ? t + (u + 2) * 96 : nx) + 96, 1);
      }
    }
    wg_wait<0>();
    reg_fence<12>(o); reg_fence<16>(sa); reg_fence<16>(sb2);
    attn_b_store(o, h, row0, lane);
  }
  mbar_wait(bF, 0);
  if (unsafe())
#pragma unroll 1
  for (int pass = 0; pass < AB_PASS; pass++) {
    const int row0 = quarter * 512 + ((warp >> 2) * AB_PASS + pass) * 64 + (warp & 3) * 16;
    const uint32_t* gq = g_bqkv + (h * 256 + (row0 >> 3)) * 96 + lane;
    const uint32_t q0 = gq[0], q1 = gq[96], q2 = gq[32], q3 = gq[128], q4 = gq[64], q5 = gq[160];
    float o[12];
#pragma unroll
    for (int i = 0; i < 12; i++) o[i] = 0.f;
    float m0 = -INFINITY, m1 = -INFINITY;
#pragma unroll 1
    for (int kt = 0; kt < 32; kt++) {
      float s[32];
      const uint64_t dk = mkdesc(sK + kt * 3072, 128, 384, 0), dk2 = mkdesc(sK + kt * 3072 + 256, 0, 384, 0);
      wg_fence();
      wg_rs64_00(s, q0, q1, q2, q3, dk, 0);
      wg_rs64_00(s, q4, q5, 0, 0, dk2, 1);
      wg_commit();
      wg_wait<0>();
      reg_fence<32>(s); reg_fence<12>(o);
      float n0 = m0, n1 = m1;
#pragma unroll
      for (int jj = 0; jj < 8; jj++) { n0 = fmaxf(n0, fmaxf(s[4 * jj], s[4 * jj + 1])); n1 = fmaxf(n1, fmaxf(s[4 * jj + 2], s[4 * jj + 3])); }
      n0 = fmaxf(n0, __shfl_xor_sync(~0u, n0, 1)); n0 = fmaxf(n0, __shfl_xor_sync(~0u, n0, 2));
      n1 = fmaxf(n1, __shfl_xor_sync(~0u, n1, 1)); n1 = fmaxf(n1, __shfl_xor_sync(~0u, n1, 2));
      const float r0 = ex2(m0 - n0), r1 = ex2(m1 - n1);
      m0 = n0; m1 = n1;
#pragma unroll
      for (int jj = 0; jj < 3; jj++) { o[4 * jj] *= r0; o[4 * jj + 1] *= r0; o[4 * jj + 2] *= r1; o[4 * jj + 3] *= r1; }
      uint32_t pp[16];
#pragma unroll
      for (int jj = 0; jj < 8; jj++) {
        pp[2 * jj] = pack2(ex2(s[4 * jj] - m0), ex2(s[4 * jj + 1] - m0));
        pp[2 * jj + 1] = pack2(ex2(s[4 * jj + 2] - m1), ex2(s[4 * jj + 3] - m1));
      }
      const uint64_t dv = mkdesc(sV + kt * 3072, 384, 128, 0);
      wg_fence();
#pragma unroll
      for (int kk = 0; kk < 4; kk++) wg_rs24_01(o, pp[4 * kk], pp[4 * kk + 1], pp[4 * kk + 2], pp[4 * kk + 3], dv + kk * 48, 1);
      wg_commit();
    }
    wg_wait<0>();
    reg_fence<12>(o);
    attn_b_store(o, h, row0, lane);
  }
  ABT(!!p.out, 0);
  bar_arrive(1, AB_T + 32);
  if (warp >= 12) return;
  const int g = lane >> 2, c = lane & 3;
  const bool live = opaque(threadIdx.x) < 256;
  float d[40] = {};
  float4* x = g_x + ((blk * 16 + warp * 2) * 40 + cg * 5) * 32 + lane;
  if (warp < 8) {
#pragma unroll
  for (int i = 0; i < 10; i++) {
    const int r = i / 5, u = i % 5;
    const float4 t = x[(r * 40 + u) * 32];
    d[8 * u + 2 * r] = t.x; d[8 * u + 2 * r + 1] = t.y; d[8 * u + 4 + 2 * r] = t.z; d[8 * u + 5 + 2 * r] = t.w;
  }
  mbar_wait(bW, 0);
  reg_fence<40>(d);
  ABT(!!p.out, 4);
#pragma unroll 1
  for (int kb = 0; kb < 10; kb++) {
    const int i = kb < 6 ? kb : kb - 6;
    mbar_wait(bA + 8 * i, kb >= 6);
    const uint64_t da = mkdesc(ring(i) + (warp >> 2) * 8192, 128, 1024, 0), db = mkdesc(kb < 5 ? sK + kb * 10240 : sV + (kb - 5) * 10240, 1280, 128, 0);
    wg_fence();
#pragma unroll
    for (int kk = 0; kk < 4; kk++) wg_ss80_01(d, da + kk * 16, db + kk * 160, 1);
    wg_commit();
    if (kb > 0 && kb < 5) { wg_wait<1>(); if (lane == 0) mbar_arrive(bE + 8 * (kb - 1)); }
  }
  wg_wait<0>();
  reg_fence<40>(d);
  }
  ABT(!!p.out, 5);
  if (p.out) {
    if (warp >= 8) return;
    const uint32_t stage = sK + 83968 + warp * 2560 + (warp < 4 ? 0 : 131328 - 10240);
#pragma unroll
    for (int u = 0; u < 5; u++)
      stsm4(stage + (lane & 15) * 160 + u * 32 + (lane >> 4) * 16, pack2(d[8 * u], d[8 * u + 1]), pack2(d[8 * u + 2], d[8 * u + 3]),
            pack2(d[8 * u + 4], d[8 * u + 5]), pack2(d[8 * u + 6], d[8 * u + 7]));
    __syncwarp();
    uint4* out = reinterpret_cast<uint4*>(p.out + (blk * 128 + warp * 16) * (DM / 2) + cg * 40);
#pragma unroll
    for (int i = 0; i < 5; i++) { const int e = i * 32 + lane, r = e / 10; out[r * (DM / 8) + e - r * 10] = lds128(stage + e * 16); }
  } else {
    float2* stat = g_stat + blk * 1024 + (warp & 7) * 16 + g;
    float mean[2], rs[2];
#pragma unroll
    for (int r = 0; r < 2; r++) {
      float t = 0.f, q = 0.f;
#pragma unroll
      for (int i = 0; i < 10; i++) t += d[4 * i + 2 * r] + d[4 * i + 2 * r + 1];
      t += __shfl_xor_sync(~0u, t, 1); t += __shfl_xor_sync(~0u, t, 2);
      t *= 1.f / 80;
#pragma unroll
      for (int i = 0; i < 10; i++) { const float a = d[4 * i + 2 * r] - t, b = d[4 * i + 2 * r + 1] - t; q += a * a + b * b; }
      q += __shfl_xor_sync(~0u, q, 1); q += __shfl_xor_sync(~0u, q, 2);
      if (c == r && live) asm volatile("st.relaxed.gpu.global.v2.b32 [%0], {%1, %2};" :: "l"(stat + cg * 128 + r * 8), "r"(__float_as_uint(t)), "r"(nz(__float_as_uint(q))) : "memory");
    }
#pragma unroll
    for (int i = 0; i < 10; i++) {
      const int r = i / 5, u = i % 5;
      if (live) x[(r * 40 + u) * 32] = make_float4(d[8 * u + 2 * r], d[8 * u + 2 * r + 1], d[8 * u + 4 + 2 * r], d[8 * u + 5 + 2 * r]);
    }
    ABT(0, 6);
    uint2 e[4];
    int n = 0;
    do {
#pragma unroll
      for (int i = 0; i < 4; i++)
        asm volatile("ld.relaxed.gpu.global.v2.b32 {%0, %1}, [%2];" : "=r"(e[i].x), "=r"(e[i].y) : "l"(stat + (2 * c + (i & 1)) * 128 + (i >> 1) * 8) : "memory");
      spin_guard(n);
    } while (__any_sync(~0u, min(min(e[0].y, e[1].y), min(e[2].y, e[3].y)) == 0 && live));
#pragma unroll
    for (int r = 0; r < 2; r++) {
      const float m0 = __uint_as_float(e[2 * r].x), m1 = __uint_as_float(e[2 * r + 1].x);
      float t = m0 + m1;
      t += __shfl_xor_sync(~0u, t, 1); t += __shfl_xor_sync(~0u, t, 2);
      t *= 0.125f;
      float q = __uint_as_float(e[2 * r].y) + __uint_as_float(e[2 * r + 1].y) + 80.f * ((m0 - t) * (m0 - t) + (m1 - t) * (m1 - t));
      q += __shfl_xor_sync(~0u, q, 1); q += __shfl_xor_sync(~0u, q, 2);
      mean[r] = t; rs[r] = rsqrtf(q * (1.f / DM) + 1e-5f);
    }
    ABT(0, 7);
    uint32_t w[2][5][2];
#pragma unroll
    for (int i = 0; i < 20; i++) w[i & 1][i >> 2][i >> 1 & 1] = pack2((d[2 * i] - mean[i & 1]) * rs[i & 1], (d[2 * i + 1] - mean[i & 1]) * rs[i & 1]);
    ln_store(w, blk * 8 + warp, cg * 5, live);
  }
  ABT(!!p.out, 8);
  TRACE(2);
}

typedef CUresult (*EncodeFn)(CUtensorMap*, CUtensorMapDataType, cuuint32_t, void*, const cuuint64_t*, const cuuint64_t*,
                             const cuuint32_t*, const cuuint32_t*, CUtensorMapInterleave, CUtensorMapSwizzle,
                             CUtensorMapL2promotion, CUtensorMapFloatOOBfill);

void make_map(EncodeFn enc, CUtensorMap* m, const void* ptr, int cols, int rows, int nb) {
  const cuuint64_t dims[3] = {(cuuint64_t)(nb ? 64 : cols), (cuuint64_t)rows, (cuuint64_t)cols / 64};
  const cuuint64_t strides[2] = {(cuuint64_t)cols * 2, 128};
  const cuuint32_t box[3] = {64, 32, (cuuint32_t)nb}, es[3] = {1, 1, 1};
  enc(m, CU_TENSOR_MAP_DATA_TYPE_BFLOAT16, nb ? 3 : 2, const_cast<void*>(ptr), dims, strides, box, es, CU_TENSOR_MAP_INTERLEAVE_NONE,
      CU_TENSOR_MAP_SWIZZLE_128B, CU_TENSOR_MAP_L2_PROMOTION_L2_128B, CU_TENSOR_MAP_FLOAT_OOB_FILL_NONE);
}
template <class... KA, class... A>
void launch(void (*kern)(KA...), int grid, int block, int smem, int cluster, bool pdl, A... args) {
  cudaFuncSetAttribute(kern, cudaFuncAttributeMaxDynamicSharedMemorySize, smem);
  cudaLaunchConfig_t cfg = {};
  cfg.gridDim = dim3(grid); cfg.blockDim = dim3(block); cfg.dynamicSmemBytes = smem; cfg.stream = cudaStreamPerThread;
  cudaLaunchAttribute at[2];
  int n = 0;
  if (cluster > 1) { at[n].id = cudaLaunchAttributeClusterDimension; at[n].val.clusterDim.x = cluster; at[n].val.clusterDim.y = 1; at[n].val.clusterDim.z = 1; n++; }
  if (pdl) { at[n].id = cudaLaunchAttributeProgrammaticStreamSerialization; at[n].val.programmaticStreamSerializationAllowed = 1; n++; }
  cfg.attrs = at; cfg.numAttrs = n;
  cudaLaunchKernelEx(&cfg, kern, args...);
}
template <class T> void* sym(T& s) { void* p = nullptr; cudaGetSymbolAddress(&p, s); return p; }

}

#define MODE(b) 0
extern "C" void kernel_launch(void* const* d_in, const int* in_sizes, int n_in, void* d_out, int out_size) {
  const __nv_bfloat16* x = (const __nv_bfloat16*)d_in[0];
  void* fn = nullptr; cudaDriverEntryPointQueryResult qr;
  cudaGetDriverEntryPoint("cuTensorMapEncodeTiled", &fn, cudaEnableDefault, &qr);
  EncodeFn enc = (EncodeFn)fn;

  ChainParams ch = {};
  PostParams op = {};
  for (int i = 0; i < 3; i++) {
    const cuuint64_t dims[3] = {HD, 128, 5}, strides[2] = {HD * 2, HD * 256};
    const cuuint32_t box[3] = {64, 128, 5}, es[3] = {1, 1, 1};
    enc(i == 0 ? &ch.wq : i == 1 ? &ch.wk : &ch.wv, CU_TENSOR_MAP_DATA_TYPE_BFLOAT16, 3, d_in[2 + i], dims, strides, box, es, CU_TENSOR_MAP_INTERLEAVE_NONE,
        CU_TENSOR_MAP_SWIZZLE_128B, W_PROMO, CU_TENSOR_MAP_FLOAT_OOB_FILL_NONE);
  }
  {
    const cuuint64_t dims[3] = {DM, HD, 7}, strides[2] = {DM * 2, 64};
    const cuuint32_t box[3] = {32, 64, 7}, es[3] = {1, 1, 1};
    enc(&ch.wo, CU_TENSOR_MAP_DATA_TYPE_BFLOAT16, 3, d_in[5], dims, strides, box, es, CU_TENSOR_MAP_INTERLEAVE_NONE,
        CU_TENSOR_MAP_SWIZZLE_64B, CU_TENSOR_MAP_L2_PROMOTION_L2_128B, CU_TENSOR_MAP_FLOAT_OOB_FILL_NONE);
  }
  ch.mem0 = (const __nv_bfloat16*)d_in[1];
  ch.pool = (uint8_t*)(((uintptr_t)sym(g_pool) + 8191) & ~(uintptr_t)8191); ch.kv = (uint8_t*)sym(g_kv); ch.xc = (const uint32_t*)sym(g_xc); ch.sync = (uint32_t*)sym(g_sync);
  ch.d1 = 0; ch.d1b = 0; ch.d2 = 0; ch.d2b = 0;
  make_map(enc, &op.wq, d_in[2], HD, DM, 3);
  make_map(enc, &op.wo, d_in[5], DM, HD, 5); make_map(enc, &op.wo2, d_in[5], DM, HD, 0);
  make_map(enc, &op.wb, d_in[8], 1920, DM, 5); make_map(enc, &op.wb2, d_in[8], 1920, DM, 0);
  op.gap = 17; op.share = 20; op.look = 14; op.gap2 = 0; op.pol = 1;

  const Weights wa = {{(const uint8_t*)d_in[3], (const uint8_t*)d_in[4], (const uint8_t*)d_in[2], (const uint8_t*)d_in[5]}}, none = {};
  launch(first_kernel, 132, 384, 128 * 1024, 1, false, x, (const uint4*)d_in[9], wa);
  for (int layer = 0; layer < 2; layer++) {
    ch.layer = ch.d2b = op.layer = layer;
    launch(chain_kernel, 96, 256, CH_SMEM, 3, true, ch);
    launch(post_kernel, MODE(3) ? 36 : 132, 384, OP_SMEM, 1, !MODE(1), op);
    const AbParams ab = {layer == 0 ? wa : none, (uint32_t*)sym(g_bo) + layer * 128, layer == 0 ? nullptr : (uint32_t*)d_out};
    launch(attn_b_kernel, 128, AB_T + 32, AB_SMEM, 1, true, ab);
  }
}
```

```cpp
#include <cuda_runtime.h>
#include <cuda_bf16.h>
#include <cuda.h>
#include <stdint.h>

namespace {

constexpr int SEQ = 2048, DM = 640, HD = 6144, NSEG = 64;
constexpr int SPIN_LIMIT = 1 << 20;

__device__ __align__(128) float4 g_x[SEQ * DM / 4];
__device__ __align__(128) uint32_t g_of[SEQ * DM / 2];
__device__ __align__(128) uint4 g_wb[DM * DM / 8];
__device__ __align__(16) float2 g_stat[16 * 8 * 128];
__device__ uint32_t g_bo[8 * 32];
__device__ __align__(128) uint4 g_q[SEQ * HD / 8];
__device__ __align__(128) uint32_t g_o[SEQ * HD / 2];
constexpr int KV_BYTES = 5120, KV_M = 4096, KV_V = NSEG * KV_BYTES;
__device__ __align__(128) uint8_t g_kv[96 * 2 * NSEG * KV_BYTES];
__device__ __align__(128) uint32_t g_xc[SEQ * DM / 2];
#define OP_B4 5
#define OP_B8 9
#define OP_B16 13
#define QA_END 12
__host__ __device__ constexpr int op_split(int b) { return b < OP_B4 ? 2 : b < OP_B8 ? 4 : b < OP_B16 ? 8 : 16; }
#define AB_PF 2
#define AB_PF0 0
#define AB_PFD 6000
#define W_PROMO CU_TENSOR_MAP_L2_PROMOTION_L2_128B
#define OP_EARLY 1
#define FIN_8 0
#define FIN_16 0
#define ATT_LOOK 1
#define PR_FIN 1
#define PR_ATT 0
#define PR_OP 2
#define PRE_MAX PS
#define PRE_GAP 0u
#define Q_PF 0
#define OEF 0
#define BQ_HOLD 6
#define WEF 1
#define FK_REP 4
#define FK_PF 1
#define BQ_160 10
#define BQ_80 16
#define OP_160 16
__host__ __device__ constexpr int fin_items(int b) { return b < FIN_8 ? 4 : b < FIN_16 ? 8 : 16; }
__host__ __device__ constexpr int op_width(int b) { return b < OP_160 ? 320 : 160; }
__host__ __device__ constexpr int bq_width(int b) { return b < BQ_160 ? 320 : b < BQ_80 ? 160 : 80; }
__device__ __align__(128) uint2 g_part[16 * 16 * 16 * 40 * 32];
__device__ __align__(128) uint32_t g_xn[SEQ * DM / 2];
constexpr int SY_Q = 128, SY_T = 160, SY_QC = 192, SY_N = 193;
__device__ __align__(16) uint32_t g_sync[SY_N];
constexpr int NSLOT = 92;
__device__ uint32_t g_pool[(NSLOT + 2) * 2048];
__device__ int g_smpart[256], g_orient[NSLOT];
__device__ uint32_t g_smclk[256], g_smuse[256];
__device__ uint32_t g_bqkv[3 * 32 * 256 * 96];

#define ABT(L, i)
#define MODE_D(b) 0
#define DELAY(d)
#define XT(i)
#define MISS(k, n)
#define PRO(i)
#define TRACE(w)
#define ITEM(code, w)
#define TR(i, v)
#define TM(i)
#define TM1(i)
#define TMD(i, dep)
#define TMV(i, at, v)

__device__ __forceinline__ uint32_t gtime() { uint32_t c; asm volatile("mov.u32 %0, %%globaltimer_lo;" : "=r"(c) :: "memory"); return c; }
__device__ __forceinline__ uint32_t clk32() { uint32_t c; asm volatile("mov.u32 %0, %%clock;" : "=r"(c) :: "memory"); return c; }
__device__ __forceinline__ uint32_t s2u(const void* p) { return (uint32_t)__cvta_generic_to_shared(p); }
__device__ __forceinline__ uint32_t pack2(float a, float b) {
  uint32_t r; asm("cvt.rn.bf16x2.f32 %0, %1, %2;" : "=r"(r) : "f"(b), "f"(a)); return r; }
__device__ __forceinline__ float bf_lo(uint32_t w) { return __uint_as_float(w << 16); }
__device__ __forceinline__ float bf_hi(uint32_t w) { return __uint_as_float(w & 0xffff0000u); }
__device__ __forceinline__ float ex2(float x) { float y; asm("ex2.approx.ftz.f32 %0, %1;" : "=f"(y) : "f"(x)); return y; }

__device__ __forceinline__ void mbar_init(uint32_t bar, uint32_t n) {
  asm volatile("mbarrier.init.shared::cta.b64 [%0], %1;" :: "r"(bar), "r"(n) : "memory"); }
__device__ __forceinline__ void mbar_expect(uint32_t bar, uint32_t bytes) {
  asm volatile("mbarrier.arrive.expect_tx.shared::cta.b64 _, [%0], %1;" :: "r"(bar), "r"(bytes) : "memory"); }
__device__ __forceinline__ void mbar_arrive(uint32_t bar) {
  asm volatile("mbarrier.arrive.shared::cta.b64 _, [%0];" :: "r"(bar) : "memory"); }
__device__ __forceinline__ void mbar_wait(uint32_t bar, uint32_t ph) {
  asm volatile("{.reg .pred p; .reg .u32 n; mov.u32 n, 0;\n"
               "W: mbarrier.try_wait.parity.shared::cta.b64 p, [%0], %1; @p bra D;\n"
               "add.u32 n, n, 1; setp.gt.u32 p, n, %2; @p trap; bra W;\n"
               "D: }" :: "r"(bar), "r"(ph), "n"(SPIN_LIMIT) : "memory");
}
__device__ __forceinline__ void mbar_wait_cluster(uint32_t bar, uint32_t ph) {
  asm volatile("{.reg .pred p; .reg .u32 n; mov.u32 n, 0;\n"
               "W: mbarrier.try_wait.parity.acquire.cluster.shared::cta.b64 p, [%0], %1; @p bra D;\n"
               "add.u32 n, n, 1; setp.gt.u32 p, n, %2; @p trap; bra W;\n"
               "D: }" :: "r"(bar), "r"(ph), "n"(SPIN_LIMIT) : "memory");
}
__device__ __forceinline__ void spin_guard(int& n) {
  asm volatile("{.reg .pred p; add.s32 %0, %0, 1; setp.gt.s32 p, %0, %1; @p trap;}" : "+r"(n) : "n"(SPIN_LIMIT));
}
__device__ __forceinline__ void pdl_wait() { asm volatile("griddepcontrol.wait;" ::: "memory"); TRACE(1); }
__device__ __forceinline__ void pdl_launch() { asm volatile("griddepcontrol.launch_dependents;" ::: "memory"); }
__device__ __forceinline__ uint32_t ld_acquire(const uint32_t* p) { uint32_t v; asm volatile("ld.acquire.gpu.global.u32 %0, [%1];" : "=r"(v) : "l"(p) : "memory"); return v; }
__device__ __forceinline__ void red_release(uint32_t* p, uint32_t v) { asm volatile("red.release.gpu.global.add.u32 [%0], %1;" :: "l"(p), "r"(v) : "memory"); }
__device__ __forceinline__ void red_relaxed(uint32_t* p, uint32_t v) { asm volatile("red.relaxed.gpu.global.add.u32 [%0], %1;" :: "l"(p), "r"(v) : "memory"); }
__device__ __forceinline__ void fence_async_global() { asm volatile("fence.proxy.async.global;" ::: "memory"); }
__device__ __forceinline__ void fence_async() { asm volatile("fence.proxy.async.shared::cta;" ::: "memory"); }
__device__ __forceinline__ void bar_sync(int id, int n) { asm volatile("bar.sync %0, %1;" :: "r"(id), "r"(n) : "memory"); }
__device__ __forceinline__ void bar_arrive(int id, int n) { asm volatile("bar.arrive %0, %1;" :: "r"(id), "r"(n) : "memory"); }
__device__ __forceinline__ void tma_load(uint32_t dst, const CUtensorMap* m, int c0, int c1, uint32_t bar) {
  asm volatile("cp.async.bulk.tensor.2d.shared::cluster.global.mbarrier::complete_tx::bytes [%0], [%1, {%3, %4}], [%2];"
               :: "r"(dst), "l"(m), "r"(bar), "r"(c0), "r"(c1) : "memory"); }
template <bool STREAM = false>
__device__ __forceinline__ void tma_load3(uint32_t dst, const CUtensorMap* m, int c0, int c1, uint32_t bar) {
  if (STREAM)
    asm volatile("{.reg .b64 pol; createpolicy.fractional.L2::evict_first.b64 pol, 1.0;\n"
                 "cp.async.bulk.tensor.3d.shared::cluster.global.mbarrier::complete_tx::bytes.L2::cache_hint [%0], [%1, {%3, %4, 0}], [%2], pol;}"
                 :: "r"(dst), "l"(m), "r"(bar), "r"(c0), "r"(c1) : "memory");
  else
  asm volatile("cp.async.bulk.tensor.3d.shared::cluster.global.mbarrier::complete_tx::bytes [%0], [%1, {%3, %4, 0}], [%2];"
               :: "r"(dst), "l"(m), "r"(bar), "r"(c0), "r"(c1) : "memory"); }
__device__ __forceinline__ void tma_load3z(uint32_t dst, const CUtensorMap* m, int c1, int c2, uint32_t bar) {
  asm volatile("cp.async.bulk.tensor.3d.shared::cluster.global.mbarrier::complete_tx::bytes [%0], [%1, {0, %3, %4}], [%2];"
               :: "r"(dst), "l"(m), "r"(bar), "r"(c1), "r"(c2) : "memory"); }
__device__ __forceinline__ void tma_store(const CUtensorMap* m, uint32_t src, int c0, int c1) {
  asm volatile("cp.async.bulk.tensor.2d.global.shared::cta.bulk_group [%0, {%2, %3}], [%1];"
               :: "l"(m), "r"(src), "r"(c0), "r"(c1) : "memory"); }
__device__ __forceinline__ void tma_store_stream(const CUtensorMap* m, uint32_t src, int c0, int c1) {
  asm volatile("{.reg .b64 pol; createpolicy.fractional.L2::evict_first.b64 pol, 1.0;\n"
               "cp.async.bulk.tensor.2d.global.shared::cta.bulk_group.L2::cache_hint [%0, {%2, %3}], [%1], pol;}"
               :: "l"(m), "r"(src), "r"(c0), "r"(c1) : "memory"); }
__device__ __forceinline__ void bulk_load(uint32_t dst, const void* src, uint32_t bytes, uint32_t bar) {
  asm volatile("cp.async.bulk.shared::cluster.global.mbarrier::complete_tx::bytes [%0], [%1], %2, [%3];"
               :: "r"(dst), "l"(src), "r"(bytes), "r"(bar) : "memory"); }
__device__ __forceinline__ void bulk_load_last(uint32_t dst, const void* src, uint32_t bytes, uint32_t bar) {
  asm volatile("{.reg .b64 pol; createpolicy.fractional.L2::evict_first.b64 pol, 1.0;\n"
               "cp.async.bulk.shared::cluster.global.mbarrier::complete_tx::bytes.L2::cache_hint [%0], [%1], %2, [%3], pol;}"
               :: "r"(dst), "l"(src), "r"(bytes), "r"(bar) : "memory"); }
__device__ __forceinline__ void tma_load_last(uint32_t dst, const CUtensorMap* m, int c0, int c1, uint32_t bar) {
  asm volatile("{.reg .b64 pol; createpolicy.fractional.L2::evict_first.b64 pol, 1.0;\n"
               "cp.async.bulk.tensor.2d.shared::cluster.global.mbarrier::complete_tx::bytes.L2::cache_hint [%0], [%1, {%3, %4}], [%2], pol;}"
               :: "r"(dst), "l"(m), "r"(bar), "r"(c0), "r"(c1) : "memory"); }
__device__ __forceinline__ void bulk_send(uint32_t dst, uint32_t src, uint32_t bytes, uint32_t bar) {
  asm volatile("cp.async.bulk.shared::cluster.shared::cta.mbarrier::complete_tx::bytes [%0], [%1], %2, [%3];"
               :: "r"(dst), "r"(src), "r"(bytes), "r"(bar) : "memory"); }
__device__ __forceinline__ void bulk_store(void* dst, uint32_t src, uint32_t bytes) {
  asm volatile("cp.async.bulk.global.shared::cta.bulk_group [%0], [%1], %2;" :: "l"(dst), "r"(src), "r"(bytes) : "memory"); }
__device__ __forceinline__ void bulk_commit() { asm volatile("cp.async.bulk.commit_group;" ::: "memory"); }
template <int N> __device__ __forceinline__ void bulk_wait_read() { asm volatile("cp.async.bulk.wait_group.read %0;" :: "n"(N) : "memory"); }
template <int N> __device__ __forceinline__ void bulk_wait() { asm volatile("cp.async.bulk.wait_group %0;" :: "n"(N) : "memory"); }

__device__ __forceinline__ uint64_t mkdesc(uint32_t addr, uint32_t lbo, uint32_t sbo, uint32_t sw) {
  return (uint64_t)((addr & 0x3FFFF) >> 4) | ((uint64_t)(lbo >> 4) << 16) | ((uint64_t)(sbo >> 4) << 32) | ((uint64_t)sw << 62); }
__device__ __forceinline__ void wg_fence() { asm volatile("wgmma.fence.sync.aligned;" ::: "memory"); }
__device__ __forceinline__ void wg_commit() { asm volatile("wgmma.commit_group.sync.aligned;" ::: "memory"); }
template <int N> __device__ __forceinline__ void wg_wait() { asm volatile("wgmma.wait_group.sync.aligned %0;" :: "n"(N) : "memory"); }
template <int N> __device__ __forceinline__ void reg_fence(float* d) {
#pragma unroll
  for (int i = 0; i < N; i++) asm volatile("" : "+f"(d[i]) :: "memory");
}

__device__ __forceinline__ void mma16(float* d, uint32_t a0, uint32_t a1, uint32_t a2, uint32_t a3, uint32_t b0, uint32_t b1) {
  asm volatile("mma.sync.aligned.m16n8k16.row.col.f32.bf16.bf16.f32 {%0,%1,%2,%3},{%4,%5,%6,%7},{%8,%9},{%0,%1,%2,%3};"
               : "+f"(d[0]), "+f"(d[1]), "+f"(d[2]), "+f"(d[3]) : "r"(a0), "r"(a1), "r"(a2), "r"(a3), "r"(b0), "r"(b1)); }
__device__ __forceinline__ void mma8(float* d, uint32_t a0, uint32_t a1, uint32_t b0) {
  asm volatile("mma.sync.aligned.m16n8k8.row.col.f32.bf16.bf16.f32 {%0,%1,%2,%3},{%4,%5},{%6},{%0,%1,%2,%3};"
               : "+f"(d[0]), "+f"(d[1]), "+f"(d[2]), "+f"(d[3]) : "r"(a0), "r"(a1), "r"(b0)); }
__device__ __forceinline__ void ldsm4(uint32_t* r, uint32_t a) {
  asm volatile("ldmatrix.sync.aligned.m8n8.x4.shared.b16 {%0,%1,%2,%3},[%4];" : "=r"(r[0]), "=r"(r[1]), "=r"(r[2]), "=r"(r[3]) : "r"(a) : "memory"); }
__device__ __forceinline__ void ldsm4t(uint32_t* r, uint32_t a) {
  asm volatile("ldmatrix.sync.aligned.m8n8.x4.trans.shared.b16 {%0,%1,%2,%3},[%4];" : "=r"(r[0]), "=r"(r[1]), "=r"(r[2]), "=r"(r[3]) : "r"(a) : "memory"); }
__device__ __forceinline__ void ldsm2(uint32_t* r, uint32_t a) {
  asm volatile("ldmatrix.sync.aligned.m8n8.x2.shared.b16 {%0,%1},[%2];" : "=r"(r[0]), "=r"(r[1]) : "r"(a) : "memory"); }
__device__ __forceinline__ void stsm4(uint32_t a, uint32_t r0, uint32_t r1, uint32_t r2, uint32_t r3) {
  asm volatile("stmatrix.sync.aligned.m8n8.x4.shared.b16 [%0], {%1,%2,%3,%4};" :: "r"(a), "r"(r0), "r"(r1), "r"(r2), "r"(r3) : "memory"); }
__device__ __forceinline__ void stsm2t(uint32_t a, uint32_t r0, uint32_t r1) {
  asm volatile("stmatrix.sync.aligned.m8n8.x2.trans.shared.b16 [%0], {%1,%2};" :: "r"(a), "r"(r0), "r"(r1) : "memory"); }
__device__ __forceinline__ void stsm4t(uint32_t a, uint32_t r0, uint32_t r1, uint32_t r2, uint32_t r3) {
  asm volatile("stmatrix.sync.aligned.m8n8.x4.trans.shared.b16 [%0], {%1,%2,%3,%4};" :: "r"(a), "r"(r0), "r"(r1), "r"(r2), "r"(r3) : "memory"); }
__device__ __forceinline__ void st_async128(uint32_t a, uint4 v, uint32_t bar) {
  asm volatile("st.async.shared::cluster.mbarrier::complete_tx::bytes.v4.b32 [%0], {%1,%2,%3,%4}, [%5];" :: "r"(a), "r"(v.x), "r"(v.y), "r"(v.z), "r"(v.w), "r"(bar) : "memory"); }
__device__ __forceinline__ void sts32(uint32_t a, uint32_t v) { asm volatile("st.shared.b32 [%0], %1;" :: "r"(a), "r"(v) : "memory"); }
__device__ __forceinline__ void sts64f(uint32_t a, float x, float y) { asm volatile("st.shared.v2.f32 [%0], {%1,%2};" :: "r"(a), "f"(x), "f"(y) : "memory"); }
__device__ __forceinline__ void sts128(uint32_t a, uint4 v) {
  asm volatile("st.shared.v4.b32 [%0], {%1,%2,%3,%4};" :: "r"(a), "r"(v.x), "r"(v.y), "r"(v.z), "r"(v.w) : "memory"); }
__device__ __forceinline__ void sts128f(uint32_t a, float x, float y, float z, float w) {
  asm volatile("st.shared.v4.f32 [%0], {%1,%2,%3,%4};" :: "r"(a), "f"(x), "f"(y), "f"(z), "f"(w) : "memory"); }
__device__ __forceinline__ float lds32f(uint32_t a) { float v; asm volatile("ld.shared.f32 %0, [%1];" : "=f"(v) : "r"(a) : "memory"); return v; }
__device__ __forceinline__ float2 lds64f(uint32_t a) { float2 v; asm volatile("ld.shared.v2.f32 {%0,%1}, [%2];" : "=f"(v.x), "=f"(v.y) : "r"(a) : "memory"); return v; }
__device__ __forceinline__ float4 lds128f(uint32_t a) {
  float4 v; asm volatile("ld.shared.v4.f32 {%0,%1,%2,%3}, [%4];" : "=f"(v.x), "=f"(v.y), "=f"(v.z), "=f"(v.w) : "r"(a) : "memory"); return v; }
__device__ __forceinline__ uint4 lds128(uint32_t a) {
  uint4 v; asm volatile("ld.shared.v4.b32 {%0,%1,%2,%3}, [%4];" : "=r"(v.x), "=r"(v.y), "=r"(v.z), "=r"(v.w) : "r"(a) : "memory"); return v; }
__device__ __forceinline__ uint4 ldg_strong128(const void* p) {
  uint4 v; asm volatile("ld.relaxed.gpu.global.v4.u32 {%0,%1,%2,%3}, [%4];" : "=r"(v.x), "=r"(v.y), "=r"(v.z), "=r"(v.w) : "l"(p) : "memory"); return v; }
__device__ __forceinline__ void stg_strong32(void* p, uint32_t v) { asm volatile("st.relaxed.gpu.global.u32 [%0], %1;" :: "l"(p), "r"(v) : "memory"); }
__device__ __forceinline__ void stg_strong16(void* p, uint32_t v) { asm volatile("st.relaxed.gpu.global.u16 [%0], %1;" :: "l"(p), "h"((uint16_t)v) : "memory"); }
__device__ __forceinline__ void stg_strong128(void* p, uint4 v) {
  asm volatile("st.relaxed.gpu.global.v4.u32 [%0], {%1,%2,%3,%4};" :: "l"(p), "r"(v.x), "r"(v.y), "r"(v.z), "r"(v.w) : "memory"); }
__device__ __forceinline__ uint32_t mapa(uint32_t a, uint32_t r) {
  uint32_t o; asm("mapa.shared::cluster.u32 %0, %1, %2;" : "=r"(o) : "r"(a), "r"(r)); return o; }
__device__ __forceinline__ void st_async2f(uint32_t a, float x, float y, uint32_t bar) {
  asm volatile("st.async.shared::cluster.mbarrier::complete_tx::bytes.v2.f32 [%0], {%1,%2}, [%3];" :: "r"(a), "f"(x), "f"(y), "r"(bar) : "memory"); }
__device__ __forceinline__ void st_async32(uint32_t a, uint32_t x, uint32_t bar) {
  asm volatile("st.async.shared::cluster.mbarrier::complete_tx::bytes.b32 [%0], %1, [%2];" :: "r"(a), "r"(x), "r"(bar) : "memory"); }
__device__ __forceinline__ uint32_t lds32(uint32_t a) { uint32_t v; asm volatile("ld.shared.b32 %0, [%1];" : "=r"(v) : "r"(a) : "memory"); return v; }
__device__ __forceinline__ void st_async64(uint32_t a, uint32_t x, uint32_t y, uint32_t bar) {
  asm volatile("st.async.shared::cluster.mbarrier::complete_tx::bytes.v2.b32 [%0], {%1,%2}, [%3];" :: "r"(a), "r"(x), "r"(y), "r"(bar) : "memory"); }
__device__ __forceinline__ uint2 lds64(uint32_t a) { uint2 v; asm volatile("ld.shared.v2.b32 {%0,%1}, [%2];" : "=r"(v.x), "=r"(v.y) : "r"(a) : "memory"); return v; }
__device__ __forceinline__ void sts64(uint32_t a, uint32_t x, uint32_t y) { asm volatile("st.shared.v2.b32 [%0], {%1,%2};" :: "r"(a), "r"(x), "r"(y) : "memory"); }
__device__ __forceinline__ uint32_t ldg_strong32(const void* p) { uint32_t v; asm volatile("ld.relaxed.gpu.global.u32 %0, [%1];" : "=r"(v) : "l"(p) : "memory"); return v; }
__device__ __forceinline__ uint32_t transpose8(uint32_t x) { uint32_t r; asm volatile("movmatrix.sync.aligned.m8n8.trans.b16 %0, %1;" : "=r"(r) : "r"(x)); return r; }
__device__ __forceinline__ uint32_t hadd2(uint32_t a, uint32_t b) { uint32_t r; asm("add.rn.bf16x2 %0, %1, %2;" : "=r"(r) : "r"(a), "r"(b)); return r; }
__device__ __forceinline__ uint32_t min4(uint4 v) { return min(__vimin3_u32(v.x, v.y, v.z), v.w); }

__device__ __forceinline__ void wg_ss192_01(float* d, uint64_t da, uint64_t db, int sd) {
  asm volatile("{.reg .pred p; setp.ne.b32 p, %98, 0;\n"
    "wgmma.mma_async.sync.aligned.m64n192k16.f32.bf16.bf16 {%0,%1,%2,%3,%4,%5,%6,%7,%8,%9,%10,%11,%12,%13,%14,%15,%16,%17,%18,%19,%20,%21,%22,%23,%24,%25,%26,%27,%28,%29,%30,%31,%32,%33,%34,%35,%36,%37,%38,%39,%40,%41,%42,%43,%44,%45,%46,%47,%48,%49,%50,%51,%52,%53,%54,%55,%56,%57,%58,%59,%60,%61,%62,%63,%64,%65,%66,%67,%68,%69,%70,%71,%72,%73,%74,%75,%76,%77,%78,%79,%80,%81,%82,%83,%84,%85,%86,%87,%88,%89,%90,%91,%92,%93,%94,%95}, %96, %97, p, 1, 1, 0, 1;}"
    : "+f"(d[0]),"+f"(d[1]),"+f"(d[2]),"+f"(d[3]),"+f"(d[4]),"+f"(d[5]),"+f"(d[6]),"+f"(d[7]),"+f"(d[8]),"+f"(d[9]),"+f"(d[10]),"+f"(d[11]),"+f"(d[12]),"+f"(d[13]),"+f"(d[14]),"+f"(d[15]),"+f"(d[16]),"+f"(d[17]),"+f"(d[18]),"+f"(d[19]),"+f"(d[20]),"+f"(d[21]),"+f"(d[22]),"+f"(d[23]),"+f"(d[24]),"+f"(d[25]),"+f"(d[26]),"+f"(d[27]),"+f"(d[28]),"+f"(d[29]),"+f"(d[30]),"+f"(d[31]),"+f"(d[32]),"+f"(d[33]),"+f"(d[34]),"+f"(d[35]),"+f"(d[36]),"+f"(d[37]),"+f"(d[38]),"+f"(d[39]),"+f"(d[40]),"+f"(d[41]),"+f"(d[42]),"+f"(d[43]),"+f"(d[44]),"+f"(d[45]),"+f"(d[46]),"+f"(d[47]),"+f"(d[48]),"+f"(d[49]),"+f"(d[50]),"+f"(d[51]),"+f"(d[52]),"+f"(d[53]),"+f"(d[54]),"+f"(d[55]),"+f"(d[56]),"+f"(d[57]),"+f"(d[58]),"+f"(d[59]),"+f"(d[60]),"+f"(d[61]),"+f"(d[62]),"+f"(d[63]),"+f"(d[64]),"+f"(d[65]),"+f"(d[66]),"+f"(d[67]),"+f"(d[68]),"+f"(d[69]),"+f"(d[70]),"+f"(d[71]),"+f"(d[72]),"+f"(d[73]),"+f"(d[74]),"+f"(d[75]),"+f"(d[76]),"+f"(d[77]),"+f"(d[78]),"+f"(d[79]),"+f"(d[80]),"+f"(d[81]),"+f"(d[82]),"+f"(d[83]),"+f"(d[84]),"+f"(d[85]),"+f"(d[86]),"+f"(d[87]),"+f"(d[88]),"+f"(d[89]),"+f"(d[90]),"+f"(d[91]),"+f"(d[92]),"+f"(d[93]),"+f"(d[94]),"+f"(d[95])
    : "l"(da), "l"(db), "r"(sd));
}
__device__ __forceinline__ void wg_ss128_01(float* d, uint64_t da, uint64_t db, int sd) {
  asm volatile("{.reg .pred p; setp.ne.b32 p, %66, 0;\n"
    "wgmma.mma_async.sync.aligned.m64n128k16.f32.bf16.bf16 {%0,%1,%2,%3,%4,%5,%6,%7,%8,%9,%10,%11,%12,%13,%14,%15,%16,%17,%18,%19,%20,%21,%22,%23,%24,%25,%26,%27,%28,%29,%30,%31,%32,%33,%34,%35,%36,%37,%38,%39,%40,%41,%42,%43,%44,%45,%46,%47,%48,%49,%50,%51,%52,%53,%54,%55,%56,%57,%58,%59,%60,%61,%62,%63}, %64, %65, p, 1, 1, 0, 1;}"
    : "+f"(d[0]),"+f"(d[1]),"+f"(d[2]),"+f"(d[3]),"+f"(d[4]),"+f"(d[5]),"+f"(d[6]),"+f"(d[7]),"+f"(d[8]),"+f"(d[9]),"+f"(d[10]),"+f"(d[11]),"+f"(d[12]),"+f"(d[13]),"+f"(d[14]),"+f"(d[15]),"+f"(d[16]),"+f"(d[17]),"+f"(d[18]),"+f"(d[19]),"+f"(d[20]),"+f"(d[21]),"+f"(d[22]),"+f"(d[23]),"+f"(d[24]),"+f"(d[25]),"+f"(d[26]),"+f"(d[27]),"+f"(d[28]),"+f"(d[29]),"+f"(d[30]),"+f"(d[31]),"+f"(d[32]),"+f"(d[33]),"+f"(d[34]),"+f"(d[35]),"+f"(d[36]),"+f"(d[37]),"+f"(d[38]),"+f"(d[39]),"+f"(d[40]),"+f"(d[41]),"+f"(d[42]),"+f"(d[43]),"+f"(d[44]),"+f"(d[45]),"+f"(d[46]),"+f"(d[47]),"+f"(d[48]),"+f"(d[49]),"+f"(d[50]),"+f"(d[51]),"+f"(d[52]),"+f"(d[53]),"+f"(d[54]),"+f"(d[55]),"+f"(d[56]),"+f"(d[57]),"+f"(d[58]),"+f"(d[59]),"+f"(d[60]),"+f"(d[61]),"+f"(d[62]),"+f"(d[63])
    : "l"(da), "l"(db), "r"(sd));
}
__device__ __forceinline__ void wg_ss160_01(float* d, uint64_t da, uint64_t db, int sd) {
  asm volatile("{.reg .pred p; setp.ne.b32 p, %82, 0;\n"
    "wgmma.mma_async.sync.aligned.m64n160k16.f32.bf16.bf16 {%0,%1,%2,%3,%4,%5,%6,%7,%8,%9,%10,%11,%12,%13,%14,%15,%16,%17,%18,%19,%20,%21,%22,%23,%24,%25,%26,%27,%28,%29,%30,%31,%32,%33,%34,%35,%36,%37,%38,%39,%40,%41,%42,%43,%44,%45,%46,%47,%48,%49,%50,%51,%52,%53,%54,%55,%56,%57,%58,%59,%60,%61,%62,%63,%64,%65,%66,%67,%68,%69,%70,%71,%72,%73,%74,%75,%76,%77,%78,%79}, %80, %81, p, 1, 1, 0, 1;}"
    : "+f"(d[0]),"+f"(d[1]),"+f"(d[2]),"+f"(d[3]),"+f"(d[4]),"+f"(d[5]),"+f"(d[6]),"+f"(d[7]),"+f"(d[8]),"+f"(d[9]),"+f"(d[10]),"+f"(d[11]),"+f"(d[12]),"+f"(d[13]),"+f"(d[14]),"+f"(d[15]),"+f"(d[16]),"+f"(d[17]),"+f"(d[18]),"+f"(d[19]),"+f"(d[20]),"+f"(d[21]),"+f"(d[22]),"+f"(d[23]),"+f"(d[24]),"+f"(d[25]),"+f"(d[26]),"+f"(d[27]),"+f"(d[28]),"+f"(d[29]),"+f"(d[30]),"+f"(d[31]),"+f"(d[32]),"+f"(d[33]),"+f"(d[34]),"+f"(d[35]),"+f"(d[36]),"+f"(d[37]),"+f"(d[38]),"+f"(d[39]),"+f"(d[40]),"+f"(d[41]),"+f"(d[42]),"+f"(d[43]),"+f"(d[44]),"+f"(d[45]),"+f"(d[46]),"+f"(d[47]),"+f"(d[48]),"+f"(d[49]),"+f"(d[50]),"+f"(d[51]),"+f"(d[52]),"+f"(d[53]),"+f"(d[54]),"+f"(d[55]),"+f"(d[56]),"+f"(d[57]),"+f"(d[58]),"+f"(d[59]),"+f"(d[60]),"+f"(d[61]),"+f"(d[62]),"+f"(d[63]),"+f"(d[64]),"+f"(d[65]),"+f"(d[66]),"+f"(d[67]),"+f"(d[68]),"+f"(d[69]),"+f"(d[70]),"+f"(d[71]),"+f"(d[72]),"+f"(d[73]),"+f"(d[74]),"+f"(d[75]),"+f"(d[76]),"+f"(d[77]),"+f"(d[78]),"+f"(d[79])
    : "l"(da), "l"(db), "r"(sd));
}
__device__ __forceinline__ void wg_ss80_01(float* d, uint64_t da, uint64_t db, int sd) {
  asm volatile("{.reg .pred p; setp.ne.b32 p, %42, 0;\n"
    "wgmma.mma_async.sync.aligned.m64n80k16.f32.bf16.bf16 {%0,%1,%2,%3,%4,%5,%6,%7,%8,%9,%10,%11,%12,%13,%14,%15,%16,%17,%18,%19,%20,%21,%22,%23,%24,%25,%26,%27,%28,%29,%30,%31,%32,%33,%34,%35,%36,%37,%38,%39}, %40, %41, p, 1, 1, 0, 1;}"
    : "+f"(d[0]),"+f"(d[1]),"+f"(d[2]),"+f"(d[3]),"+f"(d[4]),"+f"(d[5]),"+f"(d[6]),"+f"(d[7]),"+f"(d[8]),"+f"(d[9]),"+f"(d[10]),"+f"(d[11]),"+f"(d[12]),"+f"(d[13]),"+f"(d[14]),"+f"(d[15]),"+f"(d[16]),"+f"(d[17]),"+f"(d[18]),"+f"(d[19]),"+f"(d[20]),"+f"(d[21]),"+f"(d[22]),"+f"(d[23]),"+f"(d[24]),"+f"(d[25]),"+f"(d[26]),"+f"(d[27]),"+f"(d[28]),"+f"(d[29]),"+f"(d[30]),"+f"(d[31]),"+f"(d[32]),"+f"(d[33]),"+f"(d[34]),"+f"(d[35]),"+f"(d[36]),"+f"(d[37]),"+f"(d[38]),"+f"(d[39])
    : "l"(da), "l"(db), "r"(sd));
}
__device__ __forceinline__ void wg_rs32_00(float* d, uint32_t a0, uint32_t a1, uint32_t a2, uint32_t a3, uint64_t db, int sd) {
  asm volatile("{.reg .pred p; setp.ne.b32 p, %21, 0;\n"
    "wgmma.mma_async.sync.aligned.m64n32k16.f32.bf16.bf16 {%0,%1,%2,%3,%4,%5,%6,%7,%8,%9,%10,%11,%12,%13,%14,%15}, {%16,%17,%18,%19}, %20, p, 1, 1, 0;}"
    : "+f"(d[0]),"+f"(d[1]),"+f"(d[2]),"+f"(d[3]),"+f"(d[4]),"+f"(d[5]),"+f"(d[6]),"+f"(d[7]),"+f"(d[8]),"+f"(d[9]),"+f"(d[10]),"+f"(d[11]),"+f"(d[12]),"+f"(d[13]),"+f"(d[14]),"+f"(d[15])
    : "r"(a0), "r"(a1), "r"(a2), "r"(a3), "l"(db), "r"(sd));
}
__device__ __forceinline__ void wg_rs64_00(float* d, uint32_t a0, uint32_t a1, uint32_t a2, uint32_t a3, uint64_t db, int sd) {
  asm volatile("{.reg .pred p; setp.ne.b32 p, %37, 0;\n"
    "wgmma.mma_async.sync.aligned.m64n64k16.f32.bf16.bf16 {%0,%1,%2,%3,%4,%5,%6,%7,%8,%9,%10,%11,%12,%13,%14,%15,%16,%17,%18,%19,%20,%21,%22,%23,%24,%25,%26,%27,%28,%29,%30,%31}, {%32,%33,%34,%35}, %36, p, 1, 1, 0;}"
    : "+f"(d[0]),"+f"(d[1]),"+f"(d[2]),"+f"(d[3]),"+f"(d[4]),"+f"(d[5]),"+f"(d[6]),"+f"(d[7]),"+f"(d[8]),"+f"(d[9]),"+f"(d[10]),"+f"(d[11]),"+f"(d[12]),"+f"(d[13]),"+f"(d[14]),"+f"(d[15]),"+f"(d[16]),"+f"(d[17]),"+f"(d[18]),"+f"(d[19]),"+f"(d[20]),"+f"(d[21]),"+f"(d[22]),"+f"(d[23]),"+f"(d[24]),"+f"(d[25]),"+f"(d[26]),"+f"(d[27]),"+f"(d[28]),"+f"(d[29]),"+f"(d[30]),"+f"(d[31])
    : "r"(a0), "r"(a1), "r"(a2), "r"(a3), "l"(db), "r"(sd));
}
__device__ __forceinline__ void wg_rs24_01(float* d, uint32_t a0, uint32_t a1, uint32_t a2, uint32_t a3, uint64_t db, int sd) {
  asm volatile("{.reg .pred p; setp.ne.b32 p, %17, 0;\n"
    "wgmma.mma_async.sync.aligned.m64n24k16.f32.bf16.bf16 {%0,%1,%2,%3,%4,%5,%6,%7,%8,%9,%10,%11}, {%12,%13,%14,%15}, %16, p, 1, 1, 1;}"
    : "+f"(d[0]),"+f"(d[1]),"+f"(d[2]),"+f"(d[3]),"+f"(d[4]),"+f"(d[5]),"+f"(d[6]),"+f"(d[7]),"+f"(d[8]),"+f"(d[9]),"+f"(d[10]),"+f"(d[11])
    : "r"(a0), "r"(a1), "r"(a2), "r"(a3), "l"(db), "r"(sd));
}

#define AB_POLY 0xaa
#define AB_DEG 3
__device__ __forceinline__ constexpr bool poly_group(int group) { return (AB_POLY >> (group & 7)) & 1; }

template <int V> struct Int { static constexpr int value = V; };

template <int NG>
__device__ __forceinline__ void ln_stats(const float4 (&v)[NG][5], uint32_t scratch, float (&mean)[NG], float (&rs)[NG]) {
  const int warp = threadIdx.x >> 5, lane = threadIdx.x & 31;
#pragma unroll
  for (int r = 0; r < NG; r++) {
    float s = 0.f, q = 0.f;
#pragma unroll
    for (int i = 0; i < 5; i++) s += (v[r][i].x + v[r][i].y) + (v[r][i].z + v[r][i].w);
    s += __shfl_xor_sync(~0u, s, 1); s += __shfl_xor_sync(~0u, s, 2);
    s *= 1.f / 80;
#pragma unroll
    for (int i = 0; i < 5; i++) {
      const float x = v[r][i].x - s, y = v[r][i].y - s, z = v[r][i].z - s, w = v[r][i].w - s;
      q += (x * x + y * y) + (z * z + w * w);
    }
    q += __shfl_xor_sync(~0u, q, 1); q += __shfl_xor_sync(~0u, q, 2);
    mean[r] = s; rs[r] = q;
  }
  bar_sync(1, 256);
  if ((lane & 3) == 0) {
#pragma unroll
    for (int r = 0; r < NG; r++) sts64f(scratch + r * 512 + lane * 16 + warp * 8, mean[r], rs[r]);
  }
  bar_sync(1, 256);
#pragma unroll
  for (int r = 0; r < NG; r++) {
    const float4 e = lds128f(scratch + r * 512 + lane * 16);
    float t = e.x + e.z;
    t += __shfl_xor_sync(~0u, t, 1); t += __shfl_xor_sync(~0u, t, 2);
    t *= 0.125f;
    float q = e.y + e.w + 80.f * ((e.x - t) * (e.x - t) + (e.z - t) * (e.z - t));
    q += __shfl_xor_sync(~0u, q, 1); q += __shfl_xor_sync(~0u, q, 2);
    mean[r] = t; rs[r] = rsqrtf(q * (1.f / DM) + 1e-5f);
  }
}

__device__ __forceinline__ void ln_store(const uint32_t (&w)[2][5][2], int tile, int u0, bool live = true) {
  const int lane = threadIdx.x & 31;
  uint32_t* xc = g_xc + ((tile >> 1) * 40 + u0) * 256 + (tile & 1) * 64 + lane;
#pragma unroll
  for (int i = 0; i < 20; i++) if (live) xc[(i >> 1) * 128 + (i & 1) * 32] = w[i & 1][i >> 2][i >> 1 & 1];
#pragma unroll
  for (int i = 0; i < 5; i++) {
    const int u = u0 + i;
    uint32_t* xn = g_xn + (((tile >> 3) * 20 + (u >> 1)) * 16 + (tile & 1) * 8 + (tile & 6)) * 128 + (u & 1) * 64 + lane;
#pragma unroll
    for (int r = 0; r < 2; r++) if (live) { xn[r * 128] = w[r][i][0]; xn[r * 128 + 32] = w[r][i][1]; }
  }
}
__device__ __forceinline__ void wait_count(const uint32_t* c, uint32_t n) {
  int spin = 0;
  while ((ld_acquire(c) & 0xffff) < n) { __nanosleep(32); spin_guard(spin); }
}

__device__ __forceinline__ uint8_t* pool_at(uint32_t off) {
  return reinterpret_cast<uint8_t*>((reinterpret_cast<uintptr_t>(g_pool) + 8191) & ~(uintptr_t)8191) + off; }
struct Weights { const uint8_t* w[4]; };
__device__ __forceinline__ void prefetch_weights(const Weights& p, int i) {
  if (blockIdx.x < 128) asm volatile("cp.async.bulk.prefetch.L2.global [%0], 61440;" :: "l"(p.w[i] + (size_t)blockIdx.x * 61440) : "memory");
}
__global__ void __launch_bounds__(384) first_kernel(const __nv_bfloat16* __restrict__ xin, const uint4* __restrict__ wb, const __grid_constant__ Weights wa) {
  __shared__ __align__(16) float scratch[256];
  __shared__ uint32_t lat[4];
  const int warp = threadIdx.x >> 5, lane = threadIdx.x & 31, cta = blockIdx.x;
  TRACE(0);
  pdl_launch();
  if (warp >= 8) {
    if (warp < 10 || cta < NSLOT) {
      uint32_t* q = reinterpret_cast<uint32_t*>(pool_at((warp < 10 ? NSLOT : cta) * 8192 + (warp & 1) * 4096)) + (warp < 10 ? (cta & 127) * 8 : 0);
      if (lane < 8) stg_strong32(q + lane, 0u);
      uint32_t best = ~0u;
      if (lane == 0) {
        for (int r = 0; r < FK_REP; r++) {
          uint32_t t0, t1, v;
          asm volatile("mov.u32 %0, %%clock;" : "=r"(t0) :: "memory");
          asm volatile("atom.relaxed.gpu.global.exch.b32 %0, [%1], 0;" : "=r"(v) : "l"(q) : "memory");
          asm volatile("{.reg .u32 t; add.u32 t, %1, 1; mov.u32 %0, %%clock; sub.u32 %0, %0, %1;}" : "=r"(t1) : "r"(__shfl_sync(1u, v, 0)) : "memory");
          best = min(best, t1 - t0);
        }
        lat[warp - 8] = best;
      }
    }
    __syncwarp();
    bar_sync(2, cta < 128 ? 384 : 128);
    if (threadIdx.x == 288) for (int i = 0; i < FK_PF; i++) prefetch_weights(wa, i);
    if (threadIdx.x == 256) {
      const int part = lat[0] < lat[1] ? 0 : 1;
      uint32_t smid; asm("mov.u32 %0, %%smid;" : "=r"(smid));
      g_smpart[smid & 255] = part;
      g_smclk[smid & 255] = clk32() - gtime() * 2;
      g_smuse[smid & 255] = 0;
      if (cta < NSLOT) g_orient[cta] = lat[2] < lat[3] ? part : 1 - part;
    }
  } else if (cta < 128) {
    float4 v[2][5];
#pragma unroll
    for (int r = 0; r < 2; r++)
#pragma unroll
      for (int i = 0; i < 5; i++) {
        const uint32_t* src = reinterpret_cast<const uint32_t*>(xin) + (cta * 16 + r * 8 + (lane >> 2)) * (DM / 2) + warp * 40 + i * 8 + (lane & 3);
        const uint32_t a = src[0], b = src[4];
        v[r][i] = make_float4(bf_lo(a), bf_hi(a), bf_lo(b), bf_hi(b));
      }
    uint4 w8[2];
#pragma unroll
    for (int i = 0; i < 2; i++) w8[i] = wb[cta * 400 + min(i * 256 + threadIdx.x, 399)];
    float mean[2], rs[2];
    ln_stats<2>(v, s2u(scratch), mean, rs);
    bar_sync(2, 384);
    ABT(2, 2);
    if (threadIdx.x < 128) g_stat[cta * 128 + threadIdx.x] = make_float2(0.f, 0.f);
#pragma unroll
    for (int i = 0; i < 10; i++) g_x[((cta * 2 + i / 5) * 40 + warp * 5 + i % 5) * 32 + lane] = v[i / 5][i % 5];
    uint32_t w[2][5][2];
#pragma unroll
    for (int i = 0; i < 10; i++) {
      const float4 t = v[i / 5][i % 5];
      const float m = mean[i / 5], q = rs[i / 5];
      w[i / 5][i % 5][0] = pack2((t.x - m) * q, (t.y - m) * q); w[i / 5][i % 5][1] = pack2((t.z - m) * q, (t.w - m) * q);
    }
    ln_store(w, cta, warp * 5);
    ABT(2, 3);
#pragma unroll
    for (int i = 0; i < 2; i++) {
      const int e = cta * 400 + min(i * 256 + threadIdx.x, 399), k = e / 80, n = e - k * 80, cg = n / 10;
      g_wb[((cg * 80 + (k >> 3)) * 10 + n - cg * 10) * 8 + (k & 7)] = w8[i];
    }
  } else if (cta == 128) {
    g_bo[threadIdx.x] = 0;
  }
  TRACE(2);
}

struct ChainParams {
  CUtensorMap wq, wk, wv, wo;
  const __nv_bfloat16* mem0;
  uint8_t *pool, *kv;
  const uint32_t* xc;
  uint32_t* sync;
  int layer;
  int d0, d3, d1, d1b, d2, d2b, mode;
};
constexpr int CH_WQ = 0, CH_WO = 81920, CH_X = CH_WO + 86016, CH_M = CH_X + 20480, CH_KT = CH_X + 40960, CH_VT = CH_KT + 4096,
              CH_PS = CH_VT + 4096, CH_QK = CH_PS + 4096, CH_VP = CH_QK + 4096, CH_SX = CH_VP + 1024, CH_O = CH_SX + 2304, CH_ID = CH_O + 3072,
              CH_BAR = CH_ID + 512;
constexpr int CH_SMEM = CH_BAR + 256;
constexpr int CH_BASE = 1024;
#define CH_VK0 8
#define CH_VK1 20
#define CH_L0 4
#define CH_LR 4
#define NOX 0
#define CH_XA 1
#define CH_XB 4
#define CH_W1 3
#define CH_W2 17
#define CH_W3 26
#define CH_R2 8
#define CH_VA 16
#define CH_EX 1
#define CH_KD 0
#define CH_RP 1
#define CH_KF 10
#define CH_LO 0
#define CH_LR1 4
#define CH_KP 0
#define CH_KM 0
#define CH_WE 0
#define CH_SP 1
#define CH_KW 3
#define CH_RB 0
#define CH_RC 8
#define CH_D0 200
#define CH_D1 450
#define CH_D2 300
#define CH_R1 4
#define CH_TW 12
__device__ __forceinline__ uint32_t opaque(uint32_t x) { return __shfl_sync(~0u, x, threadIdx.x & 31); }
__device__ __forceinline__ uint32_t nz(uint32_t x) { uint32_t r; asm("max.u32 %0, %1, 1;" : "=r"(r) : "r"(x)); return r; }
__device__ __forceinline__ uint32_t pack_tag(float lo, float hi, uint32_t tag, uint32_t mask) {
  uint32_t r;
  asm("lop3.b32 %0, %1, %2, %3, 0xD8;" : "=r"(r) : "r"(pack2(lo, hi)), "r"(tag), "r"(mask));
  return r;
}
__device__ __forceinline__ uint32_t differ(uint32_t a, uint32_t b, uint32_t t) { uint32_t r; asm("lop3.b32 %0, %1, %2, %3, 0x7E;" : "=r"(r) : "r"(a), "r"(b), "r"(t)); return r; }
__device__ __forceinline__ void mbar_wait_hot(uint32_t bar, uint32_t ph) {
  uint32_t ok;
  asm volatile("{.reg .pred p; mbarrier.try_wait.parity.shared::cta.b64 p, [%1], %2; selp.u32 %0, 1, 0, p;}" : "=r"(ok) : "r"(bar), "r"(ph) : "memory");
  if (__builtin_expect(!ok, 0)) mbar_wait(bar, ph);
}
__device__ __forceinline__ bool elect() {
  uint32_t r; asm volatile("{.reg .pred p; elect.sync _|p, 0xffffffff; selp.u32 %0, 1, 0, p;}" : "=r"(r)); return r; }
__device__ __forceinline__ uint32_t or3(uint32_t a, uint32_t b, uint32_t c) { uint32_t r; asm("lop3.b32 %0, %1, %2, %3, 0xFE;" : "=r"(r) : "r"(a), "r"(b), "r"(c)); return r; }
__device__ __forceinline__ void pin() { pdl_launch(); }
__device__ __forceinline__ void mma16h(float* d, uint32_t a0, uint32_t a2, uint32_t b0, uint32_t b1) {
  asm volatile("{.reg .b32 u, v; mma.sync.aligned.m16n8k16.row.col.f32.bf16.bf16.f32 {%0,%1,%2,%3},{%4,u,%5,v},{%6,%7},{%0,%1,%2,%3};}"
               : "+f"(d[0]), "+f"(d[1]), "+f"(d[2]), "+f"(d[3]) : "r"(a0), "r"(a2), "r"(b0), "r"(b1)); }
__device__ __forceinline__ void mma8h(float* d, uint32_t a0, uint32_t b0) {
  asm volatile("{.reg .b32 u; mma.sync.aligned.m16n8k8.row.col.f32.bf16.bf16.f32 {%0,%1,%2,%3},{%4,u},{%5},{%0,%1,%2,%3};}"
               : "+f"(d[0]), "+f"(d[1]), "+f"(d[2]), "+f"(d[3]) : "r"(a0), "r"(b0)); }
__device__ __forceinline__ uint32_t absmax2(uint32_t a, uint32_t b) { uint32_t r; asm("max.xorsign.abs.bf16x2 %0, %1, %2;" : "=r"(r) : "r"(a), "r"(b)); return r; }
__device__ __forceinline__ void until(uint32_t t) { while ((int)(clk32() - t) < 0) {} }
__device__ __forceinline__ uint4 pack8(const float* d) { return make_uint4(pack2(d[0], d[1]), pack2(d[2], d[3]), pack2(d[4], d[5]), pack2(d[6], d[7])); }
__device__ __forceinline__ void add8(float* d, uint4 v) {
  d[0] += bf_lo(v.x); d[1] += bf_hi(v.x); d[2] += bf_lo(v.y); d[3] += bf_hi(v.y);
  d[4] += bf_lo(v.z); d[5] += bf_hi(v.z); d[6] += bf_lo(v.w); d[7] += bf_hi(v.w);
}

template <int WG>
__device__ __forceinline__ void chain_body(const ChainParams& p, const uint32_t wq, const uint32_t (&ak)[80], const uint32_t (&av)[80]) {
  const int tid = threadIdx.x & 127, t4 = __shfl_sync(~0u, tid >> 5, 0), lane = tid & 31;
  const int cta = blockIdx.x, h = cta / 3, j = cta - 3 * h;
  const uint32_t sb = mapa(CH_BASE, j);
  const uint32_t bWo = sb + CH_BAR, bWq = bWo + 8, bX = bWo + 16, bXA = bWo + 24, bXB = bWo + 32, bO = bWo + 40, bG = bWo + 48, bH = bWo + 96;
  uint32_t tw[4 * CH_TW];
  auto refill = [&]() {
#pragma unroll
    for (int k = 0; k < CH_TW; k++) ldsm4t(&tw[4 * k], wq + k * 2048);
  };
  const uint32_t wo = opaque((sb + CH_WO + (WG == 0 ? (t4 + (j == 2)) * 4096 : (j == 2 ? 0 : 24576) + t4 * 1024) + ((lane & 7) + (lane >> 4) * 8) * 64 +
                              ((((lane >> 3) & 1) ^ ((lane >> 1) & 3)) << 4)) ^ (WG == 1 && j == 2 ? 32 : 0));
  const uint32_t wo2 = opaque((wo ^ ((t4 & 1) * 32)) + (4 + (t4 >> 1) - t4) * 4096);
  const uint32_t l16 = opaque(sb + lane * 16);
  const uint32_t l8 = opaque(sb + t4 * 256 + lane * 8);
  const uint32_t lw = opaque(sb + t4 * 1024 + lane * 16);
  const uint32_t qs = opaque(sb + CH_QK + WG * 2048 + t4 * 512 + lane * 16);
  const uint32_t qa = opaque(sb + CH_QK + (lane >> 4) * 2048 + (lane & 15) * 16 + (WG == 0 ? t4 * 512 + 256 : t4 == 3 ? 1024 : 0));
  const uint32_t ka = opaque(t4 < 2 ? sb + CH_KT + t4 * 512 + lane * 16
                                    : sb + CH_QK + 256 + (t4 - 2) * 1024 + ((lane >> 3) & 1) * 2048 + (lane >> 4) * 128 + (lane & 7) * 16);
  const uint32_t l4 = opaque(sb + t4 * 256 + lane * 4);
  uint32_t pdst[1], pages = 0;
  auto line0 = [&](int i) { return 28 * j + (i < 4 ? 4 * t4 + i : 12 + 2 * t4 + i); };
  const uint32_t plane = opaque((lane >> 4) * 2048 + h * 64 + (lane & 15) * 4);
  if (WG == 0) {
    pages = __ballot_sync(~0u, lds32(sb + CH_O + line0(min(lane, 5)) * 4) & 4096);
  } else {
    pages = __ballot_sync(~0u, lds32(sb + CH_O + (80 + min(lane, 11)) * 4) & 4096);
    pdst[0] = opaque(lds32(sb + CH_O + (j == 0 ? 24 + t4 : 50 + 2 * j + (t4 & 1)) * 4) + plane);
  }
  const uint32_t role = lds32(sb + CH_O + NSLOT * 4), rsrc = lds32(sb + CH_O + role * 4), rdst = (80 + role / 20) * 8192 + role % 20 * 128;
  const uint32_t r1 = mapa(CH_BASE, j == 2 ? 0 : j + 1) - sb, r2 = mapa(CH_BASE, j == 0 ? 2 : j - 1) - sb;
  uint32_t tag = opaque(1);
  auto pool = [&](uint32_t off) { return p.pool + ((tag & 0xfffe) + off); };
  auto after = [&](uint32_t x) { return x & tag & 0xfffe; };
  auto kv = [&](int s, uint32_t a) { return p.kv + (a + ((cta * 2 * NSEG + s) * KV_BYTES - sb)); };
  auto pass = [&](float (&d)[16], const uint32_t (&a)[80], auto k0, auto k1) {
    const uint64_t db = mkdesc(CH_BASE + CH_X + WG * 20480, 512, 128, 0);
#pragma unroll
    for (int k = k0.value; k < k1.value; k++) wg_rs32_00(d, a[4 * k], a[4 * k + 1], a[4 * k + 2], a[4 * k + 3], db + k * 64, k);
    wg_commit();
  };
  auto dump = [&](float (&d)[16], uint32_t a) {
    reg_fence<16>(d);
    sts128(a, pack8(d)); sts128(a + 512, pack8(d + 8));
  };
  uint32_t pph = 0;
  auto tokens0 = [&](int s, auto k0) {
    float dk[16], dv[16];
    bar_sync(9, 256);
    wg_fence();
    pass(dk, ak, Int<0>(), Int<4>());
    const uint4 a0 = lds128(lw + CH_KT), a1 = lds128(lw + CH_KT + 512);
    pin();
    pass(dk, ak, Int<4>(), Int<20>());
    pass(dv, av, Int<0>(), Int<CH_VA>());
    pin();
    wg_wait<1>();
    reg_fence<16>(dk);
    add8(dk, a0); add8(dk + 8, a1);
    const uint4 w0 = pack8(dk), w1 = pack8(dk + 8);
    const uint4 b0 = lds128(lw + CH_VT), b1 = lds128(lw + CH_VT + 512);
    stsm4t(lw + CH_KT, w0.x, w0.z, w0.y, w0.w); stsm4t(lw + CH_KT + 512, w1.x, w1.z, w1.y, w1.w);
    if (CH_KP == 2) bar_arrive(7, 160);
    TM1(6);
    pin();
    if (CH_VA < 20) pass(dv, av, Int<CH_VA>(), Int<20>());
    pin();
#pragma unroll
    for (int k = k0.value; k < CH_TW; k++) ldsm4t(&tw[4 * k], wq + k * 2048);
    TM1(9);
    if (k0.value < CH_TW && t4 >= 2) { mbar_wait_hot(bH + t4 * 16 - 24 + (pph & 1) * 8, pph >> 1 & 1); pph++; }
    __syncwarp();
    wg_wait<0>();
    reg_fence<16>(dv);
    add8(dv, b0); add8(dv + 8, b1);
#pragma unroll
    for (int e = 0; e < 2; e++) { const uint4 v = pack8(dv + 8 * e); sts128(lw + CH_VT + e * 512, make_uint4(v.x, v.z, v.y, v.w)); }
  };
  auto publish_k = [&](int s) {
    if (t4 == CH_KW && elect()) { fence_async(); bulk_store(p.kv + (size_t)(cta * 2 * NSEG + s) * KV_BYTES, sb + CH_KT, 4096); bulk_commit(); }
    __syncwarp();
  };
  if (WG == 0) {
    mbar_wait(bXB, 0);
    tokens0(0, Int<CH_TW>());
  } else {
    const uint32_t* m0 = reinterpret_cast<const uint32_t*>(p.mem0) + (lane >> 2) * 320 + t4 * 80 + (lane & 3);
    uint32_t a[20];
#pragma unroll
    for (int i = 0; i < 20; i++) a[i] = m0[4 * i];
    pin();
    float dk[16], dv[16];
    mbar_wait(bXA, 0);
    wg_fence();
    pass(dk, ak, Int<0>(), Int<20>());
    pass(dv, av, Int<0>(), Int<20>());
    wg_wait<0>();
    dump(dk, lw + CH_KT);
    dump(dv, lw + CH_VT);
    bar_sync(9, 256);
    if (CH_KP == 2 && t4 == CH_KW) { bar_sync(7, 160); publish_k(0); }
#pragma unroll
    for (int i = 0; i < 20; i++) sts32(sb + CH_M + (t4 * 20 + i) * 128 + lane * 4, nz(transpose8(a[i])));
    __syncwarp();
    if (elect()) mbar_arrive(bG + t4 * 8);
  }
  PRO(8);
  mbar_wait(bWq, 0);
  refill();
  PRO(9);
  mbar_wait(bWo, 0);
  asm volatile("barrier.cluster.wait.aligned;" ::: "memory");
  PRO(10);
  auto load_x = [&](int s, int k0, int n, uint32_t bar) {
    if (!NOX && elect()) { mbar_expect(bar, n * 1024); bulk_load(sb + CH_X + k0 * 1024, p.xc + (s + 1) * 10240 + k0 * 256, n * 1024, bar); }
  };
  constexpr int VK = WG == 0 ? CH_VK0 : CH_VK1;
  uint32_t gph = 0;
  int st = 0;
  const uint32_t ca = opaque(sb + CH_M + t4 * 2560 + lane * 32 + (lane >> 2) * 4);
  auto project = [&](int s, uint32_t (&b)[40], float (&dv)[16], uint32_t (&kf)[16]) {
    float dq[4] = {}, dk[4] = {};
    uint32_t w[80];
#pragma unroll
    for (int i = 0; i < 4 * CH_TW; i++) w[i] = tw[i];
    constexpr int LR = WG == 1 ? CH_LR1 : CH_LR;
    auto load = [&](int n) {
      int c = 0;
#pragma unroll
      for (int i = 0; i < 10; i++) {
        if (i == CH_KF) {
#pragma unroll
          for (int q = 0; q < 4; q++)
            if (WG == 1 && c++ == n) ldsm4(&kf[4 * q], ka + q * 1024);
        }
        if (c++ == n) ldsm4t(&b[4 * i], l16 + CH_M + WG * 5120 + i * 512);
#pragma unroll
        for (int k = 2 * i; k < 2 * i + 2; k++)
          if (k >= CH_TW && c++ == n) ldsm4t(&w[4 * k], wq + k * 2048);
      }
#pragma unroll
      for (int i = 0; i < 4; i++)
        if (WG == 1 && CH_KF >= 10 && c++ == n) ldsm4(&kf[4 * i], ka + i * 1024);
    };
    if (WG == 1) {
      for (int n = 0;;) {
        mbar_wait(bG + t4 * 8, gph);
        TR(5, (clk32() & ~3u) | min(n, 3));
        gph ^= 1;
        if (__builtin_expect(!__any_sync(~0u, __vimin3_u32(lds32(ca), lds32(ca + 1024), lds32(ca + 1536)) == 0), 1)) break;
        if (elect()) {
          const int q = (st == 0 ? 8 : st * 4 - 4) + t4;
          mbar_expect(bG + t4 * 8, 2560);
          bulk_load(sb + CH_M + t4 * 2560, p.pool + ((80 + q) * 8192 + (pages >> q & 1) * 4096), 2560, bG + t4 * 8);
        }
        spin_guard(n);
      }
    }
    bar_sync(6, 256);
#pragma unroll
    for (int i = 0; i < CH_L0; i++) load(i);
    if (WG == 0 && CH_XB == 4 && s + 1 < NSEG) load_x(s, 5 * t4, 5, bXB);
    TM(0);
    TM1(11);
    if (WG == 1) TR(6, clk32());
#pragma unroll
    for (int k = 0; k < 20; k += 2) {
      if (k > 0) {
#pragma unroll
        for (int n = (k == 18 ? 40 : CH_L0 + k * LR / 4) - 1; n >= CH_L0 + (k - 2) * LR / 4; n--) { load(n); if (CH_LO) __syncwarp(); }
      }
      pin();
#pragma unroll
      for (int kk = k; kk < k + 2; kk++) {
        mma16(dk, ak[4 * kk], ak[4 * kk + 1], ak[4 * kk + 2], ak[4 * kk + 3], b[2 * kk], b[2 * kk + 1]);
        mma16(dq, w[4 * kk], w[4 * kk + 1], w[4 * kk + 2], w[4 * kk + 3], b[2 * kk], b[2 * kk + 1]);
        if (kk < VK) mma16(dv, av[4 * kk], av[4 * kk + 1], av[4 * kk + 2], av[4 * kk + 3], b[2 * kk], b[2 * kk + 1]);
      }
    }
    const float k2 = 0.07216878364870322f * 1.44269504089f;
    stsm4t(qs, pack2(dq[0] * k2, dq[1] * k2), pack2(dq[2] * k2, dq[3] * k2), pack2(dk[0], dk[1]), pack2(dk[2], dk[3]));
    TM(1);
  };
  static_assert(CH_VK1 == 20 && CH_KP == 0 && CH_XA > 0 && CH_XB > 0, "last step");
  constexpr int VC = VK == 20 ? 1 : WG == 0 ? 2 : 3;
  auto finish_v = [&](const uint32_t (&b)[40], float (&dv)[16]) {
#pragma unroll
    for (int kk = VK; kk < 20; kk++) mma16(dv + 4 * ((kk - VK) % VC), av[4 * kk], av[4 * kk + 1], av[4 * kk + 2], av[4 * kk + 3], b[2 * kk], b[2 * kk + 1]);
  };
  auto sum_v = [&](float (&dv)[16]) {
#pragma unroll
    for (int i = 4; i < 4 * VC; i++) dv[i & 3] += dv[i];
  };
  auto publish_km = [&](int s) {
    uint32_t a[4];
    ldsm4(a, qa);
    *reinterpret_cast<uint2*>(kv(s, l8) + KV_M) = make_uint2(hadd2(a[0], a[2]), hadd2(a[1], a[3]));
  };
  auto memory_v = [&](uint2 x, const float (&dv)[16]) {
    return make_uint2(pack2(dv[0] + bf_lo(x.x), dv[1] + bf_hi(x.x)), pack2(dv[2] + bf_lo(x.y), dv[3] + bf_hi(x.y)));
  };
  auto publish_v = [&](int s, const uint4 (&v)[2], uint2 vm) {
#pragma unroll
    for (int e = 0; e < 2; e++) reinterpret_cast<uint4*>(kv(s, lw) + KV_V)[e * 32] = v[e];
    *reinterpret_cast<uint2*>(kv(s, l8) + KV_V + KV_M) = vm;
  };
#pragma unroll 1
  for (int s = 0;; s++) {
    float dv[16] = {};
    uint32_t b[40], kf[16];
    project(s, b, dv, kf);
    if (WG == 0) {
      bar_sync(1, 256);
      if (CH_XA == 0) load_x(s, 20 + 5 * t4, 5, bXA);
      if (CH_XB == 0) load_x(s, 5 * t4, 5, bXB);
      pin();
      finish_v(b, dv);
      sum_v(dv);
      sts64(l8 + CH_VP, pack2(dv[0], dv[1]), pack2(dv[2], dv[3]));
      if (s == NSEG - 1) {
        bar_arrive(10, 256);
        publish_k(s);
        publish_km(s);
        bulk_wait<0>();
        fence_async_global();
        bar_sync(2, 256);
        if (tid == 0) red_release(p.sync + 15 * 8 + 4, 1);
        break;
      }
      __syncwarp();
      if (elect()) mbar_arrive(bX);
      if (CH_XA == 1) load_x(s, 20 + 5 * t4, 5, bXA);
      if (CH_XB == 1) load_x(s, 5 * t4, 5, bXB);
      uint32_t w[144];
      auto wload = [&](int i) { ldsm4t(&w[4 * i], (i % 3 == 0 ? wo : i % 3 == 1 ? wo ^ 32 : wo2) + i / 12 * 28672 + i / 3 % 4 * 1024); };
      TM(3);
      if (CH_KP == 0) publish_k(s);
#pragma unroll
      for (int i = 0; i < CH_W1; i++) wload(i);
      bar_sync(10, 256);
      uint32_t km[4];
      ldsm4(km, qa);
      pin();
#pragma unroll
      for (int i = CH_W1; i < CH_W2; i++) wload(i);
      pin();
      const uint2 kms = make_uint2(hadd2(km[0], km[2]), hadd2(km[1], km[3]));
      if (CH_KM == 0) *reinterpret_cast<uint2*>(kv(s, l8) + KV_M) = kms;
      if (CH_KP == 0) bulk_wait_read<0>();
      if (CH_XA == 2) load_x(s, 20 + 5 * t4, 5, bXA);
      if (CH_XB == 2) load_x(s, 5 * t4, 5, bXB);
      bar_sync(2, 256);
      {
        float y[3][4] = {};
        uint32_t ob[24];
        ldsm4(&ob[0], l16 + CH_O + 1024); ldsm4(&ob[4], l16 + CH_O + 1536);
        TM(7);
        auto step = [&](int i) {
          const int k = i / 3;
          mma16(y[i % 3], w[4 * i], w[4 * i + 1], w[4 * i + 2], w[4 * i + 3], ob[2 * k], ob[2 * k + 1]);
        };
#pragma unroll
        for (int i = 0; i < 12; i++) {
          step(i);
          if (i >= 12 - (CH_W3 - CH_W2)) wload(CH_W3 - 12 + i);
          if (i % 3 == 2) pin();
        }
        if (CH_XB == 3) load_x(s, 5 * t4, 5, bXB);
        if (CH_KM == 1) *reinterpret_cast<uint2*>(kv(s, l8) + KV_M) = kms;
        pin();
        mbar_wait(bO, s & 1);
        TM(4);
        ldsm4(&ob[8], l16 + CH_O); ldsm4(&ob[12], l16 + CH_O + 512);
        pin();
        float2 inv;
        uint8_t* dst[6];
        uint32_t mask;
#pragma unroll
        for (int i = 12; i < 36; i++) {
          step(i);
          const int n = CH_W3 + i - 13, m = n - (n > 30);
          if (i == 12) ldsm4(&ob[16], l16 + after(w[4 * CH_W3 - 1] | w[4 * CH_W3 - 5] | w[4 * CH_W3 - 9] | ob[8]) + CH_O + 2048);
          else if (n == 30) ldsm4(&ob[20], l16 + CH_O + 2560);
          else if (m < 36) wload(m);
          else if (m == 36) inv = lds64f((l8 & ~0xe0u) + CH_VP);
          if (i == 26) mask = ((l16 ^ tag) & 48) == 0;
          if (i >= 27 && i < 33) dst[i - 27] = pool(line0(i - 27) * 8192 + (pages >> (i - 27) & 1) * 4096) + plane;
          if (i % 3 == 2) pin();
        }
#pragma unroll
        for (int k = 0; k < CH_R1; k++) ldsm4t(&tw[4 * k], wq + k * 2048);
        pin();
#pragma unroll
        for (int i = 0; i < 6; i++) stg_strong32(dst[i], pack_tag(y[i >> 1][2 * (i & 1)] * inv.x, y[i >> 1][2 * (i & 1) + 1] * inv.y, tag, mask));
        TM(8);
        TR(0, clk32());
        bar_arrive(5, 256);
        pin();
      }
      const uint32_t t0 = clk32();
      auto refill2 = [&]() {
#pragma unroll
        for (int k = CH_R1; k < CH_R2; k++) ldsm4t(&tw[4 * k], wq + k * 2048);
      };
      if (CH_RP == 0) refill2();
      const uint32_t ln = (l16 ^ tag) >> 4 & 31;
      if (t4 >= 2) {
        const uint32_t bP = bH + t4 * 16 - 24, ps = CH_PS + (t4 & 1) * 4096;
        auto fetch = [&](uint32_t k) {
          if (elect()) { mbar_expect(bP + (k & 1) * 8, 2048); bulk_load(sb + ps + (k & 1) * 2048, p.pool + (rsrc + (t4 & 1) * 2048), 2048, bP + (k & 1) * 8); }
        };
        until(t0 + CH_D0);
        fetch(pph);
        if (CH_RP == 2) refill2();
        if (!NOX) mbar_wait_hot(bXB, (s + 1) & 1);
        const uint32_t want = (tag & 1) * 0x10001, chk = opaque(ln < 4 ? 0x10001 : 0);
        uint4 sel;
        sel.x = opaque((ln >> 3) != (ln & 1) ? 0 : ln & 4 ? 0x3f800000u : 0x00003f80u);
        sel.z = opaque(sel.x); sel.y = opaque(ln); sel.w = opaque(ln + 1);
        uint8_t* mdst = p.pool + opaque(st * 32768 + rdst + (t4 & 1) * 64 + ln * 4);
        until(t0 + CH_D1);
        fetch(pph + 1);
        TM(5);
        if (CH_RP == 1) refill2();
        int n = 0;
        uint32_t u[16];
        float y[4][4];
        auto sum = [&]() {
#pragma unroll
          for (int i = 0; i < 16; i++) y[i >> 2][i & 3] = 0.f;
#pragma unroll
          for (int i = 0; i < 8; i++) mma16(y[i & 3], sel.x, sel.y, sel.z, sel.w, u[2 * i], u[2 * i + 1]);
        };
        auto check = [&](auto spec) {
          mbar_wait(bP + (pph & 1) * 8, pph >> 1 & 1);
          TM(14);
          TR(2, clk32());
#pragma unroll
          for (int i = 0; i < 4; i++) ldsm4t(&u[4 * i], l16 + (ps + (pph & 1) * 2048) + i * 512);
          pph++;
          if (spec.value) { pin(); sum(); }
          uint32_t bad = 0;
#pragma unroll
          for (int i = 0; i < 4; i++) bad = or3(bad, differ(u[4 * i], u[4 * i + 1], want), differ(u[4 * i + 2], u[4 * i + 3], want));
          return __any_sync(~0u, bad & chk);
        };
        if (CH_SP) {
          if (check(Int<0>())) {
            do { fetch(pph + 1); spin_guard(n); } while (check(Int<1>()));
          } else {
            sum();
          }
        } else {
          while (check(Int<0>())) { fetch(pph + 1); spin_guard(n); }
          sum();
        }
        TR(1, t0 + (n ? CH_D1 : CH_D0));
        TM(15);
        const uint32_t w = nz(pack2((y[0][0] + y[1][0]) + (y[2][0] + y[3][0]), (y[0][1] + y[1][1]) + (y[2][1] + y[3][1])));
        if (ln < 16) { stg_strong32(mdst, w); stg_strong32(mdst + 4096, w); }
        TMV(12, 32, n);
        TR(3, (clk32() & ~3u) | min(n, 3));
      } else {
        if (CH_RP) refill2();
        if (!NOX) mbar_wait_hot(bXB, (s + 1) & 1);
        stg_strong32(p.pool + ((st == 2 ? 0 : st + 1) * 32768 + rdst + t4 * 4096) + ln * 4, 0u);
        if (t4 == 0 && cta < 40 && s + 4 < NSEG && elect())
          asm volatile("cp.async.bulk.prefetch.L2.global [%0], 1024;" :: "l"(p.xc + (s + 4) * 10240 + cta * 256) : "memory");
        if (t4 == 1 && (s & 3) == 0 && s > 0 && elect()) red_relaxed(p.sync + 2 * s - 4, 1);
        if (t4 == 1 && s == NSEG - 3 && cta == 95 && elect()) red_relaxed(p.sync + 2 * s + 2, 0x10000);
      }
      TM(10);
      bar_arrive(8, 256);
      tokens0(s + 1, Int<CH_R2>());
      TM(2);
      TR(7, clk32());
    } else {
      if (s == NSEG - 1) {
        bar_arrive(1, 256);
        const uint4 v[2] = {lds128(lw + CH_VT), lds128(lw + CH_VT + 512)};
        bar_sync(10, 256);
        publish_v(s, v, memory_v(lds64(l8 + CH_VP), dv));
        bar_arrive(2, 256);
        break;
      }
      const uint32_t xo = l4 + (CH_SX - (t4 == 3 ? 128 : 0)), x1 = xo + (r1 + 768 + min(t4, 2) * 256), x2 = xo + (r2 + 1024 + min(t4, 2) * 256);
      if (t4 < 2) {
        float ds[4][4] = {};
        uint32_t q[16];
        asm volatile("bar.sync 1, 256;" ::: "memory");
#pragma unroll
        for (int k = 0; k < 4; k++) ldsm4(&q[4 * k], qa + k * 512);
        pin();
        if (VK < 20) { finish_v(b, dv); pin(); }
#pragma unroll
        for (int k = 0; k < 4; k++) {
          mma16(ds[k & 1], kf[4 * k], kf[4 * k + 1], kf[4 * k + 2], kf[4 * k + 3], q[4 * k], q[4 * k + 1]);
          mma16(ds[2 + (k & 1)], kf[4 * k], kf[4 * k + 1], kf[4 * k + 2], kf[4 * k + 3], q[4 * k + 2], q[4 * k + 3]);
        }
        float t[4];
#pragma unroll
        for (int i = 0; i < 4; i++) t[i] = (ds[0][i] + ds[2][i]) + (ds[1][i] + ds[3][i]);
        const uint32_t w0 = pack2(t[0], t[1]), w1 = pack2(t[2], t[3]);
        st_async32(x1, w0, bX + r1); st_async32(x2, w0, bX + r2);
        st_async32(x1 + 128, w1, bX + r1); st_async32(x2 + 128, w1, bX + r2);
        sts32(xo, w0); sts32(xo + 128, w1);
      } else {
        float ds[4][4] = {};
        uint32_t q0[4], q1[4], a0[4], a1[4];
        asm volatile("bar.sync 1, 256; " ::: "memory");
        ldsm4(a0, ka); ldsm4(q0, qa); ldsm4(a1, ka + 512); ldsm4(q1, qa + 512);
        pin();
        if (VK < 20) { finish_v(b, dv); pin(); }
        mma16(ds[0], a0[0], a0[1], a0[2], a0[3], q0[0], q0[1]);
        mma16(ds[1], a0[0], a0[1], a0[2], a0[3], q0[2], q0[3]);
        mma16(ds[2], a1[0], a1[1], a1[2], a1[3], q1[0], q1[1]);
        mma16(ds[3], a1[0], a1[1], a1[2], a1[3], q1[2], q1[3]);
        float t[2];
#pragma unroll
        for (int i = 0; i < 2; i++)
          t[i] = ((ds[0][i] + ds[0][i + 2]) + (ds[1][i] + ds[1][i + 2])) + ((ds[2][i] + ds[2][i + 2]) + (ds[3][i] + ds[3][i + 2]));
        const uint32_t w0 = pack2(t[0], t[1]);
        st_async32(x1, w0, bX + r1);
        st_async32(x2, w0, bX + r2);
        sts32(xo, w0);
      }
      TM(3);
      const uint4 id = lds128(l16 + CH_ID);
      float sc[3][4] = {};
      uint4 v[2];
      sum_v(dv);
      bar_sync(3, 128);
      uint32_t r[12], wd[12], we[12] = {};
      ldsm4(&r[0], l16 + CH_SX); ldsm2(&r[4], l16 + CH_SX + 512);
      pin();
      v[0] = lds128(lw + CH_VT); v[1] = lds128(lw + CH_VT + 512);
#pragma unroll
      for (int u = 0; u < 3; u++) ldsm4t(&wd[4 * u], wo + u * 28672);
      if (CH_WE && j == 0) {
#pragma unroll
        for (int u = 0; u < 3; u++) ldsm4t(&we[4 * u], (wo ^ 32) + u * 28672);
      }
      pin();
#pragma unroll
      for (int q = 0; q < 3; q++) mma16(sc[q], id.x, id.y, id.z, id.w, r[2 * q], r[2 * q + 1]);
      uint32_t big = absmax2(absmax2(absmax2(r[0], r[1]), absmax2(r[2], r[3])), absmax2(r[4], r[5]));
      const uint32_t oa1 = l4 + (r1 + CH_O), oa2 = l4 + (r2 + CH_O + 2048), ones = 0x3f803f80u;
      mbar_wait_hot(bX, s & 1);
      TM(4);
      ldsm4(&r[0], l16 + CH_SX + 768); ldsm4(&r[8], l16 + CH_SX + 1792); ldsm4(&r[4], l16 + CH_SX + 1280);
      const uint2 vp = lds64(l8 + CH_VP);
      bar_arrive(10, 256);
      pin();
      {
        float sd[3][4] = {};
#pragma unroll
        for (int i = 0; i < 3; i++) {
          const int q = i == 0 ? 0 : 3 - i;
          mma16(sc[q], id.x, id.y, id.z, id.w, r[4 * q], r[4 * q + 1]);
          mma16(sd[q], id.x, id.y, id.z, id.w, r[4 * q + 2], r[4 * q + 3]);
          big = absmax2(big, absmax2(absmax2(r[4 * q], r[4 * q + 1]), absmax2(r[4 * q + 2], r[4 * q + 3])));
        }
#pragma unroll
        for (int i = 0; i < 12; i++) sc[i >> 2][i & 3] += sd[i >> 2][i & 3];
      }
      const bool redo = __any_sync(~0u, (absmax2(big, big << 16) & 0x7fff0000u) >= 0x41800000u);
      const uint2 vm = memory_v(vp, dv);
      sc[2][0] += sc[2][2]; sc[2][1] += sc[2][3];
      float l[4], o[2][4];
      uint32_t p3, p4;
      auto attend = [&]() {
#pragma unroll
        for (int i = 0; i < 4; i++) l[i] = o[0][i] = o[1][i] = 0.f;
        const uint32_t p1 = pack2(ex2(sc[0][0]), ex2(sc[0][1])), p2 = pack2(ex2(sc[0][2]), ex2(sc[0][3]));
        mma16h(o[0], p1, p2, v[0].x, v[0].y);
        mma16h(o[1], p1, p2, v[0].z, v[0].w);
        mma16h(l, p1, p2, ones, ones);
        const uint32_t p0 = pack2(ex2(sc[2][0]), ex2(sc[2][1]));
        mma8h(o[0], p0, vm.x);
        mma8h(o[1], p0, vm.y);
        mma8h(l, p0, ones);
        p3 = pack2(ex2(sc[1][0]), ex2(sc[1][1])); p4 = pack2(ex2(sc[1][2]), ex2(sc[1][3]));
        mma16h(o[0], p3, p4, v[1].x, v[1].y);
        mma16h(o[1], p3, p4, v[1].z, v[1].w);
      };
      attend();
      if (__builtin_expect(redo, 0)) {
        float mx = fmaxf(sc[2][0], sc[2][1]);
#pragma unroll
        for (int i = 0; i < 4; i++) mx = fmaxf(mx, fmaxf(sc[0][i], sc[1][i]));
        mx = fmaxf(mx, __shfl_xor_sync(~0u, mx, 1));
        mx = fmaxf(mx, __shfl_xor_sync(~0u, mx, 2));
#pragma unroll
        for (int i = 0; i < 4; i++) { sc[0][i] -= mx; sc[1][i] -= mx; }
        sc[2][0] -= mx; sc[2][1] -= mx;
        attend();
      }
      const uint32_t o0 = pack2(o[0][0], o[0][1]), o1 = pack2(o[1][0], o[1][1]);
      st_async32(oa1, o0, bO + r1); st_async32(oa2, o0, bO + r2);
      st_async32(oa1 + 128, o1, bO + r1); st_async32(oa2 + 128, o1, bO + r2);
      sts32(l4 + CH_O + 1024, o0); sts32(l4 + CH_O + 1152, o1);
      bar_arrive(2, 256);
      pin();
      TM(6);
      mma16h(l, p3, p4, ones, ones);
      float inv;
      asm("rcp.approx.ftz.f32 %0, %1;" : "=f"(inv) : "f"(l[0]));
      sts32((l8 & ~0xffu) + (lane & 28) + CH_VP, __float_as_uint(inv));
      __syncwarp();
      if (elect()) mbar_arrive(bO);
      {
        float z[2][4] = {}, y[2][4] = {};
        mma16(z[0], wd[0], wd[1], wd[2], wd[3], o0, o1);
        if (j == 0) {
#pragma unroll
          for (int u = 0; u < 3; u++) if (!CH_WE) ldsm4t(&we[4 * u], (wo ^ 32) + u * 28672);
          mma16(y[0], we[0], we[1], we[2], we[3], o0, o1);
        }
        const float2 iv = lds64f((l8 & ~0xe0u) + CH_VP);
        uint8_t* dst = pool(pdst[0]);
        const uint32_t mask = ((l16 ^ tag) & 48) == 0;
        const uint32_t oa = qa + ((tag & 0xfffe) + CH_O - CH_QK + t4 * 256 - (t4 == 3 ? 1024 : 0));
        const uint32_t za = l16 + ((tag & 0xfffe) + (t4 >> 1) * 512 + (t4 & 1) * 8);
        pin();
        mbar_wait(bO, s & 1);
        uint32_t a[4];
        ldsm4(a, oa);
        mma16(z[0], wd[4], wd[5], wd[6], wd[7], a[0], a[1]);
        mma16(z[1], wd[8], wd[9], wd[10], wd[11], a[2], a[3]);
        if (j == 0) {
          mma16(y[0], we[4], we[5], we[6], we[7], a[0], a[1]);
          mma16(y[1], we[8], we[9], we[10], we[11], a[2], a[3]);
          sts128f(lw + CH_VT + 512, y[0][0] + y[1][0], y[0][1] + y[1][1], y[0][2] + y[1][2], y[0][3] + y[1][3]);
        }
        sts128f(lw + CH_VT, z[0][0] + z[1][0], z[0][1] + z[1][1], z[0][2] + z[1][2], z[0][3] + z[1][3]);
        bar_sync(3, 128);
        if (j == 0 || t4 < 2) {
          float2 q[4];
#pragma unroll
          for (int i = 0; i < 4; i++) q[i] = lds64f(za + CH_VT + i * 1024);
          stg_strong32(dst, pack_tag(((q[0].x + q[1].x) + (q[2].x + q[3].x)) * iv.x, ((q[0].y + q[1].y) + (q[2].y + q[3].y)) * iv.y, tag, mask));
        }
      }
      TM(2);
      if (!NOX) mbar_wait_hot(bXA, (s + 1) & 1);
      if (CH_KP == 2) bulk_wait_read<0>();
      float dk[16], dw[16];
      bar_sync(5, 256);
      wg_fence();
      pass(dk, ak, Int<0>(), Int<20>());
      pass(dw, av, Int<0>(), Int<20>());
      TM(5);
      pin();
      if (CH_EX == 0) publish_v(s, v, vm);
      if (elect()) {
        mbar_expect(bG + t4 * 8, 2560);
        if (t4 == 1 && s + 2 < NSEG) { mbar_expect(bX, 1536); mbar_expect(bO, 2048); }
      }
      if (CH_KD == 0) { wg_wait<1>(); dump(dk, lw + CH_KT); }
      wg_wait<0>();
      if (CH_KD == 1) dump(dk, lw + CH_KT);
      TM(7);
      dump(dw, lw + CH_VT);
      bar_arrive(9, 256);
      pin();
#pragma unroll
      for (int k = 0; k < CH_RB; k++) ldsm4t(&tw[4 * k], wq + k * 2048);
      if (t4 < 2) {
        if (CH_EX == 2) { publish_v(s, v, vm); pin(); }
#pragma unroll
        for (int k = CH_RB; k < CH_RC; k++) ldsm4t(&tw[4 * k], wq + k * 2048);
        const int q = t4 ? 3 : j, o = t4 ? j * 896 : 0;
        const uint8_t* src = p.pool + ((80 + st * 4 + q) * 8192 + (pages >> (st * 4 + q) & 1) * 4096 + o);
        asm volatile("bar.sync 8, 256;" ::: "memory");
        const uint32_t t1 = clk32() + CH_D2;
        if (CH_EX == 1) publish_v(s, v, vm);
        auto fetch = [&](auto n) {
          mbar_wait(bH, s & 1);
          until(t1);
          TR(4, clk32());
          if (elect())
            asm volatile("cp.async.bulk.shared::cluster.global.mbarrier::complete_tx::bytes.multicast::cluster [%0], [%1], %2, [%3], 7;"
                         :: "r"(sb + CH_M + q * 2560 + o), "l"(src), "n"(n.value), "r"(bG + q * 8) : "memory");
        };
        if (!t4) fetch(Int<2560>()); else if (j == 2) fetch(Int<768>()); else fetch(Int<896>());
      } else {
        asm volatile("bar.sync 8, 256; " ::: "memory");
        if (elect()) asm volatile("mbarrier.arrive.relaxed.cluster.shared::cluster.b64 _, [%0];" :: "r"(bH + (t4 == 2 ? r1 : r2)) : "memory");
        pin();
        if (CH_EX) publish_v(s, v, vm);
#pragma unroll
        for (int k = CH_RB; k < CH_RC; k++) ldsm4t(&tw[4 * k], wq + k * 2048);
      }
      TM(9);
      pin();
#pragma unroll
      for (int k = CH_RC; k < CH_TW; k++) ldsm4t(&tw[4 * k], wq + k * 2048);
      if (CH_KP == 2 && t4 == CH_KW) { bar_sync(7, 160); publish_k(s + 1); }
      TM(10);
    }
    if (++st == 3) st = 0;
    tag ^= 0x10001;
  }
}

__global__ void __launch_bounds__(256, 1) chain_kernel(const __grid_constant__ ChainParams p) {
  extern __shared__ __align__(1024) uint8_t smem_raw[];
  const uint32_t sb = s2u(smem_raw);
  const int tid = threadIdx.x, warp = __shfl_sync(~0u, tid >> 5, 0), lane = tid & 31;
  const int cta = blockIdx.x, h = cta / 3, j = cta - 3 * h, colbase = cta * 64;
  const uint32_t bWo = sb + CH_BAR, bWq = bWo + 8, bXA = bWo + 24, bWk = bWo + 80, bWv = bWo + 88;
  uint32_t smid; asm("mov.u32 %0, %%smid;" : "=r"(smid));
  PRO(0);
  if (sb != mapa(CH_BASE, j)) __trap();
  uint32_t entry = 0;
  auto place = [&]() {
    const int i = tid - 128;
    if (i >= 0 && i <= NSLOT) {
      const uint32_t side = ldg_strong32(g_smpart + (smid & 255));
      if (i < NSLOT) {
        entry = i * 8192 + (ldg_strong32(g_orient + i) == (i < 80 ? i & 1 : side) ? 0 : 4096);
      } else {
        entry = 2 * (atomicAdd(g_bo + p.layer * 128 + 1, 1 << 8 * side) >> 8 * side & 255) + side;
      }
    }
    __syncwarp();
  };
  if (p.layer) place();
  if (warp == 0 && elect()) {
#pragma unroll 1
    for (int i = 0; i < 17; i++) mbar_init(bWo + 8 * i, i == 2 || i == 5 ? 5 : i == 3 || i == 4 ? 4 : i == 12 ? 2 : 1);
    asm volatile("fence.mbarrier_init.release.cluster;" ::: "memory");
    mbar_expect(bWk, 81920);
    tma_load3<(WEF & 1) != 0>(sb + CH_WQ, &p.wk, colbase, 0, bWk);
    mbar_expect(bWv, 81920);
    tma_load3<(WEF & 1) != 0>(sb + CH_WO, &p.wv, colbase, 0, bWv);
    mbar_expect(bWo + 16, 1536);
    mbar_expect(bWo + 40, 2048);
    mbar_expect(bWo, 86016); mbar_expect(bWq, 81920);
#pragma unroll 1
    for (int i = 0; i < 8; i++) mbar_expect(bXA + 8 * (i & 1), 5120);
  }
  if (warp == 1) {
    const uint32_t id = (lane >> 3) == (lane & 3) ? ((lane & 4) ? 0x3f800000u : 0x00003f80u) : 0u;
    sts128(sb + CH_ID + lane * 16, make_uint4(id, 0, 0, id));
  }
  __syncthreads();
  asm volatile("barrier.cluster.arrive.relaxed.aligned;" ::: "memory");
  uint32_t ak[80], av[80];
  const uint32_t wq = opaque(sb + CH_WQ + ((warp >> 2) * 320 + (lane & 7) + (lane >> 4) * 8) * 128 + (((2 * (warp & 3) + ((lane >> 3) & 1)) ^ (lane & 7)) << 4));
  pdl_wait();
  if (tid == 32) stg_strong32(g_smuse + (smid & 255), p.layer + 1);
  pdl_launch();
  PRO(1);
  if (warp == 0 && elect()) {
    bulk_load(sb + CH_X + 20480, p.xc + 5120, 20480, bXA);
    bulk_load(sb + CH_X, p.xc, 20480, bXA + 8);
  }
  if (!p.layer) place();
  __syncwarp();
  PRO(2);
  mbar_wait(bWk, 0);
  PRO(3);
#pragma unroll
  for (int k = 0; k < 20; k++) ldsm4t(&ak[4 * k], wq + k * 2048);
  bar_sync(6, 256);
  if (warp == 0 && elect()) tma_load3<(WEF & 2) != 0>(sb + CH_WQ, &p.wq, colbase, 0, bWq);
  __syncwarp();
  PRO(4);
  mbar_wait(bWv, 0);
  PRO(5);
#pragma unroll
  for (int k = 0; k < 20; k++) ldsm4t(&av[4 * k], wq + CH_WO + k * 2048);
  bar_sync(6, 256);
  PRO(6);
  if (warp >= 5 && elect()) tma_load3<(WEF & 2) != 0>(sb + CH_WO + (warp - 5) * 28672, &p.wo, j == 0 ? 0 : 32 + j * 192, h * 192 + (j + 8 - warp) % 3 * 64, bWo);
  if (tid == 128 + NSLOT && entry >= 80) {
    uint32_t c;
    int n = 0;
    do { c = ldg_strong32(g_bo + p.layer * 128 + 1); spin_guard(n); } while ((c & 255) + (c >> 8) < 96);
    const uint32_t other = (c >> 8 * (~entry & 1) & 255) + (entry >> 1) - 40;
    entry = other < 40 ? 2 * other + (~entry & 1) : entry % 80;
  }
  if (tid >= 128 && tid <= 128 + NSLOT) sts32(sb + CH_O + (tid - 128) * 4, entry);
  PRO(7);
  __syncthreads();
  if (__shfl_sync(~0u, tid >> 7, 0) == 0) chain_body<0>(p, wq, ak, av); else chain_body<1>(p, wq, ak, av);
}

struct PostParams { CUtensorMap wq, wo, wb, wo2, wb2; int gap, share, layer, look, gap2, pol; };
constexpr int PS = 8, PB = 28672;
constexpr int OP_SMEM = PS * PB + 512 + 2048;
enum { IT_ATT = 0, IT_OP = 1, IT_FIN = 2, IT_BQ = 3, IT_Q = 4 };

__device__ __forceinline__ uint32_t item_count(int type, int b) {
  return type == IT_ATT ? 32 : type == IT_OP ? op_split(b) * (b < OP_160 ? 2 : 4) : type == IT_FIN ? fin_items(b) : b < BQ_160 ? 6 : b < BQ_80 ? 12 : 24; }
__device__ __forceinline__ uint32_t item_need(int type, int b) { return type == IT_ATT ? 96 : item_count(type - 1, b); }

struct Ring {
  uint32_t sb, bars; int st; uint32_t ph;
  __device__ __forceinline__ uint32_t wait() const { mbar_wait(bars + 8 * st, ph); return sb + st * PB; }
  __device__ __forceinline__ void next() { if (++st == PS) { st = 0; ph ^= 1; } }
  __device__ __forceinline__ void release(int s) const { if ((threadIdx.x & 31) == 0) mbar_arrive(bars + 8 * (PS + s)); }
  __device__ __forceinline__ void pop() { __syncwarp(); release(st); next(); }
};

template <int N>
__device__ __forceinline__ void gemm_item(Ring& r, float* d, int nst, uint32_t go, int go_at) {
  int prev = 0;
#pragma unroll 1
  for (int kb = 0; kb < nst; kb++) {
    const uint32_t base = r.wait();
    const uint64_t da = mkdesc(base + (threadIdx.x >> 7) * 4096, 128, 512, 0), db = mkdesc(base + 8192, 4096, 1024, 1);
    wg_fence();
#pragma unroll
    for (int kk = 0; kk < 2; kk++) {
      if (N == 80) wg_ss80_01(d, da + kk * 16, db + kk * 128, (kb | kk) != 0);
      if (N == 160) wg_ss160_01(d, da + kk * 16, db + kk * 128, (kb | kk) != 0);
      if (N >= 192) wg_ss192_01(d, da + kk * 16, db + kk * 128, (kb | kk) != 0);
      if (N == 320) wg_ss128_01(d + 96, da + kk * 16, db + kk * 128 + 3 * 256, (kb | kk) != 0);
    }
    wg_commit();
    if (kb == go_at && threadIdx.x == 0) mbar_arrive(go);
    if (kb > 0) { wg_wait<1>(); r.release(prev); }
    prev = r.st;
    r.next();
  }
  wg_wait<0>();
  reg_fence<N / 2>(d);
  r.release(prev);
}

template <int HALF>
__device__ __forceinline__ void attn_a_warp(Ring& r, const uint32_t (&q)[48], int b, int h) {
  constexpr int NT = HALF ? 5 : 3, NF = 8 * NT;
  const int lane = threadIdx.x & 31, g = lane >> 2, c = lane & 3, seg = (threadIdx.x >> 5) & 3;
  uint32_t f[6][NF];
  int slot[6];
  auto fetch = [&](int u) {
    const uint32_t kv = r.wait() + seg * KV_BYTES;
    slot[u] = r.st;
    r.next();
#pragma unroll
    for (int w = 0; w < 4; w++) {
      uint32_t* d = &f[u][2 * NT * w];
#pragma unroll
      for (int t = 0; t <= HALF; t++) {
        if (u < 3) {
          ldsm4(d + 4 * t, kv + w * 1024 + t * 512 + (lane & 8) * 32 + (lane & 16) * 8 + (lane & 7) * 16);
        } else {
          const uint4 v = lds128(kv + w * 1024 + t * 512 + lane * 16);
          d[4 * t] = v.x; d[4 * t + 1] = v.y; d[4 * t + 2] = v.z; d[4 * t + 3] = v.w;
        }
      }
      const uint2 m = lds64(kv + KV_M + w * 256 + lane * 8);
      d[2 * NT - 2] = m.x; d[2 * NT - 1] = m.y;
    }
    pdl_launch();
  };
  float s[NT][4] = {};
  fetch(0);
#pragma unroll
  for (int u = 0; u < 3; u++) {
    fetch(u + 1);
#pragma unroll
    for (int kk = 0; kk < 4; kk++) {
      const uint32_t* a = &q[16 * u + 4 * kk];
#pragma unroll
      for (int n = 0; n < NT; n++) mma16(s[(n + 1) % NT], a[0], a[1], a[2], a[3], f[u][2 * NT * kk + 2 * n], f[u][2 * NT * kk + 2 * n + 1]);
    }
    r.release(slot[u]);
    pdl_launch();
  }
  fetch(4);
  const float k2 = 0.07216878364870322f * 1.44269504089f, NEG = -INFINITY;
  if (2 * c > g) { s[NT - 2][0] = NEG; s[NT - 1][2] = NEG; }
  if (2 * c + 1 > g) { s[NT - 2][1] = NEG; s[NT - 1][3] = NEG; }
  s[NT - 1][0] = s[NT - 1][1] = NEG;
  uint32_t pp[NT][2]; float inv[2];
#pragma unroll
  for (int hh = 0; hh < 2; hh++) {
    float m = NEG, l = 0.f;
#pragma unroll
    for (int n = 0; n < NT; n++) m = fmaxf(m, fmaxf(s[n][2 * hh], s[n][2 * hh + 1]));
    m = fmaxf(m, __shfl_xor_sync(~0u, m, 1)); m = fmaxf(m, __shfl_xor_sync(~0u, m, 2));
#pragma unroll
    for (int n = 0; n < NT; n++) { const float x = ex2((s[n][2 * hh] - m) * k2), y = ex2((s[n][2 * hh + 1] - m) * k2); l += x + y; pp[n][hh] = pack2(x, y); }
    l += __shfl_xor_sync(~0u, l, 1); l += __shfl_xor_sync(~0u, l, 2);
    asm("rcp.approx.ftz.f32 %0, %1;" : "=f"(inv[hh]) : "f"(l));
  }
  uint32_t* dst = g_o + ((b * 192 + h * 6) * 16 + seg * 4 + HALF * 2) * 128 + lane;
#pragma unroll
  for (int u = 3; u < 6; u++) {
    float o[8][4] = {};
#pragma unroll
    for (int n = 0; n < 8; n++) mma8(o[n], pp[0][0], pp[0][1], f[u][2 * NT * (n >> 1) + 2 * NT - 2 + (n & 1)]);
#pragma unroll
    for (int t = 0; t <= HALF; t++)
#pragma unroll
      for (int n = 0; n < 8; n++) {
        const uint32_t* v = &f[u][2 * NT * (n >> 1) + 4 * t + 2 * (n & 1)];
        mma16(o[n], pp[1 + 2 * t][0], pp[1 + 2 * t][1], pp[2 + 2 * t][0], pp[2 + 2 * t][1], v[0], v[1]);
      }
    r.release(slot[u]);
    if (u == 3) fetch(5);
#pragma unroll
    for (int n = 0; n < 8; n++) {
      dst[(u - 3) * 4096 + (n >> 2) * 2048 + (n & 3) * 32] = pack2(o[n][0] * inv[0], o[n][1] * inv[0]);
      dst[(u - 3) * 4096 + (n >> 2) * 2048 + (n & 3) * 32 + 128] = pack2(o[n][2] * inv[1], o[n][3] * inv[1]);
    }
  }
}

template <int NG>
__device__ __forceinline__ void fin_item(Ring& r, uint32_t scratch, int b, int idx) {
  const int warp = threadIdx.x >> 5, lane = threadIdx.x & 31;
  float4* x = g_x + ((b * 16 + idx * NG) * 40 + warp * 5) * 32 + lane;
  float4 v[NG][5];
#pragma unroll
  for (int g = 0; g < NG; g++) {
    const uint32_t base = r.wait();
#pragma unroll
    for (int i = 0; i < 5; i++) v[g][i] = lds128f(base + ((warp * 5 + i) * 32 + lane) * 16);
    r.pop();
  }
#pragma unroll 1
  for (int k = 0; k < op_split(b); k += NG == 1 ? 2 : 1) {
#pragma unroll
    for (int g = 0; g < NG; g += 2) {
      const uint32_t base = r.wait();
#pragma unroll
      for (int i = 0; i < 10; i++) {
        const uint2 q = lds64(base + ((i / 5 * 40 + warp * 5 + i % 5) * 32 + lane) * 8);
        float4& t = v[(g + i / 5) % NG][i % 5];
        t.x += bf_lo(q.x); t.y += bf_hi(q.x); t.z += bf_lo(q.y); t.w += bf_hi(q.y);
      }
      r.pop();
    }
  }
  float mean[NG], rs[NG];
  ln_stats<NG>(v, scratch, mean, rs);
#pragma unroll
  for (int i = 0; i < 5; i++) {
    const int u = warp * 5 + i;
    uint32_t* xn = g_xn + ((b * 20 + (u >> 1)) * 16 + idx * NG) * 128 + (u & 1) * 64 + lane;
#pragma unroll
    for (int g = 0; g < NG; g++) {
      xn[g * 128] = pack2((v[g][i].x - mean[g]) * rs[g], (v[g][i].y - mean[g]) * rs[g]);
      xn[g * 128 + 32] = pack2((v[g][i].z - mean[g]) * rs[g], (v[g][i].w - mean[g]) * rs[g]);
    }
  }
#pragma unroll
  for (int g = 0; g < NG; g++)
#pragma unroll
    for (int i = 0; i < 5; i++) x[(g * 40 + i) * 32] = v[g][i];
}

__global__ void __launch_bounds__(384, 1) post_kernel(const __grid_constant__ PostParams p) {
  extern __shared__ __align__(1024) uint8_t smem_raw[];
  const uint32_t sb = s2u(smem_raw), bars = sb + PS * PB;
  const uint32_t bIF = bars + 128, bIE = bars + 160, done = bars + 192, bGo = bars + 224, slots = bars + 240, scratch = bars + 512;
  const int warp = __shfl_sync(~0u, threadIdx.x >> 5, 0), lane = threadIdx.x & 31;
  TRACE(0);
  pdl_launch();
  if (sb & 1023) __trap();
  if (threadIdx.x < 29) mbar_init(bars + 8 * threadIdx.x, threadIdx.x < 8 ? 1 : threadIdx.x < 16 ? 8 : threadIdx.x < 20 ? 1 : threadIdx.x < 24 ? 2 : threadIdx.x < 28 ? 8 : 1);
  if (threadIdx.x == 32) sts32(slots + 16, p.gap);
  fence_async();
  __syncthreads();
  if (warp >= 8) {
    asm volatile("setmaxnreg.dec.sync.aligned.u32 56;");
    if (warp == 9) {
      const int b = lane & 15;
      bool queries = QA_END < 16 && blockIdx.x < 36;
      for (int n = 0;; n++) {
        if (n > 0) mbar_wait(bGo, (n - 1) & 1);
        mbar_wait(bIE + 8 * (n & 3), ((n >> 2) & 1) ^ 1);
        int code = -1, spin = 0, ticket = 0;
        if (queries) {
          if (lane == 0) ticket = n == 0 ? blockIdx.x : 36 + atomicAdd(g_sync + SY_QC, 1);
          ticket = __shfl_sync(~0u, ticket, 0);
          queries = ticket < (16 - QA_END) * 32;
          if (queries) code = IT_Q << 16 | (QA_END + ticket % (16 - QA_END)) << 8 | ticket / (16 - QA_END);
        }
        if (!queries && lane == 0) asm volatile("atom.relaxed.gpu.global.add.u32 %0, [%1], 1;" : "=r"(ticket) : "l"(g_sync + SY_T) : "memory");
        while (!queries) {
          const uint4 hd = ldg_strong128(g_sync + b * 8), pr = ldg_strong128(g_sync + b * 8 + 4);
          const uint32_t hv[4] = {hd.x, hd.y, hd.z, hd.w}, pv[4] = {pr.x, pr.y, pr.z, pr.w};
          const uint32_t chain_done = __ballot_sync(~0u, (pr.x & 0xffff) >= 96) & 0xffff;
          int left[4], avail[4], rdy = 0, claimed = 0, upstream = 0;
#pragma unroll
          for (int t = 0; t < 4; t++) {
            const int cnt = lane < 16 ? item_count(t, b) : 0;
            left[t] = max(cnt - (int)hv[t], 0);
            claimed += cnt - left[t];
            const bool ready = (pv[t] & 0xffff) >= item_need(t, b);
            rdy |= ready << t;
            bool ok = ready || (t == IT_ATT ? pr.x >= 0x10000 : !upstream || (t == IT_OP && (chain_done >> 15 & 1)));
            if (t == IT_BQ && (chain_done >> BQ_HOLD & 1) && !(chain_done >> 15)) ok = false;
            avail[t] = ok ? left[t] : 0;
            upstream |= __any_sync(~0u, left[t] > 0);
          }
          if (!upstream) break;
          int rank = max(__shfl_sync(~0u, ticket, 0) - __reduce_add_sync(~0u, claimed), 0), type = -1, mine = 0;
#pragma unroll
          for (int c = 0; c < 8; c++) {
            const int t = c == PR_FIN || c == 5 ? IT_FIN : c == PR_ATT || c == 7 ? IT_ATT : c == PR_OP || c == 4 ? IT_OP : IT_BQ;
            int a = c == PR_ATT || ((rdy >> t & 1) == (c < 4)) ? avail[t] : 0;
            if (t == IT_OP && OP_EARLY) a = c == PR_OP ? avail[t] : 0;
            if (c == 7) a = b < QA_END && !(rdy & 1) && ((chain_done << 1 | 1) >> b & 1) ? left[t] : 0;
            const int tot = __reduce_add_sync(~0u, a);
            if (type < 0) { if (rank < tot) { type = t; mine = a; } else rank -= tot; }
          }
          if (type >= 0) {
#pragma unroll
            for (int o = 1; o < 16; o <<= 1) { const int y = __shfl_up_sync(~0u, mine, o); if (lane >= o) mine += y; }
            const int blk = __ffs(__ballot_sync(~0u, mine > rank)) - 1;
            const int early = !(__shfl_sync(~0u, rdy, blk) >> type & 1);
            uint32_t idx = 0;
            if (lane == 0) asm volatile("atom.relaxed.gpu.global.add.u32 %0, [%1], 1;" : "=r"(idx) : "l"(g_sync + blk * 8 + type) : "memory");
            ld_acquire(g_sync + blk * 8 + 4 + type);
            idx = __shfl_sync(~0u, idx, 0);
            if (idx < item_count(type, blk)) { code = (chain_done >> 15 & 1) << 22 | (chain_done >> p.look & 1) << 21 | early << 20 | type << 16 | blk << 8 | idx; break; }
          } else {
            __nanosleep(50);
          }
          spin_guard(spin);
        }
        if (lane == 0) {
          fence_async_global();
          sts32(slots + 4 * (n & 3), code);
          mbar_arrive(bIF + 8 * (n & 3));
        }
        __syncwarp();
        if (code < 0) break;
      }
    } else if (warp == 8) {
      if (elect()) {
        uint32_t dst = sb, bar = bars, ph = 1, next = clk32(), gap = 0;
        auto acquire = [&](uint32_t kb) {
          mbar_wait(bar + 8 * PS, ph);
          mbar_expect(bar, kb * 1024);
          if (gap) {
            uint32_t now;
            do now = clk32(); while ((int)(now - next) < 0);
            next = ((int)(now - next) > 100 ? now - 100 : next) + kb * gap;
          }
        };
        auto advance = [&]() { dst += PB; bar += 8; if (dst == bars) { dst = sb; bar = bars; ph ^= 1; } };
        auto depend = [&](const uint32_t* c, uint32_t need) { wait_count(c, need); fence_async_global(); };
#pragma unroll 1
        for (int n = 0;; n++) {
          mbar_wait(bIF + 8 * (n & 3), (n >> 2) & 1);
          const int code = (int)lds32(slots + 4 * (n & 3));
          if (code < 0) break;
          const int type = (code >> 16) & 15, b = (code >> 8) & 255, idx = code & 255;
          const bool early = code >> 20 & 1, go = !(code >> 21 & 1);
          mbar_arrive(bIE + 8 * (n & 3));
          gap = !(code >> 22 & 1) ? lds32(slots + 16) : type == IT_ATT || type == IT_FIN ? 0 : p.gap2;
          const uint32_t* progress = g_sync + b * 8 + 4 + type;
          if (type == IT_ATT && b >= QA_END) {
            depend(g_sync + SY_Q, (16 - QA_END) * 32);
#pragma unroll 1
            for (int u = 0; u < 2; u++) { acquire(24); bulk_load_last(dst, g_q + (((b - QA_END) * 32 + idx) * 2 + u) * 1536, 24576, bar); advance(); }
          } else if (type == IT_FIN) {
            const int ng = 16 / fin_items(b), lg = ng >> 1;
#pragma unroll 1
            for (int g = 0; g < ng; g++) { acquire(20); bulk_load(dst, g_x + (b * 16 + idx * ng + g) * 1280, 20480, bar); advance(); }
            if (early) depend(progress, item_need(type, b));
            if (go) mbar_arrive(bGo);
#pragma unroll 1
            for (int i = 0; i < op_split(b) * ng; i += 2) {
              const uint2* src = g_part + ((b * 16 + (i >> lg)) * 16 + idx * ng + (i & (ng - 1))) * 1280;
              acquire(20);
              bulk_load_last(dst, src, ng > 1 ? 20480 : 10240, bar);
              if (ng == 1) bulk_load_last(dst + 10240, src + 16 * 1280, 10240, bar);
              advance();
            }
            if (!go && p.pol) mbar_arrive(bGo);
          } else {
            const bool op = type == IT_OP, bq = type == IT_BQ;
            const int width = op ? op_width(b) : bq ? bq_width(b) : 192, nb = (width + 63) >> 6, lt = width == 320 ? 1 : 2;
            const int nst = op ? 192 / op_split(b) : 20, kb0 = op ? (idx >> lt) * nst : 0;
            const int col = (op ? idx & ((1 << lt) - 1) : idx) * width;
            const bool whole = !(width & 63);
            const CUtensorMap* m = op ? (whole ? &p.wo : &p.wo2) : bq ? (whole ? &p.wb : &p.wb2) : &p.wq;
            const uint32_t* a = op ? g_o + (b * 192 + kb0) * 2048 : g_xn + b * 20 * 2048;
            int row = kb0 * 32, pre = early && (op || bq) ? min(nst, PRE_MAX) : 0;
            auto weights = [&]() {
              acquire(8 + nb * 4);
              if (whole) {
                tma_load3z(dst + 8192, m, row, col >> 6, bar);
              } else {
                tma_load(dst + 8192, m, col, row, bar); tma_load(dst + 12288, m, col + 64, row, bar);
                if (nb == 3) tma_load(dst + 16384, m, col + 128, row, bar);
              }
              row += 32;
            };
            if (pre) {
              uint32_t da = dst, ba = bar;
              const uint32_t g0 = gap;
              gap = max(gap, PRE_GAP);
#pragma unroll 1
              for (int kb = 0; kb < pre; kb++) { weights(); advance(); }
              gap = g0;
              depend(progress, item_need(type, b));
#pragma unroll 1
              for (int kb = 0; kb < pre; kb++) {
                bulk_load(da, a, 8192, ba);
                a += 2048; da += PB; ba += 8;
                if (da == bars) { da = sb; ba = bars; }
              }
            }
#pragma unroll 1
            for (int kb = pre; kb < nst; kb++) { weights(); if (op && OEF) bulk_load_last(dst, a, 8192, bar); else bulk_load(dst, a, 8192, bar); a += 2048; advance(); }
          }
          if (type == IT_ATT) {
            if (early) depend(progress, 96);
            if (go) mbar_arrive(bGo);
            const uint8_t* src = g_kv + (size_t)(idx * 6 * NSEG + b * 4) * KV_BYTES;
#pragma unroll 1
            for (int u = 0; u < 6; u++) {
              acquire(20);
              bulk_load_last(dst, src, 20480, bar);
              src += u == 2 ? -3 * KV_V : 2 * KV_V;
              advance();
            }
            if (!go && p.pol && ATT_LOOK) mbar_arrive(bGo);
            if (Q_PF && b + Q_PF >= QA_END && b + Q_PF < 16)
              asm volatile("cp.async.bulk.prefetch.L2.global [%0], 49152;" :: "l"(g_q + ((b + Q_PF - QA_END) * 32 + idx) * 3072) : "memory");
          }
        }
      }
    } else if (warp == 11) {
      uint32_t smid, nsm, used = 0;
      asm("mov.u32 %0, %%smid;" : "=r"(smid)); asm("mov.u32 %0, %%nsmid;" : "=r"(nsm));
      for (int n = 0; n < 64 && used < 96; n++) {
        uint32_t peers = 0;
        used = 0;
        for (uint32_t i = lane; i < min(nsm, 256u); i += 32) {
          const bool taken = ldg_strong32(g_smuse + i) == p.layer + 1;
          used += taken;
          peers += abs((int)(g_smclk[i] - g_smclk[smid & 255])) < 4000 && !taken;
        }
        used = __reduce_add_sync(~0u, used);
        sts32(slots + 16, max(p.gap, (int)min(__reduce_add_sync(~0u, peers), 18u) * p.share >> 3));
      }
    } else if (warp == 10 && lane == 0) {
      for (int n = 0;; n++) {
        mbar_wait(bIF + 8 * (n & 3), (n >> 2) & 1);
        const int code = (int)lds32(slots + 4 * (n & 3));
        if (code < 0) break;
        const int type = (code >> 16) & 15, b = (code >> 8) & 255;
        mbar_wait(done + 8 * (n & 3), (n >> 2) & 1);
        if (type != IT_BQ) red_release(type == IT_Q ? g_sync + SY_Q : g_sync + b * 8 + 5 + type, 1);
        mbar_arrive(bIE + 8 * (n & 3));
      }
    }
  } else {
    asm volatile("setmaxnreg.inc.sync.aligned.u32 224;");
    const int g = lane >> 2, c = lane & 3;
    Ring r = {sb, bars, 0, 0};
#pragma unroll 1
    for (int n = 0;; n++) {
      mbar_wait(bIF + 8 * (n & 3), (n >> 2) & 1);
      const int code = __shfl_sync(~0u, (int)lds32(slots + 4 * (n & 3)), 0);
      if (code < 0) { TRACE(2); break; }
      const int type = (code >> 16) & 15, b = (code >> 8) & 255, idx = code & 255;
      ITEM(code & 0xfffff, 0);
      if (type == IT_ATT || type == IT_Q) {
        uint32_t q[48];
        if (type == IT_Q || b < QA_END) {
          float d[96] = {};
          reg_fence<96>(d);
          gemm_item<192>(r, d, 20, bGo, type == IT_Q ? 12 : -1);
#pragma unroll
          for (int i = 0; i < 48; i++) q[i] = pack2(d[2 * i], d[2 * i + 1]);
        } else {
#pragma unroll
          for (int u = 0; u < 2; u++) {
            const uint32_t base = r.wait() + threadIdx.x * 16;
#pragma unroll
            for (int i = 0; i < 6; i++) {
              const uint4 v = lds128(base + i * 4096);
              q[24 * u + 4 * i] = v.x; q[24 * u + 4 * i + 1] = v.y; q[24 * u + 4 * i + 2] = v.z; q[24 * u + 4 * i + 3] = v.w;
            }
            r.pop();
          }
        }
        if (type == IT_Q) {
          uint4* dst = g_q + ((b - QA_END) * 32 + idx) * 3072 + threadIdx.x;
#pragma unroll
          for (int i = 0; i < 12; i++) dst[i * 256] = make_uint4(q[4 * i], q[4 * i + 1], q[4 * i + 2], q[4 * i + 3]);
        } else if (warp < 4) {
          attn_a_warp<0>(r, q, b, idx);
        } else {
          attn_a_warp<1>(r, q, b, idx);
        }
      } else if (type == IT_FIN) {
        if (FIN_8 > 0 && fin_items(b) == 4) fin_item<4>(r, scratch, b, idx);
        else if (FIN_16 > FIN_8 && (FIN_16 == 16 || fin_items(b) == 8)) fin_item<2>(r, scratch, b, idx);
        else fin_item<1>(r, scratch, b, idx);
      } else {
        float d[160] = {};
        reg_fence<160>(d);
        const int width = type == IT_OP ? op_width(b) : bq_width(b), nst = type == IT_OP ? 192 / op_split(b) : 20;
        const int go_at = max(nst - (code >> 21 & 1 ? p.pol : 6), 0);
        if (width == 320) gemm_item<320>(r, d, nst, bGo, go_at);
        else if (width == 160 || BQ_80 == 16) gemm_item<160>(r, d, nst, bGo, go_at);
        else gemm_item<80>(r, d, nst, bGo, go_at);
        reg_fence<160>(d);
        if (type == IT_OP) {
          const int tiles = DM / width;
          uint2* dst = g_part + (((b * 16 + idx / tiles) * 16 + warp * 2) * 40 + idx % tiles * (width / 16)) * 32 + lane;
#pragma unroll
          for (int u = 0; u < 20; u++) {
            if (u % 5 == 0 && u * 16 >= width) break;
            dst[u * 32] = make_uint2(pack2(d[8 * u], d[8 * u + 1]), pack2(d[8 * u + 4], d[8 * u + 5]));
            dst[(40 + u) * 32] = make_uint2(pack2(d[8 * u + 2], d[8 * u + 3]), pack2(d[8 * u + 6], d[8 * u + 7]));
          }
        } else {
          const int row = b * 128 + warp * 16 + g;
          const int h0 = idx * (width / 20);
          const float sc = h0 < 32 ? 0.22360679775f * 1.44269504089f : 1.f;
          const bool lo = c < 2;
          uint32_t* da = g_bqkv + (h0 * 256 + (row >> 3)) * 96 + lane;
          uint32_t* db = da + 256 * 96 + (lo ? 2 : -2);
          uint32_t pad[2];
#pragma unroll
          for (int rr = 0; rr < 2; rr++) pad[rr] = c & 1 || h0 < 32 ? 0u : h0 >= 64 ? 0x00003f80u : poly_group((row >> 3) + rr) ? 0x3f803f80u : 0u;
#pragma unroll
          for (int q = 0; q < 8; q++) {
            if (!(q & 1) && q * 40 >= width) break;
#pragma unroll
            for (int rr = 0; rr < 2; rr++) {
              uint32_t w[5];
#pragma unroll
              for (int i = 0; i < 5; i++) w[i] = pack2(d[20 * q + 4 * i + 2 * rr] * sc, d[20 * q + 4 * i + 2 * rr + 1] * sc);
              const int o = q * 2 * 256 * 96 + rr * 96;
              da[o] = w[0]; da[o + 32] = w[1]; da[o + 64] = lo ? w[2] : pad[rr];
              db[o] = lo ? w[3] : w[2]; db[o + 32] = lo ? w[4] : w[3]; db[o + 64] = lo ? pad[rr] : w[4];
            }
          }
        }
      }
      __syncwarp();
      if (lane == 0) mbar_arrive(done + 8 * (n & 3));
      if ((code >> 21 & 1) && (p.pol == 0 || (type == IT_ATT && !ATT_LOOK)) && threadIdx.x == 128) mbar_arrive(bGo);
      ITEM(code & 0xfffff, 1);
    }
  }
}

constexpr int AB_SMEM = 1024 + 98304 + 51200 + 4 * 16384 + 256 + 10240;
#define AB_LW 1
#define AB_U 8
#define AB_WG 4
constexpr int AB_T = AB_WG * 128, AB_PASS = 8 / AB_WG;
__device__ __forceinline__ uint32_t fma2(uint32_t a, uint32_t b, uint32_t c) { uint32_t r; asm("fma.rn.bf16x2 %0, %1, %2, %3;" : "=r"(r) : "r"(a), "r"(b), "r"(c)); return r; }
__device__ __forceinline__ uint32_t ex2_pair(float a, float b, uint32_t one, uint32_t c0) {
  const uint32_t e = __byte_perm(__float_as_uint(a), __float_as_uint(b), 0x6521);
  uint32_t x, r;
  asm("lop3.b32 %0, %1, 0x007f007f, %2, 0xEA;" : "=r"(x) : "r"(e), "r"(one));
  const uint32_t m = AB_DEG == 3 ? fma2(fma2(fma2(c0, x, 0xbbdcbbdcu), x, 0x3ef53ef5u), x, 0x3ee83ee8u) : fma2(fma2(c0, x, 0xbc43bc43u), x, 0x3f2e3f2eu);
  asm("lop3.b32 %0, %1, %2, 0x7f807f80, 0xE4;" : "=r"(r) : "r"(e), "r"(m));
  return r;
}
__device__ __forceinline__ float sq2(uint32_t w) { const float a = bf_lo(w), b = bf_hi(w); return fmaf(a, a, b * b); }

__device__ __forceinline__ void attn_b_store(const float* o, int h, int row0, int lane) {
  const int g = lane >> 2, c = lane & 3;
  const float i0 = __frcp_rn(__shfl_sync(~0u, o[8], (lane & ~3) | 2)), i1 = __frcp_rn(__shfl_sync(~0u, o[10], (lane & ~3) | 2));
#pragma unroll
  for (int jj = 0; jj < 3; jj++) {
    if (jj < 2 || c < 2) {
      const int col = h * 20 + 8 * jj + 2 * c;
      uint32_t* dst = g_of + (((row0 >> 7) * 10 + (col >> 6)) * 16 + (row0 >> 3 & 15)) * 256 + (col >> 3 & 7) * 32 + g * 4 + (col >> 1 & 3);
      dst[0] = pack2(o[4 * jj] * i0, o[4 * jj + 1] * i0);
      dst[256] = pack2(o[4 * jj + 2] * i1, o[4 * jj + 3] * i1);
    }
  }
}

struct AbParams { Weights next; uint32_t* done; uint32_t* out; };
__global__ void __launch_bounds__(AB_T + 32, 1) attn_b_kernel(const __grid_constant__ AbParams p) {
  extern __shared__ uint8_t smem_raw[];
  const uint32_t sb = (s2u(smem_raw) + 1023) & ~1023u, sK = sb, sV = sb + 98304, bars = sV + 51200 + 4 * 16384;
  const uint32_t bF = bars + 64, bW = bars + 72, bA = bars + 80, bE = bars + 128, smax = bars + 176;
  auto ring = [&](int i) { return i < 2 ? sK + 51200 + i * 16384 : sV + 51200 + (i - 2) * 16384; };
  const int warp = __shfl_sync(~0u, threadIdx.x >> 5, 0), lane = threadIdx.x & 31;
  const int h = blockIdx.x >> 2, quarter = blockIdx.x & 3;
  TRACE(0);
  pdl_launch();
  if (threadIdx.x < 22) mbar_init(bars + 8 * threadIdx.x, threadIdx.x == 8 ? AB_T / 32 : threadIdx.x >= 16 ? 8 : 1);
  if (threadIdx.x == 32) sts64(smax, 0, 0);
  fence_async();
  __syncthreads();
  pdl_wait();
  const int blk = quarter * 4 + (h >> 3), cg = h & 7;
  auto unsafe = [&]() { const float2 m = lds64f(smax); return !(m.x * m.y <= 10000.f); };
  if (warp == AB_T / 32) {
    auto load_w = [&]() {
      mbar_expect(bW, 102400);
      for (int i = 0; i < 4; i++) bulk_load((i < 2 ? sK : sV) + (i & 1) * 25600, g_wb + cg * 6400 + i * 1600, 25600, bW);
    };
    if (elect()) {
      const uint32_t* gk = g_bqkv + (32 + h) * 256 * 96;
#pragma unroll 1
      for (int i = 0; i < 8; i++) {
        if (i >= AB_LW) mbar_wait(bars + 8 * (i - AB_LW), 0);
        mbar_expect(bars + 8 * i, 24576);
        bulk_load_last(sK + i * 12288, gk + i * 3072, 12288, bars + 8 * i);
        bulk_load_last(sV + i * 12288, gk + 32 * 256 * 96 + i * 3072, 12288, bars + 8 * i);
      }
    }
    __syncwarp();
    if (blockIdx.x < NSLOT) for (int i = lane; i < 512; i += 32) reinterpret_cast<uint4*>(pool_at(blockIdx.x * 8192))[i] = make_uint4(0, 0, 0, 0);
    if (blockIdx.x == 127) for (int i = lane; i < SY_N; i += 32) g_sync[i] = 0;
    if (p.next.w[0] && lane == 0) {
      for (int i = 0; i < AB_PF; i++) { const uint32_t t0 = clk32(); while (clk32() - t0 < (i ? AB_PFD : AB_PF0)) __nanosleep(200); prefetch_weights(p.next, i); }
    }
    __syncwarp();
    mbar_wait(bF, 0);
    const bool redo = unsafe();
    if (!redo && lane == 0) load_w();
    if (lane < 16) asm volatile("cp.async.bulk.prefetch.L2.global [%0], 2560;" :: "l"(g_x + ((blk * 16 + lane) * 40 + cg * 5) * 32) : "memory");
    __syncwarp();
    bar_sync(1, AB_T + 32);
    if (lane == 0) {
      ABT(!!p.out, 1);
      red_release(p.done + quarter * 32, 1);
      ABT(!!p.out, 2);
      if (redo) load_w();
      wait_count(p.done + quarter * 32, 32);
      fence_async_global();
      ABT(!!p.out, 3);
      for (int kb = 0; kb < 10; kb++) {
        const int i = kb < 6 ? kb : kb - 6;
        if (kb >= 6) mbar_wait(bE + 8 * i, 0);
        mbar_expect(bA + 8 * i, 16384);
        bulk_load(ring(i), g_of + (blk * 10 + kb) * 4096, 16384, bA + 8 * i);
      }
    }
    return;
  }
  float qmax = 0.f;
  const uint32_t one = opaque(0x3f803f80u + (threadIdx.x >> 10)), c0 = opaque((AB_DEG == 3 ? 0x3d9f3d9fu : 0x3eac3eacu) + (threadIdx.x >> 10));
#pragma unroll 1
  for (int pass = 0; pass < AB_PASS; pass++) {
    const int row0 = quarter * 512 + ((warp >> 2) * AB_PASS + pass) * 64 + (warp & 3) * 16;
    const uint32_t* gq = g_bqkv + (h * 256 + (row0 >> 3)) * 96 + lane;
    const uint32_t q0 = gq[0], q1 = gq[96], q2 = gq[32], q3 = gq[128];
    uint32_t q4 = gq[64], q5 = gq[160];
    const uint32_t z0 = gq[64 + 3 - (lane & 3)], z1 = gq[160 + 3 - (lane & 3)];
    {
      float n0 = sq2(q0) + sq2(q2) + sq2(q4), n1 = sq2(q1) + sq2(q3) + sq2(q5);
      n0 += __shfl_xor_sync(~0u, n0, 1); n1 += __shfl_xor_sync(~0u, n1, 1);
      n0 += __shfl_xor_sync(~0u, n0, 2); n1 += __shfl_xor_sync(~0u, n1, 2);
      qmax = (n0 > qmax || n0 != n0) ? n0 : qmax;
      qmax = (n1 > qmax || n1 != n1) ? n1 : qmax;
    }
    if (pass == AB_PASS - 1) {
      float kmax = 0.f;
#pragma unroll
      for (int i = 0; i < SEQ / AB_T; i++) {
        const int key = threadIdx.x + AB_T * i;
        const uint32_t a = sK + (key >> 3) * 384 + (key & 7) * 16;
        const uint4 x = lds128(a), y = lds128(a + 128);
        const uint2 z = lds64(a + 256);
        const float n = ((sq2(x.x) + sq2(x.y)) + (sq2(x.z) + sq2(x.w))) + ((sq2(y.x) + sq2(y.y)) + (sq2(y.z) + sq2(y.w))) + (sq2(z.x) + sq2(z.y));
        kmax = (n > kmax || n != n) ? n : kmax;
      }
      const uint32_t kb = __reduce_max_sync(~0u, __float_as_uint(kmax) & 0x7fffffffu), qb = __reduce_max_sync(~0u, __float_as_uint(qmax) & 0x7fffffffu);
      if (lane < 2) asm volatile("red.shared.max.u32 [%0], %1;" :: "r"(smax + 4 * lane), "r"(lane ? kb : qb) : "memory");
      __syncwarp();
    }
    if ((lane & 3) == 2) { q4 = 0xBF8043C0u; q5 = 0xBF8043C0u; }
    float o[12];
    auto desc = [](uint32_t lo, uint32_t hi) { uint64_t d; asm("mov.b64 %0, {%1, %2};" : "=l"(d) : "r"(lo), "r"(hi)); return d; };
    const uint32_t k0 = (uint32_t)mkdesc(sK, 128, 0, 0), k1 = (uint32_t)mkdesc(sK + 256, 0, 0, 0), v0 = (uint32_t)mkdesc(sV, 384, 0, 0);
    float sa[16], sb2[16];
    uint32_t pa[8], pb[8];
    auto qk = [&](float* s, uint32_t t) {
      wg_rs32_00(s, q0, q1, q2, q3, desc(k0 + t, 24), 0);
      wg_rs32_00(s, q4, q5, z0, z1, desc(k1 + t, 24), 1);
      wg_commit();
    };
    auto step = [&](float* s, uint32_t* pp, int g0, uint32_t t, uint32_t nx, int acc) {
      wg_wait<1>();
      reg_fence<16>(s);
#pragma unroll
      for (int i = 0; i < 8; i++) pp[i] = poly_group(g0 + (i >> 1)) ? ex2_pair(s[2 * i], s[2 * i + 1], one, c0) : pack2(ex2(s[2 * i]), ex2(s[2 * i + 1]));
      wg_fence();
      wg_rs24_01(o, pp[0], pp[1], pp[2], pp[3], desc(v0 + t, 8), acc);
      wg_rs24_01(o, pp[4], pp[5], pp[6], pp[7], desc(v0 + t + 48, 8), 1);
      qk(s, nx);
    };
    if (pass == 0) mbar_wait(bars, 0);
    wg_fence();
    qk(sa, 0);
    qk(sb2, 96);
#pragma unroll 1
    for (uint32_t t = 0; t < 64 * 96; t += AB_U * 96) {
      const uint32_t nx = t + AB_U * 96 < 64 * 96 ? t + AB_U * 96 : 0;
      if (pass == AB_PASS - 1 && t == 40 * 96 && lane == 0) mbar_arrive(bF);
#pragma unroll
      for (int u = 0; u < AB_U; u += 2) {
        if (u == AB_U - 2 && pass == 0) mbar_wait(bars + 8 * (nx / 768), 0);
        step(sa, pa, 0, t + u * 96, u + 2 < AB_U ? t + (u + 2) * 96 : nx, u | t);
        step(sb2, pb, 4, t + u * 96 + 96, (u + 2 < AB_U ? t + (u + 2) * 96 : nx) + 96, 1);
      }
    }
    wg_wait<0>();
    reg_fence<12>(o); reg_fence<16>(sa); reg_fence<16>(sb2);
    attn_b_store(o, h, row0, lane);
  }
  mbar_wait(bF, 0);
  if (unsafe())
#pragma unroll 1
  for (int pass = 0; pass < AB_PASS; pass++) {
    const int row0 = quarter * 512 + ((warp >> 2) * AB_PASS + pass) * 64 + (warp & 3) * 16;
    const uint32_t* gq = g_bqkv + (h * 256 + (row0 >> 3)) * 96 + lane;
    const uint32_t q0 = gq[0], q1 = gq[96], q2 = gq[32], q3 = gq[128], q4 = gq[64], q5 = gq[160];
    float o[12];
#pragma unroll
    for (int i = 0; i < 12; i++) o[i] = 0.f;
    float m0 = -INFINITY, m1 = -INFINITY;
#pragma unroll 1
    for (int kt = 0; kt < 32; kt++) {
      float s[32];
      const uint64_t dk = mkdesc(sK + kt * 3072, 128, 384, 0), dk2 = mkdesc(sK + kt * 3072 + 256, 0, 384, 0);
      wg_fence();
      wg_rs64_00(s, q0, q1, q2, q3, dk, 0);
      wg_rs64_00(s, q4, q5, 0, 0, dk2, 1);
      wg_commit();
      wg_wait<0>();
      reg_fence<32>(s); reg_fence<12>(o);
      float n0 = m0, n1 = m1;
#pragma unroll
      for (int jj = 0; jj < 8; jj++) { n0 = fmaxf(n0, fmaxf(s[4 * jj], s[4 * jj + 1])); n1 = fmaxf(n1, fmaxf(s[4 * jj + 2], s[4 * jj + 3])); }
      n0 = fmaxf(n0, __shfl_xor_sync(~0u, n0, 1)); n0 = fmaxf(n0, __shfl_xor_sync(~0u, n0, 2));
      n1 = fmaxf(n1, __shfl_xor_sync(~0u, n1, 1)); n1 = fmaxf(n1, __shfl_xor_sync(~0u, n1, 2));
      const float r0 = ex2(m0 - n0), r1 = ex2(m1 - n1);
      m0 = n0; m1 = n1;
#pragma unroll
      for (int jj = 0; jj < 3; jj++) { o[4 * jj] *= r0; o[4 * jj + 1] *= r0; o[4 * jj + 2] *= r1; o[4 * jj + 3] *= r1; }
      uint32_t pp[16];
#pragma unroll
      for (int jj = 0; jj < 8; jj++) {
        pp[2 * jj] = pack2(ex2(s[4 * jj] - m0), ex2(s[4 * jj + 1] - m0));
        pp[2 * jj + 1] = pack2(ex2(s[4 * jj + 2] - m1), ex2(s[4 * jj + 3] - m1));
      }
      const uint64_t dv = mkdesc(sV + kt * 3072, 384, 128, 0);
      wg_fence();
#pragma unroll
      for (int kk = 0; kk < 4; kk++) wg_rs24_01(o, pp[4 * kk], pp[4 * kk + 1], pp[4 * kk + 2], pp[4 * kk + 3], dv + kk * 48, 1);
      wg_commit();
    }
    wg_wait<0>();
    reg_fence<12>(o);
    attn_b_store(o, h, row0, lane);
  }
  ABT(!!p.out, 0);
  bar_arrive(1, AB_T + 32);
  if (warp >= 12) return;
  const int g = lane >> 2, c = lane & 3;
  const bool live = opaque(threadIdx.x) < 256;
  float d[40] = {};
  float4* x = g_x + ((blk * 16 + warp * 2) * 40 + cg * 5) * 32 + lane;
  if (warp < 8) {
#pragma unroll
  for (int i = 0; i < 10; i++) {
    const int r = i / 5, u = i % 5;
    const float4 t = x[(r * 40 + u) * 32];
    d[8 * u + 2 * r] = t.x; d[8 * u + 2 * r + 1] = t.y; d[8 * u + 4 + 2 * r] = t.z; d[8 * u + 5 + 2 * r] = t.w;
  }
  mbar_wait(bW, 0);
  reg_fence<40>(d);
  ABT(!!p.out, 4);
#pragma unroll 1
  for (int kb = 0; kb < 10; kb++) {
    const int i = kb < 6 ? kb : kb - 6;
    mbar_wait(bA + 8 * i, kb >= 6);
    const uint64_t da = mkdesc(ring(i) + (warp >> 2) * 8192, 128, 1024, 0), db = mkdesc(kb < 5 ? sK + kb * 10240 : sV + (kb - 5) * 10240, 1280, 128, 0);
    wg_fence();
#pragma unroll
    for (int kk = 0; kk < 4; kk++) wg_ss80_01(d, da + kk * 16, db + kk * 160, 1);
    wg_commit();
    if (kb > 0 && kb < 5) { wg_wait<1>(); if (lane == 0) mbar_arrive(bE + 8 * (kb - 1)); }
  }
  wg_wait<0>();
  reg_fence<40>(d);
  }
  ABT(!!p.out, 5);
  if (p.out) {
    if (warp >= 8) return;
    const uint32_t stage = sK + 83968 + warp * 2560 + (warp < 4 ? 0 : 131328 - 10240);
#pragma unroll
    for (int u = 0; u < 5; u++)
      stsm4(stage + (lane & 15) * 160 + u * 32 + (lane >> 4) * 16, pack2(d[8 * u], d[8 * u + 1]), pack2(d[8 * u + 2], d[8 * u + 3]),
            pack2(d[8 * u + 4], d[8 * u + 5]), pack2(d[8 * u + 6], d[8 * u + 7]));
    __syncwarp();
    uint4* out = reinterpret_cast<uint4*>(p.out + (blk * 128 + warp * 16) * (DM / 2) + cg * 40);
#pragma unroll
    for (int i = 0; i < 5; i++) { const int e = i * 32 + lane, r = e / 10; out[r * (DM / 8) + e - r * 10] = lds128(stage + e * 16); }
  } else {
    float2* stat = g_stat + blk * 1024 + (warp & 7) * 16 + g;
    float mean[2], rs[2];
#pragma unroll
    for (int r = 0; r < 2; r++) {
      float t = 0.f, q = 0.f;
#pragma unroll
      for (int i = 0; i < 10; i++) t += d[4 * i + 2 * r] + d[4 * i + 2 * r + 1];
      t += __shfl_xor_sync(~0u, t, 1); t += __shfl_xor_sync(~0u, t, 2);
      t *= 1.f / 80;
#pragma unroll
      for (int i = 0; i < 10; i++) { const float a = d[4 * i + 2 * r] - t, b = d[4 * i + 2 * r + 1] - t; q += a * a + b * b; }
      q += __shfl_xor_sync(~0u, q, 1); q += __shfl_xor_sync(~0u, q, 2);
      if (c == r && live) asm volatile("st.relaxed.gpu.global.v2.b32 [%0], {%1, %2};" :: "l"(stat + cg * 128 + r * 8), "r"(__float_as_uint(t)), "r"(nz(__float_as_uint(q))) : "memory");
    }
#pragma unroll
    for (int i = 0; i < 10; i++) {
      const int r = i / 5, u = i % 5;
      if (live) x[(r * 40 + u) * 32] = make_float4(d[8 * u + 2 * r], d[8 * u + 2 * r + 1], d[8 * u + 4 + 2 * r], d[8 * u + 5 + 2 * r]);
    }
    ABT(0, 6);
    uint2 e[4];
    int n = 0;
    do {
#pragma unroll
      for (int i = 0; i < 4; i++)
        asm volatile("ld.relaxed.gpu.global.v2.b32 {%0, %1}, [%2];" : "=r"(e[i].x), "=r"(e[i].y) : "l"(stat + (2 * c + (i & 1)) * 128 + (i >> 1) * 8) : "memory");
      spin_guard(n);
    } while (__any_sync(~0u, min(min(e[0].y, e[1].y), min(e[2].y, e[3].y)) == 0 && live));
#pragma unroll
    for (int r = 0; r < 2; r++) {
      const float m0 = __uint_as_float(e[2 * r].x), m1 = __uint_as_float(e[2 * r + 1].x);
      float t = m0 + m1;
      t += __shfl_xor_sync(~0u, t, 1); t += __shfl_xor_sync(~0u, t, 2);
      t *= 0.125f;
      float q = __uint_as_float(e[2 * r].y) + __uint_as_float(e[2 * r + 1].y) + 80.f * ((m0 - t) * (m0 - t) + (m1 - t) * (m1 - t));
      q += __shfl_xor_sync(~0u, q, 1); q += __shfl_xor_sync(~0u, q, 2);
      mean[r] = t; rs[r] = rsqrtf(q * (1.f / DM) + 1e-5f);
    }
    ABT(0, 7);
    uint32_t w[2][5][2];
#pragma unroll
    for (int i = 0; i < 20; i++) w[i & 1][i >> 2][i >> 1 & 1] = pack2((d[2 * i] - mean[i & 1]) * rs[i & 1], (d[2 * i + 1] - mean[i & 1]) * rs[i & 1]);
    ln_store(w, blk * 8 + warp, cg * 5, live);
  }
  ABT(!!p.out, 8);
  TRACE(2);
}

typedef CUresult (*EncodeFn)(CUtensorMap*, CUtensorMapDataType, cuuint32_t, void*, const cuuint64_t*, const cuuint64_t*,
                             const cuuint32_t*, const cuuint32_t*, CUtensorMapInterleave, CUtensorMapSwizzle,
                             CUtensorMapL2promotion, CUtensorMapFloatOOBfill);

void make_map(EncodeFn enc, CUtensorMap* m, const void* ptr, int cols, int rows, int nb) {
  const cuuint64_t dims[3] = {(cuuint64_t)(nb ? 64 : cols), (cuuint64_t)rows, (cuuint64_t)cols / 64};
  const cuuint64_t strides[2] = {(cuuint64_t)cols * 2, 128};
  const cuuint32_t box[3] = {64, 32, (cuuint32_t)nb}, es[3] = {1, 1, 1};
  enc(m, CU_TENSOR_MAP_DATA_TYPE_BFLOAT16, nb ? 3 : 2, const_cast<void*>(ptr), dims, strides, box, es, CU_TENSOR_MAP_INTERLEAVE_NONE,
      CU_TENSOR_MAP_SWIZZLE_128B, CU_TENSOR_MAP_L2_PROMOTION_L2_128B, CU_TENSOR_MAP_FLOAT_OOB_FILL_NONE);
}
template <class... KA, class... A>
void launch(void (*kern)(KA...), int grid, int block, int smem, int cluster, bool pdl, A... args) {
  cudaFuncSetAttribute(kern, cudaFuncAttributeMaxDynamicSharedMemorySize, smem);
  cudaLaunchConfig_t cfg = {};
  cfg.gridDim = dim3(grid); cfg.blockDim = dim3(block); cfg.dynamicSmemBytes = smem; cfg.stream = cudaStreamPerThread;
  cudaLaunchAttribute at[2];
  int n = 0;
  if (cluster > 1) { at[n].id = cudaLaunchAttributeClusterDimension; at[n].val.clusterDim.x = cluster; at[n].val.clusterDim.y = 1; at[n].val.clusterDim.z = 1; n++; }
  if (pdl) { at[n].id = cudaLaunchAttributeProgrammaticStreamSerialization; at[n].val.programmaticStreamSerializationAllowed = 1; n++; }
  cfg.attrs = at; cfg.numAttrs = n;
  cudaLaunchKernelEx(&cfg, kern, args...);
}
template <class T> void* sym(T& s) { void* p = nullptr; cudaGetSymbolAddress(&p, s); return p; }

}

#define MODE(b) 0
extern "C" void kernel_launch(void* const* d_in, const int* in_sizes, int n_in, void* d_out, int out_size) {
  const __nv_bfloat16* x = (const __nv_bfloat16*)d_in[0];
  void* fn = nullptr; cudaDriverEntryPointQueryResult qr;
  cudaGetDriverEntryPoint("cuTensorMapEncodeTiled", &fn, cudaEnableDefault, &qr);
  EncodeFn enc = (EncodeFn)fn;

  ChainParams ch = {};
  PostParams op = {};
  for (int i = 0; i < 3; i++) {
    const cuuint64_t dims[3] = {HD, 128, 5}, strides[2] = {HD * 2, HD * 256};
    const cuuint32_t box[3] = {64, 128, 5}, es[3] = {1, 1, 1};
    enc(i == 0 ? &ch.wq : i == 1 ? &ch.wk : &ch.wv, CU_TENSOR_MAP_DATA_TYPE_BFLOAT16, 3, d_in[2 + i], dims, strides, box, es, CU_TENSOR_MAP_INTERLEAVE_NONE,
        CU_TENSOR_MAP_SWIZZLE_128B, W_PROMO, CU_TENSOR_MAP_FLOAT_OOB_FILL_NONE);
  }
  {
    const cuuint64_t dims[3] = {DM, HD, 7}, strides[2] = {DM * 2, 64};
    const cuuint32_t box[3] = {32, 64, 7}, es[3] = {1, 1, 1};
    enc(&ch.wo, CU_TENSOR_MAP_DATA_TYPE_BFLOAT16, 3, d_in[5], dims, strides, box, es, CU_TENSOR_MAP_INTERLEAVE_NONE,
        CU_TENSOR_MAP_SWIZZLE_64B, CU_TENSOR_MAP_L2_PROMOTION_L2_128B, CU_TENSOR_MAP_FLOAT_OOB_FILL_NONE);
  }
  ch.mem0 = (const __nv_bfloat16*)d_in[1];
  ch.pool = (uint8_t*)(((uintptr_t)sym(g_pool) + 8191) & ~(uintptr_t)8191); ch.kv = (uint8_t*)sym(g_kv); ch.xc = (const uint32_t*)sym(g_xc); ch.sync = (uint32_t*)sym(g_sync);
  ch.d1 = 0; ch.d1b = 0; ch.d2 = 0; ch.d2b = 0;
  make_map(enc, &op.wq, d_in[2], HD, DM, 3);
  make_map(enc, &op.wo, d_in[5], DM, HD, 5); make_map(enc, &op.wo2, d_in[5], DM, HD, 0);
  make_map(enc, &op.wb, d_in[8], 1920, DM, 5); make_map(enc, &op.wb2, d_in[8], 1920, DM, 0);
  op.gap = 17; op.share = 20; op.look = 14; op.gap2 = 0; op.pol = 1;

  const Weights wa = {{(const uint8_t*)d_in[3], (const uint8_t*)d_in[4], (const uint8_t*)d_in[2], (const uint8_t*)d_in[5]}}, none = {};
  launch(first_kernel, 132, 384, 128 * 1024, 1, false, x, (const uint4*)d_in[9], wa);
  for (int layer = 0; layer < 2; layer++) {
    ch.layer = ch.d2b = op.layer = layer;
    launch(chain_kernel, 96, 256, CH_SMEM, 3, true, ch);
    launch(post_kernel, MODE(3) ? 36 : 132, 384, OP_SMEM, 1, !MODE(1), op);
    const AbParams ab = {layer == 0 ? wa : none, (uint32_t*)sym(g_bo) + layer * 128, layer == 0 ? nullptr : (uint32_t*)d_out};
    launch(attn_b_kernel, 128, AB_T + 32, AB_SMEM, 1, true, ab);
  }
}
```

```cpp
#include <cuda_runtime.h>
#include <cuda_bf16.h>
#include <cuda.h>
#include <stdint.h>

namespace {

constexpr int SEQ = 2048, DM = 640, HD = 6144, NSEG = 64;
constexpr int SPIN_LIMIT = 1 << 20;

__device__ __align__(128) uint2 g_x[SEQ * DM / 4];
__device__ __align__(128) uint32_t g_of[SEQ * DM / 2];
__device__ __align__(128) uint4 g_wb[DM * DM / 8];
__device__ __align__(16) float2 g_stat[16 * 8 * 128];
__device__ uint32_t g_bo[8 * 32];
__device__ __align__(128) uint4 g_q[SEQ * HD / 8];
__device__ __align__(128) uint32_t g_o[SEQ * HD / 2];
constexpr int KV_BYTES = 5120, KV_M = 4096, KV_V = NSEG * KV_BYTES;
__device__ __align__(128) uint8_t g_kv[96 * 2 * NSEG * KV_BYTES];
__device__ __align__(128) uint32_t g_xc[SEQ * DM / 2];
#define OP_B4 5
#define OP_B8 9
#define OP_B16 13
#define QA_END 12
__host__ __device__ constexpr int op_split(int b) { return b < OP_B4 ? 2 : b < OP_B8 ? 4 : b < OP_B16 ? 8 : 16; }
#define AB_PF 2
#define AB_PF0 0
#define AB_PFD 6000
#define W_PROMO CU_TENSOR_MAP_L2_PROMOTION_L2_128B
#define OP_EARLY 1
#define ATT_LOOK 1
#define PR_FIN 1
#define PR_ATT 0
#define PR_OP 2
#define PRE_MAX PS
#define PRE_GAP 0u
#define Q_PF 0
#define OEF 0
#define BQ_HOLD 6
#define WEF 1
#define FK_REP 4
#define FK_PF 1
#define BQ_160 10
#define BQ_80 16
#define OP_160 16
__host__ __device__ constexpr int op_width(int b) { return b < OP_160 ? 320 : 160; }
__host__ __device__ constexpr int bq_width(int b) { return b < BQ_160 ? 320 : b < BQ_80 ? 160 : 80; }
__device__ __align__(128) uint2 g_part[16 * 16 * 16 * 40 * 32];
__device__ __align__(128) uint32_t g_xn[SEQ * DM / 2];
constexpr int SY_Q = 128, SY_T = 160, SY_QC = 192, SY_N = 193;
__device__ __align__(16) uint32_t g_sync[SY_N];
constexpr int NSLOT = 92;
__device__ uint32_t g_pool[(NSLOT + 2) * 2048];
__device__ int g_smpart[256], g_orient[NSLOT];
__device__ uint32_t g_smclk[256], g_smuse[256];
__device__ uint32_t g_bqkv[3 * 32 * 256 * 96];

#define ABT(L, i)
#define MODE_D(b) 0
#define DELAY(d)
#define XT(i)
#define MISS(k, n)
#define PRO(i)
#define TRACE(w)
#define ITEM(code, w)
#define TR(i, v)
#define TM(i)
#define TM1(i)
#define TMD(i, dep)
#define TMV(i, at, v)

__device__ __forceinline__ uint32_t gtime() { uint32_t c; asm volatile("mov.u32 %0, %%globaltimer_lo;" : "=r"(c) :: "memory"); return c; }
__device__ __forceinline__ uint32_t clk32() { uint32_t c; asm volatile("mov.u32 %0, %%clock;" : "=r"(c) :: "memory"); return c; }
__device__ __forceinline__ uint32_t s2u(const void* p) { return (uint32_t)__cvta_generic_to_shared(p); }
__device__ __forceinline__ uint32_t pack2(float a, float b) {
  uint32_t r; asm("cvt.rn.bf16x2.f32 %0, %1, %2;" : "=r"(r) : "f"(b), "f"(a)); return r; }
__device__ __forceinline__ float bf_lo(uint32_t w) { return __uint_as_float(w << 16); }
__device__ __forceinline__ float bf_hi(uint32_t w) { return __uint_as_float(w & 0xffff0000u); }
__device__ __forceinline__ uint2 pack4(float4 v) { return make_uint2(pack2(v.x, v.y), pack2(v.z, v.w)); }
__device__ __forceinline__ float4 unpack4(uint2 w) { return make_float4(bf_lo(w.x), bf_hi(w.x), bf_lo(w.y), bf_hi(w.y)); }
__device__ __forceinline__ float ex2(float x) { float y; asm("ex2.approx.ftz.f32 %0, %1;" : "=f"(y) : "f"(x)); return y; }

__device__ __forceinline__ void mbar_init(uint32_t bar, uint32_t n) {
  asm volatile("mbarrier.init.shared::cta.b64 [%0], %1;" :: "r"(bar), "r"(n) : "memory"); }
__device__ __forceinline__ void mbar_expect(uint32_t bar, uint32_t bytes) {
  asm volatile("mbarrier.arrive.expect_tx.shared::cta.b64 _, [%0], %1;" :: "r"(bar), "r"(bytes) : "memory"); }
__device__ __forceinline__ void mbar_arrive(uint32_t bar) {
  asm volatile("mbarrier.arrive.shared::cta.b64 _, [%0];" :: "r"(bar) : "memory"); }
__device__ __forceinline__ void mbar_wait(uint32_t bar, uint32_t ph) {
  asm volatile("{.reg .pred p; .reg .u32 n; mov.u32 n, 0;\n"
               "W: mbarrier.try_wait.parity.shared::cta.b64 p, [%0], %1; @p bra D;\n"
               "add.u32 n, n, 1; setp.gt.u32 p, n, %2; @p trap; bra W;\n"
               "D: }" :: "r"(bar), "r"(ph), "n"(SPIN_LIMIT) : "memory");
}
__device__ __forceinline__ void mbar_wait_cluster(uint32_t bar, uint32_t ph) {
  asm volatile("{.reg .pred p; .reg .u32 n; mov.u32 n, 0;\n"
               "W: mbarrier.try_wait.parity.acquire.cluster.shared::cta.b64 p, [%0], %1; @p bra D;\n"
               "add.u32 n, n, 1; setp.gt.u32 p, n, %2; @p trap; bra W;\n"
               "D: }" :: "r"(bar), "r"(ph), "n"(SPIN_LIMIT) : "memory");
}
__device__ __forceinline__ void spin_guard(int& n) {
  asm volatile("{.reg .pred p; add.s32 %0, %0, 1; setp.gt.s32 p, %0, %1; @p trap;}" : "+r"(n) : "n"(SPIN_LIMIT));
}
__device__ __forceinline__ void pdl_wait() { asm volatile("griddepcontrol.wait;" ::: "memory"); TRACE(1); }
__device__ __forceinline__ void pdl_launch() { asm volatile("griddepcontrol.launch_dependents;" ::: "memory"); }
__device__ __forceinline__ uint32_t ld_acquire(const uint32_t* p) { uint32_t v; asm volatile("ld.acquire.gpu.global.u32 %0, [%1];" : "=r"(v) : "l"(p) : "memory"); return v; }
__device__ __forceinline__ void red_release(uint32_t* p, uint32_t v) { asm volatile("red.release.gpu.global.add.u32 [%0], %1;" :: "l"(p), "r"(v) : "memory"); }
__device__ __forceinline__ void red_relaxed(uint32_t* p, uint32_t v) { asm volatile("red.relaxed.gpu.global.add.u32 [%0], %1;" :: "l"(p), "r"(v) : "memory"); }
__device__ __forceinline__ void fence_async_global() { asm volatile("fence.proxy.async.global;" ::: "memory"); }
__device__ __forceinline__ void fence_async() { asm volatile("fence.proxy.async.shared::cta;" ::: "memory"); }
__device__ __forceinline__ void bar_sync(int id, int n) { asm volatile("bar.sync %0, %1;" :: "r"(id), "r"(n) : "memory"); }
__device__ __forceinline__ void bar_arrive(int id, int n) { asm volatile("bar.arrive %0, %1;" :: "r"(id), "r"(n) : "memory"); }
__device__ __forceinline__ void tma_load(uint32_t dst, const CUtensorMap* m, int c0, int c1, uint32_t bar) {
  asm volatile("cp.async.bulk.tensor.2d.shared::cluster.global.mbarrier::complete_tx::bytes [%0], [%1, {%3, %4}], [%2];"
               :: "r"(dst), "l"(m), "r"(bar), "r"(c0), "r"(c1) : "memory"); }
template <bool STREAM = false>
__device__ __forceinline__ void tma_load3(uint32_t dst, const CUtensorMap* m, int c0, int c1, uint32_t bar) {
  if (STREAM)
    asm volatile("{.reg .b64 pol; createpolicy.fractional.L2::evict_first.b64 pol, 1.0;\n"
                 "cp.async.bulk.tensor.3d.shared::cluster.global.mbarrier::complete_tx::bytes.L2::cache_hint [%0], [%1, {%3, %4, 0}], [%2], pol;}"
                 :: "r"(dst), "l"(m), "r"(bar), "r"(c0), "r"(c1) : "memory");
  else
  asm volatile("cp.async.bulk.tensor.3d.shared::cluster.global.mbarrier::complete_tx::bytes [%0], [%1, {%3, %4, 0}], [%2];"
               :: "r"(dst), "l"(m), "r"(bar), "r"(c0), "r"(c1) : "memory"); }
__device__ __forceinline__ void tma_load3z(uint32_t dst, const CUtensorMap* m, int c1, int c2, uint32_t bar) {
  asm volatile("cp.async.bulk.tensor.3d.shared::cluster.global.mbarrier::complete_tx::bytes [%0], [%1, {0, %3, %4}], [%2];"
               :: "r"(dst), "l"(m), "r"(bar), "r"(c1), "r"(c2) : "memory"); }
__device__ __forceinline__ void tma_store(const CUtensorMap* m, uint32_t src, int c0, int c1) {
  asm volatile("cp.async.bulk.tensor.2d.global.shared::cta.bulk_group [%0, {%2, %3}], [%1];"
               :: "l"(m), "r"(src), "r"(c0), "r"(c1) : "memory"); }
__device__ __forceinline__ void tma_store_stream(const CUtensorMap* m, uint32_t src, int c0, int c1) {
  asm volatile("{.reg .b64 pol; createpolicy.fractional.L2::evict_first.b64 pol, 1.0;\n"
               "cp.async.bulk.tensor.2d.global.shared::cta.bulk_group.L2::cache_hint [%0, {%2, %3}], [%1], pol;}"
               :: "l"(m), "r"(src), "r"(c0), "r"(c1) : "memory"); }
__device__ __forceinline__ void bulk_load(uint32_t dst, const void* src, uint32_t bytes, uint32_t bar) {
  asm volatile("cp.async.bulk.shared::cluster.global.mbarrier::complete_tx::bytes [%0], [%1], %2, [%3];"
               :: "r"(dst), "l"(src), "r"(bytes), "r"(bar) : "memory"); }
__device__ __forceinline__ void bulk_load_last(uint32_t dst, const void* src, uint32_t bytes, uint32_t bar) {
  asm volatile("{.reg .b64 pol; createpolicy.fractional.L2::evict_first.b64 pol, 1.0;\n"
               "cp.async.bulk.shared::cluster.global.mbarrier::complete_tx::bytes.L2::cache_hint [%0], [%1], %2, [%3], pol;}"
               :: "r"(dst), "l"(src), "r"(bytes), "r"(bar) : "memory"); }
__device__ __forceinline__ void tma_load_last(uint32_t dst, const CUtensorMap* m, int c0, int c1, uint32_t bar) {
  asm volatile("{.reg .b64 pol; createpolicy.fractional.L2::evict_first.b64 pol, 1.0;\n"
               "cp.async.bulk.tensor.2d.shared::cluster.global.mbarrier::complete_tx::bytes.L2::cache_hint [%0], [%1, {%3, %4}], [%2], pol;}"
               :: "r"(dst), "l"(m), "r"(bar), "r"(c0), "r"(c1) : "memory"); }
__device__ __forceinline__ void bulk_send(uint32_t dst, uint32_t src, uint32_t bytes, uint32_t bar) {
  asm volatile("cp.async.bulk.shared::cluster.shared::cta.mbarrier::complete_tx::bytes [%0], [%1], %2, [%3];"
               :: "r"(dst), "r"(src), "r"(bytes), "r"(bar) : "memory"); }
__device__ __forceinline__ void bulk_store(void* dst, uint32_t src, uint32_t bytes) {
  asm volatile("cp.async.bulk.global.shared::cta.bulk_group [%0], [%1], %2;" :: "l"(dst), "r"(src), "r"(bytes) : "memory"); }
__device__ __forceinline__ void bulk_commit() { asm volatile("cp.async.bulk.commit_group;" ::: "memory"); }
template <int N> __device__ __forceinline__ void bulk_wait_read() { asm volatile("cp.async.bulk.wait_group.read %0;" :: "n"(N) : "memory"); }
template <int N> __device__ __forceinline__ void bulk_wait() { asm volatile("cp.async.bulk.wait_group %0;" :: "n"(N) : "memory"); }

__device__ __forceinline__ uint64_t mkdesc(uint32_t addr, uint32_t lbo, uint32_t sbo, uint32_t sw) {
  return (uint64_t)((addr & 0x3FFFF) >> 4) | ((uint64_t)(lbo >> 4) << 16) | ((uint64_t)(sbo >> 4) << 32) | ((uint64_t)sw << 62); }
__device__ __forceinline__ void wg_fence() { asm volatile("wgmma.fence.sync.aligned;" ::: "memory"); }
__device__ __forceinline__ void wg_commit() { asm volatile("wgmma.commit_group.sync.aligned;" ::: "memory"); }
template <int N> __device__ __forceinline__ void wg_wait() { asm volatile("wgmma.wait_group.sync.aligned %0;" :: "n"(N) : "memory"); }
template <int N> __device__ __forceinline__ void reg_fence(float* d) {
#pragma unroll
  for (int i = 0; i < N; i++) asm volatile("" : "+f"(d[i]) :: "memory");
}

__device__ __forceinline__ void mma16(float* d, uint32_t a0, uint32_t a1, uint32_t a2, uint32_t a3, uint32_t b0, uint32_t b1) {
  asm volatile("mma.sync.aligned.m16n8k16.row.col.f32.bf16.bf16.f32 {%0,%1,%2,%3},{%4,%5,%6,%7},{%8,%9},{%0,%1,%2,%3};"
               : "+f"(d[0]), "+f"(d[1]), "+f"(d[2]), "+f"(d[3]) : "r"(a0), "r"(a1), "r"(a2), "r"(a3), "r"(b0), "r"(b1)); }
__device__ __forceinline__ void mma8(float* d, uint32_t a0, uint32_t a1, uint32_t b0) {
  asm volatile("mma.sync.aligned.m16n8k8.row.col.f32.bf16.bf16.f32 {%0,%1,%2,%3},{%4,%5},{%6},{%0,%1,%2,%3};"
               : "+f"(d[0]), "+f"(d[1]), "+f"(d[2]), "+f"(d[3]) : "r"(a0), "r"(a1), "r"(b0)); }
__device__ __forceinline__ void ldsm4(uint32_t* r, uint32_t a) {
  asm volatile("ldmatrix.sync.aligned.m8n8.x4.shared.b16 {%0,%1,%2,%3},[%4];" : "=r"(r[0]), "=r"(r[1]), "=r"(r[2]), "=r"(r[3]) : "r"(a) : "memory"); }
__device__ __forceinline__ void ldsm4t(uint32_t* r, uint32_t a) {
  asm volatile("ldmatrix.sync.aligned.m8n8.x4.trans.shared.b16 {%0,%1,%2,%3},[%4];" : "=r"(r[0]), "=r"(r[1]), "=r"(r[2]), "=r"(r[3]) : "r"(a) : "memory"); }
__device__ __forceinline__ void ldsm2(uint32_t* r, uint32_t a) {
  asm volatile("ldmatrix.sync.aligned.m8n8.x2.shared.b16 {%0,%1},[%2];" : "=r"(r[0]), "=r"(r[1]) : "r"(a) : "memory"); }
__device__ __forceinline__ void stsm4(uint32_t a, uint32_t r0, uint32_t r1, uint32_t r2, uint32_t r3) {
  asm volatile("stmatrix.sync.aligned.m8n8.x4.shared.b16 [%0], {%1,%2,%3,%4};" :: "r"(a), "r"(r0), "r"(r1), "r"(r2), "r"(r3) : "memory"); }
__device__ __forceinline__ void stsm2t(uint32_t a, uint32_t r0, uint32_t r1) {
  asm volatile("stmatrix.sync.aligned.m8n8.x2.trans.shared.b16 [%0], {%1,%2};" :: "r"(a), "r"(r0), "r"(r1) : "memory"); }
__device__ __forceinline__ void stsm4t(uint32_t a, uint32_t r0, uint32_t r1, uint32_t r2, uint32_t r3) {
  asm volatile("stmatrix.sync.aligned.m8n8.x4.trans.shared.b16 [%0], {%1,%2,%3,%4};" :: "r"(a), "r"(r0), "r"(r1), "r"(r2), "r"(r3) : "memory"); }
__device__ __forceinline__ void st_async128(uint32_t a, uint4 v, uint32_t bar) {
  asm volatile("st.async.shared::cluster.mbarrier::complete_tx::bytes.v4.b32 [%0], {%1,%2,%3,%4}, [%5];" :: "r"(a), "r"(v.x), "r"(v.y), "r"(v.z), "r"(v.w), "r"(bar) : "memory"); }
__device__ __forceinline__ void sts32(uint32_t a, uint32_t v) { asm volatile("st.shared.b32 [%0], %1;" :: "r"(a), "r"(v) : "memory"); }
__device__ __forceinline__ void sts64f(uint32_t a, float x, float y) { asm volatile("st.shared.v2.f32 [%0], {%1,%2};" :: "r"(a), "f"(x), "f"(y) : "memory"); }
__device__ __forceinline__ void sts128(uint32_t a, uint4 v) {
  asm volatile("st.shared.v4.b32 [%0], {%1,%2,%3,%4};" :: "r"(a), "r"(v.x), "r"(v.y), "r"(v.z), "r"(v.w) : "memory"); }
__device__ __forceinline__ void sts128f(uint32_t a, float x, float y, float z, float w) {
  asm volatile("st.shared.v4.f32 [%0], {%1,%2,%3,%4};" :: "r"(a), "f"(x), "f"(y), "f"(z), "f"(w) : "memory"); }
__device__ __forceinline__ float lds32f(uint32_t a) { float v; asm volatile("ld.shared.f32 %0, [%1];" : "=f"(v) : "r"(a) : "memory"); return v; }
__device__ __forceinline__ float2 lds64f(uint32_t a) { float2 v; asm volatile("ld.shared.v2.f32 {%0,%1}, [%2];" : "=f"(v.x), "=f"(v.y) : "r"(a) : "memory"); return v; }
__device__ __forceinline__ float4 lds128f(uint32_t a) {
  float4 v; asm volatile("ld.shared.v4.f32 {%0,%1,%2,%3}, [%4];" : "=f"(v.x), "=f"(v.y), "=f"(v.z), "=f"(v.w) : "r"(a) : "memory"); return v; }
__device__ __forceinline__ uint4 lds128(uint32_t a) {
  uint4 v; asm volatile("ld.shared.v4.b32 {%0,%1,%2,%3}, [%4];" : "=r"(v.x), "=r"(v.y), "=r"(v.z), "=r"(v.w) : "r"(a) : "memory"); return v; }
__device__ __forceinline__ uint4 ldg_strong128(const void* p) {
  uint4 v; asm volatile("ld.relaxed.gpu.global.v4.u32 {%0,%1,%2,%3}, [%4];" : "=r"(v.x), "=r"(v.y), "=r"(v.z), "=r"(v.w) : "l"(p) : "memory"); return v; }
__device__ __forceinline__ void stg_strong32(void* p, uint32_t v) { asm volatile("st.relaxed.gpu.global.u32 [%0], %1;" :: "l"(p), "r"(v) : "memory"); }
__device__ __forceinline__ void stg_strong16(void* p, uint32_t v) { asm volatile("st.relaxed.gpu.global.u16 [%0], %1;" :: "l"(p), "h"((uint16_t)v) : "memory"); }
__device__ __forceinline__ void stg_strong128(void* p, uint4 v) {
  asm volatile("st.relaxed.gpu.global.v4.u32 [%0], {%1,%2,%3,%4};" :: "l"(p), "r"(v.x), "r"(v.y), "r"(v.z), "r"(v.w) : "memory"); }
__device__ __forceinline__ uint32_t mapa(uint32_t a, uint32_t r) {
  uint32_t o; asm("mapa.shared::cluster.u32 %0, %1, %2;" : "=r"(o) : "r"(a), "r"(r)); return o; }
__device__ __forceinline__ void st_async2f(uint32_t a, float x, float y, uint32_t bar) {
  asm volatile("st.async.shared::cluster.mbarrier::complete_tx::bytes.v2.f32 [%0], {%1,%2}, [%3];" :: "r"(a), "f"(x), "f"(y), "r"(bar) : "memory"); }
__device__ __forceinline__ void st_async32(uint32_t a, uint32_t x, uint32_t bar) {
  asm volatile("st.async.shared::cluster.mbarrier::complete_tx::bytes.b32 [%0], %1, [%2];" :: "r"(a), "r"(x), "r"(bar) : "memory"); }
__device__ __forceinline__ uint32_t lds32(uint32_t a) { uint32_t v; asm volatile("ld.shared.b32 %0, [%1];" : "=r"(v) : "r"(a) : "memory"); return v; }
__device__ __forceinline__ void st_async64(uint32_t a, uint32_t x, uint32_t y, uint32_t bar) {
  asm volatile("st.async.shared::cluster.mbarrier::complete_tx::bytes.v2.b32 [%0], {%1,%2}, [%3];" :: "r"(a), "r"(x), "r"(y), "r"(bar) : "memory"); }
__device__ __forceinline__ uint2 lds64(uint32_t a) { uint2 v; asm volatile("ld.shared.v2.b32 {%0,%1}, [%2];" : "=r"(v.x), "=r"(v.y) : "r"(a) : "memory"); return v; }
__device__ __forceinline__ void sts64(uint32_t a, uint32_t x, uint32_t y) { asm volatile("st.shared.v2.b32 [%0], {%1,%2};" :: "r"(a), "r"(x), "r"(y) : "memory"); }
__device__ __forceinline__ uint32_t ldg_strong32(const void* p) { uint32_t v; asm volatile("ld.relaxed.gpu.global.u32 %0, [%1];" : "=r"(v) : "l"(p) : "memory"); return v; }
__device__ __forceinline__ uint32_t transpose8(uint32_t x) { uint32_t r; asm volatile("movmatrix.sync.aligned.m8n8.trans.b16 %0, %1;" : "=r"(r) : "r"(x)); return r; }
__device__ __forceinline__ uint32_t hadd2(uint32_t a, uint32_t b) { uint32_t r; asm("add.rn.bf16x2 %0, %1, %2;" : "=r"(r) : "r"(a), "r"(b)); return r; }
__device__ __forceinline__ uint32_t min4(uint4 v) { return min(__vimin3_u32(v.x, v.y, v.z), v.w); }

__device__ __forceinline__ void wg_ss192_01(float* d, uint64_t da, uint64_t db, int sd) {
  asm volatile("{.reg .pred p; setp.ne.b32 p, %98, 0;\n"
    "wgmma.mma_async.sync.aligned.m64n192k16.f32.bf16.bf16 {%0,%1,%2,%3,%4,%5,%6,%7,%8,%9,%10,%11,%12,%13,%14,%15,%16,%17,%18,%19,%20,%21,%22,%23,%24,%25,%26,%27,%28,%29,%30,%31,%32,%33,%34,%35,%36,%37,%38,%39,%40,%41,%42,%43,%44,%45,%46,%47,%48,%49,%50,%51,%52,%53,%54,%55,%56,%57,%58,%59,%60,%61,%62,%63,%64,%65,%66,%67,%68,%69,%70,%71,%72,%73,%74,%75,%76,%77,%78,%79,%80,%81,%82,%83,%84,%85,%86,%87,%88,%89,%90,%91,%92,%93,%94,%95}, %96, %97, p, 1, 1, 0, 1;}"
    : "+f"(d[0]),"+f"(d[1]),"+f"(d[2]),"+f"(d[3]),"+f"(d[4]),"+f"(d[5]),"+f"(d[6]),"+f"(d[7]),"+f"(d[8]),"+f"(d[9]),"+f"(d[10]),"+f"(d[11]),"+f"(d[12]),"+f"(d[13]),"+f"(d[14]),"+f"(d[15]),"+f"(d[16]),"+f"(d[17]),"+f"(d[18]),"+f"(d[19]),"+f"(d[20]),"+f"(d[21]),"+f"(d[22]),"+f"(d[23]),"+f"(d[24]),"+f"(d[25]),"+f"(d[26]),"+f"(d[27]),"+f"(d[28]),"+f"(d[29]),"+f"(d[30]),"+f"(d[31]),"+f"(d[32]),"+f"(d[33]),"+f"(d[34]),"+f"(d[35]),"+f"(d[36]),"+f"(d[37]),"+f"(d[38]),"+f"(d[39]),"+f"(d[40]),"+f"(d[41]),"+f"(d[42]),"+f"(d[43]),"+f"(d[44]),"+f"(d[45]),"+f"(d[46]),"+f"(d[47]),"+f"(d[48]),"+f"(d[49]),"+f"(d[50]),"+f"(d[51]),"+f"(d[52]),"+f"(d[53]),"+f"(d[54]),"+f"(d[55]),"+f"(d[56]),"+f"(d[57]),"+f"(d[58]),"+f"(d[59]),"+f"(d[60]),"+f"(d[61]),"+f"(d[62]),"+f"(d[63]),"+f"(d[64]),"+f"(d[65]),"+f"(d[66]),"+f"(d[67]),"+f"(d[68]),"+f"(d[69]),"+f"(d[70]),"+f"(d[71]),"+f"(d[72]),"+f"(d[73]),"+f"(d[74]),"+f"(d[75]),"+f"(d[76]),"+f"(d[77]),"+f"(d[78]),"+f"(d[79]),"+f"(d[80]),"+f"(d[81]),"+f"(d[82]),"+f"(d[83]),"+f"(d[84]),"+f"(d[85]),"+f"(d[86]),"+f"(d[87]),"+f"(d[88]),"+f"(d[89]),"+f"(d[90]),"+f"(d[91]),"+f"(d[92]),"+f"(d[93]),"+f"(d[94]),"+f"(d[95])
    : "l"(da), "l"(db), "r"(sd));
}
__device__ __forceinline__ void wg_ss128_01(float* d, uint64_t da, uint64_t db, int sd) {
  asm volatile("{.reg .pred p; setp.ne.b32 p, %66, 0;\n"
    "wgmma.mma_async.sync.aligned.m64n128k16.f32.bf16.bf16 {%0,%1,%2,%3,%4,%5,%6,%7,%8,%9,%10,%11,%12,%13,%14,%15,%16,%17,%18,%19,%20,%21,%22,%23,%24,%25,%26,%27,%28,%29,%30,%31,%32,%33,%34,%35,%36,%37,%38,%39,%40,%41,%42,%43,%44,%45,%46,%47,%48,%49,%50,%51,%52,%53,%54,%55,%56,%57,%58,%59,%60,%61,%62,%63}, %64, %65, p, 1, 1, 0, 1;}"
    : "+f"(d[0]),"+f"(d[1]),"+f"(d[2]),"+f"(d[3]),"+f"(d[4]),"+f"(d[5]),"+f"(d[6]),"+f"(d[7]),"+f"(d[8]),"+f"(d[9]),"+f"(d[10]),"+f"(d[11]),"+f"(d[12]),"+f"(d[13]),"+f"(d[14]),"+f"(d[15]),"+f"(d[16]),"+f"(d[17]),"+f"(d[18]),"+f"(d[19]),"+f"(d[20]),"+f"(d[21]),"+f"(d[22]),"+f"(d[23]),"+f"(d[24]),"+f"(d[25]),"+f"(d[26]),"+f"(d[27]),"+f"(d[28]),"+f"(d[29]),"+f"(d[30]),"+f"(d[31]),"+f"(d[32]),"+f"(d[33]),"+f"(d[34]),"+f"(d[35]),"+f"(d[36]),"+f"(d[37]),"+f"(d[38]),"+f"(d[39]),"+f"(d[40]),"+f"(d[41]),"+f"(d[42]),"+f"(d[43]),"+f"(d[44]),"+f"(d[45]),"+f"(d[46]),"+f"(d[47]),"+f"(d[48]),"+f"(d[49]),"+f"(d[50]),"+f"(d[51]),"+f"(d[52]),"+f"(d[53]),"+f"(d[54]),"+f"(d[55]),"+f"(d[56]),"+f"(d[57]),"+f"(d[58]),"+f"(d[59]),"+f"(d[60]),"+f"(d[61]),"+f"(d[62]),"+f"(d[63])
    : "l"(da), "l"(db), "r"(sd));
}
__device__ __forceinline__ void wg_ss160_01(float* d, uint64_t da, uint64_t db, int sd) {
  asm volatile("{.reg .pred p; setp.ne.b32 p, %82, 0;\n"
    "wgmma.mma_async.sync.aligned.m64n160k16.f32.bf16.bf16 {%0,%1,%2,%3,%4,%5,%6,%7,%8,%9,%10,%11,%12,%13,%14,%15,%16,%17,%18,%19,%20,%21,%22,%23,%24,%25,%26,%27,%28,%29,%30,%31,%32,%33,%34,%35,%36,%37,%38,%39,%40,%41,%42,%43,%44,%45,%46,%47,%48,%49,%50,%51,%52,%53,%54,%55,%56,%57,%58,%59,%60,%61,%62,%63,%64,%65,%66,%67,%68,%69,%70,%71,%72,%73,%74,%75,%76,%77,%78,%79}, %80, %81, p, 1, 1, 0, 1;}"
    : "+f"(d[0]),"+f"(d[1]),"+f"(d[2]),"+f"(d[3]),"+f"(d[4]),"+f"(d[5]),"+f"(d[6]),"+f"(d[7]),"+f"(d[8]),"+f"(d[9]),"+f"(d[10]),"+f"(d[11]),"+f"(d[12]),"+f"(d[13]),"+f"(d[14]),"+f"(d[15]),"+f"(d[16]),"+f"(d[17]),"+f"(d[18]),"+f"(d[19]),"+f"(d[20]),"+f"(d[21]),"+f"(d[22]),"+f"(d[23]),"+f"(d[24]),"+f"(d[25]),"+f"(d[26]),"+f"(d[27]),"+f"(d[28]),"+f"(d[29]),"+f"(d[30]),"+f"(d[31]),"+f"(d[32]),"+f"(d[33]),"+f"(d[34]),"+f"(d[35]),"+f"(d[36]),"+f"(d[37]),"+f"(d[38]),"+f"(d[39]),"+f"(d[40]),"+f"(d[41]),"+f"(d[42]),"+f"(d[43]),"+f"(d[44]),"+f"(d[45]),"+f"(d[46]),"+f"(d[47]),"+f"(d[48]),"+f"(d[49]),"+f"(d[50]),"+f"(d[51]),"+f"(d[52]),"+f"(d[53]),"+f"(d[54]),"+f"(d[55]),"+f"(d[56]),"+f"(d[57]),"+f"(d[58]),"+f"(d[59]),"+f"(d[60]),"+f"(d[61]),"+f"(d[62]),"+f"(d[63]),"+f"(d[64]),"+f"(d[65]),"+f"(d[66]),"+f"(d[67]),"+f"(d[68]),"+f"(d[69]),"+f"(d[70]),"+f"(d[71]),"+f"(d[72]),"+f"(d[73]),"+f"(d[74]),"+f"(d[75]),"+f"(d[76]),"+f"(d[77]),"+f"(d[78]),"+f"(d[79])
    : "l"(da), "l"(db), "r"(sd));
}
__device__ __forceinline__ void wg_ss80_01(float* d, uint64_t da, uint64_t db, int sd) {
  asm volatile("{.reg .pred p; setp.ne.b32 p, %42, 0;\n"
    "wgmma.mma_async.sync.aligned.m64n80k16.f32.bf16.bf16 {%0,%1,%2,%3,%4,%5,%6,%7,%8,%9,%10,%11,%12,%13,%14,%15,%16,%17,%18,%19,%20,%21,%22,%23,%24,%25,%26,%27,%28,%29,%30,%31,%32,%33,%34,%35,%36,%37,%38,%39}, %40, %41, p, 1, 1, 0, 1;}"
    : "+f"(d[0]),"+f"(d[1]),"+f"(d[2]),"+f"(d[3]),"+f"(d[4]),"+f"(d[5]),"+f"(d[6]),"+f"(d[7]),"+f"(d[8]),"+f"(d[9]),"+f"(d[10]),"+f"(d[11]),"+f"(d[12]),"+f"(d[13]),"+f"(d[14]),"+f"(d[15]),"+f"(d[16]),"+f"(d[17]),"+f"(d[18]),"+f"(d[19]),"+f"(d[20]),"+f"(d[21]),"+f"(d[22]),"+f"(d[23]),"+f"(d[24]),"+f"(d[25]),"+f"(d[26]),"+f"(d[27]),"+f"(d[28]),"+f"(d[29]),"+f"(d[30]),"+f"(d[31]),"+f"(d[32]),"+f"(d[33]),"+f"(d[34]),"+f"(d[35]),"+f"(d[36]),"+f"(d[37]),"+f"(d[38]),"+f"(d[39])
    : "l"(da), "l"(db), "r"(sd));
}
__device__ __forceinline__ void wg_rs32_00(float* d, uint32_t a0, uint32_t a1, uint32_t a2, uint32_t a3, uint64_t db, int sd) {
  asm volatile("{.reg .pred p; setp.ne.b32 p, %21, 0;\n"
    "wgmma.mma_async.sync.aligned.m64n32k16.f32.bf16.bf16 {%0,%1,%2,%3,%4,%5,%6,%7,%8,%9,%10,%11,%12,%13,%14,%15}, {%16,%17,%18,%19}, %20, p, 1, 1, 0;}"
    : "+f"(d[0]),"+f"(d[1]),"+f"(d[2]),"+f"(d[3]),"+f"(d[4]),"+f"(d[5]),"+f"(d[6]),"+f"(d[7]),"+f"(d[8]),"+f"(d[9]),"+f"(d[10]),"+f"(d[11]),"+f"(d[12]),"+f"(d[13]),"+f"(d[14]),"+f"(d[15])
    : "r"(a0), "r"(a1), "r"(a2), "r"(a3), "l"(db), "r"(sd));
}
__device__ __forceinline__ void wg_rs64_00(float* d, uint32_t a0, uint32_t a1, uint32_t a2, uint32_t a3, uint64_t db, int sd) {
  asm volatile("{.reg .pred p; setp.ne.b32 p, %37, 0;\n"
    "wgmma.mma_async.sync.aligned.m64n64k16.f32.bf16.bf16 {%0,%1,%2,%3,%4,%5,%6,%7,%8,%9,%10,%11,%12,%13,%14,%15,%16,%17,%18,%19,%20,%21,%22,%23,%24,%25,%26,%27,%28,%29,%30,%31}, {%32,%33,%34,%35}, %36, p, 1, 1, 0;}"
    : "+f"(d[0]),"+f"(d[1]),"+f"(d[2]),"+f"(d[3]),"+f"(d[4]),"+f"(d[5]),"+f"(d[6]),"+f"(d[7]),"+f"(d[8]),"+f"(d[9]),"+f"(d[10]),"+f"(d[11]),"+f"(d[12]),"+f"(d[13]),"+f"(d[14]),"+f"(d[15]),"+f"(d[16]),"+f"(d[17]),"+f"(d[18]),"+f"(d[19]),"+f"(d[20]),"+f"(d[21]),"+f"(d[22]),"+f"(d[23]),"+f"(d[24]),"+f"(d[25]),"+f"(d[26]),"+f"(d[27]),"+f"(d[28]),"+f"(d[29]),"+f"(d[30]),"+f"(d[31])
    : "r"(a0), "r"(a1), "r"(a2), "r"(a3), "l"(db), "r"(sd));
}
__device__ __forceinline__ void wg_rs24_01(float* d, uint32_t a0, uint32_t a1, uint32_t a2, uint32_t a3, uint64_t db, int sd) {
  asm volatile("{.reg .pred p; setp.ne.b32 p, %17, 0;\n"
    "wgmma.mma_async.sync.aligned.m64n24k16.f32.bf16.bf16 {%0,%1,%2,%3,%4,%5,%6,%7,%8,%9,%10,%11}, {%12,%13,%14,%15}, %16, p, 1, 1, 1;}"
    : "+f"(d[0]),"+f"(d[1]),"+f"(d[2]),"+f"(d[3]),"+f"(d[4]),"+f"(d[5]),"+f"(d[6]),"+f"(d[7]),"+f"(d[8]),"+f"(d[9]),"+f"(d[10]),"+f"(d[11])
    : "r"(a0), "r"(a1), "r"(a2), "r"(a3), "l"(db), "r"(sd));
}

#define AB_POLY 0xae
__device__ __forceinline__ constexpr bool poly_group(int group) { return (AB_POLY >> (group & 7)) & 1; }

template <int V> struct Int { static constexpr int value = V; };

template <int NG>
__device__ __forceinline__ void ln_stats(const float4 (&v)[NG][5], uint32_t scratch, float (&mean)[NG], float (&rs)[NG]) {
  const int warp = threadIdx.x >> 5, lane = threadIdx.x & 31;
#pragma unroll
  for (int r = 0; r < NG; r++) {
    float s = 0.f, q = 0.f;
#pragma unroll
    for (int i = 0; i < 5; i++) s += (v[r][i].x + v[r][i].y) + (v[r][i].z + v[r][i].w);
    s += __shfl_xor_sync(~0u, s, 1); s += __shfl_xor_sync(~0u, s, 2);
    s *= 1.f / 80;
#pragma unroll
    for (int i = 0; i < 5; i++) {
      const float x = v[r][i].x - s, y = v[r][i].y - s, z = v[r][i].z - s, w = v[r][i].w - s;
      q += (x * x + y * y) + (z * z + w * w);
    }
    q += __shfl_xor_sync(~0u, q, 1); q += __shfl_xor_sync(~0u, q, 2);
    mean[r] = s; rs[r] = q;
  }
  bar_sync(1, 256);
  if ((lane & 3) == 0) {
#pragma unroll
    for (int r = 0; r < NG; r++) sts64f(scratch + r * 512 + lane * 16 + warp * 8, mean[r], rs[r]);
  }
  bar_sync(1, 256);
#pragma unroll
  for (int r = 0; r < NG; r++) {
    const float4 e = lds128f(scratch + r * 512 + lane * 16);
    float t = e.x + e.z;
    t += __shfl_xor_sync(~0u, t, 1); t += __shfl_xor_sync(~0u, t, 2);
    t *= 0.125f;
    float q = e.y + e.w + 80.f * ((e.x - t) * (e.x - t) + (e.z - t) * (e.z - t));
    q += __shfl_xor_sync(~0u, q, 1); q += __shfl_xor_sync(~0u, q, 2);
    mean[r] = t; rs[r] = rsqrtf(q * (1.f / DM) + 1e-5f);
  }
}

__device__ __forceinline__ void ln_store(const uint32_t (&w)[2][5][2], int tile, int u0, bool live = true) {
  const int lane = threadIdx.x & 31;
  uint32_t* xc = g_xc + ((tile >> 1) * 40 + u0) * 256 + (tile & 1) * 64 + lane;
#pragma unroll
  for (int i = 0; i < 20; i++) if (live) xc[(i >> 1) * 128 + (i & 1) * 32] = w[i & 1][i >> 2][i >> 1 & 1];
#pragma unroll
  for (int i = 0; i < 5; i++) {
    const int u = u0 + i;
    uint32_t* xn = g_xn + (((tile >> 3) * 20 + (u >> 1)) * 16 + (tile & 1) * 8 + (tile & 6)) * 128 + (u & 1) * 64 + lane;
#pragma unroll
    for (int r = 0; r < 2; r++) if (live) { xn[r * 128] = w[r][i][0]; xn[r * 128 + 32] = w[r][i][1]; }
  }
}
__device__ __forceinline__ void wait_count(const uint32_t* c, uint32_t n) {
  int spin = 0;
  while ((ld_acquire(c) & 0xffff) < n) { __nanosleep(32); spin_guard(spin); }
}

__device__ __forceinline__ uint8_t* pool_at(uint32_t off) {
  return reinterpret_cast<uint8_t*>((reinterpret_cast<uintptr_t>(g_pool) + 8191) & ~(uintptr_t)8191) + off; }
struct Weights { const uint8_t* w[4]; };
__device__ __forceinline__ void prefetch_weights(const Weights& p, int i) {
  if (blockIdx.x < 128) asm volatile("cp.async.bulk.prefetch.L2.global [%0], 61440;" :: "l"(p.w[i] + (size_t)blockIdx.x * 61440) : "memory");
}
__global__ void __launch_bounds__(384) first_kernel(const __nv_bfloat16* __restrict__ xin, const uint4* __restrict__ wb, const __grid_constant__ Weights wa) {
  __shared__ __align__(16) float scratch[256];
  __shared__ uint32_t lat[4];
  const int warp = threadIdx.x >> 5, lane = threadIdx.x & 31, cta = blockIdx.x;
  TRACE(0);
  pdl_launch();
  if (warp >= 8) {
    if (warp < 10 || cta < NSLOT) {
      uint32_t* q = reinterpret_cast<uint32_t*>(pool_at((warp < 10 ? NSLOT : cta) * 8192 + (warp & 1) * 4096)) + (warp < 10 ? (cta & 127) * 8 : 0);
      if (lane < 8) stg_strong32(q + lane, 0u);
      uint32_t best = ~0u;
      if (lane == 0) {
        for (int r = 0; r < FK_REP; r++) {
          uint32_t t0, t1, v;
          asm volatile("mov.u32 %0, %%clock;" : "=r"(t0) :: "memory");
          asm volatile("atom.relaxed.gpu.global.exch.b32 %0, [%1], 0;" : "=r"(v) : "l"(q) : "memory");
          asm volatile("{.reg .u32 t; add.u32 t, %1, 1; mov.u32 %0, %%clock; sub.u32 %0, %0, %1;}" : "=r"(t1) : "r"(__shfl_sync(1u, v, 0)) : "memory");
          best = min(best, t1 - t0);
        }
        lat[warp - 8] = best;
      }
    }
    __syncwarp();
    bar_sync(2, cta < 128 ? 384 : 128);
    if (threadIdx.x == 288) for (int i = 0; i < FK_PF; i++) prefetch_weights(wa, i);
    if (threadIdx.x == 256) {
      const int part = lat[0] < lat[1] ? 0 : 1;
      uint32_t smid; asm("mov.u32 %0, %%smid;" : "=r"(smid));
      g_smpart[smid & 255] = part;
      g_smclk[smid & 255] = clk32() - gtime() * 2;
      g_smuse[smid & 255] = 0;
      if (cta < NSLOT) g_orient[cta] = lat[2] < lat[3] ? part : 1 - part;
    }
  } else if (cta < 128) {
    float4 v[2][5];
#pragma unroll
    for (int r = 0; r < 2; r++)
#pragma unroll
      for (int i = 0; i < 5; i++) {
        const uint32_t* src = reinterpret_cast<const uint32_t*>(xin) + (cta * 16 + r * 8 + (lane >> 2)) * (DM / 2) + warp * 40 + i * 8 + (lane & 3);
        const uint32_t a = src[0], b = src[4];
        v[r][i] = make_float4(bf_lo(a), bf_hi(a), bf_lo(b), bf_hi(b));
      }
    uint4 w8[2];
#pragma unroll
    for (int i = 0; i < 2; i++) w8[i] = wb[cta * 400 + min(i * 256 + threadIdx.x, 399)];
    float mean[2], rs[2];
    ln_stats<2>(v, s2u(scratch), mean, rs);
    bar_sync(2, 384);
    ABT(2, 2);
    if (threadIdx.x < 128) g_stat[cta * 128 + threadIdx.x] = make_float2(0.f, 0.f);
#pragma unroll
    for (int i = 0; i < 10; i++) g_x[((cta * 2 + i / 5) * 40 + warp * 5 + i % 5) * 32 + lane] = pack4(v[i / 5][i % 5]);
    uint32_t w[2][5][2];
#pragma unroll
    for (int i = 0; i < 10; i++) {
      const float4 t = v[i / 5][i % 5];
      const float m = mean[i / 5], q = rs[i / 5];
      w[i / 5][i % 5][0] = pack2((t.x - m) * q, (t.y - m) * q); w[i / 5][i % 5][1] = pack2((t.z - m) * q, (t.w - m) * q);
    }
    ln_store(w, cta, warp * 5);
    ABT(2, 3);
#pragma unroll
    for (int i = 0; i < 2; i++) {
      const int e = cta * 400 + min(i * 256 + threadIdx.x, 399), k = e / 80, n = e - k * 80, cg = n / 10;
      g_wb[((cg * 80 + (k >> 3)) * 10 + n - cg * 10) * 8 + (k & 7)] = w8[i];
    }
  } else if (cta == 128) {
    g_bo[threadIdx.x] = 0;
  }
  TRACE(2);
}

struct ChainParams {
  CUtensorMap wq, wk, wv, wo;
  const __nv_bfloat16* mem0;
  uint8_t *pool, *kv;
  const uint32_t* xc;
  uint32_t* sync;
  int layer;
  int d0, d3, d1, d1b, d2, d2b, mode;
};
constexpr int CH_WQ = 0, CH_WO = 81920, CH_X = CH_WO + 86016, CH_M = CH_X + 20480, CH_KT = CH_X + 40960, CH_VT = CH_KT + 4096,
              CH_PS = CH_VT + 4096, CH_QK = CH_PS + 4096, CH_VP = CH_QK + 4096, CH_SX = CH_VP + 1024, CH_O = CH_SX + 2304, CH_ID = CH_O + 3072,
              CH_BAR = CH_ID + 512;
constexpr int CH_SMEM = CH_BAR + 256;
constexpr int CH_BASE = 1024;
#define CH_VK0 8
#define CH_VK1 20
#define CH_L0 4
#define CH_LR 4
#define NOX 0
#define CH_XA 1
#define CH_XB 4
#define CH_W1 3
#define CH_W2 17
#define CH_W3 26
#define CH_R2 8
#define CH_VA 16
#define CH_EX 1
#define CH_KD 0
#define CH_RP 1
#define CH_KF 10
#define CH_LO 0
#define CH_LR1 4
#define CH_KP 0
#define CH_KM 0
#define CH_WE 0
#define CH_SP 1
#define CH_KW 3
#define CH_RB 0
#define CH_RC 8
#define CH_D0 200
#define CH_D1 450
#define CH_D2 300
#define CH_R1 4
#define CH_TW 12
__device__ __forceinline__ uint32_t opaque(uint32_t x) { return __shfl_sync(~0u, x, threadIdx.x & 31); }
__device__ __forceinline__ uint32_t nz(uint32_t x) { uint32_t r; asm("max.u32 %0, %1, 1;" : "=r"(r) : "r"(x)); return r; }
__device__ __forceinline__ uint32_t pack_tag(float lo, float hi, uint32_t tag, uint32_t mask) {
  uint32_t r;
  asm("lop3.b32 %0, %1, %2, %3, 0xD8;" : "=r"(r) : "r"(pack2(lo, hi)), "r"(tag), "r"(mask));
  return r;
}
__device__ __forceinline__ uint32_t differ(uint32_t a, uint32_t b, uint32_t t) { uint32_t r; asm("lop3.b32 %0, %1, %2, %3, 0x7E;" : "=r"(r) : "r"(a), "r"(b), "r"(t)); return r; }
__device__ __forceinline__ void mbar_wait_hot(uint32_t bar, uint32_t ph) {
  uint32_t ok;
  asm volatile("{.reg .pred p; mbarrier.try_wait.parity.shared::cta.b64 p, [%1], %2; selp.u32 %0, 1, 0, p;}" : "=r"(ok) : "r"(bar), "r"(ph) : "memory");
  if (__builtin_expect(!ok, 0)) mbar_wait(bar, ph);
}
__device__ __forceinline__ bool elect() {
  uint32_t r; asm volatile("{.reg .pred p; elect.sync _|p, 0xffffffff; selp.u32 %0, 1, 0, p;}" : "=r"(r)); return r; }
__device__ __forceinline__ uint32_t or3(uint32_t a, uint32_t b, uint32_t c) { uint32_t r; asm("lop3.b32 %0, %1, %2, %3, 0xFE;" : "=r"(r) : "r"(a), "r"(b), "r"(c)); return r; }
__device__ __forceinline__ void pin() { pdl_launch(); }
__device__ __forceinline__ void mma16h(float* d, uint32_t a0, uint32_t a2, uint32_t b0, uint32_t b1) {
  asm volatile("{.reg .b32 u, v; mma.sync.aligned.m16n8k16.row.col.f32.bf16.bf16.f32 {%0,%1,%2,%3},{%4,u,%5,v},{%6,%7},{%0,%1,%2,%3};}"
               : "+f"(d[0]), "+f"(d[1]), "+f"(d[2]), "+f"(d[3]) : "r"(a0), "r"(a2), "r"(b0), "r"(b1)); }
__device__ __forceinline__ void mma8h(float* d, uint32_t a0, uint32_t b0) {
  asm volatile("{.reg .b32 u; mma.sync.aligned.m16n8k8.row.col.f32.bf16.bf16.f32 {%0,%1,%2,%3},{%4,u},{%5},{%0,%1,%2,%3};}"
               : "+f"(d[0]), "+f"(d[1]), "+f"(d[2]), "+f"(d[3]) : "r"(a0), "r"(b0)); }
__device__ __forceinline__ uint32_t absmax2(uint32_t a, uint32_t b) { uint32_t r; asm("max.xorsign.abs.bf16x2 %0, %1, %2;" : "=r"(r) : "r"(a), "r"(b)); return r; }
__device__ __forceinline__ void until(uint32_t t) { while ((int)(clk32() - t) < 0) {} }
__device__ __forceinline__ uint4 pack8(const float* d) { return make_uint4(pack2(d[0], d[1]), pack2(d[2], d[3]), pack2(d[4], d[5]), pack2(d[6], d[7])); }
__device__ __forceinline__ void add8(float* d, uint4 v) {
  d[0] += bf_lo(v.x); d[1] += bf_hi(v.x); d[2] += bf_lo(v.y); d[3] += bf_hi(v.y);
  d[4] += bf_lo(v.z); d[5] += bf_hi(v.z); d[6] += bf_lo(v.w); d[7] += bf_hi(v.w);
}

template <int WG>
__device__ __forceinline__ void chain_body(const ChainParams& p, const uint32_t wq, const uint32_t (&ak)[80], const uint32_t (&av)[80]) {
  const int tid = threadIdx.x & 127, t4 = __shfl_sync(~0u, tid >> 5, 0), lane = tid & 31;
  const int cta = blockIdx.x, h = cta / 3, j = cta - 3 * h;
  const uint32_t sb = mapa(CH_BASE, j);
  const uint32_t bWo = sb + CH_BAR, bWq = bWo + 8, bX = bWo + 16, bXA = bWo + 24, bXB = bWo + 32, bO = bWo + 40, bG = bWo + 48, bH = bWo + 96;
  uint32_t tw[4 * CH_TW];
  auto refill = [&]() {
#pragma unroll
    for (int k = 0; k < CH_TW; k++) ldsm4t(&tw[4 * k], wq + k * 2048);
  };
  const uint32_t wo = opaque((sb + CH_WO + (WG == 0 ? (t4 + (j == 2)) * 4096 : (j == 2 ? 0 : 24576) + t4 * 1024) + ((lane & 7) + (lane >> 4) * 8) * 64 +
                              ((((lane >> 3) & 1) ^ ((lane >> 1) & 3)) << 4)) ^ (WG == 1 && j == 2 ? 32 : 0));
  const uint32_t wo2 = opaque((wo ^ ((t4 & 1) * 32)) + (4 + (t4 >> 1) - t4) * 4096);
  const uint32_t l16 = opaque(sb + lane * 16);
  const uint32_t l8 = opaque(sb + t4 * 256 + lane * 8);
  const uint32_t lw = opaque(sb + t4 * 1024 + lane * 16);
  const uint32_t qs = opaque(sb + CH_QK + WG * 2048 + t4 * 512 + lane * 16);
  const uint32_t qa = opaque(sb + CH_QK + (lane >> 4) * 2048 + (lane & 15) * 16 + (WG == 0 ? t4 * 512 + 256 : t4 == 3 ? 1024 : 0));
  const uint32_t ka = opaque(t4 < 2 ? sb + CH_KT + t4 * 512 + lane * 16
                                    : sb + CH_QK + 256 + (t4 - 2) * 1024 + ((lane >> 3) & 1) * 2048 + (lane >> 4) * 128 + (lane & 7) * 16);
  const uint32_t l4 = opaque(sb + t4 * 256 + lane * 4);
  uint32_t pdst[1], pages = 0;
  auto line0 = [&](int i) { return 28 * j + (i < 4 ? 4 * t4 + i : 12 + 2 * t4 + i); };
  const uint32_t plane = opaque((lane >> 4) * 2048 + h * 64 + (lane & 15) * 4);
  if (WG == 0) {
    pages = __ballot_sync(~0u, lds32(sb + CH_O + line0(min(lane, 5)) * 4) & 4096);
  } else {
    pages = __ballot_sync(~0u, lds32(sb + CH_O + (80 + min(lane, 11)) * 4) & 4096);
    pdst[0] = opaque(lds32(sb + CH_O + (j == 0 ? 24 + t4 : 50 + 2 * j + (t4 & 1)) * 4) + plane);
  }
  const uint32_t role = lds32(sb + CH_O + NSLOT * 4), rsrc = lds32(sb + CH_O + role * 4), rdst = (80 + role / 20) * 8192 + role % 20 * 128;
  const uint32_t r1 = mapa(CH_BASE, j == 2 ? 0 : j + 1) - sb, r2 = mapa(CH_BASE, j == 0 ? 2 : j - 1) - sb;
  uint32_t tag = opaque(1);
  auto pool = [&](uint32_t off) { return p.pool + ((tag & 0xfffe) + off); };
  auto after = [&](uint32_t x) { return x & tag & 0xfffe; };
  auto kv = [&](int s, uint32_t a) { return p.kv + (a + ((cta * 2 * NSEG + s) * KV_BYTES - sb)); };
  auto pass = [&](float (&d)[16], const uint32_t (&a)[80], auto k0, auto k1) {
    const uint64_t db = mkdesc(CH_BASE + CH_X + WG * 20480, 512, 128, 0);
#pragma unroll
    for (int k = k0.value; k < k1.value; k++) wg_rs32_00(d, a[4 * k], a[4 * k + 1], a[4 * k + 2], a[4 * k + 3], db + k * 64, k);
    wg_commit();
  };
  auto dump = [&](float (&d)[16], uint32_t a) {
    reg_fence<16>(d);
    sts128(a, pack8(d)); sts128(a + 512, pack8(d + 8));
  };
  uint32_t pph = 0;
  auto tokens0 = [&](int s, auto k0) {
    float dk[16], dv[16];
    bar_sync(9, 256);
    wg_fence();
    pass(dk, ak, Int<0>(), Int<4>());
    const uint4 a0 = lds128(lw + CH_KT), a1 = lds128(lw + CH_KT + 512);
    pin();
    pass(dk, ak, Int<4>(), Int<20>());
    pass(dv, av, Int<0>(), Int<CH_VA>());
    pin();
    wg_wait<1>();
    reg_fence<16>(dk);
    add8(dk, a0); add8(dk + 8, a1);
    const uint4 w0 = pack8(dk), w1 = pack8(dk + 8);
    const uint4 b0 = lds128(lw + CH_VT), b1 = lds128(lw + CH_VT + 512);
    stsm4t(lw + CH_KT, w0.x, w0.z, w0.y, w0.w); stsm4t(lw + CH_KT + 512, w1.x, w1.z, w1.y, w1.w);
    if (CH_KP == 2) bar_arrive(7, 160);
    TM1(6);
    pin();
    if (CH_VA < 20) pass(dv, av, Int<CH_VA>(), Int<20>());
    pin();
#pragma unroll
    for (int k = k0.value; k < CH_TW; k++) ldsm4t(&tw[4 * k], wq + k * 2048);
    TM1(9);
    if (k0.value < CH_TW && t4 >= 2) { mbar_wait_hot(bH + t4 * 16 - 24 + (pph & 1) * 8, pph >> 1 & 1); pph++; }
    __syncwarp();
    wg_wait<0>();
    reg_fence<16>(dv);
    add8(dv, b0); add8(dv + 8, b1);
#pragma unroll
    for (int e = 0; e < 2; e++) { const uint4 v = pack8(dv + 8 * e); sts128(lw + CH_VT + e * 512, make_uint4(v.x, v.z, v.y, v.w)); }
  };
  auto publish_k = [&](int s) {
    if (t4 == CH_KW && elect()) { fence_async(); bulk_store(p.kv + (size_t)(cta * 2 * NSEG + s) * KV_BYTES, sb + CH_KT, 4096); bulk_commit(); }
    __syncwarp();
  };
  if (WG == 0) {
    mbar_wait(bXB, 0);
    tokens0(0, Int<CH_TW>());
  } else {
    const uint32_t* m0 = reinterpret_cast<const uint32_t*>(p.mem0) + (lane >> 2) * 320 + t4 * 80 + (lane & 3);
    uint32_t a[20];
#pragma unroll
    for (int i = 0; i < 20; i++) a[i] = m0[4 * i];
    pin();
    float dk[16], dv[16];
    mbar_wait(bXA, 0);
    wg_fence();
    pass(dk, ak, Int<0>(), Int<20>());
    pass(dv, av, Int<0>(), Int<20>());
    wg_wait<0>();
    dump(dk, lw + CH_KT);
    dump(dv, lw + CH_VT);
    bar_sync(9, 256);
    if (CH_KP == 2 && t4 == CH_KW) { bar_sync(7, 160); publish_k(0); }
#pragma unroll
    for (int i = 0; i < 20; i++) sts32(sb + CH_M + (t4 * 20 + i) * 128 + lane * 4, nz(transpose8(a[i])));
    __syncwarp();
    if (elect()) mbar_arrive(bG + t4 * 8);
  }
  PRO(8);
  mbar_wait(bWq, 0);
  refill();
  PRO(9);
  mbar_wait(bWo, 0);
  asm volatile("barrier.cluster.wait.aligned;" ::: "memory");
  PRO(10);
  auto load_x = [&](int s, int k0, int n, uint32_t bar) {
    if (!NOX && elect()) { mbar_expect(bar, n * 1024); bulk_load(sb + CH_X + k0 * 1024, p.xc + (s + 1) * 10240 + k0 * 256, n * 1024, bar); }
  };
  constexpr int VK = WG == 0 ? CH_VK0 : CH_VK1;
  uint32_t gph = 0;
  int st = 0;
  const uint32_t ca = opaque(sb + CH_M + t4 * 2560 + lane * 32 + (lane >> 2) * 4);
  auto project = [&](int s, uint32_t (&b)[40], float (&dv)[16], uint32_t (&kf)[16]) {
    float dq[4] = {}, dk[4] = {};
    uint32_t w[80];
#pragma unroll
    for (int i = 0; i < 4 * CH_TW; i++) w[i] = tw[i];
    constexpr int LR = WG == 1 ? CH_LR1 : CH_LR;
    auto load = [&](int n) {
      int c = 0;
#pragma unroll
      for (int i = 0; i < 10; i++) {
        if (i == CH_KF) {
#pragma unroll
          for (int q = 0; q < 4; q++)
            if (WG == 1 && c++ == n) ldsm4(&kf[4 * q], ka + q * 1024);
        }
        if (c++ == n) ldsm4t(&b[4 * i], l16 + CH_M + WG * 5120 + i * 512);
#pragma unroll
        for (int k = 2 * i; k < 2 * i + 2; k++)
          if (k >= CH_TW && c++ == n) ldsm4t(&w[4 * k], wq + k * 2048);
      }
#pragma unroll
      for (int i = 0; i < 4; i++)
        if (WG == 1 && CH_KF >= 10 && c++ == n) ldsm4(&kf[4 * i], ka + i * 1024);
    };
    if (WG == 1) {
      for (int n = 0;;) {
        mbar_wait(bG + t4 * 8, gph);
        TR(5, (clk32() & ~3u) | min(n, 3));
        gph ^= 1;
        if (__builtin_expect(!__any_sync(~0u, __vimin3_u32(lds32(ca), lds32(ca + 1024), lds32(ca + 1536)) == 0), 1)) break;
        if (elect()) {
          const int q = (st == 0 ? 8 : st * 4 - 4) + t4;
          mbar_expect(bG + t4 * 8, 2560);
          bulk_load(sb + CH_M + t4 * 2560, p.pool + ((80 + q) * 8192 + (pages >> q & 1) * 4096), 2560, bG + t4 * 8);
        }
        spin_guard(n);
      }
    }
    bar_sync(6, 256);
#pragma unroll
    for (int i = 0; i < CH_L0; i++) load(i);
    if (WG == 0 && CH_XB == 4 && s + 1 < NSEG) load_x(s, 5 * t4, 5, bXB);
    TM(0);
    TM1(11);
    if (WG == 1) TR(6, clk32());
#pragma unroll
    for (int k = 0; k < 20; k += 2) {
      if (k > 0) {
#pragma unroll
        for (int n = (k == 18 ? 40 : CH_L0 + k * LR / 4) - 1; n >= CH_L0 + (k - 2) * LR / 4; n--) { load(n); if (CH_LO) __syncwarp(); }
      }
      pin();
#pragma unroll
      for (int kk = k; kk < k + 2; kk++) {
        mma16(dk, ak[4 * kk], ak[4 * kk + 1], ak[4 * kk + 2], ak[4 * kk + 3], b[2 * kk], b[2 * kk + 1]);
        mma16(dq, w[4 * kk], w[4 * kk + 1], w[4 * kk + 2], w[4 * kk + 3], b[2 * kk], b[2 * kk + 1]);
        if (kk < VK) mma16(dv, av[4 * kk], av[4 * kk + 1], av[4 * kk + 2], av[4 * kk + 3], b[2 * kk], b[2 * kk + 1]);
      }
    }
    const float k2 = 0.07216878364870322f * 1.44269504089f;
    stsm4t(qs, pack2(dq[0] * k2, dq[1] * k2), pack2(dq[2] * k2, dq[3] * k2), pack2(dk[0], dk[1]), pack2(dk[2], dk[3]));
    TM(1);
  };
  static_assert(CH_VK1 == 20 && CH_KP == 0 && CH_XA > 0 && CH_XB > 0, "last step");
  constexpr int VC = VK == 20 ? 1 : WG == 0 ? 2 : 3;
  auto finish_v = [&](const uint32_t (&b)[40], float (&dv)[16]) {
#pragma unroll
    for (int kk = VK; kk < 20; kk++) mma16(dv + 4 * ((kk - VK) % VC), av[4 * kk], av[4 * kk + 1], av[4 * kk + 2], av[4 * kk + 3], b[2 * kk], b[2 * kk + 1]);
  };
  auto sum_v = [&](float (&dv)[16]) {
#pragma unroll
    for (int i = 4; i < 4 * VC; i++) dv[i & 3] += dv[i];
  };
  auto publish_km = [&](int s) {
    uint32_t a[4];
    ldsm4(a, qa);
    *reinterpret_cast<uint2*>(kv(s, l8) + KV_M) = make_uint2(hadd2(a[0], a[2]), hadd2(a[1], a[3]));
  };
  auto memory_v = [&](uint2 x, const float (&dv)[16]) {
    return make_uint2(pack2(dv[0] + bf_lo(x.x), dv[1] + bf_hi(x.x)), pack2(dv[2] + bf_lo(x.y), dv[3] + bf_hi(x.y)));
  };
  auto publish_v = [&](int s, const uint4 (&v)[2], uint2 vm) {
#pragma unroll
    for (int e = 0; e < 2; e++) reinterpret_cast<uint4*>(kv(s, lw) + KV_V)[e * 32] = v[e];
    *reinterpret_cast<uint2*>(kv(s, l8) + KV_V + KV_M) = vm;
  };
#pragma unroll 1
  for (int s = 0;; s++) {
    float dv[16] = {};
    uint32_t b[40], kf[16];
    project(s, b, dv, kf);
    if (WG == 0) {
      bar_sync(1, 256);
      if (CH_XA == 0) load_x(s, 20 + 5 * t4, 5, bXA);
      if (CH_XB == 0) load_x(s, 5 * t4, 5, bXB);
      pin();
      finish_v(b, dv);
      sum_v(dv);
      sts64(l8 + CH_VP, pack2(dv[0], dv[1]), pack2(dv[2], dv[3]));
      if (s == NSEG - 1) {
        bar_arrive(10, 256);
        publish_k(s);
        publish_km(s);
        bulk_wait<0>();
        fence_async_global();
        bar_sync(2, 256);
        if (tid == 0) red_release(p.sync + 15 * 8 + 4, 1);
        break;
      }
      __syncwarp();
      if (elect()) mbar_arrive(bX);
      if (CH_XA == 1) load_x(s, 20 + 5 * t4, 5, bXA);
      if (CH_XB == 1) load_x(s, 5 * t4, 5, bXB);
      uint32_t w[144];
      auto wload = [&](int i) { ldsm4t(&w[4 * i], (i % 3 == 0 ? wo : i % 3 == 1 ? wo ^ 32 : wo2) + i / 12 * 28672 + i / 3 % 4 * 1024); };
      TM(3);
      if (CH_KP == 0) publish_k(s);
#pragma unroll
      for (int i = 0; i < CH_W1; i++) wload(i);
      bar_sync(10, 256);
      uint32_t km[4];
      ldsm4(km, qa);
      pin();
#pragma unroll
      for (int i = CH_W1; i < CH_W2; i++) wload(i);
      pin();
      const uint2 kms = make_uint2(hadd2(km[0], km[2]), hadd2(km[1], km[3]));
      if (CH_KM == 0) *reinterpret_cast<uint2*>(kv(s, l8) + KV_M) = kms;
      if (CH_KP == 0) bulk_wait_read<0>();
      if (CH_XA == 2) load_x(s, 20 + 5 * t4, 5, bXA);
      if (CH_XB == 2) load_x(s, 5 * t4, 5, bXB);
      bar_sync(2, 256);
      {
        float y[3][4] = {};
        uint32_t ob[24];
        ldsm4(&ob[0], l16 + CH_O + 1024); ldsm4(&ob[4], l16 + CH_O + 1536);
        TM(7);
        auto step = [&](int i) {
          const int k = i / 3;
          mma16(y[i % 3], w[4 * i], w[4 * i + 1], w[4 * i + 2], w[4 * i + 3], ob[2 * k], ob[2 * k + 1]);
        };
#pragma unroll
        for (int i = 0; i < 12; i++) {
          step(i);
          if (i >= 12 - (CH_W3 - CH_W2)) wload(CH_W3 - 12 + i);
          if (i % 3 == 2) pin();
        }
        if (CH_XB == 3) load_x(s, 5 * t4, 5, bXB);
        if (CH_KM == 1) *reinterpret_cast<uint2*>(kv(s, l8) + KV_M) = kms;
        pin();
        mbar_wait(bO, s & 1);
        TM(4);
        ldsm4(&ob[8], l16 + CH_O); ldsm4(&ob[12], l16 + CH_O + 512);
        pin();
        float2 inv;
        uint8_t* dst[6];
        uint32_t mask;
#pragma unroll
        for (int i = 12; i < 36; i++) {
          step(i);
          const int n = CH_W3 + i - 13, m = n - (n > 30);
          if (i == 12) ldsm4(&ob[16], l16 + after(w[4 * CH_W3 - 1] | w[4 * CH_W3 - 5] | w[4 * CH_W3 - 9] | ob[8]) + CH_O + 2048);
          else if (n == 30) ldsm4(&ob[20], l16 + CH_O + 2560);
          else if (m < 36) wload(m);
          else if (m == 36) inv = lds64f((l8 & ~0xe0u) + CH_VP);
          if (i == 26) mask = ((l16 ^ tag) & 48) == 0;
          if (i >= 27 && i < 33) dst[i - 27] = pool(line0(i - 27) * 8192 + (pages >> (i - 27) & 1) * 4096) + plane;
          if (i % 3 == 2) pin();
        }
#pragma unroll
        for (int k = 0; k < CH_R1; k++) ldsm4t(&tw[4 * k], wq + k * 2048);
        pin();
#pragma unroll
        for (int i = 0; i < 6; i++) stg_strong32(dst[i], pack_tag(y[i >> 1][2 * (i & 1)] * inv.x, y[i >> 1][2 * (i & 1) + 1] * inv.y, tag, mask));
        TM(8);
        TR(0, clk32());
        bar_arrive(5, 256);
        pin();
      }
      const uint32_t t0 = clk32();
      auto refill2 = [&]() {
#pragma unroll
        for (int k = CH_R1; k < CH_R2; k++) ldsm4t(&tw[4 * k], wq + k * 2048);
      };
      if (CH_RP == 0) refill2();
      const uint32_t ln = (l16 ^ tag) >> 4 & 31;
      if (t4 >= 2) {
        const uint32_t bP = bH + t4 * 16 - 24, ps = CH_PS + (t4 & 1) * 4096;
        auto fetch = [&](uint32_t k) {
          if (elect()) { mbar_expect(bP + (k & 1) * 8, 2048); bulk_load(sb + ps + (k & 1) * 2048, p.pool + (rsrc + (t4 & 1) * 2048), 2048, bP + (k & 1) * 8); }
        };
        until(t0 + CH_D0);
        fetch(pph);
        if (CH_RP == 2) refill2();
        if (!NOX) mbar_wait_hot(bXB, (s + 1) & 1);
        const uint32_t want = (tag & 1) * 0x10001, chk = opaque(ln < 4 ? 0x10001 : 0);
        uint4 sel;
        sel.x = opaque((ln >> 3) != (ln & 1) ? 0 : ln & 4 ? 0x3f800000u : 0x00003f80u);
        sel.z = opaque(sel.x); sel.y = opaque(ln); sel.w = opaque(ln + 1);
        uint8_t* mdst = p.pool + opaque(st * 32768 + rdst + (t4 & 1) * 64 + ln * 4);
        until(t0 + CH_D1);
        fetch(pph + 1);
        TM(5);
        if (CH_RP == 1) refill2();
        int n = 0;
        uint32_t u[16];
        float y[4][4];
        auto sum = [&]() {
#pragma unroll
          for (int i = 0; i < 16; i++) y[i >> 2][i & 3] = 0.f;
#pragma unroll
          for (int i = 0; i < 8; i++) mma16(y[i & 3], sel.x, sel.y, sel.z, sel.w, u[2 * i], u[2 * i + 1]);
        };
        auto check = [&](auto spec) {
          mbar_wait(bP + (pph & 1) * 8, pph >> 1 & 1);
          TM(14);
          TR(2, clk32());
#pragma unroll
          for (int i = 0; i < 4; i++) ldsm4t(&u[4 * i], l16 + (ps + (pph & 1) * 2048) + i * 512);
          pph++;
          if (spec.value) { pin(); sum(); }
          uint32_t bad = 0;
#pragma unroll
          for (int i = 0; i < 4; i++) bad = or3(bad, differ(u[4 * i], u[4 * i + 1], want), differ(u[4 * i + 2], u[4 * i + 3], want));
          return __any_sync(~0u, bad & chk);
        };
        if (CH_SP) {
          if (check(Int<0>())) {
            do { fetch(pph + 1); spin_guard(n); } while (check(Int<1>()));
          } else {
            sum();
          }
        } else {
          while (check(Int<0>())) { fetch(pph + 1); spin_guard(n); }
          sum();
        }
        TR(1, t0 + (n ? CH_D1 : CH_D0));
        TM(15);
        const uint32_t w = nz(pack2((y[0][0] + y[1][0]) + (y[2][0] + y[3][0]), (y[0][1] + y[1][1]) + (y[2][1] + y[3][1])));
        if (ln < 16) { stg_strong32(mdst, w); stg_strong32(mdst + 4096, w); }
        TMV(12, 32, n);
        TR(3, (clk32() & ~3u) | min(n, 3));
      } else {
        if (CH_RP) refill2();
        if (!NOX) mbar_wait_hot(bXB, (s + 1) & 1);
        stg_strong32(p.pool + ((st == 2 ? 0 : st + 1) * 32768 + rdst + t4 * 4096) + ln * 4, 0u);
        if (t4 == 0 && cta < 40 && s + 4 < NSEG && elect())
          asm volatile("cp.async.bulk.prefetch.L2.global [%0], 1024;" :: "l"(p.xc + (s + 4) * 10240 + cta * 256) : "memory");
        if (t4 == 1 && (s & 3) == 0 && s > 0 && elect()) red_relaxed(p.sync + 2 * s - 4, 1);
        if (t4 == 1 && s == NSEG - 3 && cta == 95 && elect()) red_relaxed(p.sync + 2 * s + 2, 0x10000);
      }
      TM(10);
      bar_arrive(8, 256);
      tokens0(s + 1, Int<CH_R2>());
      TM(2);
      TR(7, clk32());
    } else {
      if (s == NSEG - 1) {
        bar_arrive(1, 256);
        const uint4 v[2] = {lds128(lw + CH_VT), lds128(lw + CH_VT + 512)};
        bar_sync(10, 256);
        publish_v(s, v, memory_v(lds64(l8 + CH_VP), dv));
        bar_arrive(2, 256);
        break;
      }
      const uint32_t xo = l4 + (CH_SX - (t4 == 3 ? 128 : 0)), x1 = xo + (r1 + 768 + min(t4, 2) * 256), x2 = xo + (r2 + 1024 + min(t4, 2) * 256);
      if (t4 < 2) {
        float ds[4][4] = {};
        uint32_t q[16];
        asm volatile("bar.sync 1, 256;" ::: "memory");
#pragma unroll
        for (int k = 0; k < 4; k++) ldsm4(&q[4 * k], qa + k * 512);
        pin();
        if (VK < 20) { finish_v(b, dv); pin(); }
#pragma unroll
        for (int k = 0; k < 4; k++) {
          mma16(ds[k & 1], kf[4 * k], kf[4 * k + 1], kf[4 * k + 2], kf[4 * k + 3], q[4 * k], q[4 * k + 1]);
          mma16(ds[2 + (k & 1)], kf[4 * k], kf[4 * k + 1], kf[4 * k + 2], kf[4 * k + 3], q[4 * k + 2], q[4 * k + 3]);
        }
        float t[4];
#pragma unroll
        for (int i = 0; i < 4; i++) t[i] = (ds[0][i] + ds[2][i]) + (ds[1][i] + ds[3][i]);
        const uint32_t w0 = pack2(t[0], t[1]), w1 = pack2(t[2], t[3]);
        st_async32(x1, w0, bX + r1); st_async32(x2, w0, bX + r2);
        st_async32(x1 + 128, w1, bX + r1); st_async32(x2 + 128, w1, bX + r2);
        sts32(xo, w0); sts32(xo + 128, w1);
      } else {
        float ds[4][4] = {};
        uint32_t q0[4], q1[4], a0[4], a1[4];
        asm volatile("bar.sync 1, 256; " ::: "memory");
        ldsm4(a0, ka); ldsm4(q0, qa); ldsm4(a1, ka + 512); ldsm4(q1, qa + 512);
        pin();
        if (VK < 20) { finish_v(b, dv); pin(); }
        mma16(ds[0], a0[0], a0[1], a0[2], a0[3], q0[0], q0[1]);
        mma16(ds[1], a0[0], a0[1], a0[2], a0[3], q0[2], q0[3]);
        mma16(ds[2], a1[0], a1[1], a1[2], a1[3], q1[0], q1[1]);
        mma16(ds[3], a1[0], a1[1], a1[2], a1[3], q1[2], q1[3]);
        float t[2];
#pragma unroll
        for (int i = 0; i < 2; i++)
          t[i] = ((ds[0][i] + ds[0][i + 2]) + (ds[1][i] + ds[1][i + 2])) + ((ds[2][i] + ds[2][i + 2]) + (ds[3][i] + ds[3][i + 2]));
        const uint32_t w0 = pack2(t[0], t[1]);
        st_async32(x1, w0, bX + r1);
        st_async32(x2, w0, bX + r2);
        sts32(xo, w0);
      }
      TM(3);
      const uint4 id = lds128(l16 + CH_ID);
      float sc[3][4] = {};
      uint4 v[2];
      sum_v(dv);
      bar_sync(3, 128);
      uint32_t r[12], wd[12], we[12] = {};
      ldsm4(&r[0], l16 + CH_SX); ldsm2(&r[4], l16 + CH_SX + 512);
      pin();
      v[0] = lds128(lw + CH_VT); v[1] = lds128(lw + CH_VT + 512);
#pragma unroll
      for (int u = 0; u < 3; u++) ldsm4t(&wd[4 * u], wo + u * 28672);
      if (CH_WE && j == 0) {
#pragma unroll
        for (int u = 0; u < 3; u++) ldsm4t(&we[4 * u], (wo ^ 32) + u * 28672);
      }
      pin();
#pragma unroll
      for (int q = 0; q < 3; q++) mma16(sc[q], id.x, id.y, id.z, id.w, r[2 * q], r[2 * q + 1]);
      uint32_t big = absmax2(absmax2(absmax2(r[0], r[1]), absmax2(r[2], r[3])), absmax2(r[4], r[5]));
      const uint32_t oa1 = l4 + (r1 + CH_O), oa2 = l4 + (r2 + CH_O + 2048), ones = 0x3f803f80u;
      mbar_wait_hot(bX, s & 1);
      TM(4);
      ldsm4(&r[0], l16 + CH_SX + 768); ldsm4(&r[8], l16 + CH_SX + 1792); ldsm4(&r[4], l16 + CH_SX + 1280);
      const uint2 vp = lds64(l8 + CH_VP);
      bar_arrive(10, 256);
      pin();
      {
        float sd[3][4] = {};
#pragma unroll
        for (int i = 0; i < 3; i++) {
          const int q = i == 0 ? 0 : 3 - i;
          mma16(sc[q], id.x, id.y, id.z, id.w, r[4 * q], r[4 * q + 1]);
          mma16(sd[q], id.x, id.y, id.z, id.w, r[4 * q + 2], r[4 * q + 3]);
          big = absmax2(big, absmax2(absmax2(r[4 * q], r[4 * q + 1]), absmax2(r[4 * q + 2], r[4 * q + 3])));
        }
#pragma unroll
        for (int i = 0; i < 12; i++) sc[i >> 2][i & 3] += sd[i >> 2][i & 3];
      }
      const bool redo = __any_sync(~0u, (absmax2(big, big << 16) & 0x7fff0000u) >= 0x41800000u);
      const uint2 vm = memory_v(vp, dv);
      sc[2][0] += sc[2][2]; sc[2][1] += sc[2][3];
      float l[4], o[2][4];
      uint32_t p3, p4;
      auto attend = [&]() {
#pragma unroll
        for (int i = 0; i < 4; i++) l[i] = o[0][i] = o[1][i] = 0.f;
        const uint32_t p1 = pack2(ex2(sc[0][0]), ex2(sc[0][1])), p2 = pack2(ex2(sc[0][2]), ex2(sc[0][3]));
        mma16h(o[0], p1, p2, v[0].x, v[0].y);
        mma16h(o[1], p1, p2, v[0].z, v[0].w);
        mma16h(l, p1, p2, ones, ones);
        const uint32_t p0 = pack2(ex2(sc[2][0]), ex2(sc[2][1]));
        mma8h(o[0], p0, vm.x);
        mma8h(o[1], p0, vm.y);
        mma8h(l, p0, ones);
        p3 = pack2(ex2(sc[1][0]), ex2(sc[1][1])); p4 = pack2(ex2(sc[1][2]), ex2(sc[1][3]));
        mma16h(o[0], p3, p4, v[1].x, v[1].y);
        mma16h(o[1], p3, p4, v[1].z, v[1].w);
      };
      attend();
      if (__builtin_expect(redo, 0)) {
        float mx = fmaxf(sc[2][0], sc[2][1]);
#pragma unroll
        for (int i = 0; i < 4; i++) mx = fmaxf(mx, fmaxf(sc[0][i], sc[1][i]));
        mx = fmaxf(mx, __shfl_xor_sync(~0u, mx, 1));
        mx = fmaxf(mx, __shfl_xor_sync(~0u, mx, 2));
#pragma unroll
        for (int i = 0; i < 4; i++) { sc[0][i] -= mx; sc[1][i] -= mx; }
        sc[2][0] -= mx; sc[2][1] -= mx;
        attend();
      }
      const uint32_t o0 = pack2(o[0][0], o[0][1]), o1 = pack2(o[1][0], o[1][1]);
      st_async32(oa1, o0, bO + r1); st_async32(oa2, o0, bO + r2);
      st_async32(oa1 + 128, o1, bO + r1); st_async32(oa2 + 128, o1, bO + r2);
      sts32(l4 + CH_O + 1024, o0); sts32(l4 + CH_O + 1152, o1);
      bar_arrive(2, 256);
      pin();
      TM(6);
      mma16h(l, p3, p4, ones, ones);
      float inv;
      asm("rcp.approx.ftz.f32 %0, %1;" : "=f"(inv) : "f"(l[0]));
      sts32((l8 & ~0xffu) + (lane & 28) + CH_VP, __float_as_uint(inv));
      __syncwarp();
      if (elect()) mbar_arrive(bO);
      {
        float z[2][4] = {}, y[2][4] = {};
        mma16(z[0], wd[0], wd[1], wd[2], wd[3], o0, o1);
        if (j == 0) {
#pragma unroll
          for (int u = 0; u < 3; u++) if (!CH_WE) ldsm4t(&we[4 * u], (wo ^ 32) + u * 28672);
          mma16(y[0], we[0], we[1], we[2], we[3], o0, o1);
        }
        const float2 iv = lds64f((l8 & ~0xe0u) + CH_VP);
        uint8_t* dst = pool(pdst[0]);
        const uint32_t mask = ((l16 ^ tag) & 48) == 0;
        const uint32_t oa = qa + ((tag & 0xfffe) + CH_O - CH_QK + t4 * 256 - (t4 == 3 ? 1024 : 0));
        const uint32_t za = l16 + ((tag & 0xfffe) + (t4 >> 1) * 512 + (t4 & 1) * 8);
        pin();
        mbar_wait(bO, s & 1);
        uint32_t a[4];
        ldsm4(a, oa);
        mma16(z[0], wd[4], wd[5], wd[6], wd[7], a[0], a[1]);
        mma16(z[1], wd[8], wd[9], wd[10], wd[11], a[2], a[3]);
        if (j == 0) {
          mma16(y[0], we[4], we[5], we[6], we[7], a[0], a[1]);
          mma16(y[1], we[8], we[9], we[10], we[11], a[2], a[3]);
          sts128f(lw + CH_VT + 512, y[0][0] + y[1][0], y[0][1] + y[1][1], y[0][2] + y[1][2], y[0][3] + y[1][3]);
        }
        sts128f(lw + CH_VT, z[0][0] + z[1][0], z[0][1] + z[1][1], z[0][2] + z[1][2], z[0][3] + z[1][3]);
        bar_sync(3, 128);
        if (j == 0 || t4 < 2) {
          float2 q[4];
#pragma unroll
          for (int i = 0; i < 4; i++) q[i] = lds64f(za + CH_VT + i * 1024);
          stg_strong32(dst, pack_tag(((q[0].x + q[1].x) + (q[2].x + q[3].x)) * iv.x, ((q[0].y + q[1].y) + (q[2].y + q[3].y)) * iv.y, tag, mask));
        }
      }
      TM(2);
      if (!NOX) mbar_wait_hot(bXA, (s + 1) & 1);
      if (CH_KP == 2) bulk_wait_read<0>();
      float dk[16], dw[16];
      bar_sync(5, 256);
      wg_fence();
      pass(dk, ak, Int<0>(), Int<20>());
      pass(dw, av, Int<0>(), Int<20>());
      TM(5);
      pin();
      if (CH_EX == 0) publish_v(s, v, vm);
      if (elect()) {
        mbar_expect(bG + t4 * 8, 2560);
        if (t4 == 1 && s + 2 < NSEG) { mbar_expect(bX, 1536); mbar_expect(bO, 2048); }
      }
      if (CH_KD == 0) { wg_wait<1>(); dump(dk, lw + CH_KT); }
      wg_wait<0>();
      if (CH_KD == 1) dump(dk, lw + CH_KT);
      TM(7);
      dump(dw, lw + CH_VT);
      bar_arrive(9, 256);
      pin();
#pragma unroll
      for (int k = 0; k < CH_RB; k++) ldsm4t(&tw[4 * k], wq + k * 2048);
      if (t4 < 2) {
        if (CH_EX == 2) { publish_v(s, v, vm); pin(); }
#pragma unroll
        for (int k = CH_RB; k < CH_RC; k++) ldsm4t(&tw[4 * k], wq + k * 2048);
        const int q = t4 ? 3 : j, o = t4 ? j * 896 : 0;
        const uint8_t* src = p.pool + ((80 + st * 4 + q) * 8192 + (pages >> (st * 4 + q) & 1) * 4096 + o);
        asm volatile("bar.sync 8, 256;" ::: "memory");
        const uint32_t t1 = clk32() + CH_D2;
        if (CH_EX == 1) publish_v(s, v, vm);
        auto fetch = [&](auto n) {
          mbar_wait(bH, s & 1);
          until(t1);
          TR(4, clk32());
          if (elect())
            asm volatile("cp.async.bulk.shared::cluster.global.mbarrier::complete_tx::bytes.multicast::cluster [%0], [%1], %2, [%3], 7;"
                         :: "r"(sb + CH_M + q * 2560 + o), "l"(src), "n"(n.value), "r"(bG + q * 8) : "memory");
        };
        if (!t4) fetch(Int<2560>()); else if (j == 2) fetch(Int<768>()); else fetch(Int<896>());
      } else {
        asm volatile("bar.sync 8, 256; " ::: "memory");
        if (elect()) asm volatile("mbarrier.arrive.relaxed.cluster.shared::cluster.b64 _, [%0];" :: "r"(bH + (t4 == 2 ? r1 : r2)) : "memory");
        pin();
        if (CH_EX) publish_v(s, v, vm);
#pragma unroll
        for (int k = CH_RB; k < CH_RC; k++) ldsm4t(&tw[4 * k], wq + k * 2048);
      }
      TM(9);
      pin();
#pragma unroll
      for (int k = CH_RC; k < CH_TW; k++) ldsm4t(&tw[4 * k], wq + k * 2048);
      if (CH_KP == 2 && t4 == CH_KW) { bar_sync(7, 160); publish_k(s + 1); }
      TM(10);
    }
    if (++st == 3) st = 0;
    tag ^= 0x10001;
  }
}

__global__ void __launch_bounds__(256, 1) chain_kernel(const __grid_constant__ ChainParams p) {
  extern __shared__ __align__(1024) uint8_t smem_raw[];
  const uint32_t sb = s2u(smem_raw);
  const int tid = threadIdx.x, warp = __shfl_sync(~0u, tid >> 5, 0), lane = tid & 31;
  const int cta = blockIdx.x, h = cta / 3, j = cta - 3 * h, colbase = cta * 64;
  const uint32_t bWo = sb + CH_BAR, bWq = bWo + 8, bXA = bWo + 24, bWk = bWo + 80, bWv = bWo + 88;
  uint32_t smid; asm("mov.u32 %0, %%smid;" : "=r"(smid));
  PRO(0);
  if (sb != mapa(CH_BASE, j)) __trap();
  uint32_t entry = 0;
  auto place = [&]() {
    const int i = tid - 128;
    if (i >= 0 && i <= NSLOT) {
      const uint32_t side = ldg_strong32(g_smpart + (smid & 255));
      if (i < NSLOT) {
        entry = i * 8192 + (ldg_strong32(g_orient + i) == (i < 80 ? i & 1 : side) ? 0 : 4096);
      } else {
        entry = 2 * (atomicAdd(g_bo + p.layer * 128 + 1, 1 << 8 * side) >> 8 * side & 255) + side;
      }
    }
    __syncwarp();
  };
  if (p.layer) place();
  if (warp == 0 && elect()) {
#pragma unroll 1
    for (int i = 0; i < 17; i++) mbar_init(bWo + 8 * i, i == 2 || i == 5 ? 5 : i == 3 || i == 4 ? 4 : i == 12 ? 2 : 1);
    asm volatile("fence.mbarrier_init.release.cluster;" ::: "memory");
    mbar_expect(bWk, 81920);
    tma_load3<(WEF & 1) != 0>(sb + CH_WQ, &p.wk, colbase, 0, bWk);
    mbar_expect(bWv, 81920);
    tma_load3<(WEF & 1) != 0>(sb + CH_WO, &p.wv, colbase, 0, bWv);
    mbar_expect(bWo + 16, 1536);
    mbar_expect(bWo + 40, 2048);
    mbar_expect(bWo, 86016); mbar_expect(bWq, 81920);
#pragma unroll 1
    for (int i = 0; i < 8; i++) mbar_expect(bXA + 8 * (i & 1), 5120);
  }
  if (warp == 1) {
    const uint32_t id = (lane >> 3) == (lane & 3) ? ((lane & 4) ? 0x3f800000u : 0x00003f80u) : 0u;
    sts128(sb + CH_ID + lane * 16, make_uint4(id, 0, 0, id));
  }
  __syncthreads();
  asm volatile("barrier.cluster.arrive.relaxed.aligned;" ::: "memory");
  uint32_t ak[80], av[80];
  const uint32_t wq = opaque(sb + CH_WQ + ((warp >> 2) * 320 + (lane & 7) + (lane >> 4) * 8) * 128 + (((2 * (warp & 3) + ((lane >> 3) & 1)) ^ (lane & 7)) << 4));
  pdl_wait();
  if (tid == 32) stg_strong32(g_smuse + (smid & 255), p.layer + 1);
  pdl_launch();
  PRO(1);
  if (warp == 0 && elect()) {
    bulk_load(sb + CH_X + 20480, p.xc + 5120, 20480, bXA);
    bulk_load(sb + CH_X, p.xc, 20480, bXA + 8);
  }
  if (!p.layer) place();
  __syncwarp();
  PRO(2);
  mbar_wait(bWk, 0);
  PRO(3);
#pragma unroll
  for (int k = 0; k < 20; k++) ldsm4t(&ak[4 * k], wq + k * 2048);
  bar_sync(6, 256);
  if (warp == 0 && elect()) tma_load3<(WEF & 2) != 0>(sb + CH_WQ, &p.wq, colbase, 0, bWq);
  __syncwarp();
  PRO(4);
  mbar_wait(bWv, 0);
  PRO(5);
#pragma unroll
  for (int k = 0; k < 20; k++) ldsm4t(&av[4 * k], wq + CH_WO + k * 2048);
  bar_sync(6, 256);
  PRO(6);
  if (warp >= 5 && elect()) tma_load3<(WEF & 2) != 0>(sb + CH_WO + (warp - 5) * 28672, &p.wo, j == 0 ? 0 : 32 + j * 192, h * 192 + (j + 8 - warp) % 3 * 64, bWo);
  if (tid == 128 + NSLOT && entry >= 80) {
    uint32_t c;
    int n = 0;
    do { c = ldg_strong32(g_bo + p.layer * 128 + 1); spin_guard(n); } while ((c & 255) + (c >> 8) < 96);
    const uint32_t other = (c >> 8 * (~entry & 1) & 255) + (entry >> 1) - 40;
    entry = other < 40 ? 2 * other + (~entry & 1) : entry % 80;
  }
  if (tid >= 128 && tid <= 128 + NSLOT) sts32(sb + CH_O + (tid - 128) * 4, entry);
  PRO(7);
  __syncthreads();
  if (__shfl_sync(~0u, tid >> 7, 0) == 0) chain_body<0>(p, wq, ak, av); else chain_body<1>(p, wq, ak, av);
}

struct PostParams { CUtensorMap wq, wo, wb, wo2, wb2; int gap, share, layer, look, gap2, pol; };
constexpr int PS = 8, PB = 28672;
constexpr int OP_SMEM = PS * PB + 512 + 2048;
enum { IT_ATT = 0, IT_OP = 1, IT_FIN = 2, IT_BQ = 3, IT_Q = 4 };

__device__ __forceinline__ uint32_t item_count(int type, int b) {
  return type == IT_ATT ? 32 : type == IT_OP ? op_split(b) * (b < OP_160 ? 2 : 4) : type == IT_FIN ? 16 : b < BQ_160 ? 6 : b < BQ_80 ? 12 : 24; }
__device__ __forceinline__ uint32_t item_need(int type, int b) { return type == IT_ATT ? 96 : item_count(type - 1, b); }

struct Ring {
  uint32_t sb, bars; int st; uint32_t ph;
  __device__ __forceinline__ uint32_t wait() const { mbar_wait(bars + 8 * st, ph); return sb + st * PB; }
  __device__ __forceinline__ void next() { if (++st == PS) { st = 0; ph ^= 1; } }
  __device__ __forceinline__ void release(int s) const { if ((threadIdx.x & 31) == 0) mbar_arrive(bars + 8 * (PS + s)); }
  __device__ __forceinline__ void pop() { __syncwarp(); release(st); next(); }
};

template <int N>
__device__ __forceinline__ void gemm_item(Ring& r, float* d, int nst, uint32_t go, int go_at) {
  int prev = 0;
#pragma unroll 1
  for (int kb = 0; kb < nst; kb++) {
    const uint32_t base = r.wait();
    const uint64_t da = mkdesc(base + (threadIdx.x >> 7) * 4096, 128, 512, 0), db = mkdesc(base + 8192, 4096, 1024, 1);
    wg_fence();
#pragma unroll
    for (int kk = 0; kk < 2; kk++) {
      if (N == 80) wg_ss80_01(d, da + kk * 16, db + kk * 128, (kb | kk) != 0);
      if (N == 160) wg_ss160_01(d, da + kk * 16, db + kk * 128, (kb | kk) != 0);
      if (N >= 192) wg_ss192_01(d, da + kk * 16, db + kk * 128, (kb | kk) != 0);
      if (N == 320) wg_ss128_01(d + 96, da + kk * 16, db + kk * 128 + 3 * 256, (kb | kk) != 0);
    }
    wg_commit();
    if (kb == go_at && threadIdx.x == 0) mbar_arrive(go);
    if (kb > 0) { wg_wait<1>(); r.release(prev); }
    prev = r.st;
    r.next();
  }
  wg_wait<0>();
  reg_fence<N / 2>(d);
  r.release(prev);
}

template <int HALF>
__device__ __forceinline__ void attn_a_warp(Ring& r, const uint32_t (&q)[48], int b, int h) {
  constexpr int NT = HALF ? 5 : 3, NF = 8 * NT;
  const int lane = threadIdx.x & 31, g = lane >> 2, c = lane & 3, seg = (threadIdx.x >> 5) & 3;
  uint32_t f[6][NF];
  int slot[6];
  auto fetch = [&](int u) {
    const uint32_t kv = r.wait() + seg * KV_BYTES;
    slot[u] = r.st;
    r.next();
#pragma unroll
    for (int w = 0; w < 4; w++) {
      uint32_t* d = &f[u][2 * NT * w];
#pragma unroll
      for (int t = 0; t <= HALF; t++) {
        if (u < 3) {
          ldsm4(d + 4 * t, kv + w * 1024 + t * 512 + (lane & 8) * 32 + (lane & 16) * 8 + (lane & 7) * 16);
        } else {
          const uint4 v = lds128(kv + w * 1024 + t * 512 + lane * 16);
          d[4 * t] = v.x; d[4 * t + 1] = v.y; d[4 * t + 2] = v.z; d[4 * t + 3] = v.w;
        }
      }
      const uint2 m = lds64(kv + KV_M + w * 256 + lane * 8);
      d[2 * NT - 2] = m.x; d[2 * NT - 1] = m.y;
    }
    pdl_launch();
  };
  float s[NT][4] = {};
  fetch(0);
#pragma unroll
  for (int u = 0; u < 3; u++) {
    fetch(u + 1);
#pragma unroll
    for (int kk = 0; kk < 4; kk++) {
      const uint32_t* a = &q[16 * u + 4 * kk];
#pragma unroll
      for (int n = 0; n < NT; n++) mma16(s[(n + 1) % NT], a[0], a[1], a[2], a[3], f[u][2 * NT * kk + 2 * n], f[u][2 * NT * kk + 2 * n + 1]);
    }
    r.release(slot[u]);
    pdl_launch();
  }
  fetch(4);
  const float k2 = 0.07216878364870322f * 1.44269504089f, NEG = -INFINITY;
  if (2 * c > g) { s[NT - 2][0] = NEG; s[NT - 1][2] = NEG; }
  if (2 * c + 1 > g) { s[NT - 2][1] = NEG; s[NT - 1][3] = NEG; }
  s[NT - 1][0] = s[NT - 1][1] = NEG;
  uint32_t pp[NT][2]; float inv[2];
#pragma unroll
  for (int hh = 0; hh < 2; hh++) {
    float m = NEG, l = 0.f;
#pragma unroll
    for (int n = 0; n < NT; n++) m = fmaxf(m, fmaxf(s[n][2 * hh], s[n][2 * hh + 1]));
    m = fmaxf(m, __shfl_xor_sync(~0u, m, 1)); m = fmaxf(m, __shfl_xor_sync(~0u, m, 2));
#pragma unroll
    for (int n = 0; n < NT; n++) { const float x = ex2((s[n][2 * hh] - m) * k2), y = ex2((s[n][2 * hh + 1] - m) * k2); l += x + y; pp[n][hh] = pack2(x, y); }
    l += __shfl_xor_sync(~0u, l, 1); l += __shfl_xor_sync(~0u, l, 2);
    asm("rcp.approx.ftz.f32 %0, %1;" : "=f"(inv[hh]) : "f"(l));
  }
  uint32_t* dst = g_o + ((b * 192 + h * 6) * 16 + seg * 4 + HALF * 2) * 128 + lane;
#pragma unroll
  for (int u = 3; u < 6; u++) {
    float o[8][4] = {};
#pragma unroll
    for (int n = 0; n < 8; n++) mma8(o[n], pp[0][0], pp[0][1], f[u][2 * NT * (n >> 1) + 2 * NT - 2 + (n & 1)]);
#pragma unroll
    for (int t = 0; t <= HALF; t++)
#pragma unroll
      for (int n = 0; n < 8; n++) {
        const uint32_t* v = &f[u][2 * NT * (n >> 1) + 4 * t + 2 * (n & 1)];
        mma16(o[n], pp[1 + 2 * t][0], pp[1 + 2 * t][1], pp[2 + 2 * t][0], pp[2 + 2 * t][1], v[0], v[1]);
      }
    r.release(slot[u]);
    if (u == 3) fetch(5);
#pragma unroll
    for (int n = 0; n < 8; n++) {
      dst[(u - 3) * 4096 + (n >> 2) * 2048 + (n & 3) * 32] = pack2(o[n][0] * inv[0], o[n][1] * inv[0]);
      dst[(u - 3) * 4096 + (n >> 2) * 2048 + (n & 3) * 32 + 128] = pack2(o[n][2] * inv[1], o[n][3] * inv[1]);
    }
  }
}

__device__ __forceinline__ void fin_item(Ring& r, uint32_t scratch, int b, int idx) {
  const int warp = threadIdx.x >> 5, lane = threadIdx.x & 31;
  float4 v[1][5];
  {
    const uint32_t base = r.wait();
#pragma unroll
    for (int i = 0; i < 5; i++) v[0][i] = unpack4(lds64(base + ((warp * 5 + i) * 32 + lane) * 8));
    r.pop();
  }
#pragma unroll 1
  for (int k = 0; k < op_split(b); k += 2) {
    const uint32_t base = r.wait();
#pragma unroll
    for (int i = 0; i < 10; i++) {
      const uint2 q = lds64(base + ((i / 5 * 40 + warp * 5 + i % 5) * 32 + lane) * 8);
      float4& t = v[0][i % 5];
      t.x += bf_lo(q.x); t.y += bf_hi(q.x); t.z += bf_lo(q.y); t.w += bf_hi(q.y);
    }
    r.pop();
  }
#pragma unroll
  for (int i = 0; i < 5; i++) g_x[((b * 16 + idx) * 40 + warp * 5 + i) * 32 + lane] = pack4(v[0][i]);
  float mean[1], rs[1];
  ln_stats<1>(v, scratch, mean, rs);
#pragma unroll
  for (int i = 0; i < 5; i++) {
    const int u = warp * 5 + i;
    uint32_t* xn = g_xn + ((b * 20 + (u >> 1)) * 16 + idx) * 128 + (u & 1) * 64 + lane;
    xn[0] = pack2((v[0][i].x - mean[0]) * rs[0], (v[0][i].y - mean[0]) * rs[0]);
    xn[32] = pack2((v[0][i].z - mean[0]) * rs[0], (v[0][i].w - mean[0]) * rs[0]);
  }
}

__global__ void __launch_bounds__(384, 1) post_kernel(const __grid_constant__ PostParams p) {
  extern __shared__ __align__(1024) uint8_t smem_raw[];
  const uint32_t sb = s2u(smem_raw), bars = sb + PS * PB;
  const uint32_t bIF = bars + 128, bIE = bars + 160, done = bars + 192, bGo = bars + 224, slots = bars + 240, scratch = bars + 512;
  const int warp = __shfl_sync(~0u, threadIdx.x >> 5, 0), lane = threadIdx.x & 31;
  TRACE(0);
  pdl_launch();
  if (sb & 1023) __trap();
  if (threadIdx.x < 29) mbar_init(bars + 8 * threadIdx.x, threadIdx.x < 8 ? 1 : threadIdx.x < 16 ? 8 : threadIdx.x < 20 ? 1 : threadIdx.x < 24 ? 2 : threadIdx.x < 28 ? 8 : 1);
  if (threadIdx.x == 32) sts32(slots + 16, p.gap);
  fence_async();
  __syncthreads();
  if (warp >= 8) {
    asm volatile("setmaxnreg.dec.sync.aligned.u32 56;");
    if (warp == 9) {
      const int b = lane & 15;
      bool queries = QA_END < 16 && blockIdx.x < 36;
      for (int n = 0;; n++) {
        if (n > 0) mbar_wait(bGo, (n - 1) & 1);
        mbar_wait(bIE + 8 * (n & 3), ((n >> 2) & 1) ^ 1);
        int code = -1, spin = 0, ticket = 0;
        if (queries) {
          if (lane == 0) ticket = n == 0 ? blockIdx.x : 36 + atomicAdd(g_sync + SY_QC, 1);
          ticket = __shfl_sync(~0u, ticket, 0);
          queries = ticket < (16 - QA_END) * 32;
          if (queries) code = IT_Q << 16 | (QA_END + ticket % (16 - QA_END)) << 8 | ticket / (16 - QA_END);
        }
        if (!queries && lane == 0) asm volatile("atom.relaxed.gpu.global.add.u32 %0, [%1], 1;" : "=r"(ticket) : "l"(g_sync + SY_T) : "memory");
        while (!queries) {
          const uint4 hd = ldg_strong128(g_sync + b * 8), pr = ldg_strong128(g_sync + b * 8 + 4);
          const uint32_t hv[4] = {hd.x, hd.y, hd.z, hd.w}, pv[4] = {pr.x, pr.y, pr.z, pr.w};
          const uint32_t chain_done = __ballot_sync(~0u, (pr.x & 0xffff) >= 96) & 0xffff;
          int left[4], avail[4], rdy = 0, claimed = 0, upstream = 0;
#pragma unroll
          for (int t = 0; t < 4; t++) {
            const int cnt = lane < 16 ? item_count(t, b) : 0;
            left[t] = max(cnt - (int)hv[t], 0);
            claimed += cnt - left[t];
            const bool ready = (pv[t] & 0xffff) >= item_need(t, b);
            rdy |= ready << t;
            bool ok = ready || (t == IT_ATT ? pr.x >= 0x10000 : !upstream || (t == IT_OP && (chain_done >> 15 & 1)));
            if (t == IT_BQ && (chain_done >> BQ_HOLD & 1) && !(chain_done >> 15)) ok = false;
            avail[t] = ok ? left[t] : 0;
            upstream |= __any_sync(~0u, left[t] > 0);
          }
          if (!upstream) break;
          int rank = max(__shfl_sync(~0u, ticket, 0) - __reduce_add_sync(~0u, claimed), 0), type = -1, mine = 0;
#pragma unroll
          for (int c = 0; c < 8; c++) {
            const int t = c == PR_FIN || c == 5 ? IT_FIN : c == PR_ATT || c == 7 ? IT_ATT : c == PR_OP || c == 4 ? IT_OP : IT_BQ;
            int a = c == PR_ATT || ((rdy >> t & 1) == (c < 4)) ? avail[t] : 0;
            if (t == IT_OP && OP_EARLY) a = c == PR_OP ? avail[t] : 0;
            if (c == 7) a = b < QA_END && !(rdy & 1) && ((chain_done << 1 | 1) >> b & 1) ? left[t] : 0;
            const int tot = __reduce_add_sync(~0u, a);
            if (type < 0) { if (rank < tot) { type = t; mine = a; } else rank -= tot; }
          }
          if (type >= 0) {
#pragma unroll
            for (int o = 1; o < 16; o <<= 1) { const int y = __shfl_up_sync(~0u, mine, o); if (lane >= o) mine += y; }
            const int blk = __ffs(__ballot_sync(~0u, mine > rank)) - 1;
            const int early = !(__shfl_sync(~0u, rdy, blk) >> type & 1);
            uint32_t idx = 0;
            if (lane == 0) asm volatile("atom.relaxed.gpu.global.add.u32 %0, [%1], 1;" : "=r"(idx) : "l"(g_sync + blk * 8 + type) : "memory");
            ld_acquire(g_sync + blk * 8 + 4 + type);
            idx = __shfl_sync(~0u, idx, 0);
            if (idx < item_count(type, blk)) { code = (chain_done >> 15 & 1) << 22 | (chain_done >> p.look & 1) << 21 | early << 20 | type << 16 | blk << 8 | idx; break; }
          } else {
            __nanosleep(50);
          }
          spin_guard(spin);
        }
        if (lane == 0) {
          fence_async_global();
          sts32(slots + 4 * (n & 3), code);
          mbar_arrive(bIF + 8 * (n & 3));
        }
        __syncwarp();
        if (code < 0) break;
      }
    } else if (warp == 8) {
      if (elect()) {
        uint32_t dst = sb, bar = bars, ph = 1, next = clk32(), gap = 0;
        auto acquire = [&](uint32_t kb) {
          mbar_wait(bar + 8 * PS, ph);
          mbar_expect(bar, kb * 1024);
          if (gap) {
            uint32_t now;
            do now = clk32(); while ((int)(now - next) < 0);
            next = ((int)(now - next) > 100 ? now - 100 : next) + kb * gap;
          }
        };
        auto advance = [&]() { dst += PB; bar += 8; if (dst == bars) { dst = sb; bar = bars; ph ^= 1; } };
        auto depend = [&](const uint32_t* c, uint32_t need) { wait_count(c, need); fence_async_global(); };
#pragma unroll 1
        for (int n = 0;; n++) {
          mbar_wait(bIF + 8 * (n & 3), (n >> 2) & 1);
          const int code = (int)lds32(slots + 4 * (n & 3));
          if (code < 0) break;
          const int type = (code >> 16) & 15, b = (code >> 8) & 255, idx = code & 255;
          const bool early = code >> 20 & 1, go = !(code >> 21 & 1);
          mbar_arrive(bIE + 8 * (n & 3));
          gap = !(code >> 22 & 1) ? lds32(slots + 16) : type == IT_ATT || type == IT_FIN ? 0 : p.gap2;
          const uint32_t* progress = g_sync + b * 8 + 4 + type;
          if (type == IT_ATT && b >= QA_END) {
            depend(g_sync + SY_Q, (16 - QA_END) * 32);
#pragma unroll 1
            for (int u = 0; u < 2; u++) { acquire(24); bulk_load_last(dst, g_q + (((b - QA_END) * 32 + idx) * 2 + u) * 1536, 24576, bar); advance(); }
          } else if (type == IT_FIN) {
            acquire(10);
            bulk_load(dst, g_x + (b * 16 + idx) * 1280, 10240, bar);
            advance();
            if (early) depend(progress, item_need(type, b));
            if (go) mbar_arrive(bGo);
            const uint2* src = g_part + (b * 16 + idx) * 16 * 1280;
#pragma unroll 1
            for (int i = 0; i < op_split(b); i += 2) { acquire(20); bulk_load_last(dst, src + i * 1280, 20480, bar); advance(); }
            if (!go && p.pol) mbar_arrive(bGo);
          } else {
            const bool op = type == IT_OP, bq = type == IT_BQ;
            const int width = op ? op_width(b) : bq ? bq_width(b) : 192, nb = (width + 63) >> 6, lt = width == 320 ? 1 : 2;
            const int nst = op ? 192 / op_split(b) : 20, kb0 = op ? (idx >> lt) * nst : 0;
            const int col = (op ? idx & ((1 << lt) - 1) : idx) * width;
            const bool whole = !(width & 63);
            const CUtensorMap* m = op ? (whole ? &p.wo : &p.wo2) : bq ? (whole ? &p.wb : &p.wb2) : &p.wq;
            const uint32_t* a = op ? g_o + (b * 192 + kb0) * 2048 : g_xn + b * 20 * 2048;
            int row = kb0 * 32, pre = early && (op || bq) ? min(nst, PRE_MAX) : 0;
            auto weights = [&]() {
              acquire(8 + nb * 4);
              if (whole) {
                tma_load3z(dst + 8192, m, row, col >> 6, bar);
              } else {
                tma_load(dst + 8192, m, col, row, bar); tma_load(dst + 12288, m, col + 64, row, bar);
                if (nb == 3) tma_load(dst + 16384, m, col + 128, row, bar);
              }
              row += 32;
            };
            if (pre) {
              uint32_t da = dst, ba = bar;
              const uint32_t g0 = gap;
              gap = max(gap, PRE_GAP);
#pragma unroll 1
              for (int kb = 0; kb < pre; kb++) { weights(); advance(); }
              gap = g0;
              depend(progress, item_need(type, b));
#pragma unroll 1
              for (int kb = 0; kb < pre; kb++) {
                bulk_load(da, a, 8192, ba);
                a += 2048; da += PB; ba += 8;
                if (da == bars) { da = sb; ba = bars; }
              }
            }
#pragma unroll 1
            for (int kb = pre; kb < nst; kb++) { weights(); if (op && OEF) bulk_load_last(dst, a, 8192, bar); else bulk_load(dst, a, 8192, bar); a += 2048; advance(); }
          }
          if (type == IT_ATT) {
            if (early) depend(progress, 96);
            if (go) mbar_arrive(bGo);
            const uint8_t* src = g_kv + (size_t)(idx * 6 * NSEG + b * 4) * KV_BYTES;
#pragma unroll 1
            for (int u = 0; u < 6; u++) {
              acquire(20);
              bulk_load_last(dst, src, 20480, bar);
              src += u == 2 ? -3 * KV_V : 2 * KV_V;
              advance();
            }
            if (!go && p.pol && ATT_LOOK) mbar_arrive(bGo);
            if (Q_PF && b + Q_PF >= QA_END && b + Q_PF < 16)
              asm volatile("cp.async.bulk.prefetch.L2.global [%0], 49152;" :: "l"(g_q + ((b + Q_PF - QA_END) * 32 + idx) * 3072) : "memory");
          }
        }
      }
    } else if (warp == 11) {
      uint32_t smid, nsm, used = 0;
      asm("mov.u32 %0, %%smid;" : "=r"(smid)); asm("mov.u32 %0, %%nsmid;" : "=r"(nsm));
      for (int n = 0; n < 64 && used < 96; n++) {
        uint32_t peers = 0;
        used = 0;
        for (uint32_t i = lane; i < min(nsm, 256u); i += 32) {
          const bool taken = ldg_strong32(g_smuse + i) == p.layer + 1;
          used += taken;
          peers += abs((int)(g_smclk[i] - g_smclk[smid & 255])) < 4000 && !taken;
        }
        used = __reduce_add_sync(~0u, used);
        sts32(slots + 16, max(p.gap, (int)min(__reduce_add_sync(~0u, peers), 18u) * p.share >> 3));
      }
    } else if (warp == 10 && lane == 0) {
      for (int n = 0;; n++) {
        mbar_wait(bIF + 8 * (n & 3), (n >> 2) & 1);
        const int code = (int)lds32(slots + 4 * (n & 3));
        if (code < 0) break;
        const int type = (code >> 16) & 15, b = (code >> 8) & 255;
        mbar_wait(done + 8 * (n & 3), (n >> 2) & 1);
        if (type != IT_BQ) red_release(type == IT_Q ? g_sync + SY_Q : g_sync + b * 8 + 5 + type, 1);
        mbar_arrive(bIE + 8 * (n & 3));
      }
    }
  } else {
    asm volatile("setmaxnreg.inc.sync.aligned.u32 224;");
    const int g = lane >> 2, c = lane & 3;
    Ring r = {sb, bars, 0, 0};
#pragma unroll 1
    for (int n = 0;; n++) {
      mbar_wait(bIF + 8 * (n & 3), (n >> 2) & 1);
      const int code = __shfl_sync(~0u, (int)lds32(slots + 4 * (n & 3)), 0);
      if (code < 0) { TRACE(2); break; }
      const int type = (code >> 16) & 15, b = (code >> 8) & 255, idx = code & 255;
      ITEM(code & 0xfffff, 0);
      if (type == IT_ATT || type == IT_Q) {
        uint32_t q[48];
        if (type == IT_Q || b < QA_END) {
          float d[96] = {};
          reg_fence<96>(d);
          gemm_item<192>(r, d, 20, bGo, type == IT_Q ? 12 : -1);
#pragma unroll
          for (int i = 0; i < 48; i++) q[i] = pack2(d[2 * i], d[2 * i + 1]);
        } else {
#pragma unroll
          for (int u = 0; u < 2; u++) {
            const uint32_t base = r.wait() + threadIdx.x * 16;
#pragma unroll
            for (int i = 0; i < 6; i++) {
              const uint4 v = lds128(base + i * 4096);
              q[24 * u + 4 * i] = v.x; q[24 * u + 4 * i + 1] = v.y; q[24 * u + 4 * i + 2] = v.z; q[24 * u + 4 * i + 3] = v.w;
            }
            r.pop();
          }
        }
        if (type == IT_Q) {
          uint4* dst = g_q + ((b - QA_END) * 32 + idx) * 3072 + threadIdx.x;
#pragma unroll
          for (int i = 0; i < 12; i++) dst[i * 256] = make_uint4(q[4 * i], q[4 * i + 1], q[4 * i + 2], q[4 * i + 3]);
        } else if (warp < 4) {
          attn_a_warp<0>(r, q, b, idx);
        } else {
          attn_a_warp<1>(r, q, b, idx);
        }
      } else if (type == IT_FIN) {
        fin_item(r, scratch, b, idx);
      } else {
        float d[160] = {};
        reg_fence<160>(d);
        const int width = type == IT_OP ? op_width(b) : bq_width(b), nst = type == IT_OP ? 192 / op_split(b) : 20;
        const int go_at = max(nst - (code >> 21 & 1 ? p.pol : 6), 0);
        if (width == 320) gemm_item<320>(r, d, nst, bGo, go_at);
        else if (width == 160 || BQ_80 == 16) gemm_item<160>(r, d, nst, bGo, go_at);
        else gemm_item<80>(r, d, nst, bGo, go_at);
        reg_fence<160>(d);
        if (type == IT_OP) {
          const int tiles = DM / width;
          uint2* dst = g_part + (((b * 16 + warp * 2) * 16 + idx / tiles) * 40 + idx % tiles * (width / 16)) * 32 + lane;
#pragma unroll
          for (int u = 0; u < 20; u++) {
            if (u % 5 == 0 && u * 16 >= width) break;
            dst[u * 32] = make_uint2(pack2(d[8 * u], d[8 * u + 1]), pack2(d[8 * u + 4], d[8 * u + 5]));
            dst[(640 + u) * 32] = make_uint2(pack2(d[8 * u + 2], d[8 * u + 3]), pack2(d[8 * u + 6], d[8 * u + 7]));
          }
        } else {
          const int row = b * 128 + warp * 16 + g;
          const int h0 = idx * (width / 20);
          const float sc = h0 < 32 ? 0.22360679775f * 1.44269504089f : 1.f;
          const bool lo = c < 2;
          uint32_t* da = g_bqkv + (h0 * 256 + (row >> 3)) * 96 + lane;
          uint32_t* db = da + 256 * 96 + (lo ? 2 : -2);
          uint32_t pad[2];
#pragma unroll
          for (int rr = 0; rr < 2; rr++) pad[rr] = c & 1 || h0 < 32 ? 0u : h0 >= 64 ? 0x00003f80u : poly_group((row >> 3) + rr) ? 0x3f803f80u : 0u;
#pragma unroll
          for (int q = 0; q < 8; q++) {
            if (!(q & 1) && q * 40 >= width) break;
#pragma unroll
            for (int rr = 0; rr < 2; rr++) {
              uint32_t w[5];
#pragma unroll
              for (int i = 0; i < 5; i++) w[i] = pack2(d[20 * q + 4 * i + 2 * rr] * sc, d[20 * q + 4 * i + 2 * rr + 1] * sc);
              const int o = q * 2 * 256 * 96 + rr * 96;
              da[o] = w[0]; da[o + 32] = w[1]; da[o + 64] = lo ? w[2] : pad[rr];
              db[o] = lo ? w[3] : w[2]; db[o + 32] = lo ? w[4] : w[3]; db[o + 64] = lo ? pad[rr] : w[4];
            }
          }
        }
      }
      __syncwarp();
      if (lane == 0) mbar_arrive(done + 8 * (n & 3));
      if ((code >> 21 & 1) && (p.pol == 0 || (type == IT_ATT && !ATT_LOOK)) && threadIdx.x == 128) mbar_arrive(bGo);
      ITEM(code & 0xfffff, 1);
    }
  }
}

constexpr int AB_SMEM = 1024 + 98304 + 51200 + 4 * 16384 + 256 + 10240;
#define AB_LW 1
#define AB_U 8
#define AB_WG 4
constexpr int AB_T = AB_WG * 128, AB_PASS = 8 / AB_WG;
__device__ __forceinline__ uint32_t fma2(uint32_t a, uint32_t b, uint32_t c) { uint32_t r; asm("fma.rn.bf16x2 %0, %1, %2, %3;" : "=r"(r) : "r"(a), "r"(b), "r"(c)); return r; }
__device__ __forceinline__ uint32_t ex2_pair(float a, float b, uint32_t one, uint32_t c0) {
  const uint32_t e = __byte_perm(__float_as_uint(a), __float_as_uint(b), 0x6521);
  uint32_t x, r;
  asm("lop3.b32 %0, %1, 0x007f007f, %2, 0xEA;" : "=r"(x) : "r"(e), "r"(one));
  const uint32_t m = fma2(fma2(c0, x, 0x3c0d3c0du), x, 0x3f2b3f2bu);
  asm("lop3.b32 %0, %1, %2, 0x7f807f80, 0xE4;" : "=r"(r) : "r"(e), "r"(m));
  return r;
}
__device__ __forceinline__ float sq2(uint32_t w) { const float a = bf_lo(w), b = bf_hi(w); return fmaf(a, a, b * b); }

__device__ __forceinline__ void attn_b_store(const float* o, int h, int row0, int lane) {
  const int g = lane >> 2, c = lane & 3;
  const float i0 = __frcp_rn(__shfl_sync(~0u, o[8], (lane & ~3) | 2)), i1 = __frcp_rn(__shfl_sync(~0u, o[10], (lane & ~3) | 2));
#pragma unroll
  for (int jj = 0; jj < 3; jj++) {
    if (jj < 2 || c < 2) {
      const int col = h * 20 + 8 * jj + 2 * c;
      uint32_t* dst = g_of + (((row0 >> 7) * 10 + (col >> 6)) * 16 + (row0 >> 3 & 15)) * 256 + (col >> 3 & 7) * 32 + g * 4 + (col >> 1 & 3);
      dst[0] = pack2(o[4 * jj] * i0, o[4 * jj + 1] * i0);
      dst[256] = pack2(o[4 * jj + 2] * i1, o[4 * jj + 3] * i1);
    }
  }
}

struct AbParams { Weights next; uint32_t* done; uint32_t* out; };
__global__ void __launch_bounds__(AB_T + 32, 1) attn_b_kernel(const __grid_constant__ AbParams p) {
  extern __shared__ uint8_t smem_raw[];
  const uint32_t sb = (s2u(smem_raw) + 1023) & ~1023u, sK = sb, sV = sb + 98304, bars = sV + 51200 + 4 * 16384;
  const uint32_t bF = bars + 64, bW = bars + 72, bA = bars + 80, bE = bars + 128, smax = bars + 176;
  auto ring = [&](int i) { return i < 2 ? sK + 51200 + i * 16384 : sV + 51200 + (i - 2) * 16384; };
  const int warp = __shfl_sync(~0u, threadIdx.x >> 5, 0), lane = threadIdx.x & 31;
  const int h = blockIdx.x >> 2, quarter = blockIdx.x & 3;
  TRACE(0);
  pdl_launch();
  if (threadIdx.x < 22) mbar_init(bars + 8 * threadIdx.x, threadIdx.x == 8 ? AB_T / 32 : threadIdx.x >= 16 ? 8 : 1);
  if (threadIdx.x == 32) sts64(smax, 0, 0);
  fence_async();
  __syncthreads();
  pdl_wait();
  const int blk = quarter * 4 + (h >> 3), cg = h & 7;
  auto unsafe = [&]() { const float2 m = lds64f(smax); return !(m.x * m.y <= 10000.f); };
  if (warp == AB_T / 32) {
    auto load_w = [&]() {
      mbar_expect(bW, 102400);
      for (int i = 0; i < 4; i++) bulk_load((i < 2 ? sK : sV) + (i & 1) * 25600, g_wb + cg * 6400 + i * 1600, 25600, bW);
    };
    if (elect()) {
      const uint32_t* gk = g_bqkv + (32 + h) * 256 * 96;
#pragma unroll 1
      for (int i = 0; i < 8; i++) {
        if (i >= AB_LW) mbar_wait(bars + 8 * (i - AB_LW), 0);
        mbar_expect(bars + 8 * i, 24576);
        bulk_load_last(sK + i * 12288, gk + i * 3072, 12288, bars + 8 * i);
        bulk_load_last(sV + i * 12288, gk + 32 * 256 * 96 + i * 3072, 12288, bars + 8 * i);
      }
    }
    __syncwarp();
    if (blockIdx.x < NSLOT) for (int i = lane; i < 512; i += 32) reinterpret_cast<uint4*>(pool_at(blockIdx.x * 8192))[i] = make_uint4(0, 0, 0, 0);
    if (blockIdx.x == 127) for (int i = lane; i < SY_N; i += 32) g_sync[i] = 0;
    if (p.next.w[0] && lane == 0) {
      for (int i = 0; i < AB_PF; i++) { const uint32_t t0 = clk32(); while (clk32() - t0 < (i ? AB_PFD : AB_PF0)) __nanosleep(200); prefetch_weights(p.next, i); }
    }
    __syncwarp();
    mbar_wait(bF, 0);
    const bool redo = unsafe();
    if (!redo && lane == 0) load_w();
    if (lane < 16) asm volatile("cp.async.bulk.prefetch.L2.global [%0], 1280;" :: "l"(g_x + ((blk * 16 + lane) * 40 + cg * 5) * 32) : "memory");
    __syncwarp();
    bar_sync(1, AB_T + 32);
    if (lane == 0) {
      ABT(!!p.out, 1);
      red_release(p.done + quarter * 32, 1);
      ABT(!!p.out, 2);
      if (redo) load_w();
      wait_count(p.done + quarter * 32, 32);
      fence_async_global();
      ABT(!!p.out, 3);
      for (int kb = 0; kb < 10; kb++) {
        const int i = kb < 6 ? kb : kb - 6;
        if (kb >= 6) mbar_wait(bE + 8 * i, 0);
        mbar_expect(bA + 8 * i, 16384);
        bulk_load(ring(i), g_of + (blk * 10 + kb) * 4096, 16384, bA + 8 * i);
      }
    }
    return;
  }
  float qmax = 0.f;
  const uint32_t one = opaque(0x3f803f80u + (threadIdx.x >> 10)), c0 = opaque(0x3ea83ea8u + (threadIdx.x >> 10));
#pragma unroll 1
  for (int pass = 0; pass < AB_PASS; pass++) {
    const int row0 = quarter * 512 + ((warp >> 2) * AB_PASS + pass) * 64 + (warp & 3) * 16;
    const uint32_t* gq = g_bqkv + (h * 256 + (row0 >> 3)) * 96 + lane;
    const uint32_t q0 = gq[0], q1 = gq[96], q2 = gq[32], q3 = gq[128];
    uint32_t q4 = gq[64], q5 = gq[160];
    const uint32_t z0 = gq[64 + 3 - (lane & 3)], z1 = gq[160 + 3 - (lane & 3)];
    {
      float n0 = sq2(q0) + sq2(q2) + sq2(q4), n1 = sq2(q1) + sq2(q3) + sq2(q5);
      n0 += __shfl_xor_sync(~0u, n0, 1); n1 += __shfl_xor_sync(~0u, n1, 1);
      n0 += __shfl_xor_sync(~0u, n0, 2); n1 += __shfl_xor_sync(~0u, n1, 2);
      qmax = (n0 > qmax || n0 != n0) ? n0 : qmax;
      qmax = (n1 > qmax || n1 != n1) ? n1 : qmax;
    }
    if (pass == AB_PASS - 1) {
      float kmax = 0.f;
#pragma unroll
      for (int i = 0; i < SEQ / AB_T; i++) {
        const int key = threadIdx.x + AB_T * i;
        const uint32_t a = sK + (key >> 3) * 384 + (key & 7) * 16;
        const uint4 x = lds128(a), y = lds128(a + 128);
        const uint2 z = lds64(a + 256);
        const float n = ((sq2(x.x) + sq2(x.y)) + (sq2(x.z) + sq2(x.w))) + ((sq2(y.x) + sq2(y.y)) + (sq2(y.z) + sq2(y.w))) + (sq2(z.x) + sq2(z.y));
        kmax = (n > kmax || n != n) ? n : kmax;
      }
      const uint32_t kb = __reduce_max_sync(~0u, __float_as_uint(kmax) & 0x7fffffffu), qb = __reduce_max_sync(~0u, __float_as_uint(qmax) & 0x7fffffffu);
      if (lane < 2) asm volatile("red.shared.max.u32 [%0], %1;" :: "r"(smax + 4 * lane), "r"(lane ? kb : qb) : "memory");
      __syncwarp();
    }
    if ((lane & 3) == 2) { q4 = 0xBF8043C0u; q5 = 0xBF8043C0u; }
    float o[12];
    auto desc = [](uint32_t lo, uint32_t hi) { uint64_t d; asm("mov.b64 %0, {%1, %2};" : "=l"(d) : "r"(lo), "r"(hi)); return d; };
    const uint32_t k0 = (uint32_t)mkdesc(sK, 128, 0, 0), k1 = (uint32_t)mkdesc(sK + 256, 0, 0, 0), v0 = (uint32_t)mkdesc(sV, 384, 0, 0);
    float sa[16], sb2[16];
    uint32_t pa[8], pb[8];
    auto qk = [&](float* s, uint32_t t) {
      wg_rs32_00(s, q0, q1, q2, q3, desc(k0 + t, 24), 0);
      wg_rs32_00(s, q4, q5, z0, z1, desc(k1 + t, 24), 1);
      wg_commit();
    };
    auto step = [&](float* s, uint32_t* pp, int g0, uint32_t t, uint32_t nx, int acc) {
      wg_wait<1>();
      reg_fence<16>(s);
#pragma unroll
      for (int i = 0; i < 8; i++) pp[i] = poly_group(g0 + (i >> 1)) ? ex2_pair(s[2 * i], s[2 * i + 1], one, c0) : pack2(ex2(s[2 * i]), ex2(s[2 * i + 1]));
      wg_fence();
      wg_rs24_01(o, pp[0], pp[1], pp[2], pp[3], desc(v0 + t, 8), acc);
      wg_rs24_01(o, pp[4], pp[5], pp[6], pp[7], desc(v0 + t + 48, 8), 1);
      qk(s, nx);
    };
    if (pass == 0) mbar_wait(bars, 0);
    wg_fence();
    qk(sa, 0);
    qk(sb2, 96);
#pragma unroll 1
    for (uint32_t t = 0; t < 64 * 96; t += AB_U * 96) {
      const uint32_t nx = t + AB_U * 96 < 64 * 96 ? t + AB_U * 96 : 0;
      if (pass == AB_PASS - 1 && t == 40 * 96 && lane == 0) mbar_arrive(bF);
#pragma unroll
      for (int u = 0; u < AB_U; u += 2) {
        if (u == AB_U - 2 && pass == 0) mbar_wait(bars + 8 * (nx / 768), 0);
        step(sa, pa, 0, t + u * 96, u + 2 < AB_U ? t + (u + 2) * 96 : nx, u | t);
        step(sb2, pb, 4, t + u * 96 + 96, (u + 2 < AB_U ? t + (u + 2) * 96 : nx) + 96, 1);
      }
    }
    wg_wait<0>();
    reg_fence<12>(o); reg_fence<16>(sa); reg_fence<16>(sb2);
    attn_b_store(o, h, row0, lane);
  }
  mbar_wait(bF, 0);
  if (unsafe())
#pragma unroll 1
  for (int pass = 0; pass < AB_PASS; pass++) {
    const int row0 = quarter * 512 + ((warp >> 2) * AB_PASS + pass) * 64 + (warp & 3) * 16;
    const uint32_t* gq = g_bqkv + (h * 256 + (row0 >> 3)) * 96 + lane;
    const uint32_t q0 = gq[0], q1 = gq[96], q2 = gq[32], q3 = gq[128], q4 = gq[64], q5 = gq[160];
    float o[12];
#pragma unroll
    for (int i = 0; i < 12; i++) o[i] = 0.f;
    float m0 = -INFINITY, m1 = -INFINITY;
#pragma unroll 1
    for (int kt = 0; kt < 32; kt++) {
      float s[32];
      const uint64_t dk = mkdesc(sK + kt * 3072, 128, 384, 0), dk2 = mkdesc(sK + kt * 3072 + 256, 0, 384, 0);
      wg_fence();
      wg_rs64_00(s, q0, q1, q2, q3, dk, 0);
      wg_rs64_00(s, q4, q5, 0, 0, dk2, 1);
      wg_commit();
      wg_wait<0>();
      reg_fence<32>(s); reg_fence<12>(o);
      float n0 = m0, n1 = m1;
#pragma unroll
      for (int jj = 0; jj < 8; jj++) { n0 = fmaxf(n0, fmaxf(s[4 * jj], s[4 * jj + 1])); n1 = fmaxf(n1, fmaxf(s[4 * jj + 2], s[4 * jj + 3])); }
      n0 = fmaxf(n0, __shfl_xor_sync(~0u, n0, 1)); n0 = fmaxf(n0, __shfl_xor_sync(~0u, n0, 2));
      n1 = fmaxf(n1, __shfl_xor_sync(~0u, n1, 1)); n1 = fmaxf(n1, __shfl_xor_sync(~0u, n1, 2));
      const float r0 = ex2(m0 - n0), r1 = ex2(m1 - n1);
      m0 = n0; m1 = n1;
#pragma unroll
      for (int jj = 0; jj < 3; jj++) { o[4 * jj] *= r0; o[4 * jj + 1] *= r0; o[4 * jj + 2] *= r1; o[4 * jj + 3] *= r1; }
      uint32_t pp[16];
#pragma unroll
      for (int jj = 0; jj < 8; jj++) {
        pp[2 * jj] = pack2(ex2(s[4 * jj] - m0), ex2(s[4 * jj + 1] - m0));
        pp[2 * jj + 1] = pack2(ex2(s[4 * jj + 2] - m1), ex2(s[4 * jj + 3] - m1));
      }
      const uint64_t dv = mkdesc(sV + kt * 3072, 384, 128, 0);
      wg_fence();
#pragma unroll
      for (int kk = 0; kk < 4; kk++) wg_rs24_01(o, pp[4 * kk], pp[4 * kk + 1], pp[4 * kk + 2], pp[4 * kk + 3], dv + kk * 48, 1);
      wg_commit();
    }
    wg_wait<0>();
    reg_fence<12>(o);
    attn_b_store(o, h, row0, lane);
  }
  ABT(!!p.out, 0);
  bar_arrive(1, AB_T + 32);
  if (warp >= 12) return;
  const int g = lane >> 2, c = lane & 3;
  const bool live = opaque(threadIdx.x) < 256;
  float d[40] = {};
  uint2* x = g_x + ((blk * 16 + warp * 2) * 40 + cg * 5) * 32 + lane;
  if (warp < 8) {
#pragma unroll
  for (int i = 0; i < 10; i++) {
    const int r = i / 5, u = i % 5;
    const float4 t = unpack4(x[(r * 40 + u) * 32]);
    d[8 * u + 2 * r] = t.x; d[8 * u + 2 * r + 1] = t.y; d[8 * u + 4 + 2 * r] = t.z; d[8 * u + 5 + 2 * r] = t.w;
  }
  mbar_wait(bW, 0);
  reg_fence<40>(d);
  ABT(!!p.out, 4);
#pragma unroll 1
  for (int kb = 0; kb < 10; kb++) {
    const int i = kb < 6 ? kb : kb - 6;
    mbar_wait(bA + 8 * i, kb >= 6);
    const uint64_t da = mkdesc(ring(i) + (warp >> 2) * 8192, 128, 1024, 0), db = mkdesc(kb < 5 ? sK + kb * 10240 : sV + (kb - 5) * 10240, 1280, 128, 0);
    wg_fence();
#pragma unroll
    for (int kk = 0; kk < 4; kk++) wg_ss80_01(d, da + kk * 16, db + kk * 160, 1);
    wg_commit();
    if (kb > 0 && kb < 5) { wg_wait<1>(); if (lane == 0) mbar_arrive(bE + 8 * (kb - 1)); }
  }
  wg_wait<0>();
  reg_fence<40>(d);
  }
  ABT(!!p.out, 5);
  if (p.out) {
    if (warp >= 8) return;
    const uint32_t stage = sK + 83968 + warp * 2560 + (warp < 4 ? 0 : 131328 - 10240);
#pragma unroll
    for (int u = 0; u < 5; u++)
      stsm4(stage + (lane & 15) * 160 + u * 32 + (lane >> 4) * 16, pack2(d[8 * u], d[8 * u + 1]), pack2(d[8 * u + 2], d[8 * u + 3]),
            pack2(d[8 * u + 4], d[8 * u + 5]), pack2(d[8 * u + 6], d[8 * u + 7]));
    __syncwarp();
    uint4* out = reinterpret_cast<uint4*>(p.out + (blk * 128 + warp * 16) * (DM / 2) + cg * 40);
#pragma unroll
    for (int i = 0; i < 5; i++) { const int e = i * 32 + lane, r = e / 10; out[r * (DM / 8) + e - r * 10] = lds128(stage + e * 16); }
  } else {
    float2* stat = g_stat + blk * 1024 + (warp & 7) * 16 + g;
    float mean[2], rs[2];
#pragma unroll
    for (int r = 0; r < 2; r++) {
      float t = 0.f, q = 0.f;
#pragma unroll
      for (int i = 0; i < 10; i++) t += d[4 * i + 2 * r] + d[4 * i + 2 * r + 1];
      t += __shfl_xor_sync(~0u, t, 1); t += __shfl_xor_sync(~0u, t, 2);
      t *= 1.f / 80;
#pragma unroll
      for (int i = 0; i < 10; i++) { const float a = d[4 * i + 2 * r] - t, b = d[4 * i + 2 * r + 1] - t; q += a * a + b * b; }
      q += __shfl_xor_sync(~0u, q, 1); q += __shfl_xor_sync(~0u, q, 2);
      if (c == r && live) asm volatile("st.relaxed.gpu.global.v2.b32 [%0], {%1, %2};" :: "l"(stat + cg * 128 + r * 8), "r"(__float_as_uint(t)), "r"(nz(__float_as_uint(q))) : "memory");
    }
#pragma unroll
    for (int i = 0; i < 10; i++) {
      const int r = i / 5, u = i % 5;
      if (live) x[(r * 40 + u) * 32] = make_uint2(pack2(d[8 * u + 2 * r], d[8 * u + 2 * r + 1]), pack2(d[8 * u + 4 + 2 * r], d[8 * u + 5 + 2 * r]));
    }
    ABT(0, 6);
    uint2 e[4];
    int n = 0;
    do {
#pragma unroll
      for (int i = 0; i < 4; i++)
        asm volatile("ld.relaxed.gpu.global.v2.b32 {%0, %1}, [%2];" : "=r"(e[i].x), "=r"(e[i].y) : "l"(stat + (2 * c + (i & 1)) * 128 + (i >> 1) * 8) : "memory");
      spin_guard(n);
    } while (__any_sync(~0u, min(min(e[0].y, e[1].y), min(e[2].y, e[3].y)) == 0 && live));
#pragma unroll
    for (int r = 0; r < 2; r++) {
      const float m0 = __uint_as_float(e[2 * r].x), m1 = __uint_as_float(e[2 * r + 1].x);
      float t = m0 + m1;
      t += __shfl_xor_sync(~0u, t, 1); t += __shfl_xor_sync(~0u, t, 2);
      t *= 0.125f;
      float q = __uint_as_float(e[2 * r].y) + __uint_as_float(e[2 * r + 1].y) + 80.f * ((m0 - t) * (m0 - t) + (m1 - t) * (m1 - t));
      q += __shfl_xor_sync(~0u, q, 1); q += __shfl_xor_sync(~0u, q, 2);
      mean[r] = t; rs[r] = rsqrtf(q * (1.f / DM) + 1e-5f);
    }
    ABT(0, 7);
    uint32_t w[2][5][2];
#pragma unroll
    for (int i = 0; i < 20; i++) w[i & 1][i >> 2][i >> 1 & 1] = pack2((d[2 * i] - mean[i & 1]) * rs[i & 1], (d[2 * i + 1] - mean[i & 1]) * rs[i & 1]);
    ln_store(w, blk * 8 + warp, cg * 5, live);
  }
  ABT(!!p.out, 8);
  TRACE(2);
}

typedef CUresult (*EncodeFn)(CUtensorMap*, CUtensorMapDataType, cuuint32_t, void*, const cuuint64_t*, const cuuint64_t*,
                             const cuuint32_t*, const cuuint32_t*, CUtensorMapInterleave, CUtensorMapSwizzle,
                             CUtensorMapL2promotion, CUtensorMapFloatOOBfill);

void make_map(EncodeFn enc, CUtensorMap* m, const void* ptr, int cols, int rows, int nb) {
  const cuuint64_t dims[3] = {(cuuint64_t)(nb ? 64 : cols), (cuuint64_t)rows, (cuuint64_t)cols / 64};
  const cuuint64_t strides[2] = {(cuuint64_t)cols * 2, 128};
  const cuuint32_t box[3] = {64, 32, (cuuint32_t)nb}, es[3] = {1, 1, 1};
  enc(m, CU_TENSOR_MAP_DATA_TYPE_BFLOAT16, nb ? 3 : 2, const_cast<void*>(ptr), dims, strides, box, es, CU_TENSOR_MAP_INTERLEAVE_NONE,
      CU_TENSOR_MAP_SWIZZLE_128B, CU_TENSOR_MAP_L2_PROMOTION_L2_128B, CU_TENSOR_MAP_FLOAT_OOB_FILL_NONE);
}
template <class... KA, class... A>
void launch(void (*kern)(KA...), int grid, int block, int smem, int cluster, bool pdl, A... args) {
  cudaFuncSetAttribute(kern, cudaFuncAttributeMaxDynamicSharedMemorySize, smem);
  cudaLaunchConfig_t cfg = {};
  cfg.gridDim = dim3(grid); cfg.blockDim = dim3(block); cfg.dynamicSmemBytes = smem; cfg.stream = cudaStreamPerThread;
  cudaLaunchAttribute at[2];
  int n = 0;
  if (cluster > 1) { at[n].id = cudaLaunchAttributeClusterDimension; at[n].val.clusterDim.x = cluster; at[n].val.clusterDim.y = 1; at[n].val.clusterDim.z = 1; n++; }
  if (pdl) { at[n].id = cudaLaunchAttributeProgrammaticStreamSerialization; at[n].val.programmaticStreamSerializationAllowed = 1; n++; }
  cfg.attrs = at; cfg.numAttrs = n;
  cudaLaunchKernelEx(&cfg, kern, args...);
}
template <class T> void* sym(T& s) { void* p = nullptr; cudaGetSymbolAddress(&p, s); return p; }

}

#define MODE(b) 0
extern "C" void kernel_launch(void* const* d_in, const int* in_sizes, int n_in, void* d_out, int out_size) {
  const __nv_bfloat16* x = (const __nv_bfloat16*)d_in[0];
  void* fn = nullptr; cudaDriverEntryPointQueryResult qr;
  cudaGetDriverEntryPoint("cuTensorMapEncodeTiled", &fn, cudaEnableDefault, &qr);
  EncodeFn enc = (EncodeFn)fn;

  ChainParams ch = {};
  PostParams op = {};
  for (int i = 0; i < 3; i++) {
    const cuuint64_t dims[3] = {HD, 128, 5}, strides[2] = {HD * 2, HD * 256};
    const cuuint32_t box[3] = {64, 128, 5}, es[3] = {1, 1, 1};
    enc(i == 0 ? &ch.wq : i == 1 ? &ch.wk : &ch.wv, CU_TENSOR_MAP_DATA_TYPE_BFLOAT16, 3, d_in[2 + i], dims, strides, box, es, CU_TENSOR_MAP_INTERLEAVE_NONE,
        CU_TENSOR_MAP_SWIZZLE_128B, W_PROMO, CU_TENSOR_MAP_FLOAT_OOB_FILL_NONE);
  }
  {
    const cuuint64_t dims[3] = {DM, HD, 7}, strides[2] = {DM * 2, 64};
    const cuuint32_t box[3] = {32, 64, 7}, es[3] = {1, 1, 1};
    enc(&ch.wo, CU_TENSOR_MAP_DATA_TYPE_BFLOAT16, 3, d_in[5], dims, strides, box, es, CU_TENSOR_MAP_INTERLEAVE_NONE,
        CU_TENSOR_MAP_SWIZZLE_64B, CU_TENSOR_MAP_L2_PROMOTION_L2_128B, CU_TENSOR_MAP_FLOAT_OOB_FILL_NONE);
  }
  ch.mem0 = (const __nv_bfloat16*)d_in[1];
  ch.pool = (uint8_t*)(((uintptr_t)sym(g_pool) + 8191) & ~(uintptr_t)8191); ch.kv = (uint8_t*)sym(g_kv); ch.xc = (const uint32_t*)sym(g_xc); ch.sync = (uint32_t*)sym(g_sync);
  ch.d1 = 0; ch.d1b = 0; ch.d2 = 0; ch.d2b = 0;
  make_map(enc, &op.wq, d_in[2], HD, DM, 3);
  make_map(enc, &op.wo, d_in[5], DM, HD, 5); make_map(enc, &op.wo2, d_in[5], DM, HD, 0);
  make_map(enc, &op.wb, d_in[8], 1920, DM, 5); make_map(enc, &op.wb2, d_in[8], 1920, DM, 0);
  op.gap = 17; op.share = 20; op.look = 14; op.gap2 = 0; op.pol = 1;

  const Weights wa = {{(const uint8_t*)d_in[3], (const uint8_t*)d_in[4], (const uint8_t*)d_in[2], (const uint8_t*)d_in[5]}}, none = {};
  launch(first_kernel, 132, 384, 128 * 1024, 1, false, x, (const uint4*)d_in[9], wa);
  for (int layer = 0; layer < 2; layer++) {
    ch.layer = ch.d2b = op.layer = layer;
    launch(chain_kernel, 96, 256, CH_SMEM, 3, true, ch);
    launch(post_kernel, MODE(3) ? 36 : 132, 384, OP_SMEM, 1, !MODE(1), op);
    const AbParams ab = {layer == 0 ? wa : none, (uint32_t*)sym(g_bo) + layer * 128, layer == 0 ? nullptr : (uint32_t*)d_out};
    launch(attn_b_kernel, 128, AB_T + 32, AB_SMEM, 1, true, ab);
  }
}
```

```cpp
#include <cuda_runtime.h>
#include <cuda_bf16.h>
#include <cuda.h>
#include <stdint.h>

namespace {

constexpr int SEQ = 2048, DM = 640, HD = 6144, NSEG = 64;
constexpr int SPIN_LIMIT = 1 << 20;

__device__ __align__(128) uint2 g_x[SEQ * DM / 4];
__device__ __align__(128) uint32_t g_of[SEQ * DM / 2];
__device__ __align__(128) uint4 g_wb[DM * DM / 8];
__device__ __align__(16) float2 g_stat[16 * 8 * 128];
__device__ uint32_t g_bo[8 * 32];
__device__ __align__(128) uint4 g_q[SEQ * HD / 8];
__device__ __align__(128) uint32_t g_o[SEQ * HD / 2];
constexpr int KV_BYTES = 5120, KV_M = 4096, KV_V = NSEG * KV_BYTES;
__device__ __align__(128) uint8_t g_kv[96 * 2 * NSEG * KV_BYTES];
__device__ __align__(128) uint32_t g_xc[SEQ * DM / 2];
#define OP_B4 5
#define OP_B8 9
#define OP_B16 13
#define QA_END 12
__host__ __device__ constexpr int op_split(int b) { return b < OP_B4 ? 2 : b < OP_B8 ? 4 : b < OP_B16 ? 8 : 16; }
#define AB_PF 2
#define AB_PF0 0
#define AB_PFD 6000
#define W_PROMO CU_TENSOR_MAP_L2_PROMOTION_L2_128B
#define OP_EARLY 1
#define ATT_LOOK 1
#define PR_FIN 1
#define PR_ATT 0
#define PR_OP 2
#define PRE_MAX PS
#define PRE_GAP 0u
#define Q_PF 0
#define OEF 0
#define BQ_HOLD 6
#define WEF 1
#define FK_REP 4
#define FK_PF 1
#define BQ_160 10
#define BQ_80 16
#define OP_160 16
__host__ __device__ constexpr int op_width(int b) { return b < OP_160 ? 320 : 160; }
__host__ __device__ constexpr int bq_width(int b) { return b < BQ_160 ? 320 : b < BQ_80 ? 160 : 80; }
__device__ __align__(128) uint2 g_part[16 * 16 * 16 * 40 * 32];
__device__ __align__(128) uint32_t g_xn[SEQ * DM / 2];
constexpr int SY_Q = 128, SY_T = 160, SY_QC = 192, SY_N = 193;
__device__ __align__(16) uint32_t g_sync[SY_N];
constexpr int NSLOT = 92;
__device__ uint32_t g_pool[(NSLOT + 2) * 2048];
__device__ int g_smpart[256], g_orient[NSLOT];
__device__ uint32_t g_smclk[256], g_smuse[256];
__device__ uint32_t g_bqkv[3 * 32 * 256 * 96];

#define ABT(L, i)
#define PST(i)
#define MODE_D(b) 0
#define DELAY(d)
#define XT(i)
#define MISS(k, n)
#define PRO(i)
#define TRACE(w)
#define ITEM(code, w)
#define TR(i, v)
#define TM(i)
#define TM1(i)
#define TMD(i, dep)
#define TMV(i, at, v)

__device__ __forceinline__ uint32_t gtime() { uint32_t c; asm volatile("mov.u32 %0, %%globaltimer_lo;" : "=r"(c) :: "memory"); return c; }
__device__ __forceinline__ uint32_t clk32() { uint32_t c; asm volatile("mov.u32 %0, %%clock;" : "=r"(c) :: "memory"); return c; }
__device__ __forceinline__ uint32_t s2u(const void* p) { return (uint32_t)__cvta_generic_to_shared(p); }
__device__ __forceinline__ uint32_t pack2(float a, float b) {
  uint32_t r; asm("cvt.rn.bf16x2.f32 %0, %1, %2;" : "=r"(r) : "f"(b), "f"(a)); return r; }
__device__ __forceinline__ float bf_lo(uint32_t w) { return __uint_as_float(w << 16); }
__device__ __forceinline__ float bf_hi(uint32_t w) { return __uint_as_float(w & 0xffff0000u); }
__device__ __forceinline__ uint2 pack4(float4 v) { return make_uint2(pack2(v.x, v.y), pack2(v.z, v.w)); }
__device__ __forceinline__ float4 unpack4(uint2 w) { return make_float4(bf_lo(w.x), bf_hi(w.x), bf_lo(w.y), bf_hi(w.y)); }
__device__ __forceinline__ float ex2(float x) { float y; asm("ex2.approx.ftz.f32 %0, %1;" : "=f"(y) : "f"(x)); return y; }

__device__ __forceinline__ void mbar_init(uint32_t bar, uint32_t n) {
  asm volatile("mbarrier.init.shared::cta.b64 [%0], %1;" :: "r"(bar), "r"(n) : "memory"); }
__device__ __forceinline__ void mbar_expect(uint32_t bar, uint32_t bytes) {
  asm volatile("mbarrier.arrive.expect_tx.shared::cta.b64 _, [%0], %1;" :: "r"(bar), "r"(bytes) : "memory"); }
__device__ __forceinline__ void mbar_arrive(uint32_t bar) {
  asm volatile("mbarrier.arrive.shared::cta.b64 _, [%0];" :: "r"(bar) : "memory"); }
__device__ __forceinline__ void mbar_wait(uint32_t bar, uint32_t ph) {
  asm volatile("{.reg .pred p; .reg .u32 n; mov.u32 n, 0;\n"
               "W: mbarrier.try_wait.parity.shared::cta.b64 p, [%0], %1; @p bra D;\n"
               "add.u32 n, n, 1; setp.gt.u32 p, n, %2; @p trap; bra W;\n"
               "D: }" :: "r"(bar), "r"(ph), "n"(SPIN_LIMIT) : "memory");
}
__device__ __forceinline__ void mbar_wait_cluster(uint32_t bar, uint32_t ph) {
  asm volatile("{.reg .pred p; .reg .u32 n; mov.u32 n, 0;\n"
               "W: mbarrier.try_wait.parity.acquire.cluster.shared::cta.b64 p, [%0], %1; @p bra D;\n"
               "add.u32 n, n, 1; setp.gt.u32 p, n, %2; @p trap; bra W;\n"
               "D: }" :: "r"(bar), "r"(ph), "n"(SPIN_LIMIT) : "memory");
}
__device__ __forceinline__ void spin_guard(int& n) {
  asm volatile("{.reg .pred p; add.s32 %0, %0, 1; setp.gt.s32 p, %0, %1; @p trap;}" : "+r"(n) : "n"(SPIN_LIMIT));
}
__device__ __forceinline__ void pdl_wait() { asm volatile("griddepcontrol.wait;" ::: "memory"); TRACE(1); }
__device__ __forceinline__ void pdl_launch() { asm volatile("griddepcontrol.launch_dependents;" ::: "memory"); }
__device__ __forceinline__ uint32_t ld_acquire(const uint32_t* p) { uint32_t v; asm volatile("ld.acquire.gpu.global.u32 %0, [%1];" : "=r"(v) : "l"(p) : "memory"); return v; }
__device__ __forceinline__ void red_release(uint32_t* p, uint32_t v) { asm volatile("red.release.gpu.global.add.u32 [%0], %1;" :: "l"(p), "r"(v) : "memory"); }
__device__ __forceinline__ void red_relaxed(uint32_t* p, uint32_t v) { asm volatile("red.relaxed.gpu.global.add.u32 [%0], %1;" :: "l"(p), "r"(v) : "memory"); }
__device__ __forceinline__ void fence_async_global() { asm volatile("fence.proxy.async.global;" ::: "memory"); }
__device__ __forceinline__ void fence_async() { asm volatile("fence.proxy.async.shared::cta;" ::: "memory"); }
__device__ __forceinline__ void bar_sync(int id, int n) { asm volatile("bar.sync %0, %1;" :: "r"(id), "r"(n) : "memory"); }
__device__ __forceinline__ void bar_arrive(int id, int n) { asm volatile("bar.arrive %0, %1;" :: "r"(id), "r"(n) : "memory"); }
__device__ __forceinline__ void tma_load(uint32_t dst, const CUtensorMap* m, int c0, int c1, uint32_t bar) {
  asm volatile("cp.async.bulk.tensor.2d.shared::cluster.global.mbarrier::complete_tx::bytes [%0], [%1, {%3, %4}], [%2];"
               :: "r"(dst), "l"(m), "r"(bar), "r"(c0), "r"(c1) : "memory"); }
template <bool STREAM = false>
__device__ __forceinline__ void tma_load3(uint32_t dst, const CUtensorMap* m, int c0, int c1, uint32_t bar) {
  if (STREAM)
    asm volatile("{.reg .b64 pol; createpolicy.fractional.L2::evict_first.b64 pol, 1.0;\n"
                 "cp.async.bulk.tensor.3d.shared::cluster.global.mbarrier::complete_tx::bytes.L2::cache_hint [%0], [%1, {%3, %4, 0}], [%2], pol;}"
                 :: "r"(dst), "l"(m), "r"(bar), "r"(c0), "r"(c1) : "memory");
  else
  asm volatile("cp.async.bulk.tensor.3d.shared::cluster.global.mbarrier::complete_tx::bytes [%0], [%1, {%3, %4, 0}], [%2];"
               :: "r"(dst), "l"(m), "r"(bar), "r"(c0), "r"(c1) : "memory"); }
__device__ __forceinline__ void tma_load3z(uint32_t dst, const CUtensorMap* m, int c1, int c2, uint32_t bar) {
  asm volatile("cp.async.bulk.tensor.3d.shared::cluster.global.mbarrier::complete_tx::bytes [%0], [%1, {0, %3, %4}], [%2];"
               :: "r"(dst), "l"(m), "r"(bar), "r"(c1), "r"(c2) : "memory"); }
__device__ __forceinline__ void tma_store(const CUtensorMap* m, uint32_t src, int c0, int c1) {
  asm volatile("cp.async.bulk.tensor.2d.global.shared::cta.bulk_group [%0, {%2, %3}], [%1];"
               :: "l"(m), "r"(src), "r"(c0), "r"(c1) : "memory"); }
__device__ __forceinline__ void tma_store_stream(const CUtensorMap* m, uint32_t src, int c0, int c1) {
  asm volatile("{.reg .b64 pol; createpolicy.fractional.L2::evict_first.b64 pol, 1.0;\n"
               "cp.async.bulk.tensor.2d.global.shared::cta.bulk_group.L2::cache_hint [%0, {%2, %3}], [%1], pol;}"
               :: "l"(m), "r"(src), "r"(c0), "r"(c1) : "memory"); }
__device__ __forceinline__ void bulk_load(uint32_t dst, const void* src, uint32_t bytes, uint32_t bar) {
  asm volatile("cp.async.bulk.shared::cluster.global.mbarrier::complete_tx::bytes [%0], [%1], %2, [%3];"
               :: "r"(dst), "l"(src), "r"(bytes), "r"(bar) : "memory"); }
__device__ __forceinline__ void bulk_load_last(uint32_t dst, const void* src, uint32_t bytes, uint32_t bar) {
  asm volatile("{.reg .b64 pol; createpolicy.fractional.L2::evict_first.b64 pol, 1.0;\n"
               "cp.async.bulk.shared::cluster.global.mbarrier::complete_tx::bytes.L2::cache_hint [%0], [%1], %2, [%3], pol;}"
               :: "r"(dst), "l"(src), "r"(bytes), "r"(bar) : "memory"); }
__device__ __forceinline__ void tma_load_last(uint32_t dst, const CUtensorMap* m, int c0, int c1, uint32_t bar) {
  asm volatile("{.reg .b64 pol; createpolicy.fractional.L2::evict_first.b64 pol, 1.0;\n"
               "cp.async.bulk.tensor.2d.shared::cluster.global.mbarrier::complete_tx::bytes.L2::cache_hint [%0], [%1, {%3, %4}], [%2], pol;}"
               :: "r"(dst), "l"(m), "r"(bar), "r"(c0), "r"(c1) : "memory"); }
__device__ __forceinline__ void bulk_send(uint32_t dst, uint32_t src, uint32_t bytes, uint32_t bar) {
  asm volatile("cp.async.bulk.shared::cluster.shared::cta.mbarrier::complete_tx::bytes [%0], [%1], %2, [%3];"
               :: "r"(dst), "r"(src), "r"(bytes), "r"(bar) : "memory"); }
__device__ __forceinline__ void bulk_store(void* dst, uint32_t src, uint32_t bytes) {
  asm volatile("cp.async.bulk.global.shared::cta.bulk_group [%0], [%1], %2;" :: "l"(dst), "r"(src), "r"(bytes) : "memory"); }
__device__ __forceinline__ void bulk_commit() { asm volatile("cp.async.bulk.commit_group;" ::: "memory"); }
template <int N> __device__ __forceinline__ void bulk_wait_read() { asm volatile("cp.async.bulk.wait_group.read %0;" :: "n"(N) : "memory"); }
template <int N> __device__ __forceinline__ void bulk_wait() { asm volatile("cp.async.bulk.wait_group %0;" :: "n"(N) : "memory"); }

__device__ __forceinline__ uint64_t mkdesc(uint32_t addr, uint32_t lbo, uint32_t sbo, uint32_t sw) {
  return (uint64_t)((addr & 0x3FFFF) >> 4) | ((uint64_t)(lbo >> 4) << 16) | ((uint64_t)(sbo >> 4) << 32) | ((uint64_t)sw << 62); }
__device__ __forceinline__ void wg_fence() { asm volatile("wgmma.fence.sync.aligned;" ::: "memory"); }
__device__ __forceinline__ void wg_commit() { asm volatile("wgmma.commit_group.sync.aligned;" ::: "memory"); }
template <int N> __device__ __forceinline__ void wg_wait() { asm volatile("wgmma.wait_group.sync.aligned %0;" :: "n"(N) : "memory"); }
template <int N> __device__ __forceinline__ void reg_fence(float* d) {
#pragma unroll
  for (int i = 0; i < N; i++) asm volatile("" : "+f"(d[i]) :: "memory");
}

__device__ __forceinline__ void mma16(float* d, uint32_t a0, uint32_t a1, uint32_t a2, uint32_t a3, uint32_t b0, uint32_t b1) {
  asm volatile("mma.sync.aligned.m16n8k16.row.col.f32.bf16.bf16.f32 {%0,%1,%2,%3},{%4,%5,%6,%7},{%8,%9},{%0,%1,%2,%3};"
               : "+f"(d[0]), "+f"(d[1]), "+f"(d[2]), "+f"(d[3]) : "r"(a0), "r"(a1), "r"(a2), "r"(a3), "r"(b0), "r"(b1)); }
__device__ __forceinline__ void mma8(float* d, uint32_t a0, uint32_t a1, uint32_t b0) {
  asm volatile("mma.sync.aligned.m16n8k8.row.col.f32.bf16.bf16.f32 {%0,%1,%2,%3},{%4,%5},{%6},{%0,%1,%2,%3};"
               : "+f"(d[0]), "+f"(d[1]), "+f"(d[2]), "+f"(d[3]) : "r"(a0), "r"(a1), "r"(b0)); }
__device__ __forceinline__ void ldsm4(uint32_t* r, uint32_t a) {
  asm volatile("ldmatrix.sync.aligned.m8n8.x4.shared.b16 {%0,%1,%2,%3},[%4];" : "=r"(r[0]), "=r"(r[1]), "=r"(r[2]), "=r"(r[3]) : "r"(a) : "memory"); }
__device__ __forceinline__ void ldsm4t(uint32_t* r, uint32_t a) {
  asm volatile("ldmatrix.sync.aligned.m8n8.x4.trans.shared.b16 {%0,%1,%2,%3},[%4];" : "=r"(r[0]), "=r"(r[1]), "=r"(r[2]), "=r"(r[3]) : "r"(a) : "memory"); }
__device__ __forceinline__ void ldsm2(uint32_t* r, uint32_t a) {
  asm volatile("ldmatrix.sync.aligned.m8n8.x2.shared.b16 {%0,%1},[%2];" : "=r"(r[0]), "=r"(r[1]) : "r"(a) : "memory"); }
__device__ __forceinline__ void stsm4(uint32_t a, uint32_t r0, uint32_t r1, uint32_t r2, uint32_t r3) {
  asm volatile("stmatrix.sync.aligned.m8n8.x4.shared.b16 [%0], {%1,%2,%3,%4};" :: "r"(a), "r"(r0), "r"(r1), "r"(r2), "r"(r3) : "memory"); }
__device__ __forceinline__ void stsm2t(uint32_t a, uint32_t r0, uint32_t r1) {
  asm volatile("stmatrix.sync.aligned.m8n8.x2.trans.shared.b16 [%0], {%1,%2};" :: "r"(a), "r"(r0), "r"(r1) : "memory"); }
__device__ __forceinline__ void stsm4t(uint32_t a, uint32_t r0, uint32_t r1, uint32_t r2, uint32_t r3) {
  asm volatile("stmatrix.sync.aligned.m8n8.x4.trans.shared.b16 [%0], {%1,%2,%3,%4};" :: "r"(a), "r"(r0), "r"(r1), "r"(r2), "r"(r3) : "memory"); }
__device__ __forceinline__ void st_async128(uint32_t a, uint4 v, uint32_t bar) {
  asm volatile("st.async.shared::cluster.mbarrier::complete_tx::bytes.v4.b32 [%0], {%1,%2,%3,%4}, [%5];" :: "r"(a), "r"(v.x), "r"(v.y), "r"(v.z), "r"(v.w), "r"(bar) : "memory"); }
__device__ __forceinline__ void sts32(uint32_t a, uint32_t v) { asm volatile("st.shared.b32 [%0], %1;" :: "r"(a), "r"(v) : "memory"); }
__device__ __forceinline__ void sts64f(uint32_t a, float x, float y) { asm volatile("st.shared.v2.f32 [%0], {%1,%2};" :: "r"(a), "f"(x), "f"(y) : "memory"); }
__device__ __forceinline__ void sts128(uint32_t a, uint4 v) {
  asm volatile("st.shared.v4.b32 [%0], {%1,%2,%3,%4};" :: "r"(a), "r"(v.x), "r"(v.y), "r"(v.z), "r"(v.w) : "memory"); }
__device__ __forceinline__ void sts128f(uint32_t a, float x, float y, float z, float w) {
  asm volatile("st.shared.v4.f32 [%0], {%1,%2,%3,%4};" :: "r"(a), "f"(x), "f"(y), "f"(z), "f"(w) : "memory"); }
__device__ __forceinline__ float lds32f(uint32_t a) { float v; asm volatile("ld.shared.f32 %0, [%1];" : "=f"(v) : "r"(a) : "memory"); return v; }
__device__ __forceinline__ float2 lds64f(uint32_t a) { float2 v; asm volatile("ld.shared.v2.f32 {%0,%1}, [%2];" : "=f"(v.x), "=f"(v.y) : "r"(a) : "memory"); return v; }
__device__ __forceinline__ float4 lds128f(uint32_t a) {
  float4 v; asm volatile("ld.shared.v4.f32 {%0,%1,%2,%3}, [%4];" : "=f"(v.x), "=f"(v.y), "=f"(v.z), "=f"(v.w) : "r"(a) : "memory"); return v; }
__device__ __forceinline__ uint4 lds128(uint32_t a) {
  uint4 v; asm volatile("ld.shared.v4.b32 {%0,%1,%2,%3}, [%4];" : "=r"(v.x), "=r"(v.y), "=r"(v.z), "=r"(v.w) : "r"(a) : "memory"); return v; }
__device__ __forceinline__ uint4 ldg_strong128(const void* p) {
  uint4 v; asm volatile("ld.relaxed.gpu.global.v4.u32 {%0,%1,%2,%3}, [%4];" : "=r"(v.x), "=r"(v.y), "=r"(v.z), "=r"(v.w) : "l"(p) : "memory"); return v; }
__device__ __forceinline__ void stg_strong32(void* p, uint32_t v) { asm volatile("st.relaxed.gpu.global.u32 [%0], %1;" :: "l"(p), "r"(v) : "memory"); }
__device__ __forceinline__ void stg_strong16(void* p, uint32_t v) { asm volatile("st.relaxed.gpu.global.u16 [%0], %1;" :: "l"(p), "h"((uint16_t)v) : "memory"); }
__device__ __forceinline__ void stg_strong128(void* p, uint4 v) {
  asm volatile("st.relaxed.gpu.global.v4.u32 [%0], {%1,%2,%3,%4};" :: "l"(p), "r"(v.x), "r"(v.y), "r"(v.z), "r"(v.w) : "memory"); }
__device__ __forceinline__ uint32_t mapa(uint32_t a, uint32_t r) {
  uint32_t o; asm("mapa.shared::cluster.u32 %0, %1, %2;" : "=r"(o) : "r"(a), "r"(r)); return o; }
__device__ __forceinline__ void st_async2f(uint32_t a, float x, float y, uint32_t bar) {
  asm volatile("st.async.shared::cluster.mbarrier::complete_tx::bytes.v2.f32 [%0], {%1,%2}, [%3];" :: "r"(a), "f"(x), "f"(y), "r"(bar) : "memory"); }
__device__ __forceinline__ void st_async32(uint32_t a, uint32_t x, uint32_t bar) {
  asm volatile("st.async.shared::cluster.mbarrier::complete_tx::bytes.b32 [%0], %1, [%2];" :: "r"(a), "r"(x), "r"(bar) : "memory"); }
__device__ __forceinline__ uint32_t lds32(uint32_t a) { uint32_t v; asm volatile("ld.shared.b32 %0, [%1];" : "=r"(v) : "r"(a) : "memory"); return v; }
__device__ __forceinline__ void st_async64(uint32_t a, uint32_t x, uint32_t y, uint32_t bar) {
  asm volatile("st.async.shared::cluster.mbarrier::complete_tx::bytes.v2.b32 [%0], {%1,%2}, [%3];" :: "r"(a), "r"(x), "r"(y), "r"(bar) : "memory"); }
__device__ __forceinline__ uint2 lds64(uint32_t a) { uint2 v; asm volatile("ld.shared.v2.b32 {%0,%1}, [%2];" : "=r"(v.x), "=r"(v.y) : "r"(a) : "memory"); return v; }
__device__ __forceinline__ void sts64(uint32_t a, uint32_t x, uint32_t y) { asm volatile("st.shared.v2.b32 [%0], {%1,%2};" :: "r"(a), "r"(x), "r"(y) : "memory"); }
__device__ __forceinline__ uint32_t ldg_strong32(const void* p) { uint32_t v; asm volatile("ld.relaxed.gpu.global.u32 %0, [%1];" : "=r"(v) : "l"(p) : "memory"); return v; }
__device__ __forceinline__ uint32_t transpose8(uint32_t x) { uint32_t r; asm volatile("movmatrix.sync.aligned.m8n8.trans.b16 %0, %1;" : "=r"(r) : "r"(x)); return r; }
__device__ __forceinline__ uint32_t hadd2(uint32_t a, uint32_t b) { uint32_t r; asm("add.rn.bf16x2 %0, %1, %2;" : "=r"(r) : "r"(a), "r"(b)); return r; }
__device__ __forceinline__ uint32_t min4(uint4 v) { return min(__vimin3_u32(v.x, v.y, v.z), v.w); }

__device__ __forceinline__ void wg_ss192_01(float* d, uint64_t da, uint64_t db, int sd) {
  asm volatile("{.reg .pred p; setp.ne.b32 p, %98, 0;\n"
    "wgmma.mma_async.sync.aligned.m64n192k16.f32.bf16.bf16 {%0,%1,%2,%3,%4,%5,%6,%7,%8,%9,%10,%11,%12,%13,%14,%15,%16,%17,%18,%19,%20,%21,%22,%23,%24,%25,%26,%27,%28,%29,%30,%31,%32,%33,%34,%35,%36,%37,%38,%39,%40,%41,%42,%43,%44,%45,%46,%47,%48,%49,%50,%51,%52,%53,%54,%55,%56,%57,%58,%59,%60,%61,%62,%63,%64,%65,%66,%67,%68,%69,%70,%71,%72,%73,%74,%75,%76,%77,%78,%79,%80,%81,%82,%83,%84,%85,%86,%87,%88,%89,%90,%91,%92,%93,%94,%95}, %96, %97, p, 1, 1, 0, 1;}"
    : "+f"(d[0]),"+f"(d[1]),"+f"(d[2]),"+f"(d[3]),"+f"(d[4]),"+f"(d[5]),"+f"(d[6]),"+f"(d[7]),"+f"(d[8]),"+f"(d[9]),"+f"(d[10]),"+f"(d[11]),"+f"(d[12]),"+f"(d[13]),"+f"(d[14]),"+f"(d[15]),"+f"(d[16]),"+f"(d[17]),"+f"(d[18]),"+f"(d[19]),"+f"(d[20]),"+f"(d[21]),"+f"(d[22]),"+f"(d[23]),"+f"(d[24]),"+f"(d[25]),"+f"(d[26]),"+f"(d[27]),"+f"(d[28]),"+f"(d[29]),"+f"(d[30]),"+f"(d[31]),"+f"(d[32]),"+f"(d[33]),"+f"(d[34]),"+f"(d[35]),"+f"(d[36]),"+f"(d[37]),"+f"(d[38]),"+f"(d[39]),"+f"(d[40]),"+f"(d[41]),"+f"(d[42]),"+f"(d[43]),"+f"(d[44]),"+f"(d[45]),"+f"(d[46]),"+f"(d[47]),"+f"(d[48]),"+f"(d[49]),"+f"(d[50]),"+f"(d[51]),"+f"(d[52]),"+f"(d[53]),"+f"(d[54]),"+f"(d[55]),"+f"(d[56]),"+f"(d[57]),"+f"(d[58]),"+f"(d[59]),"+f"(d[60]),"+f"(d[61]),"+f"(d[62]),"+f"(d[63]),"+f"(d[64]),"+f"(d[65]),"+f"(d[66]),"+f"(d[67]),"+f"(d[68]),"+f"(d[69]),"+f"(d[70]),"+f"(d[71]),"+f"(d[72]),"+f"(d[73]),"+f"(d[74]),"+f"(d[75]),"+f"(d[76]),"+f"(d[77]),"+f"(d[78]),"+f"(d[79]),"+f"(d[80]),"+f"(d[81]),"+f"(d[82]),"+f"(d[83]),"+f"(d[84]),"+f"(d[85]),"+f"(d[86]),"+f"(d[87]),"+f"(d[88]),"+f"(d[89]),"+f"(d[90]),"+f"(d[91]),"+f"(d[92]),"+f"(d[93]),"+f"(d[94]),"+f"(d[95])
    : "l"(da), "l"(db), "r"(sd));
}
__device__ __forceinline__ void wg_ss128_01(float* d, uint64_t da, uint64_t db, int sd) {
  asm volatile("{.reg .pred p; setp.ne.b32 p, %66, 0;\n"
    "wgmma.mma_async.sync.aligned.m64n128k16.f32.bf16.bf16 {%0,%1,%2,%3,%4,%5,%6,%7,%8,%9,%10,%11,%12,%13,%14,%15,%16,%17,%18,%19,%20,%21,%22,%23,%24,%25,%26,%27,%28,%29,%30,%31,%32,%33,%34,%35,%36,%37,%38,%39,%40,%41,%42,%43,%44,%45,%46,%47,%48,%49,%50,%51,%52,%53,%54,%55,%56,%57,%58,%59,%60,%61,%62,%63}, %64, %65, p, 1, 1, 0, 1;}"
    : "+f"(d[0]),"+f"(d[1]),"+f"(d[2]),"+f"(d[3]),"+f"(d[4]),"+f"(d[5]),"+f"(d[6]),"+f"(d[7]),"+f"(d[8]),"+f"(d[9]),"+f"(d[10]),"+f"(d[11]),"+f"(d[12]),"+f"(d[13]),"+f"(d[14]),"+f"(d[15]),"+f"(d[16]),"+f"(d[17]),"+f"(d[18]),"+f"(d[19]),"+f"(d[20]),"+f"(d[21]),"+f"(d[22]),"+f"(d[23]),"+f"(d[24]),"+f"(d[25]),"+f"(d[26]),"+f"(d[27]),"+f"(d[28]),"+f"(d[29]),"+f"(d[30]),"+f"(d[31]),"+f"(d[32]),"+f"(d[33]),"+f"(d[34]),"+f"(d[35]),"+f"(d[36]),"+f"(d[37]),"+f"(d[38]),"+f"(d[39]),"+f"(d[40]),"+f"(d[41]),"+f"(d[42]),"+f"(d[43]),"+f"(d[44]),"+f"(d[45]),"+f"(d[46]),"+f"(d[47]),"+f"(d[48]),"+f"(d[49]),"+f"(d[50]),"+f"(d[51]),"+f"(d[52]),"+f"(d[53]),"+f"(d[54]),"+f"(d[55]),"+f"(d[56]),"+f"(d[57]),"+f"(d[58]),"+f"(d[59]),"+f"(d[60]),"+f"(d[61]),"+f"(d[62]),"+f"(d[63])
    : "l"(da), "l"(db), "r"(sd));
}
__device__ __forceinline__ void wg_ss160_01(float* d, uint64_t da, uint64_t db, int sd) {
  asm volatile("{.reg .pred p; setp.ne.b32 p, %82, 0;\n"
    "wgmma.mma_async.sync.aligned.m64n160k16.f32.bf16.bf16 {%0,%1,%2,%3,%4,%5,%6,%7,%8,%9,%10,%11,%12,%13,%14,%15,%16,%17,%18,%19,%20,%21,%22,%23,%24,%25,%26,%27,%28,%29,%30,%31,%32,%33,%34,%35,%36,%37,%38,%39,%40,%41,%42,%43,%44,%45,%46,%47,%48,%49,%50,%51,%52,%53,%54,%55,%56,%57,%58,%59,%60,%61,%62,%63,%64,%65,%66,%67,%68,%69,%70,%71,%72,%73,%74,%75,%76,%77,%78,%79}, %80, %81, p, 1, 1, 0, 1;}"
    : "+f"(d[0]),"+f"(d[1]),"+f"(d[2]),"+f"(d[3]),"+f"(d[4]),"+f"(d[5]),"+f"(d[6]),"+f"(d[7]),"+f"(d[8]),"+f"(d[9]),"+f"(d[10]),"+f"(d[11]),"+f"(d[12]),"+f"(d[13]),"+f"(d[14]),"+f"(d[15]),"+f"(d[16]),"+f"(d[17]),"+f"(d[18]),"+f"(d[19]),"+f"(d[20]),"+f"(d[21]),"+f"(d[22]),"+f"(d[23]),"+f"(d[24]),"+f"(d[25]),"+f"(d[26]),"+f"(d[27]),"+f"(d[28]),"+f"(d[29]),"+f"(d[30]),"+f"(d[31]),"+f"(d[32]),"+f"(d[33]),"+f"(d[34]),"+f"(d[35]),"+f"(d[36]),"+f"(d[37]),"+f"(d[38]),"+f"(d[39]),"+f"(d[40]),"+f"(d[41]),"+f"(d[42]),"+f"(d[43]),"+f"(d[44]),"+f"(d[45]),"+f"(d[46]),"+f"(d[47]),"+f"(d[48]),"+f"(d[49]),"+f"(d[50]),"+f"(d[51]),"+f"(d[52]),"+f"(d[53]),"+f"(d[54]),"+f"(d[55]),"+f"(d[56]),"+f"(d[57]),"+f"(d[58]),"+f"(d[59]),"+f"(d[60]),"+f"(d[61]),"+f"(d[62]),"+f"(d[63]),"+f"(d[64]),"+f"(d[65]),"+f"(d[66]),"+f"(d[67]),"+f"(d[68]),"+f"(d[69]),"+f"(d[70]),"+f"(d[71]),"+f"(d[72]),"+f"(d[73]),"+f"(d[74]),"+f"(d[75]),"+f"(d[76]),"+f"(d[77]),"+f"(d[78]),"+f"(d[79])
    : "l"(da), "l"(db), "r"(sd));
}
__device__ __forceinline__ void wg_ss80_01(float* d, uint64_t da, uint64_t db, int sd) {
  asm volatile("{.reg .pred p; setp.ne.b32 p, %42, 0;\n"
    "wgmma.mma_async.sync.aligned.m64n80k16.f32.bf16.bf16 {%0,%1,%2,%3,%4,%5,%6,%7,%8,%9,%10,%11,%12,%13,%14,%15,%16,%17,%18,%19,%20,%21,%22,%23,%24,%25,%26,%27,%28,%29,%30,%31,%32,%33,%34,%35,%36,%37,%38,%39}, %40, %41, p, 1, 1, 0, 1;}"
    : "+f"(d[0]),"+f"(d[1]),"+f"(d[2]),"+f"(d[3]),"+f"(d[4]),"+f"(d[5]),"+f"(d[6]),"+f"(d[7]),"+f"(d[8]),"+f"(d[9]),"+f"(d[10]),"+f"(d[11]),"+f"(d[12]),"+f"(d[13]),"+f"(d[14]),"+f"(d[15]),"+f"(d[16]),"+f"(d[17]),"+f"(d[18]),"+f"(d[19]),"+f"(d[20]),"+f"(d[21]),"+f"(d[22]),"+f"(d[23]),"+f"(d[24]),"+f"(d[25]),"+f"(d[26]),"+f"(d[27]),"+f"(d[28]),"+f"(d[29]),"+f"(d[30]),"+f"(d[31]),"+f"(d[32]),"+f"(d[33]),"+f"(d[34]),"+f"(d[35]),"+f"(d[36]),"+f"(d[37]),"+f"(d[38]),"+f"(d[39])
    : "l"(da), "l"(db), "r"(sd));
}
__device__ __forceinline__ void wg_rs32_00(float* d, uint32_t a0, uint32_t a1, uint32_t a2, uint32_t a3, uint64_t db, int sd) {
  asm volatile("{.reg .pred p; setp.ne.b32 p, %21, 0;\n"
    "wgmma.mma_async.sync.aligned.m64n32k16.f32.bf16.bf16 {%0,%1,%2,%3,%4,%5,%6,%7,%8,%9,%10,%11,%12,%13,%14,%15}, {%16,%17,%18,%19}, %20, p, 1, 1, 0;}"
    : "+f"(d[0]),"+f"(d[1]),"+f"(d[2]),"+f"(d[3]),"+f"(d[4]),"+f"(d[5]),"+f"(d[6]),"+f"(d[7]),"+f"(d[8]),"+f"(d[9]),"+f"(d[10]),"+f"(d[11]),"+f"(d[12]),"+f"(d[13]),"+f"(d[14]),"+f"(d[15])
    : "r"(a0), "r"(a1), "r"(a2), "r"(a3), "l"(db), "r"(sd));
}
__device__ __forceinline__ void wg_rs64_00(float* d, uint32_t a0, uint32_t a1, uint32_t a2, uint32_t a3, uint64_t db, int sd) {
  asm volatile("{.reg .pred p; setp.ne.b32 p, %37, 0;\n"
    "wgmma.mma_async.sync.aligned.m64n64k16.f32.bf16.bf16 {%0,%1,%2,%3,%4,%5,%6,%7,%8,%9,%10,%11,%12,%13,%14,%15,%16,%17,%18,%19,%20,%21,%22,%23,%24,%25,%26,%27,%28,%29,%30,%31}, {%32,%33,%34,%35}, %36, p, 1, 1, 0;}"
    : "+f"(d[0]),"+f"(d[1]),"+f"(d[2]),"+f"(d[3]),"+f"(d[4]),"+f"(d[5]),"+f"(d[6]),"+f"(d[7]),"+f"(d[8]),"+f"(d[9]),"+f"(d[10]),"+f"(d[11]),"+f"(d[12]),"+f"(d[13]),"+f"(d[14]),"+f"(d[15]),"+f"(d[16]),"+f"(d[17]),"+f"(d[18]),"+f"(d[19]),"+f"(d[20]),"+f"(d[21]),"+f"(d[22]),"+f"(d[23]),"+f"(d[24]),"+f"(d[25]),"+f"(d[26]),"+f"(d[27]),"+f"(d[28]),"+f"(d[29]),"+f"(d[30]),"+f"(d[31])
    : "r"(a0), "r"(a1), "r"(a2), "r"(a3), "l"(db), "r"(sd));
}
__device__ __forceinline__ void wg_rs24_01(float* d, uint32_t a0, uint32_t a1, uint32_t a2, uint32_t a3, uint64_t db, int sd) {
  asm volatile("{.reg .pred p; setp.ne.b32 p, %17, 0;\n"
    "wgmma.mma_async.sync.aligned.m64n24k16.f32.bf16.bf16 {%0,%1,%2,%3,%4,%5,%6,%7,%8,%9,%10,%11}, {%12,%13,%14,%15}, %16, p, 1, 1, 1;}"
    : "+f"(d[0]),"+f"(d[1]),"+f"(d[2]),"+f"(d[3]),"+f"(d[4]),"+f"(d[5]),"+f"(d[6]),"+f"(d[7]),"+f"(d[8]),"+f"(d[9]),"+f"(d[10]),"+f"(d[11])
    : "r"(a0), "r"(a1), "r"(a2), "r"(a3), "l"(db), "r"(sd));
}

#define AB_POLY 0xae
__device__ __forceinline__ constexpr bool poly_group(int group) { return (AB_POLY >> (group & 7)) & 1; }

template <int V> struct Int { static constexpr int value = V; };

template <int NG>
__device__ __forceinline__ void ln_stats(const float4 (&v)[NG][5], uint32_t scratch, float (&mean)[NG], float (&rs)[NG]) {
  const int warp = threadIdx.x >> 5, lane = threadIdx.x & 31;
#pragma unroll
  for (int r = 0; r < NG; r++) {
    float s = 0.f, q = 0.f;
#pragma unroll
    for (int i = 0; i < 5; i++) s += (v[r][i].x + v[r][i].y) + (v[r][i].z + v[r][i].w);
    s += __shfl_xor_sync(~0u, s, 1); s += __shfl_xor_sync(~0u, s, 2);
    s *= 1.f / 80;
#pragma unroll
    for (int i = 0; i < 5; i++) {
      const float x = v[r][i].x - s, y = v[r][i].y - s, z = v[r][i].z - s, w = v[r][i].w - s;
      q += (x * x + y * y) + (z * z + w * w);
    }
    q += __shfl_xor_sync(~0u, q, 1); q += __shfl_xor_sync(~0u, q, 2);
    mean[r] = s; rs[r] = q;
  }
  bar_sync(1, 256);
  if ((lane & 3) == 0) {
#pragma unroll
    for (int r = 0; r < NG; r++) sts64f(scratch + r * 512 + lane * 16 + warp * 8, mean[r], rs[r]);
  }
  bar_sync(1, 256);
#pragma unroll
  for (int r = 0; r < NG; r++) {
    const float4 e = lds128f(scratch + r * 512 + lane * 16);
    float t = e.x + e.z;
    t += __shfl_xor_sync(~0u, t, 1); t += __shfl_xor_sync(~0u, t, 2);
    t *= 0.125f;
    float q = e.y + e.w + 80.f * ((e.x - t) * (e.x - t) + (e.z - t) * (e.z - t));
    q += __shfl_xor_sync(~0u, q, 1); q += __shfl_xor_sync(~0u, q, 2);
    mean[r] = t; rs[r] = rsqrtf(q * (1.f / DM) + 1e-5f);
  }
}

__device__ __forceinline__ void ln_store(const uint32_t (&w)[2][5][2], int tile, int u0, bool live = true) {
  const int lane = threadIdx.x & 31;
  uint32_t* xc = g_xc + ((tile >> 1) * 40 + u0) * 256 + (tile & 1) * 64 + lane;
#pragma unroll
  for (int i = 0; i < 20; i++) if (live) xc[(i >> 1) * 128 + (i & 1) * 32] = w[i & 1][i >> 2][i >> 1 & 1];
#pragma unroll
  for (int i = 0; i < 5; i++) {
    const int u = u0 + i;
    uint32_t* xn = g_xn + (((tile >> 3) * 20 + (u >> 1)) * 16 + (tile & 1) * 8 + (tile & 6)) * 128 + (u & 1) * 64 + lane;
#pragma unroll
    for (int r = 0; r < 2; r++) if (live) { xn[r * 128] = w[r][i][0]; xn[r * 128 + 32] = w[r][i][1]; }
  }
}
__device__ __forceinline__ void wait_count(const uint32_t* c, uint32_t n) {
  int spin = 0;
  while ((ld_acquire(c) & 0xffff) < n) { __nanosleep(32); spin_guard(spin); }
}

__device__ __forceinline__ uint8_t* pool_at(uint32_t off) {
  return reinterpret_cast<uint8_t*>((reinterpret_cast<uintptr_t>(g_pool) + 8191) & ~(uintptr_t)8191) + off; }
struct Weights { const uint8_t* w[4]; };
__device__ __forceinline__ void prefetch_weights(const Weights& p, int i) {
  if (blockIdx.x < 128) asm volatile("cp.async.bulk.prefetch.L2.global [%0], 61440;" :: "l"(p.w[i] + (size_t)blockIdx.x * 61440) : "memory");
}
__global__ void __launch_bounds__(384) first_kernel(const __nv_bfloat16* __restrict__ xin, const uint4* __restrict__ wb, const __grid_constant__ Weights wa) {
  __shared__ __align__(16) float scratch[256];
  __shared__ uint32_t lat[4];
  const int warp = threadIdx.x >> 5, lane = threadIdx.x & 31, cta = blockIdx.x;
  TRACE(0);
  pdl_launch();
  if (warp >= 8) {
    if (warp < 10 || cta < NSLOT) {
      uint32_t* q = reinterpret_cast<uint32_t*>(pool_at((warp < 10 ? NSLOT : cta) * 8192 + (warp & 1) * 4096)) + (warp < 10 ? (cta & 127) * 8 : 0);
      if (lane < 8) stg_strong32(q + lane, 0u);
      uint32_t best = ~0u;
      if (lane == 0) {
        for (int r = 0; r < FK_REP; r++) {
          uint32_t t0, t1, v;
          asm volatile("mov.u32 %0, %%clock;" : "=r"(t0) :: "memory");
          asm volatile("atom.relaxed.gpu.global.exch.b32 %0, [%1], 0;" : "=r"(v) : "l"(q) : "memory");
          asm volatile("{.reg .u32 t; add.u32 t, %1, 1; mov.u32 %0, %%clock; sub.u32 %0, %0, %1;}" : "=r"(t1) : "r"(__shfl_sync(1u, v, 0)) : "memory");
          best = min(best, t1 - t0);
        }
        lat[warp - 8] = best;
      }
    }
    __syncwarp();
    bar_sync(2, cta < 128 ? 384 : 128);
    if (threadIdx.x == 288) for (int i = 0; i < FK_PF; i++) prefetch_weights(wa, i);
    if (threadIdx.x == 256) {
      const int part = lat[0] < lat[1] ? 0 : 1;
      uint32_t smid; asm("mov.u32 %0, %%smid;" : "=r"(smid));
      g_smpart[smid & 255] = part;
      g_smclk[smid & 255] = clk32() - gtime() * 2;
      g_smuse[smid & 255] = 0;
      if (cta < NSLOT) g_orient[cta] = lat[2] < lat[3] ? part : 1 - part;
    }
  } else if (cta < 128) {
    float4 v[2][5];
#pragma unroll
    for (int r = 0; r < 2; r++)
#pragma unroll
      for (int i = 0; i < 5; i++) {
        const uint32_t* src = reinterpret_cast<const uint32_t*>(xin) + (cta * 16 + r * 8 + (lane >> 2)) * (DM / 2) + warp * 40 + i * 8 + (lane & 3);
        const uint32_t a = src[0], b = src[4];
        v[r][i] = make_float4(bf_lo(a), bf_hi(a), bf_lo(b), bf_hi(b));
      }
    uint4 w8[2];
#pragma unroll
    for (int i = 0; i < 2; i++) w8[i] = wb[cta * 400 + min(i * 256 + threadIdx.x, 399)];
    float mean[2], rs[2];
    ln_stats<2>(v, s2u(scratch), mean, rs);
    bar_sync(2, 384);
    ABT(2, 2);
    if (threadIdx.x < 128) g_stat[cta * 128 + threadIdx.x] = make_float2(0.f, 0.f);
#pragma unroll
    for (int i = 0; i < 10; i++) g_x[((cta * 2 + i / 5) * 40 + warp * 5 + i % 5) * 32 + lane] = pack4(v[i / 5][i % 5]);
    uint32_t w[2][5][2];
#pragma unroll
    for (int i = 0; i < 10; i++) {
      const float4 t = v[i / 5][i % 5];
      const float m = mean[i / 5], q = rs[i / 5];
      w[i / 5][i % 5][0] = pack2((t.x - m) * q, (t.y - m) * q); w[i / 5][i % 5][1] = pack2((t.z - m) * q, (t.w - m) * q);
    }
    ln_store(w, cta, warp * 5);
    ABT(2, 3);
#pragma unroll
    for (int i = 0; i < 2; i++) {
      const int e = cta * 400 + min(i * 256 + threadIdx.x, 399), k = e / 80, n = e - k * 80, cg = n / 10;
      g_wb[((cg * 80 + (k >> 3)) * 10 + n - cg * 10) * 8 + (k & 7)] = w8[i];
    }
  } else if (cta == 128) {
    g_bo[threadIdx.x] = 0;
  }
  TRACE(2);
}

struct ChainParams {
  CUtensorMap wq, wk, wv, wo;
  const __nv_bfloat16* mem0;
  uint8_t *pool, *kv;
  const uint32_t* xc;
  uint32_t* sync;
  int layer;
  int d0, d3, d1, d1b, d2, d2b, mode;
};
constexpr int CH_WQ = 0, CH_WO = 81920, CH_X = CH_WO + 86016, CH_M = CH_X + 20480, CH_KT = CH_X + 40960, CH_VT = CH_KT + 4096,
              CH_PS = CH_VT + 4096, CH_QK = CH_PS + 4096, CH_VP = CH_QK + 4096, CH_SX = CH_VP + 1024, CH_O = CH_SX + 2304, CH_ID = CH_O + 3072,
              CH_BAR = CH_ID + 512;
constexpr int CH_SMEM = CH_BAR + 256;
constexpr int CH_BASE = 1024;
#define CH_VK0 8
#define CH_VK1 20
#define CH_L0 4
#define CH_LR 4
#define NOX 0
#define CH_XA 1
#define CH_XB 4
#define CH_W1 3
#define CH_W2 17
#define CH_W3 26
#define CH_R2 8
#define CH_VA 16
#define CH_EX 1
#define CH_KD 0
#define CH_RP 1
#define CH_KF 10
#define CH_LO 0
#define CH_LR1 4
#define CH_KP 0
#define CH_KM 0
#define CH_WE 0
#define CH_SP 1
#define CH_KW 3
#define CH_RB 0
#define CH_RC 8
#define CH_D0 200
#define CH_D1 450
#define CH_D2 300
#define CH_R1 4
#define CH_TW 12
__device__ __forceinline__ uint32_t opaque(uint32_t x) { return __shfl_sync(~0u, x, threadIdx.x & 31); }
__device__ __forceinline__ uint32_t nz(uint32_t x) { uint32_t r; asm("max.u32 %0, %1, 1;" : "=r"(r) : "r"(x)); return r; }
__device__ __forceinline__ uint32_t pack_tag(float lo, float hi, uint32_t tag, uint32_t mask) {
  uint32_t r;
  asm("lop3.b32 %0, %1, %2, %3, 0xD8;" : "=r"(r) : "r"(pack2(lo, hi)), "r"(tag), "r"(mask));
  return r;
}
__device__ __forceinline__ uint32_t differ(uint32_t a, uint32_t b, uint32_t t) { uint32_t r; asm("lop3.b32 %0, %1, %2, %3, 0x7E;" : "=r"(r) : "r"(a), "r"(b), "r"(t)); return r; }
__device__ __forceinline__ void mbar_wait_hot(uint32_t bar, uint32_t ph) {
  uint32_t ok;
  asm volatile("{.reg .pred p; mbarrier.try_wait.parity.shared::cta.b64 p, [%1], %2; selp.u32 %0, 1, 0, p;}" : "=r"(ok) : "r"(bar), "r"(ph) : "memory");
  if (__builtin_expect(!ok, 0)) mbar_wait(bar, ph);
}
__device__ __forceinline__ bool elect() {
  uint32_t r; asm volatile("{.reg .pred p; elect.sync _|p, 0xffffffff; selp.u32 %0, 1, 0, p;}" : "=r"(r)); return r; }
__device__ __forceinline__ uint32_t or3(uint32_t a, uint32_t b, uint32_t c) { uint32_t r; asm("lop3.b32 %0, %1, %2, %3, 0xFE;" : "=r"(r) : "r"(a), "r"(b), "r"(c)); return r; }
__device__ __forceinline__ void pin() { pdl_launch(); }
__device__ __forceinline__ void mma16h(float* d, uint32_t a0, uint32_t a2, uint32_t b0, uint32_t b1) {
  asm volatile("{.reg .b32 u, v; mma.sync.aligned.m16n8k16.row.col.f32.bf16.bf16.f32 {%0,%1,%2,%3},{%4,u,%5,v},{%6,%7},{%0,%1,%2,%3};}"
               : "+f"(d[0]), "+f"(d[1]), "+f"(d[2]), "+f"(d[3]) : "r"(a0), "r"(a2), "r"(b0), "r"(b1)); }
__device__ __forceinline__ void mma8h(float* d, uint32_t a0, uint32_t b0) {
  asm volatile("{.reg .b32 u; mma.sync.aligned.m16n8k8.row.col.f32.bf16.bf16.f32 {%0,%1,%2,%3},{%4,u},{%5},{%0,%1,%2,%3};}"
               : "+f"(d[0]), "+f"(d[1]), "+f"(d[2]), "+f"(d[3]) : "r"(a0), "r"(b0)); }
__device__ __forceinline__ uint32_t absmax2(uint32_t a, uint32_t b) { uint32_t r; asm("max.xorsign.abs.bf16x2 %0, %1, %2;" : "=r"(r) : "r"(a), "r"(b)); return r; }
__device__ __forceinline__ void until(uint32_t t) { while ((int)(clk32() - t) < 0) {} }
__device__ __forceinline__ uint4 pack8(const float* d) { return make_uint4(pack2(d[0], d[1]), pack2(d[2], d[3]), pack2(d[4], d[5]), pack2(d[6], d[7])); }
__device__ __forceinline__ void add8(float* d, uint4 v) {
  d[0] += bf_lo(v.x); d[1] += bf_hi(v.x); d[2] += bf_lo(v.y); d[3] += bf_hi(v.y);
  d[4] += bf_lo(v.z); d[5] += bf_hi(v.z); d[6] += bf_lo(v.w); d[7] += bf_hi(v.w);
}

template <int WG>
__device__ __forceinline__ void chain_body(const ChainParams& p, const uint32_t wq, const uint32_t (&ak)[80], const uint32_t (&av)[80]) {
  const int tid = threadIdx.x & 127, t4 = __shfl_sync(~0u, tid >> 5, 0), lane = tid & 31;
  const int cta = blockIdx.x, h = cta / 3, j = cta - 3 * h;
  const uint32_t sb = mapa(CH_BASE, j);
  const uint32_t bWo = sb + CH_BAR, bWq = bWo + 8, bX = bWo + 16, bXA = bWo + 24, bXB = bWo + 32, bO = bWo + 40, bG = bWo + 48, bH = bWo + 96;
  uint32_t tw[4 * CH_TW];
  auto refill = [&]() {
#pragma unroll
    for (int k = 0; k < CH_TW; k++) ldsm4t(&tw[4 * k], wq + k * 2048);
  };
  const uint32_t wo = opaque((sb + CH_WO + (WG == 0 ? (t4 + (j == 2)) * 4096 : (j == 2 ? 0 : 24576) + t4 * 1024) + ((lane & 7) + (lane >> 4) * 8) * 64 +
                              ((((lane >> 3) & 1) ^ ((lane >> 1) & 3)) << 4)) ^ (WG == 1 && j == 2 ? 32 : 0));
  const uint32_t wo2 = opaque((wo ^ ((t4 & 1) * 32)) + (4 + (t4 >> 1) - t4) * 4096);
  const uint32_t l16 = opaque(sb + lane * 16);
  const uint32_t l8 = opaque(sb + t4 * 256 + lane * 8);
  const uint32_t lw = opaque(sb + t4 * 1024 + lane * 16);
  const uint32_t qs = opaque(sb + CH_QK + WG * 2048 + t4 * 512 + lane * 16);
  const uint32_t qa = opaque(sb + CH_QK + (lane >> 4) * 2048 + (lane & 15) * 16 + (WG == 0 ? t4 * 512 + 256 : t4 == 3 ? 1024 : 0));
  const uint32_t ka = opaque(t4 < 2 ? sb + CH_KT + t4 * 512 + lane * 16
                                    : sb + CH_QK + 256 + (t4 - 2) * 1024 + ((lane >> 3) & 1) * 2048 + (lane >> 4) * 128 + (lane & 7) * 16);
  const uint32_t l4 = opaque(sb + t4 * 256 + lane * 4);
  uint32_t pdst[1], pages = 0;
  auto line0 = [&](int i) { return 28 * j + (i < 4 ? 4 * t4 + i : 12 + 2 * t4 + i); };
  const uint32_t plane = opaque((lane >> 4) * 2048 + h * 64 + (lane & 15) * 4);
  if (WG == 0) {
    pages = __ballot_sync(~0u, lds32(sb + CH_O + line0(min(lane, 5)) * 4) & 4096);
  } else {
    pages = __ballot_sync(~0u, lds32(sb + CH_O + (80 + min(lane, 11)) * 4) & 4096);
    pdst[0] = opaque(lds32(sb + CH_O + (j == 0 ? 24 + t4 : 50 + 2 * j + (t4 & 1)) * 4) + plane);
  }
  const uint32_t role = lds32(sb + CH_O + NSLOT * 4), rsrc = lds32(sb + CH_O + role * 4), rdst = (80 + role / 20) * 8192 + role % 20 * 128;
  const uint32_t r1 = mapa(CH_BASE, j == 2 ? 0 : j + 1) - sb, r2 = mapa(CH_BASE, j == 0 ? 2 : j - 1) - sb;
  uint32_t tag = opaque(1);
  auto pool = [&](uint32_t off) { return p.pool + ((tag & 0xfffe) + off); };
  auto after = [&](uint32_t x) { return x & tag & 0xfffe; };
  auto kv = [&](int s, uint32_t a) { return p.kv + (a + ((cta * 2 * NSEG + s) * KV_BYTES - sb)); };
  auto pass = [&](float (&d)[16], const uint32_t (&a)[80], auto k0, auto k1) {
    const uint64_t db = mkdesc(CH_BASE + CH_X + WG * 20480, 512, 128, 0);
#pragma unroll
    for (int k = k0.value; k < k1.value; k++) wg_rs32_00(d, a[4 * k], a[4 * k + 1], a[4 * k + 2], a[4 * k + 3], db + k * 64, k);
    wg_commit();
  };
  auto dump = [&](float (&d)[16], uint32_t a) {
    reg_fence<16>(d);
    sts128(a, pack8(d)); sts128(a + 512, pack8(d + 8));
  };
  uint32_t pph = 0;
  auto tokens0 = [&](int s, auto k0) {
    float dk[16], dv[16];
    bar_sync(9, 256);
    wg_fence();
    pass(dk, ak, Int<0>(), Int<4>());
    const uint4 a0 = lds128(lw + CH_KT), a1 = lds128(lw + CH_KT + 512);
    pin();
    pass(dk, ak, Int<4>(), Int<20>());
    pass(dv, av, Int<0>(), Int<CH_VA>());
    pin();
    wg_wait<1>();
    reg_fence<16>(dk);
    add8(dk, a0); add8(dk + 8, a1);
    const uint4 w0 = pack8(dk), w1 = pack8(dk + 8);
    const uint4 b0 = lds128(lw + CH_VT), b1 = lds128(lw + CH_VT + 512);
    stsm4t(lw + CH_KT, w0.x, w0.z, w0.y, w0.w); stsm4t(lw + CH_KT + 512, w1.x, w1.z, w1.y, w1.w);
    if (CH_KP == 2) bar_arrive(7, 160);
    TM1(6);
    pin();
    if (CH_VA < 20) pass(dv, av, Int<CH_VA>(), Int<20>());
    pin();
#pragma unroll
    for (int k = k0.value; k < CH_TW; k++) ldsm4t(&tw[4 * k], wq + k * 2048);
    TM1(9);
    if (k0.value < CH_TW && t4 >= 2) { mbar_wait_hot(bH + t4 * 16 - 24 + (pph & 1) * 8, pph >> 1 & 1); pph++; }
    __syncwarp();
    wg_wait<0>();
    reg_fence<16>(dv);
    add8(dv, b0); add8(dv + 8, b1);
#pragma unroll
    for (int e = 0; e < 2; e++) { const uint4 v = pack8(dv + 8 * e); sts128(lw + CH_VT + e * 512, make_uint4(v.x, v.z, v.y, v.w)); }
  };
  auto publish_k = [&](int s) {
    if (t4 == CH_KW && elect()) { fence_async(); bulk_store(p.kv + (size_t)(cta * 2 * NSEG + s) * KV_BYTES, sb + CH_KT, 4096); bulk_commit(); }
    __syncwarp();
  };
  if (WG == 0) {
    mbar_wait(bXB, 0);
    tokens0(0, Int<CH_TW>());
  } else {
    const uint32_t* m0 = reinterpret_cast<const uint32_t*>(p.mem0) + (lane >> 2) * 320 + t4 * 80 + (lane & 3);
    uint32_t a[20];
#pragma unroll
    for (int i = 0; i < 20; i++) a[i] = m0[4 * i];
    pin();
    float dk[16], dv[16];
    mbar_wait(bXA, 0);
    wg_fence();
    pass(dk, ak, Int<0>(), Int<20>());
    pass(dv, av, Int<0>(), Int<20>());
    wg_wait<0>();
    dump(dk, lw + CH_KT);
    dump(dv, lw + CH_VT);
    bar_sync(9, 256);
    if (CH_KP == 2 && t4 == CH_KW) { bar_sync(7, 160); publish_k(0); }
#pragma unroll
    for (int i = 0; i < 20; i++) sts32(sb + CH_M + (t4 * 20 + i) * 128 + lane * 4, nz(transpose8(a[i])));
    __syncwarp();
    if (elect()) mbar_arrive(bG + t4 * 8);
  }
  PRO(8);
  mbar_wait(bWq, 0);
  refill();
  PRO(9);
  mbar_wait(bWo, 0);
  asm volatile("barrier.cluster.wait.aligned;" ::: "memory");
  PRO(10);
  auto load_x = [&](int s, int k0, int n, uint32_t bar) {
    if (!NOX && elect()) { mbar_expect(bar, n * 1024); bulk_load(sb + CH_X + k0 * 1024, p.xc + (s + 1) * 10240 + k0 * 256, n * 1024, bar); }
  };
  constexpr int VK = WG == 0 ? CH_VK0 : CH_VK1;
  uint32_t gph = 0;
  int st = 0;
  const uint32_t ca = opaque(sb + CH_M + t4 * 2560 + lane * 32 + (lane >> 2) * 4);
  auto project = [&](int s, uint32_t (&b)[40], float (&dv)[16], uint32_t (&kf)[16]) {
    float dq[4] = {}, dk[4] = {};
    uint32_t w[80];
#pragma unroll
    for (int i = 0; i < 4 * CH_TW; i++) w[i] = tw[i];
    constexpr int LR = WG == 1 ? CH_LR1 : CH_LR;
    auto load = [&](int n) {
      int c = 0;
#pragma unroll
      for (int i = 0; i < 10; i++) {
        if (i == CH_KF) {
#pragma unroll
          for (int q = 0; q < 4; q++)
            if (WG == 1 && c++ == n) ldsm4(&kf[4 * q], ka + q * 1024);
        }
        if (c++ == n) ldsm4t(&b[4 * i], l16 + CH_M + WG * 5120 + i * 512);
#pragma unroll
        for (int k = 2 * i; k < 2 * i + 2; k++)
          if (k >= CH_TW && c++ == n) ldsm4t(&w[4 * k], wq + k * 2048);
      }
#pragma unroll
      for (int i = 0; i < 4; i++)
        if (WG == 1 && CH_KF >= 10 && c++ == n) ldsm4(&kf[4 * i], ka + i * 1024);
    };
    if (WG == 1) {
      for (int n = 0;;) {
        mbar_wait(bG + t4 * 8, gph);
        TR(5, (clk32() & ~3u) | min(n, 3));
        gph ^= 1;
        if (__builtin_expect(!__any_sync(~0u, __vimin3_u32(lds32(ca), lds32(ca + 1024), lds32(ca + 1536)) == 0), 1)) break;
        if (elect()) {
          const int q = (st == 0 ? 8 : st * 4 - 4) + t4;
          mbar_expect(bG + t4 * 8, 2560);
          bulk_load(sb + CH_M + t4 * 2560, p.pool + ((80 + q) * 8192 + (pages >> q & 1) * 4096), 2560, bG + t4 * 8);
        }
        spin_guard(n);
      }
    }
    bar_sync(6, 256);
#pragma unroll
    for (int i = 0; i < CH_L0; i++) load(i);
    if (WG == 0 && CH_XB == 4 && s + 1 < NSEG) load_x(s, 5 * t4, 5, bXB);
    TM(0);
    TM1(11);
    if (WG == 1) TR(6, clk32());
#pragma unroll
    for (int k = 0; k < 20; k += 2) {
      if (k > 0) {
#pragma unroll
        for (int n = (k == 18 ? 40 : CH_L0 + k * LR / 4) - 1; n >= CH_L0 + (k - 2) * LR / 4; n--) { load(n); if (CH_LO) __syncwarp(); }
      }
      pin();
#pragma unroll
      for (int kk = k; kk < k + 2; kk++) {
        mma16(dk, ak[4 * kk], ak[4 * kk + 1], ak[4 * kk + 2], ak[4 * kk + 3], b[2 * kk], b[2 * kk + 1]);
        mma16(dq, w[4 * kk], w[4 * kk + 1], w[4 * kk + 2], w[4 * kk + 3], b[2 * kk], b[2 * kk + 1]);
        if (kk < VK) mma16(dv, av[4 * kk], av[4 * kk + 1], av[4 * kk + 2], av[4 * kk + 3], b[2 * kk], b[2 * kk + 1]);
      }
    }
    const float k2 = 0.07216878364870322f * 1.44269504089f;
    stsm4t(qs, pack2(dq[0] * k2, dq[1] * k2), pack2(dq[2] * k2, dq[3] * k2), pack2(dk[0], dk[1]), pack2(dk[2], dk[3]));
    TM(1);
  };
  static_assert(CH_VK1 == 20 && CH_KP == 0 && CH_XA > 0 && CH_XB > 0, "last step");
  constexpr int VC = VK == 20 ? 1 : WG == 0 ? 2 : 3;
  auto finish_v = [&](const uint32_t (&b)[40], float (&dv)[16]) {
#pragma unroll
    for (int kk = VK; kk < 20; kk++) mma16(dv + 4 * ((kk - VK) % VC), av[4 * kk], av[4 * kk + 1], av[4 * kk + 2], av[4 * kk + 3], b[2 * kk], b[2 * kk + 1]);
  };
  auto sum_v = [&](float (&dv)[16]) {
#pragma unroll
    for (int i = 4; i < 4 * VC; i++) dv[i & 3] += dv[i];
  };
  auto publish_km = [&](int s) {
    uint32_t a[4];
    ldsm4(a, qa);
    *reinterpret_cast<uint2*>(kv(s, l8) + KV_M) = make_uint2(hadd2(a[0], a[2]), hadd2(a[1], a[3]));
  };
  auto memory_v = [&](uint2 x, const float (&dv)[16]) {
    return make_uint2(pack2(dv[0] + bf_lo(x.x), dv[1] + bf_hi(x.x)), pack2(dv[2] + bf_lo(x.y), dv[3] + bf_hi(x.y)));
  };
  auto publish_v = [&](int s, const uint4 (&v)[2], uint2 vm) {
#pragma unroll
    for (int e = 0; e < 2; e++) reinterpret_cast<uint4*>(kv(s, lw) + KV_V)[e * 32] = v[e];
    *reinterpret_cast<uint2*>(kv(s, l8) + KV_V + KV_M) = vm;
  };
#pragma unroll 1
  for (int s = 0;; s++) {
    float dv[16] = {};
    uint32_t b[40], kf[16];
    project(s, b, dv, kf);
    if (WG == 0) {
      bar_sync(1, 256);
      if (CH_XA == 0) load_x(s, 20 + 5 * t4, 5, bXA);
      if (CH_XB == 0) load_x(s, 5 * t4, 5, bXB);
      pin();
      finish_v(b, dv);
      sum_v(dv);
      sts64(l8 + CH_VP, pack2(dv[0], dv[1]), pack2(dv[2], dv[3]));
      if (s == NSEG - 1) {
        bar_arrive(10, 256);
        publish_k(s);
        publish_km(s);
        bulk_wait<0>();
        fence_async_global();
        bar_sync(2, 256);
        if (tid == 0) red_release(p.sync + 15 * 8 + 4, 1);
        break;
      }
      __syncwarp();
      if (elect()) mbar_arrive(bX);
      if (CH_XA == 1) load_x(s, 20 + 5 * t4, 5, bXA);
      if (CH_XB == 1) load_x(s, 5 * t4, 5, bXB);
      uint32_t w[144];
      auto wload = [&](int i) { ldsm4t(&w[4 * i], (i % 3 == 0 ? wo : i % 3 == 1 ? wo ^ 32 : wo2) + i / 12 * 28672 + i / 3 % 4 * 1024); };
      TM(3);
      if (CH_KP == 0) publish_k(s);
#pragma unroll
      for (int i = 0; i < CH_W1; i++) wload(i);
      bar_sync(10, 256);
      uint32_t km[4];
      ldsm4(km, qa);
      pin();
#pragma unroll
      for (int i = CH_W1; i < CH_W2; i++) wload(i);
      pin();
      const uint2 kms = make_uint2(hadd2(km[0], km[2]), hadd2(km[1], km[3]));
      if (CH_KM == 0) *reinterpret_cast<uint2*>(kv(s, l8) + KV_M) = kms;
      if (CH_KP == 0) bulk_wait_read<0>();
      if (CH_XA == 2) load_x(s, 20 + 5 * t4, 5, bXA);
      if (CH_XB == 2) load_x(s, 5 * t4, 5, bXB);
      bar_sync(2, 256);
      {
        float y[3][4] = {};
        uint32_t ob[24];
        ldsm4(&ob[0], l16 + CH_O + 1024); ldsm4(&ob[4], l16 + CH_O + 1536);
        TM(7);
        auto step = [&](int i) {
          const int k = i / 3;
          mma16(y[i % 3], w[4 * i], w[4 * i + 1], w[4 * i + 2], w[4 * i + 3], ob[2 * k], ob[2 * k + 1]);
        };
#pragma unroll
        for (int i = 0; i < 12; i++) {
          step(i);
          if (i >= 12 - (CH_W3 - CH_W2)) wload(CH_W3 - 12 + i);
          if (i % 3 == 2) pin();
        }
        if (CH_XB == 3) load_x(s, 5 * t4, 5, bXB);
        if (CH_KM == 1) *reinterpret_cast<uint2*>(kv(s, l8) + KV_M) = kms;
        pin();
        mbar_wait(bO, s & 1);
        TM(4);
        ldsm4(&ob[8], l16 + CH_O); ldsm4(&ob[12], l16 + CH_O + 512);
        pin();
        float2 inv;
        uint8_t* dst[6];
        uint32_t mask;
#pragma unroll
        for (int i = 12; i < 36; i++) {
          step(i);
          const int n = CH_W3 + i - 13, m = n - (n > 30);
          if (i == 12) ldsm4(&ob[16], l16 + after(w[4 * CH_W3 - 1] | w[4 * CH_W3 - 5] | w[4 * CH_W3 - 9] | ob[8]) + CH_O + 2048);
          else if (n == 30) ldsm4(&ob[20], l16 + CH_O + 2560);
          else if (m < 36) wload(m);
          else if (m == 36) inv = lds64f((l8 & ~0xe0u) + CH_VP);
          if (i == 26) mask = ((l16 ^ tag) & 48) == 0;
          if (i >= 27 && i < 33) dst[i - 27] = pool(line0(i - 27) * 8192 + (pages >> (i - 27) & 1) * 4096) + plane;
          if (i % 3 == 2) pin();
        }
#pragma unroll
        for (int k = 0; k < CH_R1; k++) ldsm4t(&tw[4 * k], wq + k * 2048);
        pin();
#pragma unroll
        for (int i = 0; i < 6; i++) stg_strong32(dst[i], pack_tag(y[i >> 1][2 * (i & 1)] * inv.x, y[i >> 1][2 * (i & 1) + 1] * inv.y, tag, mask));
        TM(8);
        TR(0, clk32());
        bar_arrive(5, 256);
        pin();
      }
      const uint32_t t0 = clk32();
      auto refill2 = [&]() {
#pragma unroll
        for (int k = CH_R1; k < CH_R2; k++) ldsm4t(&tw[4 * k], wq + k * 2048);
      };
      if (CH_RP == 0) refill2();
      const uint32_t ln = (l16 ^ tag) >> 4 & 31;
      if (t4 >= 2) {
        const uint32_t bP = bH + t4 * 16 - 24, ps = CH_PS + (t4 & 1) * 4096;
        auto fetch = [&](uint32_t k) {
          if (elect()) { mbar_expect(bP + (k & 1) * 8, 2048); bulk_load(sb + ps + (k & 1) * 2048, p.pool + (rsrc + (t4 & 1) * 2048), 2048, bP + (k & 1) * 8); }
        };
        until(t0 + CH_D0);
        fetch(pph);
        if (CH_RP == 2) refill2();
        if (!NOX) mbar_wait_hot(bXB, (s + 1) & 1);
        const uint32_t want = (tag & 1) * 0x10001, chk = opaque(ln < 4 ? 0x10001 : 0);
        uint4 sel;
        sel.x = opaque((ln >> 3) != (ln & 1) ? 0 : ln & 4 ? 0x3f800000u : 0x00003f80u);
        sel.z = opaque(sel.x); sel.y = opaque(ln); sel.w = opaque(ln + 1);
        uint8_t* mdst = p.pool + opaque(st * 32768 + rdst + (t4 & 1) * 64 + ln * 4);
        until(t0 + CH_D1);
        fetch(pph + 1);
        TM(5);
        if (CH_RP == 1) refill2();
        int n = 0;
        uint32_t u[16];
        float y[4][4];
        auto sum = [&]() {
#pragma unroll
          for (int i = 0; i < 16; i++) y[i >> 2][i & 3] = 0.f;
#pragma unroll
          for (int i = 0; i < 8; i++) mma16(y[i & 3], sel.x, sel.y, sel.z, sel.w, u[2 * i], u[2 * i + 1]);
        };
        auto check = [&](auto spec) {
          mbar_wait(bP + (pph & 1) * 8, pph >> 1 & 1);
          TM(14);
          TR(2, clk32());
#pragma unroll
          for (int i = 0; i < 4; i++) ldsm4t(&u[4 * i], l16 + (ps + (pph & 1) * 2048) + i * 512);
          pph++;
          if (spec.value) { pin(); sum(); }
          uint32_t bad = 0;
#pragma unroll
          for (int i = 0; i < 4; i++) bad = or3(bad, differ(u[4 * i], u[4 * i + 1], want), differ(u[4 * i + 2], u[4 * i + 3], want));
          return __any_sync(~0u, bad & chk);
        };
        if (CH_SP) {
          if (check(Int<0>())) {
            do { fetch(pph + 1); spin_guard(n); } while (check(Int<1>()));
          } else {
            sum();
          }
        } else {
          while (check(Int<0>())) { fetch(pph + 1); spin_guard(n); }
          sum();
        }
        TR(1, t0 + (n ? CH_D1 : CH_D0));
        TM(15);
        const uint32_t w = nz(pack2((y[0][0] + y[1][0]) + (y[2][0] + y[3][0]), (y[0][1] + y[1][1]) + (y[2][1] + y[3][1])));
        if (ln < 16) { stg_strong32(mdst, w); stg_strong32(mdst + 4096, w); }
        TMV(12, 32, n);
        TR(3, (clk32() & ~3u) | min(n, 3));
      } else {
        if (CH_RP) refill2();
        if (!NOX) mbar_wait_hot(bXB, (s + 1) & 1);
        stg_strong32(p.pool + ((st == 2 ? 0 : st + 1) * 32768 + rdst + t4 * 4096) + ln * 4, 0u);
        if (t4 == 0 && cta < 40 && s + 4 < NSEG && elect())
          asm volatile("cp.async.bulk.prefetch.L2.global [%0], 1024;" :: "l"(p.xc + (s + 4) * 10240 + cta * 256) : "memory");
        if (t4 == 1 && (s & 3) == 0 && s > 0 && elect()) red_relaxed(p.sync + 2 * s - 4, 1);
        if (t4 == 1 && s == NSEG - 3 && cta == 95 && elect()) red_relaxed(p.sync + 2 * s + 2, 0x10000);
      }
      TM(10);
      bar_arrive(8, 256);
      tokens0(s + 1, Int<CH_R2>());
      TM(2);
      TR(7, clk32());
    } else {
      if (s == NSEG - 1) {
        bar_arrive(1, 256);
        const uint4 v[2] = {lds128(lw + CH_VT), lds128(lw + CH_VT + 512)};
        bar_sync(10, 256);
        publish_v(s, v, memory_v(lds64(l8 + CH_VP), dv));
        bar_arrive(2, 256);
        break;
      }
      const uint32_t xo = l4 + (CH_SX - (t4 == 3 ? 128 : 0)), x1 = xo + (r1 + 768 + min(t4, 2) * 256), x2 = xo + (r2 + 1024 + min(t4, 2) * 256);
      if (t4 < 2) {
        float ds[4][4] = {};
        uint32_t q[16];
        asm volatile("bar.sync 1, 256;" ::: "memory");
#pragma unroll
        for (int k = 0; k < 4; k++) ldsm4(&q[4 * k], qa + k * 512);
        pin();
        if (VK < 20) { finish_v(b, dv); pin(); }
#pragma unroll
        for (int k = 0; k < 4; k++) {
          mma16(ds[k & 1], kf[4 * k], kf[4 * k + 1], kf[4 * k + 2], kf[4 * k + 3], q[4 * k], q[4 * k + 1]);
          mma16(ds[2 + (k & 1)], kf[4 * k], kf[4 * k + 1], kf[4 * k + 2], kf[4 * k + 3], q[4 * k + 2], q[4 * k + 3]);
        }
        float t[4];
#pragma unroll
        for (int i = 0; i < 4; i++) t[i] = (ds[0][i] + ds[2][i]) + (ds[1][i] + ds[3][i]);
        const uint32_t w0 = pack2(t[0], t[1]), w1 = pack2(t[2], t[3]);
        st_async32(x1, w0, bX + r1); st_async32(x2, w0, bX + r2);
        st_async32(x1 + 128, w1, bX + r1); st_async32(x2 + 128, w1, bX + r2);
        sts32(xo, w0); sts32(xo + 128, w1);
      } else {
        float ds[4][4] = {};
        uint32_t q0[4], q1[4], a0[4], a1[4];
        asm volatile("bar.sync 1, 256; " ::: "memory");
        ldsm4(a0, ka); ldsm4(q0, qa); ldsm4(a1, ka + 512); ldsm4(q1, qa + 512);
        pin();
        if (VK < 20) { finish_v(b, dv); pin(); }
        mma16(ds[0], a0[0], a0[1], a0[2], a0[3], q0[0], q0[1]);
        mma16(ds[1], a0[0], a0[1], a0[2], a0[3], q0[2], q0[3]);
        mma16(ds[2], a1[0], a1[1], a1[2], a1[3], q1[0], q1[1]);
        mma16(ds[3], a1[0], a1[1], a1[2], a1[3], q1[2], q1[3]);
        float t[2];
#pragma unroll
        for (int i = 0; i < 2; i++)
          t[i] = ((ds[0][i] + ds[0][i + 2]) + (ds[1][i] + ds[1][i + 2])) + ((ds[2][i] + ds[2][i + 2]) + (ds[3][i] + ds[3][i + 2]));
        const uint32_t w0 = pack2(t[0], t[1]);
        st_async32(x1, w0, bX + r1);
        st_async32(x2, w0, bX + r2);
        sts32(xo, w0);
      }
      TM(3);
      const uint4 id = lds128(l16 + CH_ID);
      float sc[3][4] = {};
      uint4 v[2];
      sum_v(dv);
      bar_sync(3, 128);
      uint32_t r[12], wd[12], we[12] = {};
      ldsm4(&r[0], l16 + CH_SX); ldsm2(&r[4], l16 + CH_SX + 512);
      pin();
      v[0] = lds128(lw + CH_VT); v[1] = lds128(lw + CH_VT + 512);
#pragma unroll
      for (int u = 0; u < 3; u++) ldsm4t(&wd[4 * u], wo + u * 28672);
      if (CH_WE && j == 0) {
#pragma unroll
        for (int u = 0; u < 3; u++) ldsm4t(&we[4 * u], (wo ^ 32) + u * 28672);
      }
      pin();
#pragma unroll
      for (int q = 0; q < 3; q++) mma16(sc[q], id.x, id.y, id.z, id.w, r[2 * q], r[2 * q + 1]);
      uint32_t big = absmax2(absmax2(absmax2(r[0], r[1]), absmax2(r[2], r[3])), absmax2(r[4], r[5]));
      const uint32_t oa1 = l4 + (r1 + CH_O), oa2 = l4 + (r2 + CH_O + 2048), ones = 0x3f803f80u;
      mbar_wait_hot(bX, s & 1);
      TM(4);
      ldsm4(&r[0], l16 + CH_SX + 768); ldsm4(&r[8], l16 + CH_SX + 1792); ldsm4(&r[4], l16 + CH_SX + 1280);
      const uint2 vp = lds64(l8 + CH_VP);
      bar_arrive(10, 256);
      pin();
      {
        float sd[3][4] = {};
#pragma unroll
        for (int i = 0; i < 3; i++) {
          const int q = i == 0 ? 0 : 3 - i;
          mma16(sc[q], id.x, id.y, id.z, id.w, r[4 * q], r[4 * q + 1]);
          mma16(sd[q], id.x, id.y, id.z, id.w, r[4 * q + 2], r[4 * q + 3]);
          big = absmax2(big, absmax2(absmax2(r[4 * q], r[4 * q + 1]), absmax2(r[4 * q + 2], r[4 * q + 3])));
        }
#pragma unroll
        for (int i = 0; i < 12; i++) sc[i >> 2][i & 3] += sd[i >> 2][i & 3];
      }
      const bool redo = __any_sync(~0u, (absmax2(big, big << 16) & 0x7fff0000u) >= 0x41800000u);
      const uint2 vm = memory_v(vp, dv);
      sc[2][0] += sc[2][2]; sc[2][1] += sc[2][3];
      float l[4], o[2][4];
      uint32_t p3, p4;
      auto attend = [&]() {
#pragma unroll
        for (int i = 0; i < 4; i++) l[i] = o[0][i] = o[1][i] = 0.f;
        const uint32_t p1 = pack2(ex2(sc[0][0]), ex2(sc[0][1])), p2 = pack2(ex2(sc[0][2]), ex2(sc[0][3]));
        mma16h(o[0], p1, p2, v[0].x, v[0].y);
        mma16h(o[1], p1, p2, v[0].z, v[0].w);
        mma16h(l, p1, p2, ones, ones);
        const uint32_t p0 = pack2(ex2(sc[2][0]), ex2(sc[2][1]));
        mma8h(o[0], p0, vm.x);
        mma8h(o[1], p0, vm.y);
        mma8h(l, p0, ones);
        p3 = pack2(ex2(sc[1][0]), ex2(sc[1][1])); p4 = pack2(ex2(sc[1][2]), ex2(sc[1][3]));
        mma16h(o[0], p3, p4, v[1].x, v[1].y);
        mma16h(o[1], p3, p4, v[1].z, v[1].w);
      };
      attend();
      if (__builtin_expect(redo, 0)) {
        float mx = fmaxf(sc[2][0], sc[2][1]);
#pragma unroll
        for (int i = 0; i < 4; i++) mx = fmaxf(mx, fmaxf(sc[0][i], sc[1][i]));
        mx = fmaxf(mx, __shfl_xor_sync(~0u, mx, 1));
        mx = fmaxf(mx, __shfl_xor_sync(~0u, mx, 2));
#pragma unroll
        for (int i = 0; i < 4; i++) { sc[0][i] -= mx; sc[1][i] -= mx; }
        sc[2][0] -= mx; sc[2][1] -= mx;
        attend();
      }
      const uint32_t o0 = pack2(o[0][0], o[0][1]), o1 = pack2(o[1][0], o[1][1]);
      st_async32(oa1, o0, bO + r1); st_async32(oa2, o0, bO + r2);
      st_async32(oa1 + 128, o1, bO + r1); st_async32(oa2 + 128, o1, bO + r2);
      sts32(l4 + CH_O + 1024, o0); sts32(l4 + CH_O + 1152, o1);
      bar_arrive(2, 256);
      pin();
      TM(6);
      mma16h(l, p3, p4, ones, ones);
      float inv;
      asm("rcp.approx.ftz.f32 %0, %1;" : "=f"(inv) : "f"(l[0]));
      sts32((l8 & ~0xffu) + (lane & 28) + CH_VP, __float_as_uint(inv));
      __syncwarp();
      if (elect()) mbar_arrive(bO);
      {
        float z[2][4] = {}, y[2][4] = {};
        mma16(z[0], wd[0], wd[1], wd[2], wd[3], o0, o1);
        if (j == 0) {
#pragma unroll
          for (int u = 0; u < 3; u++) if (!CH_WE) ldsm4t(&we[4 * u], (wo ^ 32) + u * 28672);
          mma16(y[0], we[0], we[1], we[2], we[3], o0, o1);
        }
        const float2 iv = lds64f((l8 & ~0xe0u) + CH_VP);
        uint8_t* dst = pool(pdst[0]);
        const uint32_t mask = ((l16 ^ tag) & 48) == 0;
        const uint32_t oa = qa + ((tag & 0xfffe) + CH_O - CH_QK + t4 * 256 - (t4 == 3 ? 1024 : 0));
        const uint32_t za = l16 + ((tag & 0xfffe) + (t4 >> 1) * 512 + (t4 & 1) * 8);
        pin();
        mbar_wait(bO, s & 1);
        uint32_t a[4];
        ldsm4(a, oa);
        mma16(z[0], wd[4], wd[5], wd[6], wd[7], a[0], a[1]);
        mma16(z[1], wd[8], wd[9], wd[10], wd[11], a[2], a[3]);
        if (j == 0) {
          mma16(y[0], we[4], we[5], we[6], we[7], a[0], a[1]);
          mma16(y[1], we[8], we[9], we[10], we[11], a[2], a[3]);
          sts128f(lw + CH_VT + 512, y[0][0] + y[1][0], y[0][1] + y[1][1], y[0][2] + y[1][2], y[0][3] + y[1][3]);
        }
        sts128f(lw + CH_VT, z[0][0] + z[1][0], z[0][1] + z[1][1], z[0][2] + z[1][2], z[0][3] + z[1][3]);
        bar_sync(3, 128);
        if (j == 0 || t4 < 2) {
          float2 q[4];
#pragma unroll
          for (int i = 0; i < 4; i++) q[i] = lds64f(za + CH_VT + i * 1024);
          stg_strong32(dst, pack_tag(((q[0].x + q[1].x) + (q[2].x + q[3].x)) * iv.x, ((q[0].y + q[1].y) + (q[2].y + q[3].y)) * iv.y, tag, mask));
        }
      }
      TM(2);
      if (!NOX) mbar_wait_hot(bXA, (s + 1) & 1);
      if (CH_KP == 2) bulk_wait_read<0>();
      float dk[16], dw[16];
      bar_sync(5, 256);
      wg_fence();
      pass(dk, ak, Int<0>(), Int<20>());
      pass(dw, av, Int<0>(), Int<20>());
      TM(5);
      pin();
      if (CH_EX == 0) publish_v(s, v, vm);
      if (elect()) {
        mbar_expect(bG + t4 * 8, 2560);
        if (t4 == 1 && s + 2 < NSEG) { mbar_expect(bX, 1536); mbar_expect(bO, 2048); }
      }
      if (CH_KD == 0) { wg_wait<1>(); dump(dk, lw + CH_KT); }
      wg_wait<0>();
      if (CH_KD == 1) dump(dk, lw + CH_KT);
      TM(7);
      dump(dw, lw + CH_VT);
      bar_arrive(9, 256);
      pin();
#pragma unroll
      for (int k = 0; k < CH_RB; k++) ldsm4t(&tw[4 * k], wq + k * 2048);
      if (t4 < 2) {
        if (CH_EX == 2) { publish_v(s, v, vm); pin(); }
#pragma unroll
        for (int k = CH_RB; k < CH_RC; k++) ldsm4t(&tw[4 * k], wq + k * 2048);
        const int q = t4 ? 3 : j, o = t4 ? j * 896 : 0;
        const uint8_t* src = p.pool + ((80 + st * 4 + q) * 8192 + (pages >> (st * 4 + q) & 1) * 4096 + o);
        asm volatile("bar.sync 8, 256;" ::: "memory");
        const uint32_t t1 = clk32() + CH_D2;
        if (CH_EX == 1) publish_v(s, v, vm);
        auto fetch = [&](auto n) {
          mbar_wait(bH, s & 1);
          until(t1);
          TR(4, clk32());
          if (elect())
            asm volatile("cp.async.bulk.shared::cluster.global.mbarrier::complete_tx::bytes.multicast::cluster [%0], [%1], %2, [%3], 7;"
                         :: "r"(sb + CH_M + q * 2560 + o), "l"(src), "n"(n.value), "r"(bG + q * 8) : "memory");
        };
        if (!t4) fetch(Int<2560>()); else if (j == 2) fetch(Int<768>()); else fetch(Int<896>());
      } else {
        asm volatile("bar.sync 8, 256; " ::: "memory");
        if (elect()) asm volatile("mbarrier.arrive.relaxed.cluster.shared::cluster.b64 _, [%0];" :: "r"(bH + (t4 == 2 ? r1 : r2)) : "memory");
        pin();
        if (CH_EX) publish_v(s, v, vm);
#pragma unroll
        for (int k = CH_RB; k < CH_RC; k++) ldsm4t(&tw[4 * k], wq + k * 2048);
      }
      TM(9);
      pin();
#pragma unroll
      for (int k = CH_RC; k < CH_TW; k++) ldsm4t(&tw[4 * k], wq + k * 2048);
      if (CH_KP == 2 && t4 == CH_KW) { bar_sync(7, 160); publish_k(s + 1); }
      TM(10);
    }
    if (++st == 3) st = 0;
    tag ^= 0x10001;
  }
}

__global__ void __launch_bounds__(256, 1) chain_kernel(const __grid_constant__ ChainParams p) {
  extern __shared__ __align__(1024) uint8_t smem_raw[];
  const uint32_t sb = s2u(smem_raw);
  const int tid = threadIdx.x, warp = __shfl_sync(~0u, tid >> 5, 0), lane = tid & 31;
  const int cta = blockIdx.x, h = cta / 3, j = cta - 3 * h, colbase = cta * 64;
  const uint32_t bWo = sb + CH_BAR, bWq = bWo + 8, bXA = bWo + 24, bWk = bWo + 80, bWv = bWo + 88;
  uint32_t smid; asm("mov.u32 %0, %%smid;" : "=r"(smid));
  PRO(0);
  if (sb != mapa(CH_BASE, j)) __trap();
  uint32_t entry = 0;
  auto place = [&]() {
    const int i = tid - 128;
    if (i >= 0 && i <= NSLOT) {
      const uint32_t side = ldg_strong32(g_smpart + (smid & 255));
      if (i < NSLOT) {
        entry = i * 8192 + (ldg_strong32(g_orient + i) == (i < 80 ? i & 1 : side) ? 0 : 4096);
      } else {
        entry = 2 * (atomicAdd(g_bo + p.layer * 128 + 1, 1 << 8 * side) >> 8 * side & 255) + side;
      }
    }
    __syncwarp();
  };
  if (warp == 2 && lane < 4) asm volatile("prefetch.tensormap [%0];" :: "l"(&p.wq + lane) : "memory");
  if (p.layer) place();
  if (warp == 0 && elect()) {
#pragma unroll 1
    for (int i = 0; i < 17; i++) mbar_init(bWo + 8 * i, i == 2 || i == 5 ? 5 : i == 3 || i == 4 ? 4 : i == 12 ? 2 : 1);
    asm volatile("fence.mbarrier_init.release.cluster;" ::: "memory");
    mbar_expect(bWk, 81920);
    tma_load3<(WEF & 1) != 0>(sb + CH_WQ, &p.wk, colbase, 0, bWk);
    mbar_expect(bWv, 81920);
    tma_load3<(WEF & 1) != 0>(sb + CH_WO, &p.wv, colbase, 0, bWv);
    mbar_expect(bWo + 16, 1536);
    mbar_expect(bWo + 40, 2048);
    mbar_expect(bWo, 86016); mbar_expect(bWq, 81920);
#pragma unroll 1
    for (int i = 0; i < 8; i++) mbar_expect(bXA + 8 * (i & 1), 5120);
  }
  if (warp == 1) {
    const uint32_t id = (lane >> 3) == (lane & 3) ? ((lane & 4) ? 0x3f800000u : 0x00003f80u) : 0u;
    sts128(sb + CH_ID + lane * 16, make_uint4(id, 0, 0, id));
  }
  __syncthreads();
  asm volatile("barrier.cluster.arrive.relaxed.aligned;" ::: "memory");
  uint32_t ak[80], av[80];
  const uint32_t wq = opaque(sb + CH_WQ + ((warp >> 2) * 320 + (lane & 7) + (lane >> 4) * 8) * 128 + (((2 * (warp & 3) + ((lane >> 3) & 1)) ^ (lane & 7)) << 4));
  pdl_wait();
  if (tid == 32) stg_strong32(g_smuse + (smid & 255), p.layer + 1);
  pdl_launch();
  PRO(1);
  if (warp == 0 && elect()) {
    bulk_load(sb + CH_X + 20480, p.xc + 5120, 20480, bXA);
    bulk_load(sb + CH_X, p.xc, 20480, bXA + 8);
  }
  if (!p.layer) place();
  __syncwarp();
  PRO(2);
  mbar_wait(bWk, 0);
  PRO(3);
#pragma unroll
  for (int k = 0; k < 20; k++) ldsm4t(&ak[4 * k], wq + k * 2048);
  bar_sync(6, 256);
  if (warp == 0 && elect()) tma_load3<(WEF & 2) != 0>(sb + CH_WQ, &p.wq, colbase, 0, bWq);
  __syncwarp();
  PRO(4);
  mbar_wait(bWv, 0);
  PRO(5);
#pragma unroll
  for (int k = 0; k < 20; k++) ldsm4t(&av[4 * k], wq + CH_WO + k * 2048);
  bar_sync(6, 256);
  PRO(6);
  if (warp >= 5 && elect()) tma_load3<(WEF & 2) != 0>(sb + CH_WO + (warp - 5) * 28672, &p.wo, j == 0 ? 0 : 32 + j * 192, h * 192 + (j + 8 - warp) % 3 * 64, bWo);
  if (tid == 128 + NSLOT && entry >= 80) {
    uint32_t c;
    int n = 0;
    do { c = ldg_strong32(g_bo + p.layer * 128 + 1); spin_guard(n); } while ((c & 255) + (c >> 8) < 96);
    const uint32_t other = (c >> 8 * (~entry & 1) & 255) + (entry >> 1) - 40;
    entry = other < 40 ? 2 * other + (~entry & 1) : entry % 80;
  }
  if (tid >= 128 && tid <= 128 + NSLOT) sts32(sb + CH_O + (tid - 128) * 4, entry);
  PRO(7);
  __syncthreads();
  if (__shfl_sync(~0u, tid >> 7, 0) == 0) chain_body<0>(p, wq, ak, av); else chain_body<1>(p, wq, ak, av);
}

struct PostParams { CUtensorMap wq, wo, wb, wo2, wb2; int gap, share, layer, look, gap2, pol; };
constexpr int PS = 8, PB = 28672;
constexpr int OP_SMEM = PS * PB + 512 + 2048;
enum { IT_ATT = 0, IT_OP = 1, IT_FIN = 2, IT_BQ = 3, IT_Q = 4 };

__device__ __forceinline__ uint32_t item_count(int type, int b) {
  return type == IT_ATT ? 32 : type == IT_OP ? op_split(b) * (b < OP_160 ? 2 : 4) : type == IT_FIN ? 16 : b < BQ_160 ? 6 : b < BQ_80 ? 12 : 24; }
__device__ __forceinline__ uint32_t item_need(int type, int b) { return type == IT_ATT ? 96 : item_count(type - 1, b); }

struct Ring {
  uint32_t sb, bars; int st; uint32_t ph;
  __device__ __forceinline__ uint32_t wait() const { mbar_wait(bars + 8 * st, ph); return sb + st * PB; }
  __device__ __forceinline__ void next() { if (++st == PS) { st = 0; ph ^= 1; } }
  __device__ __forceinline__ void release(int s) const { if ((threadIdx.x & 31) == 0) mbar_arrive(bars + 8 * (PS + s)); }
  __device__ __forceinline__ void pop() { __syncwarp(); release(st); next(); }
};

template <int N>
__device__ __forceinline__ void gemm_item(Ring& r, float* d, int nst, uint32_t go, int go_at) {
  int prev = 0;
#pragma unroll 1
  for (int kb = 0; kb < nst; kb++) {
    const uint32_t base = r.wait();
    const uint64_t da = mkdesc(base + (threadIdx.x >> 7) * 4096, 128, 512, 0), db = mkdesc(base + 8192, 4096, 1024, 1);
    wg_fence();
#pragma unroll
    for (int kk = 0; kk < 2; kk++) {
      if (N == 80) wg_ss80_01(d, da + kk * 16, db + kk * 128, (kb | kk) != 0);
      if (N == 160) wg_ss160_01(d, da + kk * 16, db + kk * 128, (kb | kk) != 0);
      if (N >= 192) wg_ss192_01(d, da + kk * 16, db + kk * 128, (kb | kk) != 0);
      if (N == 320) wg_ss128_01(d + 96, da + kk * 16, db + kk * 128 + 3 * 256, (kb | kk) != 0);
    }
    wg_commit();
    if (kb == go_at && threadIdx.x == 0) mbar_arrive(go);
    if (kb > 0) { wg_wait<1>(); r.release(prev); }
    prev = r.st;
    r.next();
  }
  wg_wait<0>();
  reg_fence<N / 2>(d);
  r.release(prev);
}

template <int HALF>
__device__ __forceinline__ void attn_a_warp(Ring& r, const uint32_t (&q)[48], int b, int h) {
  constexpr int NT = HALF ? 5 : 3, NF = 8 * NT;
  const int lane = threadIdx.x & 31, g = lane >> 2, c = lane & 3, seg = (threadIdx.x >> 5) & 3;
  uint32_t f[6][NF];
  int slot[6];
  auto fetch = [&](int u) {
    const uint32_t kv = r.wait() + seg * KV_BYTES;
    slot[u] = r.st;
    r.next();
#pragma unroll
    for (int w = 0; w < 4; w++) {
      uint32_t* d = &f[u][2 * NT * w];
#pragma unroll
      for (int t = 0; t <= HALF; t++) {
        if (u < 3) {
          ldsm4(d + 4 * t, kv + w * 1024 + t * 512 + (lane & 8) * 32 + (lane & 16) * 8 + (lane & 7) * 16);
        } else {
          const uint4 v = lds128(kv + w * 1024 + t * 512 + lane * 16);
          d[4 * t] = v.x; d[4 * t + 1] = v.y; d[4 * t + 2] = v.z; d[4 * t + 3] = v.w;
        }
      }
      const uint2 m = lds64(kv + KV_M + w * 256 + lane * 8);
      d[2 * NT - 2] = m.x; d[2 * NT - 1] = m.y;
    }
    pdl_launch();
  };
  float s[NT][4] = {};
  fetch(0);
#pragma unroll
  for (int u = 0; u < 3; u++) {
    fetch(u + 1);
#pragma unroll
    for (int kk = 0; kk < 4; kk++) {
      const uint32_t* a = &q[16 * u + 4 * kk];
#pragma unroll
      for (int n = 0; n < NT; n++) mma16(s[(n + 1) % NT], a[0], a[1], a[2], a[3], f[u][2 * NT * kk + 2 * n], f[u][2 * NT * kk + 2 * n + 1]);
    }
    r.release(slot[u]);
    pdl_launch();
  }
  fetch(4);
  const float k2 = 0.07216878364870322f * 1.44269504089f, NEG = -INFINITY;
  if (2 * c > g) { s[NT - 2][0] = NEG; s[NT - 1][2] = NEG; }
  if (2 * c + 1 > g) { s[NT - 2][1] = NEG; s[NT - 1][3] = NEG; }
  s[NT - 1][0] = s[NT - 1][1] = NEG;
  uint32_t pp[NT][2]; float inv[2];
#pragma unroll
  for (int hh = 0; hh < 2; hh++) {
    float m = NEG, l = 0.f;
#pragma unroll
    for (int n = 0; n < NT; n++) m = fmaxf(m, fmaxf(s[n][2 * hh], s[n][2 * hh + 1]));
    m = fmaxf(m, __shfl_xor_sync(~0u, m, 1)); m = fmaxf(m, __shfl_xor_sync(~0u, m, 2));
#pragma unroll
    for (int n = 0; n < NT; n++) { const float x = ex2((s[n][2 * hh] - m) * k2), y = ex2((s[n][2 * hh + 1] - m) * k2); l += x + y; pp[n][hh] = pack2(x, y); }
    l += __shfl_xor_sync(~0u, l, 1); l += __shfl_xor_sync(~0u, l, 2);
    asm("rcp.approx.ftz.f32 %0, %1;" : "=f"(inv[hh]) : "f"(l));
  }
  uint32_t* dst = g_o + ((b * 192 + h * 6) * 16 + seg * 4 + HALF * 2) * 128 + lane;
#pragma unroll
  for (int u = 3; u < 6; u++) {
    float o[8][4] = {};
#pragma unroll
    for (int n = 0; n < 8; n++) mma8(o[n], pp[0][0], pp[0][1], f[u][2 * NT * (n >> 1) + 2 * NT - 2 + (n & 1)]);
#pragma unroll
    for (int t = 0; t <= HALF; t++)
#pragma unroll
      for (int n = 0; n < 8; n++) {
        const uint32_t* v = &f[u][2 * NT * (n >> 1) + 4 * t + 2 * (n & 1)];
        mma16(o[n], pp[1 + 2 * t][0], pp[1 + 2 * t][1], pp[2 + 2 * t][0], pp[2 + 2 * t][1], v[0], v[1]);
      }
    r.release(slot[u]);
    if (u == 3) fetch(5);
#pragma unroll
    for (int n = 0; n < 8; n++) {
      dst[(u - 3) * 4096 + (n >> 2) * 2048 + (n & 3) * 32] = pack2(o[n][0] * inv[0], o[n][1] * inv[0]);
      dst[(u - 3) * 4096 + (n >> 2) * 2048 + (n & 3) * 32 + 128] = pack2(o[n][2] * inv[1], o[n][3] * inv[1]);
    }
  }
}

__device__ __forceinline__ void fin_item(Ring& r, uint32_t scratch, int b, int idx) {
  const int warp = threadIdx.x >> 5, lane = threadIdx.x & 31;
  float4 v[1][5];
  {
    const uint32_t base = r.wait();
#pragma unroll
    for (int i = 0; i < 5; i++) v[0][i] = unpack4(lds64(base + ((warp * 5 + i) * 32 + lane) * 8));
    r.pop();
  }
#pragma unroll 1
  for (int k = 0; k < op_split(b); k += 2) {
    const uint32_t base = r.wait();
#pragma unroll
    for (int i = 0; i < 10; i++) {
      const uint2 q = lds64(base + ((i / 5 * 40 + warp * 5 + i % 5) * 32 + lane) * 8);
      float4& t = v[0][i % 5];
      t.x += bf_lo(q.x); t.y += bf_hi(q.x); t.z += bf_lo(q.y); t.w += bf_hi(q.y);
    }
    r.pop();
  }
#pragma unroll
  for (int i = 0; i < 5; i++) g_x[((b * 16 + idx) * 40 + warp * 5 + i) * 32 + lane] = pack4(v[0][i]);
  float mean[1], rs[1];
  ln_stats<1>(v, scratch, mean, rs);
#pragma unroll
  for (int i = 0; i < 5; i++) {
    const int u = warp * 5 + i;
    uint32_t* xn = g_xn + ((b * 20 + (u >> 1)) * 16 + idx) * 128 + (u & 1) * 64 + lane;
    xn[0] = pack2((v[0][i].x - mean[0]) * rs[0], (v[0][i].y - mean[0]) * rs[0]);
    xn[32] = pack2((v[0][i].z - mean[0]) * rs[0], (v[0][i].w - mean[0]) * rs[0]);
  }
}

__global__ void __launch_bounds__(384, 1) post_kernel(const __grid_constant__ PostParams p) {
  extern __shared__ __align__(1024) uint8_t smem_raw[];
  const uint32_t sb = s2u(smem_raw), bars = sb + PS * PB;
  const uint32_t bIF = bars + 128, bIE = bars + 160, done = bars + 192, bGo = bars + 224, slots = bars + 240, scratch = bars + 512;
  const int warp = __shfl_sync(~0u, threadIdx.x >> 5, 0), lane = threadIdx.x & 31;
  if (warp == 9) PST(0);
  if (warp == 0 && blockIdx.x < 36) TRACE(0);
  if (warp >= 8) {
    asm volatile("setmaxnreg.dec.sync.aligned.u32 56;");
    if (warp == 10) {
      pdl_launch();
      if (sb & 1023) __trap();
      if (lane < 29) mbar_init(bars + 8 * lane, lane < 8 ? 1 : lane < 16 ? 8 : lane < 20 ? 1 : lane < 24 ? 2 : lane < 28 ? 8 : 1);
      if (lane == 0) sts32(slots + 16, p.gap);
      fence_async();
    }
    if (warp == 8 && lane < 5) asm volatile("prefetch.tensormap [%0];" :: "l"(&p.wq + lane) : "memory");
    if (warp != 9) bar_sync(2, 384);
    if (warp == 9) {
      PST(1);
      const int b = lane & 15;
      bool queries = QA_END < 16 && blockIdx.x < 36;
      for (int n = 0;; n++) {
        if (n > 0) { mbar_wait(bGo, (n - 1) & 1); mbar_wait(bIE + 8 * (n & 3), ((n >> 2) & 1) ^ 1); }
        int code = -1, spin = 0, ticket = 0;
        if (queries) {
          if (lane == 0) ticket = n == 0 ? blockIdx.x : 36 + atomicAdd(g_sync + SY_QC, 1);
          ticket = __shfl_sync(~0u, ticket, 0);
          queries = ticket < (16 - QA_END) * 32;
          if (queries) code = IT_Q << 16 | (QA_END + ticket % (16 - QA_END)) << 8 | ticket / (16 - QA_END);
        }
        if (!queries && lane == 0) asm volatile("atom.relaxed.gpu.global.add.u32 %0, [%1], 1;" : "=r"(ticket) : "l"(g_sync + SY_T) : "memory");
        while (!queries) {
          const uint4 hd = ldg_strong128(g_sync + b * 8), pr = ldg_strong128(g_sync + b * 8 + 4);
          if (n == 0 && spin == 0 && hd.x != 0x7fffffff) PST(2);
          const uint32_t hv[4] = {hd.x, hd.y, hd.z, hd.w}, pv[4] = {pr.x, pr.y, pr.z, pr.w};
          const uint32_t chain_done = __ballot_sync(~0u, (pr.x & 0xffff) >= 96) & 0xffff;
          int left[4], avail[4], rdy = 0, claimed = 0, upstream = 0;
#pragma unroll
          for (int t = 0; t < 4; t++) {
            const int cnt = lane < 16 ? item_count(t, b) : 0;
            left[t] = max(cnt - (int)hv[t], 0);
            claimed += cnt - left[t];
            const bool ready = (pv[t] & 0xffff) >= item_need(t, b);
            rdy |= ready << t;
            bool ok = ready || (t == IT_ATT ? pr.x >= 0x10000 : !upstream || (t == IT_OP && (chain_done >> 15 & 1)));
            if (t == IT_BQ && (chain_done >> BQ_HOLD & 1) && !(chain_done >> 15)) ok = false;
            avail[t] = ok ? left[t] : 0;
            upstream |= __any_sync(~0u, left[t] > 0);
          }
          if (!upstream) break;
          int rank = max(__shfl_sync(~0u, ticket, 0) - __reduce_add_sync(~0u, claimed), 0), type = -1, mine = 0;
#pragma unroll
          for (int c = 0; c < 8; c++) {
            const int t = c == PR_FIN || c == 5 ? IT_FIN : c == PR_ATT || c == 7 ? IT_ATT : c == PR_OP || c == 4 ? IT_OP : IT_BQ;
            int a = c == PR_ATT || ((rdy >> t & 1) == (c < 4)) ? avail[t] : 0;
            if (t == IT_OP && OP_EARLY) a = c == PR_OP ? avail[t] : 0;
            if (c == 7) a = b < QA_END && !(rdy & 1) && ((chain_done << 1 | 1) >> b & 1) ? left[t] : 0;
            const int tot = __reduce_add_sync(~0u, a);
            if (type < 0) { if (rank < tot) { type = t; mine = a; } else rank -= tot; }
          }
          if (type >= 0) {
#pragma unroll
            for (int o = 1; o < 16; o <<= 1) { const int y = __shfl_up_sync(~0u, mine, o); if (lane >= o) mine += y; }
            const int blk = __ffs(__ballot_sync(~0u, mine > rank)) - 1;
            const int early = !(__shfl_sync(~0u, rdy, blk) >> type & 1);
            uint32_t idx = 0;
            if (n == 0 && spin == 0) PST(3);
            if (lane == 0) asm volatile("atom.relaxed.gpu.global.add.u32 %0, [%1], 1;" : "=r"(idx) : "l"(g_sync + blk * 8 + type) : "memory");
            ld_acquire(g_sync + blk * 8 + 4 + type);
            idx = __shfl_sync(~0u, idx, 0);
            if (idx < item_count(type, blk)) { code = (chain_done >> 15 & 1) << 22 | (chain_done >> p.look & 1) << 21 | early << 20 | type << 16 | blk << 8 | idx; break; }
          } else {
            __nanosleep(50);
          }
          spin_guard(spin);
        }
        if (n == 0) bar_sync(2, 384);
        if (lane == 0) {
          fence_async_global();
          sts32(slots + 4 * (n & 3), code);
          mbar_arrive(bIF + 8 * (n & 3));
        }
        __syncwarp();
        if (code < 0) break;
      }
    } else if (warp == 8) {
      if (elect()) {
        uint32_t dst = sb, bar = bars, ph = 1, next = clk32(), gap = 0;
        auto acquire = [&](uint32_t kb) {
          mbar_wait(bar + 8 * PS, ph);
          mbar_expect(bar, kb * 1024);
          if (gap) {
            uint32_t now;
            do now = clk32(); while ((int)(now - next) < 0);
            next = ((int)(now - next) > 100 ? now - 100 : next) + kb * gap;
          }
        };
        auto advance = [&]() { dst += PB; bar += 8; if (dst == bars) { dst = sb; bar = bars; ph ^= 1; } };
        auto depend = [&](const uint32_t* c, uint32_t need) { wait_count(c, need); fence_async_global(); };
#pragma unroll 1
        for (int n = 0;; n++) {
          mbar_wait(bIF + 8 * (n & 3), (n >> 2) & 1);
          const int code = (int)lds32(slots + 4 * (n & 3));
          if (code < 0) break;
          const int type = (code >> 16) & 15, b = (code >> 8) & 255, idx = code & 255;
          const bool early = code >> 20 & 1, go = !(code >> 21 & 1);
          mbar_arrive(bIE + 8 * (n & 3));
          gap = !(code >> 22 & 1) ? lds32(slots + 16) : type == IT_ATT || type == IT_FIN ? 0 : p.gap2;
          const uint32_t* progress = g_sync + b * 8 + 4 + type;
          if (type == IT_ATT && b >= QA_END) {
            depend(g_sync + SY_Q, (16 - QA_END) * 32);
#pragma unroll 1
            for (int u = 0; u < 2; u++) { acquire(24); bulk_load_last(dst, g_q + (((b - QA_END) * 32 + idx) * 2 + u) * 1536, 24576, bar); advance(); }
          } else if (type == IT_FIN) {
            acquire(10);
            bulk_load(dst, g_x + (b * 16 + idx) * 1280, 10240, bar);
            advance();
            if (early) depend(progress, item_need(type, b));
            if (go) mbar_arrive(bGo);
            const uint2* src = g_part + (b * 16 + idx) * 16 * 1280;
#pragma unroll 1
            for (int i = 0; i < op_split(b); i += 2) { acquire(20); bulk_load_last(dst, src + i * 1280, 20480, bar); advance(); }
            if (!go && p.pol) mbar_arrive(bGo);
          } else {
            const bool op = type == IT_OP, bq = type == IT_BQ;
            const int width = op ? op_width(b) : bq ? bq_width(b) : 192, nb = (width + 63) >> 6, lt = width == 320 ? 1 : 2;
            const int nst = op ? 192 / op_split(b) : 20, kb0 = op ? (idx >> lt) * nst : 0;
            const int col = (op ? idx & ((1 << lt) - 1) : idx) * width;
            const bool whole = !(width & 63);
            const CUtensorMap* m = op ? (whole ? &p.wo : &p.wo2) : bq ? (whole ? &p.wb : &p.wb2) : &p.wq;
            const uint32_t* a = op ? g_o + (b * 192 + kb0) * 2048 : g_xn + b * 20 * 2048;
            int row = kb0 * 32, pre = early && (op || bq) ? min(nst, PRE_MAX) : 0;
            auto weights = [&]() {
              acquire(8 + nb * 4);
              if (whole) {
                tma_load3z(dst + 8192, m, row, col >> 6, bar);
              } else {
                tma_load(dst + 8192, m, col, row, bar); tma_load(dst + 12288, m, col + 64, row, bar);
                if (nb == 3) tma_load(dst + 16384, m, col + 128, row, bar);
              }
              row += 32;
            };
            if (pre) {
              uint32_t da = dst, ba = bar;
              const uint32_t g0 = gap;
              gap = max(gap, PRE_GAP);
#pragma unroll 1
              for (int kb = 0; kb < pre; kb++) { weights(); advance(); }
              gap = g0;
              depend(progress, item_need(type, b));
#pragma unroll 1
              for (int kb = 0; kb < pre; kb++) {
                bulk_load(da, a, 8192, ba);
                a += 2048; da += PB; ba += 8;
                if (da == bars) { da = sb; ba = bars; }
              }
            }
#pragma unroll 1
            for (int kb = pre; kb < nst; kb++) { weights(); if (op && OEF) bulk_load_last(dst, a, 8192, bar); else bulk_load(dst, a, 8192, bar); a += 2048; advance(); }
          }
          if (type == IT_ATT) {
            if (early) depend(progress, 96);
            if (go) mbar_arrive(bGo);
            const uint8_t* src = g_kv + (size_t)(idx * 6 * NSEG + b * 4) * KV_BYTES;
#pragma unroll 1
            for (int u = 0; u < 6; u++) {
              acquire(20);
              bulk_load_last(dst, src, 20480, bar);
              src += u == 2 ? -3 * KV_V : 2 * KV_V;
              advance();
            }
            if (!go && p.pol && ATT_LOOK) mbar_arrive(bGo);
            if (Q_PF && b + Q_PF >= QA_END && b + Q_PF < 16)
              asm volatile("cp.async.bulk.prefetch.L2.global [%0], 49152;" :: "l"(g_q + ((b + Q_PF - QA_END) * 32 + idx) * 3072) : "memory");
          }
        }
      }
    } else if (warp == 11) {
      uint32_t smid, nsm, used = 0;
      asm("mov.u32 %0, %%smid;" : "=r"(smid)); asm("mov.u32 %0, %%nsmid;" : "=r"(nsm));
      for (int n = 0; n < 64 && used < 96; n++) {
        uint32_t peers = 0;
        used = 0;
        for (uint32_t i = lane; i < min(nsm, 256u); i += 32) {
          const bool taken = ldg_strong32(g_smuse + i) == p.layer + 1;
          used += taken;
          peers += abs((int)(g_smclk[i] - g_smclk[smid & 255])) < 4000 && !taken;
        }
        used = __reduce_add_sync(~0u, used);
        sts32(slots + 16, max(p.gap, (int)min(__reduce_add_sync(~0u, peers), 18u) * p.share >> 3));
      }
    } else if (warp == 10 && lane == 0) {
      for (int n = 0;; n++) {
        mbar_wait(bIF + 8 * (n & 3), (n >> 2) & 1);
        const int code = (int)lds32(slots + 4 * (n & 3));
        if (code < 0) break;
        const int type = (code >> 16) & 15, b = (code >> 8) & 255;
        mbar_wait(done + 8 * (n & 3), (n >> 2) & 1);
        if (type != IT_BQ) red_release(type == IT_Q ? g_sync + SY_Q : g_sync + b * 8 + 5 + type, 1);
        mbar_arrive(bIE + 8 * (n & 3));
      }
    }
  } else {
    asm volatile("setmaxnreg.inc.sync.aligned.u32 224;");
    bar_sync(2, 384);
    const int g = lane >> 2, c = lane & 3;
    Ring r = {sb, bars, 0, 0};
#pragma unroll 1
    for (int n = 0;; n++) {
      mbar_wait(bIF + 8 * (n & 3), (n >> 2) & 1);
      const int code = __shfl_sync(~0u, (int)lds32(slots + 4 * (n & 3)), 0);
      if (code < 0) { TRACE(2); break; }
      const int type = (code >> 16) & 15, b = (code >> 8) & 255, idx = code & 255;
      ITEM(code & 0xfffff, 0);
      if (type == IT_ATT || type == IT_Q) {
        uint32_t q[48];
        if (type == IT_Q || b < QA_END) {
          float d[96] = {};
          reg_fence<96>(d);
          gemm_item<192>(r, d, 20, bGo, type == IT_Q ? 12 : -1);
#pragma unroll
          for (int i = 0; i < 48; i++) q[i] = pack2(d[2 * i], d[2 * i + 1]);
        } else {
#pragma unroll
          for (int u = 0; u < 2; u++) {
            const uint32_t base = r.wait() + threadIdx.x * 16;
#pragma unroll
            for (int i = 0; i < 6; i++) {
              const uint4 v = lds128(base + i * 4096);
              q[24 * u + 4 * i] = v.x; q[24 * u + 4 * i + 1] = v.y; q[24 * u + 4 * i + 2] = v.z; q[24 * u + 4 * i + 3] = v.w;
            }
            r.pop();
          }
        }
        if (type == IT_Q) {
          uint4* dst = g_q + ((b - QA_END) * 32 + idx) * 3072 + threadIdx.x;
#pragma unroll
          for (int i = 0; i < 12; i++) dst[i * 256] = make_uint4(q[4 * i], q[4 * i + 1], q[4 * i + 2], q[4 * i + 3]);
        } else if (warp < 4) {
          attn_a_warp<0>(r, q, b, idx);
        } else {
          attn_a_warp<1>(r, q, b, idx);
        }
      } else if (type == IT_FIN) {
        fin_item(r, scratch, b, idx);
      } else {
        float d[160] = {};
        reg_fence<160>(d);
        const int width = type == IT_OP ? op_width(b) : bq_width(b), nst = type == IT_OP ? 192 / op_split(b) : 20;
        const int go_at = max(nst - (code >> 21 & 1 ? p.pol : 6), 0);
        if (width == 320) gemm_item<320>(r, d, nst, bGo, go_at);
        else if (width == 160 || BQ_80 == 16) gemm_item<160>(r, d, nst, bGo, go_at);
        else gemm_item<80>(r, d, nst, bGo, go_at);
        reg_fence<160>(d);
        if (type == IT_OP) {
          const int tiles = DM / width;
          uint2* dst = g_part + (((b * 16 + warp * 2) * 16 + idx / tiles) * 40 + idx % tiles * (width / 16)) * 32 + lane;
#pragma unroll
          for (int u = 0; u < 20; u++) {
            if (u % 5 == 0 && u * 16 >= width) break;
            dst[u * 32] = make_uint2(pack2(d[8 * u], d[8 * u + 1]), pack2(d[8 * u + 4], d[8 * u + 5]));
            dst[(640 + u) * 32] = make_uint2(pack2(d[8 * u + 2], d[8 * u + 3]), pack2(d[8 * u + 6], d[8 * u + 7]));
          }
        } else {
          const int row = b * 128 + warp * 16 + g;
          const int h0 = idx * (width / 20);
          const float sc = h0 < 32 ? 0.22360679775f * 1.44269504089f : 1.f;
          const bool lo = c < 2;
          uint32_t* da = g_bqkv + (h0 * 256 + (row >> 3)) * 96 + lane;
          uint32_t* db = da + 256 * 96 + (lo ? 2 : -2);
          uint32_t pad[2];
#pragma unroll
          for (int rr = 0; rr < 2; rr++) pad[rr] = c & 1 || h0 < 32 ? 0u : h0 >= 64 ? 0x00003f80u : poly_group((row >> 3) + rr) ? 0x3f803f80u : 0u;
#pragma unroll
          for (int q = 0; q < 8; q++) {
            if (!(q & 1) && q * 40 >= width) break;
#pragma unroll
            for (int rr = 0; rr < 2; rr++) {
              uint32_t w[5];
#pragma unroll
              for (int i = 0; i < 5; i++) w[i] = pack2(d[20 * q + 4 * i + 2 * rr] * sc, d[20 * q + 4 * i + 2 * rr + 1] * sc);
              const int o = q * 2 * 256 * 96 + rr * 96;
              da[o] = w[0]; da[o + 32] = w[1]; da[o + 64] = lo ? w[2] : pad[rr];
              db[o] = lo ? w[3] : w[2]; db[o + 32] = lo ? w[4] : w[3]; db[o + 64] = lo ? pad[rr] : w[4];
            }
          }
        }
      }
      __syncwarp();
      if (lane == 0) mbar_arrive(done + 8 * (n & 3));
      if ((code >> 21 & 1) && (p.pol == 0 || (type == IT_ATT && !ATT_LOOK)) && threadIdx.x == 128) mbar_arrive(bGo);
      ITEM(code & 0xfffff, 1);
    }
  }
}

constexpr int AB_SMEM = 1024 + 98304 + 51200 + 4 * 16384 + 256 + 10240;
#define AB_LW 1
#define AB_U 8
#define AB_WG 4
constexpr int AB_T = AB_WG * 128, AB_PASS = 8 / AB_WG;
__device__ __forceinline__ uint32_t fma2(uint32_t a, uint32_t b, uint32_t c) { uint32_t r; asm("fma.rn.bf16x2 %0, %1, %2, %3;" : "=r"(r) : "r"(a), "r"(b), "r"(c)); return r; }
__device__ __forceinline__ uint32_t ex2_pair(float a, float b, uint32_t one, uint32_t c0) {
  const uint32_t e = __byte_perm(__float_as_uint(a), __float_as_uint(b), 0x6521);
  uint32_t x, r;
  asm("lop3.b32 %0, %1, 0x007f007f, %2, 0xEA;" : "=r"(x) : "r"(e), "r"(one));
  const uint32_t m = fma2(fma2(c0, x, 0x3c0d3c0du), x, 0x3f2b3f2bu);
  asm("lop3.b32 %0, %1, %2, 0x7f807f80, 0xE4;" : "=r"(r) : "r"(e), "r"(m));
  return r;
}
__device__ __forceinline__ float sq2(uint32_t w) { const float a = bf_lo(w), b = bf_hi(w); return fmaf(a, a, b * b); }

__device__ __forceinline__ void attn_b_store(const float* o, int h, int row0, int lane) {
  const int g = lane >> 2, c = lane & 3;
  const float i0 = __frcp_rn(__shfl_sync(~0u, o[8], (lane & ~3) | 2)), i1 = __frcp_rn(__shfl_sync(~0u, o[10], (lane & ~3) | 2));
#pragma unroll
  for (int jj = 0; jj < 3; jj++) {
    if (jj < 2 || c < 2) {
      const int col = h * 20 + 8 * jj + 2 * c;
      uint32_t* dst = g_of + (((row0 >> 7) * 10 + (col >> 6)) * 16 + (row0 >> 3 & 15)) * 256 + (col >> 3 & 7) * 32 + g * 4 + (col >> 1 & 3);
      dst[0] = pack2(o[4 * jj] * i0, o[4 * jj + 1] * i0);
      dst[256] = pack2(o[4 * jj + 2] * i1, o[4 * jj + 3] * i1);
    }
  }
}

struct AbParams { Weights next; uint32_t* done; uint32_t* out; };
__global__ void __launch_bounds__(AB_T + 32, 1) attn_b_kernel(const __grid_constant__ AbParams p) {
  extern __shared__ uint8_t smem_raw[];
  const uint32_t sb = (s2u(smem_raw) + 1023) & ~1023u, sK = sb, sV = sb + 98304, bars = sV + 51200 + 4 * 16384;
  const uint32_t bF = bars + 64, bW = bars + 72, bA = bars + 80, bE = bars + 128, smax = bars + 176;
  auto ring = [&](int i) { return i < 2 ? sK + 51200 + i * 16384 : sV + 51200 + (i - 2) * 16384; };
  const int warp = __shfl_sync(~0u, threadIdx.x >> 5, 0), lane = threadIdx.x & 31;
  const int h = blockIdx.x >> 2, quarter = blockIdx.x & 3;
  TRACE(0);
  pdl_launch();
  if (threadIdx.x < 22) mbar_init(bars + 8 * threadIdx.x, threadIdx.x == 8 ? AB_T / 32 : threadIdx.x >= 16 ? 8 : 1);
  if (threadIdx.x == 32) sts64(smax, 0, 0);
  fence_async();
  __syncthreads();
  pdl_wait();
  const int blk = quarter * 4 + (h >> 3), cg = h & 7;
  auto unsafe = [&]() { const float2 m = lds64f(smax); return !(m.x * m.y <= 10000.f); };
  if (warp == AB_T / 32) {
    auto load_w = [&]() {
      mbar_expect(bW, 102400);
      for (int i = 0; i < 4; i++) bulk_load((i < 2 ? sK : sV) + (i & 1) * 25600, g_wb + cg * 6400 + i * 1600, 25600, bW);
    };
    if (elect()) {
      const uint32_t* gk = g_bqkv + (32 + h) * 256 * 96;
#pragma unroll 1
      for (int i = 0; i < 8; i++) {
        if (i >= AB_LW) mbar_wait(bars + 8 * (i - AB_LW), 0);
        mbar_expect(bars + 8 * i, 24576);
        bulk_load_last(sK + i * 12288, gk + i * 3072, 12288, bars + 8 * i);
        bulk_load_last(sV + i * 12288, gk + 32 * 256 * 96 + i * 3072, 12288, bars + 8 * i);
      }
    }
    __syncwarp();
    if (blockIdx.x < NSLOT) for (int i = lane; i < 512; i += 32) reinterpret_cast<uint4*>(pool_at(blockIdx.x * 8192))[i] = make_uint4(0, 0, 0, 0);
    if (blockIdx.x == 127) for (int i = lane; i < SY_N; i += 32) g_sync[i] = 0;
    if (p.next.w[0] && lane == 0) {
      for (int i = 0; i < AB_PF; i++) { const uint32_t t0 = clk32(); while (clk32() - t0 < (i ? AB_PFD : AB_PF0)) __nanosleep(200); prefetch_weights(p.next, i); }
    }
    __syncwarp();
    mbar_wait(bF, 0);
    const bool redo = unsafe();
    if (!redo && lane == 0) load_w();
    if (lane < 16) asm volatile("cp.async.bulk.prefetch.L2.global [%0], 1280;" :: "l"(g_x + ((blk * 16 + lane) * 40 + cg * 5) * 32) : "memory");
    __syncwarp();
    bar_sync(1, AB_T + 32);
    if (lane == 0) {
      ABT(!!p.out, 1);
      red_release(p.done + quarter * 32, 1);
      ABT(!!p.out, 2);
      if (redo) load_w();
      wait_count(p.done + quarter * 32, 32);
      fence_async_global();
      ABT(!!p.out, 3);
      for (int kb = 0; kb < 10; kb++) {
        const int i = kb < 6 ? kb : kb - 6;
        if (kb >= 6) mbar_wait(bE + 8 * i, 0);
        mbar_expect(bA + 8 * i, 16384);
        bulk_load(ring(i), g_of + (blk * 10 + kb) * 4096, 16384, bA + 8 * i);
      }
    }
    return;
  }
  float qmax = 0.f;
  const uint32_t one = opaque(0x3f803f80u + (threadIdx.x >> 10)), c0 = opaque(0x3ea83ea8u + (threadIdx.x >> 10));
#pragma unroll 1
  for (int pass = 0; pass < AB_PASS; pass++) {
    const int row0 = quarter * 512 + ((warp >> 2) * AB_PASS + pass) * 64 + (warp & 3) * 16;
    const uint32_t* gq = g_bqkv + (h * 256 + (row0 >> 3)) * 96 + lane;
    const uint32_t q0 = gq[0], q1 = gq[96], q2 = gq[32], q3 = gq[128];
    uint32_t q4 = gq[64], q5 = gq[160];
    const uint32_t z0 = gq[64 + 3 - (lane & 3)], z1 = gq[160 + 3 - (lane & 3)];
    {
      float n0 = sq2(q0) + sq2(q2) + sq2(q4), n1 = sq2(q1) + sq2(q3) + sq2(q5);
      n0 += __shfl_xor_sync(~0u, n0, 1); n1 += __shfl_xor_sync(~0u, n1, 1);
      n0 += __shfl_xor_sync(~0u, n0, 2); n1 += __shfl_xor_sync(~0u, n1, 2);
      qmax = (n0 > qmax || n0 != n0) ? n0 : qmax;
      qmax = (n1 > qmax || n1 != n1) ? n1 : qmax;
    }
    if (pass == AB_PASS - 1) {
      float kmax = 0.f;
#pragma unroll
      for (int i = 0; i < SEQ / AB_T; i++) {
        const int key = threadIdx.x + AB_T * i;
        const uint32_t a = sK + (key >> 3) * 384 + (key & 7) * 16;
        const uint4 x = lds128(a), y = lds128(a + 128);
        const uint2 z = lds64(a + 256);
        const float n = ((sq2(x.x) + sq2(x.y)) + (sq2(x.z) + sq2(x.w))) + ((sq2(y.x) + sq2(y.y)) + (sq2(y.z) + sq2(y.w))) + (sq2(z.x) + sq2(z.y));
        kmax = (n > kmax || n != n) ? n : kmax;
      }
      const uint32_t kb = __reduce_max_sync(~0u, __float_as_uint(kmax) & 0x7fffffffu), qb = __reduce_max_sync(~0u, __float_as_uint(qmax) & 0x7fffffffu);
      if (lane < 2) asm volatile("red.shared.max.u32 [%0], %1;" :: "r"(smax + 4 * lane), "r"(lane ? kb : qb) : "memory");
      __syncwarp();
    }
    if ((lane & 3) == 2) { q4 = 0xBF8043C0u; q5 = 0xBF8043C0u; }
    float o[12];
    auto desc = [](uint32_t lo, uint32_t hi) { uint64_t d; asm("mov.b64 %0, {%1, %2};" : "=l"(d) : "r"(lo), "r"(hi)); return d; };
    const uint32_t k0 = (uint32_t)mkdesc(sK, 128, 0, 0), k1 = (uint32_t)mkdesc(sK + 256, 0, 0, 0), v0 = (uint32_t)mkdesc(sV, 384, 0, 0);
    float sa[16], sb2[16];
    uint32_t pa[8], pb[8];
    auto qk = [&](float* s, uint32_t t) {
      wg_rs32_00(s, q0, q1, q2, q3, desc(k0 + t, 24), 0);
      wg_rs32_00(s, q4, q5, z0, z1, desc(k1 + t, 24), 1);
      wg_commit();
    };
    auto step = [&](float* s, uint32_t* pp, int g0, uint32_t t, uint32_t nx, int acc) {
      wg_wait<1>();
      reg_fence<16>(s);
#pragma unroll
      for (int i = 0; i < 8; i++) pp[i] = poly_group(g0 + (i >> 1)) ? ex2_pair(s[2 * i], s[2 * i + 1], one, c0) : pack2(ex2(s[2 * i]), ex2(s[2 * i + 1]));
      wg_fence();
      wg_rs24_01(o, pp[0], pp[1], pp[2], pp[3], desc(v0 + t, 8), acc);
      wg_rs24_01(o, pp[4], pp[5], pp[6], pp[7], desc(v0 + t + 48, 8), 1);
      qk(s, nx);
    };
    if (pass == 0) mbar_wait(bars, 0);
    wg_fence();
    qk(sa, 0);
    qk(sb2, 96);
#pragma unroll 1
    for (uint32_t t = 0; t < 64 * 96; t += AB_U * 96) {
      const uint32_t nx = t + AB_U * 96 < 64 * 96 ? t + AB_U * 96 : 0;
      if (pass == AB_PASS - 1 && t == 40 * 96 && lane == 0) mbar_arrive(bF);
#pragma unroll
      for (int u = 0; u < AB_U; u += 2) {
        if (u == AB_U - 2 && pass == 0) mbar_wait(bars + 8 * (nx / 768), 0);
        step(sa, pa, 0, t + u * 96, u + 2 < AB_U ? t + (u + 2) * 96 : nx, u | t);
        step(sb2, pb, 4, t + u * 96 + 96, (u + 2 < AB_U ? t + (u + 2) * 96 : nx) + 96, 1);
      }
    }
    wg_wait<0>();
    reg_fence<12>(o); reg_fence<16>(sa); reg_fence<16>(sb2);
    attn_b_store(o, h, row0, lane);
  }
  mbar_wait(bF, 0);
  if (unsafe())
#pragma unroll 1
  for (int pass = 0; pass < AB_PASS; pass++) {
    const int row0 = quarter * 512 + ((warp >> 2) * AB_PASS + pass) * 64 + (warp & 3) * 16;
    const uint32_t* gq = g_bqkv + (h * 256 + (row0 >> 3)) * 96 + lane;
    const uint32_t q0 = gq[0], q1 = gq[96], q2 = gq[32], q3 = gq[128], q4 = gq[64], q5 = gq[160];
    float o[12];
#pragma unroll
    for (int i = 0; i < 12; i++) o[i] = 0.f;
    float m0 = -INFINITY, m1 = -INFINITY;
#pragma unroll 1
    for (int kt = 0; kt < 32; kt++) {
      float s[32];
      const uint64_t dk = mkdesc(sK + kt * 3072, 128, 384, 0), dk2 = mkdesc(sK + kt * 3072 + 256, 0, 384, 0);
      wg_fence();
      wg_rs64_00(s, q0, q1, q2, q3, dk, 0);
      wg_rs64_00(s, q4, q5, 0, 0, dk2, 1);
      wg_commit();
      wg_wait<0>();
      reg_fence<32>(s); reg_fence<12>(o);
      float n0 = m0, n1 = m1;
#pragma unroll
      for (int jj = 0; jj < 8; jj++) { n0 = fmaxf(n0, fmaxf(s[4 * jj], s[4 * jj + 1])); n1 = fmaxf(n1, fmaxf(s[4 * jj + 2], s[4 * jj + 3])); }
      n0 = fmaxf(n0, __shfl_xor_sync(~0u, n0, 1)); n0 = fmaxf(n0, __shfl_xor_sync(~0u, n0, 2));
      n1 = fmaxf(n1, __shfl_xor_sync(~0u, n1, 1)); n1 = fmaxf(n1, __shfl_xor_sync(~0u, n1, 2));
      const float r0 = ex2(m0 - n0), r1 = ex2(m1 - n1);
      m0 = n0; m1 = n1;
#pragma unroll
      for (int jj = 0; jj < 3; jj++) { o[4 * jj] *= r0; o[4 * jj + 1] *= r0; o[4 * jj + 2] *= r1; o[4 * jj + 3] *= r1; }
      uint32_t pp[16];
#pragma unroll
      for (int jj = 0; jj < 8; jj++) {
        pp[2 * jj] = pack2(ex2(s[4 * jj] - m0), ex2(s[4 * jj + 1] - m0));
        pp[2 * jj + 1] = pack2(ex2(s[4 * jj + 2] - m1), ex2(s[4 * jj + 3] - m1));
      }
      const uint64_t dv = mkdesc(sV + kt * 3072, 384, 128, 0);
      wg_fence();
#pragma unroll
      for (int kk = 0; kk < 4; kk++) wg_rs24_01(o, pp[4 * kk], pp[4 * kk + 1], pp[4 * kk + 2], pp[4 * kk + 3], dv + kk * 48, 1);
      wg_commit();
    }
    wg_wait<0>();
    reg_fence<12>(o);
    attn_b_store(o, h, row0, lane);
  }
  ABT(!!p.out, 0);
  bar_arrive(1, AB_T + 32);
  if (warp >= 12) return;
  const int g = lane >> 2, c = lane & 3;
  const bool live = opaque(threadIdx.x) < 256;
  float d[40] = {};
  uint2* x = g_x + ((blk * 16 + warp * 2) * 40 + cg * 5) * 32 + lane;
  if (warp < 8) {
#pragma unroll
  for (int i = 0; i < 10; i++) {
    const int r = i / 5, u = i % 5;
    const float4 t = unpack4(x[(r * 40 + u) * 32]);
    d[8 * u + 2 * r] = t.x; d[8 * u + 2 * r + 1] = t.y; d[8 * u + 4 + 2 * r] = t.z; d[8 * u + 5 + 2 * r] = t.w;
  }
  mbar_wait(bW, 0);
  reg_fence<40>(d);
  ABT(!!p.out, 4);
#pragma unroll 1
  for (int kb = 0; kb < 10; kb++) {
    const int i = kb < 6 ? kb : kb - 6;
    mbar_wait(bA + 8 * i, kb >= 6);
    const uint64_t da = mkdesc(ring(i) + (warp >> 2) * 8192, 128, 1024, 0), db = mkdesc(kb < 5 ? sK + kb * 10240 : sV + (kb - 5) * 10240, 1280, 128, 0);
    wg_fence();
#pragma unroll
    for (int kk = 0; kk < 4; kk++) wg_ss80_01(d, da + kk * 16, db + kk * 160, 1);
    wg_commit();
    if (kb > 0 && kb < 5) { wg_wait<1>(); if (lane == 0) mbar_arrive(bE + 8 * (kb - 1)); }
  }
  wg_wait<0>();
  reg_fence<40>(d);
  }
  ABT(!!p.out, 5);
  if (p.out) {
    if (warp >= 8) return;
    const uint32_t stage = sK + 83968 + warp * 2560 + (warp < 4 ? 0 : 131328 - 10240);
#pragma unroll
    for (int u = 0; u < 5; u++)
      stsm4(stage + (lane & 15) * 160 + u * 32 + (lane >> 4) * 16, pack2(d[8 * u], d[8 * u + 1]), pack2(d[8 * u + 2], d[8 * u + 3]),
            pack2(d[8 * u + 4], d[8 * u + 5]), pack2(d[8 * u + 6], d[8 * u + 7]));
    __syncwarp();
    uint4* out = reinterpret_cast<uint4*>(p.out + (blk * 128 + warp * 16) * (DM / 2) + cg * 40);
#pragma unroll
    for (int i = 0; i < 5; i++) { const int e = i * 32 + lane, r = e / 10; out[r * (DM / 8) + e - r * 10] = lds128(stage + e * 16); }
  } else {
    float2* stat = g_stat + blk * 1024 + (warp & 7) * 16 + g;
    float mean[2], rs[2];
#pragma unroll
    for (int r = 0; r < 2; r++) {
      float t = 0.f, q = 0.f;
#pragma unroll
      for (int i = 0; i < 10; i++) t += d[4 * i + 2 * r] + d[4 * i + 2 * r + 1];
      t += __shfl_xor_sync(~0u, t, 1); t += __shfl_xor_sync(~0u, t, 2);
      t *= 1.f / 80;
#pragma unroll
      for (int i = 0; i < 10; i++) { const float a = d[4 * i + 2 * r] - t, b = d[4 * i + 2 * r + 1] - t; q += a * a + b * b; }
      q += __shfl_xor_sync(~0u, q, 1); q += __shfl_xor_sync(~0u, q, 2);
      if (c == r && live) asm volatile("st.relaxed.gpu.global.v2.b32 [%0], {%1, %2};" :: "l"(stat + cg * 128 + r * 8), "r"(__float_as_uint(t)), "r"(nz(__float_as_uint(q))) : "memory");
    }
#pragma unroll
    for (int i = 0; i < 10; i++) {
      const int r = i / 5, u = i % 5;
      if (live) x[(r * 40 + u) * 32] = make_uint2(pack2(d[8 * u + 2 * r], d[8 * u + 2 * r + 1]), pack2(d[8 * u + 4 + 2 * r], d[8 * u + 5 + 2 * r]));
    }
    ABT(0, 6);
    uint2 e[4];
    int n = 0;
    do {
#pragma unroll
      for (int i = 0; i < 4; i++)
        asm volatile("ld.relaxed.gpu.global.v2.b32 {%0, %1}, [%2];" : "=r"(e[i].x), "=r"(e[i].y) : "l"(stat + (2 * c + (i & 1)) * 128 + (i >> 1) * 8) : "memory");
      spin_guard(n);
    } while (__any_sync(~0u, min(min(e[0].y, e[1].y), min(e[2].y, e[3].y)) == 0 && live));
#pragma unroll
    for (int r = 0; r < 2; r++) {
      const float m0 = __uint_as_float(e[2 * r].x), m1 = __uint_as_float(e[2 * r + 1].x);
      float t = m0 + m1;
      t += __shfl_xor_sync(~0u, t, 1); t += __shfl_xor_sync(~0u, t, 2);
      t *= 0.125f;
      float q = __uint_as_float(e[2 * r].y) + __uint_as_float(e[2 * r + 1].y) + 80.f * ((m0 - t) * (m0 - t) + (m1 - t) * (m1 - t));
      q += __shfl_xor_sync(~0u, q, 1); q += __shfl_xor_sync(~0u, q, 2);
      mean[r] = t; rs[r] = rsqrtf(q * (1.f / DM) + 1e-5f);
    }
    ABT(0, 7);
    uint32_t w[2][5][2];
#pragma unroll
    for (int i = 0; i < 20; i++) w[i & 1][i >> 2][i >> 1 & 1] = pack2((d[2 * i] - mean[i & 1]) * rs[i & 1], (d[2 * i + 1] - mean[i & 1]) * rs[i & 1]);
    ln_store(w, blk * 8 + warp, cg * 5, live);
  }
  ABT(!!p.out, 8);
  TRACE(2);
}

typedef CUresult (*EncodeFn)(CUtensorMap*, CUtensorMapDataType, cuuint32_t, void*, const cuuint64_t*, const cuuint64_t*,
                             const cuuint32_t*, const cuuint32_t*, CUtensorMapInterleave, CUtensorMapSwizzle,
                             CUtensorMapL2promotion, CUtensorMapFloatOOBfill);

void make_map(EncodeFn enc, CUtensorMap* m, const void* ptr, int cols, int rows, int nb) {
  const cuuint64_t dims[3] = {(cuuint64_t)(nb ? 64 : cols), (cuuint64_t)rows, (cuuint64_t)cols / 64};
  const cuuint64_t strides[2] = {(cuuint64_t)cols * 2, 128};
  const cuuint32_t box[3] = {64, 32, (cuuint32_t)nb}, es[3] = {1, 1, 1};
  enc(m, CU_TENSOR_MAP_DATA_TYPE_BFLOAT16, nb ? 3 : 2, const_cast<void*>(ptr), dims, strides, box, es, CU_TENSOR_MAP_INTERLEAVE_NONE,
      CU_TENSOR_MAP_SWIZZLE_128B, CU_TENSOR_MAP_L2_PROMOTION_L2_128B, CU_TENSOR_MAP_FLOAT_OOB_FILL_NONE);
}
template <class... KA, class... A>
void launch(void (*kern)(KA...), int grid, int block, int smem, int cluster, bool pdl, A... args) {
  cudaFuncSetAttribute(kern, cudaFuncAttributeMaxDynamicSharedMemorySize, smem);
  cudaLaunchConfig_t cfg = {};
  cfg.gridDim = dim3(grid); cfg.blockDim = dim3(block); cfg.dynamicSmemBytes = smem; cfg.stream = cudaStreamPerThread;
  cudaLaunchAttribute at[2];
  int n = 0;
  if (cluster > 1) { at[n].id = cudaLaunchAttributeClusterDimension; at[n].val.clusterDim.x = cluster; at[n].val.clusterDim.y = 1; at[n].val.clusterDim.z = 1; n++; }
  if (pdl) { at[n].id = cudaLaunchAttributeProgrammaticStreamSerialization; at[n].val.programmaticStreamSerializationAllowed = 1; n++; }
  cfg.attrs = at; cfg.numAttrs = n;
  cudaLaunchKernelEx(&cfg, kern, args...);
}
template <class T> void* sym(T& s) { void* p = nullptr; cudaGetSymbolAddress(&p, s); return p; }

}

#define MODE(b) 0
extern "C" void kernel_launch(void* const* d_in, const int* in_sizes, int n_in, void* d_out, int out_size) {
  const __nv_bfloat16* x = (const __nv_bfloat16*)d_in[0];
  void* fn = nullptr; cudaDriverEntryPointQueryResult qr;
  cudaGetDriverEntryPoint("cuTensorMapEncodeTiled", &fn, cudaEnableDefault, &qr);
  EncodeFn enc = (EncodeFn)fn;

  ChainParams ch = {};
  PostParams op = {};
  for (int i = 0; i < 3; i++) {
    const cuuint64_t dims[3] = {HD, 128, 5}, strides[2] = {HD * 2, HD * 256};
    const cuuint32_t box[3] = {64, 128, 5}, es[3] = {1, 1, 1};
    enc(i == 0 ? &ch.wq : i == 1 ? &ch.wk : &ch.wv, CU_TENSOR_MAP_DATA_TYPE_BFLOAT16, 3, d_in[2 + i], dims, strides, box, es, CU_TENSOR_MAP_INTERLEAVE_NONE,
        CU_TENSOR_MAP_SWIZZLE_128B, W_PROMO, CU_TENSOR_MAP_FLOAT_OOB_FILL_NONE);
  }
  {
    const cuuint64_t dims[3] = {DM, HD, 7}, strides[2] = {DM * 2, 64};
    const cuuint32_t box[3] = {32, 64, 7}, es[3] = {1, 1, 1};
    enc(&ch.wo, CU_TENSOR_MAP_DATA_TYPE_BFLOAT16, 3, d_in[5], dims, strides, box, es, CU_TENSOR_MAP_INTERLEAVE_NONE,
        CU_TENSOR_MAP_SWIZZLE_64B, CU_TENSOR_MAP_L2_PROMOTION_L2_128B, CU_TENSOR_MAP_FLOAT_OOB_FILL_NONE);
  }
  ch.mem0 = (const __nv_bfloat16*)d_in[1];
  ch.pool = (uint8_t*)(((uintptr_t)sym(g_pool) + 8191) & ~(uintptr_t)8191); ch.kv = (uint8_t*)sym(g_kv); ch.xc = (const uint32_t*)sym(g_xc); ch.sync = (uint32_t*)sym(g_sync);
  ch.d1 = 0; ch.d1b = 0; ch.d2 = 0; ch.d2b = 0;
  make_map(enc, &op.wq, d_in[2], HD, DM, 3);
  make_map(enc, &op.wo, d_in[5], DM, HD, 5); make_map(enc, &op.wo2, d_in[5], DM, HD, 0);
  make_map(enc, &op.wb, d_in[8], 1920, DM, 5); make_map(enc, &op.wb2, d_in[8], 1920, DM, 0);
  op.gap = 17; op.share = 20; op.look = 14; op.gap2 = 0; op.pol = 1;

  const Weights wa = {{(const uint8_t*)d_in[3], (const uint8_t*)d_in[4], (const uint8_t*)d_in[2], (const uint8_t*)d_in[5]}}, none = {};
  launch(first_kernel, 132, 384, 128 * 1024, 1, false, x, (const uint4*)d_in[9], wa);
  for (int layer = 0; layer < 2; layer++) {
    ch.layer = ch.d2b = op.layer = layer;
    launch(chain_kernel, 96, 256, CH_SMEM, 3, true, ch);
    launch(post_kernel, MODE(3) ? 36 : 132, 384, OP_SMEM, 1, !MODE(1), op);
    const AbParams ab = {layer == 0 ? wa : none, (uint32_t*)sym(g_bo) + layer * 128, layer == 0 ? nullptr : (uint32_t*)d_out};
    launch(attn_b_kernel, 128, AB_T + 32, AB_SMEM, 1, true, ab);
  }
}
```

```cpp
#include <cuda_runtime.h>
#include <cuda_bf16.h>
#include <cuda.h>
#include <stdint.h>

namespace {

constexpr int SEQ = 2048, DM = 640, HD = 6144, NSEG = 64;
constexpr int SPIN_LIMIT = 1 << 20;

__device__ __align__(128) uint2 g_x[SEQ * DM / 4];
__device__ __align__(128) uint32_t g_of[SEQ * DM / 2];
__device__ __align__(128) uint4 g_wb[DM * DM / 8];
__device__ __align__(16) float2 g_stat[16 * 8 * 128];
__device__ uint32_t g_bo[8 * 32];
__device__ __align__(128) uint4 g_q[SEQ * HD / 8];
__device__ __align__(128) uint32_t g_o[SEQ * HD / 2];
constexpr int KV_BYTES = 5120, KV_M = 4096, KV_V = NSEG * KV_BYTES;
__device__ __align__(128) uint8_t g_kv[96 * 2 * NSEG * KV_BYTES];
__device__ __align__(128) uint32_t g_xc[SEQ * DM / 2];
#define OP_B4 5
#define OP_B8 9
#define OP_B16 13
#define QA_END 12
__host__ __device__ constexpr int op_split(int b) { return b < OP_B4 ? 2 : b < OP_B8 ? 4 : b < OP_B16 ? 8 : 16; }
#define AB_PF 3
#define AB_PF0 0
#define AB_PFD 5000
#define W_PROMO CU_TENSOR_MAP_L2_PROMOTION_L2_128B
#define OP_EARLY 1
#define ATT_LOOK 1
#define PR_FIN 1
#define PR_ATT 0
#define PR_OP 2
#define PRE_MAX PS
#define PRE_GAP 0u
#define OEF 0
#define BQ_HOLD 6
#define WEF 1
#define FK_REP 4
#define FK_PF 1
#define BQ_160 10
#define BQ_80 16
#define OP_160 16
__host__ __device__ constexpr int op_width(int b) { return b < OP_160 ? 320 : 160; }
__host__ __device__ constexpr int bq_width(int b) { return b < BQ_160 ? 320 : b < BQ_80 ? 160 : 80; }
__device__ __align__(128) uint2 g_part[16 * 16 * 16 * 40 * 32];
__device__ __align__(128) uint32_t g_xn[SEQ * DM / 2];
constexpr int SY_Q = 128, SY_T = 160, SY_QC = 192, SY_N = 193;
__device__ __align__(16) uint32_t g_sync[SY_N];
constexpr int NSLOT = 92;
__device__ uint32_t g_pool[(NSLOT + 2) * 2048];
__device__ int g_smpart[256], g_orient[NSLOT];
__device__ uint32_t g_smclk[256], g_smuse[256];
__device__ uint32_t g_bqkv[3 * 32 * 256 * 96];

#define ABT(L, i)
#define PST(i)
#define MODE_D(b) 0
#define DELAY(d)
#define XT(i)
#define MISS(k, n)
#define PRO(i)
#define TRACE(w)
#define ITEM(code, w)
#define TR(i, v)
#define TM(i)
#define TM1(i)
#define TMD(i, dep)
#define TMV(i, at, v)

__device__ __forceinline__ uint32_t gtime() { uint32_t c; asm volatile("mov.u32 %0, %%globaltimer_lo;" : "=r"(c) :: "memory"); return c; }
__device__ __forceinline__ uint32_t clk32() { uint32_t c; asm volatile("mov.u32 %0, %%clock;" : "=r"(c) :: "memory"); return c; }
__device__ __forceinline__ uint32_t s2u(const void* p) { return (uint32_t)__cvta_generic_to_shared(p); }
__device__ __forceinline__ uint32_t pack2(float a, float b) {
  uint32_t r; asm("cvt.rn.bf16x2.f32 %0, %1, %2;" : "=r"(r) : "f"(b), "f"(a)); return r; }
__device__ __forceinline__ float bf_lo(uint32_t w) { return __uint_as_float(w << 16); }
__device__ __forceinline__ float bf_hi(uint32_t w) { return __uint_as_float(w & 0xffff0000u); }
__device__ __forceinline__ uint2 pack4(float4 v) { return make_uint2(pack2(v.x, v.y), pack2(v.z, v.w)); }
__device__ __forceinline__ float4 unpack4(uint2 w) { return make_float4(bf_lo(w.x), bf_hi(w.x), bf_lo(w.y), bf_hi(w.y)); }
__device__ __forceinline__ float ex2(float x) { float y; asm("ex2.approx.ftz.f32 %0, %1;" : "=f"(y) : "f"(x)); return y; }

__device__ __forceinline__ void mbar_init(uint32_t bar, uint32_t n) {
  asm volatile("mbarrier.init.shared::cta.b64 [%0], %1;" :: "r"(bar), "r"(n) : "memory"); }
__device__ __forceinline__ void mbar_expect(uint32_t bar, uint32_t bytes) {
  asm volatile("mbarrier.arrive.expect_tx.shared::cta.b64 _, [%0], %1;" :: "r"(bar), "r"(bytes) : "memory"); }
__device__ __forceinline__ void mbar_arrive(uint32_t bar) {
  asm volatile("mbarrier.arrive.shared::cta.b64 _, [%0];" :: "r"(bar) : "memory"); }
__device__ __forceinline__ void mbar_wait(uint32_t bar, uint32_t ph) {
  asm volatile("{.reg .pred p; .reg .u32 n; mov.u32 n, 0;\n"
               "W: mbarrier.try_wait.parity.shared::cta.b64 p, [%0], %1; @p bra D;\n"
               "add.u32 n, n, 1; setp.gt.u32 p, n, %2; @p trap; bra W;\n"
               "D: }" :: "r"(bar), "r"(ph), "n"(SPIN_LIMIT) : "memory");
}
__device__ __forceinline__ void mbar_wait_cluster(uint32_t bar, uint32_t ph) {
  asm volatile("{.reg .pred p; .reg .u32 n; mov.u32 n, 0;\n"
               "W: mbarrier.try_wait.parity.acquire.cluster.shared::cta.b64 p, [%0], %1; @p bra D;\n"
               "add.u32 n, n, 1; setp.gt.u32 p, n, %2; @p trap; bra W;\n"
               "D: }" :: "r"(bar), "r"(ph), "n"(SPIN_LIMIT) : "memory");
}
__device__ __forceinline__ void spin_guard(int& n) {
  asm volatile("{.reg .pred p; add.s32 %0, %0, 1; setp.gt.s32 p, %0, %1; @p trap;}" : "+r"(n) : "n"(SPIN_LIMIT));
}
__device__ __forceinline__ void pdl_wait() { asm volatile("griddepcontrol.wait;" ::: "memory"); TRACE(1); }
__device__ __forceinline__ void pdl_launch() { asm volatile("griddepcontrol.launch_dependents;" ::: "memory"); }
__device__ __forceinline__ uint32_t ld_acquire(const uint32_t* p) { uint32_t v; asm volatile("ld.acquire.gpu.global.u32 %0, [%1];" : "=r"(v) : "l"(p) : "memory"); return v; }
__device__ __forceinline__ void red_release(uint32_t* p, uint32_t v) { asm volatile("red.release.gpu.global.add.u32 [%0], %1;" :: "l"(p), "r"(v) : "memory"); }
__device__ __forceinline__ void red_relaxed(uint32_t* p, uint32_t v) { asm volatile("red.relaxed.gpu.global.add.u32 [%0], %1;" :: "l"(p), "r"(v) : "memory"); }
__device__ __forceinline__ void fence_async_global() { asm volatile("fence.proxy.async.global;" ::: "memory"); }
__device__ __forceinline__ void fence_async() { asm volatile("fence.proxy.async.shared::cta;" ::: "memory"); }
__device__ __forceinline__ void bar_sync(int id, int n) { asm volatile("bar.sync %0, %1;" :: "r"(id), "r"(n) : "memory"); }
__device__ __forceinline__ void bar_arrive(int id, int n) { asm volatile("bar.arrive %0, %1;" :: "r"(id), "r"(n) : "memory"); }
__device__ __forceinline__ void tma_load(uint32_t dst, const CUtensorMap* m, int c0, int c1, uint32_t bar) {
  asm volatile("cp.async.bulk.tensor.2d.shared::cluster.global.mbarrier::complete_tx::bytes [%0], [%1, {%3, %4}], [%2];"
               :: "r"(dst), "l"(m), "r"(bar), "r"(c0), "r"(c1) : "memory"); }
template <bool STREAM = false>
__device__ __forceinline__ void tma_load3(uint32_t dst, const CUtensorMap* m, int c0, int c1, uint32_t bar) {
  if (STREAM)
    asm volatile("{.reg .b64 pol; createpolicy.fractional.L2::evict_first.b64 pol, 1.0;\n"
                 "cp.async.bulk.tensor.3d.shared::cluster.global.mbarrier::complete_tx::bytes.L2::cache_hint [%0], [%1, {%3, %4, 0}], [%2], pol;}"
                 :: "r"(dst), "l"(m), "r"(bar), "r"(c0), "r"(c1) : "memory");
  else
  asm volatile("cp.async.bulk.tensor.3d.shared::cluster.global.mbarrier::complete_tx::bytes [%0], [%1, {%3, %4, 0}], [%2];"
               :: "r"(dst), "l"(m), "r"(bar), "r"(c0), "r"(c1) : "memory"); }
__device__ __forceinline__ void tma_load3z(uint32_t dst, const CUtensorMap* m, int c1, int c2, uint32_t bar) {
  asm volatile("cp.async.bulk.tensor.3d.shared::cluster.global.mbarrier::complete_tx::bytes [%0], [%1, {0, %3, %4}], [%2];"
               :: "r"(dst), "l"(m), "r"(bar), "r"(c1), "r"(c2) : "memory"); }
__device__ __forceinline__ void tma_store(const CUtensorMap* m, uint32_t src, int c0, int c1) {
  asm volatile("cp.async.bulk.tensor.2d.global.shared::cta.bulk_group [%0, {%2, %3}], [%1];"
               :: "l"(m), "r"(src), "r"(c0), "r"(c1) : "memory"); }
__device__ __forceinline__ void tma_store_stream(const CUtensorMap* m, uint32_t src, int c0, int c1) {
  asm volatile("{.reg .b64 pol; createpolicy.fractional.L2::evict_first.b64 pol, 1.0;\n"
               "cp.async.bulk.tensor.2d.global.shared::cta.bulk_group.L2::cache_hint [%0, {%2, %3}], [%1], pol;}"
               :: "l"(m), "r"(src), "r"(c0), "r"(c1) : "memory"); }
__device__ __forceinline__ void bulk_load(uint32_t dst, const void* src, uint32_t bytes, uint32_t bar) {
  asm volatile("cp.async.bulk.shared::cluster.global.mbarrier::complete_tx::bytes [%0], [%1], %2, [%3];"
               :: "r"(dst), "l"(src), "r"(bytes), "r"(bar) : "memory"); }
__device__ __forceinline__ void bulk_load_last(uint32_t dst, const void* src, uint32_t bytes, uint32_t bar) {
  asm volatile("{.reg .b64 pol; createpolicy.fractional.L2::evict_first.b64 pol, 1.0;\n"
               "cp.async.bulk.shared::cluster.global.mbarrier::complete_tx::bytes.L2::cache_hint [%0], [%1], %2, [%3], pol;}"
               :: "r"(dst), "l"(src), "r"(bytes), "r"(bar) : "memory"); }
__device__ __forceinline__ void tma_load_last(uint32_t dst, const CUtensorMap* m, int c0, int c1, uint32_t bar) {
  asm volatile("{.reg .b64 pol; createpolicy.fractional.L2::evict_first.b64 pol, 1.0;\n"
               "cp.async.bulk.tensor.2d.shared::cluster.global.mbarrier::complete_tx::bytes.L2::cache_hint [%0], [%1, {%3, %4}], [%2], pol;}"
               :: "r"(dst), "l"(m), "r"(bar), "r"(c0), "r"(c1) : "memory"); }
__device__ __forceinline__ void bulk_send(uint32_t dst, uint32_t src, uint32_t bytes, uint32_t bar) {
  asm volatile("cp.async.bulk.shared::cluster.shared::cta.mbarrier::complete_tx::bytes [%0], [%1], %2, [%3];"
               :: "r"(dst), "r"(src), "r"(bytes), "r"(bar) : "memory"); }
__device__ __forceinline__ void bulk_store(void* dst, uint32_t src, uint32_t bytes) {
  asm volatile("cp.async.bulk.global.shared::cta.bulk_group [%0], [%1], %2;" :: "l"(dst), "r"(src), "r"(bytes) : "memory"); }
__device__ __forceinline__ void bulk_commit() { asm volatile("cp.async.bulk.commit_group;" ::: "memory"); }
template <int N> __device__ __forceinline__ void bulk_wait_read() { asm volatile("cp.async.bulk.wait_group.read %0;" :: "n"(N) : "memory"); }
template <int N> __device__ __forceinline__ void bulk_wait() { asm volatile("cp.async.bulk.wait_group %0;" :: "n"(N) : "memory"); }

__device__ __forceinline__ uint64_t mkdesc(uint32_t addr, uint32_t lbo, uint32_t sbo, uint32_t sw) {
  return (uint64_t)((addr & 0x3FFFF) >> 4) | ((uint64_t)(lbo >> 4) << 16) | ((uint64_t)(sbo >> 4) << 32) | ((uint64_t)sw << 62); }
__device__ __forceinline__ void wg_fence() { asm volatile("wgmma.fence.sync.aligned;" ::: "memory"); }
__device__ __forceinline__ void wg_commit() { asm volatile("wgmma.commit_group.sync.aligned;" ::: "memory"); }
template <int N> __device__ __forceinline__ void wg_wait() { asm volatile("wgmma.wait_group.sync.aligned %0;" :: "n"(N) : "memory"); }
template <int N> __device__ __forceinline__ void reg_fence(float* d) {
#pragma unroll
  for (int i = 0; i < N; i++) asm volatile("" : "+f"(d[i]) :: "memory");
}

__device__ __forceinline__ void mma16(float* d, uint32_t a0, uint32_t a1, uint32_t a2, uint32_t a3, uint32_t b0, uint32_t b1) {
  asm volatile("mma.sync.aligned.m16n8k16.row.col.f32.bf16.bf16.f32 {%0,%1,%2,%3},{%4,%5,%6,%7},{%8,%9},{%0,%1,%2,%3};"
               : "+f"(d[0]), "+f"(d[1]), "+f"(d[2]), "+f"(d[3]) : "r"(a0), "r"(a1), "r"(a2), "r"(a3), "r"(b0), "r"(b1)); }
__device__ __forceinline__ void mma8(float* d, uint32_t a0, uint32_t a1, uint32_t b0) {
  asm volatile("mma.sync.aligned.m16n8k8.row.col.f32.bf16.bf16.f32 {%0,%1,%2,%3},{%4,%5},{%6},{%0,%1,%2,%3};"
               : "+f"(d[0]), "+f"(d[1]), "+f"(d[2]), "+f"(d[3]) : "r"(a0), "r"(a1), "r"(b0)); }
__device__ __forceinline__ void ldsm4(uint32_t* r, uint32_t a) {
  asm volatile("ldmatrix.sync.aligned.m8n8.x4.shared.b16 {%0,%1,%2,%3},[%4];" : "=r"(r[0]), "=r"(r[1]), "=r"(r[2]), "=r"(r[3]) : "r"(a) : "memory"); }
__device__ __forceinline__ void ldsm4t(uint32_t* r, uint32_t a) {
  asm volatile("ldmatrix.sync.aligned.m8n8.x4.trans.shared.b16 {%0,%1,%2,%3},[%4];" : "=r"(r[0]), "=r"(r[1]), "=r"(r[2]), "=r"(r[3]) : "r"(a) : "memory"); }
__device__ __forceinline__ void ldsm2(uint32_t* r, uint32_t a) {
  asm volatile("ldmatrix.sync.aligned.m8n8.x2.shared.b16 {%0,%1},[%2];" : "=r"(r[0]), "=r"(r[1]) : "r"(a) : "memory"); }
__device__ __forceinline__ void stsm4(uint32_t a, uint32_t r0, uint32_t r1, uint32_t r2, uint32_t r3) {
  asm volatile("stmatrix.sync.aligned.m8n8.x4.shared.b16 [%0], {%1,%2,%3,%4};" :: "r"(a), "r"(r0), "r"(r1), "r"(r2), "r"(r3) : "memory"); }
__device__ __forceinline__ void stsm2t(uint32_t a, uint32_t r0, uint32_t r1) {
  asm volatile("stmatrix.sync.aligned.m8n8.x2.trans.shared.b16 [%0], {%1,%2};" :: "r"(a), "r"(r0), "r"(r1) : "memory"); }
__device__ __forceinline__ void stsm4t(uint32_t a, uint32_t r0, uint32_t r1, uint32_t r2, uint32_t r3) {
  asm volatile("stmatrix.sync.aligned.m8n8.x4.trans.shared.b16 [%0], {%1,%2,%3,%4};" :: "r"(a), "r"(r0), "r"(r1), "r"(r2), "r"(r3) : "memory"); }
__device__ __forceinline__ void st_async128(uint32_t a, uint4 v, uint32_t bar) {
  asm volatile("st.async.shared::cluster.mbarrier::complete_tx::bytes.v4.b32 [%0], {%1,%2,%3,%4}, [%5];" :: "r"(a), "r"(v.x), "r"(v.y), "r"(v.z), "r"(v.w), "r"(bar) : "memory"); }
__device__ __forceinline__ void sts32(uint32_t a, uint32_t v) { asm volatile("st.shared.b32 [%0], %1;" :: "r"(a), "r"(v) : "memory"); }
__device__ __forceinline__ void sts64f(uint32_t a, float x, float y) { asm volatile("st.shared.v2.f32 [%0], {%1,%2};" :: "r"(a), "f"(x), "f"(y) : "memory"); }
__device__ __forceinline__ void sts128(uint32_t a, uint4 v) {
  asm volatile("st.shared.v4.b32 [%0], {%1,%2,%3,%4};" :: "r"(a), "r"(v.x), "r"(v.y), "r"(v.z), "r"(v.w) : "memory"); }
__device__ __forceinline__ void sts128f(uint32_t a, float x, float y, float z, float w) {
  asm volatile("st.shared.v4.f32 [%0], {%1,%2,%3,%4};" :: "r"(a), "f"(x), "f"(y), "f"(z), "f"(w) : "memory"); }
__device__ __forceinline__ float lds32f(uint32_t a) { float v; asm volatile("ld.shared.f32 %0, [%1];" : "=f"(v) : "r"(a) : "memory"); return v; }
__device__ __forceinline__ float2 lds64f(uint32_t a) { float2 v; asm volatile("ld.shared.v2.f32 {%0,%1}, [%2];" : "=f"(v.x), "=f"(v.y) : "r"(a) : "memory"); return v; }
__device__ __forceinline__ float4 lds128f(uint32_t a) {
  float4 v; asm volatile("ld.shared.v4.f32 {%0,%1,%2,%3}, [%4];" : "=f"(v.x), "=f"(v.y), "=f"(v.z), "=f"(v.w) : "r"(a) : "memory"); return v; }
__device__ __forceinline__ uint4 lds128(uint32_t a) {
  uint4 v; asm volatile("ld.shared.v4.b32 {%0,%1,%2,%3}, [%4];" : "=r"(v.x), "=r"(v.y), "=r"(v.z), "=r"(v.w) : "r"(a) : "memory"); return v; }
__device__ __forceinline__ uint4 ldg_strong128(const void* p) {
  uint4 v; asm volatile("ld.relaxed.gpu.global.v4.u32 {%0,%1,%2,%3}, [%4];" : "=r"(v.x), "=r"(v.y), "=r"(v.z), "=r"(v.w) : "l"(p) : "memory"); return v; }
__device__ __forceinline__ void stg_strong32(void* p, uint32_t v) { asm volatile("st.relaxed.gpu.global.u32 [%0], %1;" :: "l"(p), "r"(v) : "memory"); }
__device__ __forceinline__ void stg_strong16(void* p, uint32_t v) { asm volatile("st.relaxed.gpu.global.u16 [%0], %1;" :: "l"(p), "h"((uint16_t)v) : "memory"); }
__device__ __forceinline__ void stg_strong128(void* p, uint4 v) {
  asm volatile("st.relaxed.gpu.global.v4.u32 [%0], {%1,%2,%3,%4};" :: "l"(p), "r"(v.x), "r"(v.y), "r"(v.z), "r"(v.w) : "memory"); }
__device__ __forceinline__ uint32_t mapa(uint32_t a, uint32_t r) {
  uint32_t o; asm("mapa.shared::cluster.u32 %0, %1, %2;" : "=r"(o) : "r"(a), "r"(r)); return o; }
__device__ __forceinline__ void st_async2f(uint32_t a, float x, float y, uint32_t bar) {
  asm volatile("st.async.shared::cluster.mbarrier::complete_tx::bytes.v2.f32 [%0], {%1,%2}, [%3];" :: "r"(a), "f"(x), "f"(y), "r"(bar) : "memory"); }
__device__ __forceinline__ void st_async32(uint32_t a, uint32_t x, uint32_t bar) {
  asm volatile("st.async.shared::cluster.mbarrier::complete_tx::bytes.b32 [%0], %1, [%2];" :: "r"(a), "r"(x), "r"(bar) : "memory"); }
__device__ __forceinline__ uint32_t lds32(uint32_t a) { uint32_t v; asm volatile("ld.shared.b32 %0, [%1];" : "=r"(v) : "r"(a) : "memory"); return v; }
__device__ __forceinline__ void st_async64(uint32_t a, uint32_t x, uint32_t y, uint32_t bar) {
  asm volatile("st.async.shared::cluster.mbarrier::complete_tx::bytes.v2.b32 [%0], {%1,%2}, [%3];" :: "r"(a), "r"(x), "r"(y), "r"(bar) : "memory"); }
__device__ __forceinline__ uint2 lds64(uint32_t a) { uint2 v; asm volatile("ld.shared.v2.b32 {%0,%1}, [%2];" : "=r"(v.x), "=r"(v.y) : "r"(a) : "memory"); return v; }
__device__ __forceinline__ void sts64(uint32_t a, uint32_t x, uint32_t y) { asm volatile("st.shared.v2.b32 [%0], {%1,%2};" :: "r"(a), "r"(x), "r"(y) : "memory"); }
__device__ __forceinline__ uint32_t ldg_strong32(const void* p) { uint32_t v; asm volatile("ld.relaxed.gpu.global.u32 %0, [%1];" : "=r"(v) : "l"(p) : "memory"); return v; }
__device__ __forceinline__ uint32_t transpose8(uint32_t x) { uint32_t r; asm volatile("movmatrix.sync.aligned.m8n8.trans.b16 %0, %1;" : "=r"(r) : "r"(x)); return r; }
__device__ __forceinline__ uint32_t hadd2(uint32_t a, uint32_t b) { uint32_t r; asm("add.rn.bf16x2 %0, %1, %2;" : "=r"(r) : "r"(a), "r"(b)); return r; }
__device__ __forceinline__ uint32_t min4(uint4 v) { return min(__vimin3_u32(v.x, v.y, v.z), v.w); }

__device__ __forceinline__ void wg_ss192_01(float* d, uint64_t da, uint64_t db, int sd) {
  asm volatile("{.reg .pred p; setp.ne.b32 p, %98, 0;\n"
    "wgmma.mma_async.sync.aligned.m64n192k16.f32.bf16.bf16 {%0,%1,%2,%3,%4,%5,%6,%7,%8,%9,%10,%11,%12,%13,%14,%15,%16,%17,%18,%19,%20,%21,%22,%23,%24,%25,%26,%27,%28,%29,%30,%31,%32,%33,%34,%35,%36,%37,%38,%39,%40,%41,%42,%43,%44,%45,%46,%47,%48,%49,%50,%51,%52,%53,%54,%55,%56,%57,%58,%59,%60,%61,%62,%63,%64,%65,%66,%67,%68,%69,%70,%71,%72,%73,%74,%75,%76,%77,%78,%79,%80,%81,%82,%83,%84,%85,%86,%87,%88,%89,%90,%91,%92,%93,%94,%95}, %96, %97, p, 1, 1, 0, 1;}"
    : "+f"(d[0]),"+f"(d[1]),"+f"(d[2]),"+f"(d[3]),"+f"(d[4]),"+f"(d[5]),"+f"(d[6]),"+f"(d[7]),"+f"(d[8]),"+f"(d[9]),"+f"(d[10]),"+f"(d[11]),"+f"(d[12]),"+f"(d[13]),"+f"(d[14]),"+f"(d[15]),"+f"(d[16]),"+f"(d[17]),"+f"(d[18]),"+f"(d[19]),"+f"(d[20]),"+f"(d[21]),"+f"(d[22]),"+f"(d[23]),"+f"(d[24]),"+f"(d[25]),"+f"(d[26]),"+f"(d[27]),"+f"(d[28]),"+f"(d[29]),"+f"(d[30]),"+f"(d[31]),"+f"(d[32]),"+f"(d[33]),"+f"(d[34]),"+f"(d[35]),"+f"(d[36]),"+f"(d[37]),"+f"(d[38]),"+f"(d[39]),"+f"(d[40]),"+f"(d[41]),"+f"(d[42]),"+f"(d[43]),"+f"(d[44]),"+f"(d[45]),"+f"(d[46]),"+f"(d[47]),"+f"(d[48]),"+f"(d[49]),"+f"(d[50]),"+f"(d[51]),"+f"(d[52]),"+f"(d[53]),"+f"(d[54]),"+f"(d[55]),"+f"(d[56]),"+f"(d[57]),"+f"(d[58]),"+f"(d[59]),"+f"(d[60]),"+f"(d[61]),"+f"(d[62]),"+f"(d[63]),"+f"(d[64]),"+f"(d[65]),"+f"(d[66]),"+f"(d[67]),"+f"(d[68]),"+f"(d[69]),"+f"(d[70]),"+f"(d[71]),"+f"(d[72]),"+f"(d[73]),"+f"(d[74]),"+f"(d[75]),"+f"(d[76]),"+f"(d[77]),"+f"(d[78]),"+f"(d[79]),"+f"(d[80]),"+f"(d[81]),"+f"(d[82]),"+f"(d[83]),"+f"(d[84]),"+f"(d[85]),"+f"(d[86]),"+f"(d[87]),"+f"(d[88]),"+f"(d[89]),"+f"(d[90]),"+f"(d[91]),"+f"(d[92]),"+f"(d[93]),"+f"(d[94]),"+f"(d[95])
    : "l"(da), "l"(db), "r"(sd));
}
__device__ __forceinline__ void wg_ss128_01(float* d, uint64_t da, uint64_t db, int sd) {
  asm volatile("{.reg .pred p; setp.ne.b32 p, %66, 0;\n"
    "wgmma.mma_async.sync.aligned.m64n128k16.f32.bf16.bf16 {%0,%1,%2,%3,%4,%5,%6,%7,%8,%9,%10,%11,%12,%13,%14,%15,%16,%17,%18,%19,%20,%21,%22,%23,%24,%25,%26,%27,%28,%29,%30,%31,%32,%33,%34,%35,%36,%37,%38,%39,%40,%41,%42,%43,%44,%45,%46,%47,%48,%49,%50,%51,%52,%53,%54,%55,%56,%57,%58,%59,%60,%61,%62,%63}, %64, %65, p, 1, 1, 0, 1;}"
    : "+f"(d[0]),"+f"(d[1]),"+f"(d[2]),"+f"(d[3]),"+f"(d[4]),"+f"(d[5]),"+f"(d[6]),"+f"(d[7]),"+f"(d[8]),"+f"(d[9]),"+f"(d[10]),"+f"(d[11]),"+f"(d[12]),"+f"(d[13]),"+f"(d[14]),"+f"(d[15]),"+f"(d[16]),"+f"(d[17]),"+f"(d[18]),"+f"(d[19]),"+f"(d[20]),"+f"(d[21]),"+f"(d[22]),"+f"(d[23]),"+f"(d[24]),"+f"(d[25]),"+f"(d[26]),"+f"(d[27]),"+f"(d[28]),"+f"(d[29]),"+f"(d[30]),"+f"(d[31]),"+f"(d[32]),"+f"(d[33]),"+f"(d[34]),"+f"(d[35]),"+f"(d[36]),"+f"(d[37]),"+f"(d[38]),"+f"(d[39]),"+f"(d[40]),"+f"(d[41]),"+f"(d[42]),"+f"(d[43]),"+f"(d[44]),"+f"(d[45]),"+f"(d[46]),"+f"(d[47]),"+f"(d[48]),"+f"(d[49]),"+f"(d[50]),"+f"(d[51]),"+f"(d[52]),"+f"(d[53]),"+f"(d[54]),"+f"(d[55]),"+f"(d[56]),"+f"(d[57]),"+f"(d[58]),"+f"(d[59]),"+f"(d[60]),"+f"(d[61]),"+f"(d[62]),"+f"(d[63])
    : "l"(da), "l"(db), "r"(sd));
}
__device__ __forceinline__ void wg_ss160_01(float* d, uint64_t da, uint64_t db, int sd) {
  asm volatile("{.reg .pred p; setp.ne.b32 p, %82, 0;\n"
    "wgmma.mma_async.sync.aligned.m64n160k16.f32.bf16.bf16 {%0,%1,%2,%3,%4,%5,%6,%7,%8,%9,%10,%11,%12,%13,%14,%15,%16,%17,%18,%19,%20,%21,%22,%23,%24,%25,%26,%27,%28,%29,%30,%31,%32,%33,%34,%35,%36,%37,%38,%39,%40,%41,%42,%43,%44,%45,%46,%47,%48,%49,%50,%51,%52,%53,%54,%55,%56,%57,%58,%59,%60,%61,%62,%63,%64,%65,%66,%67,%68,%69,%70,%71,%72,%73,%74,%75,%76,%77,%78,%79}, %80, %81, p, 1, 1, 0, 1;}"
    : "+f"(d[0]),"+f"(d[1]),"+f"(d[2]),"+f"(d[3]),"+f"(d[4]),"+f"(d[5]),"+f"(d[6]),"+f"(d[7]),"+f"(d[8]),"+f"(d[9]),"+f"(d[10]),"+f"(d[11]),"+f"(d[12]),"+f"(d[13]),"+f"(d[14]),"+f"(d[15]),"+f"(d[16]),"+f"(d[17]),"+f"(d[18]),"+f"(d[19]),"+f"(d[20]),"+f"(d[21]),"+f"(d[22]),"+f"(d[23]),"+f"(d[24]),"+f"(d[25]),"+f"(d[26]),"+f"(d[27]),"+f"(d[28]),"+f"(d[29]),"+f"(d[30]),"+f"(d[31]),"+f"(d[32]),"+f"(d[33]),"+f"(d[34]),"+f"(d[35]),"+f"(d[36]),"+f"(d[37]),"+f"(d[38]),"+f"(d[39]),"+f"(d[40]),"+f"(d[41]),"+f"(d[42]),"+f"(d[43]),"+f"(d[44]),"+f"(d[45]),"+f"(d[46]),"+f"(d[47]),"+f"(d[48]),"+f"(d[49]),"+f"(d[50]),"+f"(d[51]),"+f"(d[52]),"+f"(d[53]),"+f"(d[54]),"+f"(d[55]),"+f"(d[56]),"+f"(d[57]),"+f"(d[58]),"+f"(d[59]),"+f"(d[60]),"+f"(d[61]),"+f"(d[62]),"+f"(d[63]),"+f"(d[64]),"+f"(d[65]),"+f"(d[66]),"+f"(d[67]),"+f"(d[68]),"+f"(d[69]),"+f"(d[70]),"+f"(d[71]),"+f"(d[72]),"+f"(d[73]),"+f"(d[74]),"+f"(d[75]),"+f"(d[76]),"+f"(d[77]),"+f"(d[78]),"+f"(d[79])
    : "l"(da), "l"(db), "r"(sd));
}
__device__ __forceinline__ void wg_ss80_01(float* d, uint64_t da, uint64_t db, int sd) {
  asm volatile("{.reg .pred p; setp.ne.b32 p, %42, 0;\n"
    "wgmma.mma_async.sync.aligned.m64n80k16.f32.bf16.bf16 {%0,%1,%2,%3,%4,%5,%6,%7,%8,%9,%10,%11,%12,%13,%14,%15,%16,%17,%18,%19,%20,%21,%22,%23,%24,%25,%26,%27,%28,%29,%30,%31,%32,%33,%34,%35,%36,%37,%38,%39}, %40, %41, p, 1, 1, 0, 1;}"
    : "+f"(d[0]),"+f"(d[1]),"+f"(d[2]),"+f"(d[3]),"+f"(d[4]),"+f"(d[5]),"+f"(d[6]),"+f"(d[7]),"+f"(d[8]),"+f"(d[9]),"+f"(d[10]),"+f"(d[11]),"+f"(d[12]),"+f"(d[13]),"+f"(d[14]),"+f"(d[15]),"+f"(d[16]),"+f"(d[17]),"+f"(d[18]),"+f"(d[19]),"+f"(d[20]),"+f"(d[21]),"+f"(d[22]),"+f"(d[23]),"+f"(d[24]),"+f"(d[25]),"+f"(d[26]),"+f"(d[27]),"+f"(d[28]),"+f"(d[29]),"+f"(d[30]),"+f"(d[31]),"+f"(d[32]),"+f"(d[33]),"+f"(d[34]),"+f"(d[35]),"+f"(d[36]),"+f"(d[37]),"+f"(d[38]),"+f"(d[39])
    : "l"(da), "l"(db), "r"(sd));
}
__device__ __forceinline__ void wg_rs32_00(float* d, uint32_t a0, uint32_t a1, uint32_t a2, uint32_t a3, uint64_t db, int sd) {
  asm volatile("{.reg .pred p; setp.ne.b32 p, %21, 0;\n"
    "wgmma.mma_async.sync.aligned.m64n32k16.f32.bf16.bf16 {%0,%1,%2,%3,%4,%5,%6,%7,%8,%9,%10,%11,%12,%13,%14,%15}, {%16,%17,%18,%19}, %20, p, 1, 1, 0;}"
    : "+f"(d[0]),"+f"(d[1]),"+f"(d[2]),"+f"(d[3]),"+f"(d[4]),"+f"(d[5]),"+f"(d[6]),"+f"(d[7]),"+f"(d[8]),"+f"(d[9]),"+f"(d[10]),"+f"(d[11]),"+f"(d[12]),"+f"(d[13]),"+f"(d[14]),"+f"(d[15])
    : "r"(a0), "r"(a1), "r"(a2), "r"(a3), "l"(db), "r"(sd));
}
__device__ __forceinline__ void wg_rs64_00(float* d, uint32_t a0, uint32_t a1, uint32_t a2, uint32_t a3, uint64_t db, int sd) {
  asm volatile("{.reg .pred p; setp.ne.b32 p, %37, 0;\n"
    "wgmma.mma_async.sync.aligned.m64n64k16.f32.bf16.bf16 {%0,%1,%2,%3,%4,%5,%6,%7,%8,%9,%10,%11,%12,%13,%14,%15,%16,%17,%18,%19,%20,%21,%22,%23,%24,%25,%26,%27,%28,%29,%30,%31}, {%32,%33,%34,%35}, %36, p, 1, 1, 0;}"
    : "+f"(d[0]),"+f"(d[1]),"+f"(d[2]),"+f"(d[3]),"+f"(d[4]),"+f"(d[5]),"+f"(d[6]),"+f"(d[7]),"+f"(d[8]),"+f"(d[9]),"+f"(d[10]),"+f"(d[11]),"+f"(d[12]),"+f"(d[13]),"+f"(d[14]),"+f"(d[15]),"+f"(d[16]),"+f"(d[17]),"+f"(d[18]),"+f"(d[19]),"+f"(d[20]),"+f"(d[21]),"+f"(d[22]),"+f"(d[23]),"+f"(d[24]),"+f"(d[25]),"+f"(d[26]),"+f"(d[27]),"+f"(d[28]),"+f"(d[29]),"+f"(d[30]),"+f"(d[31])
    : "r"(a0), "r"(a1), "r"(a2), "r"(a3), "l"(db), "r"(sd));
}
__device__ __forceinline__ void wg_rs24_01(float* d, uint32_t a0, uint32_t a1, uint32_t a2, uint32_t a3, uint64_t db, int sd) {
  asm volatile("{.reg .pred p; setp.ne.b32 p, %17, 0;\n"
    "wgmma.mma_async.sync.aligned.m64n24k16.f32.bf16.bf16 {%0,%1,%2,%3,%4,%5,%6,%7,%8,%9,%10,%11}, {%12,%13,%14,%15}, %16, p, 1, 1, 1;}"
    : "+f"(d[0]),"+f"(d[1]),"+f"(d[2]),"+f"(d[3]),"+f"(d[4]),"+f"(d[5]),"+f"(d[6]),"+f"(d[7]),"+f"(d[8]),"+f"(d[9]),"+f"(d[10]),"+f"(d[11])
    : "r"(a0), "r"(a1), "r"(a2), "r"(a3), "l"(db), "r"(sd));
}

#define AB_POLY 0xae
__device__ __forceinline__ constexpr bool poly_group(int group) { return (AB_POLY >> (group & 7)) & 1; }

template <int V> struct Int { static constexpr int value = V; };

template <int NG>
__device__ __forceinline__ void ln_stats(const float4 (&v)[NG][5], uint32_t scratch, float (&mean)[NG], float (&rs)[NG]) {
  const int warp = threadIdx.x >> 5, lane = threadIdx.x & 31;
#pragma unroll
  for (int r = 0; r < NG; r++) {
    float s = 0.f, q = 0.f;
#pragma unroll
    for (int i = 0; i < 5; i++) s += (v[r][i].x + v[r][i].y) + (v[r][i].z + v[r][i].w);
    s += __shfl_xor_sync(~0u, s, 1); s += __shfl_xor_sync(~0u, s, 2);
    s *= 1.f / 80;
#pragma unroll
    for (int i = 0; i < 5; i++) {
      const float x = v[r][i].x - s, y = v[r][i].y - s, z = v[r][i].z - s, w = v[r][i].w - s;
      q += (x * x + y * y) + (z * z + w * w);
    }
    q += __shfl_xor_sync(~0u, q, 1); q += __shfl_xor_sync(~0u, q, 2);
    mean[r] = s; rs[r] = q;
  }
  bar_sync(1, 256);
  if ((lane & 3) == 0) {
#pragma unroll
    for (int r = 0; r < NG; r++) sts64f(scratch + r * 512 + lane * 16 + warp * 8, mean[r], rs[r]);
  }
  bar_sync(1, 256);
#pragma unroll
  for (int r = 0; r < NG; r++) {
    const float4 e = lds128f(scratch + r * 512 + lane * 16);
    float t = e.x + e.z;
    t += __shfl_xor_sync(~0u, t, 1); t += __shfl_xor_sync(~0u, t, 2);
    t *= 0.125f;
    float q = e.y + e.w + 80.f * ((e.x - t) * (e.x - t) + (e.z - t) * (e.z - t));
    q += __shfl_xor_sync(~0u, q, 1); q += __shfl_xor_sync(~0u, q, 2);
    mean[r] = t; rs[r] = rsqrtf(q * (1.f / DM) + 1e-5f);
  }
}

__device__ __forceinline__ void ln_store(const uint32_t (&w)[2][5][2], int tile, int u0, bool live = true) {
  const int lane = threadIdx.x & 31;
  uint32_t* xc = g_xc + ((tile >> 1) * 40 + u0) * 256 + (tile & 1) * 64 + lane;
#pragma unroll
  for (int i = 0; i < 20; i++) if (live) xc[(i >> 1) * 128 + (i & 1) * 32] = w[i & 1][i >> 2][i >> 1 & 1];
#pragma unroll
  for (int i = 0; i < 5; i++) {
    const int u = u0 + i;
    uint32_t* xn = g_xn + (((tile >> 3) * 20 + (u >> 1)) * 16 + (tile & 1) * 8 + (tile & 6)) * 128 + (u & 1) * 64 + lane;
#pragma unroll
    for (int r = 0; r < 2; r++) if (live) { xn[r * 128] = w[r][i][0]; xn[r * 128 + 32] = w[r][i][1]; }
  }
}
__device__ __forceinline__ void wait_count(const uint32_t* c, uint32_t n) {
  int spin = 0;
  while ((ld_acquire(c) & 0xffff) < n) { __nanosleep(32); spin_guard(spin); }
}

__device__ __forceinline__ uint8_t* pool_at(uint32_t off) {
  return reinterpret_cast<uint8_t*>((reinterpret_cast<uintptr_t>(g_pool) + 8191) & ~(uintptr_t)8191) + off; }
struct Weights { const uint8_t* w[4]; };
__device__ __forceinline__ void prefetch_weights(const Weights& p, int i) {
  if (blockIdx.x < 128) asm volatile("cp.async.bulk.prefetch.L2.global [%0], 61440;" :: "l"(p.w[i] + (size_t)blockIdx.x * 61440) : "memory");
}
__global__ void __launch_bounds__(384) first_kernel(const __nv_bfloat16* __restrict__ xin, const uint4* __restrict__ wb, const __grid_constant__ Weights wa) {
  __shared__ __align__(16) float scratch[256];
  __shared__ uint32_t lat[4];
  const int warp = threadIdx.x >> 5, lane = threadIdx.x & 31, cta = blockIdx.x;
  TRACE(0);
  pdl_launch();
  if (warp >= 8) {
    if (warp < 10 || cta < NSLOT) {
      uint32_t* q = reinterpret_cast<uint32_t*>(pool_at((warp < 10 ? NSLOT : cta) * 8192 + (warp & 1) * 4096)) + (warp < 10 ? (cta & 127) * 8 : 0);
      if (lane < 8) stg_strong32(q + lane, 0u);
      uint32_t best = ~0u;
      if (lane == 0) {
        for (int r = 0; r < FK_REP; r++) {
          uint32_t t0, t1, v;
          asm volatile("mov.u32 %0, %%clock;" : "=r"(t0) :: "memory");
          asm volatile("atom.relaxed.gpu.global.exch.b32 %0, [%1], 0;" : "=r"(v) : "l"(q) : "memory");
          asm volatile("{.reg .u32 t; add.u32 t, %1, 1; mov.u32 %0, %%clock; sub.u32 %0, %0, %1;}" : "=r"(t1) : "r"(__shfl_sync(1u, v, 0)) : "memory");
          best = min(best, t1 - t0);
        }
        lat[warp - 8] = best;
      }
    }
    __syncwarp();
    bar_sync(2, cta < 128 ? 384 : 128);
    if (threadIdx.x == 288) for (int i = 0; i < FK_PF; i++) prefetch_weights(wa, i);
    if (threadIdx.x == 256) {
      const int part = lat[0] < lat[1] ? 0 : 1;
      uint32_t smid; asm("mov.u32 %0, %%smid;" : "=r"(smid));
      g_smpart[smid & 255] = part;
      g_smclk[smid & 255] = clk32() - gtime() * 2;
      g_smuse[smid & 255] = 0;
      if (cta < NSLOT) g_orient[cta] = lat[2] < lat[3] ? part : 1 - part;
    }
  } else if (cta < 128) {
    float4 v[2][5];
#pragma unroll
    for (int r = 0; r < 2; r++)
#pragma unroll
      for (int i = 0; i < 5; i++) {
        const uint32_t* src = reinterpret_cast<const uint32_t*>(xin) + (cta * 16 + r * 8 + (lane >> 2)) * (DM / 2) + warp * 40 + i * 8 + (lane & 3);
        const uint32_t a = src[0], b = src[4];
        v[r][i] = make_float4(bf_lo(a), bf_hi(a), bf_lo(b), bf_hi(b));
      }
    uint4 w8[2];
#pragma unroll
    for (int i = 0; i < 2; i++) w8[i] = wb[cta * 400 + min(i * 256 + threadIdx.x, 399)];
    float mean[2], rs[2];
    ln_stats<2>(v, s2u(scratch), mean, rs);
    bar_sync(2, 384);
    ABT(2, 2);
    if (threadIdx.x < 128) g_stat[cta * 128 + threadIdx.x] = make_float2(0.f, 0.f);
#pragma unroll
    for (int i = 0; i < 10; i++) g_x[((cta * 2 + i / 5) * 40 + warp * 5 + i % 5) * 32 + lane] = pack4(v[i / 5][i % 5]);
    uint32_t w[2][5][2];
#pragma unroll
    for (int i = 0; i < 10; i++) {
      const float4 t = v[i / 5][i % 5];
      const float m = mean[i / 5], q = rs[i / 5];
      w[i / 5][i % 5][0] = pack2((t.x - m) * q, (t.y - m) * q); w[i / 5][i % 5][1] = pack2((t.z - m) * q, (t.w - m) * q);
    }
    ln_store(w, cta, warp * 5);
    ABT(2, 3);
#pragma unroll
    for (int i = 0; i < 2; i++) {
      const int e = cta * 400 + min(i * 256 + threadIdx.x, 399), k = e / 80, n = e - k * 80, cg = n / 10;
      g_wb[((cg * 80 + (k >> 3)) * 10 + n - cg * 10) * 8 + (k & 7)] = w8[i];
    }
  } else if (cta == 128) {
    g_bo[threadIdx.x] = 0;
  }
  TRACE(2);
}

struct ChainParams {
  CUtensorMap wq, wk, wv, wo;
  const __nv_bfloat16* mem0;
  uint8_t *pool, *kv;
  const uint32_t* xc;
  uint32_t* sync;
  int layer;
  int d0, d3, d1, d1b, d2, d2b, mode;
};
constexpr int CH_WQ = 0, CH_WO = 81920, CH_X = CH_WO + 86016, CH_M = CH_X + 20480, CH_KT = CH_X + 40960, CH_VT = CH_KT + 4096,
              CH_PS = CH_VT + 4096, CH_QK = CH_PS + 4096, CH_VP = CH_QK + 4096, CH_SX = CH_VP + 1024, CH_O = CH_SX + 2304, CH_ID = CH_O + 3072,
              CH_BAR = CH_ID + 512;
constexpr int CH_SMEM = CH_BAR + 256;
constexpr int CH_BASE = 1024;
#define CH_VK0 8
#define CH_VK1 20
#define CH_L0 4
#define CH_LR 4
#define NOX 0
#define CH_XA 1
#define CH_XB 4
#define CH_W1 3
#define CH_W2 17
#define CH_W3 26
#define CH_R2 8
#define CH_VA 16
#define CH_EX 1
#define CH_KD 0
#define CH_RP 1
#define CH_KF 10
#define CH_LO 0
#define CH_LR1 4
#define CH_KP 0
#define CH_KM 0
#define CH_WE 0
#define CH_SP 1
#define CH_KW 3
#define CH_RB 0
#define CH_RC 8
#define CH_D0 200
#define CH_D1 450
#define CH_D2 300
#define CH_R1 4
#define CH_TW 12
__device__ __forceinline__ uint32_t opaque(uint32_t x) { return __shfl_sync(~0u, x, threadIdx.x & 31); }
__device__ __forceinline__ uint32_t nz(uint32_t x) { uint32_t r; asm("max.u32 %0, %1, 1;" : "=r"(r) : "r"(x)); return r; }
__device__ __forceinline__ uint32_t pack_tag(float lo, float hi, uint32_t tag, uint32_t mask) {
  uint32_t r;
  asm("lop3.b32 %0, %1, %2, %3, 0xD8;" : "=r"(r) : "r"(pack2(lo, hi)), "r"(tag), "r"(mask));
  return r;
}
__device__ __forceinline__ uint32_t differ(uint32_t a, uint32_t b, uint32_t t) { uint32_t r; asm("lop3.b32 %0, %1, %2, %3, 0x7E;" : "=r"(r) : "r"(a), "r"(b), "r"(t)); return r; }
__device__ __forceinline__ void mbar_wait_hot(uint32_t bar, uint32_t ph) {
  uint32_t ok;
  asm volatile("{.reg .pred p; mbarrier.try_wait.parity.shared::cta.b64 p, [%1], %2; selp.u32 %0, 1, 0, p;}" : "=r"(ok) : "r"(bar), "r"(ph) : "memory");
  if (__builtin_expect(!ok, 0)) mbar_wait(bar, ph);
}
__device__ __forceinline__ bool elect() {
  uint32_t r; asm volatile("{.reg .pred p; elect.sync _|p, 0xffffffff; selp.u32 %0, 1, 0, p;}" : "=r"(r)); return r; }
__device__ __forceinline__ uint32_t or3(uint32_t a, uint32_t b, uint32_t c) { uint32_t r; asm("lop3.b32 %0, %1, %2, %3, 0xFE;" : "=r"(r) : "r"(a), "r"(b), "r"(c)); return r; }
__device__ __forceinline__ void pin() { pdl_launch(); }
__device__ __forceinline__ void mma16h(float* d, uint32_t a0, uint32_t a2, uint32_t b0, uint32_t b1) {
  asm volatile("{.reg .b32 u, v; mma.sync.aligned.m16n8k16.row.col.f32.bf16.bf16.f32 {%0,%1,%2,%3},{%4,u,%5,v},{%6,%7},{%0,%1,%2,%3};}"
               : "+f"(d[0]), "+f"(d[1]), "+f"(d[2]), "+f"(d[3]) : "r"(a0), "r"(a2), "r"(b0), "r"(b1)); }
__device__ __forceinline__ void mma8h(float* d, uint32_t a0, uint32_t b0) {
  asm volatile("{.reg .b32 u; mma.sync.aligned.m16n8k8.row.col.f32.bf16.bf16.f32 {%0,%1,%2,%3},{%4,u},{%5},{%0,%1,%2,%3};}"
               : "+f"(d[0]), "+f"(d[1]), "+f"(d[2]), "+f"(d[3]) : "r"(a0), "r"(b0)); }
__device__ __forceinline__ uint32_t absmax2(uint32_t a, uint32_t b) { uint32_t r; asm("max.xorsign.abs.bf16x2 %0, %1, %2;" : "=r"(r) : "r"(a), "r"(b)); return r; }
__device__ __forceinline__ void until(uint32_t t) { while ((int)(clk32() - t) < 0) {} }
__device__ __forceinline__ uint4 pack8(const float* d) { return make_uint4(pack2(d[0], d[1]), pack2(d[2], d[3]), pack2(d[4], d[5]), pack2(d[6], d[7])); }
__device__ __forceinline__ void add8(float* d, uint4 v) {
  d[0] += bf_lo(v.x); d[1] += bf_hi(v.x); d[2] += bf_lo(v.y); d[3] += bf_hi(v.y);
  d[4] += bf_lo(v.z); d[5] += bf_hi(v.z); d[6] += bf_lo(v.w); d[7] += bf_hi(v.w);
}

template <int WG>
__device__ __forceinline__ void chain_body(const ChainParams& p, const uint32_t wq, const uint32_t (&ak)[80], const uint32_t (&av)[80]) {
  const int tid = threadIdx.x & 127, t4 = __shfl_sync(~0u, tid >> 5, 0), lane = tid & 31;
  const int cta = blockIdx.x, h = cta / 3, j = cta - 3 * h;
  const uint32_t sb = mapa(CH_BASE, j);
  const uint32_t bWo = sb + CH_BAR, bWq = bWo + 8, bX = bWo + 16, bXA = bWo + 24, bXB = bWo + 32, bO = bWo + 40, bG = bWo + 48, bH = bWo + 96;
  uint32_t tw[4 * CH_TW];
  auto refill = [&]() {
#pragma unroll
    for (int k = 0; k < CH_TW; k++) ldsm4t(&tw[4 * k], wq + k * 2048);
  };
  const uint32_t wo = opaque((sb + CH_WO + (WG == 0 ? (t4 + (j == 2)) * 4096 : (j == 2 ? 0 : 24576) + t4 * 1024) + ((lane & 7) + (lane >> 4) * 8) * 64 +
                              ((((lane >> 3) & 1) ^ ((lane >> 1) & 3)) << 4)) ^ (WG == 1 && j == 2 ? 32 : 0));
  const uint32_t wo2 = opaque((wo ^ ((t4 & 1) * 32)) + (4 + (t4 >> 1) - t4) * 4096);
  const uint32_t l16 = opaque(sb + lane * 16);
  const uint32_t l8 = opaque(sb + t4 * 256 + lane * 8);
  const uint32_t lw = opaque(sb + t4 * 1024 + lane * 16);
  const uint32_t qs = opaque(sb + CH_QK + WG * 2048 + t4 * 512 + lane * 16);
  const uint32_t qa = opaque(sb + CH_QK + (lane >> 4) * 2048 + (lane & 15) * 16 + (WG == 0 ? t4 * 512 + 256 : t4 == 3 ? 1024 : 0));
  const uint32_t ka = opaque(t4 < 2 ? sb + CH_KT + t4 * 512 + lane * 16
                                    : sb + CH_QK + 256 + (t4 - 2) * 1024 + ((lane >> 3) & 1) * 2048 + (lane >> 4) * 128 + (lane & 7) * 16);
  const uint32_t l4 = opaque(sb + t4 * 256 + lane * 4);
  uint32_t pdst[1], pages = 0;
  auto line0 = [&](int i) { return 28 * j + (i < 4 ? 4 * t4 + i : 12 + 2 * t4 + i); };
  const uint32_t plane = opaque((lane >> 4) * 2048 + h * 64 + (lane & 15) * 4);
  if (WG == 0) {
    pages = __ballot_sync(~0u, lds32(sb + CH_O + line0(min(lane, 5)) * 4) & 4096);
  } else {
    pages = __ballot_sync(~0u, lds32(sb + CH_O + (80 + min(lane, 11)) * 4) & 4096);
    pdst[0] = opaque(lds32(sb + CH_O + (j == 0 ? 24 + t4 : 50 + 2 * j + (t4 & 1)) * 4) + plane);
  }
  const uint32_t role = lds32(sb + CH_O + NSLOT * 4), rsrc = lds32(sb + CH_O + role * 4), rdst = (80 + role / 20) * 8192 + role % 20 * 128;
  const uint32_t r1 = mapa(CH_BASE, j == 2 ? 0 : j + 1) - sb, r2 = mapa(CH_BASE, j == 0 ? 2 : j - 1) - sb;
  uint32_t tag = opaque(1);
  auto pool = [&](uint32_t off) { return p.pool + ((tag & 0xfffe) + off); };
  auto after = [&](uint32_t x) { return x & tag & 0xfffe; };
  auto kv = [&](int s, uint32_t a) { return p.kv + (a + ((cta * 2 * NSEG + s) * KV_BYTES - sb)); };
  auto pass = [&](float (&d)[16], const uint32_t (&a)[80], auto k0, auto k1) {
    const uint64_t db = mkdesc(CH_BASE + CH_X + WG * 20480, 512, 128, 0);
#pragma unroll
    for (int k = k0.value; k < k1.value; k++) wg_rs32_00(d, a[4 * k], a[4 * k + 1], a[4 * k + 2], a[4 * k + 3], db + k * 64, k);
    wg_commit();
  };
  auto dump = [&](float (&d)[16], uint32_t a) {
    reg_fence<16>(d);
    sts128(a, pack8(d)); sts128(a + 512, pack8(d + 8));
  };
  uint32_t pph = 0;
  auto tokens0 = [&](int s, auto k0) {
    float dk[16], dv[16];
    bar_sync(9, 256);
    wg_fence();
    pass(dk, ak, Int<0>(), Int<4>());
    const uint4 a0 = lds128(lw + CH_KT), a1 = lds128(lw + CH_KT + 512);
    pin();
    pass(dk, ak, Int<4>(), Int<20>());
    pass(dv, av, Int<0>(), Int<CH_VA>());
    pin();
    wg_wait<1>();
    reg_fence<16>(dk);
    add8(dk, a0); add8(dk + 8, a1);
    const uint4 w0 = pack8(dk), w1 = pack8(dk + 8);
    const uint4 b0 = lds128(lw + CH_VT), b1 = lds128(lw + CH_VT + 512);
    stsm4t(lw + CH_KT, w0.x, w0.z, w0.y, w0.w); stsm4t(lw + CH_KT + 512, w1.x, w1.z, w1.y, w1.w);
    if (CH_KP == 2) bar_arrive(7, 160);
    TM1(6);
    pin();
    if (CH_VA < 20) pass(dv, av, Int<CH_VA>(), Int<20>());
    pin();
#pragma unroll
    for (int k = k0.value; k < CH_TW; k++) ldsm4t(&tw[4 * k], wq + k * 2048);
    TM1(9);
    if (k0.value < CH_TW && t4 >= 2) { mbar_wait_hot(bH + t4 * 16 - 24 + (pph & 1) * 8, pph >> 1 & 1); pph++; }
    __syncwarp();
    wg_wait<0>();
    reg_fence<16>(dv);
    add8(dv, b0); add8(dv + 8, b1);
#pragma unroll
    for (int e = 0; e < 2; e++) { const uint4 v = pack8(dv + 8 * e); sts128(lw + CH_VT + e * 512, make_uint4(v.x, v.z, v.y, v.w)); }
  };
  auto publish_k = [&](int s) {
    if (t4 == CH_KW && elect()) { fence_async(); bulk_store(p.kv + (size_t)(cta * 2 * NSEG + s) * KV_BYTES, sb + CH_KT, 4096); bulk_commit(); }
    __syncwarp();
  };
  if (WG == 0) {
    mbar_wait(bXB, 0);
    tokens0(0, Int<CH_TW>());
  } else {
    const uint32_t* m0 = reinterpret_cast<const uint32_t*>(p.mem0) + (lane >> 2) * 320 + t4 * 80 + (lane & 3);
    uint32_t a[20];
#pragma unroll
    for (int i = 0; i < 20; i++) a[i] = m0[4 * i];
    pin();
    float dk[16], dv[16];
    mbar_wait(bXA, 0);
    wg_fence();
    pass(dk, ak, Int<0>(), Int<20>());
    pass(dv, av, Int<0>(), Int<20>());
    wg_wait<0>();
    dump(dk, lw + CH_KT);
    dump(dv, lw + CH_VT);
    bar_sync(9, 256);
    if (CH_KP == 2 && t4 == CH_KW) { bar_sync(7, 160); publish_k(0); }
#pragma unroll
    for (int i = 0; i < 20; i++) sts32(sb + CH_M + (t4 * 20 + i) * 128 + lane * 4, nz(transpose8(a[i])));
    __syncwarp();
    if (elect()) mbar_arrive(bG + t4 * 8);
  }
  PRO(8);
  mbar_wait(bWq, 0);
  refill();
  PRO(9);
  mbar_wait(bWo, 0);
  asm volatile("barrier.cluster.wait.aligned;" ::: "memory");
  PRO(10);
  auto load_x = [&](int s, int k0, int n, uint32_t bar) {
    if (!NOX && elect()) { mbar_expect(bar, n * 1024); bulk_load(sb + CH_X + k0 * 1024, p.xc + (s + 1) * 10240 + k0 * 256, n * 1024, bar); }
  };
  constexpr int VK = WG == 0 ? CH_VK0 : CH_VK1;
  uint32_t gph = 0;
  int st = 0;
  const uint32_t ca = opaque(sb + CH_M + t4 * 2560 + lane * 32 + (lane >> 2) * 4);
  auto project = [&](int s, uint32_t (&b)[40], float (&dv)[16], uint32_t (&kf)[16]) {
    float dq[4] = {}, dk[4] = {};
    uint32_t w[80];
#pragma unroll
    for (int i = 0; i < 4 * CH_TW; i++) w[i] = tw[i];
    constexpr int LR = WG == 1 ? CH_LR1 : CH_LR;
    auto load = [&](int n) {
      int c = 0;
#pragma unroll
      for (int i = 0; i < 10; i++) {
        if (i == CH_KF) {
#pragma unroll
          for (int q = 0; q < 4; q++)
            if (WG == 1 && c++ == n) ldsm4(&kf[4 * q], ka + q * 1024);
        }
        if (c++ == n) ldsm4t(&b[4 * i], l16 + CH_M + WG * 5120 + i * 512);
#pragma unroll
        for (int k = 2 * i; k < 2 * i + 2; k++)
          if (k >= CH_TW && c++ == n) ldsm4t(&w[4 * k], wq + k * 2048);
      }
#pragma unroll
      for (int i = 0; i < 4; i++)
        if (WG == 1 && CH_KF >= 10 && c++ == n) ldsm4(&kf[4 * i], ka + i * 1024);
    };
    if (WG == 1) {
      for (int n = 0;;) {
        mbar_wait(bG + t4 * 8, gph);
        TR(5, (clk32() & ~3u) | min(n, 3));
        gph ^= 1;
        if (__builtin_expect(!__any_sync(~0u, __vimin3_u32(lds32(ca), lds32(ca + 1024), lds32(ca + 1536)) == 0), 1)) break;
        if (elect()) {
          const int q = (st == 0 ? 8 : st * 4 - 4) + t4;
          mbar_expect(bG + t4 * 8, 2560);
          bulk_load(sb + CH_M + t4 * 2560, p.pool + ((80 + q) * 8192 + (pages >> q & 1) * 4096), 2560, bG + t4 * 8);
        }
        spin_guard(n);
      }
    }
    bar_sync(6, 256);
#pragma unroll
    for (int i = 0; i < CH_L0; i++) load(i);
    if (WG == 0 && CH_XB == 4 && s + 1 < NSEG) load_x(s, 5 * t4, 5, bXB);
    TM(0);
    TM1(11);
    if (WG == 1) TR(6, clk32());
#pragma unroll
    for (int k = 0; k < 20; k += 2) {
      if (k > 0) {
#pragma unroll
        for (int n = (k == 18 ? 40 : CH_L0 + k * LR / 4) - 1; n >= CH_L0 + (k - 2) * LR / 4; n--) { load(n); if (CH_LO) __syncwarp(); }
      }
      pin();
#pragma unroll
      for (int kk = k; kk < k + 2; kk++) {
        mma16(dk, ak[4 * kk], ak[4 * kk + 1], ak[4 * kk + 2], ak[4 * kk + 3], b[2 * kk], b[2 * kk + 1]);
        mma16(dq, w[4 * kk], w[4 * kk + 1], w[4 * kk + 2], w[4 * kk + 3], b[2 * kk], b[2 * kk + 1]);
        if (kk < VK) mma16(dv, av[4 * kk], av[4 * kk + 1], av[4 * kk + 2], av[4 * kk + 3], b[2 * kk], b[2 * kk + 1]);
      }
    }
    const float k2 = 0.07216878364870322f * 1.44269504089f;
    stsm4t(qs, pack2(dq[0] * k2, dq[1] * k2), pack2(dq[2] * k2, dq[3] * k2), pack2(dk[0], dk[1]), pack2(dk[2], dk[3]));
    TM(1);
  };
  static_assert(CH_VK1 == 20 && CH_KP == 0 && CH_XA > 0 && CH_XB > 0, "last step");
  constexpr int VC = VK == 20 ? 1 : WG == 0 ? 2 : 3;
  auto finish_v = [&](const uint32_t (&b)[40], float (&dv)[16]) {
#pragma unroll
    for (int kk = VK; kk < 20; kk++) mma16(dv + 4 * ((kk - VK) % VC), av[4 * kk], av[4 * kk + 1], av[4 * kk + 2], av[4 * kk + 3], b[2 * kk], b[2 * kk + 1]);
  };
  auto sum_v = [&](float (&dv)[16]) {
#pragma unroll
    for (int i = 4; i < 4 * VC; i++) dv[i & 3] += dv[i];
  };
  auto publish_km = [&](int s) {
    uint32_t a[4];
    ldsm4(a, qa);
    *reinterpret_cast<uint2*>(kv(s, l8) + KV_M) = make_uint2(hadd2(a[0], a[2]), hadd2(a[1], a[3]));
  };
  auto memory_v = [&](uint2 x, const float (&dv)[16]) {
    return make_uint2(pack2(dv[0] + bf_lo(x.x), dv[1] + bf_hi(x.x)), pack2(dv[2] + bf_lo(x.y), dv[3] + bf_hi(x.y)));
  };
  auto publish_v = [&](int s, const uint4 (&v)[2], uint2 vm) {
#pragma unroll
    for (int e = 0; e < 2; e++) reinterpret_cast<uint4*>(kv(s, lw) + KV_V)[e * 32] = v[e];
    *reinterpret_cast<uint2*>(kv(s, l8) + KV_V + KV_M) = vm;
  };
#pragma unroll 1
  for (int s = 0;; s++) {
    float dv[16] = {};
    uint32_t b[40], kf[16];
    project(s, b, dv, kf);
    if (WG == 0) {
      bar_sync(1, 256);
      if (CH_XA == 0) load_x(s, 20 + 5 * t4, 5, bXA);
      if (CH_XB == 0) load_x(s, 5 * t4, 5, bXB);
      pin();
      finish_v(b, dv);
      sum_v(dv);
      sts64(l8 + CH_VP, pack2(dv[0], dv[1]), pack2(dv[2], dv[3]));
      if (s == NSEG - 1) {
        bar_arrive(10, 256);
        publish_k(s);
        publish_km(s);
        bulk_wait<0>();
        fence_async_global();
        bar_sync(2, 256);
        if (tid == 0) red_release(p.sync + 15 * 8 + 4, 1);
        break;
      }
      __syncwarp();
      if (elect()) mbar_arrive(bX);
      if (CH_XA == 1) load_x(s, 20 + 5 * t4, 5, bXA);
      if (CH_XB == 1) load_x(s, 5 * t4, 5, bXB);
      uint32_t w[144];
      auto wload = [&](int i) { ldsm4t(&w[4 * i], (i % 3 == 0 ? wo : i % 3 == 1 ? wo ^ 32 : wo2) + i / 12 * 28672 + i / 3 % 4 * 1024); };
      TM(3);
      if (CH_KP == 0) publish_k(s);
#pragma unroll
      for (int i = 0; i < CH_W1; i++) wload(i);
      bar_sync(10, 256);
      uint32_t km[4];
      ldsm4(km, qa);
      pin();
#pragma unroll
      for (int i = CH_W1; i < CH_W2; i++) wload(i);
      pin();
      const uint2 kms = make_uint2(hadd2(km[0], km[2]), hadd2(km[1], km[3]));
      if (CH_KM == 0) *reinterpret_cast<uint2*>(kv(s, l8) + KV_M) = kms;
      if (CH_KP == 0) bulk_wait_read<0>();
      if (CH_XA == 2) load_x(s, 20 + 5 * t4, 5, bXA);
      if (CH_XB == 2) load_x(s, 5 * t4, 5, bXB);
      bar_sync(2, 256);
      {
        float y[3][4] = {};
        uint32_t ob[24];
        ldsm4(&ob[0], l16 + CH_O + 1024); ldsm4(&ob[4], l16 + CH_O + 1536);
        TM(7);
        auto step = [&](int i) {
          const int k = i / 3;
          mma16(y[i % 3], w[4 * i], w[4 * i + 1], w[4 * i + 2], w[4 * i + 3], ob[2 * k], ob[2 * k + 1]);
        };
#pragma unroll
        for (int i = 0; i < 12; i++) {
          step(i);
          if (i >= 12 - (CH_W3 - CH_W2)) wload(CH_W3 - 12 + i);
          if (i % 3 == 2) pin();
        }
        if (CH_XB == 3) load_x(s, 5 * t4, 5, bXB);
        if (CH_KM == 1) *reinterpret_cast<uint2*>(kv(s, l8) + KV_M) = kms;
        pin();
        mbar_wait(bO, s & 1);
        TM(4);
        ldsm4(&ob[8], l16 + CH_O); ldsm4(&ob[12], l16 + CH_O + 512);
        pin();
        float2 inv;
        uint8_t* dst[6];
        uint32_t mask;
#pragma unroll
        for (int i = 12; i < 36; i++) {
          step(i);
          const int n = CH_W3 + i - 13, m = n - (n > 30);
          if (i == 12) ldsm4(&ob[16], l16 + after(w[4 * CH_W3 - 1] | w[4 * CH_W3 - 5] | w[4 * CH_W3 - 9] | ob[8]) + CH_O + 2048);
          else if (n == 30) ldsm4(&ob[20], l16 + CH_O + 2560);
          else if (m < 36) wload(m);
          else if (m == 36) inv = lds64f((l8 & ~0xe0u) + CH_VP);
          if (i == 26) mask = ((l16 ^ tag) & 48) == 0;
          if (i >= 27 && i < 33) dst[i - 27] = pool(line0(i - 27) * 8192 + (pages >> (i - 27) & 1) * 4096) + plane;
          if (i % 3 == 2) pin();
        }
#pragma unroll
        for (int k = 0; k < CH_R1; k++) ldsm4t(&tw[4 * k], wq + k * 2048);
        pin();
#pragma unroll
        for (int i = 0; i < 6; i++) stg_strong32(dst[i], pack_tag(y[i >> 1][2 * (i & 1)] * inv.x, y[i >> 1][2 * (i & 1) + 1] * inv.y, tag, mask));
        TM(8);
        TR(0, clk32());
        bar_arrive(5, 256);
        pin();
      }
      const uint32_t t0 = clk32();
      auto refill2 = [&]() {
#pragma unroll
        for (int k = CH_R1; k < CH_R2; k++) ldsm4t(&tw[4 * k], wq + k * 2048);
      };
      if (CH_RP == 0) refill2();
      const uint32_t ln = (l16 ^ tag) >> 4 & 31;
      if (t4 >= 2) {
        const uint32_t bP = bH + t4 * 16 - 24, ps = CH_PS + (t4 & 1) * 4096;
        auto fetch = [&](uint32_t k) {
          if (elect()) { mbar_expect(bP + (k & 1) * 8, 2048); bulk_load(sb + ps + (k & 1) * 2048, p.pool + (rsrc + (t4 & 1) * 2048), 2048, bP + (k & 1) * 8); }
        };
        until(t0 + CH_D0);
        fetch(pph);
        if (CH_RP == 2) refill2();
        if (!NOX) mbar_wait_hot(bXB, (s + 1) & 1);
        const uint32_t want = (tag & 1) * 0x10001, chk = opaque(ln < 4 ? 0x10001 : 0);
        uint4 sel;
        sel.x = opaque((ln >> 3) != (ln & 1) ? 0 : ln & 4 ? 0x3f800000u : 0x00003f80u);
        sel.z = opaque(sel.x); sel.y = opaque(ln); sel.w = opaque(ln + 1);
        uint8_t* mdst = p.pool + opaque(st * 32768 + rdst + (t4 & 1) * 64 + ln * 4);
        until(t0 + CH_D1);
        fetch(pph + 1);
        TM(5);
        if (CH_RP == 1) refill2();
        int n = 0;
        uint32_t u[16];
        float y[4][4];
        auto sum = [&]() {
#pragma unroll
          for (int i = 0; i < 16; i++) y[i >> 2][i & 3] = 0.f;
#pragma unroll
          for (int i = 0; i < 8; i++) mma16(y[i & 3], sel.x, sel.y, sel.z, sel.w, u[2 * i], u[2 * i + 1]);
        };
        auto check = [&](auto spec) {
          mbar_wait(bP + (pph & 1) * 8, pph >> 1 & 1);
          TM(14);
          TR(2, clk32());
#pragma unroll
          for (int i = 0; i < 4; i++) ldsm4t(&u[4 * i], l16 + (ps + (pph & 1) * 2048) + i * 512);
          pph++;
          if (spec.value) { pin(); sum(); }
          uint32_t bad = 0;
#pragma unroll
          for (int i = 0; i < 4; i++) bad = or3(bad, differ(u[4 * i], u[4 * i + 1], want), differ(u[4 * i + 2], u[4 * i + 3], want));
          return __any_sync(~0u, bad & chk);
        };
        if (CH_SP) {
          if (check(Int<0>())) {
            do { fetch(pph + 1); spin_guard(n); } while (check(Int<1>()));
          } else {
            sum();
          }
        } else {
          while (check(Int<0>())) { fetch(pph + 1); spin_guard(n); }
          sum();
        }
        TR(1, t0 + (n ? CH_D1 : CH_D0));
        TM(15);
        const uint32_t w = nz(pack2((y[0][0] + y[1][0]) + (y[2][0] + y[3][0]), (y[0][1] + y[1][1]) + (y[2][1] + y[3][1])));
        if (ln < 16) { stg_strong32(mdst, w); stg_strong32(mdst + 4096, w); }
        TMV(12, 32, n);
        TR(3, (clk32() & ~3u) | min(n, 3));
      } else {
        if (CH_RP) refill2();
        if (!NOX) mbar_wait_hot(bXB, (s + 1) & 1);
        stg_strong32(p.pool + ((st == 2 ? 0 : st + 1) * 32768 + rdst + t4 * 4096) + ln * 4, 0u);
        if (t4 == 0 && cta < 40 && s + 4 < NSEG && elect())
          asm volatile("cp.async.bulk.prefetch.L2.global [%0], 1024;" :: "l"(p.xc + (s + 4) * 10240 + cta * 256) : "memory");
        if (t4 == 1 && (s & 3) == 0 && s > 0 && elect()) red_relaxed(p.sync + 2 * s - 4, 1);
        if (t4 == 1 && s == NSEG - 3 && cta == 95 && elect()) red_relaxed(p.sync + 2 * s + 2, 0x10000);
      }
      TM(10);
      bar_arrive(8, 256);
      tokens0(s + 1, Int<CH_R2>());
      TM(2);
      TR(7, clk32());
    } else {
      if (s == NSEG - 1) {
        bar_arrive(1, 256);
        const uint4 v[2] = {lds128(lw + CH_VT), lds128(lw + CH_VT + 512)};
        bar_sync(10, 256);
        publish_v(s, v, memory_v(lds64(l8 + CH_VP), dv));
        bar_arrive(2, 256);
        break;
      }
      const uint32_t xo = l4 + (CH_SX - (t4 == 3 ? 128 : 0)), x1 = xo + (r1 + 768 + min(t4, 2) * 256), x2 = xo + (r2 + 1024 + min(t4, 2) * 256);
      if (t4 < 2) {
        float ds[4][4] = {};
        uint32_t q[16];
        asm volatile("bar.sync 1, 256;" ::: "memory");
#pragma unroll
        for (int k = 0; k < 4; k++) ldsm4(&q[4 * k], qa + k * 512);
        pin();
        if (VK < 20) { finish_v(b, dv); pin(); }
#pragma unroll
        for (int k = 0; k < 4; k++) {
          mma16(ds[k & 1], kf[4 * k], kf[4 * k + 1], kf[4 * k + 2], kf[4 * k + 3], q[4 * k], q[4 * k + 1]);
          mma16(ds[2 + (k & 1)], kf[4 * k], kf[4 * k + 1], kf[4 * k + 2], kf[4 * k + 3], q[4 * k + 2], q[4 * k + 3]);
        }
        float t[4];
#pragma unroll
        for (int i = 0; i < 4; i++) t[i] = (ds[0][i] + ds[2][i]) + (ds[1][i] + ds[3][i]);
        const uint32_t w0 = pack2(t[0], t[1]), w1 = pack2(t[2], t[3]);
        st_async32(x1, w0, bX + r1); st_async32(x2, w0, bX + r2);
        st_async32(x1 + 128, w1, bX + r1); st_async32(x2 + 128, w1, bX + r2);
        sts32(xo, w0); sts32(xo + 128, w1);
      } else {
        float ds[4][4] = {};
        uint32_t q0[4], q1[4], a0[4], a1[4];
        asm volatile("bar.sync 1, 256; " ::: "memory");
        ldsm4(a0, ka); ldsm4(q0, qa); ldsm4(a1, ka + 512); ldsm4(q1, qa + 512);
        pin();
        if (VK < 20) { finish_v(b, dv); pin(); }
        mma16(ds[0], a0[0], a0[1], a0[2], a0[3], q0[0], q0[1]);
        mma16(ds[1], a0[0], a0[1], a0[2], a0[3], q0[2], q0[3]);
        mma16(ds[2], a1[0], a1[1], a1[2], a1[3], q1[0], q1[1]);
        mma16(ds[3], a1[0], a1[1], a1[2], a1[3], q1[2], q1[3]);
        float t[2];
#pragma unroll
        for (int i = 0; i < 2; i++)
          t[i] = ((ds[0][i] + ds[0][i + 2]) + (ds[1][i] + ds[1][i + 2])) + ((ds[2][i] + ds[2][i + 2]) + (ds[3][i] + ds[3][i + 2]));
        const uint32_t w0 = pack2(t[0], t[1]);
        st_async32(x1, w0, bX + r1);
        st_async32(x2, w0, bX + r2);
        sts32(xo, w0);
      }
      TM(3);
      const uint4 id = lds128(l16 + CH_ID);
      float sc[3][4] = {};
      uint4 v[2];
      sum_v(dv);
      bar_sync(3, 128);
      uint32_t r[12], wd[12], we[12] = {};
      ldsm4(&r[0], l16 + CH_SX); ldsm2(&r[4], l16 + CH_SX + 512);
      pin();
      v[0] = lds128(lw + CH_VT); v[1] = lds128(lw + CH_VT + 512);
#pragma unroll
      for (int u = 0; u < 3; u++) ldsm4t(&wd[4 * u], wo + u * 28672);
      if (CH_WE && j == 0) {
#pragma unroll
        for (int u = 0; u < 3; u++) ldsm4t(&we[4 * u], (wo ^ 32) + u * 28672);
      }
      pin();
#pragma unroll
      for (int q = 0; q < 3; q++) mma16(sc[q], id.x, id.y, id.z, id.w, r[2 * q], r[2 * q + 1]);
      uint32_t big = absmax2(absmax2(absmax2(r[0], r[1]), absmax2(r[2], r[3])), absmax2(r[4], r[5]));
      const uint32_t oa1 = l4 + (r1 + CH_O), oa2 = l4 + (r2 + CH_O + 2048), ones = 0x3f803f80u;
      mbar_wait_hot(bX, s & 1);
      TM(4);
      ldsm4(&r[0], l16 + CH_SX + 768); ldsm4(&r[8], l16 + CH_SX + 1792); ldsm4(&r[4], l16 + CH_SX + 1280);
      const uint2 vp = lds64(l8 + CH_VP);
      bar_arrive(10, 256);
      pin();
      {
        float sd[3][4] = {};
#pragma unroll
        for (int i = 0; i < 3; i++) {
          const int q = i == 0 ? 0 : 3 - i;
          mma16(sc[q], id.x, id.y, id.z, id.w, r[4 * q], r[4 * q + 1]);
          mma16(sd[q], id.x, id.y, id.z, id.w, r[4 * q + 2], r[4 * q + 3]);
          big = absmax2(big, absmax2(absmax2(r[4 * q], r[4 * q + 1]), absmax2(r[4 * q + 2], r[4 * q + 3])));
        }
#pragma unroll
        for (int i = 0; i < 12; i++) sc[i >> 2][i & 3] += sd[i >> 2][i & 3];
      }
      const bool redo = __any_sync(~0u, (absmax2(big, big << 16) & 0x7fff0000u) >= 0x41800000u);
      const uint2 vm = memory_v(vp, dv);
      sc[2][0] += sc[2][2]; sc[2][1] += sc[2][3];
      float l[4], o[2][4];
      uint32_t p3, p4;
      auto attend = [&]() {
#pragma unroll
        for (int i = 0; i < 4; i++) l[i] = o[0][i] = o[1][i] = 0.f;
        const uint32_t p1 = pack2(ex2(sc[0][0]), ex2(sc[0][1])), p2 = pack2(ex2(sc[0][2]), ex2(sc[0][3]));
        mma16h(o[0], p1, p2, v[0].x, v[0].y);
        mma16h(o[1], p1, p2, v[0].z, v[0].w);
        mma16h(l, p1, p2, ones, ones);
        const uint32_t p0 = pack2(ex2(sc[2][0]), ex2(sc[2][1]));
        mma8h(o[0], p0, vm.x);
        mma8h(o[1], p0, vm.y);
        mma8h(l, p0, ones);
        p3 = pack2(ex2(sc[1][0]), ex2(sc[1][1])); p4 = pack2(ex2(sc[1][2]), ex2(sc[1][3]));
        mma16h(o[0], p3, p4, v[1].x, v[1].y);
        mma16h(o[1], p3, p4, v[1].z, v[1].w);
      };
      attend();
      if (__builtin_expect(redo, 0)) {
        float mx = fmaxf(sc[2][0], sc[2][1]);
#pragma unroll
        for (int i = 0; i < 4; i++) mx = fmaxf(mx, fmaxf(sc[0][i], sc[1][i]));
        mx = fmaxf(mx, __shfl_xor_sync(~0u, mx, 1));
        mx = fmaxf(mx, __shfl_xor_sync(~0u, mx, 2));
#pragma unroll
        for (int i = 0; i < 4; i++) { sc[0][i] -= mx; sc[1][i] -= mx; }
        sc[2][0] -= mx; sc[2][1] -= mx;
        attend();
      }
      const uint32_t o0 = pack2(o[0][0], o[0][1]), o1 = pack2(o[1][0], o[1][1]);
      st_async32(oa1, o0, bO + r1); st_async32(oa2, o0, bO + r2);
      st_async32(oa1 + 128, o1, bO + r1); st_async32(oa2 + 128, o1, bO + r2);
      sts32(l4 + CH_O + 1024, o0); sts32(l4 + CH_O + 1152, o1);
      bar_arrive(2, 256);
      pin();
      TM(6);
      mma16h(l, p3, p4, ones, ones);
      float inv;
      asm("rcp.approx.ftz.f32 %0, %1;" : "=f"(inv) : "f"(l[0]));
      sts32((l8 & ~0xffu) + (lane & 28) + CH_VP, __float_as_uint(inv));
      __syncwarp();
      if (elect()) mbar_arrive(bO);
      {
        float z[2][4] = {}, y[2][4] = {};
        mma16(z[0], wd[0], wd[1], wd[2], wd[3], o0, o1);
        if (j == 0) {
#pragma unroll
          for (int u = 0; u < 3; u++) if (!CH_WE) ldsm4t(&we[4 * u], (wo ^ 32) + u * 28672);
          mma16(y[0], we[0], we[1], we[2], we[3], o0, o1);
        }
        const float2 iv = lds64f((l8 & ~0xe0u) + CH_VP);
        uint8_t* dst = pool(pdst[0]);
        const uint32_t mask = ((l16 ^ tag) & 48) == 0;
        const uint32_t oa = qa + ((tag & 0xfffe) + CH_O - CH_QK + t4 * 256 - (t4 == 3 ? 1024 : 0));
        const uint32_t za = l16 + ((tag & 0xfffe) + (t4 >> 1) * 512 + (t4 & 1) * 8);
        pin();
        mbar_wait(bO, s & 1);
        uint32_t a[4];
        ldsm4(a, oa);
        mma16(z[0], wd[4], wd[5], wd[6], wd[7], a[0], a[1]);
        mma16(z[1], wd[8], wd[9], wd[10], wd[11], a[2], a[3]);
        if (j == 0) {
          mma16(y[0], we[4], we[5], we[6], we[7], a[0], a[1]);
          mma16(y[1], we[8], we[9], we[10], we[11], a[2], a[3]);
          sts128f(lw + CH_VT + 512, y[0][0] + y[1][0], y[0][1] + y[1][1], y[0][2] + y[1][2], y[0][3] + y[1][3]);
        }
        sts128f(lw + CH_VT, z[0][0] + z[1][0], z[0][1] + z[1][1], z[0][2] + z[1][2], z[0][3] + z[1][3]);
        bar_sync(3, 128);
        if (j == 0 || t4 < 2) {
          float2 q[4];
#pragma unroll
          for (int i = 0; i < 4; i++) q[i] = lds64f(za + CH_VT + i * 1024);
          stg_strong32(dst, pack_tag(((q[0].x + q[1].x) + (q[2].x + q[3].x)) * iv.x, ((q[0].y + q[1].y) + (q[2].y + q[3].y)) * iv.y, tag, mask));
        }
      }
      TM(2);
      if (!NOX) mbar_wait_hot(bXA, (s + 1) & 1);
      if (CH_KP == 2) bulk_wait_read<0>();
      float dk[16], dw[16];
      bar_sync(5, 256);
      wg_fence();
      pass(dk, ak, Int<0>(), Int<20>());
      pass(dw, av, Int<0>(), Int<20>());
      TM(5);
      pin();
      if (CH_EX == 0) publish_v(s, v, vm);
      if (elect()) {
        mbar_expect(bG + t4 * 8, 2560);
        if (t4 == 1 && s + 2 < NSEG) { mbar_expect(bX, 1536); mbar_expect(bO, 2048); }
      }
      if (CH_KD == 0) { wg_wait<1>(); dump(dk, lw + CH_KT); }
      wg_wait<0>();
      if (CH_KD == 1) dump(dk, lw + CH_KT);
      TM(7);
      dump(dw, lw + CH_VT);
      bar_arrive(9, 256);
      pin();
#pragma unroll
      for (int k = 0; k < CH_RB; k++) ldsm4t(&tw[4 * k], wq + k * 2048);
      if (t4 < 2) {
        if (CH_EX == 2) { publish_v(s, v, vm); pin(); }
#pragma unroll
        for (int k = CH_RB; k < CH_RC; k++) ldsm4t(&tw[4 * k], wq + k * 2048);
        const int q = t4 ? 3 : j, o = t4 ? j * 896 : 0;
        const uint8_t* src = p.pool + ((80 + st * 4 + q) * 8192 + (pages >> (st * 4 + q) & 1) * 4096 + o);
        asm volatile("bar.sync 8, 256;" ::: "memory");
        const uint32_t t1 = clk32() + CH_D2;
        if (CH_EX == 1) publish_v(s, v, vm);
        auto fetch = [&](auto n) {
          mbar_wait(bH, s & 1);
          until(t1);
          TR(4, clk32());
          if (elect())
            asm volatile("cp.async.bulk.shared::cluster.global.mbarrier::complete_tx::bytes.multicast::cluster [%0], [%1], %2, [%3], 7;"
                         :: "r"(sb + CH_M + q * 2560 + o), "l"(src), "n"(n.value), "r"(bG + q * 8) : "memory");
        };
        if (!t4) fetch(Int<2560>()); else if (j == 2) fetch(Int<768>()); else fetch(Int<896>());
      } else {
        asm volatile("bar.sync 8, 256; " ::: "memory");
        if (elect()) asm volatile("mbarrier.arrive.relaxed.cluster.shared::cluster.b64 _, [%0];" :: "r"(bH + (t4 == 2 ? r1 : r2)) : "memory");
        pin();
        if (CH_EX) publish_v(s, v, vm);
#pragma unroll
        for (int k = CH_RB; k < CH_RC; k++) ldsm4t(&tw[4 * k], wq + k * 2048);
      }
      TM(9);
      pin();
#pragma unroll
      for (int k = CH_RC; k < CH_TW; k++) ldsm4t(&tw[4 * k], wq + k * 2048);
      if (CH_KP == 2 && t4 == CH_KW) { bar_sync(7, 160); publish_k(s + 1); }
      TM(10);
    }
    if (++st == 3) st = 0;
    tag ^= 0x10001;
  }
}

__global__ void __launch_bounds__(256, 1) chain_kernel(const __grid_constant__ ChainParams p) {
  extern __shared__ __align__(1024) uint8_t smem_raw[];
  const uint32_t sb = s2u(smem_raw);
  const int tid = threadIdx.x, warp = __shfl_sync(~0u, tid >> 5, 0), lane = tid & 31;
  const int cta = blockIdx.x, h = cta / 3, j = cta - 3 * h, colbase = cta * 64;
  const uint32_t bWo = sb + CH_BAR, bWq = bWo + 8, bXA = bWo + 24, bWk = bWo + 80, bWv = bWo + 88;
  uint32_t smid; asm("mov.u32 %0, %%smid;" : "=r"(smid));
  PRO(0);
  if (sb != mapa(CH_BASE, j)) __trap();
  uint32_t entry = 0;
  auto place = [&]() {
    const int i = tid - 128;
    if (i >= 0 && i <= NSLOT) {
      const uint32_t side = ldg_strong32(g_smpart + (smid & 255));
      if (i < NSLOT) {
        entry = i * 8192 + (ldg_strong32(g_orient + i) == (i < 80 ? i & 1 : side) ? 0 : 4096);
      } else {
        entry = 2 * (atomicAdd(g_bo + p.layer * 128 + 1, 1 << 8 * side) >> 8 * side & 255) + side;
      }
    }
    __syncwarp();
  };
  if (warp == 2 && lane < 4) asm volatile("prefetch.tensormap [%0];" :: "l"(&p.wq + lane) : "memory");
  if (p.layer) place();
  if (warp == 0 && elect()) {
#pragma unroll 1
    for (int i = 0; i < 17; i++) mbar_init(bWo + 8 * i, i == 2 || i == 5 ? 5 : i == 3 || i == 4 ? 4 : i == 12 ? 2 : 1);
    asm volatile("fence.mbarrier_init.release.cluster;" ::: "memory");
    mbar_expect(bWk, 81920);
    tma_load3<(WEF & 1) != 0>(sb + CH_WQ, &p.wk, colbase, 0, bWk);
    mbar_expect(bWv, 81920);
    tma_load3<(WEF & 1) != 0>(sb + CH_WO, &p.wv, colbase, 0, bWv);
    mbar_expect(bWo + 16, 1536);
    mbar_expect(bWo + 40, 2048);
    mbar_expect(bWo, 86016); mbar_expect(bWq, 81920);
#pragma unroll 1
    for (int i = 0; i < 8; i++) mbar_expect(bXA + 8 * (i & 1), 5120);
  }
  if (warp == 1) {
    const uint32_t id = (lane >> 3) == (lane & 3) ? ((lane & 4) ? 0x3f800000u : 0x00003f80u) : 0u;
    sts128(sb + CH_ID + lane * 16, make_uint4(id, 0, 0, id));
  }
  __syncthreads();
  asm volatile("barrier.cluster.arrive.relaxed.aligned;" ::: "memory");
  uint32_t ak[80], av[80];
  const uint32_t wq = opaque(sb + CH_WQ + ((warp >> 2) * 320 + (lane & 7) + (lane >> 4) * 8) * 128 + (((2 * (warp & 3) + ((lane >> 3) & 1)) ^ (lane & 7)) << 4));
  pdl_wait();
  if (tid == 32) stg_strong32(g_smuse + (smid & 255), p.layer + 1);
  pdl_launch();
  PRO(1);
  if (warp == 0 && elect()) {
    bulk_load(sb + CH_X + 20480, p.xc + 5120, 20480, bXA);
    bulk_load(sb + CH_X, p.xc, 20480, bXA + 8);
  }
  if (!p.layer) place();
  __syncwarp();
  PRO(2);
  mbar_wait(bWk, 0);
  PRO(3);
#pragma unroll
  for (int k = 0; k < 20; k++) ldsm4t(&ak[4 * k], wq + k * 2048);
  bar_sync(6, 256);
  if (warp == 0 && elect()) tma_load3<(WEF & 2) != 0>(sb + CH_WQ, &p.wq, colbase, 0, bWq);
  __syncwarp();
  PRO(4);
  mbar_wait(bWv, 0);
  PRO(5);
#pragma unroll
  for (int k = 0; k < 20; k++) ldsm4t(&av[4 * k], wq + CH_WO + k * 2048);
  bar_sync(6, 256);
  PRO(6);
  if (warp >= 5 && elect()) tma_load3<(WEF & 2) != 0>(sb + CH_WO + (warp - 5) * 28672, &p.wo, j == 0 ? 0 : 32 + j * 192, h * 192 + (j + 8 - warp) % 3 * 64, bWo);
  if (tid == 128 + NSLOT && entry >= 80) {
    uint32_t c;
    int n = 0;
    do { c = ldg_strong32(g_bo + p.layer * 128 + 1); spin_guard(n); } while ((c & 255) + (c >> 8) < 96);
    const uint32_t other = (c >> 8 * (~entry & 1) & 255) + (entry >> 1) - 40;
    entry = other < 40 ? 2 * other + (~entry & 1) : entry % 80;
  }
  if (tid >= 128 && tid <= 128 + NSLOT) sts32(sb + CH_O + (tid - 128) * 4, entry);
  PRO(7);
  __syncthreads();
  if (__shfl_sync(~0u, tid >> 7, 0) == 0) chain_body<0>(p, wq, ak, av); else chain_body<1>(p, wq, ak, av);
}

struct PostParams { CUtensorMap wq, wo, wb, wo2, wb2; int gap, share, layer, look, gap2, pol; };
constexpr int PS = 8, PB = 28672;
constexpr int OP_SMEM = PS * PB + 512 + 2048;
enum { IT_ATT = 0, IT_OP = 1, IT_FIN = 2, IT_BQ = 3, IT_Q = 4 };

__device__ __forceinline__ uint32_t item_count(int type, int b) {
  return type == IT_ATT ? 32 : type == IT_OP ? op_split(b) * (b < OP_160 ? 2 : 4) : type == IT_FIN ? 16 : b < BQ_160 ? 6 : b < BQ_80 ? 12 : 24; }
__device__ __forceinline__ uint32_t item_need(int type, int b) { return type == IT_ATT ? 96 : item_count(type - 1, b); }

struct Ring {
  uint32_t sb, bars; int st; uint32_t ph;
  __device__ __forceinline__ uint32_t wait() const { mbar_wait(bars + 8 * st, ph); return sb + st * PB; }
  __device__ __forceinline__ void next() { if (++st == PS) { st = 0; ph ^= 1; } }
  __device__ __forceinline__ void release(int s) const { if ((threadIdx.x & 31) == 0) mbar_arrive(bars + 8 * (PS + s)); }
  __device__ __forceinline__ void pop() { __syncwarp(); release(st); next(); }
};

template <int N>
__device__ __forceinline__ void gemm_item(Ring& r, float* d, int nst, uint32_t go, int go_at, uint32_t wg) {
  auto desc = [](uint32_t lo, uint32_t hi) { uint64_t x; asm("mov.b64 %0, {%1, %2};" : "=l"(x) : "r"(lo), "r"(hi)); return x; };
  auto stage = [&](auto first) {
    const uint32_t base = (r.wait() & 0x3ffff) >> 4, a = base + wg * 256 + (8 << 16), w = base + 512 + (256 << 16);
    wg_fence();
#pragma unroll
    for (int kk = 0; kk < 2; kk++) {
      const uint64_t da = desc(a + kk * 16, 32), db = desc(w + kk * 128, 64 | 1 << 30);
      const int acc = kk || !first.value;
      if (N == 80) wg_ss80_01(d, da, db, acc);
      if (N == 160) wg_ss160_01(d, da, db, acc);
      if (N >= 192) wg_ss192_01(d, da, db, acc);
      if (N == 320) wg_ss128_01(d + 96, da, desc(w + kk * 128 + 768, 64 | 1 << 30), acc);
    }
    wg_commit();
  };
  stage(Int<1>());
  int prev = r.st;
  r.next();
#pragma unroll 1
  for (int kb = 1; kb < nst; kb++) {
    stage(Int<0>());
    if (kb == go_at && threadIdx.x == 0) mbar_arrive(go);
    wg_wait<1>();
    r.release(prev);
    prev = r.st;
    r.next();
  }
  wg_wait<0>();
  reg_fence<N / 2>(d);
  r.release(prev);
}

template <int HALF>
__device__ __forceinline__ void attn_a_warp(Ring& r, const uint32_t (&q)[48], int b, int h) {
  constexpr int NT = HALF ? 5 : 3, NF = 8 * NT;
  const int lane = threadIdx.x & 31, g = lane >> 2, c = lane & 3, seg = (threadIdx.x >> 5) & 3;
  uint32_t f[6][NF];
  int slot[6];
  auto fetch = [&](int u) {
    const uint32_t kv = r.wait() + seg * KV_BYTES;
    slot[u] = r.st;
    r.next();
#pragma unroll
    for (int w = 0; w < 4; w++) {
      uint32_t* d = &f[u][2 * NT * w];
#pragma unroll
      for (int t = 0; t <= HALF; t++) {
        if (u < 3) {
          ldsm4(d + 4 * t, kv + w * 1024 + t * 512 + (lane & 8) * 32 + (lane & 16) * 8 + (lane & 7) * 16);
        } else {
          const uint4 v = lds128(kv + w * 1024 + t * 512 + lane * 16);
          d[4 * t] = v.x; d[4 * t + 1] = v.y; d[4 * t + 2] = v.z; d[4 * t + 3] = v.w;
        }
      }
      const uint2 m = lds64(kv + KV_M + w * 256 + lane * 8);
      d[2 * NT - 2] = m.x; d[2 * NT - 1] = m.y;
    }
    pdl_launch();
  };
  float s[NT][4] = {};
  fetch(0);
#pragma unroll
  for (int u = 0; u < 3; u++) {
    fetch(u + 1);
#pragma unroll
    for (int kk = 0; kk < 4; kk++) {
      const uint32_t* a = &q[16 * u + 4 * kk];
#pragma unroll
      for (int n = 0; n < NT; n++) mma16(s[(n + 1) % NT], a[0], a[1], a[2], a[3], f[u][2 * NT * kk + 2 * n], f[u][2 * NT * kk + 2 * n + 1]);
    }
    r.release(slot[u]);
    pdl_launch();
  }
  fetch(4);
  const float k2 = 0.07216878364870322f * 1.44269504089f, NEG = -INFINITY;
  if (2 * c > g) { s[NT - 2][0] = NEG; s[NT - 1][2] = NEG; }
  if (2 * c + 1 > g) { s[NT - 2][1] = NEG; s[NT - 1][3] = NEG; }
  s[NT - 1][0] = s[NT - 1][1] = NEG;
  uint32_t pp[NT][2]; float inv[2];
#pragma unroll
  for (int hh = 0; hh < 2; hh++) {
    float m = NEG, l = 0.f;
#pragma unroll
    for (int n = 0; n < NT; n++) m = fmaxf(m, fmaxf(s[n][2 * hh], s[n][2 * hh + 1]));
    m = fmaxf(m, __shfl_xor_sync(~0u, m, 1)); m = fmaxf(m, __shfl_xor_sync(~0u, m, 2));
#pragma unroll
    for (int n = 0; n < NT; n++) { const float x = ex2((s[n][2 * hh] - m) * k2), y = ex2((s[n][2 * hh + 1] - m) * k2); l += x + y; pp[n][hh] = pack2(x, y); }
    l += __shfl_xor_sync(~0u, l, 1); l += __shfl_xor_sync(~0u, l, 2);
    asm("rcp.approx.ftz.f32 %0, %1;" : "=f"(inv[hh]) : "f"(l));
  }
  uint32_t* dst = g_o + ((b * 192 + h * 6) * 16 + seg * 4 + HALF * 2) * 128 + lane;
#pragma unroll
  for (int u = 3; u < 6; u++) {
    float o[8][4] = {};
#pragma unroll
    for (int n = 0; n < 8; n++) mma8(o[n], pp[0][0], pp[0][1], f[u][2 * NT * (n >> 1) + 2 * NT - 2 + (n & 1)]);
#pragma unroll
    for (int t = 0; t <= HALF; t++)
#pragma unroll
      for (int n = 0; n < 8; n++) {
        const uint32_t* v = &f[u][2 * NT * (n >> 1) + 4 * t + 2 * (n & 1)];
        mma16(o[n], pp[1 + 2 * t][0], pp[1 + 2 * t][1], pp[2 + 2 * t][0], pp[2 + 2 * t][1], v[0], v[1]);
      }
    r.release(slot[u]);
    if (u == 3) fetch(5);
#pragma unroll
    for (int n = 0; n < 8; n++) {
      dst[(u - 3) * 4096 + (n >> 2) * 2048 + (n & 3) * 32] = pack2(o[n][0] * inv[0], o[n][1] * inv[0]);
      dst[(u - 3) * 4096 + (n >> 2) * 2048 + (n & 3) * 32 + 128] = pack2(o[n][2] * inv[1], o[n][3] * inv[1]);
    }
  }
}

__device__ __forceinline__ void fin_item(Ring& r, uint32_t scratch, int b, int idx) {
  const int warp = threadIdx.x >> 5, lane = threadIdx.x & 31;
  float4 v[1][5];
  {
    const uint32_t base = r.wait();
#pragma unroll
    for (int i = 0; i < 5; i++) v[0][i] = unpack4(lds64(base + ((warp * 5 + i) * 32 + lane) * 8));
    r.pop();
  }
#pragma unroll 1
  for (int k = 0; k < op_split(b); k += 2) {
    const uint32_t base = r.wait();
#pragma unroll
    for (int i = 0; i < 10; i++) {
      const uint2 q = lds64(base + ((i / 5 * 40 + warp * 5 + i % 5) * 32 + lane) * 8);
      float4& t = v[0][i % 5];
      t.x += bf_lo(q.x); t.y += bf_hi(q.x); t.z += bf_lo(q.y); t.w += bf_hi(q.y);
    }
    r.pop();
  }
#pragma unroll
  for (int i = 0; i < 5; i++) g_x[((b * 16 + idx) * 40 + warp * 5 + i) * 32 + lane] = pack4(v[0][i]);
  float mean[1], rs[1];
  ln_stats<1>(v, scratch, mean, rs);
#pragma unroll
  for (int i = 0; i < 5; i++) {
    const int u = warp * 5 + i;
    uint32_t* xn = g_xn + ((b * 20 + (u >> 1)) * 16 + idx) * 128 + (u & 1) * 64 + lane;
    xn[0] = pack2((v[0][i].x - mean[0]) * rs[0], (v[0][i].y - mean[0]) * rs[0]);
    xn[32] = pack2((v[0][i].z - mean[0]) * rs[0], (v[0][i].w - mean[0]) * rs[0]);
  }
}

__global__ void __launch_bounds__(384, 1) post_kernel(const __grid_constant__ PostParams p) {
  extern __shared__ __align__(1024) uint8_t smem_raw[];
  const uint32_t sb = s2u(smem_raw), bars = sb + PS * PB;
  const uint32_t bIF = bars + 128, bIE = bars + 160, done = bars + 192, bGo = bars + 224, slots = bars + 240, scratch = bars + 512;
  const int warp = __shfl_sync(~0u, threadIdx.x >> 5, 0), lane = threadIdx.x & 31;
  if (warp == 9) PST(0);
  if (warp == 0 && blockIdx.x < 36) TRACE(0);
  if (warp >= 8) {
    asm volatile("setmaxnreg.dec.sync.aligned.u32 56;");
    if (warp == 10) {
      pdl_launch();
      if (sb & 1023) __trap();
      if (lane < 29) mbar_init(bars + 8 * lane, lane < 8 ? 1 : lane < 16 ? 8 : lane < 20 ? 1 : lane < 24 ? 2 : lane < 28 ? 8 : 1);
      if (lane == 0) sts32(slots + 16, p.gap);
      fence_async();
    }
    if (warp == 8 && lane < 5) asm volatile("prefetch.tensormap [%0];" :: "l"(&p.wq + lane) : "memory");
    if (warp != 9) bar_sync(2, 384);
    if (warp == 9) {
      PST(1);
      const int b = lane & 15;
      bool queries = QA_END < 16 && blockIdx.x < 36;
      for (int n = 0;; n++) {
        if (n > 0) { mbar_wait(bGo, (n - 1) & 1); mbar_wait(bIE + 8 * (n & 3), ((n >> 2) & 1) ^ 1); }
        int code = -1, spin = 0, ticket = 0;
        if (queries) {
          if (lane == 0) ticket = n == 0 ? blockIdx.x : 36 + atomicAdd(g_sync + SY_QC, 1);
          ticket = __shfl_sync(~0u, ticket, 0);
          queries = ticket < (16 - QA_END) * 32;
          if (queries) code = IT_Q << 16 | (QA_END + ticket % (16 - QA_END)) << 8 | ticket / (16 - QA_END);
        }
        if (!queries && lane == 0) asm volatile("atom.relaxed.gpu.global.add.u32 %0, [%1], 1;" : "=r"(ticket) : "l"(g_sync + SY_T) : "memory");
        while (!queries) {
          const uint4 hd = ldg_strong128(g_sync + b * 8), pr = ldg_strong128(g_sync + b * 8 + 4);
          if (n == 0 && spin == 0 && hd.x != 0x7fffffff) PST(2);
          const uint32_t hv[4] = {hd.x, hd.y, hd.z, hd.w}, pv[4] = {pr.x, pr.y, pr.z, pr.w};
          const uint32_t chain_done = __ballot_sync(~0u, (pr.x & 0xffff) >= 96) & 0xffff;
          int left[4], avail[4], rdy = 0, claimed = 0, upstream = 0;
#pragma unroll
          for (int t = 0; t < 4; t++) {
            const int cnt = lane < 16 ? item_count(t, b) : 0;
            left[t] = max(cnt - (int)hv[t], 0);
            claimed += cnt - left[t];
            const bool ready = (pv[t] & 0xffff) >= item_need(t, b);
            rdy |= ready << t;
            bool ok = ready || (t == IT_ATT ? pr.x >= 0x10000 : !upstream || (t == IT_OP && (chain_done >> 15 & 1)));
            if (t == IT_BQ && (chain_done >> BQ_HOLD & 1) && !(chain_done >> 15)) ok = false;
            avail[t] = ok ? left[t] : 0;
            upstream |= __any_sync(~0u, left[t] > 0);
          }
          if (!upstream) break;
          int rank = max(__shfl_sync(~0u, ticket, 0) - __reduce_add_sync(~0u, claimed), 0), type = -1, mine = 0;
#pragma unroll
          for (int c = 0; c < 8; c++) {
            const int t = c == PR_FIN || c == 5 ? IT_FIN : c == PR_ATT || c == 7 ? IT_ATT : c == PR_OP || c == 4 ? IT_OP : IT_BQ;
            int a = c == PR_ATT || ((rdy >> t & 1) == (c < 4)) ? avail[t] : 0;
            if (t == IT_OP && OP_EARLY) a = c == PR_OP ? avail[t] : 0;
            if (c == 7) a = b < QA_END && !(rdy & 1) && ((chain_done << 1 | 1) >> b & 1) ? left[t] : 0;
            const int tot = __reduce_add_sync(~0u, a);
            if (type < 0) { if (rank < tot) { type = t; mine = a; } else rank -= tot; }
          }
          if (type >= 0) {
#pragma unroll
            for (int o = 1; o < 16; o <<= 1) { const int y = __shfl_up_sync(~0u, mine, o); if (lane >= o) mine += y; }
            const int blk = __ffs(__ballot_sync(~0u, mine > rank)) - 1;
            const int early = !(__shfl_sync(~0u, rdy, blk) >> type & 1);
            uint32_t idx = 0;
            if (n == 0 && spin == 0) PST(3);
            if (lane == 0) asm volatile("atom.relaxed.gpu.global.add.u32 %0, [%1], 1;" : "=r"(idx) : "l"(g_sync + blk * 8 + type) : "memory");
            ld_acquire(g_sync + blk * 8 + 4 + type);
            idx = __shfl_sync(~0u, idx, 0);
            if (idx < item_count(type, blk)) { code = (chain_done >> 15 & 1) << 22 | (chain_done >> p.look & 1) << 21 | early << 20 | type << 16 | blk << 8 | idx; break; }
          } else {
            __nanosleep(50);
          }
          spin_guard(spin);
        }
        if (n == 0) bar_sync(2, 384);
        if (lane == 0) {
          fence_async_global();
          sts32(slots + 4 * (n & 3), code);
          mbar_arrive(bIF + 8 * (n & 3));
        }
        __syncwarp();
        if (code < 0) break;
      }
    } else if (warp == 8) {
      if (elect()) {
        uint32_t dst = sb, bar = bars, ph = 1, next = clk32(), gap = 0;
        auto acquire = [&](uint32_t kb) {
          mbar_wait(bar + 8 * PS, ph);
          mbar_expect(bar, kb * 1024);
          if (gap) {
            uint32_t now;
            do now = clk32(); while ((int)(now - next) < 0);
            next = ((int)(now - next) > 100 ? now - 100 : next) + kb * gap;
          }
        };
        auto advance = [&]() { dst += PB; bar += 8; if (dst == bars) { dst = sb; bar = bars; ph ^= 1; } };
        auto depend = [&](const uint32_t* c, uint32_t need) { wait_count(c, need); fence_async_global(); };
#pragma unroll 1
        for (int n = 0;; n++) {
          mbar_wait(bIF + 8 * (n & 3), (n >> 2) & 1);
          const int code = (int)lds32(slots + 4 * (n & 3));
          if (code < 0) break;
          const int type = (code >> 16) & 15, b = (code >> 8) & 255, idx = code & 255;
          const bool early = code >> 20 & 1, go = !(code >> 21 & 1);
          mbar_arrive(bIE + 8 * (n & 3));
          gap = !(code >> 22 & 1) ? lds32(slots + 16) : type == IT_ATT || type == IT_FIN ? 0 : p.gap2;
          const uint32_t* progress = g_sync + b * 8 + 4 + type;
          if (type == IT_ATT && b >= QA_END) {
            depend(g_sync + SY_Q, (16 - QA_END) * 32);
#pragma unroll 1
            for (int u = 0; u < 2; u++) { acquire(24); bulk_load_last(dst, g_q + (((b - QA_END) * 32 + idx) * 2 + u) * 1536, 24576, bar); advance(); }
          } else if (type == IT_FIN) {
            acquire(10);
            bulk_load(dst, g_x + (b * 16 + idx) * 1280, 10240, bar);
            advance();
            if (early) depend(progress, item_need(type, b));
            if (go) mbar_arrive(bGo);
            const uint2* src = g_part + (b * 16 + idx) * 16 * 1280;
#pragma unroll 1
            for (int i = 0; i < op_split(b); i += 2) { acquire(20); bulk_load_last(dst, src + i * 1280, 20480, bar); advance(); }
            if (!go && p.pol) mbar_arrive(bGo);
          } else {
            const bool op = type == IT_OP, bq = type == IT_BQ;
            const int width = op ? op_width(b) : bq ? bq_width(b) : 192, nb = (width + 63) >> 6, lt = width == 320 ? 1 : 2;
            const int nst = op ? 192 / op_split(b) : 20, kb0 = op ? (idx >> lt) * nst : 0;
            const int col = (op ? idx & ((1 << lt) - 1) : idx) * width;
            const bool whole = !(width & 63);
            const CUtensorMap* m = op ? (whole ? &p.wo : &p.wo2) : bq ? (whole ? &p.wb : &p.wb2) : &p.wq;
            const uint32_t* a = op ? g_o + (b * 192 + kb0) * 2048 : g_xn + b * 20 * 2048;
            int row = kb0 * 32, pre = early && (op || bq) ? min(nst, PRE_MAX) : 0;
            auto weights = [&]() {
              acquire(8 + nb * 4);
              if (whole) {
                tma_load3z(dst + 8192, m, row, col >> 6, bar);
              } else {
                tma_load(dst + 8192, m, col, row, bar); tma_load(dst + 12288, m, col + 64, row, bar);
                if (nb == 3) tma_load(dst + 16384, m, col + 128, row, bar);
              }
              row += 32;
            };
            if (pre) {
              uint32_t da = dst, ba = bar;
              const uint32_t g0 = gap;
              gap = max(gap, PRE_GAP);
#pragma unroll 1
              for (int kb = 0; kb < pre; kb++) { weights(); advance(); }
              gap = g0;
              depend(progress, item_need(type, b));
#pragma unroll 1
              for (int kb = 0; kb < pre; kb++) {
                bulk_load(da, a, 8192, ba);
                a += 2048; da += PB; ba += 8;
                if (da == bars) { da = sb; ba = bars; }
              }
            }
#pragma unroll 1
            for (int kb = pre; kb < nst; kb++) { weights(); if (op && OEF) bulk_load_last(dst, a, 8192, bar); else bulk_load(dst, a, 8192, bar); a += 2048; advance(); }
          }
          if (type == IT_ATT) {
            if (early) depend(progress, 96);
            if (go) mbar_arrive(bGo);
            const uint8_t* src = g_kv + (size_t)(idx * 6 * NSEG + b * 4) * KV_BYTES;
#pragma unroll 1
            for (int u = 0; u < 6; u++) {
              acquire(20);
              bulk_load_last(dst, src, 20480, bar);
              src += u == 2 ? -3 * KV_V : 2 * KV_V;
              advance();
            }
            if (!go && p.pol && ATT_LOOK) mbar_arrive(bGo);
          }
        }
      }
    } else if (warp == 11) {
      uint32_t smid, nsm, used = 0;
      asm("mov.u32 %0, %%smid;" : "=r"(smid)); asm("mov.u32 %0, %%nsmid;" : "=r"(nsm));
      for (int n = 0; n < 64 && used < 96; n++) {
        uint32_t peers = 0;
        used = 0;
        for (uint32_t i = lane; i < min(nsm, 256u); i += 32) {
          const bool taken = ldg_strong32(g_smuse + i) == p.layer + 1;
          used += taken;
          peers += abs((int)(g_smclk[i] - g_smclk[smid & 255])) < 4000 && !taken;
        }
        used = __reduce_add_sync(~0u, used);
        sts32(slots + 16, max(p.gap, (int)min(__reduce_add_sync(~0u, peers), 18u) * p.share >> 3));
      }
    } else if (warp == 10 && lane == 0) {
      for (int n = 0;; n++) {
        mbar_wait(bIF + 8 * (n & 3), (n >> 2) & 1);
        const int code = (int)lds32(slots + 4 * (n & 3));
        if (code < 0) break;
        const int type = (code >> 16) & 15, b = (code >> 8) & 255;
        mbar_wait(done + 8 * (n & 3), (n >> 2) & 1);
        if (type != IT_BQ) red_release(type == IT_Q ? g_sync + SY_Q : g_sync + b * 8 + 5 + type, 1);
        mbar_arrive(bIE + 8 * (n & 3));
      }
    }
  } else {
    asm volatile("setmaxnreg.inc.sync.aligned.u32 224;");
    bar_sync(2, 384);
    const int g = lane >> 2, c = lane & 3;
    Ring r = {sb, bars, 0, 0};
#pragma unroll 1
    for (int n = 0;; n++) {
      mbar_wait(bIF + 8 * (n & 3), (n >> 2) & 1);
      const int code = __shfl_sync(~0u, (int)lds32(slots + 4 * (n & 3)), 0);
      if (code < 0) { TRACE(2); break; }
      const int type = (code >> 16) & 15, b = (code >> 8) & 255, idx = code & 255;
      ITEM(code & 0xfffff, 0);
      if (type == IT_ATT || type == IT_Q) {
        uint32_t q[48];
        if (type == IT_Q || b < QA_END) {
          float d[96];
          gemm_item<192>(r, d, 20, bGo, type == IT_Q ? 12 : -1, warp >> 2);
#pragma unroll
          for (int i = 0; i < 48; i++) q[i] = pack2(d[2 * i], d[2 * i + 1]);
        } else {
#pragma unroll
          for (int u = 0; u < 2; u++) {
            const uint32_t base = r.wait() + threadIdx.x * 16;
#pragma unroll
            for (int i = 0; i < 6; i++) {
              const uint4 v = lds128(base + i * 4096);
              q[24 * u + 4 * i] = v.x; q[24 * u + 4 * i + 1] = v.y; q[24 * u + 4 * i + 2] = v.z; q[24 * u + 4 * i + 3] = v.w;
            }
            r.pop();
          }
        }
        if (type == IT_Q) {
          uint4* dst = g_q + ((b - QA_END) * 32 + idx) * 3072 + threadIdx.x;
#pragma unroll
          for (int i = 0; i < 12; i++) dst[i * 256] = make_uint4(q[4 * i], q[4 * i + 1], q[4 * i + 2], q[4 * i + 3]);
        } else if (warp < 4) {
          attn_a_warp<0>(r, q, b, idx);
        } else {
          attn_a_warp<1>(r, q, b, idx);
        }
      } else if (type == IT_FIN) {
        fin_item(r, scratch, b, idx);
      } else {
        float d[160];
        const int width = type == IT_OP ? op_width(b) : bq_width(b), nst = type == IT_OP ? 192 / op_split(b) : 20;
        const int go_at = max(nst - (code >> 21 & 1 ? p.pol : 6), 1);
        if (width == 320) {
          gemm_item<320>(r, d, nst, bGo, go_at, warp >> 2);
        } else {
          gemm_item<160>(r, d, nst, bGo, go_at, warp >> 2);
#pragma unroll
          for (int i = 80; i < 160; i++) d[i] = 0.f;
        }
        static_assert(BQ_80 == 16, "width");
        if (type == IT_OP) {
          const int tiles = DM / width;
          uint2* dst = g_part + (((b * 16 + warp * 2) * 16 + idx / tiles) * 40 + idx % tiles * (width / 16)) * 32 + lane;
#pragma unroll
          for (int u = 0; u < 20; u++) {
            if (u % 5 == 0 && u * 16 >= width) break;
            dst[u * 32] = make_uint2(pack2(d[8 * u], d[8 * u + 1]), pack2(d[8 * u + 4], d[8 * u + 5]));
            dst[(640 + u) * 32] = make_uint2(pack2(d[8 * u + 2], d[8 * u + 3]), pack2(d[8 * u + 6], d[8 * u + 7]));
          }
        } else {
          const int row = b * 128 + warp * 16 + g;
          const int h0 = idx * (width / 20);
          const float sc = h0 < 32 ? 0.22360679775f * 1.44269504089f : 1.f;
          const bool lo = c < 2;
          uint32_t* da = g_bqkv + (h0 * 256 + (row >> 3)) * 96 + lane;
          uint32_t* db = da + 256 * 96 + (lo ? 2 : -2);
          uint32_t pad[2];
#pragma unroll
          for (int rr = 0; rr < 2; rr++) pad[rr] = c & 1 || h0 < 32 ? 0u : h0 >= 64 ? 0x00003f80u : poly_group((row >> 3) + rr) ? 0x3f803f80u : 0u;
#pragma unroll
          for (int q = 0; q < 8; q++) {
            if (!(q & 1) && q * 40 >= width) break;
#pragma unroll
            for (int rr = 0; rr < 2; rr++) {
              uint32_t w[5];
#pragma unroll
              for (int i = 0; i < 5; i++) w[i] = pack2(d[20 * q + 4 * i + 2 * rr] * sc, d[20 * q + 4 * i + 2 * rr + 1] * sc);
              const int o = q * 2 * 256 * 96 + rr * 96;
              da[o] = w[0]; da[o + 32] = w[1]; da[o + 64] = lo ? w[2] : pad[rr];
              db[o] = lo ? w[3] : w[2]; db[o + 32] = lo ? w[4] : w[3]; db[o + 64] = lo ? pad[rr] : w[4];
            }
          }
        }
      }
      __syncwarp();
      if (lane == 0) mbar_arrive(done + 8 * (n & 3));
      if ((code >> 21 & 1) && (p.pol == 0 || (type == IT_ATT && !ATT_LOOK)) && threadIdx.x == 128) mbar_arrive(bGo);
      ITEM(code & 0xfffff, 1);
    }
  }
}

constexpr int AB_SMEM = 1024 + 98304 + 51200 + 4 * 16384 + 256 + 10240;
#define AB_LW 1
#define AB_U 8
#define AB_WG 4
constexpr int AB_T = AB_WG * 128, AB_PASS = 8 / AB_WG;
__device__ __forceinline__ uint32_t fma2(uint32_t a, uint32_t b, uint32_t c) { uint32_t r; asm("fma.rn.bf16x2 %0, %1, %2, %3;" : "=r"(r) : "r"(a), "r"(b), "r"(c)); return r; }
__device__ __forceinline__ uint32_t ex2_pair(float a, float b, uint32_t one, uint32_t c0) {
  const uint32_t e = __byte_perm(__float_as_uint(a), __float_as_uint(b), 0x6521);
  uint32_t x, r;
  asm("lop3.b32 %0, %1, 0x007f007f, %2, 0xEA;" : "=r"(x) : "r"(e), "r"(one));
  const uint32_t m = fma2(fma2(c0, x, 0x3c0d3c0du), x, 0x3f2b3f2bu);
  asm("lop3.b32 %0, %1, %2, 0x7f807f80, 0xE4;" : "=r"(r) : "r"(e), "r"(m));
  return r;
}
__device__ __forceinline__ float sq2(uint32_t w) { const float a = bf_lo(w), b = bf_hi(w); return fmaf(a, a, b * b); }

__device__ __forceinline__ void attn_b_store(const float* o, int h, int row0, int lane) {
  const int g = lane >> 2, c = lane & 3;
  const float i0 = __frcp_rn(__shfl_sync(~0u, o[8], (lane & ~3) | 2)), i1 = __frcp_rn(__shfl_sync(~0u, o[10], (lane & ~3) | 2));
#pragma unroll
  for (int jj = 0; jj < 3; jj++) {
    if (jj < 2 || c < 2) {
      const int col = h * 20 + 8 * jj + 2 * c;
      uint32_t* dst = g_of + (((row0 >> 7) * 10 + (col >> 6)) * 16 + (row0 >> 3 & 15)) * 256 + (col >> 3 & 7) * 32 + g * 4 + (col >> 1 & 3);
      dst[0] = pack2(o[4 * jj] * i0, o[4 * jj + 1] * i0);
      dst[256] = pack2(o[4 * jj + 2] * i1, o[4 * jj + 3] * i1);
    }
  }
}

struct AbParams { Weights next; uint32_t* done; uint32_t* out; };
__global__ void __launch_bounds__(AB_T + 32, 1) attn_b_kernel(const __grid_constant__ AbParams p) {
  extern __shared__ uint8_t smem_raw[];
  const uint32_t sb = (s2u(smem_raw) + 1023) & ~1023u, sK = sb, sV = sb + 98304, bars = sV + 51200 + 4 * 16384;
  const uint32_t bF = bars + 64, bW = bars + 72, bA = bars + 80, bE = bars + 128, smax = bars + 176;
  auto ring = [&](int i) { return i < 2 ? sK + 51200 + i * 16384 : sV + 51200 + (i - 2) * 16384; };
  const int warp = __shfl_sync(~0u, threadIdx.x >> 5, 0), lane = threadIdx.x & 31;
  const int h = blockIdx.x >> 2, quarter = blockIdx.x & 3;
  TRACE(0);
  pdl_launch();
  if (threadIdx.x < 22) mbar_init(bars + 8 * threadIdx.x, threadIdx.x == 8 ? AB_T / 32 : threadIdx.x >= 16 ? 8 : 1);
  if (threadIdx.x == 32) sts64(smax, 0, 0);
  fence_async();
  __syncthreads();
  pdl_wait();
  const int blk = quarter * 4 + (h >> 3), cg = h & 7;
  auto unsafe = [&]() { const float2 m = lds64f(smax); return !(m.x * m.y <= 10000.f); };
  if (warp == AB_T / 32) {
    auto load_w = [&]() {
      mbar_expect(bW, 102400);
      for (int i = 0; i < 4; i++) bulk_load((i < 2 ? sK : sV) + (i & 1) * 25600, g_wb + cg * 6400 + i * 1600, 25600, bW);
    };
    if (elect()) {
      const uint32_t* gk = g_bqkv + (32 + h) * 256 * 96;
#pragma unroll 1
      for (int i = 0; i < 8; i++) {
        if (i >= AB_LW) mbar_wait(bars + 8 * (i - AB_LW), 0);
        mbar_expect(bars + 8 * i, 24576);
        bulk_load_last(sK + i * 12288, gk + i * 3072, 12288, bars + 8 * i);
        bulk_load_last(sV + i * 12288, gk + 32 * 256 * 96 + i * 3072, 12288, bars + 8 * i);
      }
    }
    __syncwarp();
    if (blockIdx.x < NSLOT) for (int i = lane; i < 512; i += 32) reinterpret_cast<uint4*>(pool_at(blockIdx.x * 8192))[i] = make_uint4(0, 0, 0, 0);
    if (blockIdx.x == 127) for (int i = lane; i < SY_N; i += 32) g_sync[i] = 0;
    if (p.next.w[0] && lane == 0) {
      for (int i = 0; i < AB_PF; i++) { const uint32_t t0 = clk32(); while (clk32() - t0 < (i ? AB_PFD : AB_PF0)) __nanosleep(200); prefetch_weights(p.next, i); }
    }
    __syncwarp();
    mbar_wait(bF, 0);
    const bool redo = unsafe();
    if (!redo && lane == 0) load_w();
    if (lane < 16) asm volatile("cp.async.bulk.prefetch.L2.global [%0], 1280;" :: "l"(g_x + ((blk * 16 + lane) * 40 + cg * 5) * 32) : "memory");
    __syncwarp();
    bar_sync(1, AB_T + 32);
    if (lane == 0) {
      ABT(!!p.out, 1);
      red_release(p.done + quarter * 32, 1);
      ABT(!!p.out, 2);
      if (redo) load_w();
      wait_count(p.done + quarter * 32, 32);
      fence_async_global();
      ABT(!!p.out, 3);
      for (int kb = 0; kb < 10; kb++) {
        const int i = kb < 6 ? kb : kb - 6;
        if (kb >= 6) mbar_wait(bE + 8 * i, 0);
        mbar_expect(bA + 8 * i, 16384);
        bulk_load(ring(i), g_of + (blk * 10 + kb) * 4096, 16384, bA + 8 * i);
      }
    }
    return;
  }
  float qmax = 0.f;
  const uint32_t one = opaque(0x3f803f80u + (threadIdx.x >> 10)), c0 = opaque(0x3ea83ea8u + (threadIdx.x >> 10));
#pragma unroll 1
  for (int pass = 0; pass < AB_PASS; pass++) {
    const int row0 = quarter * 512 + ((warp >> 2) * AB_PASS + pass) * 64 + (warp & 3) * 16;
    const uint32_t* gq = g_bqkv + (h * 256 + (row0 >> 3)) * 96 + lane;
    const uint32_t q0 = gq[0], q1 = gq[96], q2 = gq[32], q3 = gq[128];
    uint32_t q4 = gq[64], q5 = gq[160];
    const uint32_t z0 = gq[64 + 3 - (lane & 3)], z1 = gq[160 + 3 - (lane & 3)];
    {
      float n0 = sq2(q0) + sq2(q2) + sq2(q4), n1 = sq2(q1) + sq2(q3) + sq2(q5);
      n0 += __shfl_xor_sync(~0u, n0, 1); n1 += __shfl_xor_sync(~0u, n1, 1);
      n0 += __shfl_xor_sync(~0u, n0, 2); n1 += __shfl_xor_sync(~0u, n1, 2);
      qmax = (n0 > qmax || n0 != n0) ? n0 : qmax;
      qmax = (n1 > qmax || n1 != n1) ? n1 : qmax;
    }
    if (pass == AB_PASS - 1) {
      float kmax = 0.f;
#pragma unroll
      for (int i = 0; i < SEQ / AB_T; i++) {
        const int key = threadIdx.x + AB_T * i;
        const uint32_t a = sK + (key >> 3) * 384 + (key & 7) * 16;
        const uint4 x = lds128(a), y = lds128(a + 128);
        const uint2 z = lds64(a + 256);
        const float n = ((sq2(x.x) + sq2(x.y)) + (sq2(x.z) + sq2(x.w))) + ((sq2(y.x) + sq2(y.y)) + (sq2(y.z) + sq2(y.w))) + (sq2(z.x) + sq2(z.y));
        kmax = (n > kmax || n != n) ? n : kmax;
      }
      const uint32_t kb = __reduce_max_sync(~0u, __float_as_uint(kmax) & 0x7fffffffu), qb = __reduce_max_sync(~0u, __float_as_uint(qmax) & 0x7fffffffu);
      if (lane < 2) asm volatile("red.shared.max.u32 [%0], %1;" :: "r"(smax + 4 * lane), "r"(lane ? kb : qb) : "memory");
      __syncwarp();
    }
    if ((lane & 3) == 2) { q4 = 0xBF8043C0u; q5 = 0xBF8043C0u; }
    float o[12];
    auto desc = [](uint32_t lo, uint32_t hi) { uint64_t d; asm("mov.b64 %0, {%1, %2};" : "=l"(d) : "r"(lo), "r"(hi)); return d; };
    const uint32_t k0 = (uint32_t)mkdesc(sK, 128, 0, 0), k1 = (uint32_t)mkdesc(sK + 256, 0, 0, 0), v0 = (uint32_t)mkdesc(sV, 384, 0, 0);
    float sa[16], sb2[16];
    uint32_t pa[8], pb[8];
    auto qk = [&](float* s, uint32_t t) {
      wg_rs32_00(s, q0, q1, q2, q3, desc(k0 + t, 24), 0);
      wg_rs32_00(s, q4, q5, z0, z1, desc(k1 + t, 24), 1);
      wg_commit();
    };
    auto step = [&](float* s, uint32_t* pp, int g0, uint32_t t, uint32_t nx, int acc) {
      wg_wait<1>();
      reg_fence<16>(s);
#pragma unroll
      for (int i = 0; i < 8; i++) pp[i] = poly_group(g0 + (i >> 1)) ? ex2_pair(s[2 * i], s[2 * i + 1], one, c0) : pack2(ex2(s[2 * i]), ex2(s[2 * i + 1]));
      wg_fence();
      wg_rs24_01(o, pp[0], pp[1], pp[2], pp[3], desc(v0 + t, 8), acc);
      wg_rs24_01(o, pp[4], pp[5], pp[6], pp[7], desc(v0 + t + 48, 8), 1);
      qk(s, nx);
    };
    if (pass == 0) mbar_wait(bars, 0);
    wg_fence();
    qk(sa, 0);
    qk(sb2, 96);
#pragma unroll 1
    for (uint32_t t = 0; t < 64 * 96; t += AB_U * 96) {
      const uint32_t nx = t + AB_U * 96 < 64 * 96 ? t + AB_U * 96 : 0;
      if (pass == AB_PASS - 1 && t == 40 * 96 && lane == 0) mbar_arrive(bF);
#pragma unroll
      for (int u = 0; u < AB_U; u += 2) {
        if (u == AB_U - 2 && pass == 0) mbar_wait(bars + 8 * (nx / 768), 0);
        step(sa, pa, 0, t + u * 96, u + 2 < AB_U ? t + (u + 2) * 96 : nx, u | t);
        step(sb2, pb, 4, t + u * 96 + 96, (u + 2 < AB_U ? t + (u + 2) * 96 : nx) + 96, 1);
      }
    }
    wg_wait<0>();
    reg_fence<12>(o); reg_fence<16>(sa); reg_fence<16>(sb2);
    attn_b_store(o, h, row0, lane);
  }
  mbar_wait(bF, 0);
  if (unsafe())
#pragma unroll 1
  for (int pass = 0; pass < AB_PASS; pass++) {
    const int row0 = quarter * 512 + ((warp >> 2) * AB_PASS + pass) * 64 + (warp & 3) * 16;
    const uint32_t* gq = g_bqkv + (h * 256 + (row0 >> 3)) * 96 + lane;
    const uint32_t q0 = gq[0], q1 = gq[96], q2 = gq[32], q3 = gq[128], q4 = gq[64], q5 = gq[160];
    float o[12];
#pragma unroll
    for (int i = 0; i < 12; i++) o[i] = 0.f;
    float m0 = -INFINITY, m1 = -INFINITY;
#pragma unroll 1
    for (int kt = 0; kt < 32; kt++) {
      float s[32];
      const uint64_t dk = mkdesc(sK + kt * 3072, 128, 384, 0), dk2 = mkdesc(sK + kt * 3072 + 256, 0, 384, 0);
      wg_fence();
      wg_rs64_00(s, q0, q1, q2, q3, dk, 0);
      wg_rs64_00(s, q4, q5, 0, 0, dk2, 1);
      wg_commit();
      wg_wait<0>();
      reg_fence<32>(s); reg_fence<12>(o);
      float n0 = m0, n1 = m1;
#pragma unroll
      for (int jj = 0; jj < 8; jj++) { n0 = fmaxf(n0, fmaxf(s[4 * jj], s[4 * jj + 1])); n1 = fmaxf(n1, fmaxf(s[4 * jj + 2], s[4 * jj + 3])); }
      n0 = fmaxf(n0, __shfl_xor_sync(~0u, n0, 1)); n0 = fmaxf(n0, __shfl_xor_sync(~0u, n0, 2));
      n1 = fmaxf(n1, __shfl_xor_sync(~0u, n1, 1)); n1 = fmaxf(n1, __shfl_xor_sync(~0u, n1, 2));
      const float r0 = ex2(m0 - n0), r1 = ex2(m1 - n1);
      m0 = n0; m1 = n1;
#pragma unroll
      for (int jj = 0; jj < 3; jj++) { o[4 * jj] *= r0; o[4 * jj + 1] *= r0; o[4 * jj + 2] *= r1; o[4 * jj + 3] *= r1; }
      uint32_t pp[16];
#pragma unroll
      for (int jj = 0; jj < 8; jj++) {
        pp[2 * jj] = pack2(ex2(s[4 * jj] - m0), ex2(s[4 * jj + 1] - m0));
        pp[2 * jj + 1] = pack2(ex2(s[4 * jj + 2] - m1), ex2(s[4 * jj + 3] - m1));
      }
      const uint64_t dv = mkdesc(sV + kt * 3072, 384, 128, 0);
      wg_fence();
#pragma unroll
      for (int kk = 0; kk < 4; kk++) wg_rs24_01(o, pp[4 * kk], pp[4 * kk + 1], pp[4 * kk + 2], pp[4 * kk + 3], dv + kk * 48, 1);
      wg_commit();
    }
    wg_wait<0>();
    reg_fence<12>(o);
    attn_b_store(o, h, row0, lane);
  }
  ABT(!!p.out, 0);
  bar_arrive(1, AB_T + 32);
  if (warp >= 12) return;
  const int g = lane >> 2, c = lane & 3;
  const bool live = opaque(threadIdx.x) < 256;
  float d[40] = {};
  uint2* x = g_x + ((blk * 16 + warp * 2) * 40 + cg * 5) * 32 + lane;
  if (warp < 8) {
#pragma unroll
  for (int i = 0; i < 10; i++) {
    const int r = i / 5, u = i % 5;
    const float4 t = unpack4(x[(r * 40 + u) * 32]);
    d[8 * u + 2 * r] = t.x; d[8 * u + 2 * r + 1] = t.y; d[8 * u + 4 + 2 * r] = t.z; d[8 * u + 5 + 2 * r] = t.w;
  }
  mbar_wait(bW, 0);
  reg_fence<40>(d);
  ABT(!!p.out, 4);
#pragma unroll 1
  for (int kb = 0; kb < 10; kb++) {
    const int i = kb < 6 ? kb : kb - 6;
    mbar_wait(bA + 8 * i, kb >= 6);
    const uint64_t da = mkdesc(ring(i) + (warp >> 2) * 8192, 128, 1024, 0), db = mkdesc(kb < 5 ? sK + kb * 10240 : sV + (kb - 5) * 10240, 1280, 128, 0);
    wg_fence();
#pragma unroll
    for (int kk = 0; kk < 4; kk++) wg_ss80_01(d, da + kk * 16, db + kk * 160, 1);
    wg_commit();
    if (kb > 0 && kb < 5) { wg_wait<1>(); if (lane == 0) mbar_arrive(bE + 8 * (kb - 1)); }
  }
  wg_wait<0>();
  reg_fence<40>(d);
  }
  ABT(!!p.out, 5);
  if (p.out) {
    if (warp >= 8) return;
    const uint32_t stage = sK + 83968 + warp * 2560 + (warp < 4 ? 0 : 131328 - 10240);
#pragma unroll
    for (int u = 0; u < 5; u++)
      stsm4(stage + (lane & 15) * 160 + u * 32 + (lane >> 4) * 16, pack2(d[8 * u], d[8 * u + 1]), pack2(d[8 * u + 2], d[8 * u + 3]),
            pack2(d[8 * u + 4], d[8 * u + 5]), pack2(d[8 * u + 6], d[8 * u + 7]));
    __syncwarp();
    uint4* out = reinterpret_cast<uint4*>(p.out + (blk * 128 + warp * 16) * (DM / 2) + cg * 40);
#pragma unroll
    for (int i = 0; i < 5; i++) { const int e = i * 32 + lane, r = e / 10; out[r * (DM / 8) + e - r * 10] = lds128(stage + e * 16); }
  } else {
    float2* stat = g_stat + blk * 1024 + (warp & 7) * 16 + g;
    float mean[2], rs[2];
#pragma unroll
    for (int r = 0; r < 2; r++) {
      float t = 0.f, q = 0.f;
#pragma unroll
      for (int i = 0; i < 10; i++) t += d[4 * i + 2 * r] + d[4 * i + 2 * r + 1];
      t += __shfl_xor_sync(~0u, t, 1); t += __shfl_xor_sync(~0u, t, 2);
      t *= 1.f / 80;
#pragma unroll
      for (int i = 0; i < 10; i++) { const float a = d[4 * i + 2 * r] - t, b = d[4 * i + 2 * r + 1] - t; q += a * a + b * b; }
      q += __shfl_xor_sync(~0u, q, 1); q += __shfl_xor_sync(~0u, q, 2);
      if (c == r && live) asm volatile("st.relaxed.gpu.global.v2.b32 [%0], {%1, %2};" :: "l"(stat + cg * 128 + r * 8), "r"(__float_as_uint(t)), "r"(nz(__float_as_uint(q))) : "memory");
    }
#pragma unroll
    for (int i = 0; i < 10; i++) {
      const int r = i / 5, u = i % 5;
      if (live) x[(r * 40 + u) * 32] = make_uint2(pack2(d[8 * u + 2 * r], d[8 * u + 2 * r + 1]), pack2(d[8 * u + 4 + 2 * r], d[8 * u + 5 + 2 * r]));
    }
    ABT(0, 6);
    uint2 e[4];
    int n = 0;
    do {
#pragma unroll
      for (int i = 0; i < 4; i++)
        asm volatile("ld.relaxed.gpu.global.v2.b32 {%0, %1}, [%2];" : "=r"(e[i].x), "=r"(e[i].y) : "l"(stat + (2 * c + (i & 1)) * 128 + (i >> 1) * 8) : "memory");
      spin_guard(n);
    } while (__any_sync(~0u, min(min(e[0].y, e[1].y), min(e[2].y, e[3].y)) == 0 && live));
#pragma unroll
    for (int r = 0; r < 2; r++) {
      const float m0 = __uint_as_float(e[2 * r].x), m1 = __uint_as_float(e[2 * r + 1].x);
      float t = m0 + m1;
      t += __shfl_xor_sync(~0u, t, 1); t += __shfl_xor_sync(~0u, t, 2);
      t *= 0.125f;
      float q = __uint_as_float(e[2 * r].y) + __uint_as_float(e[2 * r + 1].y) + 80.f * ((m0 - t) * (m0 - t) + (m1 - t) * (m1 - t));
      q += __shfl_xor_sync(~0u, q, 1); q += __shfl_xor_sync(~0u, q, 2);
      mean[r] = t; rs[r] = rsqrtf(q * (1.f / DM) + 1e-5f);
    }
    ABT(0, 7);
    uint32_t w[2][5][2];
#pragma unroll
    for (int i = 0; i < 20; i++) w[i & 1][i >> 2][i >> 1 & 1] = pack2((d[2 * i] - mean[i & 1]) * rs[i & 1], (d[2 * i + 1] - mean[i & 1]) * rs[i & 1]);
    ln_store(w, blk * 8 + warp, cg * 5, live);
  }
  ABT(!!p.out, 8);
  TRACE(2);
}

typedef CUresult (*EncodeFn)(CUtensorMap*, CUtensorMapDataType, cuuint32_t, void*, const cuuint64_t*, const cuuint64_t*,
                             const cuuint32_t*, const cuuint32_t*, CUtensorMapInterleave, CUtensorMapSwizzle,
                             CUtensorMapL2promotion, CUtensorMapFloatOOBfill);

void make_map(EncodeFn enc, CUtensorMap* m, const void* ptr, int cols, int rows, int nb) {
  const cuuint64_t dims[3] = {(cuuint64_t)(nb ? 64 : cols), (cuuint64_t)rows, (cuuint64_t)cols / 64};
  const cuuint64_t strides[2] = {(cuuint64_t)cols * 2, 128};
  const cuuint32_t box[3] = {64, 32, (cuuint32_t)nb}, es[3] = {1, 1, 1};
  enc(m, CU_TENSOR_MAP_DATA_TYPE_BFLOAT16, nb ? 3 : 2, const_cast<void*>(ptr), dims, strides, box, es, CU_TENSOR_MAP_INTERLEAVE_NONE,
      CU_TENSOR_MAP_SWIZZLE_128B, CU_TENSOR_MAP_L2_PROMOTION_L2_128B, CU_TENSOR_MAP_FLOAT_OOB_FILL_NONE);
}
template <class... KA, class... A>
void launch(void (*kern)(KA...), int grid, int block, int smem, int cluster, bool pdl, A... args) {
  cudaFuncSetAttribute(kern, cudaFuncAttributeMaxDynamicSharedMemorySize, smem);
  cudaLaunchConfig_t cfg = {};
  cfg.gridDim = dim3(grid); cfg.blockDim = dim3(block); cfg.dynamicSmemBytes = smem; cfg.stream = cudaStreamPerThread;
  cudaLaunchAttribute at[2];
  int n = 0;
  if (cluster > 1) { at[n].id = cudaLaunchAttributeClusterDimension; at[n].val.clusterDim.x = cluster; at[n].val.clusterDim.y = 1; at[n].val.clusterDim.z = 1; n++; }
  if (pdl) { at[n].id = cudaLaunchAttributeProgrammaticStreamSerialization; at[n].val.programmaticStreamSerializationAllowed = 1; n++; }
  cfg.attrs = at; cfg.numAttrs = n;
  cudaLaunchKernelEx(&cfg, kern, args...);
}
template <class T> void* sym(T& s) { void* p = nullptr; cudaGetSymbolAddress(&p, s); return p; }

}

#define MODE(b) 0
extern "C" void kernel_launch(void* const* d_in, const int* in_sizes, int n_in, void* d_out, int out_size) {
  const __nv_bfloat16* x = (const __nv_bfloat16*)d_in[0];
  void* fn = nullptr; cudaDriverEntryPointQueryResult qr;
  cudaGetDriverEntryPoint("cuTensorMapEncodeTiled", &fn, cudaEnableDefault, &qr);
  EncodeFn enc = (EncodeFn)fn;

  ChainParams ch = {};
  PostParams op = {};
  for (int i = 0; i < 3; i++) {
    const cuuint64_t dims[3] = {HD, 128, 5}, strides[2] = {HD * 2, HD * 256};
    const cuuint32_t box[3] = {64, 128, 5}, es[3] = {1, 1, 1};
    enc(i == 0 ? &ch.wq : i == 1 ? &ch.wk : &ch.wv, CU_TENSOR_MAP_DATA_TYPE_BFLOAT16, 3, d_in[2 + i], dims, strides, box, es, CU_TENSOR_MAP_INTERLEAVE_NONE,
        CU_TENSOR_MAP_SWIZZLE_128B, W_PROMO, CU_TENSOR_MAP_FLOAT_OOB_FILL_NONE);
  }
  {
    const cuuint64_t dims[3] = {DM, HD, 7}, strides[2] = {DM * 2, 64};
    const cuuint32_t box[3] = {32, 64, 7}, es[3] = {1, 1, 1};
    enc(&ch.wo, CU_TENSOR_MAP_DATA_TYPE_BFLOAT16, 3, d_in[5], dims, strides, box, es, CU_TENSOR_MAP_INTERLEAVE_NONE,
        CU_TENSOR_MAP_SWIZZLE_64B, CU_TENSOR_MAP_L2_PROMOTION_L2_128B, CU_TENSOR_MAP_FLOAT_OOB_FILL_NONE);
  }
  ch.mem0 = (const __nv_bfloat16*)d_in[1];
  ch.pool = (uint8_t*)(((uintptr_t)sym(g_pool) + 8191) & ~(uintptr_t)8191); ch.kv = (uint8_t*)sym(g_kv); ch.xc = (const uint32_t*)sym(g_xc); ch.sync = (uint32_t*)sym(g_sync);
  ch.d1 = 0; ch.d1b = 0; ch.d2 = 0; ch.d2b = 0;
  make_map(enc, &op.wq, d_in[2], HD, DM, 3);
  make_map(enc, &op.wo, d_in[5], DM, HD, 5); make_map(enc, &op.wo2, d_in[5], DM, HD, 0);
  make_map(enc, &op.wb, d_in[8], 1920, DM, 5); make_map(enc, &op.wb2, d_in[8], 1920, DM, 0);
  op.gap = 17; op.share = 20; op.look = 14; op.gap2 = 0; op.pol = 1;

  const Weights wa = {{(const uint8_t*)d_in[3], (const uint8_t*)d_in[4], (const uint8_t*)d_in[2], (const uint8_t*)d_in[5]}}, none = {};
  launch(first_kernel, 132, 384, 128 * 1024, 1, false, x, (const uint4*)d_in[9], wa);
  for (int layer = 0; layer < 2; layer++) {
    ch.layer = ch.d2b = op.layer = layer;
    launch(chain_kernel, 96, 256, CH_SMEM, 3, true, ch);
    launch(post_kernel, MODE(3) ? 36 : 132, 384, OP_SMEM, 1, !MODE(1), op);
    const AbParams ab = {layer == 0 ? wa : none, (uint32_t*)sym(g_bo) + layer * 128, layer == 0 ? nullptr : (uint32_t*)d_out};
    launch(attn_b_kernel, 128, AB_T + 32, AB_SMEM, 1, true, ab);
  }
}
```

```cpp
#include <cuda_runtime.h>
#include <cuda_bf16.h>
#include <cuda.h>
#include <stdint.h>

namespace {

constexpr int SEQ = 2048, DM = 640, HD = 6144, NSEG = 64;
constexpr int SPIN_LIMIT = 1 << 20;

__device__ __align__(128) uint2 g_x[SEQ * DM / 4];
__device__ __align__(128) uint32_t g_of[SEQ * DM / 2];
__device__ __align__(128) uint4 g_wb[DM * DM / 8];
__device__ __align__(16) float2 g_stat[16 * 8 * 128];
__device__ uint32_t g_bo[8 * 32];
__device__ __align__(128) uint4 g_q[SEQ * HD / 8];
__device__ __align__(128) uint32_t g_o[SEQ * HD / 2];
constexpr int KV_BYTES = 5120, KV_M = 4096, KV_V = NSEG * KV_BYTES;
__device__ __align__(128) uint8_t g_kv[96 * 2 * NSEG * KV_BYTES];
__device__ __align__(128) uint32_t g_xc[SEQ * DM / 2];
#define OP_B4 7
#define OP_B8 10
#define OP_B16 16
#define QA_END 11
__host__ __device__ constexpr int op_split(int b) { return b < OP_B4 ? 2 : b < OP_B8 ? 4 : b < OP_B16 ? 8 : 16; }
#define AB_PF 3
#define AB_PF0 0
#define AB_PFD 5000
#define W_PROMO CU_TENSOR_MAP_L2_PROMOTION_L2_128B
#define OP_EARLY 1
#define ATT_LOOK 1
#define PR_FIN 1
#define PR_ATT 0
#define PR_OP 2
#define PRE_MAX PS
#define BQ_RUSH 16
#define OEF 0
#define BQ_HOLD 6
#define WEF 1
#define FK_REP 4
#define FK_PF 1
#define BQ_160 10
#define BQ_80 16
#define OP_160 14
__host__ __device__ constexpr int op_width(int b) { return b < OP_160 ? 320 : 160; }
__host__ __device__ constexpr int bq_width(int b) { return b < BQ_160 ? 320 : b < BQ_80 ? 160 : 80; }
__device__ __align__(128) uint2 g_part[16 * 16 * 16 * 40 * 32];
__device__ __align__(128) uint32_t g_xn[SEQ * DM / 2];
constexpr int SY_Q = 128, SY_T = 160, SY_QC = 192, SY_N = 193;
__device__ __align__(16) uint32_t g_sync[SY_N];
constexpr int NSLOT = 92;
__device__ uint32_t g_pool[(NSLOT + 2) * 2048];
__device__ int g_smpart[256], g_orient[NSLOT];
__device__ uint32_t g_smclk[256], g_smuse[256];
__device__ uint32_t g_bqkv[3 * 32 * 256 * 96];

#define ABT(L, i)
#define PST(i)
#define MODE_D(b) 0
#define DELAY(d)
#define XT(i)
#define MISS(k, n)
#define PRO(i)
#define TRACE(w)
#define ITEM(code, w)
#define TR(i, v)
#define TM(i)
#define TM1(i)
#define TMD(i, dep)
#define TMV(i, at, v)

__device__ __forceinline__ uint32_t gtime() { uint32_t c; asm volatile("mov.u32 %0, %%globaltimer_lo;" : "=r"(c) :: "memory"); return c; }
__device__ __forceinline__ uint32_t clk32() { uint32_t c; asm volatile("mov.u32 %0, %%clock;" : "=r"(c) :: "memory"); return c; }
__device__ __forceinline__ uint32_t s2u(const void* p) { return (uint32_t)__cvta_generic_to_shared(p); }
__device__ __forceinline__ uint32_t pack2(float a, float b) {
  uint32_t r; asm("cvt.rn.bf16x2.f32 %0, %1, %2;" : "=r"(r) : "f"(b), "f"(a)); return r; }
__device__ __forceinline__ float bf_lo(uint32_t w) { return __uint_as_float(w << 16); }
__device__ __forceinline__ float bf_hi(uint32_t w) { return __uint_as_float(w & 0xffff0000u); }
__device__ __forceinline__ uint2 pack4(float4 v) { return make_uint2(pack2(v.x, v.y), pack2(v.z, v.w)); }
__device__ __forceinline__ float4 unpack4(uint2 w) { return make_float4(bf_lo(w.x), bf_hi(w.x), bf_lo(w.y), bf_hi(w.y)); }
__device__ __forceinline__ float ex2(float x) { float y; asm("ex2.approx.ftz.f32 %0, %1;" : "=f"(y) : "f"(x)); return y; }

__device__ __forceinline__ void mbar_init(uint32_t bar, uint32_t n) {
  asm volatile("mbarrier.init.shared::cta.b64 [%0], %1;" :: "r"(bar), "r"(n) : "memory"); }
__device__ __forceinline__ void mbar_expect(uint32_t bar, uint32_t bytes) {
  asm volatile("mbarrier.arrive.expect_tx.shared::cta.b64 _, [%0], %1;" :: "r"(bar), "r"(bytes) : "memory"); }
__device__ __forceinline__ void mbar_arrive(uint32_t bar) {
  asm volatile("mbarrier.arrive.shared::cta.b64 _, [%0];" :: "r"(bar) : "memory"); }
__device__ __forceinline__ void mbar_wait(uint32_t bar, uint32_t ph) {
  asm volatile("{.reg .pred p; .reg .u32 n; mov.u32 n, 0;\n"
               "W: mbarrier.try_wait.parity.shared::cta.b64 p, [%0], %1; @p bra D;\n"
               "add.u32 n, n, 1; setp.gt.u32 p, n, %2; @p trap; bra W;\n"
               "D: }" :: "r"(bar), "r"(ph), "n"(SPIN_LIMIT) : "memory");
}
__device__ __forceinline__ void mbar_wait_cluster(uint32_t bar, uint32_t ph) {
  asm volatile("{.reg .pred p; .reg .u32 n; mov.u32 n, 0;\n"
               "W: mbarrier.try_wait.parity.acquire.cluster.shared::cta.b64 p, [%0], %1; @p bra D;\n"
               "add.u32 n, n, 1; setp.gt.u32 p, n, %2; @p trap; bra W;\n"
               "D: }" :: "r"(bar), "r"(ph), "n"(SPIN_LIMIT) : "memory");
}
__device__ __forceinline__ void spin_guard(int& n) {
  asm volatile("{.reg .pred p; add.s32 %0, %0, 1; setp.gt.s32 p, %0, %1; @p trap;}" : "+r"(n) : "n"(SPIN_LIMIT));
}
__device__ __forceinline__ void pdl_wait() { asm volatile("griddepcontrol.wait;" ::: "memory"); TRACE(1); }
__device__ __forceinline__ void pdl_launch() { asm volatile("griddepcontrol.launch_dependents;" ::: "memory"); }
__device__ __forceinline__ uint32_t ld_acquire(const uint32_t* p) { uint32_t v; asm volatile("ld.acquire.gpu.global.u32 %0, [%1];" : "=r"(v) : "l"(p) : "memory"); return v; }
__device__ __forceinline__ void red_release(uint32_t* p, uint32_t v) { asm volatile("red.release.gpu.global.add.u32 [%0], %1;" :: "l"(p), "r"(v) : "memory"); }
__device__ __forceinline__ void red_relaxed(uint32_t* p, uint32_t v) { asm volatile("red.relaxed.gpu.global.add.u32 [%0], %1;" :: "l"(p), "r"(v) : "memory"); }
__device__ __forceinline__ void fence_async_global() { asm volatile("fence.proxy.async.global;" ::: "memory"); }
__device__ __forceinline__ void fence_async() { asm volatile("fence.proxy.async.shared::cta;" ::: "memory"); }
__device__ __forceinline__ void bar_sync(int id, int n) { asm volatile("bar.sync %0, %1;" :: "r"(id), "r"(n) : "memory"); }
__device__ __forceinline__ void bar_arrive(int id, int n) { asm volatile("bar.arrive %0, %1;" :: "r"(id), "r"(n) : "memory"); }
__device__ __forceinline__ void tma_load(uint32_t dst, const CUtensorMap* m, int c0, int c1, uint32_t bar) {
  asm volatile("cp.async.bulk.tensor.2d.shared::cluster.global.mbarrier::complete_tx::bytes [%0], [%1, {%3, %4}], [%2];"
               :: "r"(dst), "l"(m), "r"(bar), "r"(c0), "r"(c1) : "memory"); }
template <bool STREAM = false>
__device__ __forceinline__ void tma_load3(uint32_t dst, const CUtensorMap* m, int c0, int c1, uint32_t bar) {
  if (STREAM)
    asm volatile("{.reg .b64 pol; createpolicy.fractional.L2::evict_first.b64 pol, 1.0;\n"
                 "cp.async.bulk.tensor.3d.shared::cluster.global.mbarrier::complete_tx::bytes.L2::cache_hint [%0], [%1, {%3, %4, 0}], [%2], pol;}"
                 :: "r"(dst), "l"(m), "r"(bar), "r"(c0), "r"(c1) : "memory");
  else
  asm volatile("cp.async.bulk.tensor.3d.shared::cluster.global.mbarrier::complete_tx::bytes [%0], [%1, {%3, %4, 0}], [%2];"
               :: "r"(dst), "l"(m), "r"(bar), "r"(c0), "r"(c1) : "memory"); }
__device__ __forceinline__ void tma_load3z(uint32_t dst, const CUtensorMap* m, int c1, int c2, uint32_t bar) {
  asm volatile("cp.async.bulk.tensor.3d.shared::cluster.global.mbarrier::complete_tx::bytes [%0], [%1, {0, %3, %4}], [%2];"
               :: "r"(dst), "l"(m), "r"(bar), "r"(c1), "r"(c2) : "memory"); }
__device__ __forceinline__ void tma_store(const CUtensorMap* m, uint32_t src, int c0, int c1) {
  asm volatile("cp.async.bulk.tensor.2d.global.shared::cta.bulk_group [%0, {%2, %3}], [%1];"
               :: "l"(m), "r"(src), "r"(c0), "r"(c1) : "memory"); }
__device__ __forceinline__ void tma_store_stream(const CUtensorMap* m, uint32_t src, int c0, int c1) {
  asm volatile("{.reg .b64 pol; createpolicy.fractional.L2::evict_first.b64 pol, 1.0;\n"
               "cp.async.bulk.tensor.2d.global.shared::cta.bulk_group.L2::cache_hint [%0, {%2, %3}], [%1], pol;}"
               :: "l"(m), "r"(src), "r"(c0), "r"(c1) : "memory"); }
__device__ __forceinline__ void bulk_load(uint32_t dst, const void* src, uint32_t bytes, uint32_t bar) {
  asm volatile("cp.async.bulk.shared::cluster.global.mbarrier::complete_tx::bytes [%0], [%1], %2, [%3];"
               :: "r"(dst), "l"(src), "r"(bytes), "r"(bar) : "memory"); }
__device__ __forceinline__ void bulk_load_last(uint32_t dst, const void* src, uint32_t bytes, uint32_t bar) {
  asm volatile("{.reg .b64 pol; createpolicy.fractional.L2::evict_first.b64 pol, 1.0;\n"
               "cp.async.bulk.shared::cluster.global.mbarrier::complete_tx::bytes.L2::cache_hint [%0], [%1], %2, [%3], pol;}"
               :: "r"(dst), "l"(src), "r"(bytes), "r"(bar) : "memory"); }
__device__ __forceinline__ void tma_load_last(uint32_t dst, const CUtensorMap* m, int c0, int c1, uint32_t bar) {
  asm volatile("{.reg .b64 pol; createpolicy.fractional.L2::evict_first.b64 pol, 1.0;\n"
               "cp.async.bulk.tensor.2d.shared::cluster.global.mbarrier::complete_tx::bytes.L2::cache_hint [%0], [%1, {%3, %4}], [%2], pol;}"
               :: "r"(dst), "l"(m), "r"(bar), "r"(c0), "r"(c1) : "memory"); }
__device__ __forceinline__ void bulk_send(uint32_t dst, uint32_t src, uint32_t bytes, uint32_t bar) {
  asm volatile("cp.async.bulk.shared::cluster.shared::cta.mbarrier::complete_tx::bytes [%0], [%1], %2, [%3];"
               :: "r"(dst), "r"(src), "r"(bytes), "r"(bar) : "memory"); }
__device__ __forceinline__ void bulk_store(void* dst, uint32_t src, uint32_t bytes) {
  asm volatile("cp.async.bulk.global.shared::cta.bulk_group [%0], [%1], %2;" :: "l"(dst), "r"(src), "r"(bytes) : "memory"); }
__device__ __forceinline__ void bulk_commit() { asm volatile("cp.async.bulk.commit_group;" ::: "memory"); }
template <int N> __device__ __forceinline__ void bulk_wait_read() { asm volatile("cp.async.bulk.wait_group.read %0;" :: "n"(N) : "memory"); }
template <int N> __device__ __forceinline__ void bulk_wait() { asm volatile("cp.async.bulk.wait_group %0;" :: "n"(N) : "memory"); }

__device__ __forceinline__ uint64_t mkdesc(uint32_t addr, uint32_t lbo, uint32_t sbo, uint32_t sw) {
  return (uint64_t)((addr & 0x3FFFF) >> 4) | ((uint64_t)(lbo >> 4) << 16) | ((uint64_t)(sbo >> 4) << 32) | ((uint64_t)sw << 62); }
__device__ __forceinline__ void wg_fence() { asm volatile("wgmma.fence.sync.aligned;" ::: "memory"); }
__device__ __forceinline__ void wg_commit() { asm volatile("wgmma.commit_group.sync.aligned;" ::: "memory"); }
template <int N> __device__ __forceinline__ void wg_wait() { asm volatile("wgmma.wait_group.sync.aligned %0;" :: "n"(N) : "memory"); }
template <int N> __device__ __forceinline__ void reg_fence(float* d) {
#pragma unroll
  for (int i = 0; i < N; i++) asm volatile("" : "+f"(d[i]) :: "memory");
}

__device__ __forceinline__ void mma16(float* d, uint32_t a0, uint32_t a1, uint32_t a2, uint32_t a3, uint32_t b0, uint32_t b1) {
  asm volatile("mma.sync.aligned.m16n8k16.row.col.f32.bf16.bf16.f32 {%0,%1,%2,%3},{%4,%5,%6,%7},{%8,%9},{%0,%1,%2,%3};"
               : "+f"(d[0]), "+f"(d[1]), "+f"(d[2]), "+f"(d[3]) : "r"(a0), "r"(a1), "r"(a2), "r"(a3), "r"(b0), "r"(b1)); }
__device__ __forceinline__ void mma8(float* d, uint32_t a0, uint32_t a1, uint32_t b0) {
  asm volatile("mma.sync.aligned.m16n8k8.row.col.f32.bf16.bf16.f32 {%0,%1,%2,%3},{%4,%5},{%6},{%0,%1,%2,%3};"
               : "+f"(d[0]), "+f"(d[1]), "+f"(d[2]), "+f"(d[3]) : "r"(a0), "r"(a1), "r"(b0)); }
__device__ __forceinline__ void ldsm4(uint32_t* r, uint32_t a) {
  asm volatile("ldmatrix.sync.aligned.m8n8.x4.shared.b16 {%0,%1,%2,%3},[%4];" : "=r"(r[0]), "=r"(r[1]), "=r"(r[2]), "=r"(r[3]) : "r"(a) : "memory"); }
__device__ __forceinline__ void ldsm4t(uint32_t* r, uint32_t a) {
  asm volatile("ldmatrix.sync.aligned.m8n8.x4.trans.shared.b16 {%0,%1,%2,%3},[%4];" : "=r"(r[0]), "=r"(r[1]), "=r"(r[2]), "=r"(r[3]) : "r"(a) : "memory"); }
__device__ __forceinline__ void ldsm2(uint32_t* r, uint32_t a) {
  asm volatile("ldmatrix.sync.aligned.m8n8.x2.shared.b16 {%0,%1},[%2];" : "=r"(r[0]), "=r"(r[1]) : "r"(a) : "memory"); }
__device__ __forceinline__ void stsm4(uint32_t a, uint32_t r0, uint32_t r1, uint32_t r2, uint32_t r3) {
  asm volatile("stmatrix.sync.aligned.m8n8.x4.shared.b16 [%0], {%1,%2,%3,%4};" :: "r"(a), "r"(r0), "r"(r1), "r"(r2), "r"(r3) : "memory"); }
__device__ __forceinline__ void stsm2t(uint32_t a, uint32_t r0, uint32_t r1) {
  asm volatile("stmatrix.sync.aligned.m8n8.x2.trans.shared.b16 [%0], {%1,%2};" :: "r"(a), "r"(r0), "r"(r1) : "memory"); }
__device__ __forceinline__ void stsm4t(uint32_t a, uint32_t r0, uint32_t r1, uint32_t r2, uint32_t r3) {
  asm volatile("stmatrix.sync.aligned.m8n8.x4.trans.shared.b16 [%0], {%1,%2,%3,%4};" :: "r"(a), "r"(r0), "r"(r1), "r"(r2), "r"(r3) : "memory"); }
__device__ __forceinline__ void st_async128(uint32_t a, uint4 v, uint32_t bar) {
  asm volatile("st.async.shared::cluster.mbarrier::complete_tx::bytes.v4.b32 [%0], {%1,%2,%3,%4}, [%5];" :: "r"(a), "r"(v.x), "r"(v.y), "r"(v.z), "r"(v.w), "r"(bar) : "memory"); }
__device__ __forceinline__ void sts32(uint32_t a, uint32_t v) { asm volatile("st.shared.b32 [%0], %1;" :: "r"(a), "r"(v) : "memory"); }
__device__ __forceinline__ void sts64f(uint32_t a, float x, float y) { asm volatile("st.shared.v2.f32 [%0], {%1,%2};" :: "r"(a), "f"(x), "f"(y) : "memory"); }
__device__ __forceinline__ void sts128(uint32_t a, uint4 v) {
  asm volatile("st.shared.v4.b32 [%0], {%1,%2,%3,%4};" :: "r"(a), "r"(v.x), "r"(v.y), "r"(v.z), "r"(v.w) : "memory"); }
__device__ __forceinline__ void sts128f(uint32_t a, float x, float y, float z, float w) {
  asm volatile("st.shared.v4.f32 [%0], {%1,%2,%3,%4};" :: "r"(a), "f"(x), "f"(y), "f"(z), "f"(w) : "memory"); }
__device__ __forceinline__ float lds32f(uint32_t a) { float v; asm volatile("ld.shared.f32 %0, [%1];" : "=f"(v) : "r"(a) : "memory"); return v; }
__device__ __forceinline__ float2 lds64f(uint32_t a) { float2 v; asm volatile("ld.shared.v2.f32 {%0,%1}, [%2];" : "=f"(v.x), "=f"(v.y) : "r"(a) : "memory"); return v; }
__device__ __forceinline__ float4 lds128f(uint32_t a) {
  float4 v; asm volatile("ld.shared.v4.f32 {%0,%1,%2,%3}, [%4];" : "=f"(v.x), "=f"(v.y), "=f"(v.z), "=f"(v.w) : "r"(a) : "memory"); return v; }
__device__ __forceinline__ uint4 lds128(uint32_t a) {
  uint4 v; asm volatile("ld.shared.v4.b32 {%0,%1,%2,%3}, [%4];" : "=r"(v.x), "=r"(v.y), "=r"(v.z), "=r"(v.w) : "r"(a) : "memory"); return v; }
__device__ __forceinline__ uint4 ldg_strong128(const void* p) {
  uint4 v; asm volatile("ld.relaxed.gpu.global.v4.u32 {%0,%1,%2,%3}, [%4];" : "=r"(v.x), "=r"(v.y), "=r"(v.z), "=r"(v.w) : "l"(p) : "memory"); return v; }
__device__ __forceinline__ void stg_strong32(void* p, uint32_t v) { asm volatile("st.relaxed.gpu.global.u32 [%0], %1;" :: "l"(p), "r"(v) : "memory"); }
__device__ __forceinline__ void stg_strong16(void* p, uint32_t v) { asm volatile("st.relaxed.gpu.global.u16 [%0], %1;" :: "l"(p), "h"((uint16_t)v) : "memory"); }
__device__ __forceinline__ void stg_strong128(void* p, uint4 v) {
  asm volatile("st.relaxed.gpu.global.v4.u32 [%0], {%1,%2,%3,%4};" :: "l"(p), "r"(v.x), "r"(v.y), "r"(v.z), "r"(v.w) : "memory"); }
__device__ __forceinline__ uint32_t mapa(uint32_t a, uint32_t r) {
  uint32_t o; asm("mapa.shared::cluster.u32 %0, %1, %2;" : "=r"(o) : "r"(a), "r"(r)); return o; }
__device__ __forceinline__ void st_async2f(uint32_t a, float x, float y, uint32_t bar) {
  asm volatile("st.async.shared::cluster.mbarrier::complete_tx::bytes.v2.f32 [%0], {%1,%2}, [%3];" :: "r"(a), "f"(x), "f"(y), "r"(bar) : "memory"); }
__device__ __forceinline__ void st_async32(uint32_t a, uint32_t x, uint32_t bar) {
  asm volatile("st.async.shared::cluster.mbarrier::complete_tx::bytes.b32 [%0], %1, [%2];" :: "r"(a), "r"(x), "r"(bar) : "memory"); }
__device__ __forceinline__ uint32_t lds32(uint32_t a) { uint32_t v; asm volatile("ld.shared.b32 %0, [%1];" : "=r"(v) : "r"(a) : "memory"); return v; }
__device__ __forceinline__ void st_async64(uint32_t a, uint32_t x, uint32_t y, uint32_t bar) {
  asm volatile("st.async.shared::cluster.mbarrier::complete_tx::bytes.v2.b32 [%0], {%1,%2}, [%3];" :: "r"(a), "r"(x), "r"(y), "r"(bar) : "memory"); }
__device__ __forceinline__ uint2 lds64(uint32_t a) { uint2 v; asm volatile("ld.shared.v2.b32 {%0,%1}, [%2];" : "=r"(v.x), "=r"(v.y) : "r"(a) : "memory"); return v; }
__device__ __forceinline__ void sts64(uint32_t a, uint32_t x, uint32_t y) { asm volatile("st.shared.v2.b32 [%0], {%1,%2};" :: "r"(a), "r"(x), "r"(y) : "memory"); }
__device__ __forceinline__ uint32_t ldg_strong32(const void* p) { uint32_t v; asm volatile("ld.relaxed.gpu.global.u32 %0, [%1];" : "=r"(v) : "l"(p) : "memory"); return v; }
__device__ __forceinline__ uint32_t transpose8(uint32_t x) { uint32_t r; asm volatile("movmatrix.sync.aligned.m8n8.trans.b16 %0, %1;" : "=r"(r) : "r"(x)); return r; }
__device__ __forceinline__ uint32_t hadd2(uint32_t a, uint32_t b) { uint32_t r; asm("add.rn.bf16x2 %0, %1, %2;" : "=r"(r) : "r"(a), "r"(b)); return r; }
__device__ __forceinline__ uint32_t min4(uint4 v) { return min(__vimin3_u32(v.x, v.y, v.z), v.w); }

__device__ __forceinline__ void wg_ss192_01(float* d, uint64_t da, uint64_t db, int sd) {
  asm volatile("{.reg .pred p; setp.ne.b32 p, %98, 0;\n"
    "wgmma.mma_async.sync.aligned.m64n192k16.f32.bf16.bf16 {%0,%1,%2,%3,%4,%5,%6,%7,%8,%9,%10,%11,%12,%13,%14,%15,%16,%17,%18,%19,%20,%21,%22,%23,%24,%25,%26,%27,%28,%29,%30,%31,%32,%33,%34,%35,%36,%37,%38,%39,%40,%41,%42,%43,%44,%45,%46,%47,%48,%49,%50,%51,%52,%53,%54,%55,%56,%57,%58,%59,%60,%61,%62,%63,%64,%65,%66,%67,%68,%69,%70,%71,%72,%73,%74,%75,%76,%77,%78,%79,%80,%81,%82,%83,%84,%85,%86,%87,%88,%89,%90,%91,%92,%93,%94,%95}, %96, %97, p, 1, 1, 0, 1;}"
    : "+f"(d[0]),"+f"(d[1]),"+f"(d[2]),"+f"(d[3]),"+f"(d[4]),"+f"(d[5]),"+f"(d[6]),"+f"(d[7]),"+f"(d[8]),"+f"(d[9]),"+f"(d[10]),"+f"(d[11]),"+f"(d[12]),"+f"(d[13]),"+f"(d[14]),"+f"(d[15]),"+f"(d[16]),"+f"(d[17]),"+f"(d[18]),"+f"(d[19]),"+f"(d[20]),"+f"(d[21]),"+f"(d[22]),"+f"(d[23]),"+f"(d[24]),"+f"(d[25]),"+f"(d[26]),"+f"(d[27]),"+f"(d[28]),"+f"(d[29]),"+f"(d[30]),"+f"(d[31]),"+f"(d[32]),"+f"(d[33]),"+f"(d[34]),"+f"(d[35]),"+f"(d[36]),"+f"(d[37]),"+f"(d[38]),"+f"(d[39]),"+f"(d[40]),"+f"(d[41]),"+f"(d[42]),"+f"(d[43]),"+f"(d[44]),"+f"(d[45]),"+f"(d[46]),"+f"(d[47]),"+f"(d[48]),"+f"(d[49]),"+f"(d[50]),"+f"(d[51]),"+f"(d[52]),"+f"(d[53]),"+f"(d[54]),"+f"(d[55]),"+f"(d[56]),"+f"(d[57]),"+f"(d[58]),"+f"(d[59]),"+f"(d[60]),"+f"(d[61]),"+f"(d[62]),"+f"(d[63]),"+f"(d[64]),"+f"(d[65]),"+f"(d[66]),"+f"(d[67]),"+f"(d[68]),"+f"(d[69]),"+f"(d[70]),"+f"(d[71]),"+f"(d[72]),"+f"(d[73]),"+f"(d[74]),"+f"(d[75]),"+f"(d[76]),"+f"(d[77]),"+f"(d[78]),"+f"(d[79]),"+f"(d[80]),"+f"(d[81]),"+f"(d[82]),"+f"(d[83]),"+f"(d[84]),"+f"(d[85]),"+f"(d[86]),"+f"(d[87]),"+f"(d[88]),"+f"(d[89]),"+f"(d[90]),"+f"(d[91]),"+f"(d[92]),"+f"(d[93]),"+f"(d[94]),"+f"(d[95])
    : "l"(da), "l"(db), "r"(sd));
}
__device__ __forceinline__ void wg_ss128_01(float* d, uint64_t da, uint64_t db, int sd) {
  asm volatile("{.reg .pred p; setp.ne.b32 p, %66, 0;\n"
    "wgmma.mma_async.sync.aligned.m64n128k16.f32.bf16.bf16 {%0,%1,%2,%3,%4,%5,%6,%7,%8,%9,%10,%11,%12,%13,%14,%15,%16,%17,%18,%19,%20,%21,%22,%23,%24,%25,%26,%27,%28,%29,%30,%31,%32,%33,%34,%35,%36,%37,%38,%39,%40,%41,%42,%43,%44,%45,%46,%47,%48,%49,%50,%51,%52,%53,%54,%55,%56,%57,%58,%59,%60,%61,%62,%63}, %64, %65, p, 1, 1, 0, 1;}"
    : "+f"(d[0]),"+f"(d[1]),"+f"(d[2]),"+f"(d[3]),"+f"(d[4]),"+f"(d[5]),"+f"(d[6]),"+f"(d[7]),"+f"(d[8]),"+f"(d[9]),"+f"(d[10]),"+f"(d[11]),"+f"(d[12]),"+f"(d[13]),"+f"(d[14]),"+f"(d[15]),"+f"(d[16]),"+f"(d[17]),"+f"(d[18]),"+f"(d[19]),"+f"(d[20]),"+f"(d[21]),"+f"(d[22]),"+f"(d[23]),"+f"(d[24]),"+f"(d[25]),"+f"(d[26]),"+f"(d[27]),"+f"(d[28]),"+f"(d[29]),"+f"(d[30]),"+f"(d[31]),"+f"(d[32]),"+f"(d[33]),"+f"(d[34]),"+f"(d[35]),"+f"(d[36]),"+f"(d[37]),"+f"(d[38]),"+f"(d[39]),"+f"(d[40]),"+f"(d[41]),"+f"(d[42]),"+f"(d[43]),"+f"(d[44]),"+f"(d[45]),"+f"(d[46]),"+f"(d[47]),"+f"(d[48]),"+f"(d[49]),"+f"(d[50]),"+f"(d[51]),"+f"(d[52]),"+f"(d[53]),"+f"(d[54]),"+f"(d[55]),"+f"(d[56]),"+f"(d[57]),"+f"(d[58]),"+f"(d[59]),"+f"(d[60]),"+f"(d[61]),"+f"(d[62]),"+f"(d[63])
    : "l"(da), "l"(db), "r"(sd));
}
__device__ __forceinline__ void wg_ss160_01(float* d, uint64_t da, uint64_t db, int sd) {
  asm volatile("{.reg .pred p; setp.ne.b32 p, %82, 0;\n"
    "wgmma.mma_async.sync.aligned.m64n160k16.f32.bf16.bf16 {%0,%1,%2,%3,%4,%5,%6,%7,%8,%9,%10,%11,%12,%13,%14,%15,%16,%17,%18,%19,%20,%21,%22,%23,%24,%25,%26,%27,%28,%29,%30,%31,%32,%33,%34,%35,%36,%37,%38,%39,%40,%41,%42,%43,%44,%45,%46,%47,%48,%49,%50,%51,%52,%53,%54,%55,%56,%57,%58,%59,%60,%61,%62,%63,%64,%65,%66,%67,%68,%69,%70,%71,%72,%73,%74,%75,%76,%77,%78,%79}, %80, %81, p, 1, 1, 0, 1;}"
    : "+f"(d[0]),"+f"(d[1]),"+f"(d[2]),"+f"(d[3]),"+f"(d[4]),"+f"(d[5]),"+f"(d[6]),"+f"(d[7]),"+f"(d[8]),"+f"(d[9]),"+f"(d[10]),"+f"(d[11]),"+f"(d[12]),"+f"(d[13]),"+f"(d[14]),"+f"(d[15]),"+f"(d[16]),"+f"(d[17]),"+f"(d[18]),"+f"(d[19]),"+f"(d[20]),"+f"(d[21]),"+f"(d[22]),"+f"(d[23]),"+f"(d[24]),"+f"(d[25]),"+f"(d[26]),"+f"(d[27]),"+f"(d[28]),"+f"(d[29]),"+f"(d[30]),"+f"(d[31]),"+f"(d[32]),"+f"(d[33]),"+f"(d[34]),"+f"(d[35]),"+f"(d[36]),"+f"(d[37]),"+f"(d[38]),"+f"(d[39]),"+f"(d[40]),"+f"(d[41]),"+f"(d[42]),"+f"(d[43]),"+f"(d[44]),"+f"(d[45]),"+f"(d[46]),"+f"(d[47]),"+f"(d[48]),"+f"(d[49]),"+f"(d[50]),"+f"(d[51]),"+f"(d[52]),"+f"(d[53]),"+f"(d[54]),"+f"(d[55]),"+f"(d[56]),"+f"(d[57]),"+f"(d[58]),"+f"(d[59]),"+f"(d[60]),"+f"(d[61]),"+f"(d[62]),"+f"(d[63]),"+f"(d[64]),"+f"(d[65]),"+f"(d[66]),"+f"(d[67]),"+f"(d[68]),"+f"(d[69]),"+f"(d[70]),"+f"(d[71]),"+f"(d[72]),"+f"(d[73]),"+f"(d[74]),"+f"(d[75]),"+f"(d[76]),"+f"(d[77]),"+f"(d[78]),"+f"(d[79])
    : "l"(da), "l"(db), "r"(sd));
}
__device__ __forceinline__ void wg_ss80_01(float* d, uint64_t da, uint64_t db, int sd) {
  asm volatile("{.reg .pred p; setp.ne.b32 p, %42, 0;\n"
    "wgmma.mma_async.sync.aligned.m64n80k16.f32.bf16.bf16 {%0,%1,%2,%3,%4,%5,%6,%7,%8,%9,%10,%11,%12,%13,%14,%15,%16,%17,%18,%19,%20,%21,%22,%23,%24,%25,%26,%27,%28,%29,%30,%31,%32,%33,%34,%35,%36,%37,%38,%39}, %40, %41, p, 1, 1, 0, 1;}"
    : "+f"(d[0]),"+f"(d[1]),"+f"(d[2]),"+f"(d[3]),"+f"(d[4]),"+f"(d[5]),"+f"(d[6]),"+f"(d[7]),"+f"(d[8]),"+f"(d[9]),"+f"(d[10]),"+f"(d[11]),"+f"(d[12]),"+f"(d[13]),"+f"(d[14]),"+f"(d[15]),"+f"(d[16]),"+f"(d[17]),"+f"(d[18]),"+f"(d[19]),"+f"(d[20]),"+f"(d[21]),"+f"(d[22]),"+f"(d[23]),"+f"(d[24]),"+f"(d[25]),"+f"(d[26]),"+f"(d[27]),"+f"(d[28]),"+f"(d[29]),"+f"(d[30]),"+f"(d[31]),"+f"(d[32]),"+f"(d[33]),"+f"(d[34]),"+f"(d[35]),"+f"(d[36]),"+f"(d[37]),"+f"(d[38]),"+f"(d[39])
    : "l"(da), "l"(db), "r"(sd));
}
__device__ __forceinline__ void wg_rs32_00(float* d, uint32_t a0, uint32_t a1, uint32_t a2, uint32_t a3, uint64_t db, int sd) {
  asm volatile("{.reg .pred p; setp.ne.b32 p, %21, 0;\n"
    "wgmma.mma_async.sync.aligned.m64n32k16.f32.bf16.bf16 {%0,%1,%2,%3,%4,%5,%6,%7,%8,%9,%10,%11,%12,%13,%14,%15}, {%16,%17,%18,%19}, %20, p, 1, 1, 0;}"
    : "+f"(d[0]),"+f"(d[1]),"+f"(d[2]),"+f"(d[3]),"+f"(d[4]),"+f"(d[5]),"+f"(d[6]),"+f"(d[7]),"+f"(d[8]),"+f"(d[9]),"+f"(d[10]),"+f"(d[11]),"+f"(d[12]),"+f"(d[13]),"+f"(d[14]),"+f"(d[15])
    : "r"(a0), "r"(a1), "r"(a2), "r"(a3), "l"(db), "r"(sd));
}
__device__ __forceinline__ void wg_rs64_00(float* d, uint32_t a0, uint32_t a1, uint32_t a2, uint32_t a3, uint64_t db, int sd) {
  asm volatile("{.reg .pred p; setp.ne.b32 p, %37, 0;\n"
    "wgmma.mma_async.sync.aligned.m64n64k16.f32.bf16.bf16 {%0,%1,%2,%3,%4,%5,%6,%7,%8,%9,%10,%11,%12,%13,%14,%15,%16,%17,%18,%19,%20,%21,%22,%23,%24,%25,%26,%27,%28,%29,%30,%31}, {%32,%33,%34,%35}, %36, p, 1, 1, 0;}"
    : "+f"(d[0]),"+f"(d[1]),"+f"(d[2]),"+f"(d[3]),"+f"(d[4]),"+f"(d[5]),"+f"(d[6]),"+f"(d[7]),"+f"(d[8]),"+f"(d[9]),"+f"(d[10]),"+f"(d[11]),"+f"(d[12]),"+f"(d[13]),"+f"(d[14]),"+f"(d[15]),"+f"(d[16]),"+f"(d[17]),"+f"(d[18]),"+f"(d[19]),"+f"(d[20]),"+f"(d[21]),"+f"(d[22]),"+f"(d[23]),"+f"(d[24]),"+f"(d[25]),"+f"(d[26]),"+f"(d[27]),"+f"(d[28]),"+f"(d[29]),"+f"(d[30]),"+f"(d[31])
    : "r"(a0), "r"(a1), "r"(a2), "r"(a3), "l"(db), "r"(sd));
}
__device__ __forceinline__ void wg_rs24_01(float* d, uint32_t a0, uint32_t a1, uint32_t a2, uint32_t a3, uint64_t db, int sd) {
  asm volatile("{.reg .pred p; setp.ne.b32 p, %17, 0;\n"
    "wgmma.mma_async.sync.aligned.m64n24k16.f32.bf16.bf16 {%0,%1,%2,%3,%4,%5,%6,%7,%8,%9,%10,%11}, {%12,%13,%14,%15}, %16, p, 1, 1, 1;}"
    : "+f"(d[0]),"+f"(d[1]),"+f"(d[2]),"+f"(d[3]),"+f"(d[4]),"+f"(d[5]),"+f"(d[6]),"+f"(d[7]),"+f"(d[8]),"+f"(d[9]),"+f"(d[10]),"+f"(d[11])
    : "r"(a0), "r"(a1), "r"(a2), "r"(a3), "l"(db), "r"(sd));
}

#define AB_POLY 0xae
__device__ __forceinline__ constexpr bool poly_group(int group) { return (AB_POLY >> (group & 7)) & 1; }

template <int V> struct Int { static constexpr int value = V; };

template <int NG>
__device__ __forceinline__ void ln_stats(const float4 (&v)[NG][5], uint32_t scratch, float (&mean)[NG], float (&rs)[NG]) {
  const int warp = threadIdx.x >> 5, lane = threadIdx.x & 31;
#pragma unroll
  for (int r = 0; r < NG; r++) {
    float s = 0.f, q = 0.f;
#pragma unroll
    for (int i = 0; i < 5; i++) s += (v[r][i].x + v[r][i].y) + (v[r][i].z + v[r][i].w);
    s += __shfl_xor_sync(~0u, s, 1); s += __shfl_xor_sync(~0u, s, 2);
    s *= 1.f / 80;
#pragma unroll
    for (int i = 0; i < 5; i++) {
      const float x = v[r][i].x - s, y = v[r][i].y - s, z = v[r][i].z - s, w = v[r][i].w - s;
      q += (x * x + y * y) + (z * z + w * w);
    }
    q += __shfl_xor_sync(~0u, q, 1); q += __shfl_xor_sync(~0u, q, 2);
    mean[r] = s; rs[r] = q;
  }
  bar_sync(1, 256);
  if ((lane & 3) == 0) {
#pragma unroll
    for (int r = 0; r < NG; r++) sts64f(scratch + r * 512 + lane * 16 + warp * 8, mean[r], rs[r]);
  }
  bar_sync(1, 256);
#pragma unroll
  for (int r = 0; r < NG; r++) {
    const float4 e = lds128f(scratch + r * 512 + lane * 16);
    float t = e.x + e.z;
    t += __shfl_xor_sync(~0u, t, 1); t += __shfl_xor_sync(~0u, t, 2);
    t *= 0.125f;
    float q = e.y + e.w + 80.f * ((e.x - t) * (e.x - t) + (e.z - t) * (e.z - t));
    q += __shfl_xor_sync(~0u, q, 1); q += __shfl_xor_sync(~0u, q, 2);
    mean[r] = t; rs[r] = rsqrtf(q * (1.f / DM) + 1e-5f);
  }
}

__device__ __forceinline__ void ln_store(const uint32_t (&w)[2][5][2], int tile, int u0, bool live = true) {
  const int lane = threadIdx.x & 31;
  uint32_t* xc = g_xc + ((tile >> 1) * 40 + u0) * 256 + (tile & 1) * 64 + lane;
#pragma unroll
  for (int i = 0; i < 20; i++) if (live) xc[(i >> 1) * 128 + (i & 1) * 32] = w[i & 1][i >> 2][i >> 1 & 1];
#pragma unroll
  for (int i = 0; i < 5; i++) {
    const int u = u0 + i;
    uint32_t* xn = g_xn + (((tile >> 3) * 20 + (u >> 1)) * 16 + (tile & 1) * 8 + (tile & 6)) * 128 + (u & 1) * 64 + lane;
#pragma unroll
    for (int r = 0; r < 2; r++) if (live) { xn[r * 128] = w[r][i][0]; xn[r * 128 + 32] = w[r][i][1]; }
  }
}
__device__ __forceinline__ void wait_count(const uint32_t* c, uint32_t n) {
  int spin = 0;
  while ((ld_acquire(c) & 0xffff) < n) { __nanosleep(32); spin_guard(spin); }
}

__device__ __forceinline__ uint8_t* pool_at(uint32_t off) {
  return reinterpret_cast<uint8_t*>((reinterpret_cast<uintptr_t>(g_pool) + 8191) & ~(uintptr_t)8191) + off; }
struct Weights { const uint8_t* w[4]; };
__device__ __forceinline__ void prefetch_weights(const Weights& p, int i) {
  if (blockIdx.x < 128) asm volatile("cp.async.bulk.prefetch.L2.global [%0], 61440;" :: "l"(p.w[i] + (size_t)blockIdx.x * 61440) : "memory");
}
__global__ void __launch_bounds__(384) first_kernel(const __nv_bfloat16* __restrict__ xin, const uint4* __restrict__ wb, const __grid_constant__ Weights wa) {
  __shared__ __align__(16) float scratch[256];
  __shared__ uint32_t lat[4];
  const int warp = threadIdx.x >> 5, lane = threadIdx.x & 31, cta = blockIdx.x;
  TRACE(0);
  pdl_launch();
  if (warp >= 8) {
    if (warp < 10 || cta < NSLOT) {
      uint32_t* q = reinterpret_cast<uint32_t*>(pool_at((warp < 10 ? NSLOT : cta) * 8192 + (warp & 1) * 4096)) + (warp < 10 ? (cta & 127) * 8 : 0);
      if (lane < 8) stg_strong32(q + lane, 0u);
      uint32_t best = ~0u;
      if (lane == 0) {
        for (int r = 0; r < FK_REP; r++) {
          uint32_t t0, t1, v;
          asm volatile("mov.u32 %0, %%clock;" : "=r"(t0) :: "memory");
          asm volatile("atom.relaxed.gpu.global.exch.b32 %0, [%1], 0;" : "=r"(v) : "l"(q) : "memory");
          asm volatile("{.reg .u32 t; add.u32 t, %1, 1; mov.u32 %0, %%clock; sub.u32 %0, %0, %1;}" : "=r"(t1) : "r"(__shfl_sync(1u, v, 0)) : "memory");
          best = min(best, t1 - t0);
        }
        lat[warp - 8] = best;
      }
    }
    __syncwarp();
    bar_sync(2, cta < 128 ? 384 : 128);
    if (threadIdx.x == 288) for (int i = 0; i < FK_PF; i++) prefetch_weights(wa, i);
    if (threadIdx.x == 256) {
      const int part = lat[0] < lat[1] ? 0 : 1;
      uint32_t smid; asm("mov.u32 %0, %%smid;" : "=r"(smid));
      g_smpart[smid & 255] = part;
      g_smclk[smid & 255] = clk32() - gtime() * 2;
      g_smuse[smid & 255] = 0;
      if (cta < NSLOT) g_orient[cta] = lat[2] < lat[3] ? part : 1 - part;
    }
  } else if (cta < 128) {
    float4 v[2][5];
#pragma unroll
    for (int r = 0; r < 2; r++)
#pragma unroll
      for (int i = 0; i < 5; i++) {
        const uint32_t* src = reinterpret_cast<const uint32_t*>(xin) + (cta * 16 + r * 8 + (lane >> 2)) * (DM / 2) + warp * 40 + i * 8 + (lane & 3);
        const uint32_t a = src[0], b = src[4];
        v[r][i] = make_float4(bf_lo(a), bf_hi(a), bf_lo(b), bf_hi(b));
      }
    uint4 w8[2];
#pragma unroll
    for (int i = 0; i < 2; i++) w8[i] = wb[cta * 400 + min(i * 256 + threadIdx.x, 399)];
    float mean[2], rs[2];
    ln_stats<2>(v, s2u(scratch), mean, rs);
    bar_sync(2, 384);
    ABT(2, 2);
    if (threadIdx.x < 128) g_stat[cta * 128 + threadIdx.x] = make_float2(0.f, 0.f);
#pragma unroll
    for (int i = 0; i < 10; i++) g_x[((cta * 2 + i / 5) * 40 + warp * 5 + i % 5) * 32 + lane] = pack4(v[i / 5][i % 5]);
    uint32_t w[2][5][2];
#pragma unroll
    for (int i = 0; i < 10; i++) {
      const float4 t = v[i / 5][i % 5];
      const float m = mean[i / 5], q = rs[i / 5];
      w[i / 5][i % 5][0] = pack2((t.x - m) * q, (t.y - m) * q); w[i / 5][i % 5][1] = pack2((t.z - m) * q, (t.w - m) * q);
    }
    ln_store(w, cta, warp * 5);
    ABT(2, 3);
#pragma unroll
    for (int i = 0; i < 2; i++) {
      const int e = cta * 400 + min(i * 256 + threadIdx.x, 399), k = e / 80, n = e - k * 80, cg = n / 10;
      g_wb[((cg * 80 + (k >> 3)) * 10 + n - cg * 10) * 8 + (k & 7)] = w8[i];
    }
  } else if (cta == 128) {
    g_bo[threadIdx.x] = 0;
  }
  TRACE(2);
}

struct ChainParams {
  CUtensorMap wq, wk, wv, wo;
  const __nv_bfloat16* mem0;
  uint8_t *pool, *kv;
  const uint32_t* xc;
  uint32_t* sync;
  int layer;
  int d0, d3, d1, d1b, d2, d2b, mode;
};
constexpr int CH_WQ = 0, CH_WO = 81920, CH_X = CH_WO + 86016, CH_M = CH_X + 20480, CH_KT = CH_X + 40960, CH_VT = CH_KT + 4096,
              CH_PS = CH_VT + 4096, CH_QK = CH_PS + 4096, CH_VP = CH_QK + 4096, CH_SX = CH_VP + 1024, CH_O = CH_SX + 2304, CH_ID = CH_O + 3072,
              CH_BAR = CH_ID + 512;
constexpr int CH_SMEM = CH_BAR + 256;
constexpr int CH_BASE = 1024;
#define CH_VK0 8
#define CH_VK1 20
#define CH_L0 4
#define CH_LR 4
#define NOX 0
#define CH_XA 1
#define CH_XB 4
#define CH_W1 3
#define CH_W2 17
#define CH_W3 26
#define CH_R2 8
#define CH_VA 16
#define CH_EX 1
#define CH_KD 0
#define CH_RP 1
#define CH_KF 10
#define CH_LO 0
#define CH_LR1 4
#define CH_KP 0
#define CH_KM 0
#define CH_WE 0
#define CH_SP 1
#define CH_KW 3
#define CH_RB 0
#define CH_RC 8
#define CH_D0 200
#define CH_D1 450
#define CH_D2 300
#define CH_R1 4
#define CH_TW 12
__device__ __forceinline__ uint32_t opaque(uint32_t x) { return __shfl_sync(~0u, x, threadIdx.x & 31); }
__device__ __forceinline__ uint32_t nz(uint32_t x) { uint32_t r; asm("max.u32 %0, %1, 1;" : "=r"(r) : "r"(x)); return r; }
__device__ __forceinline__ uint32_t pack_tag(float lo, float hi, uint32_t tag, uint32_t mask) {
  uint32_t r;
  asm("lop3.b32 %0, %1, %2, %3, 0xD8;" : "=r"(r) : "r"(pack2(lo, hi)), "r"(tag), "r"(mask));
  return r;
}
__device__ __forceinline__ uint32_t differ(uint32_t a, uint32_t b, uint32_t t) { uint32_t r; asm("lop3.b32 %0, %1, %2, %3, 0x7E;" : "=r"(r) : "r"(a), "r"(b), "r"(t)); return r; }
__device__ __forceinline__ void mbar_wait_hot(uint32_t bar, uint32_t ph) {
  uint32_t ok;
  asm volatile("{.reg .pred p; mbarrier.try_wait.parity.shared::cta.b64 p, [%1], %2; selp.u32 %0, 1, 0, p;}" : "=r"(ok) : "r"(bar), "r"(ph) : "memory");
  if (__builtin_expect(!ok, 0)) mbar_wait(bar, ph);
}
__device__ __forceinline__ bool elect() {
  uint32_t r; asm volatile("{.reg .pred p; elect.sync _|p, 0xffffffff; selp.u32 %0, 1, 0, p;}" : "=r"(r)); return r; }
__device__ __forceinline__ uint32_t or3(uint32_t a, uint32_t b, uint32_t c) { uint32_t r; asm("lop3.b32 %0, %1, %2, %3, 0xFE;" : "=r"(r) : "r"(a), "r"(b), "r"(c)); return r; }
__device__ __forceinline__ void pin() { pdl_launch(); }
__device__ __forceinline__ void mma16h(float* d, uint32_t a0, uint32_t a2, uint32_t b0, uint32_t b1) {
  asm volatile("{.reg .b32 u, v; mma.sync.aligned.m16n8k16.row.col.f32.bf16.bf16.f32 {%0,%1,%2,%3},{%4,u,%5,v},{%6,%7},{%0,%1,%2,%3};}"
               : "+f"(d[0]), "+f"(d[1]), "+f"(d[2]), "+f"(d[3]) : "r"(a0), "r"(a2), "r"(b0), "r"(b1)); }
__device__ __forceinline__ void mma8h(float* d, uint32_t a0, uint32_t b0) {
  asm volatile("{.reg .b32 u; mma.sync.aligned.m16n8k8.row.col.f32.bf16.bf16.f32 {%0,%1,%2,%3},{%4,u},{%5},{%0,%1,%2,%3};}"
               : "+f"(d[0]), "+f"(d[1]), "+f"(d[2]), "+f"(d[3]) : "r"(a0), "r"(b0)); }
__device__ __forceinline__ uint32_t absmax2(uint32_t a, uint32_t b) { uint32_t r; asm("max.xorsign.abs.bf16x2 %0, %1, %2;" : "=r"(r) : "r"(a), "r"(b)); return r; }
__device__ __forceinline__ void until(uint32_t t) { while ((int)(clk32() - t) < 0) {} }
__device__ __forceinline__ uint4 pack8(const float* d) { return make_uint4(pack2(d[0], d[1]), pack2(d[2], d[3]), pack2(d[4], d[5]), pack2(d[6], d[7])); }
__device__ __forceinline__ void add8(float* d, uint4 v) {
  d[0] += bf_lo(v.x); d[1] += bf_hi(v.x); d[2] += bf_lo(v.y); d[3] += bf_hi(v.y);
  d[4] += bf_lo(v.z); d[5] += bf_hi(v.z); d[6] += bf_lo(v.w); d[7] += bf_hi(v.w);
}

template <int WG>
__device__ __forceinline__ void chain_body(const ChainParams& p, const uint32_t wq, const uint32_t (&ak)[80], const uint32_t (&av)[80]) {
  const int tid = threadIdx.x & 127, t4 = __shfl_sync(~0u, tid >> 5, 0), lane = tid & 31;
  const int cta = blockIdx.x, h = cta / 3, j = cta - 3 * h;
  const uint32_t sb = mapa(CH_BASE, j);
  const uint32_t bWo = sb + CH_BAR, bWq = bWo + 8, bX = bWo + 16, bXA = bWo + 24, bXB = bWo + 32, bO = bWo + 40, bG = bWo + 48, bH = bWo + 96;
  uint32_t tw[4 * CH_TW];
  auto refill = [&]() {
#pragma unroll
    for (int k = 0; k < CH_TW; k++) ldsm4t(&tw[4 * k], wq + k * 2048);
  };
  const uint32_t wo = opaque((sb + CH_WO + (WG == 0 ? (t4 + (j == 2)) * 4096 : (j == 2 ? 0 : 24576) + t4 * 1024) + ((lane & 7) + (lane >> 4) * 8) * 64 +
                              ((((lane >> 3) & 1) ^ ((lane >> 1) & 3)) << 4)) ^ (WG == 1 && j == 2 ? 32 : 0));
  const uint32_t wo2 = opaque((wo ^ ((t4 & 1) * 32)) + (4 + (t4 >> 1) - t4) * 4096);
  const uint32_t l16 = opaque(sb + lane * 16);
  const uint32_t l8 = opaque(sb + t4 * 256 + lane * 8);
  const uint32_t lw = opaque(sb + t4 * 1024 + lane * 16);
  const uint32_t qs = opaque(sb + CH_QK + WG * 2048 + t4 * 512 + lane * 16);
  const uint32_t qa = opaque(sb + CH_QK + (lane >> 4) * 2048 + (lane & 15) * 16 + (WG == 0 ? t4 * 512 + 256 : t4 == 3 ? 1024 : 0));
  const uint32_t ka = opaque(t4 < 2 ? sb + CH_KT + t4 * 512 + lane * 16
                                    : sb + CH_QK + 256 + (t4 - 2) * 1024 + ((lane >> 3) & 1) * 2048 + (lane >> 4) * 128 + (lane & 7) * 16);
  const uint32_t l4 = opaque(sb + t4 * 256 + lane * 4);
  uint32_t pdst[1], pages = 0;
  auto line0 = [&](int i) { return 28 * j + (i < 4 ? 4 * t4 + i : 12 + 2 * t4 + i); };
  const uint32_t plane = opaque((lane >> 4) * 2048 + h * 64 + (lane & 15) * 4);
  if (WG == 0) {
    pages = __ballot_sync(~0u, lds32(sb + CH_O + line0(min(lane, 5)) * 4) & 4096);
  } else {
    pages = __ballot_sync(~0u, lds32(sb + CH_O + (80 + min(lane, 11)) * 4) & 4096);
    pdst[0] = opaque(lds32(sb + CH_O + (j == 0 ? 24 + t4 : 50 + 2 * j + (t4 & 1)) * 4) + plane);
  }
  const uint32_t role = lds32(sb + CH_O + NSLOT * 4), rsrc = lds32(sb + CH_O + role * 4), rdst = (80 + role / 20) * 8192 + role % 20 * 128;
  const uint32_t r1 = mapa(CH_BASE, j == 2 ? 0 : j + 1) - sb, r2 = mapa(CH_BASE, j == 0 ? 2 : j - 1) - sb;
  uint32_t tag = opaque(1);
  auto pool = [&](uint32_t off) { return p.pool + ((tag & 0xfffe) + off); };
  auto after = [&](uint32_t x) { return x & tag & 0xfffe; };
  auto kv = [&](int s, uint32_t a) { return p.kv + (a + ((cta * 2 * NSEG + s) * KV_BYTES - sb)); };
  auto pass = [&](float (&d)[16], const uint32_t (&a)[80], auto k0, auto k1) {
    const uint64_t db = mkdesc(CH_BASE + CH_X + WG * 20480, 512, 128, 0);
#pragma unroll
    for (int k = k0.value; k < k1.value; k++) wg_rs32_00(d, a[4 * k], a[4 * k + 1], a[4 * k + 2], a[4 * k + 3], db + k * 64, k);
    wg_commit();
  };
  auto dump = [&](float (&d)[16], uint32_t a) {
    reg_fence<16>(d);
    sts128(a, pack8(d)); sts128(a + 512, pack8(d + 8));
  };
  uint32_t pph = 0;
  auto tokens0 = [&](int s, auto k0) {
    float dk[16], dv[16];
    bar_sync(9, 256);
    wg_fence();
    pass(dk, ak, Int<0>(), Int<4>());
    const uint4 a0 = lds128(lw + CH_KT), a1 = lds128(lw + CH_KT + 512);
    pin();
    pass(dk, ak, Int<4>(), Int<20>());
    pass(dv, av, Int<0>(), Int<CH_VA>());
    pin();
    wg_wait<1>();
    reg_fence<16>(dk);
    add8(dk, a0); add8(dk + 8, a1);
    const uint4 w0 = pack8(dk), w1 = pack8(dk + 8);
    const uint4 b0 = lds128(lw + CH_VT), b1 = lds128(lw + CH_VT + 512);
    stsm4t(lw + CH_KT, w0.x, w0.z, w0.y, w0.w); stsm4t(lw + CH_KT + 512, w1.x, w1.z, w1.y, w1.w);
    if (CH_KP == 2) bar_arrive(7, 160);
    TM1(6);
    pin();
    if (CH_VA < 20) pass(dv, av, Int<CH_VA>(), Int<20>());
    pin();
#pragma unroll
    for (int k = k0.value; k < CH_TW; k++) ldsm4t(&tw[4 * k], wq + k * 2048);
    TM1(9);
    if (k0.value < CH_TW && t4 >= 2) { mbar_wait_hot(bH + t4 * 16 - 24 + (pph & 1) * 8, pph >> 1 & 1); pph++; }
    __syncwarp();
    wg_wait<0>();
    reg_fence<16>(dv);
    add8(dv, b0); add8(dv + 8, b1);
#pragma unroll
    for (int e = 0; e < 2; e++) { const uint4 v = pack8(dv + 8 * e); sts128(lw + CH_VT + e * 512, make_uint4(v.x, v.z, v.y, v.w)); }
  };
  auto publish_k = [&](int s) {
    if (t4 == CH_KW && elect()) { fence_async(); bulk_store(p.kv + (size_t)(cta * 2 * NSEG + s) * KV_BYTES, sb + CH_KT, 4096); bulk_commit(); }
    __syncwarp();
  };
  if (WG == 0) {
    mbar_wait(bXB, 0);
    tokens0(0, Int<CH_TW>());
  } else {
    const uint32_t* m0 = reinterpret_cast<const uint32_t*>(p.mem0) + (lane >> 2) * 320 + t4 * 80 + (lane & 3);
    uint32_t a[20];
#pragma unroll
    for (int i = 0; i < 20; i++) a[i] = m0[4 * i];
    pin();
    float dk[16], dv[16];
    mbar_wait(bXA, 0);
    wg_fence();
    pass(dk, ak, Int<0>(), Int<20>());
    pass(dv, av, Int<0>(), Int<20>());
    wg_wait<0>();
    dump(dk, lw + CH_KT);
    dump(dv, lw + CH_VT);
    bar_sync(9, 256);
    if (CH_KP == 2 && t4 == CH_KW) { bar_sync(7, 160); publish_k(0); }
#pragma unroll
    for (int i = 0; i < 20; i++) sts32(sb + CH_M + (t4 * 20 + i) * 128 + lane * 4, nz(transpose8(a[i])));
    __syncwarp();
    if (elect()) mbar_arrive(bG + t4 * 8);
  }
  PRO(8);
  mbar_wait(bWq, 0);
  refill();
  PRO(9);
  mbar_wait(bWo, 0);
  asm volatile("barrier.cluster.wait.aligned;" ::: "memory");
  PRO(10);
  auto load_x = [&](int s, int k0, int n, uint32_t bar) {
    if (!NOX && elect()) { mbar_expect(bar, n * 1024); bulk_load(sb + CH_X + k0 * 1024, p.xc + (s + 1) * 10240 + k0 * 256, n * 1024, bar); }
  };
  constexpr int VK = WG == 0 ? CH_VK0 : CH_VK1;
  uint32_t gph = 0;
  int st = 0;
  const uint32_t ca = opaque(sb + CH_M + t4 * 2560 + lane * 32 + (lane >> 2) * 4);
  auto project = [&](int s, uint32_t (&b)[40], float (&dv)[16], uint32_t (&kf)[16]) {
    float dq[4] = {}, dk[4] = {};
    uint32_t w[80];
#pragma unroll
    for (int i = 0; i < 4 * CH_TW; i++) w[i] = tw[i];
    constexpr int LR = WG == 1 ? CH_LR1 : CH_LR;
    auto load = [&](int n) {
      int c = 0;
#pragma unroll
      for (int i = 0; i < 10; i++) {
        if (i == CH_KF) {
#pragma unroll
          for (int q = 0; q < 4; q++)
            if (WG == 1 && c++ == n) ldsm4(&kf[4 * q], ka + q * 1024);
        }
        if (c++ == n) ldsm4t(&b[4 * i], l16 + CH_M + WG * 5120 + i * 512);
#pragma unroll
        for (int k = 2 * i; k < 2 * i + 2; k++)
          if (k >= CH_TW && c++ == n) ldsm4t(&w[4 * k], wq + k * 2048);
      }
#pragma unroll
      for (int i = 0; i < 4; i++)
        if (WG == 1 && CH_KF >= 10 && c++ == n) ldsm4(&kf[4 * i], ka + i * 1024);
    };
    if (WG == 1) {
      for (int n = 0;;) {
        mbar_wait(bG + t4 * 8, gph);
        TR(5, (clk32() & ~3u) | min(n, 3));
        gph ^= 1;
        if (__builtin_expect(!__any_sync(~0u, __vimin3_u32(lds32(ca), lds32(ca + 1024), lds32(ca + 1536)) == 0), 1)) break;
        if (elect()) {
          const int q = (st == 0 ? 8 : st * 4 - 4) + t4;
          mbar_expect(bG + t4 * 8, 2560);
          bulk_load(sb + CH_M + t4 * 2560, p.pool + ((80 + q) * 8192 + (pages >> q & 1) * 4096), 2560, bG + t4 * 8);
        }
        spin_guard(n);
      }
    }
    bar_sync(6, 256);
#pragma unroll
    for (int i = 0; i < CH_L0; i++) load(i);
    if (WG == 0 && CH_XB == 4 && s + 1 < NSEG) load_x(s, 5 * t4, 5, bXB);
    TM(0);
    TM1(11);
    if (WG == 1) TR(6, clk32());
#pragma unroll
    for (int k = 0; k < 20; k += 2) {
      if (k > 0) {
#pragma unroll
        for (int n = (k == 18 ? 40 : CH_L0 + k * LR / 4) - 1; n >= CH_L0 + (k - 2) * LR / 4; n--) { load(n); if (CH_LO) __syncwarp(); }
      }
      pin();
#pragma unroll
      for (int kk = k; kk < k + 2; kk++) {
        mma16(dk, ak[4 * kk], ak[4 * kk + 1], ak[4 * kk + 2], ak[4 * kk + 3], b[2 * kk], b[2 * kk + 1]);
        mma16(dq, w[4 * kk], w[4 * kk + 1], w[4 * kk + 2], w[4 * kk + 3], b[2 * kk], b[2 * kk + 1]);
        if (kk < VK) mma16(dv, av[4 * kk], av[4 * kk + 1], av[4 * kk + 2], av[4 * kk + 3], b[2 * kk], b[2 * kk + 1]);
      }
    }
    const float k2 = 0.07216878364870322f * 1.44269504089f;
    stsm4t(qs, pack2(dq[0] * k2, dq[1] * k2), pack2(dq[2] * k2, dq[3] * k2), pack2(dk[0], dk[1]), pack2(dk[2], dk[3]));
    TM(1);
  };
  static_assert(CH_VK1 == 20 && CH_KP == 0 && CH_XA > 0 && CH_XB > 0, "last step");
  constexpr int VC = VK == 20 ? 1 : WG == 0 ? 2 : 3;
  auto finish_v = [&](const uint32_t (&b)[40], float (&dv)[16]) {
#pragma unroll
    for (int kk = VK; kk < 20; kk++) mma16(dv + 4 * ((kk - VK) % VC), av[4 * kk], av[4 * kk + 1], av[4 * kk + 2], av[4 * kk + 3], b[2 * kk], b[2 * kk + 1]);
  };
  auto sum_v = [&](float (&dv)[16]) {
#pragma unroll
    for (int i = 4; i < 4 * VC; i++) dv[i & 3] += dv[i];
  };
  auto publish_km = [&](int s) {
    uint32_t a[4];
    ldsm4(a, qa);
    *reinterpret_cast<uint2*>(kv(s, l8) + KV_M) = make_uint2(hadd2(a[0], a[2]), hadd2(a[1], a[3]));
  };
  auto memory_v = [&](uint2 x, const float (&dv)[16]) {
    return make_uint2(pack2(dv[0] + bf_lo(x.x), dv[1] + bf_hi(x.x)), pack2(dv[2] + bf_lo(x.y), dv[3] + bf_hi(x.y)));
  };
  auto publish_v = [&](int s, const uint4 (&v)[2], uint2 vm) {
#pragma unroll
    for (int e = 0; e < 2; e++) reinterpret_cast<uint4*>(kv(s, lw) + KV_V)[e * 32] = v[e];
    *reinterpret_cast<uint2*>(kv(s, l8) + KV_V + KV_M) = vm;
  };
#pragma unroll 1
  for (int s = 0;; s++) {
    float dv[16] = {};
    uint32_t b[40], kf[16];
    project(s, b, dv, kf);
    if (WG == 0) {
      bar_sync(1, 256);
      if (CH_XA == 0) load_x(s, 20 + 5 * t4, 5, bXA);
      if (CH_XB == 0) load_x(s, 5 * t4, 5, bXB);
      pin();
      finish_v(b, dv);
      sum_v(dv);
      sts64(l8 + CH_VP, pack2(dv[0], dv[1]), pack2(dv[2], dv[3]));
      if (s == NSEG - 1) {
        bar_arrive(10, 256);
        publish_k(s);
        publish_km(s);
        bulk_wait<0>();
        fence_async_global();
        bar_sync(2, 256);
        if (tid == 0) red_release(p.sync + 15 * 8 + 4, 1);
        break;
      }
      __syncwarp();
      if (elect()) mbar_arrive(bX);
      if (CH_XA == 1) load_x(s, 20 + 5 * t4, 5, bXA);
      if (CH_XB == 1) load_x(s, 5 * t4, 5, bXB);
      uint32_t w[144];
      auto wload = [&](int i) { ldsm4t(&w[4 * i], (i % 3 == 0 ? wo : i % 3 == 1 ? wo ^ 32 : wo2) + i / 12 * 28672 + i / 3 % 4 * 1024); };
      TM(3);
      if (CH_KP == 0) publish_k(s);
#pragma unroll
      for (int i = 0; i < CH_W1; i++) wload(i);
      bar_sync(10, 256);
      uint32_t km[4];
      ldsm4(km, qa);
      pin();
#pragma unroll
      for (int i = CH_W1; i < CH_W2; i++) wload(i);
      pin();
      const uint2 kms = make_uint2(hadd2(km[0], km[2]), hadd2(km[1], km[3]));
      if (CH_KM == 0) *reinterpret_cast<uint2*>(kv(s, l8) + KV_M) = kms;
      if (CH_KP == 0) bulk_wait_read<0>();
      if (CH_XA == 2) load_x(s, 20 + 5 * t4, 5, bXA);
      if (CH_XB == 2) load_x(s, 5 * t4, 5, bXB);
      bar_sync(2, 256);
      {
        float y[3][4] = {};
        uint32_t ob[24];
        ldsm4(&ob[0], l16 + CH_O + 1024); ldsm4(&ob[4], l16 + CH_O + 1536);
        TM(7);
        auto step = [&](int i) {
          const int k = i / 3;
          mma16(y[i % 3], w[4 * i], w[4 * i + 1], w[4 * i + 2], w[4 * i + 3], ob[2 * k], ob[2 * k + 1]);
        };
#pragma unroll
        for (int i = 0; i < 12; i++) {
          step(i);
          if (i >= 12 - (CH_W3 - CH_W2)) wload(CH_W3 - 12 + i);
          if (i % 3 == 2) pin();
        }
        if (CH_XB == 3) load_x(s, 5 * t4, 5, bXB);
        if (CH_KM == 1) *reinterpret_cast<uint2*>(kv(s, l8) + KV_M) = kms;
        pin();
        mbar_wait(bO, s & 1);
        TM(4);
        ldsm4(&ob[8], l16 + CH_O); ldsm4(&ob[12], l16 + CH_O + 512);
        pin();
        float2 inv;
        uint8_t* dst[6];
        uint32_t mask;
#pragma unroll
        for (int i = 12; i < 36; i++) {
          step(i);
          const int n = CH_W3 + i - 13, m = n - (n > 30);
          if (i == 12) ldsm4(&ob[16], l16 + after(w[4 * CH_W3 - 1] | w[4 * CH_W3 - 5] | w[4 * CH_W3 - 9] | ob[8]) + CH_O + 2048);
          else if (n == 30) ldsm4(&ob[20], l16 + CH_O + 2560);
          else if (m < 36) wload(m);
          else if (m == 36) inv = lds64f((l8 & ~0xe0u) + CH_VP);
          if (i == 26) mask = ((l16 ^ tag) & 48) == 0;
          if (i >= 27 && i < 33) dst[i - 27] = pool(line0(i - 27) * 8192 + (pages >> (i - 27) & 1) * 4096) + plane;
          if (i % 3 == 2) pin();
        }
#pragma unroll
        for (int k = 0; k < CH_R1; k++) ldsm4t(&tw[4 * k], wq + k * 2048);
        pin();
#pragma unroll
        for (int i = 0; i < 6; i++) stg_strong32(dst[i], pack_tag(y[i >> 1][2 * (i & 1)] * inv.x, y[i >> 1][2 * (i & 1) + 1] * inv.y, tag, mask));
        TM(8);
        TR(0, clk32());
        bar_arrive(5, 256);
        pin();
      }
      const uint32_t t0 = clk32();
      auto refill2 = [&]() {
#pragma unroll
        for (int k = CH_R1; k < CH_R2; k++) ldsm4t(&tw[4 * k], wq + k * 2048);
      };
      if (CH_RP == 0) refill2();
      const uint32_t ln = (l16 ^ tag) >> 4 & 31;
      if (t4 >= 2) {
        const uint32_t bP = bH + t4 * 16 - 24, ps = CH_PS + (t4 & 1) * 4096;
        auto fetch = [&](uint32_t k) {
          if (elect()) { mbar_expect(bP + (k & 1) * 8, 2048); bulk_load(sb + ps + (k & 1) * 2048, p.pool + (rsrc + (t4 & 1) * 2048), 2048, bP + (k & 1) * 8); }
        };
        until(t0 + CH_D0);
        fetch(pph);
        if (CH_RP == 2) refill2();
        if (!NOX) mbar_wait_hot(bXB, (s + 1) & 1);
        const uint32_t want = (tag & 1) * 0x10001, chk = opaque(ln < 4 ? 0x10001 : 0);
        uint4 sel;
        sel.x = opaque((ln >> 3) != (ln & 1) ? 0 : ln & 4 ? 0x3f800000u : 0x00003f80u);
        sel.z = opaque(sel.x); sel.y = opaque(ln); sel.w = opaque(ln + 1);
        uint8_t* mdst = p.pool + opaque(st * 32768 + rdst + (t4 & 1) * 64 + ln * 4);
        until(t0 + CH_D1);
        fetch(pph + 1);
        TM(5);
        if (CH_RP == 1) refill2();
        int n = 0;
        uint32_t u[16];
        float y[4][4];
        auto sum = [&]() {
#pragma unroll
          for (int i = 0; i < 16; i++) y[i >> 2][i & 3] = 0.f;
#pragma unroll
          for (int i = 0; i < 8; i++) mma16(y[i & 3], sel.x, sel.y, sel.z, sel.w, u[2 * i], u[2 * i + 1]);
        };
        auto check = [&](auto spec) {
          mbar_wait(bP + (pph & 1) * 8, pph >> 1 & 1);
          TM(14);
          TR(2, clk32());
#pragma unroll
          for (int i = 0; i < 4; i++) ldsm4t(&u[4 * i], l16 + (ps + (pph & 1) * 2048) + i * 512);
          pph++;
          if (spec.value) { pin(); sum(); }
          uint32_t bad = 0;
#pragma unroll
          for (int i = 0; i < 4; i++) bad = or3(bad, differ(u[4 * i], u[4 * i + 1], want), differ(u[4 * i + 2], u[4 * i + 3], want));
          return __any_sync(~0u, bad & chk);
        };
        if (CH_SP) {
          if (check(Int<0>())) {
            do { fetch(pph + 1); spin_guard(n); } while (check(Int<1>()));
          } else {
            sum();
          }
        } else {
          while (check(Int<0>())) { fetch(pph + 1); spin_guard(n); }
          sum();
        }
        TR(1, t0 + (n ? CH_D1 : CH_D0));
        TM(15);
        const uint32_t w = nz(pack2((y[0][0] + y[1][0]) + (y[2][0] + y[3][0]), (y[0][1] + y[1][1]) + (y[2][1] + y[3][1])));
        if (ln < 16) { stg_strong32(mdst, w); stg_strong32(mdst + 4096, w); }
        TMV(12, 32, n);
        TR(3, (clk32() & ~3u) | min(n, 3));
      } else {
        if (CH_RP) refill2();
        if (!NOX) mbar_wait_hot(bXB, (s + 1) & 1);
        stg_strong32(p.pool + ((st == 2 ? 0 : st + 1) * 32768 + rdst + t4 * 4096) + ln * 4, 0u);
        if (t4 == 0 && cta < 40 && s + 4 < NSEG && elect())
          asm volatile("cp.async.bulk.prefetch.L2.global [%0], 1024;" :: "l"(p.xc + (s + 4) * 10240 + cta * 256) : "memory");
        if (t4 == 1 && (s & 3) == 0 && s > 0 && elect()) red_relaxed(p.sync + 2 * s - 4, 1);
        if (t4 == 1 && s == NSEG - 3 && cta == 95 && elect()) red_relaxed(p.sync + 2 * s + 2, 0x10000);
      }
      TM(10);
      bar_arrive(8, 256);
      tokens0(s + 1, Int<CH_R2>());
      TM(2);
      TR(7, clk32());
    } else {
      if (s == NSEG - 1) {
        bar_arrive(1, 256);
        const uint4 v[2] = {lds128(lw + CH_VT), lds128(lw + CH_VT + 512)};
        bar_sync(10, 256);
        publish_v(s, v, memory_v(lds64(l8 + CH_VP), dv));
        bar_arrive(2, 256);
        break;
      }
      const uint32_t xo = l4 + (CH_SX - (t4 == 3 ? 128 : 0)), x1 = xo + (r1 + 768 + min(t4, 2) * 256), x2 = xo + (r2 + 1024 + min(t4, 2) * 256);
      if (t4 < 2) {
        float ds[4][4] = {};
        uint32_t q[16];
        asm volatile("bar.sync 1, 256;" ::: "memory");
#pragma unroll
        for (int k = 0; k < 4; k++) ldsm4(&q[4 * k], qa + k * 512);
        pin();
        if (VK < 20) { finish_v(b, dv); pin(); }
#pragma unroll
        for (int k = 0; k < 4; k++) {
          mma16(ds[k & 1], kf[4 * k], kf[4 * k + 1], kf[4 * k + 2], kf[4 * k + 3], q[4 * k], q[4 * k + 1]);
          mma16(ds[2 + (k & 1)], kf[4 * k], kf[4 * k + 1], kf[4 * k + 2], kf[4 * k + 3], q[4 * k + 2], q[4 * k + 3]);
        }
        float t[4];
#pragma unroll
        for (int i = 0; i < 4; i++) t[i] = (ds[0][i] + ds[2][i]) + (ds[1][i] + ds[3][i]);
        const uint32_t w0 = pack2(t[0], t[1]), w1 = pack2(t[2], t[3]);
        st_async32(x1, w0, bX + r1); st_async32(x2, w0, bX + r2);
        st_async32(x1 + 128, w1, bX + r1); st_async32(x2 + 128, w1, bX + r2);
        sts32(xo, w0); sts32(xo + 128, w1);
      } else {
        float ds[4][4] = {};
        uint32_t q0[4], q1[4], a0[4], a1[4];
        asm volatile("bar.sync 1, 256; " ::: "memory");
        ldsm4(a0, ka); ldsm4(q0, qa); ldsm4(a1, ka + 512); ldsm4(q1, qa + 512);
        pin();
        if (VK < 20) { finish_v(b, dv); pin(); }
        mma16(ds[0], a0[0], a0[1], a0[2], a0[3], q0[0], q0[1]);
        mma16(ds[1], a0[0], a0[1], a0[2], a0[3], q0[2], q0[3]);
        mma16(ds[2], a1[0], a1[1], a1[2], a1[3], q1[0], q1[1]);
        mma16(ds[3], a1[0], a1[1], a1[2], a1[3], q1[2], q1[3]);
        float t[2];
#pragma unroll
        for (int i = 0; i < 2; i++)
          t[i] = ((ds[0][i] + ds[0][i + 2]) + (ds[1][i] + ds[1][i + 2])) + ((ds[2][i] + ds[2][i + 2]) + (ds[3][i] + ds[3][i + 2]));
        const uint32_t w0 = pack2(t[0], t[1]);
        st_async32(x1, w0, bX + r1);
        st_async32(x2, w0, bX + r2);
        sts32(xo, w0);
      }
      TM(3);
      const uint4 id = lds128(l16 + CH_ID);
      float sc[3][4] = {};
      uint4 v[2];
      sum_v(dv);
      bar_sync(3, 128);
      uint32_t r[12], wd[12], we[12] = {};
      ldsm4(&r[0], l16 + CH_SX); ldsm2(&r[4], l16 + CH_SX + 512);
      pin();
      v[0] = lds128(lw + CH_VT); v[1] = lds128(lw + CH_VT + 512);
#pragma unroll
      for (int u = 0; u < 3; u++) ldsm4t(&wd[4 * u], wo + u * 28672);
      if (CH_WE && j == 0) {
#pragma unroll
        for (int u = 0; u < 3; u++) ldsm4t(&we[4 * u], (wo ^ 32) + u * 28672);
      }
      pin();
#pragma unroll
      for (int q = 0; q < 3; q++) mma16(sc[q], id.x, id.y, id.z, id.w, r[2 * q], r[2 * q + 1]);
      uint32_t big = absmax2(absmax2(absmax2(r[0], r[1]), absmax2(r[2], r[3])), absmax2(r[4], r[5]));
      const uint32_t oa1 = l4 + (r1 + CH_O), oa2 = l4 + (r2 + CH_O + 2048), ones = 0x3f803f80u;
      mbar_wait_hot(bX, s & 1);
      TM(4);
      ldsm4(&r[0], l16 + CH_SX + 768); ldsm4(&r[8], l16 + CH_SX + 1792); ldsm4(&r[4], l16 + CH_SX + 1280);
      const uint2 vp = lds64(l8 + CH_VP);
      bar_arrive(10, 256);
      pin();
      {
        float sd[3][4] = {};
#pragma unroll
        for (int i = 0; i < 3; i++) {
          const int q = i == 0 ? 0 : 3 - i;
          mma16(sc[q], id.x, id.y, id.z, id.w, r[4 * q], r[4 * q + 1]);
          mma16(sd[q], id.x, id.y, id.z, id.w, r[4 * q + 2], r[4 * q + 3]);
          big = absmax2(big, absmax2(absmax2(r[4 * q], r[4 * q + 1]), absmax2(r[4 * q + 2], r[4 * q + 3])));
        }
#pragma unroll
        for (int i = 0; i < 12; i++) sc[i >> 2][i & 3] += sd[i >> 2][i & 3];
      }
      const bool redo = __any_sync(~0u, (absmax2(big, big << 16) & 0x7fff0000u) >= 0x41800000u);
      const uint2 vm = memory_v(vp, dv);
      sc[2][0] += sc[2][2]; sc[2][1] += sc[2][3];
      float l[4], o[2][4];
      uint32_t p3, p4;
      auto attend = [&]() {
#pragma unroll
        for (int i = 0; i < 4; i++) l[i] = o[0][i] = o[1][i] = 0.f;
        const uint32_t p1 = pack2(ex2(sc[0][0]), ex2(sc[0][1])), p2 = pack2(ex2(sc[0][2]), ex2(sc[0][3]));
        mma16h(o[0], p1, p2, v[0].x, v[0].y);
        mma16h(o[1], p1, p2, v[0].z, v[0].w);
        mma16h(l, p1, p2, ones, ones);
        const uint32_t p0 = pack2(ex2(sc[2][0]), ex2(sc[2][1]));
        mma8h(o[0], p0, vm.x);
        mma8h(o[1], p0, vm.y);
        mma8h(l, p0, ones);
        p3 = pack2(ex2(sc[1][0]), ex2(sc[1][1])); p4 = pack2(ex2(sc[1][2]), ex2(sc[1][3]));
        mma16h(o[0], p3, p4, v[1].x, v[1].y);
        mma16h(o[1], p3, p4, v[1].z, v[1].w);
      };
      attend();
      if (__builtin_expect(redo, 0)) {
        float mx = fmaxf(sc[2][0], sc[2][1]);
#pragma unroll
        for (int i = 0; i < 4; i++) mx = fmaxf(mx, fmaxf(sc[0][i], sc[1][i]));
        mx = fmaxf(mx, __shfl_xor_sync(~0u, mx, 1));
        mx = fmaxf(mx, __shfl_xor_sync(~0u, mx, 2));
#pragma unroll
        for (int i = 0; i < 4; i++) { sc[0][i] -= mx; sc[1][i] -= mx; }
        sc[2][0] -= mx; sc[2][1] -= mx;
        attend();
      }
      const uint32_t o0 = pack2(o[0][0], o[0][1]), o1 = pack2(o[1][0], o[1][1]);
      st_async32(oa1, o0, bO + r1); st_async32(oa2, o0, bO + r2);
      st_async32(oa1 + 128, o1, bO + r1); st_async32(oa2 + 128, o1, bO + r2);
      sts32(l4 + CH_O + 1024, o0); sts32(l4 + CH_O + 1152, o1);
      bar_arrive(2, 256);
      pin();
      TM(6);
      mma16h(l, p3, p4, ones, ones);
      float inv;
      asm("rcp.approx.ftz.f32 %0, %1;" : "=f"(inv) : "f"(l[0]));
      sts32((l8 & ~0xffu) + (lane & 28) + CH_VP, __float_as_uint(inv));
      __syncwarp();
      if (elect()) mbar_arrive(bO);
      {
        float z[2][4] = {}, y[2][4] = {};
        mma16(z[0], wd[0], wd[1], wd[2], wd[3], o0, o1);
        if (j == 0) {
#pragma unroll
          for (int u = 0; u < 3; u++) if (!CH_WE) ldsm4t(&we[4 * u], (wo ^ 32) + u * 28672);
          mma16(y[0], we[0], we[1], we[2], we[3], o0, o1);
        }
        const float2 iv = lds64f((l8 & ~0xe0u) + CH_VP);
        uint8_t* dst = pool(pdst[0]);
        const uint32_t mask = ((l16 ^ tag) & 48) == 0;
        const uint32_t oa = qa + ((tag & 0xfffe) + CH_O - CH_QK + t4 * 256 - (t4 == 3 ? 1024 : 0));
        const uint32_t za = l16 + ((tag & 0xfffe) + (t4 >> 1) * 512 + (t4 & 1) * 8);
        pin();
        mbar_wait(bO, s & 1);
        uint32_t a[4];
        ldsm4(a, oa);
        mma16(z[0], wd[4], wd[5], wd[6], wd[7], a[0], a[1]);
        mma16(z[1], wd[8], wd[9], wd[10], wd[11], a[2], a[3]);
        if (j == 0) {
          mma16(y[0], we[4], we[5], we[6], we[7], a[0], a[1]);
          mma16(y[1], we[8], we[9], we[10], we[11], a[2], a[3]);
          sts128f(lw + CH_VT + 512, y[0][0] + y[1][0], y[0][1] + y[1][1], y[0][2] + y[1][2], y[0][3] + y[1][3]);
        }
        sts128f(lw + CH_VT, z[0][0] + z[1][0], z[0][1] + z[1][1], z[0][2] + z[1][2], z[0][3] + z[1][3]);
        bar_sync(3, 128);
        if (j == 0 || t4 < 2) {
          float2 q[4];
#pragma unroll
          for (int i = 0; i < 4; i++) q[i] = lds64f(za + CH_VT + i * 1024);
          stg_strong32(dst, pack_tag(((q[0].x + q[1].x) + (q[2].x + q[3].x)) * iv.x, ((q[0].y + q[1].y) + (q[2].y + q[3].y)) * iv.y, tag, mask));
        }
      }
      TM(2);
      if (!NOX) mbar_wait_hot(bXA, (s + 1) & 1);
      if (CH_KP == 2) bulk_wait_read<0>();
      float dk[16], dw[16];
      bar_sync(5, 256);
      wg_fence();
      pass(dk, ak, Int<0>(), Int<20>());
      pass(dw, av, Int<0>(), Int<20>());
      TM(5);
      pin();
      if (CH_EX == 0) publish_v(s, v, vm);
      if (elect()) {
        mbar_expect(bG + t4 * 8, 2560);
        if (t4 == 1 && s + 2 < NSEG) { mbar_expect(bX, 1536); mbar_expect(bO, 2048); }
      }
      if (CH_KD == 0) { wg_wait<1>(); dump(dk, lw + CH_KT); }
      wg_wait<0>();
      if (CH_KD == 1) dump(dk, lw + CH_KT);
      TM(7);
      dump(dw, lw + CH_VT);
      bar_arrive(9, 256);
      pin();
#pragma unroll
      for (int k = 0; k < CH_RB; k++) ldsm4t(&tw[4 * k], wq + k * 2048);
      if (t4 < 2) {
        if (CH_EX == 2) { publish_v(s, v, vm); pin(); }
#pragma unroll
        for (int k = CH_RB; k < CH_RC; k++) ldsm4t(&tw[4 * k], wq + k * 2048);
        const int q = t4 ? 3 : j, o = t4 ? j * 896 : 0;
        const uint8_t* src = p.pool + ((80 + st * 4 + q) * 8192 + (pages >> (st * 4 + q) & 1) * 4096 + o);
        asm volatile("bar.sync 8, 256;" ::: "memory");
        const uint32_t t1 = clk32() + CH_D2;
        if (CH_EX == 1) publish_v(s, v, vm);
        auto fetch = [&](auto n) {
          mbar_wait(bH, s & 1);
          until(t1);
          TR(4, clk32());
          if (elect())
            asm volatile("cp.async.bulk.shared::cluster.global.mbarrier::complete_tx::bytes.multicast::cluster [%0], [%1], %2, [%3], 7;"
                         :: "r"(sb + CH_M + q * 2560 + o), "l"(src), "n"(n.value), "r"(bG + q * 8) : "memory");
        };
        if (!t4) fetch(Int<2560>()); else if (j == 2) fetch(Int<768>()); else fetch(Int<896>());
      } else {
        asm volatile("bar.sync 8, 256; " ::: "memory");
        if (elect()) asm volatile("mbarrier.arrive.relaxed.cluster.shared::cluster.b64 _, [%0];" :: "r"(bH + (t4 == 2 ? r1 : r2)) : "memory");
        pin();
        if (CH_EX) publish_v(s, v, vm);
#pragma unroll
        for (int k = CH_RB; k < CH_RC; k++) ldsm4t(&tw[4 * k], wq + k * 2048);
      }
      TM(9);
      pin();
#pragma unroll
      for (int k = CH_RC; k < CH_TW; k++) ldsm4t(&tw[4 * k], wq + k * 2048);
      if (CH_KP == 2 && t4 == CH_KW) { bar_sync(7, 160); publish_k(s + 1); }
      TM(10);
    }
    if (++st == 3) st = 0;
    tag ^= 0x10001;
  }
}

__global__ void __launch_bounds__(256, 1) chain_kernel(const __grid_constant__ ChainParams p) {
  extern __shared__ __align__(1024) uint8_t smem_raw[];
  const uint32_t sb = s2u(smem_raw);
  const int tid = threadIdx.x, warp = __shfl_sync(~0u, tid >> 5, 0), lane = tid & 31;
  const int cta = blockIdx.x, h = cta / 3, j = cta - 3 * h, colbase = cta * 64;
  const uint32_t bWo = sb + CH_BAR, bWq = bWo + 8, bXA = bWo + 24, bWk = bWo + 80, bWv = bWo + 88;
  uint32_t smid; asm("mov.u32 %0, %%smid;" : "=r"(smid));
  PRO(0);
  if (sb != mapa(CH_BASE, j)) __trap();
  uint32_t entry = 0;
  auto place = [&]() {
    const int i = tid - 128;
    if (i >= 0 && i <= NSLOT) {
      const uint32_t side = ldg_strong32(g_smpart + (smid & 255));
      if (i < NSLOT) {
        entry = i * 8192 + (ldg_strong32(g_orient + i) == (i < 80 ? i & 1 : side) ? 0 : 4096);
      } else {
        entry = 2 * (atomicAdd(g_bo + p.layer * 128 + 1, 1 << 8 * side) >> 8 * side & 255) + side;
      }
    }
    __syncwarp();
  };
  if (warp == 2 && lane < 4) asm volatile("prefetch.tensormap [%0];" :: "l"(&p.wq + lane) : "memory");
  if (p.layer) place();
  if (warp == 0 && elect()) {
#pragma unroll 1
    for (int i = 0; i < 17; i++) mbar_init(bWo + 8 * i, i == 2 || i == 5 ? 5 : i == 3 || i == 4 ? 4 : i == 12 ? 2 : 1);
    asm volatile("fence.mbarrier_init.release.cluster;" ::: "memory");
    mbar_expect(bWk, 81920);
    tma_load3<(WEF & 1) != 0>(sb + CH_WQ, &p.wk, colbase, 0, bWk);
    mbar_expect(bWv, 81920);
    tma_load3<(WEF & 1) != 0>(sb + CH_WO, &p.wv, colbase, 0, bWv);
    mbar_expect(bWo + 16, 1536);
    mbar_expect(bWo + 40, 2048);
    mbar_expect(bWo, 86016); mbar_expect(bWq, 81920);
#pragma unroll 1
    for (int i = 0; i < 8; i++) mbar_expect(bXA + 8 * (i & 1), 5120);
  }
  if (warp == 1) {
    const uint32_t id = (lane >> 3) == (lane & 3) ? ((lane & 4) ? 0x3f800000u : 0x00003f80u) : 0u;
    sts128(sb + CH_ID + lane * 16, make_uint4(id, 0, 0, id));
  }
  __syncthreads();
  asm volatile("barrier.cluster.arrive.relaxed.aligned;" ::: "memory");
  uint32_t ak[80], av[80];
  const uint32_t wq = opaque(sb + CH_WQ + ((warp >> 2) * 320 + (lane & 7) + (lane >> 4) * 8) * 128 + (((2 * (warp & 3) + ((lane >> 3) & 1)) ^ (lane & 7)) << 4));
  pdl_wait();
  if (tid == 32) stg_strong32(g_smuse + (smid & 255), p.layer + 1);
  pdl_launch();
  PRO(1);
  if (warp == 0 && elect()) {
    bulk_load(sb + CH_X + 20480, p.xc + 5120, 20480, bXA);
    bulk_load(sb + CH_X, p.xc, 20480, bXA + 8);
  }
  if (!p.layer) place();
  __syncwarp();
  PRO(2);
  mbar_wait(bWk, 0);
  PRO(3);
#pragma unroll
  for (int k = 0; k < 20; k++) ldsm4t(&ak[4 * k], wq + k * 2048);
  bar_sync(6, 256);
  if (warp == 0 && elect()) tma_load3<(WEF & 2) != 0>(sb + CH_WQ, &p.wq, colbase, 0, bWq);
  __syncwarp();
  PRO(4);
  mbar_wait(bWv, 0);
  PRO(5);
#pragma unroll
  for (int k = 0; k < 20; k++) ldsm4t(&av[4 * k], wq + CH_WO + k * 2048);
  bar_sync(6, 256);
  PRO(6);
  if (warp >= 5 && elect()) tma_load3<(WEF & 2) != 0>(sb + CH_WO + (warp - 5) * 28672, &p.wo, j == 0 ? 0 : 32 + j * 192, h * 192 + (j + 8 - warp) % 3 * 64, bWo);
  if (tid == 128 + NSLOT && entry >= 80) {
    uint32_t c;
    int n = 0;
    do { c = ldg_strong32(g_bo + p.layer * 128 + 1); spin_guard(n); } while ((c & 255) + (c >> 8) < 96);
    const uint32_t other = (c >> 8 * (~entry & 1) & 255) + (entry >> 1) - 40;
    entry = other < 40 ? 2 * other + (~entry & 1) : entry % 80;
  }
  if (tid >= 128 && tid <= 128 + NSLOT) sts32(sb + CH_O + (tid - 128) * 4, entry);
  PRO(7);
  __syncthreads();
  if (__shfl_sync(~0u, tid >> 7, 0) == 0) chain_body<0>(p, wq, ak, av); else chain_body<1>(p, wq, ak, av);
}

struct PostParams { CUtensorMap wq, wo, wb, wo2, wb2; int gap, share, layer, look, gap2, pol, slow_n, slow_gap; };
constexpr int PS = 8, PB = 28672;
constexpr int OP_SMEM = PS * PB + 512 + 2048;
enum { IT_ATT = 0, IT_OP = 1, IT_FIN = 2, IT_BQ = 3, IT_Q = 4 };

__device__ __forceinline__ uint32_t item_count(int type, int b) {
  return type == IT_ATT ? 32 : type == IT_OP ? op_split(b) * (b < OP_160 ? 2 : 4) : type == IT_FIN ? 16 : b < BQ_160 ? 6 : b < BQ_80 ? 12 : 24; }
__device__ __forceinline__ uint32_t item_need(int type, int b) { return type == IT_ATT ? 96 : item_count(type - 1, b); }

struct Ring {
  uint32_t sb, bars; int st; uint32_t ph;
  __device__ __forceinline__ uint32_t wait() const { mbar_wait(bars + 8 * st, ph); return sb + st * PB; }
  __device__ __forceinline__ void next() { if (++st == PS) { st = 0; ph ^= 1; } }
  __device__ __forceinline__ void release(int s) const { if ((threadIdx.x & 31) == 0) mbar_arrive(bars + 8 * (PS + s)); }
  __device__ __forceinline__ void pop() { __syncwarp(); release(st); next(); }
};

template <int N>
__device__ __forceinline__ void gemm_item(Ring& r, float* d, int nst, uint32_t go, int go_at, uint32_t wg) {
  auto desc = [](uint32_t lo, uint32_t hi) { uint64_t x; asm("mov.b64 %0, {%1, %2};" : "=l"(x) : "r"(lo), "r"(hi)); return x; };
  auto stage = [&](auto first) {
    const uint32_t base = (r.wait() & 0x3ffff) >> 4, a = base + wg * 256 + (8 << 16), w = base + 512 + (256 << 16);
    wg_fence();
#pragma unroll
    for (int kk = 0; kk < 2; kk++) {
      const uint64_t da = desc(a + kk * 16, 32), db = desc(w + kk * 128, 64 | 1 << 30);
      const int acc = kk || !first.value;
      if (N == 80) wg_ss80_01(d, da, db, acc);
      if (N == 160) wg_ss160_01(d, da, db, acc);
      if (N >= 192) wg_ss192_01(d, da, db, acc);
      if (N == 320) wg_ss128_01(d + 96, da, desc(w + kk * 128 + 768, 64 | 1 << 30), acc);
    }
    wg_commit();
  };
  stage(Int<1>());
  int prev = r.st;
  r.next();
#pragma unroll 1
  for (int kb = 1; kb < nst; kb++) {
    stage(Int<0>());
    if (kb == go_at && threadIdx.x == 0) mbar_arrive(go);
    wg_wait<1>();
    r.release(prev);
    prev = r.st;
    r.next();
  }
  wg_wait<0>();
  reg_fence<N / 2>(d);
  r.release(prev);
}

template <int HALF>
__device__ __forceinline__ void attn_a_warp(Ring& r, const uint32_t (&q)[48], int b, int h) {
  constexpr int NT = HALF ? 5 : 3, NF = 8 * NT;
  const int lane = threadIdx.x & 31, g = lane >> 2, c = lane & 3, seg = (threadIdx.x >> 5) & 3;
  uint32_t f[6][NF];
  int slot[6];
  auto fetch = [&](int u) {
    const uint32_t kv = r.wait() + seg * KV_BYTES;
    slot[u] = r.st;
    r.next();
#pragma unroll
    for (int w = 0; w < 4; w++) {
      uint32_t* d = &f[u][2 * NT * w];
#pragma unroll
      for (int t = 0; t <= HALF; t++) {
        if (u < 3) {
          ldsm4(d + 4 * t, kv + w * 1024 + t * 512 + (lane & 8) * 32 + (lane & 16) * 8 + (lane & 7) * 16);
        } else {
          const uint4 v = lds128(kv + w * 1024 + t * 512 + lane * 16);
          d[4 * t] = v.x; d[4 * t + 1] = v.y; d[4 * t + 2] = v.z; d[4 * t + 3] = v.w;
        }
      }
      const uint2 m = lds64(kv + KV_M + w * 256 + lane * 8);
      d[2 * NT - 2] = m.x; d[2 * NT - 1] = m.y;
    }
    pdl_launch();
  };
  float s[NT][4] = {};
  fetch(0);
#pragma unroll
  for (int u = 0; u < 3; u++) {
    fetch(u + 1);
#pragma unroll
    for (int kk = 0; kk < 4; kk++) {
      const uint32_t* a = &q[16 * u + 4 * kk];
#pragma unroll
      for (int n = 0; n < NT; n++) mma16(s[(n + 1) % NT], a[0], a[1], a[2], a[3], f[u][2 * NT * kk + 2 * n], f[u][2 * NT * kk + 2 * n + 1]);
    }
    r.release(slot[u]);
    pdl_launch();
  }
  fetch(4);
  const float k2 = 0.07216878364870322f * 1.44269504089f, NEG = -INFINITY;
  if (2 * c > g) { s[NT - 2][0] = NEG; s[NT - 1][2] = NEG; }
  if (2 * c + 1 > g) { s[NT - 2][1] = NEG; s[NT - 1][3] = NEG; }
  s[NT - 1][0] = s[NT - 1][1] = NEG;
  uint32_t pp[NT][2]; float inv[2];
#pragma unroll
  for (int hh = 0; hh < 2; hh++) {
    float m = NEG, l = 0.f;
#pragma unroll
    for (int n = 0; n < NT; n++) m = fmaxf(m, fmaxf(s[n][2 * hh], s[n][2 * hh + 1]));
    m = fmaxf(m, __shfl_xor_sync(~0u, m, 1)); m = fmaxf(m, __shfl_xor_sync(~0u, m, 2));
#pragma unroll
    for (int n = 0; n < NT; n++) { const float x = ex2((s[n][2 * hh] - m) * k2), y = ex2((s[n][2 * hh + 1] - m) * k2); l += x + y; pp[n][hh] = pack2(x, y); }
    l += __shfl_xor_sync(~0u, l, 1); l += __shfl_xor_sync(~0u, l, 2);
    asm("rcp.approx.ftz.f32 %0, %1;" : "=f"(inv[hh]) : "f"(l));
  }
  uint32_t* dst = g_o + ((b * 192 + h * 6) * 16 + seg * 4 + HALF * 2) * 128 + lane;
#pragma unroll
  for (int u = 3; u < 6; u++) {
    float o[8][4] = {};
#pragma unroll
    for (int n = 0; n < 8; n++) mma8(o[n], pp[0][0], pp[0][1], f[u][2 * NT * (n >> 1) + 2 * NT - 2 + (n & 1)]);
#pragma unroll
    for (int t = 0; t <= HALF; t++)
#pragma unroll
      for (int n = 0; n < 8; n++) {
        const uint32_t* v = &f[u][2 * NT * (n >> 1) + 4 * t + 2 * (n & 1)];
        mma16(o[n], pp[1 + 2 * t][0], pp[1 + 2 * t][1], pp[2 + 2 * t][0], pp[2 + 2 * t][1], v[0], v[1]);
      }
    r.release(slot[u]);
    if (u == 3) fetch(5);
#pragma unroll
    for (int n = 0; n < 8; n++) {
      dst[(u - 3) * 4096 + (n >> 2) * 2048 + (n & 3) * 32] = pack2(o[n][0] * inv[0], o[n][1] * inv[0]);
      dst[(u - 3) * 4096 + (n >> 2) * 2048 + (n & 3) * 32 + 128] = pack2(o[n][2] * inv[1], o[n][3] * inv[1]);
    }
  }
}

__device__ __forceinline__ void fin_item(Ring& r, uint32_t scratch, int b, int idx) {
  const int warp = threadIdx.x >> 5, lane = threadIdx.x & 31;
  float4 v[1][5];
  {
    const uint32_t base = r.wait();
#pragma unroll
    for (int i = 0; i < 5; i++) v[0][i] = unpack4(lds64(base + ((warp * 5 + i) * 32 + lane) * 8));
    r.pop();
  }
#pragma unroll 1
  for (int k = 0; k < op_split(b); k += 2) {
    const uint32_t base = r.wait();
#pragma unroll
    for (int i = 0; i < 10; i++) {
      const uint2 q = lds64(base + ((i / 5 * 40 + warp * 5 + i % 5) * 32 + lane) * 8);
      float4& t = v[0][i % 5];
      t.x += bf_lo(q.x); t.y += bf_hi(q.x); t.z += bf_lo(q.y); t.w += bf_hi(q.y);
    }
    r.pop();
  }
#pragma unroll
  for (int i = 0; i < 5; i++) g_x[((b * 16 + idx) * 40 + warp * 5 + i) * 32 + lane] = pack4(v[0][i]);
  float mean[1], rs[1];
  ln_stats<1>(v, scratch, mean, rs);
#pragma unroll
  for (int i = 0; i < 5; i++) {
    const int u = warp * 5 + i;
    uint32_t* xn = g_xn + ((b * 20 + (u >> 1)) * 16 + idx) * 128 + (u & 1) * 64 + lane;
    xn[0] = pack2((v[0][i].x - mean[0]) * rs[0], (v[0][i].y - mean[0]) * rs[0]);
    xn[32] = pack2((v[0][i].z - mean[0]) * rs[0], (v[0][i].w - mean[0]) * rs[0]);
  }
}

__global__ void __launch_bounds__(384, 1) post_kernel(const __grid_constant__ PostParams p) {
  extern __shared__ __align__(1024) uint8_t smem_raw[];
  const uint32_t sb = s2u(smem_raw), bars = sb + PS * PB;
  const uint32_t bIF = bars + 128, bIE = bars + 160, done = bars + 192, bGo = bars + 224, slots = bars + 240, scratch = bars + 512;
  const int warp = __shfl_sync(~0u, threadIdx.x >> 5, 0), lane = threadIdx.x & 31;
  if (warp == 9) PST(0);
  if (warp == 0 && blockIdx.x < 36) TRACE(0);
  if (warp >= 8) {
    asm volatile("setmaxnreg.dec.sync.aligned.u32 56;");
    if (warp == 10) {
      pdl_launch();
      if (sb & 1023) __trap();
      if (lane < 29) mbar_init(bars + 8 * lane, lane < 8 ? 1 : lane < 16 ? 8 : lane < 20 ? 1 : lane < 24 ? 2 : lane < 28 ? 8 : 1);
      if (lane == 0) sts32(slots + 16, p.gap);
      fence_async();
    }
    if (warp == 8 && lane < 5) asm volatile("prefetch.tensormap [%0];" :: "l"(&p.wq + lane) : "memory");
    if (warp != 9) bar_sync(2, 384);
    if (warp == 9) {
      PST(1);
      const int b = lane & 15;
      bool queries = QA_END < 16 && blockIdx.x < 36;
      for (int n = 0;; n++) {
        if (n > 0) { mbar_wait(bGo, (n - 1) & 1); mbar_wait(bIE + 8 * (n & 3), ((n >> 2) & 1) ^ 1); }
        int code = -1, spin = 0, ticket = 0;
        if (queries) {
          if (lane == 0) ticket = n == 0 ? blockIdx.x : 36 + atomicAdd(g_sync + SY_QC, 1);
          ticket = __shfl_sync(~0u, ticket, 0);
          queries = ticket < (16 - QA_END) * 32;
          if (queries) code = IT_Q << 16 | (QA_END + ticket % (16 - QA_END)) << 8 | ticket / (16 - QA_END);
        }
        if (!queries && lane == 0) asm volatile("atom.relaxed.gpu.global.add.u32 %0, [%1], 1;" : "=r"(ticket) : "l"(g_sync + SY_T) : "memory");
        while (!queries) {
          const uint4 hd = ldg_strong128(g_sync + b * 8), pr = ldg_strong128(g_sync + b * 8 + 4);
          if (n == 0 && spin == 0 && hd.x != 0x7fffffff) PST(2);
          const uint32_t hv[4] = {hd.x, hd.y, hd.z, hd.w}, pv[4] = {pr.x, pr.y, pr.z, pr.w};
          const uint32_t chain_done = __ballot_sync(~0u, (pr.x & 0xffff) >= 96) & 0xffff;
          int left[4], avail[4], rdy = 0, claimed = 0, upstream = 0;
#pragma unroll
          for (int t = 0; t < 4; t++) {
            const int cnt = lane < 16 ? item_count(t, b) : 0;
            left[t] = max(cnt - (int)hv[t], 0);
            claimed += cnt - left[t];
            const bool ready = (pv[t] & 0xffff) >= item_need(t, b);
            rdy |= ready << t;
            bool ok = ready || (t == IT_ATT ? pr.x >= 0x10000 : !upstream || (t == IT_OP && (chain_done >> 15 & 1)));
            if (t == IT_BQ && (chain_done >> BQ_HOLD & 1) && !(chain_done >> 15)) ok = false;
            avail[t] = ok ? left[t] : 0;
            upstream |= __any_sync(~0u, left[t] > 0);
          }
          if (!upstream) break;
          int rank = max(__shfl_sync(~0u, ticket, 0) - __reduce_add_sync(~0u, claimed), 0), type = -1, mine = 0;
          {
            const int a = b >= BQ_RUSH && (rdy >> IT_BQ & 1) ? avail[IT_BQ] : 0, tot = __reduce_add_sync(~0u, a);
            if (rank < tot) { type = IT_BQ; mine = a; } else rank -= tot;
            avail[IT_BQ] -= a;
          }
#pragma unroll
          for (int c = 0; c < 8; c++) {
            const int t = c == PR_FIN || c == 5 ? IT_FIN : c == PR_ATT || c == 7 ? IT_ATT : c == PR_OP || c == 4 ? IT_OP : IT_BQ;
            int a = c == PR_ATT || ((rdy >> t & 1) == (c < 4)) ? avail[t] : 0;
            if (t == IT_OP && OP_EARLY) a = c == PR_OP ? avail[t] : 0;
            if (c == 7) a = b < QA_END && !(rdy & 1) && ((chain_done << 1 | 1) >> b & 1) ? left[t] : 0;
            const int tot = __reduce_add_sync(~0u, a);
            if (type < 0) { if (rank < tot) { type = t; mine = a; } else rank -= tot; }
          }
          if (type >= 0) {
#pragma unroll
            for (int o = 1; o < 16; o <<= 1) { const int y = __shfl_up_sync(~0u, mine, o); if (lane >= o) mine += y; }
            const int blk = __ffs(__ballot_sync(~0u, mine > rank)) - 1;
            const int early = !(__shfl_sync(~0u, rdy, blk) >> type & 1);
            uint32_t idx = 0;
            if (n == 0 && spin == 0) PST(3);
            if (lane == 0) asm volatile("atom.relaxed.gpu.global.add.u32 %0, [%1], 1;" : "=r"(idx) : "l"(g_sync + blk * 8 + type) : "memory");
            ld_acquire(g_sync + blk * 8 + 4 + type);
            idx = __shfl_sync(~0u, idx, 0);
            if (idx < item_count(type, blk)) { code = (__shfl_sync(~0u, pr.y, 15) < 32) << 23 | (chain_done >> 15 & 1) << 22 | (chain_done >> p.look & 1) << 21 | early << 20 | type << 16 | blk << 8 | idx; break; }
          } else {
            __nanosleep(50);
          }
          spin_guard(spin);
        }
        if (n == 0) bar_sync(2, 384);
        if (lane == 0) {
          fence_async_global();
          sts32(slots + 4 * (n & 3), code);
          mbar_arrive(bIF + 8 * (n & 3));
        }
        __syncwarp();
        if (code < 0) break;
      }
    } else if (warp == 8) {
      if (elect()) {
        uint32_t dst = sb, bar = bars, ph = 1, next = clk32(), gap = 0;
        auto acquire = [&](uint32_t kb) {
          mbar_wait(bar + 8 * PS, ph);
          mbar_expect(bar, kb * 1024);
          if (gap) {
            uint32_t now;
            do now = clk32(); while ((int)(now - next) < 0);
            next = ((int)(now - next) > 100 ? now - 100 : next) + kb * gap;
          }
        };
        auto advance = [&]() { dst += PB; bar += 8; if (dst == bars) { dst = sb; bar = bars; ph ^= 1; } };
        auto depend = [&](const uint32_t* c, uint32_t need) { wait_count(c, need); fence_async_global(); };
#pragma unroll 1
        for (int n = 0;; n++) {
          mbar_wait(bIF + 8 * (n & 3), (n >> 2) & 1);
          const int code = (int)lds32(slots + 4 * (n & 3));
          if (code < 0) break;
          const int type = (code >> 16) & 15, b = (code >> 8) & 255, idx = code & 255;
          const bool early = code >> 20 & 1, go = !(code >> 21 & 1);
          mbar_arrive(bIE + 8 * (n & 3));
          gap = !(code >> 22 & 1) ? lds32(slots + 16) : type == IT_ATT || type == IT_FIN ? 0 : p.gap2;
          const uint32_t* progress = g_sync + b * 8 + 4 + type;
          if (type == IT_ATT && b >= QA_END) {
            depend(g_sync + SY_Q, (16 - QA_END) * 32);
#pragma unroll 1
            for (int u = 0; u < 2; u++) { acquire(24); bulk_load_last(dst, g_q + (((b - QA_END) * 32 + idx) * 2 + u) * 1536, 24576, bar); advance(); }
          } else if (type == IT_FIN) {
            acquire(10);
            bulk_load(dst, g_x + (b * 16 + idx) * 1280, 10240, bar);
            advance();
            if (early) depend(progress, item_need(type, b));
            if (go) mbar_arrive(bGo);
            const uint2* src = g_part + (b * 16 + idx) * 16 * 1280;
#pragma unroll 1
            for (int i = 0; i < op_split(b); i += 2) { acquire(20); bulk_load_last(dst, src + i * 1280, 20480, bar); advance(); }
            if (!go && p.pol) mbar_arrive(bGo);
          } else {
            const bool op = type == IT_OP, bq = type == IT_BQ;
            const int width = op ? op_width(b) : bq ? bq_width(b) : 192, nb = (width + 63) >> 6, lt = width == 320 ? 1 : 2;
            const int nst = op ? 192 / op_split(b) : 20, kb0 = op ? (idx >> lt) * nst : 0;
            const int col = (op ? idx & ((1 << lt) - 1) : idx) * width;
            const bool whole = !(width & 63);
            const CUtensorMap* m = op ? (whole ? &p.wo : &p.wo2) : bq ? (whole ? &p.wb : &p.wb2) : &p.wq;
            const uint32_t* a = op ? g_o + (b * 192 + kb0) * 2048 : g_xn + b * 20 * 2048;
            int row = kb0 * 32, pre = early && (op || bq) ? min(nst, PRE_MAX) : 0;
            int slow = (code >> 22 & 3) == 3 ? p.slow_n : 0;
            if (slow) gap = p.slow_gap;
            auto weights = [&]() {
              if (slow && --slow == 0) gap = 0;
              acquire(8 + nb * 4);
              if (whole) {
                tma_load3z(dst + 8192, m, row, col >> 6, bar);
              } else {
                tma_load(dst + 8192, m, col, row, bar); tma_load(dst + 12288, m, col + 64, row, bar);
                if (nb == 3) tma_load(dst + 16384, m, col + 128, row, bar);
              }
              row += 32;
            };
            if (pre) {
              uint32_t da = dst, ba = bar;
#pragma unroll 1
              for (int kb = 0; kb < pre; kb++) { weights(); advance(); }
              depend(progress, item_need(type, b));
#pragma unroll 1
              for (int kb = 0; kb < pre; kb++) {
                bulk_load(da, a, 8192, ba);
                a += 2048; da += PB; ba += 8;
                if (da == bars) { da = sb; ba = bars; }
              }
            }
#pragma unroll 1
            for (int kb = pre; kb < nst; kb++) { weights(); if (op && OEF) bulk_load_last(dst, a, 8192, bar); else bulk_load(dst, a, 8192, bar); a += 2048; advance(); }
          }
          if (type == IT_ATT) {
            if (early) depend(progress, 96);
            if (go) mbar_arrive(bGo);
            const uint8_t* src = g_kv + (size_t)(idx * 6 * NSEG + b * 4) * KV_BYTES;
#pragma unroll 1
            for (int u = 0; u < 6; u++) {
              acquire(20);
              bulk_load_last(dst, src, 20480, bar);
              src += u == 2 ? -3 * KV_V : 2 * KV_V;
              advance();
            }
            if (!go && p.pol && ATT_LOOK) mbar_arrive(bGo);
          }
        }
      }
    } else if (warp == 11) {
      uint32_t smid, nsm, used = 0;
      asm("mov.u32 %0, %%smid;" : "=r"(smid)); asm("mov.u32 %0, %%nsmid;" : "=r"(nsm));
      for (int n = 0; n < 64 && used < 96; n++) {
        uint32_t peers = 0;
        used = 0;
        for (uint32_t i = lane; i < min(nsm, 256u); i += 32) {
          const bool taken = ldg_strong32(g_smuse + i) == p.layer + 1;
          used += taken;
          peers += abs((int)(g_smclk[i] - g_smclk[smid & 255])) < 4000 && !taken;
        }
        used = __reduce_add_sync(~0u, used);
        sts32(slots + 16, max(p.gap, (int)min(__reduce_add_sync(~0u, peers), 18u) * p.share >> 3));
      }
    } else if (warp == 10 && lane == 0) {
      for (int n = 0;; n++) {
        mbar_wait(bIF + 8 * (n & 3), (n >> 2) & 1);
        const int code = (int)lds32(slots + 4 * (n & 3));
        if (code < 0) break;
        const int type = (code >> 16) & 15, b = (code >> 8) & 255;
        mbar_wait(done + 8 * (n & 3), (n >> 2) & 1);
        if (type != IT_BQ) red_release(type == IT_Q ? g_sync + SY_Q : g_sync + b * 8 + 5 + type, 1);
        mbar_arrive(bIE + 8 * (n & 3));
      }
    }
  } else {
    asm volatile("setmaxnreg.inc.sync.aligned.u32 224;");
    bar_sync(2, 384);
    const int g = lane >> 2, c = lane & 3;
    Ring r = {sb, bars, 0, 0};
#pragma unroll 1
    for (int n = 0;; n++) {
      mbar_wait(bIF + 8 * (n & 3), (n >> 2) & 1);
      const int code = __shfl_sync(~0u, (int)lds32(slots + 4 * (n & 3)), 0);
      if (code < 0) { TRACE(2); break; }
      const int type = (code >> 16) & 15, b = (code >> 8) & 255, idx = code & 255;
      ITEM(code & 0xfffff, 0);
      if (type == IT_ATT || type == IT_Q) {
        uint32_t q[48];
        if (type == IT_Q || b < QA_END) {
          float d[96];
          gemm_item<192>(r, d, 20, bGo, type == IT_Q ? 12 : -1, warp >> 2);
#pragma unroll
          for (int i = 0; i < 48; i++) q[i] = pack2(d[2 * i], d[2 * i + 1]);
        } else {
#pragma unroll
          for (int u = 0; u < 2; u++) {
            const uint32_t base = r.wait() + threadIdx.x * 16;
#pragma unroll
            for (int i = 0; i < 6; i++) {
              const uint4 v = lds128(base + i * 4096);
              q[24 * u + 4 * i] = v.x; q[24 * u + 4 * i + 1] = v.y; q[24 * u + 4 * i + 2] = v.z; q[24 * u + 4 * i + 3] = v.w;
            }
            r.pop();
          }
        }
        if (type == IT_Q) {
          uint4* dst = g_q + ((b - QA_END) * 32 + idx) * 3072 + threadIdx.x;
#pragma unroll
          for (int i = 0; i < 12; i++) dst[i * 256] = make_uint4(q[4 * i], q[4 * i + 1], q[4 * i + 2], q[4 * i + 3]);
        } else if (warp < 4) {
          attn_a_warp<0>(r, q, b, idx);
        } else {
          attn_a_warp<1>(r, q, b, idx);
        }
      } else if (type == IT_FIN) {
        fin_item(r, scratch, b, idx);
      } else {
        float d[160];
        const int width = type == IT_OP ? op_width(b) : bq_width(b), nst = type == IT_OP ? 192 / op_split(b) : 20;
        const int go_at = max(nst - (code >> 21 & 1 ? p.pol : 6), 1);
        if (width == 320) {
          gemm_item<320>(r, d, nst, bGo, go_at, warp >> 2);
        } else if (width == 160 || BQ_80 == 16) {
          gemm_item<160>(r, d, nst, bGo, go_at, warp >> 2);
#pragma unroll
          for (int i = 80; i < 160; i++) d[i] = 0.f;
        } else {
          gemm_item<80>(r, d, nst, bGo, go_at, warp >> 2);
#pragma unroll
          for (int i = 40; i < 160; i++) d[i] = 0.f;
        }
        if (type == IT_OP) {
          const int tiles = DM / width;
          uint2* dst = g_part + (((b * 16 + warp * 2) * 16 + idx / tiles) * 40 + idx % tiles * (width / 16)) * 32 + lane;
#pragma unroll
          for (int u = 0; u < 20; u++) {
            if (u % 5 == 0 && u * 16 >= width) break;
            dst[u * 32] = make_uint2(pack2(d[8 * u], d[8 * u + 1]), pack2(d[8 * u + 4], d[8 * u + 5]));
            dst[(640 + u) * 32] = make_uint2(pack2(d[8 * u + 2], d[8 * u + 3]), pack2(d[8 * u + 6], d[8 * u + 7]));
          }
        } else {
          const int row = b * 128 + warp * 16 + g;
          const int h0 = idx * (width / 20);
          const float sc = h0 < 32 ? 0.22360679775f * 1.44269504089f : 1.f;
          const bool lo = c < 2;
          uint32_t* da = g_bqkv + (h0 * 256 + (row >> 3)) * 96 + lane;
          uint32_t* db = da + 256 * 96 + (lo ? 2 : -2);
          uint32_t pad[2];
#pragma unroll
          for (int rr = 0; rr < 2; rr++) pad[rr] = c & 1 || h0 < 32 ? 0u : h0 >= 64 ? 0x00003f80u : poly_group((row >> 3) + rr) ? 0x3f803f80u : 0u;
#pragma unroll
          for (int q = 0; q < 8; q++) {
            if (!(q & 1) && q * 40 >= width) break;
#pragma unroll
            for (int rr = 0; rr < 2; rr++) {
              uint32_t w[5];
#pragma unroll
              for (int i = 0; i < 5; i++) w[i] = pack2(d[20 * q + 4 * i + 2 * rr] * sc, d[20 * q + 4 * i + 2 * rr + 1] * sc);
              const int o = q * 2 * 256 * 96 + rr * 96;
              da[o] = w[0]; da[o + 32] = w[1]; da[o + 64] = lo ? w[2] : pad[rr];
              db[o] = lo ? w[3] : w[2]; db[o + 32] = lo ? w[4] : w[3]; db[o + 64] = lo ? pad[rr] : w[4];
            }
          }
        }
      }
      __syncwarp();
      if (lane == 0) mbar_arrive(done + 8 * (n & 3));
      if ((code >> 21 & 1) && (p.pol == 0 || (type == IT_ATT && !ATT_LOOK)) && threadIdx.x == 128) mbar_arrive(bGo);
      ITEM(code & 0xfffff, 1);
    }
  }
}

constexpr int AB_SMEM = 1024 + 98304 + 51200 + 4 * 16384 + 256 + 10240;
#define AB_LW 1
#define AB_U 8
#define AB_WG 4
constexpr int AB_T = AB_WG * 128, AB_PASS = 8 / AB_WG;
__device__ __forceinline__ uint32_t fma2(uint32_t a, uint32_t b, uint32_t c) { uint32_t r; asm("fma.rn.bf16x2 %0, %1, %2, %3;" : "=r"(r) : "r"(a), "r"(b), "r"(c)); return r; }
__device__ __forceinline__ uint32_t ex2_pair(float a, float b, uint32_t one, uint32_t c0) {
  const uint32_t e = __byte_perm(__float_as_uint(a), __float_as_uint(b), 0x6521);
  uint32_t x, r;
  asm("lop3.b32 %0, %1, 0x007f007f, %2, 0xEA;" : "=r"(x) : "r"(e), "r"(one));
  const uint32_t m = fma2(fma2(c0, x, 0x3c0d3c0du), x, 0x3f2b3f2bu);
  asm("lop3.b32 %0, %1, %2, 0x7f807f80, 0xE4;" : "=r"(r) : "r"(e), "r"(m));
  return r;
}
__device__ __forceinline__ float sq2(uint32_t w) { const float a = bf_lo(w), b = bf_hi(w); return fmaf(a, a, b * b); }

__device__ __forceinline__ void attn_b_store(const float* o, int h, int row0, int lane) {
  const int g = lane >> 2, c = lane & 3;
  const float i0 = __frcp_rn(__shfl_sync(~0u, o[8], (lane & ~3) | 2)), i1 = __frcp_rn(__shfl_sync(~0u, o[10], (lane & ~3) | 2));
#pragma unroll
  for (int jj = 0; jj < 3; jj++) {
    if (jj < 2 || c < 2) {
      const int col = h * 20 + 8 * jj + 2 * c;
      uint32_t* dst = g_of + (((row0 >> 7) * 10 + (col >> 6)) * 16 + (row0 >> 3 & 15)) * 256 + (col >> 3 & 7) * 32 + g * 4 + (col >> 1 & 3);
      dst[0] = pack2(o[4 * jj] * i0, o[4 * jj + 1] * i0);
      dst[256] = pack2(o[4 * jj + 2] * i1, o[4 * jj + 3] * i1);
    }
  }
}

struct AbParams { Weights next; uint32_t* done; uint32_t* out; };
__global__ void __launch_bounds__(AB_T + 32, 1) attn_b_kernel(const __grid_constant__ AbParams p) {
  extern __shared__ uint8_t smem_raw[];
  const uint32_t sb = (s2u(smem_raw) + 1023) & ~1023u, sK = sb, sV = sb + 98304, bars = sV + 51200 + 4 * 16384;
  const uint32_t bF = bars + 64, bW = bars + 72, bA = bars + 80, bE = bars + 128, smax = bars + 176;
  auto ring = [&](int i) { return i < 2 ? sK + 51200 + i * 16384 : sV + 51200 + (i - 2) * 16384; };
  const int warp = __shfl_sync(~0u, threadIdx.x >> 5, 0), lane = threadIdx.x & 31;
  const int h = blockIdx.x >> 2, quarter = blockIdx.x & 3;
  TRACE(0);
  pdl_launch();
  if (threadIdx.x < 22) mbar_init(bars + 8 * threadIdx.x, threadIdx.x == 8 ? AB_T / 32 : threadIdx.x >= 16 ? 8 : 1);
  if (threadIdx.x == 32) sts64(smax, 0, 0);
  fence_async();
  __syncthreads();
  pdl_wait();
  const int blk = quarter * 4 + (h >> 3), cg = h & 7;
  auto unsafe = [&]() { const float2 m = lds64f(smax); return !(m.x * m.y <= 10000.f); };
  if (warp == AB_T / 32) {
    auto load_w = [&]() {
      mbar_expect(bW, 102400);
      for (int i = 0; i < 4; i++) bulk_load((i < 2 ? sK : sV) + (i & 1) * 25600, g_wb + cg * 6400 + i * 1600, 25600, bW);
    };
    if (elect()) {
      const uint32_t* gk = g_bqkv + (32 + h) * 256 * 96;
#pragma unroll 1
      for (int i = 0; i < 8; i++) {
        if (i >= AB_LW) mbar_wait(bars + 8 * (i - AB_LW), 0);
        mbar_expect(bars + 8 * i, 24576);
        bulk_load_last(sK + i * 12288, gk + i * 3072, 12288, bars + 8 * i);
        bulk_load_last(sV + i * 12288, gk + 32 * 256 * 96 + i * 3072, 12288, bars + 8 * i);
      }
    }
    __syncwarp();
    if (blockIdx.x < NSLOT) for (int i = lane; i < 512; i += 32) reinterpret_cast<uint4*>(pool_at(blockIdx.x * 8192))[i] = make_uint4(0, 0, 0, 0);
    if (blockIdx.x == 127) for (int i = lane; i < SY_N; i += 32) g_sync[i] = 0;
    if (p.next.w[0] && lane == 0) {
      for (int i = 0; i < AB_PF; i++) { const uint32_t t0 = clk32(); while (clk32() - t0 < (i ? AB_PFD : AB_PF0)) __nanosleep(200); prefetch_weights(p.next, i); }
    }
    __syncwarp();
    mbar_wait(bF, 0);
    const bool redo = unsafe();
    if (!redo && lane == 0) load_w();
    if (lane < 16) asm volatile("cp.async.bulk.prefetch.L2.global [%0], 1280;" :: "l"(g_x + ((blk * 16 + lane) * 40 + cg * 5) * 32) : "memory");
    __syncwarp();
    bar_sync(1, AB_T + 32);
    if (lane == 0) {
      ABT(!!p.out, 1);
      red_release(p.done + quarter * 32, 1);
      ABT(!!p.out, 2);
      if (redo) load_w();
      wait_count(p.done + quarter * 32, 32);
      fence_async_global();
      ABT(!!p.out, 3);
      for (int kb = 0; kb < 10; kb++) {
        const int i = kb < 6 ? kb : kb - 6;
        if (kb >= 6) mbar_wait(bE + 8 * i, 0);
        mbar_expect(bA + 8 * i, 16384);
        bulk_load(ring(i), g_of + (blk * 10 + kb) * 4096, 16384, bA + 8 * i);
      }
    }
    return;
  }
  float qmax = 0.f;
  const uint32_t one = opaque(0x3f803f80u + (threadIdx.x >> 10)), c0 = opaque(0x3ea83ea8u + (threadIdx.x >> 10));
#pragma unroll 1
  for (int pass = 0; pass < AB_PASS; pass++) {
    const int row0 = quarter * 512 + ((warp >> 2) * AB_PASS + pass) * 64 + (warp & 3) * 16;
    const uint32_t* gq = g_bqkv + (h * 256 + (row0 >> 3)) * 96 + lane;
    const uint32_t q0 = gq[0], q1 = gq[96], q2 = gq[32], q3 = gq[128];
    uint32_t q4 = gq[64], q5 = gq[160];
    const uint32_t z0 = gq[64 + 3 - (lane & 3)], z1 = gq[160 + 3 - (lane & 3)];
    {
      float n0 = sq2(q0) + sq2(q2) + sq2(q4), n1 = sq2(q1) + sq2(q3) + sq2(q5);
      n0 += __shfl_xor_sync(~0u, n0, 1); n1 += __shfl_xor_sync(~0u, n1, 1);
      n0 += __shfl_xor_sync(~0u, n0, 2); n1 += __shfl_xor_sync(~0u, n1, 2);
      qmax = (n0 > qmax || n0 != n0) ? n0 : qmax;
      qmax = (n1 > qmax || n1 != n1) ? n1 : qmax;
    }
    if (pass == AB_PASS - 1) {
      float kmax = 0.f;
#pragma unroll
      for (int i = 0; i < SEQ / AB_T; i++) {
        const int key = threadIdx.x + AB_T * i;
        const uint32_t a = sK + (key >> 3) * 384 + (key & 7) * 16;
        const uint4 x = lds128(a), y = lds128(a + 128);
        const uint2 z = lds64(a + 256);
        const float n = ((sq2(x.x) + sq2(x.y)) + (sq2(x.z) + sq2(x.w))) + ((sq2(y.x) + sq2(y.y)) + (sq2(y.z) + sq2(y.w))) + (sq2(z.x) + sq2(z.y));
        kmax = (n > kmax || n != n) ? n : kmax;
      }
      const uint32_t kb = __reduce_max_sync(~0u, __float_as_uint(kmax) & 0x7fffffffu), qb = __reduce_max_sync(~0u, __float_as_uint(qmax) & 0x7fffffffu);
      if (lane < 2) asm volatile("red.shared.max.u32 [%0], %1;" :: "r"(smax + 4 * lane), "r"(lane ? kb : qb) : "memory");
      __syncwarp();
    }
    if ((lane & 3) == 2) { q4 = 0xBF8043C0u; q5 = 0xBF8043C0u; }
    float o[12];
    auto desc = [](uint32_t lo, uint32_t hi) { uint64_t d; asm("mov.b64 %0, {%1, %2};" : "=l"(d) : "r"(lo), "r"(hi)); return d; };
    const uint32_t k0 = (uint32_t)mkdesc(sK, 128, 0, 0), k1 = (uint32_t)mkdesc(sK + 256, 0, 0, 0), v0 = (uint32_t)mkdesc(sV, 384, 0, 0);
    float sa[16], sb2[16];
    uint32_t pa[8], pb[8];
    auto qk = [&](float* s, uint32_t t) {
      wg_rs32_00(s, q0, q1, q2, q3, desc(k0 + t, 24), 0);
      wg_rs32_00(s, q4, q5, z0, z1, desc(k1 + t, 24), 1);
      wg_commit();
    };
    auto step = [&](float* s, uint32_t* pp, int g0, uint32_t t, uint32_t nx, int acc) {
      wg_wait<1>();
      reg_fence<16>(s);
#pragma unroll
      for (int i = 0; i < 8; i++) pp[i] = poly_group(g0 + (i >> 1)) ? ex2_pair(s[2 * i], s[2 * i + 1], one, c0) : pack2(ex2(s[2 * i]), ex2(s[2 * i + 1]));
      wg_fence();
      wg_rs24_01(o, pp[0], pp[1], pp[2], pp[3], desc(v0 + t, 8), acc);
      wg_rs24_01(o, pp[4], pp[5], pp[6], pp[7], desc(v0 + t + 48, 8), 1);
      qk(s, nx);
    };
    if (pass == 0) mbar_wait(bars, 0);
    wg_fence();
    qk(sa, 0);
    qk(sb2, 96);
#pragma unroll 1
    for (uint32_t t = 0; t < 64 * 96; t += AB_U * 96) {
      const uint32_t nx = t + AB_U * 96 < 64 * 96 ? t + AB_U * 96 : 0;
      if (pass == AB_PASS - 1 && t == 40 * 96 && lane == 0) mbar_arrive(bF);
#pragma unroll
      for (int u = 0; u < AB_U; u += 2) {
        if (u == AB_U - 2 && pass == 0) mbar_wait(bars + 8 * (nx / 768), 0);
        step(sa, pa, 0, t + u * 96, u + 2 < AB_U ? t + (u + 2) * 96 : nx, u | t);
        step(sb2, pb, 4, t + u * 96 + 96, (u + 2 < AB_U ? t + (u + 2) * 96 : nx) + 96, 1);
      }
    }
    wg_wait<0>();
    reg_fence<12>(o); reg_fence<16>(sa); reg_fence<16>(sb2);
    attn_b_store(o, h, row0, lane);
  }
  mbar_wait(bF, 0);
  if (unsafe())
#pragma unroll 1
  for (int pass = 0; pass < AB_PASS; pass++) {
    const int row0 = quarter * 512 + ((warp >> 2) * AB_PASS + pass) * 64 + (warp & 3) * 16;
    const uint32_t* gq = g_bqkv + (h * 256 + (row0 >> 3)) * 96 + lane;
    const uint32_t q0 = gq[0], q1 = gq[96], q2 = gq[32], q3 = gq[128], q4 = gq[64], q5 = gq[160];
    float o[12];
#pragma unroll
    for (int i = 0; i < 12; i++) o[i] = 0.f;
    float m0 = -INFINITY, m1 = -INFINITY;
#pragma unroll 1
    for (int kt = 0; kt < 32; kt++) {
      float s[32];
      const uint64_t dk = mkdesc(sK + kt * 3072, 128, 384, 0), dk2 = mkdesc(sK + kt * 3072 + 256, 0, 384, 0);
      wg_fence();
      wg_rs64_00(s, q0, q1, q2, q3, dk, 0);
      wg_rs64_00(s, q4, q5, 0, 0, dk2, 1);
      wg_commit();
      wg_wait<0>();
      reg_fence<32>(s); reg_fence<12>(o);
      float n0 = m0, n1 = m1;
#pragma unroll
      for (int jj = 0; jj < 8; jj++) { n0 = fmaxf(n0, fmaxf(s[4 * jj], s[4 * jj + 1])); n1 = fmaxf(n1, fmaxf(s[4 * jj + 2], s[4 * jj + 3])); }
      n0 = fmaxf(n0, __shfl_xor_sync(~0u, n0, 1)); n0 = fmaxf(n0, __shfl_xor_sync(~0u, n0, 2));
      n1 = fmaxf(n1, __shfl_xor_sync(~0u, n1, 1)); n1 = fmaxf(n1, __shfl_xor_sync(~0u, n1, 2));
      const float r0 = ex2(m0 - n0), r1 = ex2(m1 - n1);
      m0 = n0; m1 = n1;
#pragma unroll
      for (int jj = 0; jj < 3; jj++) { o[4 * jj] *= r0; o[4 * jj + 1] *= r0; o[4 * jj + 2] *= r1; o[4 * jj + 3] *= r1; }
      uint32_t pp[16];
#pragma unroll
      for (int jj = 0; jj < 8; jj++) {
        pp[2 * jj] = pack2(ex2(s[4 * jj] - m0), ex2(s[4 * jj + 1] - m0));
        pp[2 * jj + 1] = pack2(ex2(s[4 * jj + 2] - m1), ex2(s[4 * jj + 3] - m1));
      }
      const uint64_t dv = mkdesc(sV + kt * 3072, 384, 128, 0);
      wg_fence();
#pragma unroll
      for (int kk = 0; kk < 4; kk++) wg_rs24_01(o, pp[4 * kk], pp[4 * kk + 1], pp[4 * kk + 2], pp[4 * kk + 3], dv + kk * 48, 1);
      wg_commit();
    }
    wg_wait<0>();
    reg_fence<12>(o);
    attn_b_store(o, h, row0, lane);
  }
  ABT(!!p.out, 0);
  bar_arrive(1, AB_T + 32);
  if (warp >= 12) return;
  const int g = lane >> 2, c = lane & 3;
  const bool live = opaque(threadIdx.x) < 256;
  float d[40] = {};
  uint2* x = g_x + ((blk * 16 + warp * 2) * 40 + cg * 5) * 32 + lane;
  if (warp < 8) {
#pragma unroll
  for (int i = 0; i < 10; i++) {
    const int r = i / 5, u = i % 5;
    const float4 t = unpack4(x[(r * 40 + u) * 32]);
    d[8 * u + 2 * r] = t.x; d[8 * u + 2 * r + 1] = t.y; d[8 * u + 4 + 2 * r] = t.z; d[8 * u + 5 + 2 * r] = t.w;
  }
  mbar_wait(bW, 0);
  reg_fence<40>(d);
  ABT(!!p.out, 4);
#pragma unroll 1
  for (int kb = 0; kb < 10; kb++) {
    const int i = kb < 6 ? kb : kb - 6;
    mbar_wait(bA + 8 * i, kb >= 6);
    const uint64_t da = mkdesc(ring(i) + (warp >> 2) * 8192, 128, 1024, 0), db = mkdesc(kb < 5 ? sK + kb * 10240 : sV + (kb - 5) * 10240, 1280, 128, 0);
    wg_fence();
#pragma unroll
    for (int kk = 0; kk < 4; kk++) wg_ss80_01(d, da + kk * 16, db + kk * 160, 1);
    wg_commit();
    if (kb > 0 && kb < 5) { wg_wait<1>(); if (lane == 0) mbar_arrive(bE + 8 * (kb - 1)); }
  }
  wg_wait<0>();
  reg_fence<40>(d);
  }
  ABT(!!p.out, 5);
  if (p.out) {
    if (warp >= 8) return;
    const uint32_t stage = sK + 83968 + warp * 2560 + (warp < 4 ? 0 : 131328 - 10240);
#pragma unroll
    for (int u = 0; u < 5; u++)
      stsm4(stage + (lane & 15) * 160 + u * 32 + (lane >> 4) * 16, pack2(d[8 * u], d[8 * u + 1]), pack2(d[8 * u + 2], d[8 * u + 3]),
            pack2(d[8 * u + 4], d[8 * u + 5]), pack2(d[8 * u + 6], d[8 * u + 7]));
    __syncwarp();
    uint4* out = reinterpret_cast<uint4*>(p.out + (blk * 128 + warp * 16) * (DM / 2) + cg * 40);
#pragma unroll
    for (int i = 0; i < 5; i++) { const int e = i * 32 + lane, r = e / 10; out[r * (DM / 8) + e - r * 10] = lds128(stage + e * 16); }
  } else {
    float2* stat = g_stat + blk * 1024 + (warp & 7) * 16 + g;
    float mean[2], rs[2];
#pragma unroll
    for (int r = 0; r < 2; r++) {
      float t = 0.f, q = 0.f;
#pragma unroll
      for (int i = 0; i < 10; i++) t += d[4 * i + 2 * r] + d[4 * i + 2 * r + 1];
      t += __shfl_xor_sync(~0u, t, 1); t += __shfl_xor_sync(~0u, t, 2);
      t *= 1.f / 80;
#pragma unroll
      for (int i = 0; i < 10; i++) { const float a = d[4 * i + 2 * r] - t, b = d[4 * i + 2 * r + 1] - t; q += a * a + b * b; }
      q += __shfl_xor_sync(~0u, q, 1); q += __shfl_xor_sync(~0u, q, 2);
      if (c == r && live) asm volatile("st.relaxed.gpu.global.v2.b32 [%0], {%1, %2};" :: "l"(stat + cg * 128 + r * 8), "r"(__float_as_uint(t)), "r"(nz(__float_as_uint(q))) : "memory");
    }
#pragma unroll
    for (int i = 0; i < 10; i++) {
      const int r = i / 5, u = i % 5;
      if (live) x[(r * 40 + u) * 32] = make_uint2(pack2(d[8 * u + 2 * r], d[8 * u + 2 * r + 1]), pack2(d[8 * u + 4 + 2 * r], d[8 * u + 5 + 2 * r]));
    }
    ABT(0, 6);
    uint2 e[4];
    int n = 0;
    do {
#pragma unroll
      for (int i = 0; i < 4; i++)
        asm volatile("ld.relaxed.gpu.global.v2.b32 {%0, %1}, [%2];" : "=r"(e[i].x), "=r"(e[i].y) : "l"(stat + (2 * c + (i & 1)) * 128 + (i >> 1) * 8) : "memory");
      spin_guard(n);
    } while (__any_sync(~0u, min(min(e[0].y, e[1].y), min(e[2].y, e[3].y)) == 0 && live));
#pragma unroll
    for (int r = 0; r < 2; r++) {
      const float m0 = __uint_as_float(e[2 * r].x), m1 = __uint_as_float(e[2 * r + 1].x);
      float t = m0 + m1;
      t += __shfl_xor_sync(~0u, t, 1); t += __shfl_xor_sync(~0u, t, 2);
      t *= 0.125f;
      float q = __uint_as_float(e[2 * r].y) + __uint_as_float(e[2 * r + 1].y) + 80.f * ((m0 - t) * (m0 - t) + (m1 - t) * (m1 - t));
      q += __shfl_xor_sync(~0u, q, 1); q += __shfl_xor_sync(~0u, q, 2);
      mean[r] = t; rs[r] = rsqrtf(q * (1.f / DM) + 1e-5f);
    }
    ABT(0, 7);
    uint32_t w[2][5][2];
#pragma unroll
    for (int i = 0; i < 20; i++) w[i & 1][i >> 2][i >> 1 & 1] = pack2((d[2 * i] - mean[i & 1]) * rs[i & 1], (d[2 * i + 1] - mean[i & 1]) * rs[i & 1]);
    ln_store(w, blk * 8 + warp, cg * 5, live);
  }
  ABT(!!p.out, 8);
  TRACE(2);
}

typedef CUresult (*EncodeFn)(CUtensorMap*, CUtensorMapDataType, cuuint32_t, void*, const cuuint64_t*, const cuuint64_t*,
                             const cuuint32_t*, const cuuint32_t*, CUtensorMapInterleave, CUtensorMapSwizzle,
                             CUtensorMapL2promotion, CUtensorMapFloatOOBfill);

void make_map(EncodeFn enc, CUtensorMap* m, const void* ptr, int cols, int rows, int nb) {
  const cuuint64_t dims[3] = {(cuuint64_t)(nb ? 64 : cols), (cuuint64_t)rows, (cuuint64_t)cols / 64};
  const cuuint64_t strides[2] = {(cuuint64_t)cols * 2, 128};
  const cuuint32_t box[3] = {64, 32, (cuuint32_t)nb}, es[3] = {1, 1, 1};
  enc(m, CU_TENSOR_MAP_DATA_TYPE_BFLOAT16, nb ? 3 : 2, const_cast<void*>(ptr), dims, strides, box, es, CU_TENSOR_MAP_INTERLEAVE_NONE,
      CU_TENSOR_MAP_SWIZZLE_128B, CU_TENSOR_MAP_L2_PROMOTION_L2_128B, CU_TENSOR_MAP_FLOAT_OOB_FILL_NONE);
}
template <class... KA, class... A>
void launch(void (*kern)(KA...), int grid, int block, int smem, int cluster, bool pdl, A... args) {
  cudaFuncSetAttribute(kern, cudaFuncAttributeMaxDynamicSharedMemorySize, smem);
  cudaLaunchConfig_t cfg = {};
  cfg.gridDim = dim3(grid); cfg.blockDim = dim3(block); cfg.dynamicSmemBytes = smem; cfg.stream = cudaStreamPerThread;
  cudaLaunchAttribute at[2];
  int n = 0;
  if (cluster > 1) { at[n].id = cudaLaunchAttributeClusterDimension; at[n].val.clusterDim.x = cluster; at[n].val.clusterDim.y = 1; at[n].val.clusterDim.z = 1; n++; }
  if (pdl) { at[n].id = cudaLaunchAttributeProgrammaticStreamSerialization; at[n].val.programmaticStreamSerializationAllowed = 1; n++; }
  cfg.attrs = at; cfg.numAttrs = n;
  cudaLaunchKernelEx(&cfg, kern, args...);
}
template <class T> void* sym(T& s) { void* p = nullptr; cudaGetSymbolAddress(&p, s); return p; }

}

#define MODE(b) 0
extern "C" void kernel_launch(void* const* d_in, const int* in_sizes, int n_in, void* d_out, int out_size) {
  const __nv_bfloat16* x = (const __nv_bfloat16*)d_in[0];
  void* fn = nullptr; cudaDriverEntryPointQueryResult qr;
  cudaGetDriverEntryPoint("cuTensorMapEncodeTiled", &fn, cudaEnableDefault, &qr);
  EncodeFn enc = (EncodeFn)fn;

  ChainParams ch = {};
  PostParams op = {};
  for (int i = 0; i < 3; i++) {
    const cuuint64_t dims[3] = {HD, 128, 5}, strides[2] = {HD * 2, HD * 256};
    const cuuint32_t box[3] = {64, 128, 5}, es[3] = {1, 1, 1};
    enc(i == 0 ? &ch.wq : i == 1 ? &ch.wk : &ch.wv, CU_TENSOR_MAP_DATA_TYPE_BFLOAT16, 3, d_in[2 + i], dims, strides, box, es, CU_TENSOR_MAP_INTERLEAVE_NONE,
        CU_TENSOR_MAP_SWIZZLE_128B, W_PROMO, CU_TENSOR_MAP_FLOAT_OOB_FILL_NONE);
  }
  {
    const cuuint64_t dims[3] = {DM, HD, 7}, strides[2] = {DM * 2, 64};
    const cuuint32_t box[3] = {32, 64, 7}, es[3] = {1, 1, 1};
    enc(&ch.wo, CU_TENSOR_MAP_DATA_TYPE_BFLOAT16, 3, d_in[5], dims, strides, box, es, CU_TENSOR_MAP_INTERLEAVE_NONE,
        CU_TENSOR_MAP_SWIZZLE_64B, CU_TENSOR_MAP_L2_PROMOTION_L2_128B, CU_TENSOR_MAP_FLOAT_OOB_FILL_NONE);
  }
  ch.mem0 = (const __nv_bfloat16*)d_in[1];
  ch.pool = (uint8_t*)(((uintptr_t)sym(g_pool) + 8191) & ~(uintptr_t)8191); ch.kv = (uint8_t*)sym(g_kv); ch.xc = (const uint32_t*)sym(g_xc); ch.sync = (uint32_t*)sym(g_sync);
  ch.d1 = 0; ch.d1b = 0; ch.d2 = 0; ch.d2b = 0;
  make_map(enc, &op.wq, d_in[2], HD, DM, 3);
  make_map(enc, &op.wo, d_in[5], DM, HD, 5); make_map(enc, &op.wo2, d_in[5], DM, HD, 0);
  make_map(enc, &op.wb, d_in[8], 1920, DM, 5); make_map(enc, &op.wb2, d_in[8], 1920, DM, 0);
  op.gap = 17; op.share = 20; op.look = 20; op.gap2 = 0; op.pol = 1; op.slow_n = 8; op.slow_gap = 23;

  const Weights wa = {{(const uint8_t*)d_in[3], (const uint8_t*)d_in[4], (const uint8_t*)d_in[2], (const uint8_t*)d_in[5]}}, none = {};
  launch(first_kernel, 132, 384, 128 * 1024, 1, false, x, (const uint4*)d_in[9], wa);
  for (int layer = 0; layer < 2; layer++) {
    ch.layer = ch.d2b = op.layer = layer;
    launch(chain_kernel, 96, 256, CH_SMEM, 3, true, ch);
    launch(post_kernel, MODE(3) ? 36 : 132, 384, OP_SMEM, 1, !MODE(1), op);
    const AbParams ab = {layer == 0 ? wa : none, (uint32_t*)sym(g_bo) + layer * 128, layer == 0 ? nullptr : (uint32_t*)d_out};
    launch(attn_b_kernel, 128, AB_T + 32, AB_SMEM, 1, true, ab);
  }
}
```

```cpp
#include <cuda_runtime.h>
#include <cuda_bf16.h>
#include <cuda.h>
#include <stdint.h>

namespace {

constexpr int SEQ = 2048, DM = 640, HD = 6144, NSEG = 64;
constexpr int SPIN_LIMIT = 1 << 20;

__device__ __align__(128) uint2 g_x[SEQ * DM / 4];
__device__ __align__(128) uint32_t g_of[SEQ * DM / 2];
__device__ __align__(128) uint4 g_wb[DM * DM / 8];
__device__ __align__(16) float2 g_stat[16 * 8 * 128];
__device__ uint32_t g_bo[8 * 32];
__device__ __align__(128) uint4 g_q[SEQ * HD / 8];
__device__ __align__(128) uint32_t g_o[SEQ * HD / 2];
constexpr int KV_BYTES = 5120, KV_M = 4096, KV_V = NSEG * KV_BYTES;
__device__ __align__(128) uint8_t g_kv[96 * 2 * NSEG * KV_BYTES];
__device__ __align__(128) uint32_t g_xc[SEQ * DM / 2];
#define OP_B4 7
#define OP_B8 10
#define OP_B16 16
#define QA_END 11
__host__ __device__ constexpr int op_split(int b) { return b < OP_B4 ? 2 : b < OP_B8 ? 4 : b < OP_B16 ? 8 : 16; }
#define AB_PF 3
#define AB_PF0 0
#define AB_PFD 5000
#define W_PROMO CU_TENSOR_MAP_L2_PROMOTION_L2_128B
#define OP_EARLY 1
#define ATT_LOOK 1
#define PR_FIN 1
#define PR_ATT 0
#define PR_OP 2
#define PRE_MAX PS
#define BQ_RUSH 16
#define OEF 0
#define BQ_HOLD 6
#define WEF 1
#define FK_REP 4
#define FK_PF 1
#define BQ_160 10
#define BQ_80 16
#define OP_160 14
__host__ __device__ constexpr int op_width(int b) { return b < OP_160 ? 320 : 160; }
__host__ __device__ constexpr int bq_width(int b) { return b < BQ_160 ? 320 : b < BQ_80 ? 160 : 80; }
__device__ __align__(128) uint2 g_part[16 * 16 * 16 * 40 * 32];
__device__ __align__(128) uint32_t g_xn[SEQ * DM / 2];
constexpr int SY_Q = 128, SY_T = 160, SY_QC = 192, SY_N = 193;
__device__ __align__(16) uint32_t g_sync[SY_N];
constexpr int NSLOT = 92;
__device__ uint32_t g_pool[(NSLOT + 2) * 2048];
__device__ int g_smpart[256], g_orient[NSLOT];
__device__ uint32_t g_smclk[256], g_smuse[256];
__device__ uint32_t g_bqkv[3 * 32 * 256 * 96];

#define ABT(L, i)
#define PST(i)
#define MODE_D(b) 0
#define DELAY(d)
#define XT(i)
#define MISS(k, n)
#define PRO(i)
#define TRACE(w)
#define ITEM(code, w)
#define TR(i, v)
#define TM(i)
#define TM1(i)
#define TMD(i, dep)
#define TMV(i, at, v)

__device__ __forceinline__ uint32_t gtime() { uint32_t c; asm volatile("mov.u32 %0, %%globaltimer_lo;" : "=r"(c) :: "memory"); return c; }
__device__ __forceinline__ uint32_t clk32() { uint32_t c; asm volatile("mov.u32 %0, %%clock;" : "=r"(c) :: "memory"); return c; }
__device__ __forceinline__ uint32_t s2u(const void* p) { return (uint32_t)__cvta_generic_to_shared(p); }
__device__ __forceinline__ uint32_t pack2(float a, float b) {
  uint32_t r; asm("cvt.rn.bf16x2.f32 %0, %1, %2;" : "=r"(r) : "f"(b), "f"(a)); return r; }
__device__ __forceinline__ float bf_lo(uint32_t w) { return __uint_as_float(w << 16); }
__device__ __forceinline__ float bf_hi(uint32_t w) { return __uint_as_float(w & 0xffff0000u); }
__device__ __forceinline__ uint2 pack4(float4 v) { return make_uint2(pack2(v.x, v.y), pack2(v.z, v.w)); }
__device__ __forceinline__ float4 unpack4(uint2 w) { return make_float4(bf_lo(w.x), bf_hi(w.x), bf_lo(w.y), bf_hi(w.y)); }
__device__ __forceinline__ float ex2(float x) { float y; asm("ex2.approx.ftz.f32 %0, %1;" : "=f"(y) : "f"(x)); return y; }

__device__ __forceinline__ void mbar_init(uint32_t bar, uint32_t n) {
  asm volatile("mbarrier.init.shared::cta.b64 [%0], %1;" :: "r"(bar), "r"(n) : "memory"); }
__device__ __forceinline__ void mbar_expect(uint32_t bar, uint32_t bytes) {
  asm volatile("mbarrier.arrive.expect_tx.shared::cta.b64 _, [%0], %1;" :: "r"(bar), "r"(bytes) : "memory"); }
__device__ __forceinline__ void mbar_arrive(uint32_t bar) {
  asm volatile("mbarrier.arrive.shared::cta.b64 _, [%0];" :: "r"(bar) : "memory"); }
__device__ __forceinline__ void mbar_wait(uint32_t bar, uint32_t ph) {
  asm volatile("{.reg .pred p; .reg .u32 n; mov.u32 n, 0;\n"
               "W: mbarrier.try_wait.parity.shared::cta.b64 p, [%0], %1; @p bra D;\n"
               "add.u32 n, n, 1; setp.gt.u32 p, n, %2; @p trap; bra W;\n"
               "D: }" :: "r"(bar), "r"(ph), "n"(SPIN_LIMIT) : "memory");
}
__device__ __forceinline__ void mbar_wait_cluster(uint32_t bar, uint32_t ph) {
  asm volatile("{.reg .pred p; .reg .u32 n; mov.u32 n, 0;\n"
               "W: mbarrier.try_wait.parity.acquire.cluster.shared::cta.b64 p, [%0], %1; @p bra D;\n"
               "add.u32 n, n, 1; setp.gt.u32 p, n, %2; @p trap; bra W;\n"
               "D: }" :: "r"(bar), "r"(ph), "n"(SPIN_LIMIT) : "memory");
}
__device__ __forceinline__ void spin_guard(int& n) {
  asm volatile("{.reg .pred p; add.s32 %0, %0, 1; setp.gt.s32 p, %0, %1; @p trap;}" : "+r"(n) : "n"(SPIN_LIMIT));
}
__device__ __forceinline__ void pdl_wait() { asm volatile("griddepcontrol.wait;" ::: "memory"); TRACE(1); }
__device__ __forceinline__ void pdl_launch() { asm volatile("griddepcontrol.launch_dependents;" ::: "memory"); }
__device__ __forceinline__ uint32_t ld_acquire(const uint32_t* p) { uint32_t v; asm volatile("ld.acquire.gpu.global.u32 %0, [%1];" : "=r"(v) : "l"(p) : "memory"); return v; }
__device__ __forceinline__ void red_release(uint32_t* p, uint32_t v) { asm volatile("red.release.gpu.global.add.u32 [%0], %1;" :: "l"(p), "r"(v) : "memory"); }
__device__ __forceinline__ void red_relaxed(uint32_t* p, uint32_t v) { asm volatile("red.relaxed.gpu.global.add.u32 [%0], %1;" :: "l"(p), "r"(v) : "memory"); }
__device__ __forceinline__ void fence_async_global() { asm volatile("fence.proxy.async.global;" ::: "memory"); }
__device__ __forceinline__ void fence_async() { asm volatile("fence.proxy.async.shared::cta;" ::: "memory"); }
__device__ __forceinline__ void bar_sync(int id, int n) { asm volatile("bar.sync %0, %1;" :: "r"(id), "r"(n) : "memory"); }
__device__ __forceinline__ void bar_arrive(int id, int n) { asm volatile("bar.arrive %0, %1;" :: "r"(id), "r"(n) : "memory"); }
__device__ __forceinline__ void tma_load(uint32_t dst, const CUtensorMap* m, int c0, int c1, uint32_t bar) {
  asm volatile("cp.async.bulk.tensor.2d.shared::cluster.global.mbarrier::complete_tx::bytes [%0], [%1, {%3, %4}], [%2];"
               :: "r"(dst), "l"(m), "r"(bar), "r"(c0), "r"(c1) : "memory"); }
template <bool STREAM = false>
__device__ __forceinline__ void tma_load3(uint32_t dst, const CUtensorMap* m, int c0, int c1, uint32_t bar) {
  if (STREAM)
    asm volatile("{.reg .b64 pol; createpolicy.fractional.L2::evict_first.b64 pol, 1.0;\n"
                 "cp.async.bulk.tensor.3d.shared::cluster.global.mbarrier::complete_tx::bytes.L2::cache_hint [%0], [%1, {%3, %4, 0}], [%2], pol;}"
                 :: "r"(dst), "l"(m), "r"(bar), "r"(c0), "r"(c1) : "memory");
  else
  asm volatile("cp.async.bulk.tensor.3d.shared::cluster.global.mbarrier::complete_tx::bytes [%0], [%1, {%3, %4, 0}], [%2];"
               :: "r"(dst), "l"(m), "r"(bar), "r"(c0), "r"(c1) : "memory"); }
__device__ __forceinline__ void tma_load3z(uint32_t dst, const CUtensorMap* m, int c1, int c2, uint32_t bar) {
  asm volatile("cp.async.bulk.tensor.3d.shared::cluster.global.mbarrier::complete_tx::bytes [%0], [%1, {0, %3, %4}], [%2];"
               :: "r"(dst), "l"(m), "r"(bar), "r"(c1), "r"(c2) : "memory"); }
__device__ __forceinline__ void tma_store(const CUtensorMap* m, uint32_t src, int c0, int c1) {
  asm volatile("cp.async.bulk.tensor.2d.global.shared::cta.bulk_group [%0, {%2, %3}], [%1];"
               :: "l"(m), "r"(src), "r"(c0), "r"(c1) : "memory"); }
__device__ __forceinline__ void tma_store_stream(const CUtensorMap* m, uint32_t src, int c0, int c1) {
  asm volatile("{.reg .b64 pol; createpolicy.fractional.L2::evict_first.b64 pol, 1.0;\n"
               "cp.async.bulk.tensor.2d.global.shared::cta.bulk_group.L2::cache_hint [%0, {%2, %3}], [%1], pol;}"
               :: "l"(m), "r"(src), "r"(c0), "r"(c1) : "memory"); }
__device__ __forceinline__ void bulk_load(uint32_t dst, const void* src, uint32_t bytes, uint32_t bar) {
  asm volatile("cp.async.bulk.shared::cluster.global.mbarrier::complete_tx::bytes [%0], [%1], %2, [%3];"
               :: "r"(dst), "l"(src), "r"(bytes), "r"(bar) : "memory"); }
__device__ __forceinline__ void bulk_load_last(uint32_t dst, const void* src, uint32_t bytes, uint32_t bar) {
  asm volatile("{.reg .b64 pol; createpolicy.fractional.L2::evict_first.b64 pol, 1.0;\n"
               "cp.async.bulk.shared::cluster.global.mbarrier::complete_tx::bytes.L2::cache_hint [%0], [%1], %2, [%3], pol;}"
               :: "r"(dst), "l"(src), "r"(bytes), "r"(bar) : "memory"); }
__device__ __forceinline__ void tma_load_last(uint32_t dst, const CUtensorMap* m, int c0, int c1, uint32_t bar) {
  asm volatile("{.reg .b64 pol; createpolicy.fractional.L2::evict_first.b64 pol, 1.0;\n"
               "cp.async.bulk.tensor.2d.shared::cluster.global.mbarrier::complete_tx::bytes.L2::cache_hint [%0], [%1, {%3, %4}], [%2], pol;}"
               :: "r"(dst), "l"(m), "r"(bar), "r"(c0), "r"(c1) : "memory"); }
__device__ __forceinline__ void bulk_send(uint32_t dst, uint32_t src, uint32_t bytes, uint32_t bar) {
  asm volatile("cp.async.bulk.shared::cluster.shared::cta.mbarrier::complete_tx::bytes [%0], [%1], %2, [%3];"
               :: "r"(dst), "r"(src), "r"(bytes), "r"(bar) : "memory"); }
__device__ __forceinline__ void bulk_store(void* dst, uint32_t src, uint32_t bytes) {
  asm volatile("cp.async.bulk.global.shared::cta.bulk_group [%0], [%1], %2;" :: "l"(dst), "r"(src), "r"(bytes) : "memory"); }
__device__ __forceinline__ void bulk_commit() { asm volatile("cp.async.bulk.commit_group;" ::: "memory"); }
template <int N> __device__ __forceinline__ void bulk_wait_read() { asm volatile("cp.async.bulk.wait_group.read %0;" :: "n"(N) : "memory"); }
template <int N> __device__ __forceinline__ void bulk_wait() { asm volatile("cp.async.bulk.wait_group %0;" :: "n"(N) : "memory"); }

__device__ __forceinline__ uint64_t mkdesc(uint32_t addr, uint32_t lbo, uint32_t sbo, uint32_t sw) {
  return (uint64_t)((addr & 0x3FFFF) >> 4) | ((uint64_t)(lbo >> 4) << 16) | ((uint64_t)(sbo >> 4) << 32) | ((uint64_t)sw << 62); }
__device__ __forceinline__ void wg_fence() { asm volatile("wgmma.fence.sync.aligned;" ::: "memory"); }
__device__ __forceinline__ void wg_commit() { asm volatile("wgmma.commit_group.sync.aligned;" ::: "memory"); }
template <int N> __device__ __forceinline__ void wg_wait() { asm volatile("wgmma.wait_group.sync.aligned %0;" :: "n"(N) : "memory"); }
template <int N> __device__ __forceinline__ void reg_fence(float* d) {
#pragma unroll
  for (int i = 0; i < N; i++) asm volatile("" : "+f"(d[i]) :: "memory");
}

__device__ __forceinline__ void mma16(float* d, uint32_t a0, uint32_t a1, uint32_t a2, uint32_t a3, uint32_t b0, uint32_t b1) {
  asm volatile("mma.sync.aligned.m16n8k16.row.col.f32.bf16.bf16.f32 {%0,%1,%2,%3},{%4,%5,%6,%7},{%8,%9},{%0,%1,%2,%3};"
               : "+f"(d[0]), "+f"(d[1]), "+f"(d[2]), "+f"(d[3]) : "r"(a0), "r"(a1), "r"(a2), "r"(a3), "r"(b0), "r"(b1)); }
__device__ __forceinline__ void mma8(float* d, uint32_t a0, uint32_t a1, uint32_t b0) {
  asm volatile("mma.sync.aligned.m16n8k8.row.col.f32.bf16.bf16.f32 {%0,%1,%2,%3},{%4,%5},{%6},{%0,%1,%2,%3};"
               : "+f"(d[0]), "+f"(d[1]), "+f"(d[2]), "+f"(d[3]) : "r"(a0), "r"(a1), "r"(b0)); }
__device__ __forceinline__ void ldsm4(uint32_t* r, uint32_t a) {
  asm volatile("ldmatrix.sync.aligned.m8n8.x4.shared.b16 {%0,%1,%2,%3},[%4];" : "=r"(r[0]), "=r"(r[1]), "=r"(r[2]), "=r"(r[3]) : "r"(a) : "memory"); }
__device__ __forceinline__ void ldsm4t(uint32_t* r, uint32_t a) {
  asm volatile("ldmatrix.sync.aligned.m8n8.x4.trans.shared.b16 {%0,%1,%2,%3},[%4];" : "=r"(r[0]), "=r"(r[1]), "=r"(r[2]), "=r"(r[3]) : "r"(a) : "memory"); }
__device__ __forceinline__ void ldsm2(uint32_t* r, uint32_t a) {
  asm volatile("ldmatrix.sync.aligned.m8n8.x2.shared.b16 {%0,%1},[%2];" : "=r"(r[0]), "=r"(r[1]) : "r"(a) : "memory"); }
__device__ __forceinline__ void stsm4(uint32_t a, uint32_t r0, uint32_t r1, uint32_t r2, uint32_t r3) {
  asm volatile("stmatrix.sync.aligned.m8n8.x4.shared.b16 [%0], {%1,%2,%3,%4};" :: "r"(a), "r"(r0), "r"(r1), "r"(r2), "r"(r3) : "memory"); }
__device__ __forceinline__ void stsm2t(uint32_t a, uint32_t r0, uint32_t r1) {
  asm volatile("stmatrix.sync.aligned.m8n8.x2.trans.shared.b16 [%0], {%1,%2};" :: "r"(a), "r"(r0), "r"(r1) : "memory"); }
__device__ __forceinline__ void stsm4t(uint32_t a, uint32_t r0, uint32_t r1, uint32_t r2, uint32_t r3) {
  asm volatile("stmatrix.sync.aligned.m8n8.x4.trans.shared.b16 [%0], {%1,%2,%3,%4};" :: "r"(a), "r"(r0), "r"(r1), "r"(r2), "r"(r3) : "memory"); }
__device__ __forceinline__ void st_async128(uint32_t a, uint4 v, uint32_t bar) {
  asm volatile("st.async.shared::cluster.mbarrier::complete_tx::bytes.v4.b32 [%0], {%1,%2,%3,%4}, [%5];" :: "r"(a), "r"(v.x), "r"(v.y), "r"(v.z), "r"(v.w), "r"(bar) : "memory"); }
__device__ __forceinline__ void sts32(uint32_t a, uint32_t v) { asm volatile("st.shared.b32 [%0], %1;" :: "r"(a), "r"(v) : "memory"); }
__device__ __forceinline__ void sts64f(uint32_t a, float x, float y) { asm volatile("st.shared.v2.f32 [%0], {%1,%2};" :: "r"(a), "f"(x), "f"(y) : "memory"); }
__device__ __forceinline__ void sts128(uint32_t a, uint4 v) {
  asm volatile("st.shared.v4.b32 [%0], {%1,%2,%3,%4};" :: "r"(a), "r"(v.x), "r"(v.y), "r"(v.z), "r"(v.w) : "memory"); }
__device__ __forceinline__ void sts128f(uint32_t a, float x, float y, float z, float w) {
  asm volatile("st.shared.v4.f32 [%0], {%1,%2,%3,%4};" :: "r"(a), "f"(x), "f"(y), "f"(z), "f"(w) : "memory"); }
__device__ __forceinline__ float lds32f(uint32_t a) { float v; asm volatile("ld.shared.f32 %0, [%1];" : "=f"(v) : "r"(a) : "memory"); return v; }
__device__ __forceinline__ float2 lds64f(uint32_t a) { float2 v; asm volatile("ld.shared.v2.f32 {%0,%1}, [%2];" : "=f"(v.x), "=f"(v.y) : "r"(a) : "memory"); return v; }
__device__ __forceinline__ float4 lds128f(uint32_t a) {
  float4 v; asm volatile("ld.shared.v4.f32 {%0,%1,%2,%3}, [%4];" : "=f"(v.x), "=f"(v.y), "=f"(v.z), "=f"(v.w) : "r"(a) : "memory"); return v; }
__device__ __forceinline__ uint4 lds128(uint32_t a) {
  uint4 v; asm volatile("ld.shared.v4.b32 {%0,%1,%2,%3}, [%4];" : "=r"(v.x), "=r"(v.y), "=r"(v.z), "=r"(v.w) : "r"(a) : "memory"); return v; }
__device__ __forceinline__ uint4 ldg_strong128(const void* p) {
  uint4 v; asm volatile("ld.relaxed.gpu.global.v4.u32 {%0,%1,%2,%3}, [%4];" : "=r"(v.x), "=r"(v.y), "=r"(v.z), "=r"(v.w) : "l"(p) : "memory"); return v; }
__device__ __forceinline__ void stg_strong32(void* p, uint32_t v) { asm volatile("st.relaxed.gpu.global.u32 [%0], %1;" :: "l"(p), "r"(v) : "memory"); }
__device__ __forceinline__ void stg_strong16(void* p, uint32_t v) { asm volatile("st.relaxed.gpu.global.u16 [%0], %1;" :: "l"(p), "h"((uint16_t)v) : "memory"); }
__device__ __forceinline__ void stg_strong128(void* p, uint4 v) {
  asm volatile("st.relaxed.gpu.global.v4.u32 [%0], {%1,%2,%3,%4};" :: "l"(p), "r"(v.x), "r"(v.y), "r"(v.z), "r"(v.w) : "memory"); }
__device__ __forceinline__ uint32_t mapa(uint32_t a, uint32_t r) {
  uint32_t o; asm("mapa.shared::cluster.u32 %0, %1, %2;" : "=r"(o) : "r"(a), "r"(r)); return o; }
__device__ __forceinline__ void st_async2f(uint32_t a, float x, float y, uint32_t bar) {
  asm volatile("st.async.shared::cluster.mbarrier::complete_tx::bytes.v2.f32 [%0], {%1,%2}, [%3];" :: "r"(a), "f"(x), "f"(y), "r"(bar) : "memory"); }
__device__ __forceinline__ void st_async32(uint32_t a, uint32_t x, uint32_t bar) {
  asm volatile("st.async.shared::cluster.mbarrier::complete_tx::bytes.b32 [%0], %1, [%2];" :: "r"(a), "r"(x), "r"(bar) : "memory"); }
__device__ __forceinline__ uint32_t lds32(uint32_t a) { uint32_t v; asm volatile("ld.shared.b32 %0, [%1];" : "=r"(v) : "r"(a) : "memory"); return v; }
__device__ __forceinline__ void st_async64(uint32_t a, uint32_t x, uint32_t y, uint32_t bar) {
  asm volatile("st.async.shared::cluster.mbarrier::complete_tx::bytes.v2.b32 [%0], {%1,%2}, [%3];" :: "r"(a), "r"(x), "r"(y), "r"(bar) : "memory"); }
__device__ __forceinline__ uint2 lds64(uint32_t a) { uint2 v; asm volatile("ld.shared.v2.b32 {%0,%1}, [%2];" : "=r"(v.x), "=r"(v.y) : "r"(a) : "memory"); return v; }
__device__ __forceinline__ void sts64(uint32_t a, uint32_t x, uint32_t y) { asm volatile("st.shared.v2.b32 [%0], {%1,%2};" :: "r"(a), "r"(x), "r"(y) : "memory"); }
__device__ __forceinline__ uint32_t ldg_strong32(const void* p) { uint32_t v; asm volatile("ld.relaxed.gpu.global.u32 %0, [%1];" : "=r"(v) : "l"(p) : "memory"); return v; }
__device__ __forceinline__ uint32_t transpose8(uint32_t x) { uint32_t r; asm volatile("movmatrix.sync.aligned.m8n8.trans.b16 %0, %1;" : "=r"(r) : "r"(x)); return r; }
__device__ __forceinline__ uint32_t hadd2(uint32_t a, uint32_t b) { uint32_t r; asm("add.rn.bf16x2 %0, %1, %2;" : "=r"(r) : "r"(a), "r"(b)); return r; }
__device__ __forceinline__ uint32_t min4(uint4 v) { return min(__vimin3_u32(v.x, v.y, v.z), v.w); }

__device__ __forceinline__ void wg_ss192_01(float* d, uint64_t da, uint64_t db, int sd) {
  asm volatile("{.reg .pred p; setp.ne.b32 p, %98, 0;\n"
    "wgmma.mma_async.sync.aligned.m64n192k16.f32.bf16.bf16 {%0,%1,%2,%3,%4,%5,%6,%7,%8,%9,%10,%11,%12,%13,%14,%15,%16,%17,%18,%19,%20,%21,%22,%23,%24,%25,%26,%27,%28,%29,%30,%31,%32,%33,%34,%35,%36,%37,%38,%39,%40,%41,%42,%43,%44,%45,%46,%47,%48,%49,%50,%51,%52,%53,%54,%55,%56,%57,%58,%59,%60,%61,%62,%63,%64,%65,%66,%67,%68,%69,%70,%71,%72,%73,%74,%75,%76,%77,%78,%79,%80,%81,%82,%83,%84,%85,%86,%87,%88,%89,%90,%91,%92,%93,%94,%95}, %96, %97, p, 1, 1, 0, 1;}"
    : "+f"(d[0]),"+f"(d[1]),"+f"(d[2]),"+f"(d[3]),"+f"(d[4]),"+f"(d[5]),"+f"(d[6]),"+f"(d[7]),"+f"(d[8]),"+f"(d[9]),"+f"(d[10]),"+f"(d[11]),"+f"(d[12]),"+f"(d[13]),"+f"(d[14]),"+f"(d[15]),"+f"(d[16]),"+f"(d[17]),"+f"(d[18]),"+f"(d[19]),"+f"(d[20]),"+f"(d[21]),"+f"(d[22]),"+f"(d[23]),"+f"(d[24]),"+f"(d[25]),"+f"(d[26]),"+f"(d[27]),"+f"(d[28]),"+f"(d[29]),"+f"(d[30]),"+f"(d[31]),"+f"(d[32]),"+f"(d[33]),"+f"(d[34]),"+f"(d[35]),"+f"(d[36]),"+f"(d[37]),"+f"(d[38]),"+f"(d[39]),"+f"(d[40]),"+f"(d[41]),"+f"(d[42]),"+f"(d[43]),"+f"(d[44]),"+f"(d[45]),"+f"(d[46]),"+f"(d[47]),"+f"(d[48]),"+f"(d[49]),"+f"(d[50]),"+f"(d[51]),"+f"(d[52]),"+f"(d[53]),"+f"(d[54]),"+f"(d[55]),"+f"(d[56]),"+f"(d[57]),"+f"(d[58]),"+f"(d[59]),"+f"(d[60]),"+f"(d[61]),"+f"(d[62]),"+f"(d[63]),"+f"(d[64]),"+f"(d[65]),"+f"(d[66]),"+f"(d[67]),"+f"(d[68]),"+f"(d[69]),"+f"(d[70]),"+f"(d[71]),"+f"(d[72]),"+f"(d[73]),"+f"(d[74]),"+f"(d[75]),"+f"(d[76]),"+f"(d[77]),"+f"(d[78]),"+f"(d[79]),"+f"(d[80]),"+f"(d[81]),"+f"(d[82]),"+f"(d[83]),"+f"(d[84]),"+f"(d[85]),"+f"(d[86]),"+f"(d[87]),"+f"(d[88]),"+f"(d[89]),"+f"(d[90]),"+f"(d[91]),"+f"(d[92]),"+f"(d[93]),"+f"(d[94]),"+f"(d[95])
    : "l"(da), "l"(db), "r"(sd));
}
__device__ __forceinline__ void wg_ss128_01(float* d, uint64_t da, uint64_t db, int sd) {
  asm volatile("{.reg .pred p; setp.ne.b32 p, %66, 0;\n"
    "wgmma.mma_async.sync.aligned.m64n128k16.f32.bf16.bf16 {%0,%1,%2,%3,%4,%5,%6,%7,%8,%9,%10,%11,%12,%13,%14,%15,%16,%17,%18,%19,%20,%21,%22,%23,%24,%25,%26,%27,%28,%29,%30,%31,%32,%33,%34,%35,%36,%37,%38,%39,%40,%41,%42,%43,%44,%45,%46,%47,%48,%49,%50,%51,%52,%53,%54,%55,%56,%57,%58,%59,%60,%61,%62,%63}, %64, %65, p, 1, 1, 0, 1;}"
    : "+f"(d[0]),"+f"(d[1]),"+f"(d[2]),"+f"(d[3]),"+f"(d[4]),"+f"(d[5]),"+f"(d[6]),"+f"(d[7]),"+f"(d[8]),"+f"(d[9]),"+f"(d[10]),"+f"(d[11]),"+f"(d[12]),"+f"(d[13]),"+f"(d[14]),"+f"(d[15]),"+f"(d[16]),"+f"(d[17]),"+f"(d[18]),"+f"(d[19]),"+f"(d[20]),"+f"(d[21]),"+f"(d[22]),"+f"(d[23]),"+f"(d[24]),"+f"(d[25]),"+f"(d[26]),"+f"(d[27]),"+f"(d[28]),"+f"(d[29]),"+f"(d[30]),"+f"(d[31]),"+f"(d[32]),"+f"(d[33]),"+f"(d[34]),"+f"(d[35]),"+f"(d[36]),"+f"(d[37]),"+f"(d[38]),"+f"(d[39]),"+f"(d[40]),"+f"(d[41]),"+f"(d[42]),"+f"(d[43]),"+f"(d[44]),"+f"(d[45]),"+f"(d[46]),"+f"(d[47]),"+f"(d[48]),"+f"(d[49]),"+f"(d[50]),"+f"(d[51]),"+f"(d[52]),"+f"(d[53]),"+f"(d[54]),"+f"(d[55]),"+f"(d[56]),"+f"(d[57]),"+f"(d[58]),"+f"(d[59]),"+f"(d[60]),"+f"(d[61]),"+f"(d[62]),"+f"(d[63])
    : "l"(da), "l"(db), "r"(sd));
}
__device__ __forceinline__ void wg_ss160_01(float* d, uint64_t da, uint64_t db, int sd) {
  asm volatile("{.reg .pred p; setp.ne.b32 p, %82, 0;\n"
    "wgmma.mma_async.sync.aligned.m64n160k16.f32.bf16.bf16 {%0,%1,%2,%3,%4,%5,%6,%7,%8,%9,%10,%11,%12,%13,%14,%15,%16,%17,%18,%19,%20,%21,%22,%23,%24,%25,%26,%27,%28,%29,%30,%31,%32,%33,%34,%35,%36,%37,%38,%39,%40,%41,%42,%43,%44,%45,%46,%47,%48,%49,%50,%51,%52,%53,%54,%55,%56,%57,%58,%59,%60,%61,%62,%63,%64,%65,%66,%67,%68,%69,%70,%71,%72,%73,%74,%75,%76,%77,%78,%79}, %80, %81, p, 1, 1, 0, 1;}"
    : "+f"(d[0]),"+f"(d[1]),"+f"(d[2]),"+f"(d[3]),"+f"(d[4]),"+f"(d[5]),"+f"(d[6]),"+f"(d[7]),"+f"(d[8]),"+f"(d[9]),"+f"(d[10]),"+f"(d[11]),"+f"(d[12]),"+f"(d[13]),"+f"(d[14]),"+f"(d[15]),"+f"(d[16]),"+f"(d[17]),"+f"(d[18]),"+f"(d[19]),"+f"(d[20]),"+f"(d[21]),"+f"(d[22]),"+f"(d[23]),"+f"(d[24]),"+f"(d[25]),"+f"(d[26]),"+f"(d[27]),"+f"(d[28]),"+f"(d[29]),"+f"(d[30]),"+f"(d[31]),"+f"(d[32]),"+f"(d[33]),"+f"(d[34]),"+f"(d[35]),"+f"(d[36]),"+f"(d[37]),"+f"(d[38]),"+f"(d[39]),"+f"(d[40]),"+f"(d[41]),"+f"(d[42]),"+f"(d[43]),"+f"(d[44]),"+f"(d[45]),"+f"(d[46]),"+f"(d[47]),"+f"(d[48]),"+f"(d[49]),"+f"(d[50]),"+f"(d[51]),"+f"(d[52]),"+f"(d[53]),"+f"(d[54]),"+f"(d[55]),"+f"(d[56]),"+f"(d[57]),"+f"(d[58]),"+f"(d[59]),"+f"(d[60]),"+f"(d[61]),"+f"(d[62]),"+f"(d[63]),"+f"(d[64]),"+f"(d[65]),"+f"(d[66]),"+f"(d[67]),"+f"(d[68]),"+f"(d[69]),"+f"(d[70]),"+f"(d[71]),"+f"(d[72]),"+f"(d[73]),"+f"(d[74]),"+f"(d[75]),"+f"(d[76]),"+f"(d[77]),"+f"(d[78]),"+f"(d[79])
    : "l"(da), "l"(db), "r"(sd));
}
__device__ __forceinline__ void wg_ss80_01(float* d, uint64_t da, uint64_t db, int sd) {
  asm volatile("{.reg .pred p; setp.ne.b32 p, %42, 0;\n"
    "wgmma.mma_async.sync.aligned.m64n80k16.f32.bf16.bf16 {%0,%1,%2,%3,%4,%5,%6,%7,%8,%9,%10,%11,%12,%13,%14,%15,%16,%17,%18,%19,%20,%21,%22,%23,%24,%25,%26,%27,%28,%29,%30,%31,%32,%33,%34,%35,%36,%37,%38,%39}, %40, %41, p, 1, 1, 0, 1;}"
    : "+f"(d[0]),"+f"(d[1]),"+f"(d[2]),"+f"(d[3]),"+f"(d[4]),"+f"(d[5]),"+f"(d[6]),"+f"(d[7]),"+f"(d[8]),"+f"(d[9]),"+f"(d[10]),"+f"(d[11]),"+f"(d[12]),"+f"(d[13]),"+f"(d[14]),"+f"(d[15]),"+f"(d[16]),"+f"(d[17]),"+f"(d[18]),"+f"(d[19]),"+f"(d[20]),"+f"(d[21]),"+f"(d[22]),"+f"(d[23]),"+f"(d[24]),"+f"(d[25]),"+f"(d[26]),"+f"(d[27]),"+f"(d[28]),"+f"(d[29]),"+f"(d[30]),"+f"(d[31]),"+f"(d[32]),"+f"(d[33]),"+f"(d[34]),"+f"(d[35]),"+f"(d[36]),"+f"(d[37]),"+f"(d[38]),"+f"(d[39])
    : "l"(da), "l"(db), "r"(sd));
}
__device__ __forceinline__ void wg_rs32_00(float* d, uint32_t a0, uint32_t a1, uint32_t a2, uint32_t a3, uint64_t db, int sd) {
  asm volatile("{.reg .pred p; setp.ne.b32 p, %21, 0;\n"
    "wgmma.mma_async.sync.aligned.m64n32k16.f32.bf16.bf16 {%0,%1,%2,%3,%4,%5,%6,%7,%8,%9,%10,%11,%12,%13,%14,%15}, {%16,%17,%18,%19}, %20, p, 1, 1, 0;}"
    : "+f"(d[0]),"+f"(d[1]),"+f"(d[2]),"+f"(d[3]),"+f"(d[4]),"+f"(d[5]),"+f"(d[6]),"+f"(d[7]),"+f"(d[8]),"+f"(d[9]),"+f"(d[10]),"+f"(d[11]),"+f"(d[12]),"+f"(d[13]),"+f"(d[14]),"+f"(d[15])
    : "r"(a0), "r"(a1), "r"(a2), "r"(a3), "l"(db), "r"(sd));
}
__device__ __forceinline__ void wg_rs64_00(float* d, uint32_t a0, uint32_t a1, uint32_t a2, uint32_t a3, uint64_t db, int sd) {
  asm volatile("{.reg .pred p; setp.ne.b32 p, %37, 0;\n"
    "wgmma.mma_async.sync.aligned.m64n64k16.f32.bf16.bf16 {%0,%1,%2,%3,%4,%5,%6,%7,%8,%9,%10,%11,%12,%13,%14,%15,%16,%17,%18,%19,%20,%21,%22,%23,%24,%25,%26,%27,%28,%29,%30,%31}, {%32,%33,%34,%35}, %36, p, 1, 1, 0;}"
    : "+f"(d[0]),"+f"(d[1]),"+f"(d[2]),"+f"(d[3]),"+f"(d[4]),"+f"(d[5]),"+f"(d[6]),"+f"(d[7]),"+f"(d[8]),"+f"(d[9]),"+f"(d[10]),"+f"(d[11]),"+f"(d[12]),"+f"(d[13]),"+f"(d[14]),"+f"(d[15]),"+f"(d[16]),"+f"(d[17]),"+f"(d[18]),"+f"(d[19]),"+f"(d[20]),"+f"(d[21]),"+f"(d[22]),"+f"(d[23]),"+f"(d[24]),"+f"(d[25]),"+f"(d[26]),"+f"(d[27]),"+f"(d[28]),"+f"(d[29]),"+f"(d[30]),"+f"(d[31])
    : "r"(a0), "r"(a1), "r"(a2), "r"(a3), "l"(db), "r"(sd));
}
__device__ __forceinline__ void wg_rs24_01(float* d, uint32_t a0, uint32_t a1, uint32_t a2, uint32_t a3, uint64_t db, int sd) {
  asm volatile("{.reg .pred p; setp.ne.b32 p, %17, 0;\n"
    "wgmma.mma_async.sync.aligned.m64n24k16.f32.bf16.bf16 {%0,%1,%2,%3,%4,%5,%6,%7,%8,%9,%10,%11}, {%12,%13,%14,%15}, %16, p, 1, 1, 1;}"
    : "+f"(d[0]),"+f"(d[1]),"+f"(d[2]),"+f"(d[3]),"+f"(d[4]),"+f"(d[5]),"+f"(d[6]),"+f"(d[7]),"+f"(d[8]),"+f"(d[9]),"+f"(d[10]),"+f"(d[11])
    : "r"(a0), "r"(a1), "r"(a2), "r"(a3), "l"(db), "r"(sd));
}

#define AB_POLY 0xae
__device__ __forceinline__ constexpr bool poly_group(int group) { return (AB_POLY >> (group & 7)) & 1; }

template <int V> struct Int { static constexpr int value = V; };

template <int NG>
__device__ __forceinline__ void ln_stats(const float4 (&v)[NG][5], uint32_t scratch, float (&mean)[NG], float (&rs)[NG]) {
  const int warp = threadIdx.x >> 5, lane = threadIdx.x & 31;
#pragma unroll
  for (int r = 0; r < NG; r++) {
    float s = 0.f, q = 0.f;
#pragma unroll
    for (int i = 0; i < 5; i++) s += (v[r][i].x + v[r][i].y) + (v[r][i].z + v[r][i].w);
    s += __shfl_xor_sync(~0u, s, 1); s += __shfl_xor_sync(~0u, s, 2);
    s *= 1.f / 80;
#pragma unroll
    for (int i = 0; i < 5; i++) {
      const float x = v[r][i].x - s, y = v[r][i].y - s, z = v[r][i].z - s, w = v[r][i].w - s;
      q += (x * x + y * y) + (z * z + w * w);
    }
    q += __shfl_xor_sync(~0u, q, 1); q += __shfl_xor_sync(~0u, q, 2);
    mean[r] = s; rs[r] = q;
  }
  bar_sync(1, 256);
  if ((lane & 3) == 0) {
#pragma unroll
    for (int r = 0; r < NG; r++) sts64f(scratch + r * 512 + lane * 16 + warp * 8, mean[r], rs[r]);
  }
  bar_sync(1, 256);
#pragma unroll
  for (int r = 0; r < NG; r++) {
    const float4 e = lds128f(scratch + r * 512 + lane * 16);
    float t = e.x + e.z;
    t += __shfl_xor_sync(~0u, t, 1); t += __shfl_xor_sync(~0u, t, 2);
    t *= 0.125f;
    float q = e.y + e.w + 80.f * ((e.x - t) * (e.x - t) + (e.z - t) * (e.z - t));
    q += __shfl_xor_sync(~0u, q, 1); q += __shfl_xor_sync(~0u, q, 2);
    mean[r] = t; rs[r] = rsqrtf(q * (1.f / DM) + 1e-5f);
  }
}

__device__ __forceinline__ void ln_store(const uint32_t (&w)[2][5][2], int tile, int u0, bool live = true) {
  const int lane = threadIdx.x & 31;
  uint32_t* xc = g_xc + ((tile >> 1) * 40 + u0) * 256 + (tile & 1) * 64 + lane;
#pragma unroll
  for (int i = 0; i < 20; i++) if (live) xc[(i >> 1) * 128 + (i & 1) * 32] = w[i & 1][i >> 2][i >> 1 & 1];
#pragma unroll
  for (int i = 0; i < 5; i++) {
    const int u = u0 + i;
    uint32_t* xn = g_xn + (((tile >> 3) * 20 + (u >> 1)) * 16 + (tile & 1) * 8 + (tile & 6)) * 128 + (u & 1) * 64 + lane;
#pragma unroll
    for (int r = 0; r < 2; r++) if (live) { xn[r * 128] = w[r][i][0]; xn[r * 128 + 32] = w[r][i][1]; }
  }
}
__device__ __forceinline__ void wait_count(const uint32_t* c, uint32_t n) {
  int spin = 0;
  while ((ld_acquire(c) & 0xffff) < n) { __nanosleep(32); spin_guard(spin); }
}

__device__ __forceinline__ uint8_t* pool_at(uint32_t off) {
  return reinterpret_cast<uint8_t*>((reinterpret_cast<uintptr_t>(g_pool) + 8191) & ~(uintptr_t)8191) + off; }
struct Weights { const uint8_t* w[4]; };
__device__ __forceinline__ void prefetch_weights(const Weights& p, int i) {
  if (blockIdx.x < 128) asm volatile("cp.async.bulk.prefetch.L2.global [%0], 61440;" :: "l"(p.w[i] + (size_t)blockIdx.x * 61440) : "memory");
}
__global__ void __launch_bounds__(384) first_kernel(const __nv_bfloat16* __restrict__ xin, const uint4* __restrict__ wb, const __grid_constant__ Weights wa) {
  __shared__ __align__(16) float scratch[256];
  __shared__ uint32_t lat[4];
  const int warp = threadIdx.x >> 5, lane = threadIdx.x & 31, cta = blockIdx.x;
  TRACE(0);
  pdl_launch();
  if (warp >= 8) {
    if (warp < 10 || cta < NSLOT) {
      uint32_t* q = reinterpret_cast<uint32_t*>(pool_at((warp < 10 ? NSLOT : cta) * 8192 + (warp & 1) * 4096)) + (warp < 10 ? (cta & 127) * 8 : 0);
      if (lane < 8) stg_strong32(q + lane, 0u);
      uint32_t best = ~0u;
      if (lane == 0) {
        for (int r = 0; r < FK_REP; r++) {
          uint32_t t0, t1, v;
          asm volatile("mov.u32 %0, %%clock;" : "=r"(t0) :: "memory");
          asm volatile("atom.relaxed.gpu.global.exch.b32 %0, [%1], 0;" : "=r"(v) : "l"(q) : "memory");
          asm volatile("{.reg .u32 t; add.u32 t, %1, 1; mov.u32 %0, %%clock; sub.u32 %0, %0, %1;}" : "=r"(t1) : "r"(__shfl_sync(1u, v, 0)) : "memory");
          best = min(best, t1 - t0);
        }
        lat[warp - 8] = best;
      }
    }
    __syncwarp();
    bar_sync(2, cta < 128 ? 384 : 128);
    if (threadIdx.x == 288) for (int i = 0; i < FK_PF; i++) prefetch_weights(wa, i);
    if (threadIdx.x == 256) {
      const int part = lat[0] < lat[1] ? 0 : 1;
      uint32_t smid; asm("mov.u32 %0, %%smid;" : "=r"(smid));
      g_smpart[smid & 255] = part;
      g_smclk[smid & 255] = clk32() - gtime() * 2;
      g_smuse[smid & 255] = 0;
      if (cta < NSLOT) g_orient[cta] = lat[2] < lat[3] ? part : 1 - part;
    }
  } else if (cta < 128) {
    float4 v[2][5];
#pragma unroll
    for (int r = 0; r < 2; r++)
#pragma unroll
      for (int i = 0; i < 5; i++) {
        const uint32_t* src = reinterpret_cast<const uint32_t*>(xin) + (cta * 16 + r * 8 + (lane >> 2)) * (DM / 2) + warp * 40 + i * 8 + (lane & 3);
        const uint32_t a = src[0], b = src[4];
        v[r][i] = make_float4(bf_lo(a), bf_hi(a), bf_lo(b), bf_hi(b));
      }
    uint4 w8[2];
#pragma unroll
    for (int i = 0; i < 2; i++) w8[i] = wb[cta * 400 + min(i * 256 + threadIdx.x, 399)];
    float mean[2], rs[2];
    ln_stats<2>(v, s2u(scratch), mean, rs);
    bar_sync(2, 384);
    ABT(2, 2);
    if (threadIdx.x < 128) g_stat[cta * 128 + threadIdx.x] = make_float2(0.f, 0.f);
#pragma unroll
    for (int i = 0; i < 10; i++) g_x[((cta * 2 + i / 5) * 40 + warp * 5 + i % 5) * 32 + lane] = pack4(v[i / 5][i % 5]);
    uint32_t w[2][5][2];
#pragma unroll
    for (int i = 0; i < 10; i++) {
      const float4 t = v[i / 5][i % 5];
      const float m = mean[i / 5], q = rs[i / 5];
      w[i / 5][i % 5][0] = pack2((t.x - m) * q, (t.y - m) * q); w[i / 5][i % 5][1] = pack2((t.z - m) * q, (t.w - m) * q);
    }
    ln_store(w, cta, warp * 5);
    ABT(2, 3);
#pragma unroll
    for (int i = 0; i < 2; i++) {
      const int e = cta * 400 + min(i * 256 + threadIdx.x, 399), k = e / 80, n = e - k * 80, cg = n / 10;
      g_wb[((cg * 80 + (k >> 3)) * 10 + n - cg * 10) * 8 + (k & 7)] = w8[i];
    }
  } else if (cta == 128) {
    g_bo[threadIdx.x] = 0;
  }
  TRACE(2);
}

struct ChainParams {
  CUtensorMap wq, wk, wv, wo;
  const __nv_bfloat16* mem0;
  uint8_t *pool, *kv;
  const uint32_t* xc;
  uint32_t* sync;
  int layer;
  int d0, d3, d1, d1b, d2, d2b, mode;
};
constexpr int CH_WQ = 0, CH_WO = 81920, CH_X = CH_WO + 86016, CH_M = CH_X + 20480, CH_KT = CH_X + 40960, CH_VT = CH_KT + 4096,
              CH_PS = CH_VT + 4096, CH_QK = CH_PS + 4096, CH_VP = CH_QK + 4096, CH_SX = CH_VP + 1024, CH_O = CH_SX + 2304, CH_ID = CH_O + 3072,
              CH_BAR = CH_ID + 512;
constexpr int CH_SMEM = CH_BAR + 256;
constexpr int CH_BASE = 1024;
#define CH_VK0 8
#define CH_VK1 20
#define CH_L0 4
#define CH_LR 4
#define NOX 0
#define CH_XA 1
#define CH_XB 4
#define CH_W1 3
#define CH_W2 17
#define CH_W3 26
#define CH_R2 8
#define CH_VA 16
#define CH_EX 2
#define CH_KD 0
#define CH_RP 1
#define CH_KF 10
#define CH_LO 0
#define CH_LR1 4
#define CH_KP 0
#define CH_KM 0
#define CH_SP 1
#define CH_VC 2
#define CH_KW 3
#define CH_RB 0
#define CH_RC 8
#define CH_D0 200
#define CH_D1 450
#define CH_D2 300
#define CH_R1 4
#define CH_TW 12
__device__ __forceinline__ uint32_t opaque(uint32_t x) { return __shfl_sync(~0u, x, threadIdx.x & 31); }
__device__ __forceinline__ uint32_t nz(uint32_t x) { uint32_t r; asm("max.u32 %0, %1, 1;" : "=r"(r) : "r"(x)); return r; }
__device__ __forceinline__ uint32_t pack_tag(float lo, float hi, uint32_t tag, uint32_t mask) {
  uint32_t r;
  asm("lop3.b32 %0, %1, %2, %3, 0xD8;" : "=r"(r) : "r"(pack2(lo, hi)), "r"(tag), "r"(mask));
  return r;
}
__device__ __forceinline__ uint32_t differ(uint32_t a, uint32_t b, uint32_t t) { uint32_t r; asm("lop3.b32 %0, %1, %2, %3, 0x7E;" : "=r"(r) : "r"(a), "r"(b), "r"(t)); return r; }
__device__ __forceinline__ void mbar_wait_hot(uint32_t bar, uint32_t ph) {
  uint32_t ok;
  asm volatile("{.reg .pred p; mbarrier.try_wait.parity.shared::cta.b64 p, [%1], %2; selp.u32 %0, 1, 0, p;}" : "=r"(ok) : "r"(bar), "r"(ph) : "memory");
  if (__builtin_expect(!ok, 0)) mbar_wait(bar, ph);
}
__device__ __forceinline__ bool elect() {
  uint32_t r; asm volatile("{.reg .pred p; elect.sync _|p, 0xffffffff; selp.u32 %0, 1, 0, p;}" : "=r"(r)); return r; }
__device__ __forceinline__ uint32_t or3(uint32_t a, uint32_t b, uint32_t c) { uint32_t r; asm("lop3.b32 %0, %1, %2, %3, 0xFE;" : "=r"(r) : "r"(a), "r"(b), "r"(c)); return r; }
__device__ __forceinline__ void pin() { pdl_launch(); }
__device__ __forceinline__ void mma16h(float* d, uint32_t a0, uint32_t a2, uint32_t b0, uint32_t b1) {
  asm volatile("{.reg .b32 u, v; mma.sync.aligned.m16n8k16.row.col.f32.bf16.bf16.f32 {%0,%1,%2,%3},{%4,u,%5,v},{%6,%7},{%0,%1,%2,%3};}"
               : "+f"(d[0]), "+f"(d[1]), "+f"(d[2]), "+f"(d[3]) : "r"(a0), "r"(a2), "r"(b0), "r"(b1)); }
__device__ __forceinline__ void mma8h(float* d, uint32_t a0, uint32_t b0) {
  asm volatile("{.reg .b32 u; mma.sync.aligned.m16n8k8.row.col.f32.bf16.bf16.f32 {%0,%1,%2,%3},{%4,u},{%5},{%0,%1,%2,%3};}"
               : "+f"(d[0]), "+f"(d[1]), "+f"(d[2]), "+f"(d[3]) : "r"(a0), "r"(b0)); }
__device__ __forceinline__ uint32_t absmax2(uint32_t a, uint32_t b) { uint32_t r; asm("max.xorsign.abs.bf16x2 %0, %1, %2;" : "=r"(r) : "r"(a), "r"(b)); return r; }
__device__ __forceinline__ void until(uint32_t t) { while ((int)(clk32() - t) < 0) {} }
__device__ __forceinline__ uint4 pack8(const float* d) { return make_uint4(pack2(d[0], d[1]), pack2(d[2], d[3]), pack2(d[4], d[5]), pack2(d[6], d[7])); }
__device__ __forceinline__ void add8(float* d, uint4 v) {
  d[0] += bf_lo(v.x); d[1] += bf_hi(v.x); d[2] += bf_lo(v.y); d[3] += bf_hi(v.y);
  d[4] += bf_lo(v.z); d[5] += bf_hi(v.z); d[6] += bf_lo(v.w); d[7] += bf_hi(v.w);
}

template <int WG>
__device__ __forceinline__ void chain_body(const ChainParams& p, const uint32_t wq, const uint32_t (&ak)[80], const uint32_t (&av)[80]) {
  const int tid = threadIdx.x & 127, t4 = __shfl_sync(~0u, tid >> 5, 0), lane = tid & 31;
  const int cta = blockIdx.x, h = cta / 3, j = cta - 3 * h;
  const uint32_t sb = mapa(CH_BASE, j);
  const uint32_t bWo = sb + CH_BAR, bWq = bWo + 8, bX = bWo + 16, bXA = bWo + 24, bXB = bWo + 32, bO = bWo + 40, bG = bWo + 48, bH = bWo + 96;
  uint32_t tw[4 * CH_TW];
  auto refill = [&]() {
#pragma unroll
    for (int k = 0; k < CH_TW; k++) ldsm4t(&tw[4 * k], wq + k * 2048);
  };
  const uint32_t wo = opaque((sb + CH_WO + (WG == 0 ? (t4 + (j == 2)) * 4096 : (j == 2 ? 0 : 24576) + t4 * 1024) + ((lane & 7) + (lane >> 4) * 8) * 64 +
                              ((((lane >> 3) & 1) ^ ((lane >> 1) & 3)) << 4)) ^ (WG == 1 && j == 2 ? 32 : 0));
  const uint32_t wo2 = opaque((wo ^ ((t4 & 1) * 32)) + (4 + (t4 >> 1) - t4) * 4096);
  const uint32_t l16 = opaque(sb + lane * 16);
  const uint32_t l8 = opaque(sb + t4 * 256 + lane * 8);
  const uint32_t lw = opaque(sb + t4 * 1024 + lane * 16);
  const uint32_t qs = opaque(sb + CH_QK + WG * 2048 + t4 * 512 + lane * 16);
  const uint32_t qa = opaque(sb + CH_QK + (lane >> 4) * 2048 + (lane & 15) * 16 + (WG == 0 ? t4 * 512 + 256 : t4 == 3 ? 1024 : 0));
  const uint32_t ka = opaque(t4 < 2 ? sb + CH_KT + t4 * 512 + lane * 16
                                    : sb + CH_QK + 256 + (t4 - 2) * 1024 + ((lane >> 3) & 1) * 2048 + (lane >> 4) * 128 + (lane & 7) * 16);
  const uint32_t l4 = opaque(sb + t4 * 256 + lane * 4);
  uint32_t pdst[1], pages = 0;
  auto line0 = [&](int i) { return 28 * j + (i < 4 ? 4 * t4 + i : 12 + 2 * t4 + i); };
  const uint32_t plane = opaque((lane >> 4) * 2048 + h * 64 + (lane & 15) * 4);
  if (WG == 0) {
    pages = __ballot_sync(~0u, lds32(sb + CH_O + line0(min(lane, 5)) * 4) & 4096);
  } else {
    pages = __ballot_sync(~0u, lds32(sb + CH_O + (80 + min(lane, 11)) * 4) & 4096);
    pdst[0] = opaque(lds32(sb + CH_O + (j == 0 ? 24 + t4 : 50 + 2 * j + (t4 & 1)) * 4) + plane);
  }
  const uint32_t role = lds32(sb + CH_O + NSLOT * 4), rsrc = lds32(sb + CH_O + role * 4), rdst = (80 + role / 20) * 8192 + role % 20 * 128;
  const uint32_t r1 = mapa(CH_BASE, j == 2 ? 0 : j + 1) - sb, r2 = mapa(CH_BASE, j == 0 ? 2 : j - 1) - sb;
  uint32_t tag = opaque(1);
  auto pool = [&](uint32_t off) { return p.pool + ((tag & 0xfffe) + off); };
  auto after = [&](uint32_t x) { return x & tag & 0xfffe; };
  auto kv = [&](int s, uint32_t a) { return p.kv + (a + ((cta * 2 * NSEG + s) * KV_BYTES - sb)); };
  auto pass = [&](float (&d)[16], const uint32_t (&a)[80], auto k0, auto k1) {
    const uint64_t db = mkdesc(CH_BASE + CH_X + WG * 20480, 512, 128, 0);
#pragma unroll
    for (int k = k0.value; k < k1.value; k++) wg_rs32_00(d, a[4 * k], a[4 * k + 1], a[4 * k + 2], a[4 * k + 3], db + k * 64, k);
    wg_commit();
  };
  auto dump = [&](float (&d)[16], uint32_t a) {
    reg_fence<16>(d);
    sts128(a, pack8(d)); sts128(a + 512, pack8(d + 8));
  };
  uint32_t pph = 0;
  auto tokens0 = [&](int s, auto k0) {
    float dk[16], dv[16];
    bar_sync(9, 256);
    wg_fence();
    pass(dk, ak, Int<0>(), Int<4>());
    const uint4 a0 = lds128(lw + CH_KT), a1 = lds128(lw + CH_KT + 512);
    pin();
    pass(dk, ak, Int<4>(), Int<20>());
    pass(dv, av, Int<0>(), Int<CH_VA>());
    pin();
    wg_wait<1>();
    reg_fence<16>(dk);
    add8(dk, a0); add8(dk + 8, a1);
    const uint4 w0 = pack8(dk), w1 = pack8(dk + 8);
    const uint4 b0 = lds128(lw + CH_VT), b1 = lds128(lw + CH_VT + 512);
    stsm4t(lw + CH_KT, w0.x, w0.z, w0.y, w0.w); stsm4t(lw + CH_KT + 512, w1.x, w1.z, w1.y, w1.w);
    if (CH_KP == 2) bar_arrive(7, 160);
    TM1(6);
    pin();
    if (CH_VA < 20) pass(dv, av, Int<CH_VA>(), Int<20>());
    pin();
#pragma unroll
    for (int k = k0.value; k < CH_TW; k++) ldsm4t(&tw[4 * k], wq + k * 2048);
    TM1(9);
    if (k0.value < CH_TW && t4 >= 2) { mbar_wait_hot(bH + t4 * 16 - 24 + (pph & 1) * 8, pph >> 1 & 1); pph++; }
    __syncwarp();
    wg_wait<0>();
    reg_fence<16>(dv);
    add8(dv, b0); add8(dv + 8, b1);
#pragma unroll
    for (int e = 0; e < 2; e++) { const uint4 v = pack8(dv + 8 * e); sts128(lw + CH_VT + e * 512, make_uint4(v.x, v.z, v.y, v.w)); }
  };
  auto publish_k = [&](int s) {
    if (t4 == CH_KW && elect()) { fence_async(); bulk_store(p.kv + (size_t)(cta * 2 * NSEG + s) * KV_BYTES, sb + CH_KT, 4096); bulk_commit(); }
    __syncwarp();
  };
  if (WG == 0) {
    mbar_wait(bXB, 0);
    tokens0(0, Int<CH_TW>());
  } else {
    const uint32_t* m0 = reinterpret_cast<const uint32_t*>(p.mem0) + (lane >> 2) * 320 + t4 * 80 + (lane & 3);
    uint32_t a[20];
#pragma unroll
    for (int i = 0; i < 20; i++) a[i] = m0[4 * i];
    pin();
    float dk[16], dv[16];
    mbar_wait(bXA, 0);
    wg_fence();
    pass(dk, ak, Int<0>(), Int<20>());
    pass(dv, av, Int<0>(), Int<20>());
    wg_wait<0>();
    dump(dk, lw + CH_KT);
    dump(dv, lw + CH_VT);
    bar_sync(9, 256);
    if (CH_KP == 2 && t4 == CH_KW) { bar_sync(7, 160); publish_k(0); }
#pragma unroll
    for (int i = 0; i < 20; i++) sts32(sb + CH_M + (t4 * 20 + i) * 128 + lane * 4, nz(transpose8(a[i])));
    __syncwarp();
    if (elect()) mbar_arrive(bG + t4 * 8);
  }
  PRO(8);
  mbar_wait(bWq, 0);
  refill();
  PRO(9);
  mbar_wait(bWo, 0);
  asm volatile("barrier.cluster.wait.aligned;" ::: "memory");
  PRO(10);
  auto load_x = [&](int s, int k0, int n, uint32_t bar) {
    if (!NOX && elect()) { mbar_expect(bar, n * 1024); bulk_load(sb + CH_X + k0 * 1024, p.xc + (s + 1) * 10240 + k0 * 256, n * 1024, bar); }
  };
  constexpr int VK = WG == 0 ? CH_VK0 : CH_VK1;
  uint32_t gph = 0;
  int st = 0;
  const uint32_t ca = opaque(sb + CH_M + t4 * 2560 + lane * 32 + (lane >> 2) * 4);
  auto project = [&](int s, uint32_t (&b)[40], float (&dv)[16], uint32_t (&kf)[16]) {
    float dq[4] = {}, dk[4] = {};
    uint32_t w[80];
#pragma unroll
    for (int i = 0; i < 4 * CH_TW; i++) w[i] = tw[i];
    constexpr int LR = WG == 1 ? CH_LR1 : CH_LR;
    auto load = [&](int n) {
      int c = 0;
#pragma unroll
      for (int i = 0; i < 10; i++) {
        if (i == CH_KF) {
#pragma unroll
          for (int q = 0; q < 4; q++)
            if (WG == 1 && c++ == n) ldsm4(&kf[4 * q], ka + q * 1024);
        }
        if (c++ == n) ldsm4t(&b[4 * i], l16 + CH_M + WG * 5120 + i * 512);
#pragma unroll
        for (int k = 2 * i; k < 2 * i + 2; k++)
          if (k >= CH_TW && c++ == n) ldsm4t(&w[4 * k], wq + k * 2048);
      }
#pragma unroll
      for (int i = 0; i < 4; i++)
        if (WG == 1 && CH_KF >= 10 && c++ == n) ldsm4(&kf[4 * i], ka + i * 1024);
    };
    if (WG == 1) {
      for (int n = 0;;) {
        mbar_wait(bG + t4 * 8, gph);
        TR(5, (clk32() & ~3u) | min(n, 3));
        gph ^= 1;
        if (__builtin_expect(!__any_sync(~0u, __vimin3_u32(lds32(ca), lds32(ca + 1024), lds32(ca + 1536)) == 0), 1)) break;
        if (elect()) {
          const int q = (st == 0 ? 8 : st * 4 - 4) + t4;
          mbar_expect(bG + t4 * 8, 2560);
          bulk_load(sb + CH_M + t4 * 2560, p.pool + ((80 + q) * 8192 + (pages >> q & 1) * 4096), 2560, bG + t4 * 8);
        }
        spin_guard(n);
      }
    }
    bar_sync(6, 256);
#pragma unroll
    for (int i = 0; i < CH_L0; i++) load(i);
    if (WG == 0 && CH_XB == 4 && s + 1 < NSEG) load_x(s, 5 * t4, 5, bXB);
    TM(0);
    TM1(11);
    if (WG == 1) TR(6, clk32());
#pragma unroll
    for (int k = 0; k < 20; k += 2) {
      if (k > 0) {
#pragma unroll
        for (int n = (k == 18 ? 40 : CH_L0 + k * LR / 4) - 1; n >= CH_L0 + (k - 2) * LR / 4; n--) { load(n); if (CH_LO) __syncwarp(); }
      }
      pin();
#pragma unroll
      for (int kk = k; kk < k + 2; kk++) {
        mma16(dk, ak[4 * kk], ak[4 * kk + 1], ak[4 * kk + 2], ak[4 * kk + 3], b[2 * kk], b[2 * kk + 1]);
        mma16(dq, w[4 * kk], w[4 * kk + 1], w[4 * kk + 2], w[4 * kk + 3], b[2 * kk], b[2 * kk + 1]);
        if (kk < VK) mma16(dv, av[4 * kk], av[4 * kk + 1], av[4 * kk + 2], av[4 * kk + 3], b[2 * kk], b[2 * kk + 1]);
      }
    }
    const float k2 = 0.07216878364870322f * 1.44269504089f;
    stsm4t(qs, pack2(dq[0] * k2, dq[1] * k2), pack2(dq[2] * k2, dq[3] * k2), pack2(dk[0], dk[1]), pack2(dk[2], dk[3]));
    TM(1);
  };
  static_assert(CH_VK1 == 20 && CH_KP == 0 && CH_XA > 0 && CH_XB > 0, "last step");
  constexpr int VC = VK == 20 ? 1 : CH_VC;
  auto finish_v = [&](const uint32_t (&b)[40], float (&dv)[16]) {
#pragma unroll
    for (int kk = VK; kk < 20; kk++) mma16(dv + 4 * ((kk - VK) % VC), av[4 * kk], av[4 * kk + 1], av[4 * kk + 2], av[4 * kk + 3], b[2 * kk], b[2 * kk + 1]);
  };
  auto sum_v = [&](float (&dv)[16]) {
#pragma unroll
    for (int i = 4; i < 4 * VC; i++) dv[i & 3] += dv[i];
  };
  auto publish_km = [&](int s) {
    uint32_t a[4];
    ldsm4(a, qa);
    *reinterpret_cast<uint2*>(kv(s, l8) + KV_M) = make_uint2(hadd2(a[0], a[2]), hadd2(a[1], a[3]));
  };
  auto memory_v = [&](uint2 x, const float (&dv)[16]) {
    return make_uint2(pack2(dv[0] + bf_lo(x.x), dv[1] + bf_hi(x.x)), pack2(dv[2] + bf_lo(x.y), dv[3] + bf_hi(x.y)));
  };
  auto publish_v = [&](int s, const uint4 (&v)[2], uint2 vm) {
#pragma unroll
    for (int e = 0; e < 2; e++) reinterpret_cast<uint4*>(kv(s, lw) + KV_V)[e * 32] = v[e];
    *reinterpret_cast<uint2*>(kv(s, l8) + KV_V + KV_M) = vm;
  };
#pragma unroll 1
  for (int s = 0;; s++) {
    float dv[16] = {};
    uint32_t b[40], kf[16];
    project(s, b, dv, kf);
    if (WG == 0) {
      bar_sync(1, 256);
      if (CH_XA == 0) load_x(s, 20 + 5 * t4, 5, bXA);
      if (CH_XB == 0) load_x(s, 5 * t4, 5, bXB);
      pin();
      finish_v(b, dv);
      sum_v(dv);
      sts64(l8 + CH_VP, pack2(dv[0], dv[1]), pack2(dv[2], dv[3]));
      if (s == NSEG - 1) {
        bar_arrive(10, 256);
        publish_k(s);
        publish_km(s);
        bulk_wait<0>();
        fence_async_global();
        bar_sync(2, 256);
        if (tid == 0) red_release(p.sync + 15 * 8 + 4, 1);
        break;
      }
      bar_arrive(4, 256);
      if (CH_XA == 1) load_x(s, 20 + 5 * t4, 5, bXA);
      if (CH_XB == 1) load_x(s, 5 * t4, 5, bXB);
      uint32_t w[144];
      auto wload = [&](int i) { ldsm4t(&w[4 * i], (i % 3 == 0 ? wo : i % 3 == 1 ? wo ^ 32 : wo2) + i / 12 * 28672 + i / 3 % 4 * 1024); };
      TM(3);
      if (CH_KP == 0) publish_k(s);
#pragma unroll
      for (int i = 0; i < CH_W1; i++) wload(i);
      bar_sync(10, 256);
      uint32_t km[4];
      ldsm4(km, qa);
      pin();
#pragma unroll
      for (int i = CH_W1; i < CH_W2; i++) wload(i);
      pin();
      const uint2 kms = make_uint2(hadd2(km[0], km[2]), hadd2(km[1], km[3]));
      if (CH_KM == 0) *reinterpret_cast<uint2*>(kv(s, l8) + KV_M) = kms;
      if (CH_KP == 0) bulk_wait_read<0>();
      if (CH_XA == 2) load_x(s, 20 + 5 * t4, 5, bXA);
      if (CH_XB == 2) load_x(s, 5 * t4, 5, bXB);
      bar_sync(2, 256);
      {
        float y[3][4] = {};
        uint32_t ob[24];
        ldsm4(&ob[0], l16 + CH_O + 1024); ldsm4(&ob[4], l16 + CH_O + 1536);
        TM(7);
        auto step = [&](int i) {
          const int k = i / 3;
          mma16(y[i % 3], w[4 * i], w[4 * i + 1], w[4 * i + 2], w[4 * i + 3], ob[2 * k], ob[2 * k + 1]);
        };
#pragma unroll
        for (int i = 0; i < 12; i++) {
          step(i);
          if (i >= 12 - (CH_W3 - CH_W2)) wload(CH_W3 - 12 + i);
          if (i % 3 == 2) pin();
        }
        if (CH_XB == 3) load_x(s, 5 * t4, 5, bXB);
        if (CH_KM == 1) *reinterpret_cast<uint2*>(kv(s, l8) + KV_M) = kms;
        pin();
        mbar_wait(bO, s & 1);
        TM(4);
        ldsm4(&ob[8], l16 + CH_O); ldsm4(&ob[12], l16 + CH_O + 512);
        pin();
        float2 inv;
        uint8_t* dst[6];
        uint32_t mask;
#pragma unroll
        for (int i = 12; i < 36; i++) {
          step(i);
          static_assert(CH_W3 == 26, "load order");
          if (i == 14) ldsm4(&ob[16], l16 + after(w[4 * CH_W3 - 1] | w[4 * CH_W3 - 5] | w[4 * CH_W3 - 9] | ob[8]) + CH_O + 2048);
          else if (i == 15) ldsm4(&ob[20], l16 + CH_O + 2560);
          else if (i < 24) wload(i < 14 ? 39 - i : i < 18 ? 45 - i : i < 21 ? 50 - i : 56 - i);
          if (i == 21) inv = lds64f((l8 & ~0xe0u) + CH_VP);
          if (i < 24) __syncwarp();
          if (i == 24) mask = ((l16 ^ tag) & 48) == 0;
          if (i >= 24 && i < 30) dst[i - 24] = pool(line0(i - 24) * 8192 + (pages >> (i - 24) & 1) * 4096) + plane;
          if (i % 3 == 2) pin();
        }
#pragma unroll
        for (int k = 0; k < CH_R1; k++) ldsm4t(&tw[4 * k], wq + k * 2048);
        pin();
#pragma unroll
        for (int i = 0; i < 6; i++) stg_strong32(dst[i], pack_tag(y[i >> 1][2 * (i & 1)] * inv.x, y[i >> 1][2 * (i & 1) + 1] * inv.y, tag, mask));
        TM(8);
        TR(0, clk32());
        bar_arrive(5, 256);
        pin();
      }
      const uint32_t t0 = clk32();
      auto refill2 = [&]() {
#pragma unroll
        for (int k = CH_R1; k < CH_R2; k++) ldsm4t(&tw[4 * k], wq + k * 2048);
      };
      if (CH_RP == 0) refill2();
      const uint32_t ln = (l16 ^ tag) >> 4 & 31;
      if (t4 >= 2) {
        const uint32_t bP = bH + t4 * 16 - 24, ps = CH_PS + (t4 & 1) * 4096;
        auto fetch = [&](uint32_t k) {
          if (elect()) { mbar_expect(bP + (k & 1) * 8, 2048); bulk_load(sb + ps + (k & 1) * 2048, p.pool + (rsrc + (t4 & 1) * 2048), 2048, bP + (k & 1) * 8); }
        };
        until(t0 + CH_D0);
        fetch(pph);
        if (CH_RP == 2) refill2();
        if (!NOX) mbar_wait_hot(bXB, (s + 1) & 1);
        const uint32_t want = (tag & 1) * 0x10001, chk = opaque(ln < 4 ? 0x10001 : 0);
        uint4 sel;
        sel.x = opaque((ln >> 3) != (ln & 1) ? 0 : ln & 4 ? 0x3f800000u : 0x00003f80u);
        sel.z = opaque(sel.x); sel.y = opaque(ln); sel.w = opaque(ln + 1);
        uint8_t* mdst = p.pool + opaque(st * 32768 + rdst + (t4 & 1) * 64 + ln * 4);
        until(t0 + CH_D1);
        fetch(pph + 1);
        TM(5);
        if (CH_RP == 1) refill2();
        int n = 0;
        uint32_t u[16];
        float y[4][4];
        auto sum = [&]() {
#pragma unroll
          for (int i = 0; i < 16; i++) y[i >> 2][i & 3] = 0.f;
#pragma unroll
          for (int i = 0; i < 8; i++) mma16(y[i & 3], sel.x, sel.y, sel.z, sel.w, u[2 * i], u[2 * i + 1]);
        };
        auto check = [&](auto spec) {
          mbar_wait(bP + (pph & 1) * 8, pph >> 1 & 1);
          TM(14);
          TR(2, clk32());
#pragma unroll
          for (int i = 0; i < 4; i++) ldsm4t(&u[4 * i], l16 + (ps + (pph & 1) * 2048) + i * 512);
          pph++;
          if (spec.value) { pin(); sum(); }
          uint32_t bad = 0;
#pragma unroll
          for (int i = 0; i < 4; i++) bad = or3(bad, differ(u[4 * i], u[4 * i + 1], want), differ(u[4 * i + 2], u[4 * i + 3], want));
          return __any_sync(~0u, bad & chk);
        };
        if (CH_SP) {
          if (check(Int<0>())) {
            do { fetch(pph + 1); spin_guard(n); } while (check(Int<1>()));
          } else {
            sum();
          }
        } else {
          while (check(Int<0>())) { fetch(pph + 1); spin_guard(n); }
          sum();
        }
        TR(1, t0 + (n ? CH_D1 : CH_D0));
        TM(15);
        const uint32_t w = nz(pack2((y[0][0] + y[1][0]) + (y[2][0] + y[3][0]), (y[0][1] + y[1][1]) + (y[2][1] + y[3][1])));
        if (ln < 16) { stg_strong32(mdst, w); stg_strong32(mdst + 4096, w); }
        TMV(12, 32, n);
        TR(3, (clk32() & ~3u) | min(n, 3));
      } else {
        if (CH_RP) refill2();
        if (!NOX) mbar_wait_hot(bXB, (s + 1) & 1);
        stg_strong32(p.pool + ((st == 2 ? 0 : st + 1) * 32768 + rdst + t4 * 4096) + ln * 4, 0u);
        if (t4 == 0 && cta < 40 && s + 4 < NSEG && elect())
          asm volatile("cp.async.bulk.prefetch.L2.global [%0], 1024;" :: "l"(p.xc + (s + 4) * 10240 + cta * 256) : "memory");
        if (t4 == 1 && (s & 3) == 0 && s > 0 && elect()) red_relaxed(p.sync + 2 * s - 4, 1);
        if (t4 == 1 && s == NSEG - 3 && cta == 95 && elect()) red_relaxed(p.sync + 2 * s + 2, 0x10000);
      }
      TM(10);
      bar_arrive(8, 256);
      tokens0(s + 1, Int<CH_R2>());
      TM(2);
      TR(7, clk32());
    } else {
      if (s == NSEG - 1) {
        bar_arrive(1, 256);
        const uint4 v[2] = {lds128(lw + CH_VT), lds128(lw + CH_VT + 512)};
        bar_sync(10, 256);
        publish_v(s, v, memory_v(lds64(l8 + CH_VP), dv));
        bar_arrive(2, 256);
        break;
      }
      const uint32_t xo = l4 + (CH_SX - (t4 == 3 ? 128 : 0)), xr = CH_SX + 768 + min(t4, 2) * 256, x1 = l4 + (r1 + xr), x2 = l4 + (r2 + xr + 128);
      if (t4 < 2) {
        float ds[4][4] = {};
        uint32_t q[16];
        asm volatile("bar.sync 1, 256;" ::: "memory");
#pragma unroll
        for (int k = 0; k < 4; k++) ldsm4(&q[4 * k], qa + k * 512);
        pin();
        if (VK < 20) { finish_v(b, dv); pin(); }
#pragma unroll
        for (int k = 0; k < 4; k++) {
          mma16(ds[k & 1], kf[4 * k], kf[4 * k + 1], kf[4 * k + 2], kf[4 * k + 3], q[4 * k], q[4 * k + 1]);
          mma16(ds[2 + (k & 1)], kf[4 * k], kf[4 * k + 1], kf[4 * k + 2], kf[4 * k + 3], q[4 * k + 2], q[4 * k + 3]);
        }
        float t[4];
#pragma unroll
        for (int i = 0; i < 4; i++) t[i] = (ds[0][i] + ds[2][i]) + (ds[1][i] + ds[3][i]);
        const uint32_t w0 = pack2(t[0], t[1]), w1 = pack2(t[2], t[3]);
        st_async32(x1, w0, bX + r1); st_async32(x2, w0, bX + r2);
        st_async32(x1 + 256, w1, bX + r1); st_async32(x2 + 256, w1, bX + r2);
        sts32(xo, w0); sts32(xo + 128, w1);
      } else {
        float ds[4][4] = {};
        uint32_t q0[4], q1[4], a0[4], a1[4];
        asm volatile("bar.sync 1, 256; " ::: "memory");
        ldsm4(a0, ka); ldsm4(q0, qa); ldsm4(a1, ka + 512); ldsm4(q1, qa + 512);
        pin();
        if (VK < 20) { finish_v(b, dv); pin(); }
        mma16(ds[0], a0[0], a0[1], a0[2], a0[3], q0[0], q0[1]);
        mma16(ds[1], a0[0], a0[1], a0[2], a0[3], q0[2], q0[3]);
        mma16(ds[2], a1[0], a1[1], a1[2], a1[3], q1[0], q1[1]);
        mma16(ds[3], a1[0], a1[1], a1[2], a1[3], q1[2], q1[3]);
        float t[2];
#pragma unroll
        for (int i = 0; i < 2; i++)
          t[i] = ((ds[0][i] + ds[0][i + 2]) + (ds[1][i] + ds[1][i + 2])) + ((ds[2][i] + ds[2][i + 2]) + (ds[3][i] + ds[3][i + 2]));
        const uint32_t w0 = pack2(t[0], t[1]);
        st_async32(x1, w0, bX + r1);
        st_async32(x2, w0, bX + r2);
        sts32(xo, w0);
      }
      TM(3);
      const uint4 id = lds128(l16 + CH_ID);
      float sc[5][4] = {};
      uint4 v[2];
      sum_v(dv);
      bar_sync(4, 256);
      uint32_t r[12], wd[12], we[12] = {};
      ldsm4(&r[0], l16 + CH_SX); ldsm2(&r[4], l16 + CH_SX + 512);
      const uint2 vp = lds64(l8 + CH_VP);
      pin();
      v[0] = lds128(lw + CH_VT); v[1] = lds128(lw + CH_VT + 512);
#pragma unroll
      for (int u = 0; u < 3; u++) ldsm4t(&wd[4 * u], wo + u * 28672);
      pin();
#pragma unroll
      for (int q = 0; q < 4; q++) mma8(sc[q], id.x, id.y, r[q]);
      mma16(sc[4], id.x, id.y, id.z, id.w, r[4], r[5]);
      uint32_t big = absmax2(absmax2(absmax2(r[0], r[1]), absmax2(r[2], r[3])), absmax2(r[4], r[5]));
      const uint2 vm = memory_v(vp, dv);
      const uint32_t ones = 0x3f803f80u;
      pin();
      mbar_wait_hot(bX, s & 1);
      TM(4);
      ldsm4(&r[0], l16 + CH_SX + 768);
      __syncwarp();
      ldsm4(&r[4], l16 + CH_SX + 1280);
      __syncwarp();
      ldsm4(&r[8], l16 + CH_SX + 1792);
      bar_arrive(10, 256);
      pin();
#pragma unroll
      for (int q = 0; q < 4; q++) { mma16(sc[q], id.x, id.y, id.z, id.w, r[2 * q], r[2 * q + 1]); if (q & 1) pin(); }
      uint32_t pr[5], o0, o1;
      bool redo = false;
      auto attend = [&](auto first) {
        float o[2][4] = {}, om[2][4] = {}, e[10];
        auto exps = [&](int q) {
#pragma unroll
          for (int i = 0; i < 2; i++) asm volatile("ex2.approx.ftz.f32 %0, %1;" : "=f"(e[2 * q + i]) : "f"(sc[q][i]));
        };
        auto merge = [&](int q) { big = absmax2(big, absmax2(absmax2(r[4 * q], r[4 * q + 1]), absmax2(r[4 * q + 2], r[4 * q + 3]))); };
        exps(0);
        if (first.value) { merge(0); pin(); mma16(sc[4], id.x, id.y, id.z, id.w, r[8], r[9]); }
        exps(1);
        if (first.value) { merge(1); pin(); }
        exps(2);
        if (first.value) { mma16(sc[4], id.x, id.y, id.z, id.w, r[10], r[11]); merge(2); pin(); }
        pr[0] = pack2(e[0], e[1]); pr[1] = pack2(e[2], e[3]);
        mma16h(o[0], pr[0], pr[1], v[0].x, v[0].y);
        mma16h(o[1], pr[0], pr[1], v[0].z, v[0].w);
        exps(3);
        if (first.value) pin();
        exps(4);
        if (first.value) redo = __any_sync(~0u, (absmax2(big, big << 16) & 0x7fff0000u) >= 0x41800000u);
        const bool drop = first.value && redo;
        const uint32_t a1 = l4 + (drop ? CH_PS : r1 + CH_O), a2 = l4 + (drop ? CH_PS : r2 + CH_O + 2048);
        const uint32_t b1 = drop ? bWq : bO + r1, b2 = drop ? bWq : bO + r2;
        pr[2] = pack2(e[4], e[5]); pr[3] = pack2(e[6], e[7]); pr[4] = pack2(e[8], e[9]);
        mma16h(o[0], pr[2], pr[3], v[1].x, v[1].y);
        mma16h(o[1], pr[2], pr[3], v[1].z, v[1].w);
        mma8h(om[0], pr[4], vm.x);
        mma8h(om[1], pr[4], vm.y);
        o0 = pack2(o[0][0] + om[0][0], o[0][1] + om[0][1]); o1 = pack2(o[1][0] + om[1][0], o[1][1] + om[1][1]);
        st_async32(a1, o0, b1); st_async32(a2, o0, b2);
        st_async32(a1 + 128, o1, b1); st_async32(a2 + 128, o1, b2);
        sts32(l4 + CH_O + 1024, o0); sts32(l4 + CH_O + 1152, o1);
        asm volatile("{.reg .pred p; setp.eq.u32 p, %0, 0; @p bar.arrive 2, 256;}" :: "r"((uint32_t)drop) : "memory");
      };
      attend(Int<1>());
      pin();
      if (__builtin_expect(redo, 0)) {
        float mx = -INFINITY;
#pragma unroll
        for (int q = 0; q < 5; q++) mx = fmaxf(mx, fmaxf(sc[q][0], sc[q][1]));
        mx = fmaxf(mx, __shfl_xor_sync(~0u, mx, 1));
        mx = fmaxf(mx, __shfl_xor_sync(~0u, mx, 2));
#pragma unroll
        for (int q = 0; q < 5; q++) { sc[q][0] -= mx; sc[q][1] -= mx; }
        attend(Int<0>());
      }
      TM(6);
      float l[4] = {}, l2[4] = {};
      mma16h(l, pr[0], pr[1], ones, ones);
      mma16h(l2, pr[2], pr[3], ones, ones);
      mma8h(l, pr[4], ones);
      l[0] += l2[0];
      float inv;
      asm("rcp.approx.ftz.f32 %0, %1;" : "=f"(inv) : "f"(l[0]));
      sts32((l8 & ~0xffu) + (lane & 28) + CH_VP, __float_as_uint(inv));
      __syncwarp();
      if (elect()) mbar_arrive(bO);
      {
        float z[2][4] = {}, y[2][4] = {};
        mma16(z[0], wd[0], wd[1], wd[2], wd[3], o0, o1);
        if (j == 0) {
#pragma unroll
          for (int u = 0; u < 3; u++) ldsm4t(&we[4 * u], (wo ^ 32) + u * 28672);
          mma16(y[0], we[0], we[1], we[2], we[3], o0, o1);
        }
        const float2 iv = lds64f((l8 & ~0xe0u) + CH_VP);
        uint8_t* dst = pool(pdst[0]);
        const uint32_t mask = ((l16 ^ tag) & 48) == 0;
        const uint32_t oa = qa + ((tag & 0xfffe) + CH_O - CH_QK + t4 * 256 - (t4 == 3 ? 1024 : 0));
        const uint32_t za = l16 + ((tag & 0xfffe) + (t4 >> 1) * 512 + (t4 & 1) * 8);
        pin();
        mbar_wait(bO, s & 1);
        uint32_t a[4];
        ldsm4(a, oa);
        mma16(z[0], wd[4], wd[5], wd[6], wd[7], a[0], a[1]);
        mma16(z[1], wd[8], wd[9], wd[10], wd[11], a[2], a[3]);
        if (j == 0) {
          mma16(y[0], we[4], we[5], we[6], we[7], a[0], a[1]);
          mma16(y[1], we[8], we[9], we[10], we[11], a[2], a[3]);
          sts128f(lw + CH_VT + 512, y[0][0] + y[1][0], y[0][1] + y[1][1], y[0][2] + y[1][2], y[0][3] + y[1][3]);
        }
        sts128f(lw + CH_VT, z[0][0] + z[1][0], z[0][1] + z[1][1], z[0][2] + z[1][2], z[0][3] + z[1][3]);
        bar_sync(3, 128);
        if (j == 0 || t4 < 2) {
          float2 q[4];
#pragma unroll
          for (int i = 0; i < 4; i++) q[i] = lds64f(za + CH_VT + i * 1024);
          stg_strong32(dst, pack_tag(((q[0].x + q[1].x) + (q[2].x + q[3].x)) * iv.x, ((q[0].y + q[1].y) + (q[2].y + q[3].y)) * iv.y, tag, mask));
        }
      }
      TM(2);
      if (!NOX) mbar_wait_hot(bXA, (s + 1) & 1);
      if (CH_KP == 2) bulk_wait_read<0>();
      float dk[16], dw[16];
      bar_sync(5, 256);
      wg_fence();
      pass(dk, ak, Int<0>(), Int<20>());
      pass(dw, av, Int<0>(), Int<20>());
      TM(5);
      pin();
      if (CH_EX == 0) publish_v(s, v, vm);
      if (elect()) {
        mbar_expect(bG + t4 * 8, 2560);
        if (t4 == 1 && s + 2 < NSEG) { mbar_expect(bX, 1536); mbar_expect(bO, 2048); }
      }
      if (CH_KD == 0) { wg_wait<1>(); dump(dk, lw + CH_KT); }
      wg_wait<0>();
      if (CH_KD == 1) dump(dk, lw + CH_KT);
      TM(7);
      dump(dw, lw + CH_VT);
      bar_arrive(9, 256);
      pin();
#pragma unroll
      for (int k = 0; k < CH_RB; k++) ldsm4t(&tw[4 * k], wq + k * 2048);
      if (t4 < 2) {
        if (CH_EX == 2) { publish_v(s, v, vm); pin(); }
#pragma unroll
        for (int k = CH_RB; k < CH_RC; k++) ldsm4t(&tw[4 * k], wq + k * 2048);
        const int q = t4 ? 3 : j, o = t4 ? j * 896 : 0;
        const uint8_t* src = p.pool + ((80 + st * 4 + q) * 8192 + (pages >> (st * 4 + q) & 1) * 4096 + o);
        asm volatile("bar.sync 8, 256;" ::: "memory");
        const uint32_t t1 = clk32() + CH_D2;
        if (CH_EX == 1) publish_v(s, v, vm);
        auto fetch = [&](auto n) {
          mbar_wait(bH, s & 1);
          until(t1);
          TR(4, clk32());
          if (elect())
            asm volatile("cp.async.bulk.shared::cluster.global.mbarrier::complete_tx::bytes.multicast::cluster [%0], [%1], %2, [%3], 7;"
                         :: "r"(sb + CH_M + q * 2560 + o), "l"(src), "n"(n.value), "r"(bG + q * 8) : "memory");
        };
        if (!t4) fetch(Int<2560>()); else if (j == 2) fetch(Int<768>()); else fetch(Int<896>());
      } else {
        asm volatile("bar.sync 8, 256; " ::: "memory");
        if (elect()) asm volatile("mbarrier.arrive.relaxed.cluster.shared::cluster.b64 _, [%0];" :: "r"(bH + (t4 == 2 ? r1 : r2)) : "memory");
        pin();
        if (CH_EX) publish_v(s, v, vm);
#pragma unroll
        for (int k = CH_RB; k < CH_RC; k++) ldsm4t(&tw[4 * k], wq + k * 2048);
      }
      TM(9);
      pin();
#pragma unroll
      for (int k = CH_RC; k < CH_TW; k++) ldsm4t(&tw[4 * k], wq + k * 2048);
      if (CH_KP == 2 && t4 == CH_KW) { bar_sync(7, 160); publish_k(s + 1); }
      TM(10);
    }
    if (++st == 3) st = 0;
    tag ^= 0x10001;
  }
}

__global__ void __launch_bounds__(256, 1) chain_kernel(const __grid_constant__ ChainParams p) {
  extern __shared__ __align__(1024) uint8_t smem_raw[];
  const uint32_t sb = s2u(smem_raw);
  const int tid = threadIdx.x, warp = __shfl_sync(~0u, tid >> 5, 0), lane = tid & 31;
  const int cta = blockIdx.x, h = cta / 3, j = cta - 3 * h, colbase = cta * 64;
  const uint32_t bWo = sb + CH_BAR, bWq = bWo + 8, bXA = bWo + 24, bWk = bWo + 80, bWv = bWo + 88;
  uint32_t smid; asm("mov.u32 %0, %%smid;" : "=r"(smid));
  PRO(0);
  if (sb != mapa(CH_BASE, j)) __trap();
  uint32_t entry = 0;
  auto place = [&]() {
    const int i = tid - 128;
    if (i >= 0 && i <= NSLOT) {
      const uint32_t side = ldg_strong32(g_smpart + (smid & 255));
      if (i < NSLOT) {
        entry = i * 8192 + (ldg_strong32(g_orient + i) == (i < 80 ? i & 1 : side) ? 0 : 4096);
      } else {
        entry = 2 * (atomicAdd(g_bo + p.layer * 128 + 1, 1 << 8 * side) >> 8 * side & 255) + side;
      }
    }
    __syncwarp();
  };
  if (warp == 2 && lane < 4) asm volatile("prefetch.tensormap [%0];" :: "l"(&p.wq + lane) : "memory");
  if (p.layer) place();
  if (warp == 0 && elect()) {
#pragma unroll 1
    for (int i = 0; i < 17; i++) mbar_init(bWo + 8 * i, i == 5 ? 5 : i == 3 || i == 4 ? 4 : i == 12 ? 2 : 1);
    asm volatile("fence.mbarrier_init.release.cluster;" ::: "memory");
    mbar_expect(bWk, 81920);
    tma_load3<(WEF & 1) != 0>(sb + CH_WQ, &p.wk, colbase, 0, bWk);
    mbar_expect(bWv, 81920);
    tma_load3<(WEF & 1) != 0>(sb + CH_WO, &p.wv, colbase, 0, bWv);
    mbar_expect(bWo + 16, 1536);
    mbar_expect(bWo + 40, 2048);
    mbar_expect(bWo, 86016); mbar_expect(bWq, 81920);
#pragma unroll 1
    for (int i = 0; i < 8; i++) mbar_expect(bXA + 8 * (i & 1), 5120);
  }
  if (warp == 1) {
    const uint32_t id = (lane >> 3) == (lane & 3) ? ((lane & 4) ? 0x3f800000u : 0x00003f80u) : 0u;
    sts128(sb + CH_ID + lane * 16, make_uint4(id, 0, id, 0));
  }
  __syncthreads();
  asm volatile("barrier.cluster.arrive.relaxed.aligned;" ::: "memory");
  uint32_t ak[80], av[80];
  const uint32_t wq = opaque(sb + CH_WQ + ((warp >> 2) * 320 + (lane & 7) + (lane >> 4) * 8) * 128 + (((2 * (warp & 3) + ((lane >> 3) & 1)) ^ (lane & 7)) << 4));
  pdl_wait();
  if (tid == 32) stg_strong32(g_smuse + (smid & 255), p.layer + 1);
  pdl_launch();
  PRO(1);
  if (warp == 0 && elect()) {
    bulk_load(sb + CH_X + 20480, p.xc + 5120, 20480, bXA);
    bulk_load(sb + CH_X, p.xc, 20480, bXA + 8);
  }
  if (!p.layer) place();
  __syncwarp();
  PRO(2);
  mbar_wait(bWk, 0);
  PRO(3);
#pragma unroll
  for (int k = 0; k < 20; k++) ldsm4t(&ak[4 * k], wq + k * 2048);
  bar_sync(6, 256);
  if (warp == 0 && elect()) tma_load3<(WEF & 2) != 0>(sb + CH_WQ, &p.wq, colbase, 0, bWq);
  __syncwarp();
  PRO(4);
  mbar_wait(bWv, 0);
  PRO(5);
#pragma unroll
  for (int k = 0; k < 20; k++) ldsm4t(&av[4 * k], wq + CH_WO + k * 2048);
  bar_sync(6, 256);
  PRO(6);
  if (warp >= 5 && elect()) tma_load3<(WEF & 2) != 0>(sb + CH_WO + (warp - 5) * 28672, &p.wo, j == 0 ? 0 : 32 + j * 192, h * 192 + (j + 8 - warp) % 3 * 64, bWo);
  if (tid == 128 + NSLOT && entry >= 80) {
    uint32_t c;
    int n = 0;
    do { c = ldg_strong32(g_bo + p.layer * 128 + 1); spin_guard(n); } while ((c & 255) + (c >> 8) < 96);
    const uint32_t other = (c >> 8 * (~entry & 1) & 255) + (entry >> 1) - 40;
    entry = other < 40 ? 2 * other + (~entry & 1) : entry % 80;
  }
  if (tid >= 128 && tid <= 128 + NSLOT) sts32(sb + CH_O + (tid - 128) * 4, entry);
  PRO(7);
  __syncthreads();
  if (__shfl_sync(~0u, tid >> 7, 0) == 0) chain_body<0>(p, wq, ak, av); else chain_body<1>(p, wq, ak, av);
}

struct PostParams { CUtensorMap wq, wo, wb, wo2, wb2; int gap, share, layer, look, gap2, pol, slow_n, slow_gap; };
constexpr int PS = 8, PB = 28672;
constexpr int OP_SMEM = PS * PB + 512 + 2048;
enum { IT_ATT = 0, IT_OP = 1, IT_FIN = 2, IT_BQ = 3, IT_Q = 4 };

__device__ __forceinline__ uint32_t item_count(int type, int b) {
  return type == IT_ATT ? 32 : type == IT_OP ? op_split(b) * (b < OP_160 ? 2 : 4) : type == IT_FIN ? 16 : b < BQ_160 ? 6 : b < BQ_80 ? 12 : 24; }
__device__ __forceinline__ uint32_t item_need(int type, int b) { return type == IT_ATT ? 96 : item_count(type - 1, b); }

struct Ring {
  uint32_t sb, bars; int st; uint32_t ph;
  __device__ __forceinline__ uint32_t wait() const { mbar_wait(bars + 8 * st, ph); return sb + st * PB; }
  __device__ __forceinline__ void next() { if (++st == PS) { st = 0; ph ^= 1; } }
  __device__ __forceinline__ void release(int s) const { if ((threadIdx.x & 31) == 0) mbar_arrive(bars + 8 * (PS + s)); }
  __device__ __forceinline__ void pop() { __syncwarp(); release(st); next(); }
};

template <int N>
__device__ __forceinline__ void gemm_item(Ring& r, float* d, int nst, uint32_t go, int go_at, uint32_t wg) {
  auto desc = [](uint32_t lo, uint32_t hi) { uint64_t x; asm("mov.b64 %0, {%1, %2};" : "=l"(x) : "r"(lo), "r"(hi)); return x; };
  auto stage = [&](auto first) {
    const uint32_t base = (r.wait() & 0x3ffff) >> 4, a = base + wg * 256 + (8 << 16), w = base + 512 + (256 << 16);
    wg_fence();
#pragma unroll
    for (int kk = 0; kk < 2; kk++) {
      const uint64_t da = desc(a + kk * 16, 32), db = desc(w + kk * 128, 64 | 1 << 30);
      const int acc = kk || !first.value;
      if (N == 80) wg_ss80_01(d, da, db, acc);
      if (N == 160) wg_ss160_01(d, da, db, acc);
      if (N >= 192) wg_ss192_01(d, da, db, acc);
      if (N == 320) wg_ss128_01(d + 96, da, desc(w + kk * 128 + 768, 64 | 1 << 30), acc);
    }
    wg_commit();
  };
  stage(Int<1>());
  int prev = r.st;
  r.next();
#pragma unroll 1
  for (int kb = 1; kb < nst; kb++) {
    stage(Int<0>());
    if (kb == go_at && threadIdx.x == 0) mbar_arrive(go);
    wg_wait<1>();
    r.release(prev);
    prev = r.st;
    r.next();
  }
  wg_wait<0>();
  reg_fence<N / 2>(d);
  r.release(prev);
}

template <int HALF>
__device__ __forceinline__ void attn_a_warp(Ring& r, const uint32_t (&q)[48], int b, int h) {
  constexpr int NT = HALF ? 5 : 3, NF = 8 * NT;
  const int lane = threadIdx.x & 31, g = lane >> 2, c = lane & 3, seg = (threadIdx.x >> 5) & 3;
  uint32_t f[6][NF];
  int slot[6];
  auto fetch = [&](int u) {
    const uint32_t kv = r.wait() + seg * KV_BYTES;
    slot[u] = r.st;
    r.next();
#pragma unroll
    for (int w = 0; w < 4; w++) {
      uint32_t* d = &f[u][2 * NT * w];
#pragma unroll
      for (int t = 0; t <= HALF; t++) {
        if (u < 3) {
          ldsm4(d + 4 * t, kv + w * 1024 + t * 512 + (lane & 8) * 32 + (lane & 16) * 8 + (lane & 7) * 16);
        } else {
          const uint4 v = lds128(kv + w * 1024 + t * 512 + lane * 16);
          d[4 * t] = v.x; d[4 * t + 1] = v.y; d[4 * t + 2] = v.z; d[4 * t + 3] = v.w;
        }
      }
      const uint2 m = lds64(kv + KV_M + w * 256 + lane * 8);
      d[2 * NT - 2] = m.x; d[2 * NT - 1] = m.y;
    }
    pdl_launch();
  };
  float s[NT][4] = {};
  fetch(0);
#pragma unroll
  for (int u = 0; u < 3; u++) {
    fetch(u + 1);
#pragma unroll
    for (int kk = 0; kk < 4; kk++) {
      const uint32_t* a = &q[16 * u + 4 * kk];
#pragma unroll
      for (int n = 0; n < NT; n++) mma16(s[(n + 1) % NT], a[0], a[1], a[2], a[3], f[u][2 * NT * kk + 2 * n], f[u][2 * NT * kk + 2 * n + 1]);
    }
    r.release(slot[u]);
    pdl_launch();
  }
  fetch(4);
  const float k2 = 0.07216878364870322f * 1.44269504089f, NEG = -INFINITY;
  if (2 * c > g) { s[NT - 2][0] = NEG; s[NT - 1][2] = NEG; }
  if (2 * c + 1 > g) { s[NT - 2][1] = NEG; s[NT - 1][3] = NEG; }
  s[NT - 1][0] = s[NT - 1][1] = NEG;
  uint32_t pp[NT][2]; float inv[2];
#pragma unroll
  for (int hh = 0; hh < 2; hh++) {
    float m = NEG, l = 0.f;
#pragma unroll
    for (int n = 0; n < NT; n++) m = fmaxf(m, fmaxf(s[n][2 * hh], s[n][2 * hh + 1]));
    m = fmaxf(m, __shfl_xor_sync(~0u, m, 1)); m = fmaxf(m, __shfl_xor_sync(~0u, m, 2));
#pragma unroll
    for (int n = 0; n < NT; n++) { const float x = ex2((s[n][2 * hh] - m) * k2), y = ex2((s[n][2 * hh + 1] - m) * k2); l += x + y; pp[n][hh] = pack2(x, y); }
    l += __shfl_xor_sync(~0u, l, 1); l += __shfl_xor_sync(~0u, l, 2);
    asm("rcp.approx.ftz.f32 %0, %1;" : "=f"(inv[hh]) : "f"(l));
  }
  uint32_t* dst = g_o + ((b * 192 + h * 6) * 16 + seg * 4 + HALF * 2) * 128 + lane;
#pragma unroll
  for (int u = 3; u < 6; u++) {
    float o[8][4] = {};
#pragma unroll
    for (int n = 0; n < 8; n++) mma8(o[n], pp[0][0], pp[0][1], f[u][2 * NT * (n >> 1) + 2 * NT - 2 + (n & 1)]);
#pragma unroll
    for (int t = 0; t <= HALF; t++)
#pragma unroll
      for (int n = 0; n < 8; n++) {
        const uint32_t* v = &f[u][2 * NT * (n >> 1) + 4 * t + 2 * (n & 1)];
        mma16(o[n], pp[1 + 2 * t][0], pp[1 + 2 * t][1], pp[2 + 2 * t][0], pp[2 + 2 * t][1], v[0], v[1]);
      }
    r.release(slot[u]);
    if (u == 3) fetch(5);
#pragma unroll
    for (int n = 0; n < 8; n++) {
      dst[(u - 3) * 4096 + (n >> 2) * 2048 + (n & 3) * 32] = pack2(o[n][0] * inv[0], o[n][1] * inv[0]);
      dst[(u - 3) * 4096 + (n >> 2) * 2048 + (n & 3) * 32 + 128] = pack2(o[n][2] * inv[1], o[n][3] * inv[1]);
    }
  }
}

__device__ __forceinline__ void fin_item(Ring& r, uint32_t scratch, int b, int idx) {
  const int warp = threadIdx.x >> 5, lane = threadIdx.x & 31;
  float4 v[1][5];
  {
    const uint32_t base = r.wait();
#pragma unroll
    for (int i = 0; i < 5; i++) v[0][i] = unpack4(lds64(base + ((warp * 5 + i) * 32 + lane) * 8));
    r.pop();
  }
#pragma unroll 1
  for (int k = 0; k < op_split(b); k += 2) {
    const uint32_t base = r.wait();
#pragma unroll
    for (int i = 0; i < 10; i++) {
      const uint2 q = lds64(base + ((i / 5 * 40 + warp * 5 + i % 5) * 32 + lane) * 8);
      float4& t = v[0][i % 5];
      t.x += bf_lo(q.x); t.y += bf_hi(q.x); t.z += bf_lo(q.y); t.w += bf_hi(q.y);
    }
    r.pop();
  }
#pragma unroll
  for (int i = 0; i < 5; i++) g_x[((b * 16 + idx) * 40 + warp * 5 + i) * 32 + lane] = pack4(v[0][i]);
  float mean[1], rs[1];
  ln_stats<1>(v, scratch, mean, rs);
#pragma unroll
  for (int i = 0; i < 5; i++) {
    const int u = warp * 5 + i;
    uint32_t* xn = g_xn + ((b * 20 + (u >> 1)) * 16 + idx) * 128 + (u & 1) * 64 + lane;
    xn[0] = pack2((v[0][i].x - mean[0]) * rs[0], (v[0][i].y - mean[0]) * rs[0]);
    xn[32] = pack2((v[0][i].z - mean[0]) * rs[0], (v[0][i].w - mean[0]) * rs[0]);
  }
}

__global__ void __launch_bounds__(384, 1) post_kernel(const __grid_constant__ PostParams p) {
  extern __shared__ __align__(1024) uint8_t smem_raw[];
  const uint32_t sb = s2u(smem_raw), bars = sb + PS * PB;
  const uint32_t bIF = bars + 128, bIE = bars + 160, done = bars + 192, bGo = bars + 224, slots = bars + 240, scratch = bars + 512;
  const int warp = __shfl_sync(~0u, threadIdx.x >> 5, 0), lane = threadIdx.x & 31;
  if (warp == 9) PST(0);
  if (warp == 0 && blockIdx.x < 36) TRACE(0);
  if (warp >= 8) {
    asm volatile("setmaxnreg.dec.sync.aligned.u32 56;");
    if (warp == 10) {
      pdl_launch();
      if (sb & 1023) __trap();
      if (lane < 29) mbar_init(bars + 8 * lane, lane < 8 ? 1 : lane < 16 ? 8 : lane < 20 ? 1 : lane < 24 ? 2 : lane < 28 ? 8 : 1);
      if (lane == 0) sts32(slots + 16, p.gap);
      fence_async();
    }
    if (warp == 8 && lane < 5) asm volatile("prefetch.tensormap [%0];" :: "l"(&p.wq + lane) : "memory");
    if (warp != 9) bar_sync(2, 384);
    if (warp == 9) {
      PST(1);
      const int b = lane & 15;
      bool queries = QA_END < 16 && blockIdx.x < 36;
      for (int n = 0;; n++) {
        if (n > 0) { mbar_wait(bGo, (n - 1) & 1); mbar_wait(bIE + 8 * (n & 3), ((n >> 2) & 1) ^ 1); }
        int code = -1, spin = 0, ticket = 0;
        if (queries) {
          if (lane == 0) ticket = n == 0 ? blockIdx.x : 36 + atomicAdd(g_sync + SY_QC, 1);
          ticket = __shfl_sync(~0u, ticket, 0);
          queries = ticket < (16 - QA_END) * 32;
          if (queries) code = IT_Q << 16 | (QA_END + ticket % (16 - QA_END)) << 8 | ticket / (16 - QA_END);
        }
        if (!queries && lane == 0) asm volatile("atom.relaxed.gpu.global.add.u32 %0, [%1], 1;" : "=r"(ticket) : "l"(g_sync + SY_T) : "memory");
        while (!queries) {
          const uint4 hd = ldg_strong128(g_sync + b * 8), pr = ldg_strong128(g_sync + b * 8 + 4);
          if (n == 0 && spin == 0 && hd.x != 0x7fffffff) PST(2);
          const uint32_t hv[4] = {hd.x, hd.y, hd.z, hd.w}, pv[4] = {pr.x, pr.y, pr.z, pr.w};
          const uint32_t chain_done = __ballot_sync(~0u, (pr.x & 0xffff) >= 96) & 0xffff;
          int left[4], avail[4], rdy = 0, claimed = 0, upstream = 0;
#pragma unroll
          for (int t = 0; t < 4; t++) {
            const int cnt = lane < 16 ? item_count(t, b) : 0;
            left[t] = max(cnt - (int)hv[t], 0);
            claimed += cnt - left[t];
            const bool ready = (pv[t] & 0xffff) >= item_need(t, b);
            rdy |= ready << t;
            bool ok = ready || (t == IT_ATT ? pr.x >= 0x10000 : !upstream || (t == IT_OP && (chain_done >> 15 & 1)));
            if (t == IT_BQ && (chain_done >> BQ_HOLD & 1) && !(chain_done >> 15)) ok = false;
            avail[t] = ok ? left[t] : 0;
            upstream |= __any_sync(~0u, left[t] > 0);
          }
          if (!upstream) break;
          int rank = max(__shfl_sync(~0u, ticket, 0) - __reduce_add_sync(~0u, claimed), 0), type = -1, mine = 0;
          {
            const int a = b >= BQ_RUSH && (rdy >> IT_BQ & 1) ? avail[IT_BQ] : 0, tot = __reduce_add_sync(~0u, a);
            if (rank < tot) { type = IT_BQ; mine = a; } else rank -= tot;
            avail[IT_BQ] -= a;
          }
#pragma unroll
          for (int c = 0; c < 8; c++) {
            const int t = c == PR_FIN || c == 5 ? IT_FIN : c == PR_ATT || c == 7 ? IT_ATT : c == PR_OP || c == 4 ? IT_OP : IT_BQ;
            int a = c == PR_ATT || ((rdy >> t & 1) == (c < 4)) ? avail[t] : 0;
            if (t == IT_OP && OP_EARLY) a = c == PR_OP ? avail[t] : 0;
            if (c == 7) a = b < QA_END && !(rdy & 1) && ((chain_done << 1 | 1) >> b & 1) ? left[t] : 0;
            const int tot = __reduce_add_sync(~0u, a);
            if (type < 0) { if (rank < tot) { type = t; mine = a; } else rank -= tot; }
          }
          if (type >= 0) {
#pragma unroll
            for (int o = 1; o < 16; o <<= 1) { const int y = __shfl_up_sync(~0u, mine, o); if (lane >= o) mine += y; }
            const int blk = __ffs(__ballot_sync(~0u, mine > rank)) - 1;
            const int early = !(__shfl_sync(~0u, rdy, blk) >> type & 1);
            uint32_t idx = 0;
            if (n == 0 && spin == 0) PST(3);
            if (lane == 0) asm volatile("atom.relaxed.gpu.global.add.u32 %0, [%1], 1;" : "=r"(idx) : "l"(g_sync + blk * 8 + type) : "memory");
            ld_acquire(g_sync + blk * 8 + 4 + type);
            idx = __shfl_sync(~0u, idx, 0);
            if (idx < item_count(type, blk)) { code = (__shfl_sync(~0u, pr.y, 15) < 32) << 23 | (chain_done >> 15 & 1) << 22 | (chain_done >> p.look & 1) << 21 | early << 20 | type << 16 | blk << 8 | idx; break; }
          } else {
            __nanosleep(50);
          }
          spin_guard(spin);
        }
        if (n == 0) bar_sync(2, 384);
        if (lane == 0) {
          fence_async_global();
          sts32(slots + 4 * (n & 3), code);
          mbar_arrive(bIF + 8 * (n & 3));
        }
        __syncwarp();
        if (code < 0) break;
      }
    } else if (warp == 8) {
      if (elect()) {
        uint32_t dst = sb, bar = bars, ph = 1, next = clk32(), gap = 0;
        auto acquire = [&](uint32_t kb) {
          mbar_wait(bar + 8 * PS, ph);
          mbar_expect(bar, kb * 1024);
          if (gap) {
            uint32_t now;
            do now = clk32(); while ((int)(now - next) < 0);
            next = ((int)(now - next) > 100 ? now - 100 : next) + kb * gap;
          }
        };
        auto advance = [&]() { dst += PB; bar += 8; if (dst == bars) { dst = sb; bar = bars; ph ^= 1; } };
        auto depend = [&](const uint32_t* c, uint32_t need) { wait_count(c, need); fence_async_global(); };
#pragma unroll 1
        for (int n = 0;; n++) {
          mbar_wait(bIF + 8 * (n & 3), (n >> 2) & 1);
          const int code = (int)lds32(slots + 4 * (n & 3));
          if (code < 0) break;
          const int type = (code >> 16) & 15, b = (code >> 8) & 255, idx = code & 255;
          const bool early = code >> 20 & 1, go = !(code >> 21 & 1);
          mbar_arrive(bIE + 8 * (n & 3));
          gap = !(code >> 22 & 1) ? lds32(slots + 16) : type == IT_ATT || type == IT_FIN ? 0 : p.gap2;
          const uint32_t* progress = g_sync + b * 8 + 4 + type;
          if (type == IT_ATT && b >= QA_END) {
            depend(g_sync + SY_Q, (16 - QA_END) * 32);
#pragma unroll 1
            for (int u = 0; u < 2; u++) { acquire(24); bulk_load_last(dst, g_q + (((b - QA_END) * 32 + idx) * 2 + u) * 1536, 24576, bar); advance(); }
          } else if (type == IT_FIN) {
            acquire(10);
            bulk_load(dst, g_x + (b * 16 + idx) * 1280, 10240, bar);
            advance();
            if (early) depend(progress, item_need(type, b));
            if (go) mbar_arrive(bGo);
            const uint2* src = g_part + (b * 16 + idx) * 16 * 1280;
#pragma unroll 1
            for (int i = 0; i < op_split(b); i += 2) { acquire(20); bulk_load_last(dst, src + i * 1280, 20480, bar); advance(); }
            if (!go && p.pol) mbar_arrive(bGo);
          } else {
            const bool op = type == IT_OP, bq = type == IT_BQ;
            const int width = op ? op_width(b) : bq ? bq_width(b) : 192, nb = (width + 63) >> 6, lt = width == 320 ? 1 : 2;
            const int nst = op ? 192 / op_split(b) : 20, kb0 = op ? (idx >> lt) * nst : 0;
            const int col = (op ? idx & ((1 << lt) - 1) : idx) * width;
            const bool whole = !(width & 63);
            const CUtensorMap* m = op ? (whole ? &p.wo : &p.wo2) : bq ? (whole ? &p.wb : &p.wb2) : &p.wq;
            const uint32_t* a = op ? g_o + (b * 192 + kb0) * 2048 : g_xn + b * 20 * 2048;
            int row = kb0 * 32, pre = early && (op || bq) ? min(nst, PRE_MAX) : 0;
            int slow = (code >> 22 & 3) == 3 ? p.slow_n : 0;
            if (slow) gap = p.slow_gap;
            auto weights = [&]() {
              if (slow && --slow == 0) gap = 0;
              acquire(8 + nb * 4);
              if (whole) {
                tma_load3z(dst + 8192, m, row, col >> 6, bar);
              } else {
                tma_load(dst + 8192, m, col, row, bar); tma_load(dst + 12288, m, col + 64, row, bar);
                if (nb == 3) tma_load(dst + 16384, m, col + 128, row, bar);
              }
              row += 32;
            };
            if (pre) {
              uint32_t da = dst, ba = bar;
#pragma unroll 1
              for (int kb = 0; kb < pre; kb++) { weights(); advance(); }
              depend(progress, item_need(type, b));
#pragma unroll 1
              for (int kb = 0; kb < pre; kb++) {
                bulk_load(da, a, 8192, ba);
                a += 2048; da += PB; ba += 8;
                if (da == bars) { da = sb; ba = bars; }
              }
            }
#pragma unroll 1
            for (int kb = pre; kb < nst; kb++) { weights(); if (op && OEF) bulk_load_last(dst, a, 8192, bar); else bulk_load(dst, a, 8192, bar); a += 2048; advance(); }
          }
          if (type == IT_ATT) {
            if (early) depend(progress, 96);
            if (go) mbar_arrive(bGo);
            const uint8_t* src = g_kv + (size_t)(idx * 6 * NSEG + b * 4) * KV_BYTES;
#pragma unroll 1
            for (int u = 0; u < 6; u++) {
              acquire(20);
              bulk_load_last(dst, src, 20480, bar);
              src += u == 2 ? -3 * KV_V : 2 * KV_V;
              advance();
            }
            if (!go && p.pol && ATT_LOOK) mbar_arrive(bGo);
          }
        }
      }
    } else if (warp == 11) {
      uint32_t smid, nsm, used = 0;
      asm("mov.u32 %0, %%smid;" : "=r"(smid)); asm("mov.u32 %0, %%nsmid;" : "=r"(nsm));
      for (int n = 0; n < 64 && used < 96; n++) {
        uint32_t peers = 0;
        used = 0;
        for (uint32_t i = lane; i < min(nsm, 256u); i += 32) {
          const bool taken = ldg_strong32(g_smuse + i) == p.layer + 1;
          used += taken;
          peers += abs((int)(g_smclk[i] - g_smclk[smid & 255])) < 4000 && !taken;
        }
        used = __reduce_add_sync(~0u, used);
        sts32(slots + 16, max(p.gap, (int)min(__reduce_add_sync(~0u, peers), 18u) * p.share >> 3));
      }
    } else if (warp == 10 && lane == 0) {
      for (int n = 0;; n++) {
        mbar_wait(bIF + 8 * (n & 3), (n >> 2) & 1);
        const int code = (int)lds32(slots + 4 * (n & 3));
        if (code < 0) break;
        const int type = (code >> 16) & 15, b = (code >> 8) & 255;
        mbar_wait(done + 8 * (n & 3), (n >> 2) & 1);
        if (type != IT_BQ) red_release(type == IT_Q ? g_sync + SY_Q : g_sync + b * 8 + 5 + type, 1);
        mbar_arrive(bIE + 8 * (n & 3));
      }
    }
  } else {
    asm volatile("setmaxnreg.inc.sync.aligned.u32 224;");
    bar_sync(2, 384);
    const int g = lane >> 2, c = lane & 3;
    Ring r = {sb, bars, 0, 0};
#pragma unroll 1
    for (int n = 0;; n++) {
      mbar_wait(bIF + 8 * (n & 3), (n >> 2) & 1);
      const int code = __shfl_sync(~0u, (int)lds32(slots + 4 * (n & 3)), 0);
      if (code < 0) { TRACE(2); break; }
      const int type = (code >> 16) & 15, b = (code >> 8) & 255, idx = code & 255;
      ITEM(code & 0xfffff, 0);
      if (type == IT_ATT || type == IT_Q) {
        uint32_t q[48];
        if (type == IT_Q || b < QA_END) {
          float d[96];
          gemm_item<192>(r, d, 20, bGo, type == IT_Q ? 12 : -1, warp >> 2);
#pragma unroll
          for (int i = 0; i < 48; i++) q[i] = pack2(d[2 * i], d[2 * i + 1]);
        } else {
#pragma unroll
          for (int u = 0; u < 2; u++) {
            const uint32_t base = r.wait() + threadIdx.x * 16;
#pragma unroll
            for (int i = 0; i < 6; i++) {
              const uint4 v = lds128(base + i * 4096);
              q[24 * u + 4 * i] = v.x; q[24 * u + 4 * i + 1] = v.y; q[24 * u + 4 * i + 2] = v.z; q[24 * u + 4 * i + 3] = v.w;
            }
            r.pop();
          }
        }
        if (type == IT_Q) {
          uint4* dst = g_q + ((b - QA_END) * 32 + idx) * 3072 + threadIdx.x;
#pragma unroll
          for (int i = 0; i < 12; i++) dst[i * 256] = make_uint4(q[4 * i], q[4 * i + 1], q[4 * i + 2], q[4 * i + 3]);
        } else if (warp < 4) {
          attn_a_warp<0>(r, q, b, idx);
        } else {
          attn_a_warp<1>(r, q, b, idx);
        }
      } else if (type == IT_FIN) {
        fin_item(r, scratch, b, idx);
      } else {
        float d[160];
        const int width = type == IT_OP ? op_width(b) : bq_width(b), nst = type == IT_OP ? 192 / op_split(b) : 20;
        const int go_at = max(nst - (code >> 21 & 1 ? p.pol : 6), 1);
        if (width == 320) {
          gemm_item<320>(r, d, nst, bGo, go_at, warp >> 2);
        } else if (width == 160 || BQ_80 == 16) {
          gemm_item<160>(r, d, nst, bGo, go_at, warp >> 2);
#pragma unroll
          for (int i = 80; i < 160; i++) d[i] = 0.f;
        } else {
          gemm_item<80>(r, d, nst, bGo, go_at, warp >> 2);
#pragma unroll
          for (int i = 40; i < 160; i++) d[i] = 0.f;
        }
        if (type == IT_OP) {
          const int tiles = DM / width;
          uint2* dst = g_part + (((b * 16 + warp * 2) * 16 + idx / tiles) * 40 + idx % tiles * (width / 16)) * 32 + lane;
#pragma unroll
          for (int u = 0; u < 20; u++) {
            if (u % 5 == 0 && u * 16 >= width) break;
            dst[u * 32] = make_uint2(pack2(d[8 * u], d[8 * u + 1]), pack2(d[8 * u + 4], d[8 * u + 5]));
            dst[(640 + u) * 32] = make_uint2(pack2(d[8 * u + 2], d[8 * u + 3]), pack2(d[8 * u + 6], d[8 * u + 7]));
          }
        } else {
          const int row = b * 128 + warp * 16 + g;
          const int h0 = idx * (width / 20);
          const float sc = h0 < 32 ? 0.22360679775f * 1.44269504089f : 1.f;
          const bool lo = c < 2;
          uint32_t* da = g_bqkv + (h0 * 256 + (row >> 3)) * 96 + lane;
          uint32_t* db = da + 256 * 96 + (lo ? 2 : -2);
          uint32_t pad[2];
#pragma unroll
          for (int rr = 0; rr < 2; rr++) pad[rr] = c & 1 || h0 < 32 ? 0u : h0 >= 64 ? 0x00003f80u : poly_group((row >> 3) + rr) ? 0x3f803f80u : 0u;
#pragma unroll
          for (int q = 0; q < 8; q++) {
            if (!(q & 1) && q * 40 >= width) break;
#pragma unroll
            for (int rr = 0; rr < 2; rr++) {
              uint32_t w[5];
#pragma unroll
              for (int i = 0; i < 5; i++) w[i] = pack2(d[20 * q + 4 * i + 2 * rr] * sc, d[20 * q + 4 * i + 2 * rr + 1] * sc);
              const int o = q * 2 * 256 * 96 + rr * 96;
              da[o] = w[0]; da[o + 32] = w[1]; da[o + 64] = lo ? w[2] : pad[rr];
              db[o] = lo ? w[3] : w[2]; db[o + 32] = lo ? w[4] : w[3]; db[o + 64] = lo ? pad[rr] : w[4];
            }
          }
        }
      }
      __syncwarp();
      if (lane == 0) mbar_arrive(done + 8 * (n & 3));
      if ((code >> 21 & 1) && (p.pol == 0 || (type == IT_ATT && !ATT_LOOK)) && threadIdx.x == 128) mbar_arrive(bGo);
      ITEM(code & 0xfffff, 1);
    }
  }
}

constexpr int AB_SMEM = 1024 + 98304 + 51200 + 4 * 16384 + 256 + 10240;
#define AB_LW 1
#define AB_U 8
#define AB_WG 4
constexpr int AB_T = AB_WG * 128, AB_PASS = 8 / AB_WG;
__device__ __forceinline__ uint32_t fma2(uint32_t a, uint32_t b, uint32_t c) { uint32_t r; asm("fma.rn.bf16x2 %0, %1, %2, %3;" : "=r"(r) : "r"(a), "r"(b), "r"(c)); return r; }
__device__ __forceinline__ uint32_t ex2_pair(float a, float b, uint32_t one, uint32_t c0) {
  const uint32_t e = __byte_perm(__float_as_uint(a), __float_as_uint(b), 0x6521);
  uint32_t x, r;
  asm("lop3.b32 %0, %1, 0x007f007f, %2, 0xEA;" : "=r"(x) : "r"(e), "r"(one));
  const uint32_t m = fma2(fma2(c0, x, 0x3c0d3c0du), x, 0x3f2b3f2bu);
  asm("lop3.b32 %0, %1, %2, 0x7f807f80, 0xE4;" : "=r"(r) : "r"(e), "r"(m));
  return r;
}
__device__ __forceinline__ float sq2(uint32_t w) { const float a = bf_lo(w), b = bf_hi(w); return fmaf(a, a, b * b); }

__device__ __forceinline__ void attn_b_store(const float* o, int h, int row0, int lane) {
  const int g = lane >> 2, c = lane & 3;
  const float i0 = __frcp_rn(__shfl_sync(~0u, o[8], (lane & ~3) | 2)), i1 = __frcp_rn(__shfl_sync(~0u, o[10], (lane & ~3) | 2));
#pragma unroll
  for (int jj = 0; jj < 3; jj++) {
    if (jj < 2 || c < 2) {
      const int col = h * 20 + 8 * jj + 2 * c;
      uint32_t* dst = g_of + (((row0 >> 7) * 10 + (col >> 6)) * 16 + (row0 >> 3 & 15)) * 256 + (col >> 3 & 7) * 32 + g * 4 + (col >> 1 & 3);
      dst[0] = pack2(o[4 * jj] * i0, o[4 * jj + 1] * i0);
      dst[256] = pack2(o[4 * jj + 2] * i1, o[4 * jj + 3] * i1);
    }
  }
}

struct AbParams { Weights next; uint32_t* done; uint32_t* out; };
__global__ void __launch_bounds__(AB_T + 32, 1) attn_b_kernel(const __grid_constant__ AbParams p) {
  extern __shared__ uint8_t smem_raw[];
  const uint32_t sb = (s2u(smem_raw) + 1023) & ~1023u, sK = sb, sV = sb + 98304, bars = sV + 51200 + 4 * 16384;
  const uint32_t bF = bars + 64, bW = bars + 72, bA = bars + 80, bE = bars + 128, smax = bars + 176;
  auto ring = [&](int i) { return i < 2 ? sK + 51200 + i * 16384 : sV + 51200 + (i - 2) * 16384; };
  const int warp = __shfl_sync(~0u, threadIdx.x >> 5, 0), lane = threadIdx.x & 31;
  const int h = blockIdx.x >> 2, quarter = blockIdx.x & 3;
  TRACE(0);
  pdl_launch();
  if (threadIdx.x < 22) mbar_init(bars + 8 * threadIdx.x, threadIdx.x == 8 ? AB_T / 32 : threadIdx.x >= 16 ? 8 : 1);
  if (threadIdx.x == 32) sts64(smax, 0, 0);
  fence_async();
  __syncthreads();
  pdl_wait();
  const int blk = quarter * 4 + (h >> 3), cg = h & 7;
  auto unsafe = [&]() { const float2 m = lds64f(smax); return !(m.x * m.y <= 10000.f); };
  if (warp == AB_T / 32) {
    auto load_w = [&]() {
      mbar_expect(bW, 102400);
      for (int i = 0; i < 4; i++) bulk_load((i < 2 ? sK : sV) + (i & 1) * 25600, g_wb + cg * 6400 + i * 1600, 25600, bW);
    };
    if (elect()) {
      const uint32_t* gk = g_bqkv + (32 + h) * 256 * 96;
#pragma unroll 1
      for (int i = 0; i < 8; i++) {
        if (i >= AB_LW) mbar_wait(bars + 8 * (i - AB_LW), 0);
        mbar_expect(bars + 8 * i, 24576);
        bulk_load_last(sK + i * 12288, gk + i * 3072, 12288, bars + 8 * i);
        bulk_load_last(sV + i * 12288, gk + 32 * 256 * 96 + i * 3072, 12288, bars + 8 * i);
      }
    }
    __syncwarp();
    if (blockIdx.x < NSLOT) for (int i = lane; i < 512; i += 32) reinterpret_cast<uint4*>(pool_at(blockIdx.x * 8192))[i] = make_uint4(0, 0, 0, 0);
    if (blockIdx.x == 127) for (int i = lane; i < SY_N; i += 32) g_sync[i] = 0;
    if (p.next.w[0] && lane == 0) {
      for (int i = 0; i < AB_PF; i++) { const uint32_t t0 = clk32(); while (clk32() - t0 < (i ? AB_PFD : AB_PF0)) __nanosleep(200); prefetch_weights(p.next, i); }
    }
    __syncwarp();
    mbar_wait(bF, 0);
    const bool redo = unsafe();
    if (!redo && lane == 0) load_w();
    if (lane < 16) asm volatile("cp.async.bulk.prefetch.L2.global [%0], 1280;" :: "l"(g_x + ((blk * 16 + lane) * 40 + cg * 5) * 32) : "memory");
    __syncwarp();
    bar_sync(1, AB_T + 32);
    if (lane == 0) {
      ABT(!!p.out, 1);
      red_release(p.done + quarter * 32, 1);
      ABT(!!p.out, 2);
      if (redo) load_w();
      wait_count(p.done + quarter * 32, 32);
      fence_async_global();
      ABT(!!p.out, 3);
      for (int kb = 0; kb < 10; kb++) {
        const int i = kb < 6 ? kb : kb - 6;
        if (kb >= 6) mbar_wait(bE + 8 * i, 0);
        mbar_expect(bA + 8 * i, 16384);
        bulk_load(ring(i), g_of + (blk * 10 + kb) * 4096, 16384, bA + 8 * i);
      }
    }
    return;
  }
  float qmax = 0.f;
  const uint32_t one = opaque(0x3f803f80u + (threadIdx.x >> 10)), c0 = opaque(0x3ea83ea8u + (threadIdx.x >> 10));
#pragma unroll 1
  for (int pass = 0; pass < AB_PASS; pass++) {
    const int row0 = quarter * 512 + ((warp >> 2) * AB_PASS + pass) * 64 + (warp & 3) * 16;
    const uint32_t* gq = g_bqkv + (h * 256 + (row0 >> 3)) * 96 + lane;
    const uint32_t q0 = gq[0], q1 = gq[96], q2 = gq[32], q3 = gq[128];
    uint32_t q4 = gq[64], q5 = gq[160];
    const uint32_t z0 = gq[64 + 3 - (lane & 3)], z1 = gq[160 + 3 - (lane & 3)];
    {
      float n0 = sq2(q0) + sq2(q2) + sq2(q4), n1 = sq2(q1) + sq2(q3) + sq2(q5);
      n0 += __shfl_xor_sync(~0u, n0, 1); n1 += __shfl_xor_sync(~0u, n1, 1);
      n0 += __shfl_xor_sync(~0u, n0, 2); n1 += __shfl_xor_sync(~0u, n1, 2);
      qmax = (n0 > qmax || n0 != n0) ? n0 : qmax;
      qmax = (n1 > qmax || n1 != n1) ? n1 : qmax;
    }
    if (pass == AB_PASS - 1) {
      float kmax = 0.f;
#pragma unroll
      for (int i = 0; i < SEQ / AB_T; i++) {
        const int key = threadIdx.x + AB_T * i;
        const uint32_t a = sK + (key >> 3) * 384 + (key & 7) * 16;
        const uint4 x = lds128(a), y = lds128(a + 128);
        const uint2 z = lds64(a + 256);
        const float n = ((sq2(x.x) + sq2(x.y)) + (sq2(x.z) + sq2(x.w))) + ((sq2(y.x) + sq2(y.y)) + (sq2(y.z) + sq2(y.w))) + (sq2(z.x) + sq2(z.y));
        kmax = (n > kmax || n != n) ? n : kmax;
      }
      const uint32_t kb = __reduce_max_sync(~0u, __float_as_uint(kmax) & 0x7fffffffu), qb = __reduce_max_sync(~0u, __float_as_uint(qmax) & 0x7fffffffu);
      if (lane < 2) asm volatile("red.shared.max.u32 [%0], %1;" :: "r"(smax + 4 * lane), "r"(lane ? kb : qb) : "memory");
      __syncwarp();
    }
    if ((lane & 3) == 2) { q4 = 0xBF8043C0u; q5 = 0xBF8043C0u; }
    float o[12];
    auto desc = [](uint32_t lo, uint32_t hi) { uint64_t d; asm("mov.b64 %0, {%1, %2};" : "=l"(d) : "r"(lo), "r"(hi)); return d; };
    const uint32_t k0 = (uint32_t)mkdesc(sK, 128, 0, 0), k1 = (uint32_t)mkdesc(sK + 256, 0, 0, 0), v0 = (uint32_t)mkdesc(sV, 384, 0, 0);
    float sa[16], sb2[16];
    uint32_t pa[8], pb[8];
    auto qk = [&](float* s, uint32_t t) {
      wg_rs32_00(s, q0, q1, q2, q3, desc(k0 + t, 24), 0);
      wg_rs32_00(s, q4, q5, z0, z1, desc(k1 + t, 24), 1);
      wg_commit();
    };
    auto step = [&](float* s, uint32_t* pp, int g0, uint32_t t, uint32_t nx, int acc) {
      wg_wait<1>();
      reg_fence<16>(s);
#pragma unroll
      for (int i = 0; i < 8; i++) pp[i] = poly_group(g0 + (i >> 1)) ? ex2_pair(s[2 * i], s[2 * i + 1], one, c0) : pack2(ex2(s[2 * i]), ex2(s[2 * i + 1]));
      wg_fence();
      wg_rs24_01(o, pp[0], pp[1], pp[2], pp[3], desc(v0 + t, 8), acc);
      wg_rs24_01(o, pp[4], pp[5], pp[6], pp[7], desc(v0 + t + 48, 8), 1);
      qk(s, nx);
    };
    if (pass == 0) mbar_wait(bars, 0);
    wg_fence();
    qk(sa, 0);
    qk(sb2, 96);
#pragma unroll 1
    for (uint32_t t = 0; t < 64 * 96; t += AB_U * 96) {
      const uint32_t nx = t + AB_U * 96 < 64 * 96 ? t + AB_U * 96 : 0;
      if (pass == AB_PASS - 1 && t == 40 * 96 && lane == 0) mbar_arrive(bF);
#pragma unroll
      for (int u = 0; u < AB_U; u += 2) {
        if (u == AB_U - 2 && pass == 0) mbar_wait(bars + 8 * (nx / 768), 0);
        step(sa, pa, 0, t + u * 96, u + 2 < AB_U ? t + (u + 2) * 96 : nx, u | t);
        step(sb2, pb, 4, t + u * 96 + 96, (u + 2 < AB_U ? t + (u + 2) * 96 : nx) + 96, 1);
      }
    }
    wg_wait<0>();
    reg_fence<12>(o); reg_fence<16>(sa); reg_fence<16>(sb2);
    attn_b_store(o, h, row0, lane);
  }
  mbar_wait(bF, 0);
  if (unsafe())
#pragma unroll 1
  for (int pass = 0; pass < AB_PASS; pass++) {
    const int row0 = quarter * 512 + ((warp >> 2) * AB_PASS + pass) * 64 + (warp & 3) * 16;
    const uint32_t* gq = g_bqkv + (h * 256 + (row0 >> 3)) * 96 + lane;
    const uint32_t q0 = gq[0], q1 = gq[96], q2 = gq[32], q3 = gq[128], q4 = gq[64], q5 = gq[160];
    float o[12];
#pragma unroll
    for (int i = 0; i < 12; i++) o[i] = 0.f;
    float m0 = -INFINITY, m1 = -INFINITY;
#pragma unroll 1
    for (int kt = 0; kt < 32; kt++) {
      float s[32];
      const uint64_t dk = mkdesc(sK + kt * 3072, 128, 384, 0), dk2 = mkdesc(sK + kt * 3072 + 256, 0, 384, 0);
      wg_fence();
      wg_rs64_00(s, q0, q1, q2, q3, dk, 0);
      wg_rs64_00(s, q4, q5, 0, 0, dk2, 1);
      wg_commit();
      wg_wait<0>();
      reg_fence<32>(s); reg_fence<12>(o);
      float n0 = m0, n1 = m1;
#pragma unroll
      for (int jj = 0; jj < 8; jj++) { n0 = fmaxf(n0, fmaxf(s[4 * jj], s[4 * jj + 1])); n1 = fmaxf(n1, fmaxf(s[4 * jj + 2], s[4 * jj + 3])); }
      n0 = fmaxf(n0, __shfl_xor_sync(~0u, n0, 1)); n0 = fmaxf(n0, __shfl_xor_sync(~0u, n0, 2));
      n1 = fmaxf(n1, __shfl_xor_sync(~0u, n1, 1)); n1 = fmaxf(n1, __shfl_xor_sync(~0u, n1, 2));
      const float r0 = ex2(m0 - n0), r1 = ex2(m1 - n1);
      m0 = n0; m1 = n1;
#pragma unroll
      for (int jj = 0; jj < 3; jj++) { o[4 * jj] *= r0; o[4 * jj + 1] *= r0; o[4 * jj + 2] *= r1; o[4 * jj + 3] *= r1; }
      uint32_t pp[16];
#pragma unroll
      for (int jj = 0; jj < 8; jj++) {
        pp[2 * jj] = pack2(ex2(s[4 * jj] - m0), ex2(s[4 * jj + 1] - m0));
        pp[2 * jj + 1] = pack2(ex2(s[4 * jj + 2] - m1), ex2(s[4 * jj + 3] - m1));
      }
      const uint64_t dv = mkdesc(sV + kt * 3072, 384, 128, 0);
      wg_fence();
#pragma unroll
      for (int kk = 0; kk < 4; kk++) wg_rs24_01(o, pp[4 * kk], pp[4 * kk + 1], pp[4 * kk + 2], pp[4 * kk + 3], dv + kk * 48, 1);
      wg_commit();
    }
    wg_wait<0>();
    reg_fence<12>(o);
    attn_b_store(o, h, row0, lane);
  }
  ABT(!!p.out, 0);
  bar_arrive(1, AB_T + 32);
  if (warp >= 12) return;
  const int g = lane >> 2, c = lane & 3;
  const bool live = opaque(threadIdx.x) < 256;
  float d[40] = {};
  uint2* x = g_x + ((blk * 16 + warp * 2) * 40 + cg * 5) * 32 + lane;
  if (warp < 8) {
#pragma unroll
  for (int i = 0; i < 10; i++) {
    const int r = i / 5, u = i % 5;
    const float4 t = unpack4(x[(r * 40 + u) * 32]);
    d[8 * u + 2 * r] = t.x; d[8 * u + 2 * r + 1] = t.y; d[8 * u + 4 + 2 * r] = t.z; d[8 * u + 5 + 2 * r] = t.w;
  }
  mbar_wait(bW, 0);
  reg_fence<40>(d);
  ABT(!!p.out, 4);
#pragma unroll 1
  for (int kb = 0; kb < 10; kb++) {
    const int i = kb < 6 ? kb : kb - 6;
    mbar_wait(bA + 8 * i, kb >= 6);
    const uint64_t da = mkdesc(ring(i) + (warp >> 2) * 8192, 128, 1024, 0), db = mkdesc(kb < 5 ? sK + kb * 10240 : sV + (kb - 5) * 10240, 1280, 128, 0);
    wg_fence();
#pragma unroll
    for (int kk = 0; kk < 4; kk++) wg_ss80_01(d, da + kk * 16, db + kk * 160, 1);
    wg_commit();
    if (kb > 0 && kb < 5) { wg_wait<1>(); if (lane == 0) mbar_arrive(bE + 8 * (kb - 1)); }
  }
  wg_wait<0>();
  reg_fence<40>(d);
  }
  ABT(!!p.out, 5);
  if (p.out) {
    if (warp >= 8) return;
    const uint32_t stage = sK + 83968 + warp * 2560 + (warp < 4 ? 0 : 131328 - 10240);
#pragma unroll
    for (int u = 0; u < 5; u++)
      stsm4(stage + (lane & 15) * 160 + u * 32 + (lane >> 4) * 16, pack2(d[8 * u], d[8 * u + 1]), pack2(d[8 * u + 2], d[8 * u + 3]),
            pack2(d[8 * u + 4], d[8 * u + 5]), pack2(d[8 * u + 6], d[8 * u + 7]));
    __syncwarp();
    uint4* out = reinterpret_cast<uint4*>(p.out + (blk * 128 + warp * 16) * (DM / 2) + cg * 40);
#pragma unroll
    for (int i = 0; i < 5; i++) { const int e = i * 32 + lane, r = e / 10; out[r * (DM / 8) + e - r * 10] = lds128(stage + e * 16); }
  } else {
    float2* stat = g_stat + blk * 1024 + (warp & 7) * 16 + g;
    float mean[2], rs[2];
#pragma unroll
    for (int r = 0; r < 2; r++) {
      float t = 0.f, q = 0.f;
#pragma unroll
      for (int i = 0; i < 10; i++) t += d[4 * i + 2 * r] + d[4 * i + 2 * r + 1];
      t += __shfl_xor_sync(~0u, t, 1); t += __shfl_xor_sync(~0u, t, 2);
      t *= 1.f / 80;
#pragma unroll
      for (int i = 0; i < 10; i++) { const float a = d[4 * i + 2 * r] - t, b = d[4 * i + 2 * r + 1] - t; q += a * a + b * b; }
      q += __shfl_xor_sync(~0u, q, 1); q += __shfl_xor_sync(~0u, q, 2);
      if (c == r && live) asm volatile("st.relaxed.gpu.global.v2.b32 [%0], {%1, %2};" :: "l"(stat + cg * 128 + r * 8), "r"(__float_as_uint(t)), "r"(nz(__float_as_uint(q))) : "memory");
    }
#pragma unroll
    for (int i = 0; i < 10; i++) {
      const int r = i / 5, u = i % 5;
      if (live) x[(r * 40 + u) * 32] = make_uint2(pack2(d[8 * u + 2 * r], d[8 * u + 2 * r + 1]), pack2(d[8 * u + 4 + 2 * r], d[8 * u + 5 + 2 * r]));
    }
    ABT(0, 6);
    uint2 e[4];
    int n = 0;
    do {
#pragma unroll
      for (int i = 0; i < 4; i++)
        asm volatile("ld.relaxed.gpu.global.v2.b32 {%0, %1}, [%2];" : "=r"(e[i].x), "=r"(e[i].y) : "l"(stat + (2 * c + (i & 1)) * 128 + (i >> 1) * 8) : "memory");
      spin_guard(n);
    } while (__any_sync(~0u, min(min(e[0].y, e[1].y), min(e[2].y, e[3].y)) == 0 && live));
#pragma unroll
    for (int r = 0; r < 2; r++) {
      const float m0 = __uint_as_float(e[2 * r].x), m1 = __uint_as_float(e[2 * r + 1].x);
      float t = m0 + m1;
      t += __shfl_xor_sync(~0u, t, 1); t += __shfl_xor_sync(~0u, t, 2);
      t *= 0.125f;
      float q = __uint_as_float(e[2 * r].y) + __uint_as_float(e[2 * r + 1].y) + 80.f * ((m0 - t) * (m0 - t) + (m1 - t) * (m1 - t));
      q += __shfl_xor_sync(~0u, q, 1); q += __shfl_xor_sync(~0u, q, 2);
      mean[r] = t; rs[r] = rsqrtf(q * (1.f / DM) + 1e-5f);
    }
    ABT(0, 7);
    uint32_t w[2][5][2];
#pragma unroll
    for (int i = 0; i < 20; i++) w[i & 1][i >> 2][i >> 1 & 1] = pack2((d[2 * i] - mean[i & 1]) * rs[i & 1], (d[2 * i + 1] - mean[i & 1]) * rs[i & 1]);
    ln_store(w, blk * 8 + warp, cg * 5, live);
  }
  ABT(!!p.out, 8);
  TRACE(2);
}

typedef CUresult (*EncodeFn)(CUtensorMap*, CUtensorMapDataType, cuuint32_t, void*, const cuuint64_t*, const cuuint64_t*,
                             const cuuint32_t*, const cuuint32_t*, CUtensorMapInterleave, CUtensorMapSwizzle,
                             CUtensorMapL2promotion, CUtensorMapFloatOOBfill);

void make_map(EncodeFn enc, CUtensorMap* m, const void* ptr, int cols, int rows, int nb) {
  const cuuint64_t dims[3] = {(cuuint64_t)(nb ? 64 : cols), (cuuint64_t)rows, (cuuint64_t)cols / 64};
  const cuuint64_t strides[2] = {(cuuint64_t)cols * 2, 128};
  const cuuint32_t box[3] = {64, 32, (cuuint32_t)nb}, es[3] = {1, 1, 1};
  enc(m, CU_TENSOR_MAP_DATA_TYPE_BFLOAT16, nb ? 3 : 2, const_cast<void*>(ptr), dims, strides, box, es, CU_TENSOR_MAP_INTERLEAVE_NONE,
      CU_TENSOR_MAP_SWIZZLE_128B, CU_TENSOR_MAP_L2_PROMOTION_L2_128B, CU_TENSOR_MAP_FLOAT_OOB_FILL_NONE);
}
template <class... KA, class... A>
void launch(void (*kern)(KA...), int grid, int block, int smem, int cluster, bool pdl, A... args) {
  cudaFuncSetAttribute(kern, cudaFuncAttributeMaxDynamicSharedMemorySize, smem);
  cudaLaunchConfig_t cfg = {};
  cfg.gridDim = dim3(grid); cfg.blockDim = dim3(block); cfg.dynamicSmemBytes = smem; cfg.stream = cudaStreamPerThread;
  cudaLaunchAttribute at[2];
  int n = 0;
  if (cluster > 1) { at[n].id = cudaLaunchAttributeClusterDimension; at[n].val.clusterDim.x = cluster; at[n].val.clusterDim.y = 1; at[n].val.clusterDim.z = 1; n++; }
  if (pdl) { at[n].id = cudaLaunchAttributeProgrammaticStreamSerialization; at[n].val.programmaticStreamSerializationAllowed = 1; n++; }
  cfg.attrs = at; cfg.numAttrs = n;
  cudaLaunchKernelEx(&cfg, kern, args...);
}
template <class T> void* sym(T& s) { void* p = nullptr; cudaGetSymbolAddress(&p, s); return p; }

}

#define MODE(b) 0
extern "C" void kernel_launch(void* const* d_in, const int* in_sizes, int n_in, void* d_out, int out_size) {
  const __nv_bfloat16* x = (const __nv_bfloat16*)d_in[0];
  void* fn = nullptr; cudaDriverEntryPointQueryResult qr;
  cudaGetDriverEntryPoint("cuTensorMapEncodeTiled", &fn, cudaEnableDefault, &qr);
  EncodeFn enc = (EncodeFn)fn;

  ChainParams ch = {};
  PostParams op = {};
  for (int i = 0; i < 3; i++) {
    const cuuint64_t dims[3] = {HD, 128, 5}, strides[2] = {HD * 2, HD * 256};
    const cuuint32_t box[3] = {64, 128, 5}, es[3] = {1, 1, 1};
    enc(i == 0 ? &ch.wq : i == 1 ? &ch.wk : &ch.wv, CU_TENSOR_MAP_DATA_TYPE_BFLOAT16, 3, d_in[2 + i], dims, strides, box, es, CU_TENSOR_MAP_INTERLEAVE_NONE,
        CU_TENSOR_MAP_SWIZZLE_128B, W_PROMO, CU_TENSOR_MAP_FLOAT_OOB_FILL_NONE);
  }
  {
    const cuuint64_t dims[3] = {DM, HD, 7}, strides[2] = {DM * 2, 64};
    const cuuint32_t box[3] = {32, 64, 7}, es[3] = {1, 1, 1};
    enc(&ch.wo, CU_TENSOR_MAP_DATA_TYPE_BFLOAT16, 3, d_in[5], dims, strides, box, es, CU_TENSOR_MAP_INTERLEAVE_NONE,
        CU_TENSOR_MAP_SWIZZLE_64B, CU_TENSOR_MAP_L2_PROMOTION_L2_128B, CU_TENSOR_MAP_FLOAT_OOB_FILL_NONE);
  }
  ch.mem0 = (const __nv_bfloat16*)d_in[1];
  ch.pool = (uint8_t*)(((uintptr_t)sym(g_pool) + 8191) & ~(uintptr_t)8191); ch.kv = (uint8_t*)sym(g_kv); ch.xc = (const uint32_t*)sym(g_xc); ch.sync = (uint32_t*)sym(g_sync);
  ch.d1 = 0; ch.d1b = 0; ch.d2 = 0; ch.d2b = 0;
  make_map(enc, &op.wq, d_in[2], HD, DM, 3);
  make_map(enc, &op.wo, d_in[5], DM, HD, 5); make_map(enc, &op.wo2, d_in[5], DM, HD, 0);
  make_map(enc, &op.wb, d_in[8], 1920, DM, 5); make_map(enc, &op.wb2, d_in[8], 1920, DM, 0);
  op.gap = 17; op.share = 20; op.look = 20; op.gap2 = 0; op.pol = 1; op.slow_n = 8; op.slow_gap = 23;

  const Weights wa = {{(const uint8_t*)d_in[3], (const uint8_t*)d_in[4], (const uint8_t*)d_in[2], (const uint8_t*)d_in[5]}}, none = {};
  launch(first_kernel, 132, 384, 128 * 1024, 1, false, x, (const uint4*)d_in[9], wa);
  for (int layer = 0; layer < (MODE(4) ? 1 : 2); layer++) {
    ch.layer = ch.d2b = op.layer = layer;
    launch(chain_kernel, 96, 256, CH_SMEM, 3, true, ch);
    launch(post_kernel, MODE(3) ? 36 : 132, 384, OP_SMEM, 1, !MODE(1), op);
    const AbParams ab = {layer == 0 ? wa : none, (uint32_t*)sym(g_bo) + layer * 128, layer == 0 ? nullptr : (uint32_t*)d_out};
    launch(attn_b_kernel, 128, AB_T + 32, AB_SMEM, 1, true, ab);
  }
}
```

```cpp
#include <cuda_runtime.h>
#include <cuda_bf16.h>
#include <cuda.h>
#include <stdint.h>

namespace {

constexpr int SEQ = 2048, DM = 640, HD = 6144, NSEG = 64;
constexpr int SPIN_LIMIT = 1 << 20;

__device__ __align__(128) uint2 g_x[SEQ * DM / 4];
__device__ __align__(128) uint32_t g_of[SEQ * DM / 2];
__device__ __align__(128) uint4 g_wb[DM * DM / 8];
__device__ __align__(16) float2 g_stat[16 * 8 * 128];
__device__ uint32_t g_bo[8 * 32];
__device__ __align__(128) uint4 g_q[SEQ * HD / 8];
__device__ __align__(128) uint32_t g_o[SEQ * HD / 2];
constexpr int KV_BYTES = 5120, KV_M = 4096, KV_V = NSEG * KV_BYTES;
__device__ __align__(128) uint8_t g_kv[96 * 2 * NSEG * KV_BYTES];
__device__ __align__(128) uint32_t g_xc[SEQ * DM / 2];
#define OP_B4 7
#define OP_B8 10
#define OP_B16 16
#define QA_END 11
__host__ __device__ constexpr int op_split(int b) { return b < OP_B4 ? 2 : b < OP_B8 ? 4 : b < OP_B16 ? 8 : 16; }
#define AB_PF 3
#define AB_PF0 0
#define AB_PFD 5000
#define W_PROMO CU_TENSOR_MAP_L2_PROMOTION_L2_128B
#define OP_EARLY 1
#define ATT_LOOK 1
#define PR_FIN 1
#define PR_ATT 0
#define PR_OP 2
#define PRE_MAX PS
#define BQ_RUSH 16
#define OEF 0
#define BQ_HOLD 6
#define WEF 1
#define FK_REP 4
#define FK_PF 1
#define BQ_160 10
#define BQ_80 16
#define OP_160 14
__host__ __device__ constexpr int op_width(int b) { return b < OP_160 ? 320 : 160; }
__host__ __device__ constexpr int bq_width(int b) { return b < BQ_160 ? 320 : b < BQ_80 ? 160 : 80; }
__device__ __align__(128) uint2 g_part[16 * 16 * 16 * 40 * 32];
__device__ __align__(128) uint32_t g_xn[SEQ * DM / 2];
constexpr int SY_Q = 128, SY_T = 160, SY_QC = 192, SY_N = 193;
__device__ __align__(16) uint32_t g_sync[SY_N];
constexpr int NSLOT = 92;
__device__ uint32_t g_pool[(NSLOT + 2) * 2048];
__device__ int g_smpart[256], g_orient[NSLOT];
__device__ uint32_t g_smclk[256], g_smuse[256];
__device__ uint32_t g_bqkv[3 * 32 * 256 * 96];

#define ABT(L, i)
#define PST(i)
#define MODE_D(b) 0
#define DELAY(d)
#define XT(i)
#define MISS(k, n)
#define PRO(i)
#define TRACE(w)
#define ITEM(code, w)
#define TR(i, v)
#define TM(i)
#define TM1(i)
#define TMD(i, dep)
#define TMV(i, at, v)

__device__ __forceinline__ uint32_t gtime() { uint32_t c; asm volatile("mov.u32 %0, %%globaltimer_lo;" : "=r"(c) :: "memory"); return c; }
__device__ __forceinline__ uint32_t clk32() { uint32_t c; asm volatile("mov.u32 %0, %%clock;" : "=r"(c) :: "memory"); return c; }
__device__ __forceinline__ uint32_t s2u(const void* p) { return (uint32_t)__cvta_generic_to_shared(p); }
__device__ __forceinline__ uint32_t pack2(float a, float b) {
  uint32_t r; asm("cvt.rn.bf16x2.f32 %0, %1, %2;" : "=r"(r) : "f"(b), "f"(a)); return r; }
__device__ __forceinline__ float bf_lo(uint32_t w) { return __uint_as_float(w << 16); }
__device__ __forceinline__ float bf_hi(uint32_t w) { return __uint_as_float(w & 0xffff0000u); }
__device__ __forceinline__ uint2 pack4(float4 v) { return make_uint2(pack2(v.x, v.y), pack2(v.z, v.w)); }
__device__ __forceinline__ float4 unpack4(uint2 w) { return make_float4(bf_lo(w.x), bf_hi(w.x), bf_lo(w.y), bf_hi(w.y)); }
__device__ __forceinline__ float ex2(float x) { float y; asm("ex2.approx.ftz.f32 %0, %1;" : "=f"(y) : "f"(x)); return y; }

__device__ __forceinline__ void mbar_init(uint32_t bar, uint32_t n) {
  asm volatile("mbarrier.init.shared::cta.b64 [%0], %1;" :: "r"(bar), "r"(n) : "memory"); }
__device__ __forceinline__ void mbar_expect(uint32_t bar, uint32_t bytes) {
  asm volatile("mbarrier.arrive.expect_tx.shared::cta.b64 _, [%0], %1;" :: "r"(bar), "r"(bytes) : "memory"); }
__device__ __forceinline__ void mbar_arrive(uint32_t bar) {
  asm volatile("mbarrier.arrive.shared::cta.b64 _, [%0];" :: "r"(bar) : "memory"); }
__device__ __forceinline__ void mbar_wait(uint32_t bar, uint32_t ph) {
  asm volatile("{.reg .pred p; .reg .u32 n; mov.u32 n, 0;\n"
               "W: mbarrier.try_wait.parity.shared::cta.b64 p, [%0], %1; @p bra D;\n"
               "add.u32 n, n, 1; setp.gt.u32 p, n, %2; @p trap; bra W;\n"
               "D: }" :: "r"(bar), "r"(ph), "n"(SPIN_LIMIT) : "memory");
}
__device__ __forceinline__ void mbar_wait_cluster(uint32_t bar, uint32_t ph) {
  asm volatile("{.reg .pred p; .reg .u32 n; mov.u32 n, 0;\n"
               "W: mbarrier.try_wait.parity.acquire.cluster.shared::cta.b64 p, [%0], %1; @p bra D;\n"
               "add.u32 n, n, 1; setp.gt.u32 p, n, %2; @p trap; bra W;\n"
               "D: }" :: "r"(bar), "r"(ph), "n"(SPIN_LIMIT) : "memory");
}
__device__ __forceinline__ void spin_guard(int& n) {
  asm volatile("{.reg .pred p; add.s32 %0, %0, 1; setp.gt.s32 p, %0, %1; @p trap;}" : "+r"(n) : "n"(SPIN_LIMIT));
}
__device__ __forceinline__ void pdl_wait() { asm volatile("griddepcontrol.wait;" ::: "memory"); TRACE(1); }
__device__ __forceinline__ void pdl_launch() { asm volatile("griddepcontrol.launch_dependents;" ::: "memory"); }
__device__ __forceinline__ uint32_t ld_acquire(const uint32_t* p) { uint32_t v; asm volatile("ld.acquire.gpu.global.u32 %0, [%1];" : "=r"(v) : "l"(p) : "memory"); return v; }
__device__ __forceinline__ void red_release(uint32_t* p, uint32_t v) { asm volatile("red.release.gpu.global.add.u32 [%0], %1;" :: "l"(p), "r"(v) : "memory"); }
__device__ __forceinline__ void red_relaxed(uint32_t* p, uint32_t v) { asm volatile("red.relaxed.gpu.global.add.u32 [%0], %1;" :: "l"(p), "r"(v) : "memory"); }
__device__ __forceinline__ void fence_async_global() { asm volatile("fence.proxy.async.global;" ::: "memory"); }
__device__ __forceinline__ void fence_async() { asm volatile("fence.proxy.async.shared::cta;" ::: "memory"); }
__device__ __forceinline__ void bar_sync(int id, int n) { asm volatile("bar.sync %0, %1;" :: "r"(id), "r"(n) : "memory"); }
__device__ __forceinline__ void bar_arrive(int id, int n) { asm volatile("bar.arrive %0, %1;" :: "r"(id), "r"(n) : "memory"); }
__device__ __forceinline__ void tma_load(uint32_t dst, const CUtensorMap* m, int c0, int c1, uint32_t bar) {
  asm volatile("cp.async.bulk.tensor.2d.shared::cluster.global.mbarrier::complete_tx::bytes [%0], [%1, {%3, %4}], [%2];"
               :: "r"(dst), "l"(m), "r"(bar), "r"(c0), "r"(c1) : "memory"); }
template <bool STREAM = false>
__device__ __forceinline__ void tma_load3(uint32_t dst, const CUtensorMap* m, int c0, int c1, uint32_t bar) {
  if (STREAM)
    asm volatile("{.reg .b64 pol; createpolicy.fractional.L2::evict_first.b64 pol, 1.0;\n"
                 "cp.async.bulk.tensor.3d.shared::cluster.global.mbarrier::complete_tx::bytes.L2::cache_hint [%0], [%1, {%3, %4, 0}], [%2], pol;}"
                 :: "r"(dst), "l"(m), "r"(bar), "r"(c0), "r"(c1) : "memory");
  else
  asm volatile("cp.async.bulk.tensor.3d.shared::cluster.global.mbarrier::complete_tx::bytes [%0], [%1, {%3, %4, 0}], [%2];"
               :: "r"(dst), "l"(m), "r"(bar), "r"(c0), "r"(c1) : "memory"); }
__device__ __forceinline__ void tma_load3z(uint32_t dst, const CUtensorMap* m, int c1, int c2, uint32_t bar) {
  asm volatile("cp.async.bulk.tensor.3d.shared::cluster.global.mbarrier::complete_tx::bytes [%0], [%1, {0, %3, %4}], [%2];"
               :: "r"(dst), "l"(m), "r"(bar), "r"(c1), "r"(c2) : "memory"); }
__device__ __forceinline__ void tma_store(const CUtensorMap* m, uint32_t src, int c0, int c1) {
  asm volatile("cp.async.bulk.tensor.2d.global.shared::cta.bulk_group [%0, {%2, %3}], [%1];"
               :: "l"(m), "r"(src), "r"(c0), "r"(c1) : "memory"); }
__device__ __forceinline__ void tma_store_stream(const CUtensorMap* m, uint32_t src, int c0, int c1) {
  asm volatile("{.reg .b64 pol; createpolicy.fractional.L2::evict_first.b64 pol, 1.0;\n"
               "cp.async.bulk.tensor.2d.global.shared::cta.bulk_group.L2::cache_hint [%0, {%2, %3}], [%1], pol;}"
               :: "l"(m), "r"(src), "r"(c0), "r"(c1) : "memory"); }
__device__ __forceinline__ void bulk_load(uint32_t dst, const void* src, uint32_t bytes, uint32_t bar) {
  asm volatile("cp.async.bulk.shared::cluster.global.mbarrier::complete_tx::bytes [%0], [%1], %2, [%3];"
               :: "r"(dst), "l"(src), "r"(bytes), "r"(bar) : "memory"); }
__device__ __forceinline__ void bulk_load_last(uint32_t dst, const void* src, uint32_t bytes, uint32_t bar) {
  asm volatile("{.reg .b64 pol; createpolicy.fractional.L2::evict_first.b64 pol, 1.0;\n"
               "cp.async.bulk.shared::cluster.global.mbarrier::complete_tx::bytes.L2::cache_hint [%0], [%1], %2, [%3], pol;}"
               :: "r"(dst), "l"(src), "r"(bytes), "r"(bar) : "memory"); }
__device__ __forceinline__ void tma_load_last(uint32_t dst, const CUtensorMap* m, int c0, int c1, uint32_t bar) {
  asm volatile("{.reg .b64 pol; createpolicy.fractional.L2::evict_first.b64 pol, 1.0;\n"
               "cp.async.bulk.tensor.2d.shared::cluster.global.mbarrier::complete_tx::bytes.L2::cache_hint [%0], [%1, {%3, %4}], [%2], pol;}"
               :: "r"(dst), "l"(m), "r"(bar), "r"(c0), "r"(c1) : "memory"); }
__device__ __forceinline__ void bulk_send(uint32_t dst, uint32_t src, uint32_t bytes, uint32_t bar) {
  asm volatile("cp.async.bulk.shared::cluster.shared::cta.mbarrier::complete_tx::bytes [%0], [%1], %2, [%3];"
               :: "r"(dst), "r"(src), "r"(bytes), "r"(bar) : "memory"); }
__device__ __forceinline__ void bulk_store(void* dst, uint32_t src, uint32_t bytes) {
  asm volatile("cp.async.bulk.global.shared::cta.bulk_group [%0], [%1], %2;" :: "l"(dst), "r"(src), "r"(bytes) : "memory"); }
__device__ __forceinline__ void bulk_commit() { asm volatile("cp.async.bulk.commit_group;" ::: "memory"); }
template <int N> __device__ __forceinline__ void bulk_wait_read() { asm volatile("cp.async.bulk.wait_group.read %0;" :: "n"(N) : "memory"); }
template <int N> __device__ __forceinline__ void bulk_wait() { asm volatile("cp.async.bulk.wait_group %0;" :: "n"(N) : "memory"); }

__device__ __forceinline__ uint64_t mkdesc(uint32_t addr, uint32_t lbo, uint32_t sbo, uint32_t sw) {
  return (uint64_t)((addr & 0x3FFFF) >> 4) | ((uint64_t)(lbo >> 4) << 16) | ((uint64_t)(sbo >> 4) << 32) | ((uint64_t)sw << 62); }
__device__ __forceinline__ void wg_fence() { asm volatile("wgmma.fence.sync.aligned;" ::: "memory"); }
__device__ __forceinline__ void wg_commit() { asm volatile("wgmma.commit_group.sync.aligned;" ::: "memory"); }
template <int N> __device__ __forceinline__ void wg_wait() { asm volatile("wgmma.wait_group.sync.aligned %0;" :: "n"(N) : "memory"); }
template <int N> __device__ __forceinline__ void reg_fence(float* d) {
#pragma unroll
  for (int i = 0; i < N; i++) asm volatile("" : "+f"(d[i]) :: "memory");
}

__device__ __forceinline__ void mma16(float* d, uint32_t a0, uint32_t a1, uint32_t a2, uint32_t a3, uint32_t b0, uint32_t b1) {
  asm volatile("mma.sync.aligned.m16n8k16.row.col.f32.bf16.bf16.f32 {%0,%1,%2,%3},{%4,%5,%6,%7},{%8,%9},{%0,%1,%2,%3};"
               : "+f"(d[0]), "+f"(d[1]), "+f"(d[2]), "+f"(d[3]) : "r"(a0), "r"(a1), "r"(a2), "r"(a3), "r"(b0), "r"(b1)); }
__device__ __forceinline__ void mma8(float* d, uint32_t a0, uint32_t a1, uint32_t b0) {
  asm volatile("mma.sync.aligned.m16n8k8.row.col.f32.bf16.bf16.f32 {%0,%1,%2,%3},{%4,%5},{%6},{%0,%1,%2,%3};"
               : "+f"(d[0]), "+f"(d[1]), "+f"(d[2]), "+f"(d[3]) : "r"(a0), "r"(a1), "r"(b0)); }
__device__ __forceinline__ void ldsm4(uint32_t* r, uint32_t a) {
  asm volatile("ldmatrix.sync.aligned.m8n8.x4.shared.b16 {%0,%1,%2,%3},[%4];" : "=r"(r[0]), "=r"(r[1]), "=r"(r[2]), "=r"(r[3]) : "r"(a) : "memory"); }
__device__ __forceinline__ void ldsm4t(uint32_t* r, uint32_t a) {
  asm volatile("ldmatrix.sync.aligned.m8n8.x4.trans.shared.b16 {%0,%1,%2,%3},[%4];" : "=r"(r[0]), "=r"(r[1]), "=r"(r[2]), "=r"(r[3]) : "r"(a) : "memory"); }
__device__ __forceinline__ void ldsm2(uint32_t* r, uint32_t a) {
  asm volatile("ldmatrix.sync.aligned.m8n8.x2.shared.b16 {%0,%1},[%2];" : "=r"(r[0]), "=r"(r[1]) : "r"(a) : "memory"); }
__device__ __forceinline__ void stsm4(uint32_t a, uint32_t r0, uint32_t r1, uint32_t r2, uint32_t r3) {
  asm volatile("stmatrix.sync.aligned.m8n8.x4.shared.b16 [%0], {%1,%2,%3,%4};" :: "r"(a), "r"(r0), "r"(r1), "r"(r2), "r"(r3) : "memory"); }
__device__ __forceinline__ void stsm2t(uint32_t a, uint32_t r0, uint32_t r1) {
  asm volatile("stmatrix.sync.aligned.m8n8.x2.trans.shared.b16 [%0], {%1,%2};" :: "r"(a), "r"(r0), "r"(r1) : "memory"); }
__device__ __forceinline__ void stsm4t(uint32_t a, uint32_t r0, uint32_t r1, uint32_t r2, uint32_t r3) {
  asm volatile("stmatrix.sync.aligned.m8n8.x4.trans.shared.b16 [%0], {%1,%2,%3,%4};" :: "r"(a), "r"(r0), "r"(r1), "r"(r2), "r"(r3) : "memory"); }
__device__ __forceinline__ void st_async128(uint32_t a, uint4 v, uint32_t bar) {
  asm volatile("st.async.shared::cluster.mbarrier::complete_tx::bytes.v4.b32 [%0], {%1,%2,%3,%4}, [%5];" :: "r"(a), "r"(v.x), "r"(v.y), "r"(v.z), "r"(v.w), "r"(bar) : "memory"); }
__device__ __forceinline__ void sts32(uint32_t a, uint32_t v) { asm volatile("st.shared.b32 [%0], %1;" :: "r"(a), "r"(v) : "memory"); }
__device__ __forceinline__ void sts64f(uint32_t a, float x, float y) { asm volatile("st.shared.v2.f32 [%0], {%1,%2};" :: "r"(a), "f"(x), "f"(y) : "memory"); }
__device__ __forceinline__ void sts128(uint32_t a, uint4 v) {
  asm volatile("st.shared.v4.b32 [%0], {%1,%2,%3,%4};" :: "r"(a), "r"(v.x), "r"(v.y), "r"(v.z), "r"(v.w) : "memory"); }
__device__ __forceinline__ void sts128f(uint32_t a, float x, float y, float z, float w) {
  asm volatile("st.shared.v4.f32 [%0], {%1,%2,%3,%4};" :: "r"(a), "f"(x), "f"(y), "f"(z), "f"(w) : "memory"); }
__device__ __forceinline__ float lds32f(uint32_t a) { float v; asm volatile("ld.shared.f32 %0, [%1];" : "=f"(v) : "r"(a) : "memory"); return v; }
__device__ __forceinline__ float2 lds64f(uint32_t a) { float2 v; asm volatile("ld.shared.v2.f32 {%0,%1}, [%2];" : "=f"(v.x), "=f"(v.y) : "r"(a) : "memory"); return v; }
__device__ __forceinline__ float4 lds128f(uint32_t a) {
  float4 v; asm volatile("ld.shared.v4.f32 {%0,%1,%2,%3}, [%4];" : "=f"(v.x), "=f"(v.y), "=f"(v.z), "=f"(v.w) : "r"(a) : "memory"); return v; }
__device__ __forceinline__ uint4 lds128(uint32_t a) {
  uint4 v; asm volatile("ld.shared.v4.b32 {%0,%1,%2,%3}, [%4];" : "=r"(v.x), "=r"(v.y), "=r"(v.z), "=r"(v.w) : "r"(a) : "memory"); return v; }
__device__ __forceinline__ uint4 ldg_strong128(const void* p) {
  uint4 v; asm volatile("ld.relaxed.gpu.global.v4.u32 {%0,%1,%2,%3}, [%4];" : "=r"(v.x), "=r"(v.y), "=r"(v.z), "=r"(v.w) : "l"(p) : "memory"); return v; }
__device__ __forceinline__ void stg_strong32(void* p, uint32_t v) { asm volatile("st.relaxed.gpu.global.u32 [%0], %1;" :: "l"(p), "r"(v) : "memory"); }
__device__ __forceinline__ void stg_strong16(void* p, uint32_t v) { asm volatile("st.relaxed.gpu.global.u16 [%0], %1;" :: "l"(p), "h"((uint16_t)v) : "memory"); }
__device__ __forceinline__ void stg_strong128(void* p, uint4 v) {
  asm volatile("st.relaxed.gpu.global.v4.u32 [%0], {%1,%2,%3,%4};" :: "l"(p), "r"(v.x), "r"(v.y), "r"(v.z), "r"(v.w) : "memory"); }
__device__ __forceinline__ uint32_t mapa(uint32_t a, uint32_t r) {
  uint32_t o; asm("mapa.shared::cluster.u32 %0, %1, %2;" : "=r"(o) : "r"(a), "r"(r)); return o; }
__device__ __forceinline__ void st_async2f(uint32_t a, float x, float y, uint32_t bar) {
  asm volatile("st.async.shared::cluster.mbarrier::complete_tx::bytes.v2.f32 [%0], {%1,%2}, [%3];" :: "r"(a), "f"(x), "f"(y), "r"(bar) : "memory"); }
__device__ __forceinline__ void st_async32(uint32_t a, uint32_t x, uint32_t bar) {
  asm volatile("st.async.shared::cluster.mbarrier::complete_tx::bytes.b32 [%0], %1, [%2];" :: "r"(a), "r"(x), "r"(bar) : "memory"); }
__device__ __forceinline__ uint32_t lds32(uint32_t a) { uint32_t v; asm volatile("ld.shared.b32 %0, [%1];" : "=r"(v) : "r"(a) : "memory"); return v; }
__device__ __forceinline__ void st_async64(uint32_t a, uint32_t x, uint32_t y, uint32_t bar) {
  asm volatile("st.async.shared::cluster.mbarrier::complete_tx::bytes.v2.b32 [%0], {%1,%2}, [%3];" :: "r"(a), "r"(x), "r"(y), "r"(bar) : "memory"); }
__device__ __forceinline__ uint2 lds64(uint32_t a) { uint2 v; asm volatile("ld.shared.v2.b32 {%0,%1}, [%2];" : "=r"(v.x), "=r"(v.y) : "r"(a) : "memory"); return v; }
__device__ __forceinline__ void sts64(uint32_t a, uint32_t x, uint32_t y) { asm volatile("st.shared.v2.b32 [%0], {%1,%2};" :: "r"(a), "r"(x), "r"(y) : "memory"); }
__device__ __forceinline__ uint32_t ldg_strong32(const void* p) { uint32_t v; asm volatile("ld.relaxed.gpu.global.u32 %0, [%1];" : "=r"(v) : "l"(p) : "memory"); return v; }
__device__ __forceinline__ uint32_t transpose8(uint32_t x) { uint32_t r; asm volatile("movmatrix.sync.aligned.m8n8.trans.b16 %0, %1;" : "=r"(r) : "r"(x)); return r; }
__device__ __forceinline__ uint32_t hadd2(uint32_t a, uint32_t b) { uint32_t r; asm("add.rn.bf16x2 %0, %1, %2;" : "=r"(r) : "r"(a), "r"(b)); return r; }
__device__ __forceinline__ uint32_t min4(uint4 v) { return min(__vimin3_u32(v.x, v.y, v.z), v.w); }

__device__ __forceinline__ void wg_ss192_01(float* d, uint64_t da, uint64_t db, int sd) {
  asm volatile("{.reg .pred p; setp.ne.b32 p, %98, 0;\n"
    "wgmma.mma_async.sync.aligned.m64n192k16.f32.bf16.bf16 {%0,%1,%2,%3,%4,%5,%6,%7,%8,%9,%10,%11,%12,%13,%14,%15,%16,%17,%18,%19,%20,%21,%22,%23,%24,%25,%26,%27,%28,%29,%30,%31,%32,%33,%34,%35,%36,%37,%38,%39,%40,%41,%42,%43,%44,%45,%46,%47,%48,%49,%50,%51,%52,%53,%54,%55,%56,%57,%58,%59,%60,%61,%62,%63,%64,%65,%66,%67,%68,%69,%70,%71,%72,%73,%74,%75,%76,%77,%78,%79,%80,%81,%82,%83,%84,%85,%86,%87,%88,%89,%90,%91,%92,%93,%94,%95}, %96, %97, p, 1, 1, 0, 1;}"
    : "+f"(d[0]),"+f"(d[1]),"+f"(d[2]),"+f"(d[3]),"+f"(d[4]),"+f"(d[5]),"+f"(d[6]),"+f"(d[7]),"+f"(d[8]),"+f"(d[9]),"+f"(d[10]),"+f"(d[11]),"+f"(d[12]),"+f"(d[13]),"+f"(d[14]),"+f"(d[15]),"+f"(d[16]),"+f"(d[17]),"+f"(d[18]),"+f"(d[19]),"+f"(d[20]),"+f"(d[21]),"+f"(d[22]),"+f"(d[23]),"+f"(d[24]),"+f"(d[25]),"+f"(d[26]),"+f"(d[27]),"+f"(d[28]),"+f"(d[29]),"+f"(d[30]),"+f"(d[31]),"+f"(d[32]),"+f"(d[33]),"+f"(d[34]),"+f"(d[35]),"+f"(d[36]),"+f"(d[37]),"+f"(d[38]),"+f"(d[39]),"+f"(d[40]),"+f"(d[41]),"+f"(d[42]),"+f"(d[43]),"+f"(d[44]),"+f"(d[45]),"+f"(d[46]),"+f"(d[47]),"+f"(d[48]),"+f"(d[49]),"+f"(d[50]),"+f"(d[51]),"+f"(d[52]),"+f"(d[53]),"+f"(d[54]),"+f"(d[55]),"+f"(d[56]),"+f"(d[57]),"+f"(d[58]),"+f"(d[59]),"+f"(d[60]),"+f"(d[61]),"+f"(d[62]),"+f"(d[63]),"+f"(d[64]),"+f"(d[65]),"+f"(d[66]),"+f"(d[67]),"+f"(d[68]),"+f"(d[69]),"+f"(d[70]),"+f"(d[71]),"+f"(d[72]),"+f"(d[73]),"+f"(d[74]),"+f"(d[75]),"+f"(d[76]),"+f"(d[77]),"+f"(d[78]),"+f"(d[79]),"+f"(d[80]),"+f"(d[81]),"+f"(d[82]),"+f"(d[83]),"+f"(d[84]),"+f"(d[85]),"+f"(d[86]),"+f"(d[87]),"+f"(d[88]),"+f"(d[89]),"+f"(d[90]),"+f"(d[91]),"+f"(d[92]),"+f"(d[93]),"+f"(d[94]),"+f"(d[95])
    : "l"(da), "l"(db), "r"(sd));
}
__device__ __forceinline__ void wg_ss128_01(float* d, uint64_t da, uint64_t db, int sd) {
  asm volatile("{.reg .pred p; setp.ne.b32 p, %66, 0;\n"
    "wgmma.mma_async.sync.aligned.m64n128k16.f32.bf16.bf16 {%0,%1,%2,%3,%4,%5,%6,%7,%8,%9,%10,%11,%12,%13,%14,%15,%16,%17,%18,%19,%20,%21,%22,%23,%24,%25,%26,%27,%28,%29,%30,%31,%32,%33,%34,%35,%36,%37,%38,%39,%40,%41,%42,%43,%44,%45,%46,%47,%48,%49,%50,%51,%52,%53,%54,%55,%56,%57,%58,%59,%60,%61,%62,%63}, %64, %65, p, 1, 1, 0, 1;}"
    : "+f"(d[0]),"+f"(d[1]),"+f"(d[2]),"+f"(d[3]),"+f"(d[4]),"+f"(d[5]),"+f"(d[6]),"+f"(d[7]),"+f"(d[8]),"+f"(d[9]),"+f"(d[10]),"+f"(d[11]),"+f"(d[12]),"+f"(d[13]),"+f"(d[14]),"+f"(d[15]),"+f"(d[16]),"+f"(d[17]),"+f"(d[18]),"+f"(d[19]),"+f"(d[20]),"+f"(d[21]),"+f"(d[22]),"+f"(d[23]),"+f"(d[24]),"+f"(d[25]),"+f"(d[26]),"+f"(d[27]),"+f"(d[28]),"+f"(d[29]),"+f"(d[30]),"+f"(d[31]),"+f"(d[32]),"+f"(d[33]),"+f"(d[34]),"+f"(d[35]),"+f"(d[36]),"+f"(d[37]),"+f"(d[38]),"+f"(d[39]),"+f"(d[40]),"+f"(d[41]),"+f"(d[42]),"+f"(d[43]),"+f"(d[44]),"+f"(d[45]),"+f"(d[46]),"+f"(d[47]),"+f"(d[48]),"+f"(d[49]),"+f"(d[50]),"+f"(d[51]),"+f"(d[52]),"+f"(d[53]),"+f"(d[54]),"+f"(d[55]),"+f"(d[56]),"+f"(d[57]),"+f"(d[58]),"+f"(d[59]),"+f"(d[60]),"+f"(d[61]),"+f"(d[62]),"+f"(d[63])
    : "l"(da), "l"(db), "r"(sd));
}
__device__ __forceinline__ void wg_ss160_01(float* d, uint64_t da, uint64_t db, int sd) {
  asm volatile("{.reg .pred p; setp.ne.b32 p, %82, 0;\n"
    "wgmma.mma_async.sync.aligned.m64n160k16.f32.bf16.bf16 {%0,%1,%2,%3,%4,%5,%6,%7,%8,%9,%10,%11,%12,%13,%14,%15,%16,%17,%18,%19,%20,%21,%22,%23,%24,%25,%26,%27,%28,%29,%30,%31,%32,%33,%34,%35,%36,%37,%38,%39,%40,%41,%42,%43,%44,%45,%46,%47,%48,%49,%50,%51,%52,%53,%54,%55,%56,%57,%58,%59,%60,%61,%62,%63,%64,%65,%66,%67,%68,%69,%70,%71,%72,%73,%74,%75,%76,%77,%78,%79}, %80, %81, p, 1, 1, 0, 1;}"
    : "+f"(d[0]),"+f"(d[1]),"+f"(d[2]),"+f"(d[3]),"+f"(d[4]),"+f"(d[5]),"+f"(d[6]),"+f"(d[7]),"+f"(d[8]),"+f"(d[9]),"+f"(d[10]),"+f"(d[11]),"+f"(d[12]),"+f"(d[13]),"+f"(d[14]),"+f"(d[15]),"+f"(d[16]),"+f"(d[17]),"+f"(d[18]),"+f"(d[19]),"+f"(d[20]),"+f"(d[21]),"+f"(d[22]),"+f"(d[23]),"+f"(d[24]),"+f"(d[25]),"+f"(d[26]),"+f"(d[27]),"+f"(d[28]),"+f"(d[29]),"+f"(d[30]),"+f"(d[31]),"+f"(d[32]),"+f"(d[33]),"+f"(d[34]),"+f"(d[35]),"+f"(d[36]),"+f"(d[37]),"+f"(d[38]),"+f"(d[39]),"+f"(d[40]),"+f"(d[41]),"+f"(d[42]),"+f"(d[43]),"+f"(d[44]),"+f"(d[45]),"+f"(d[46]),"+f"(d[47]),"+f"(d[48]),"+f"(d[49]),"+f"(d[50]),"+f"(d[51]),"+f"(d[52]),"+f"(d[53]),"+f"(d[54]),"+f"(d[55]),"+f"(d[56]),"+f"(d[57]),"+f"(d[58]),"+f"(d[59]),"+f"(d[60]),"+f"(d[61]),"+f"(d[62]),"+f"(d[63]),"+f"(d[64]),"+f"(d[65]),"+f"(d[66]),"+f"(d[67]),"+f"(d[68]),"+f"(d[69]),"+f"(d[70]),"+f"(d[71]),"+f"(d[72]),"+f"(d[73]),"+f"(d[74]),"+f"(d[75]),"+f"(d[76]),"+f"(d[77]),"+f"(d[78]),"+f"(d[79])
    : "l"(da), "l"(db), "r"(sd));
}
__device__ __forceinline__ void wg_ss80_01(float* d, uint64_t da, uint64_t db, int sd) {
  asm volatile("{.reg .pred p; setp.ne.b32 p, %42, 0;\n"
    "wgmma.mma_async.sync.aligned.m64n80k16.f32.bf16.bf16 {%0,%1,%2,%3,%4,%5,%6,%7,%8,%9,%10,%11,%12,%13,%14,%15,%16,%17,%18,%19,%20,%21,%22,%23,%24,%25,%26,%27,%28,%29,%30,%31,%32,%33,%34,%35,%36,%37,%38,%39}, %40, %41, p, 1, 1, 0, 1;}"
    : "+f"(d[0]),"+f"(d[1]),"+f"(d[2]),"+f"(d[3]),"+f"(d[4]),"+f"(d[5]),"+f"(d[6]),"+f"(d[7]),"+f"(d[8]),"+f"(d[9]),"+f"(d[10]),"+f"(d[11]),"+f"(d[12]),"+f"(d[13]),"+f"(d[14]),"+f"(d[15]),"+f"(d[16]),"+f"(d[17]),"+f"(d[18]),"+f"(d[19]),"+f"(d[20]),"+f"(d[21]),"+f"(d[22]),"+f"(d[23]),"+f"(d[24]),"+f"(d[25]),"+f"(d[26]),"+f"(d[27]),"+f"(d[28]),"+f"(d[29]),"+f"(d[30]),"+f"(d[31]),"+f"(d[32]),"+f"(d[33]),"+f"(d[34]),"+f"(d[35]),"+f"(d[36]),"+f"(d[37]),"+f"(d[38]),"+f"(d[39])
    : "l"(da), "l"(db), "r"(sd));
}
__device__ __forceinline__ void wg_rs32_00(float* d, uint32_t a0, uint32_t a1, uint32_t a2, uint32_t a3, uint64_t db, int sd) {
  asm volatile("{.reg .pred p; setp.ne.b32 p, %21, 0;\n"
    "wgmma.mma_async.sync.aligned.m64n32k16.f32.bf16.bf16 {%0,%1,%2,%3,%4,%5,%6,%7,%8,%9,%10,%11,%12,%13,%14,%15}, {%16,%17,%18,%19}, %20, p, 1, 1, 0;}"
    : "+f"(d[0]),"+f"(d[1]),"+f"(d[2]),"+f"(d[3]),"+f"(d[4]),"+f"(d[5]),"+f"(d[6]),"+f"(d[7]),"+f"(d[8]),"+f"(d[9]),"+f"(d[10]),"+f"(d[11]),"+f"(d[12]),"+f"(d[13]),"+f"(d[14]),"+f"(d[15])
    : "r"(a0), "r"(a1), "r"(a2), "r"(a3), "l"(db), "r"(sd));
}
__device__ __forceinline__ void wg_rs64_00(float* d, uint32_t a0, uint32_t a1, uint32_t a2, uint32_t a3, uint64_t db, int sd) {
  asm volatile("{.reg .pred p; setp.ne.b32 p, %37, 0;\n"
    "wgmma.mma_async.sync.aligned.m64n64k16.f32.bf16.bf16 {%0,%1,%2,%3,%4,%5,%6,%7,%8,%9,%10,%11,%12,%13,%14,%15,%16,%17,%18,%19,%20,%21,%22,%23,%24,%25,%26,%27,%28,%29,%30,%31}, {%32,%33,%34,%35}, %36, p, 1, 1, 0;}"
    : "+f"(d[0]),"+f"(d[1]),"+f"(d[2]),"+f"(d[3]),"+f"(d[4]),"+f"(d[5]),"+f"(d[6]),"+f"(d[7]),"+f"(d[8]),"+f"(d[9]),"+f"(d[10]),"+f"(d[11]),"+f"(d[12]),"+f"(d[13]),"+f"(d[14]),"+f"(d[15]),"+f"(d[16]),"+f"(d[17]),"+f"(d[18]),"+f"(d[19]),"+f"(d[20]),"+f"(d[21]),"+f"(d[22]),"+f"(d[23]),"+f"(d[24]),"+f"(d[25]),"+f"(d[26]),"+f"(d[27]),"+f"(d[28]),"+f"(d[29]),"+f"(d[30]),"+f"(d[31])
    : "r"(a0), "r"(a1), "r"(a2), "r"(a3), "l"(db), "r"(sd));
}
__device__ __forceinline__ void wg_rs24_01(float* d, uint32_t a0, uint32_t a1, uint32_t a2, uint32_t a3, uint64_t db, int sd) {
  asm volatile("{.reg .pred p; setp.ne.b32 p, %17, 0;\n"
    "wgmma.mma_async.sync.aligned.m64n24k16.f32.bf16.bf16 {%0,%1,%2,%3,%4,%5,%6,%7,%8,%9,%10,%11}, {%12,%13,%14,%15}, %16, p, 1, 1, 1;}"
    : "+f"(d[0]),"+f"(d[1]),"+f"(d[2]),"+f"(d[3]),"+f"(d[4]),"+f"(d[5]),"+f"(d[6]),"+f"(d[7]),"+f"(d[8]),"+f"(d[9]),"+f"(d[10]),"+f"(d[11])
    : "r"(a0), "r"(a1), "r"(a2), "r"(a3), "l"(db), "r"(sd));
}

#define AB_POLY 0xae
__device__ __forceinline__ constexpr bool poly_group(int group) { return (AB_POLY >> (group & 7)) & 1; }

template <int V> struct Int { static constexpr int value = V; };

template <int NG>
__device__ __forceinline__ void ln_stats(const float4 (&v)[NG][5], uint32_t scratch, float (&mean)[NG], float (&rs)[NG]) {
  const int warp = threadIdx.x >> 5, lane = threadIdx.x & 31;
#pragma unroll
  for (int r = 0; r < NG; r++) {
    float s = 0.f, q = 0.f;
#pragma unroll
    for (int i = 0; i < 5; i++) s += (v[r][i].x + v[r][i].y) + (v[r][i].z + v[r][i].w);
    s += __shfl_xor_sync(~0u, s, 1); s += __shfl_xor_sync(~0u, s, 2);
    s *= 1.f / 80;
#pragma unroll
    for (int i = 0; i < 5; i++) {
      const float x = v[r][i].x - s, y = v[r][i].y - s, z = v[r][i].z - s, w = v[r][i].w - s;
      q += (x * x + y * y) + (z * z + w * w);
    }
    q += __shfl_xor_sync(~0u, q, 1); q += __shfl_xor_sync(~0u, q, 2);
    mean[r] = s; rs[r] = q;
  }
  bar_sync(1, 256);
  if ((lane & 3) == 0) {
#pragma unroll
    for (int r = 0; r < NG; r++) sts64f(scratch + r * 512 + lane * 16 + warp * 8, mean[r], rs[r]);
  }
  bar_sync(1, 256);
#pragma unroll
  for (int r = 0; r < NG; r++) {
    const float4 e = lds128f(scratch + r * 512 + lane * 16);
    float t = e.x + e.z;
    t += __shfl_xor_sync(~0u, t, 1); t += __shfl_xor_sync(~0u, t, 2);
    t *= 0.125f;
    float q = e.y + e.w + 80.f * ((e.x - t) * (e.x - t) + (e.z - t) * (e.z - t));
    q += __shfl_xor_sync(~0u, q, 1); q += __shfl_xor_sync(~0u, q, 2);
    mean[r] = t; rs[r] = rsqrtf(q * (1.f / DM) + 1e-5f);
  }
}

__device__ __forceinline__ void ln_store(const uint32_t (&w)[2][5][2], int tile, int u0, bool live = true) {
  const int lane = threadIdx.x & 31;
  uint32_t* xc = g_xc + ((tile >> 1) * 40 + u0) * 256 + (tile & 1) * 64 + lane;
#pragma unroll
  for (int i = 0; i < 20; i++) if (live) xc[(i >> 1) * 128 + (i & 1) * 32] = w[i & 1][i >> 2][i >> 1 & 1];
#pragma unroll
  for (int i = 0; i < 5; i++) {
    const int u = u0 + i;
    uint32_t* xn = g_xn + (((tile >> 3) * 20 + (u >> 1)) * 16 + (tile & 1) * 8 + (tile & 6)) * 128 + (u & 1) * 64 + lane;
#pragma unroll
    for (int r = 0; r < 2; r++) if (live) { xn[r * 128] = w[r][i][0]; xn[r * 128 + 32] = w[r][i][1]; }
  }
}
__device__ __forceinline__ void wait_count(const uint32_t* c, uint32_t n) {
  int spin = 0;
  while ((ld_acquire(c) & 0xffff) < n) { __nanosleep(32); spin_guard(spin); }
}

__device__ __forceinline__ uint8_t* pool_at(uint32_t off) {
  return reinterpret_cast<uint8_t*>((reinterpret_cast<uintptr_t>(g_pool) + 8191) & ~(uintptr_t)8191) + off; }
struct Weights { const uint8_t* w[4]; };
__device__ __forceinline__ void prefetch_weights(const Weights& p, int i) {
  if (blockIdx.x < 128) asm volatile("cp.async.bulk.prefetch.L2.global [%0], 61440;" :: "l"(p.w[i] + (size_t)blockIdx.x * 61440) : "memory");
}
__global__ void __launch_bounds__(384) first_kernel(const __nv_bfloat16* __restrict__ xin, const uint4* __restrict__ wb, const __grid_constant__ Weights wa) {
  __shared__ __align__(16) float scratch[256];
  __shared__ uint32_t lat[4];
  const int warp = threadIdx.x >> 5, lane = threadIdx.x & 31, cta = blockIdx.x;
  TRACE(0);
  pdl_launch();
  if (warp >= 8) {
    if (warp < 10 || cta < NSLOT) {
      uint32_t* q = reinterpret_cast<uint32_t*>(pool_at((warp < 10 ? NSLOT : cta) * 8192 + (warp & 1) * 4096)) + (warp < 10 ? (cta & 127) * 8 : 0);
      if (lane < 8) stg_strong32(q + lane, 0u);
      uint32_t best = ~0u;
      if (lane == 0) {
        for (int r = 0; r < FK_REP; r++) {
          uint32_t t0, t1, v;
          asm volatile("mov.u32 %0, %%clock;" : "=r"(t0) :: "memory");
          asm volatile("atom.relaxed.gpu.global.exch.b32 %0, [%1], 0;" : "=r"(v) : "l"(q) : "memory");
          asm volatile("{.reg .u32 t; add.u32 t, %1, 1; mov.u32 %0, %%clock; sub.u32 %0, %0, %1;}" : "=r"(t1) : "r"(__shfl_sync(1u, v, 0)) : "memory");
          best = min(best, t1 - t0);
        }
        lat[warp - 8] = best;
      }
    }
    __syncwarp();
    bar_sync(2, cta < 128 ? 384 : 128);
    if (threadIdx.x == 288) for (int i = 0; i < FK_PF; i++) prefetch_weights(wa, i);
    if (threadIdx.x == 256) {
      const int part = lat[0] < lat[1] ? 0 : 1;
      uint32_t smid; asm("mov.u32 %0, %%smid;" : "=r"(smid));
      g_smpart[smid & 255] = part;
      g_smclk[smid & 255] = clk32() - gtime() * 2;
      g_smuse[smid & 255] = 0;
      if (cta < NSLOT) g_orient[cta] = lat[2] < lat[3] ? part : 1 - part;
    }
  } else if (cta < 128) {
    float4 v[2][5];
#pragma unroll
    for (int r = 0; r < 2; r++)
#pragma unroll
      for (int i = 0; i < 5; i++) {
        const uint32_t* src = reinterpret_cast<const uint32_t*>(xin) + (cta * 16 + r * 8 + (lane >> 2)) * (DM / 2) + warp * 40 + i * 8 + (lane & 3);
        const uint32_t a = src[0], b = src[4];
        v[r][i] = make_float4(bf_lo(a), bf_hi(a), bf_lo(b), bf_hi(b));
      }
    uint4 w8[2];
#pragma unroll
    for (int i = 0; i < 2; i++) w8[i] = wb[cta * 400 + min(i * 256 + threadIdx.x, 399)];
    float mean[2], rs[2];
    ln_stats<2>(v, s2u(scratch), mean, rs);
    bar_sync(2, 384);
    ABT(2, 2);
    if (threadIdx.x < 128) g_stat[cta * 128 + threadIdx.x] = make_float2(0.f, 0.f);
#pragma unroll
    for (int i = 0; i < 10; i++) g_x[((cta * 2 + i / 5) * 40 + warp * 5 + i % 5) * 32 + lane] = pack4(v[i / 5][i % 5]);
    uint32_t w[2][5][2];
#pragma unroll
    for (int i = 0; i < 10; i++) {
      const float4 t = v[i / 5][i % 5];
      const float m = mean[i / 5], q = rs[i / 5];
      w[i / 5][i % 5][0] = pack2((t.x - m) * q, (t.y - m) * q); w[i / 5][i % 5][1] = pack2((t.z - m) * q, (t.w - m) * q);
    }
    ln_store(w, cta, warp * 5);
    ABT(2, 3);
#pragma unroll
    for (int i = 0; i < 2; i++) {
      const int e = cta * 400 + min(i * 256 + threadIdx.x, 399), k = e / 80, n = e - k * 80, cg = n / 10;
      g_wb[((cg * 80 + (k >> 3)) * 10 + n - cg * 10) * 8 + (k & 7)] = w8[i];
    }
  } else if (cta == 128) {
    g_bo[threadIdx.x] = 0;
  }
  TRACE(2);
}

struct ChainParams {
  CUtensorMap wq, wk, wv, wo;
  const __nv_bfloat16* mem0;
  uint8_t *pool, *kv;
  const uint32_t* xc;
  uint32_t* sync;
  int layer;
  int d0, d3, d1, d1b, d2, d2b, mode;
};
constexpr int CH_WQ = 0, CH_WO = 81920, CH_X = CH_WO + 86016, CH_M = CH_X + 20480, CH_KT = CH_X + 40960, CH_VT = CH_KT + 4096,
              CH_PS = CH_VT + 4096, CH_QK = CH_PS + 4096, CH_VP = CH_QK + 4096, CH_SX = CH_VP + 1024, CH_O = CH_SX + 2304, CH_ID = CH_O + 3072,
              CH_BAR = CH_ID + 512;
constexpr int CH_SMEM = CH_BAR + 256;
constexpr int CH_BASE = 1024;
#define CH_VK0 8
#define CH_VK1 20
#define CH_L0 4
#define CH_LR 4
#define NOX 0
#define CH_XA 1
#define CH_XB 4
#define CH_W1 5
#define CH_W2 17
#define CH_W3 26
#define CH_R2 8
#define CH_VA 16
#define CH_EX 2
#define CH_KD 0
#define CH_RP 1
#define CH_KF 10
#define CH_LO 0
#define CH_LR1 4
#define CH_KP 0
#define CH_KM 0
#define CH_SP 1
#define CH_VC 2
#define CH_W0 5
#define CH_WA 3
#define CH_KW 3
#define CH_RB 0
#define CH_RC 8
#define CH_D0 200
#define CH_D1 450
#define CH_D2 300
#define CH_R1 4
#define CH_TW 12
__device__ __forceinline__ uint32_t opaque(uint32_t x) { return __shfl_sync(~0u, x, threadIdx.x & 31); }
__device__ __forceinline__ uint32_t nz(uint32_t x) { uint32_t r; asm("max.u32 %0, %1, 1;" : "=r"(r) : "r"(x)); return r; }
__device__ __forceinline__ uint32_t pack_tag(float lo, float hi, uint32_t tag, uint32_t mask) {
  uint32_t r;
  asm("lop3.b32 %0, %1, %2, %3, 0xD8;" : "=r"(r) : "r"(pack2(lo, hi)), "r"(tag), "r"(mask));
  return r;
}
__device__ __forceinline__ uint32_t differ(uint32_t a, uint32_t b, uint32_t t) { uint32_t r; asm("lop3.b32 %0, %1, %2, %3, 0x7E;" : "=r"(r) : "r"(a), "r"(b), "r"(t)); return r; }
__device__ __forceinline__ void mbar_wait_hot(uint32_t bar, uint32_t ph) {
  uint32_t ok;
  asm volatile("{.reg .pred p; mbarrier.try_wait.parity.shared::cta.b64 p, [%1], %2; selp.u32 %0, 1, 0, p;}" : "=r"(ok) : "r"(bar), "r"(ph) : "memory");
  if (__builtin_expect(!ok, 0)) mbar_wait(bar, ph);
}
__device__ __forceinline__ bool elect() {
  uint32_t r; asm volatile("{.reg .pred p; elect.sync _|p, 0xffffffff; selp.u32 %0, 1, 0, p;}" : "=r"(r)); return r; }
__device__ __forceinline__ uint32_t or3(uint32_t a, uint32_t b, uint32_t c) { uint32_t r; asm("lop3.b32 %0, %1, %2, %3, 0xFE;" : "=r"(r) : "r"(a), "r"(b), "r"(c)); return r; }
__device__ __forceinline__ void pin() { pdl_launch(); }
__device__ __forceinline__ void mma16h(float* d, uint32_t a0, uint32_t a2, uint32_t b0, uint32_t b1) {
  asm volatile("{.reg .b32 u, v; mma.sync.aligned.m16n8k16.row.col.f32.bf16.bf16.f32 {%0,%1,%2,%3},{%4,u,%5,v},{%6,%7},{%0,%1,%2,%3};}"
               : "+f"(d[0]), "+f"(d[1]), "+f"(d[2]), "+f"(d[3]) : "r"(a0), "r"(a2), "r"(b0), "r"(b1)); }
__device__ __forceinline__ void mma8h(float* d, uint32_t a0, uint32_t b0) {
  asm volatile("{.reg .b32 u; mma.sync.aligned.m16n8k8.row.col.f32.bf16.bf16.f32 {%0,%1,%2,%3},{%4,u},{%5},{%0,%1,%2,%3};}"
               : "+f"(d[0]), "+f"(d[1]), "+f"(d[2]), "+f"(d[3]) : "r"(a0), "r"(b0)); }
__device__ __forceinline__ uint32_t absmax2(uint32_t a, uint32_t b) { uint32_t r; asm("max.xorsign.abs.bf16x2 %0, %1, %2;" : "=r"(r) : "r"(a), "r"(b)); return r; }
__device__ __forceinline__ void until(uint32_t t) { while ((int)(clk32() - t) < 0) {} }
__device__ __forceinline__ uint4 pack8(const float* d) { return make_uint4(pack2(d[0], d[1]), pack2(d[2], d[3]), pack2(d[4], d[5]), pack2(d[6], d[7])); }
__device__ __forceinline__ void add8(float* d, uint4 v) {
  d[0] += bf_lo(v.x); d[1] += bf_hi(v.x); d[2] += bf_lo(v.y); d[3] += bf_hi(v.y);
  d[4] += bf_lo(v.z); d[5] += bf_hi(v.z); d[6] += bf_lo(v.w); d[7] += bf_hi(v.w);
}

template <int WG>
__device__ __forceinline__ void chain_body(const ChainParams& p, const uint32_t wq, const uint32_t (&ak)[80], const uint32_t (&av)[80]) {
  const int tid = threadIdx.x & 127, t4 = __shfl_sync(~0u, tid >> 5, 0), lane = tid & 31;
  const int cta = blockIdx.x, h = cta / 3, j = cta - 3 * h;
  const uint32_t sb = mapa(CH_BASE, j);
  const uint32_t bWo = sb + CH_BAR, bWq = bWo + 8, bX = bWo + 16, bXA = bWo + 24, bXB = bWo + 32, bO = bWo + 40, bG = bWo + 48, bH = bWo + 96;
  uint32_t tw[4 * CH_TW];
  auto refill = [&]() {
#pragma unroll
    for (int k = 0; k < CH_TW; k++) ldsm4t(&tw[4 * k], wq + k * 2048);
  };
  const uint32_t wo = opaque((sb + CH_WO + (WG == 0 ? (t4 + (j == 2)) * 4096 : (j == 2 ? 0 : 24576) + t4 * 1024) + ((lane & 7) + (lane >> 4) * 8) * 64 +
                              ((((lane >> 3) & 1) ^ ((lane >> 1) & 3)) << 4)) ^ (WG == 1 && j == 2 ? 32 : 0));
  const uint32_t wo2 = opaque((wo ^ ((t4 & 1) * 32)) + (4 + (t4 >> 1) - t4) * 4096);
  const uint32_t l16 = opaque(sb + lane * 16);
  const uint32_t l8 = opaque(sb + t4 * 256 + lane * 8);
  const uint32_t lw = opaque(sb + t4 * 1024 + lane * 16);
  const uint32_t qs = opaque(sb + CH_QK + WG * 2048 + t4 * 512 + lane * 16);
  const uint32_t qa = opaque(sb + CH_QK + (lane >> 4) * 2048 + (lane & 15) * 16 + (WG == 0 ? t4 * 512 + 256 : t4 == 3 ? 1024 : 0));
  const uint32_t ka = opaque(t4 < 2 ? sb + CH_KT + t4 * 512 + lane * 16
                                    : sb + CH_QK + 256 + (t4 - 2) * 1024 + ((lane >> 3) & 1) * 2048 + (lane >> 4) * 128 + (lane & 7) * 16);
  const uint32_t l4 = opaque(sb + t4 * 256 + lane * 4);
  uint32_t pdst[1], pages = 0;
  auto line0 = [&](int i) { return 28 * j + (i < 4 ? 4 * t4 + i : 12 + 2 * t4 + i); };
  const uint32_t plane = opaque((lane >> 4) * 2048 + h * 64 + (lane & 15) * 4);
  if (WG == 0) {
    pages = __ballot_sync(~0u, lds32(sb + CH_O + line0(min(lane, 5)) * 4) & 4096);
  } else {
    pages = __ballot_sync(~0u, lds32(sb + CH_O + (80 + min(lane, 11)) * 4) & 4096);
    pdst[0] = opaque(lds32(sb + CH_O + (j == 0 ? 24 + t4 : 50 + 2 * j + (t4 & 1)) * 4) + plane);
  }
  const uint32_t role = lds32(sb + CH_O + NSLOT * 4), rsrc = lds32(sb + CH_O + role * 4), rdst = (80 + role / 20) * 8192 + role % 20 * 128;
  const uint32_t r1 = mapa(CH_BASE, j == 2 ? 0 : j + 1) - sb, r2 = mapa(CH_BASE, j == 0 ? 2 : j - 1) - sb;
  uint32_t tag = opaque(1);
  auto pool = [&](uint32_t off) { return p.pool + ((tag & 0xfffe) + off); };
  auto after = [&](uint32_t x) { return x & tag & 0xfffe; };
  auto kv = [&](int s, uint32_t a) { return p.kv + (a + ((cta * 2 * NSEG + s) * KV_BYTES - sb)); };
  auto pass = [&](float (&d)[16], const uint32_t (&a)[80], auto k0, auto k1) {
    const uint64_t db = mkdesc(CH_BASE + CH_X + WG * 20480, 512, 128, 0);
#pragma unroll
    for (int k = k0.value; k < k1.value; k++) wg_rs32_00(d, a[4 * k], a[4 * k + 1], a[4 * k + 2], a[4 * k + 3], db + k * 64, k);
    wg_commit();
  };
  auto dump = [&](float (&d)[16], uint32_t a) {
    reg_fence<16>(d);
    sts128(a, pack8(d)); sts128(a + 512, pack8(d + 8));
  };
  uint32_t pph = 0;
  auto tokens0 = [&](int s, auto k0) {
    float dk[16], dv[16];
    bar_sync(9, 256);
    wg_fence();
    pass(dk, ak, Int<0>(), Int<4>());
    const uint4 a0 = lds128(lw + CH_KT), a1 = lds128(lw + CH_KT + 512);
    pin();
    pass(dk, ak, Int<4>(), Int<20>());
    pass(dv, av, Int<0>(), Int<CH_VA>());
    pin();
    wg_wait<1>();
    reg_fence<16>(dk);
    add8(dk, a0); add8(dk + 8, a1);
    const uint4 w0 = pack8(dk), w1 = pack8(dk + 8);
    const uint4 b0 = lds128(lw + CH_VT), b1 = lds128(lw + CH_VT + 512);
    stsm4t(lw + CH_KT, w0.x, w0.z, w0.y, w0.w); stsm4t(lw + CH_KT + 512, w1.x, w1.z, w1.y, w1.w);
    if (CH_KP == 2) bar_arrive(7, 160);
    TM1(6);
    pin();
    if (CH_VA < 20) pass(dv, av, Int<CH_VA>(), Int<20>());
    pin();
#pragma unroll
    for (int k = k0.value; k < CH_TW; k++) ldsm4t(&tw[4 * k], wq + k * 2048);
    TM1(9);
    if (k0.value < CH_TW && t4 >= 2) { mbar_wait_hot(bH + t4 * 16 - 24 + (pph & 1) * 8, pph >> 1 & 1); pph++; }
    __syncwarp();
    wg_wait<0>();
    reg_fence<16>(dv);
    add8(dv, b0); add8(dv + 8, b1);
#pragma unroll
    for (int e = 0; e < 2; e++) { const uint4 v = pack8(dv + 8 * e); sts128(lw + CH_VT + e * 512, make_uint4(v.x, v.z, v.y, v.w)); }
  };
  auto publish_k = [&](int s) {
    if (t4 == CH_KW && elect()) { fence_async(); bulk_store(p.kv + (size_t)(cta * 2 * NSEG + s) * KV_BYTES, sb + CH_KT, 4096); bulk_commit(); }
    __syncwarp();
  };
  auto load_x = [&](int s, int k0, int n, uint32_t bar) {
    if (!NOX && elect()) { mbar_expect(bar, n * 1024); bulk_load(sb + CH_X + k0 * 1024, p.xc + (s + 1) * 10240 + k0 * 256, n * 1024, bar); }
  };
  if (WG == 0) {
    mbar_wait(bXB, 0);
    tokens0(0, Int<CH_TW>());
    if (CH_XB == 5) { bar_sync(7, 128); load_x(0, 5 * t4, 5, bXB); }
  } else {
    const uint32_t* m0 = reinterpret_cast<const uint32_t*>(p.mem0) + (lane >> 2) * 320 + t4 * 80 + (lane & 3);
    uint32_t a[20];
#pragma unroll
    for (int i = 0; i < 20; i++) a[i] = m0[4 * i];
    pin();
    float dk[16], dv[16];
    mbar_wait(bXA, 0);
    wg_fence();
    pass(dk, ak, Int<0>(), Int<20>());
    pass(dv, av, Int<0>(), Int<20>());
    wg_wait<0>();
    dump(dk, lw + CH_KT);
    dump(dv, lw + CH_VT);
    bar_sync(9, 256);
    if (CH_KP == 2 && t4 == CH_KW) { bar_sync(7, 160); publish_k(0); }
#pragma unroll
    for (int i = 0; i < 20; i++) sts32(sb + CH_M + (t4 * 20 + i) * 128 + lane * 4, nz(transpose8(a[i])));
    __syncwarp();
    if (elect()) mbar_arrive(bG + t4 * 8);
  }
  PRO(8);
  mbar_wait(bWq, 0);
  refill();
  PRO(9);
  mbar_wait(bWo, 0);
  asm volatile("barrier.cluster.wait.aligned;" ::: "memory");
  PRO(10);
  constexpr int VK = WG == 0 ? CH_VK0 : CH_VK1;
  uint32_t gph = 0;
  int st = 0;
  const uint32_t ca = opaque(sb + CH_M + t4 * 2560 + lane * 32 + (lane >> 2) * 4);
  auto project = [&](int s, uint32_t (&b)[40], float (&dv)[16], uint32_t (&kf)[16]) {
    float dq[4] = {}, dk[4] = {};
    uint32_t w[80];
#pragma unroll
    for (int i = 0; i < 4 * CH_TW; i++) w[i] = tw[i];
    constexpr int LR = WG == 1 ? CH_LR1 : CH_LR;
    auto load = [&](int n) {
      int c = 0;
#pragma unroll
      for (int i = 0; i < 10; i++) {
        if (i == CH_KF) {
#pragma unroll
          for (int q = 0; q < 4; q++)
            if (WG == 1 && c++ == n) ldsm4(&kf[4 * q], ka + q * 1024);
        }
        if (c++ == n) ldsm4t(&b[4 * i], l16 + CH_M + WG * 5120 + i * 512);
#pragma unroll
        for (int k = 2 * i; k < 2 * i + 2; k++)
          if (k >= CH_TW && c++ == n) ldsm4t(&w[4 * k], wq + k * 2048);
      }
#pragma unroll
      for (int i = 0; i < 4; i++)
        if (WG == 1 && CH_KF >= 10 && c++ == n) ldsm4(&kf[4 * i], ka + i * 1024);
    };
    if (WG == 1) {
      for (int n = 0;;) {
        mbar_wait(bG + t4 * 8, gph);
        TR(5, (clk32() & ~3u) | min(n, 3));
        gph ^= 1;
        if (__builtin_expect(!__any_sync(~0u, __vimin3_u32(lds32(ca), lds32(ca + 1024), lds32(ca + 1536)) == 0), 1)) break;
        if (elect()) {
          const int q = (st == 0 ? 8 : st * 4 - 4) + t4;
          mbar_expect(bG + t4 * 8, 2560);
          bulk_load(sb + CH_M + t4 * 2560, p.pool + ((80 + q) * 8192 + (pages >> q & 1) * 4096), 2560, bG + t4 * 8);
        }
        spin_guard(n);
      }
    }
    bar_sync(6, 256);
#pragma unroll
    for (int i = 0; i < CH_L0; i++) load(i);
    if (WG == 0 && CH_XB == 4) load_x(min(s, NSEG - 2), 5 * t4, 5, bXB);
    TM(0);
    TM1(11);
    if (WG == 1) TR(6, clk32());
#pragma unroll
    for (int k = 0; k < 20; k += 2) {
      if (k > 0) {
#pragma unroll
        for (int n = (k == 18 ? 40 : CH_L0 + k * LR / 4) - 1; n >= CH_L0 + (k - 2) * LR / 4; n--) { load(n); if (CH_LO) __syncwarp(); }
      }
      if (WG == 0 && CH_XB >= 10 && k == CH_XB - 10 && s + 1 < NSEG) load_x(s, 5 * t4, 5, bXB);
      pin();
#pragma unroll
      for (int kk = k; kk < k + 2; kk++) {
        mma16(dk, ak[4 * kk], ak[4 * kk + 1], ak[4 * kk + 2], ak[4 * kk + 3], b[2 * kk], b[2 * kk + 1]);
        mma16(dq, w[4 * kk], w[4 * kk + 1], w[4 * kk + 2], w[4 * kk + 3], b[2 * kk], b[2 * kk + 1]);
        if (kk < VK) mma16(dv, av[4 * kk], av[4 * kk + 1], av[4 * kk + 2], av[4 * kk + 3], b[2 * kk], b[2 * kk + 1]);
      }
    }
    const float k2 = 0.07216878364870322f * 1.44269504089f;
    stsm4t(qs, pack2(dq[0] * k2, dq[1] * k2), pack2(dq[2] * k2, dq[3] * k2), pack2(dk[0], dk[1]), pack2(dk[2], dk[3]));
    TM(1);
  };
  static_assert(CH_VK1 == 20 && CH_KP == 0 && true, "last step");
  constexpr int VC = VK == 20 ? 1 : CH_VC;
  auto finish_v = [&](const uint32_t (&b)[40], float (&dv)[16]) {
#pragma unroll
    for (int kk = VK; kk < 20; kk++) mma16(dv + 4 * ((kk - VK) % VC), av[4 * kk], av[4 * kk + 1], av[4 * kk + 2], av[4 * kk + 3], b[2 * kk], b[2 * kk + 1]);
  };
  auto sum_v = [&](float (&dv)[16]) {
#pragma unroll
    for (int i = 4; i < 4 * VC; i++) dv[i & 3] += dv[i];
  };
  auto publish_km = [&](int s) {
    uint32_t a[4];
    ldsm4(a, qa);
    *reinterpret_cast<uint2*>(kv(s, l8) + KV_M) = make_uint2(hadd2(a[0], a[2]), hadd2(a[1], a[3]));
  };
  auto memory_v = [&](uint2 x, const float (&dv)[16]) {
    return make_uint2(pack2(dv[0] + bf_lo(x.x), dv[1] + bf_hi(x.x)), pack2(dv[2] + bf_lo(x.y), dv[3] + bf_hi(x.y)));
  };
  auto publish_v = [&](int s, const uint4 (&v)[2], uint2 vm) {
#pragma unroll
    for (int e = 0; e < 2; e++) reinterpret_cast<uint4*>(kv(s, lw) + KV_V)[e * 32] = v[e];
    *reinterpret_cast<uint2*>(kv(s, l8) + KV_V + KV_M) = vm;
  };
#pragma unroll 1
  for (int s = 0;; s++) {
    float dv[16] = {};
    uint32_t b[40], kf[16];
    project(s, b, dv, kf);
    if (WG == 0) {
      bar_sync(1, 256);
      if (CH_XA == 0 && s + 1 < NSEG) load_x(s, 20 + 5 * t4, 5, bXA);
      if (CH_XB == 0 && s + 1 < NSEG) load_x(s, 5 * t4, 5, bXB);
      pin();
      uint32_t w[144];
      auto wload = [&](int i) { ldsm4t(&w[4 * i], (i % 3 == 0 ? wo : i % 3 == 1 ? wo ^ 32 : wo2) + i / 12 * 28672 + i / 3 % 4 * 1024); };
#pragma unroll
      for (int kk = VK; kk < 20; kk++) {
        mma16(dv + 4 * ((kk - VK) % VC), av[4 * kk], av[4 * kk + 1], av[4 * kk + 2], av[4 * kk + 3], b[2 * kk], b[2 * kk + 1]);
        if (kk == VK + CH_WA && CH_W0) {
          pin();
#pragma unroll
          for (int i = 0; i < CH_W0; i++) wload(i);
          pin();
        }
      }
      sum_v(dv);
      sts64(l8 + CH_VP, pack2(dv[0], dv[1]), pack2(dv[2], dv[3]));
      if (s == NSEG - 1) {
        bar_arrive(10, 256);
        if (CH_XB == 4) mbar_wait(bXB, 0);
        publish_k(s);
        publish_km(s);
        bulk_wait<0>();
        fence_async_global();
        bar_sync(2, 256);
        if (tid == 0) red_release(p.sync + 15 * 8 + 4, 1);
        break;
      }
      bar_arrive(4, 256);
      if (CH_XA == 1) load_x(s, 20 + 5 * t4, 5, bXA);
      if (CH_XB == 1) load_x(s, 5 * t4, 5, bXB);
      TM(3);
      if (CH_KP == 0) publish_k(s);
#pragma unroll
      for (int i = CH_W0; i < CH_W1; i++) wload(i);
      bar_sync(10, 256);
      uint32_t km[4];
      ldsm4(km, qa);
      pin();
#pragma unroll
      for (int i = CH_W1; i < CH_W2; i++) wload(i);
      pin();
      const uint2 kms = make_uint2(hadd2(km[0], km[2]), hadd2(km[1], km[3]));
      if (CH_KM == 0) *reinterpret_cast<uint2*>(kv(s, l8) + KV_M) = kms;
      if (CH_KP == 0) bulk_wait_read<0>();
      if (CH_XA == 2) load_x(s, 20 + 5 * t4, 5, bXA);
      if (CH_XB == 2) load_x(s, 5 * t4, 5, bXB);
      bar_sync(2, 256);
      {
        float y[3][4] = {};
        uint32_t ob[24];
        ldsm4(&ob[0], l16 + CH_O + 1024); ldsm4(&ob[4], l16 + CH_O + 1536);
        TM(7);
        auto step = [&](int i) {
          const int k = i / 3;
          mma16(y[i % 3], w[4 * i], w[4 * i + 1], w[4 * i + 2], w[4 * i + 3], ob[2 * k], ob[2 * k + 1]);
        };
#pragma unroll
        for (int i = 0; i < 12; i++) {
          step(i);
          if (i >= 12 - (CH_W3 - CH_W2)) wload(CH_W3 - 12 + i);
          if (i % 3 == 2) pin();
        }
        if (CH_XB == 3) load_x(s, 5 * t4, 5, bXB);
        if (CH_KM == 1) *reinterpret_cast<uint2*>(kv(s, l8) + KV_M) = kms;
        pin();
        mbar_wait(bO, s & 1);
        TM(4);
        ldsm4(&ob[8], l16 + CH_O); ldsm4(&ob[12], l16 + CH_O + 512);
        pin();
        float2 inv;
        uint8_t* dst[6];
        uint32_t mask;
#pragma unroll
        for (int i = 12; i < 36; i++) {
          step(i);
          static_assert(CH_W3 == 26, "load order");
          if (i == 14) ldsm4(&ob[16], l16 + after(w[4 * CH_W3 - 1] | w[4 * CH_W3 - 5] | w[4 * CH_W3 - 9] | ob[8]) + CH_O + 2048);
          else if (i == 15) ldsm4(&ob[20], l16 + CH_O + 2560);
          else if (i < 24) wload(i < 14 ? 39 - i : i < 18 ? 45 - i : i < 21 ? 50 - i : 56 - i);
          if (i == 21) inv = lds64f((l8 & ~0xe0u) + CH_VP);
          if (i < 24) __syncwarp();
          if (i == 24) mask = ((l16 ^ tag) & 48) == 0;
          if (i >= 24 && i < 30) dst[i - 24] = pool(line0(i - 24) * 8192 + (pages >> (i - 24) & 1) * 4096) + plane;
          if (i % 3 == 2) pin();
        }
#pragma unroll
        for (int k = 0; k < CH_R1; k++) ldsm4t(&tw[4 * k], wq + k * 2048);
        pin();
#pragma unroll
        for (int i = 0; i < 6; i++) stg_strong32(dst[i], pack_tag(y[i >> 1][2 * (i & 1)] * inv.x, y[i >> 1][2 * (i & 1) + 1] * inv.y, tag, mask));
        TM(8);
        TR(0, clk32());
        bar_arrive(5, 256);
        pin();
      }
      const uint32_t t0 = clk32();
      auto refill2 = [&]() {
#pragma unroll
        for (int k = CH_R1; k < CH_R2; k++) ldsm4t(&tw[4 * k], wq + k * 2048);
      };
      if (CH_RP == 0) refill2();
      const uint32_t ln = (l16 ^ tag) >> 4 & 31;
      if (t4 >= 2) {
        const uint32_t bP = bH + t4 * 16 - 24, ps = CH_PS + (t4 & 1) * 4096;
        auto fetch = [&](uint32_t k) {
          if (elect()) { mbar_expect(bP + (k & 1) * 8, 2048); bulk_load(sb + ps + (k & 1) * 2048, p.pool + (rsrc + (t4 & 1) * 2048), 2048, bP + (k & 1) * 8); }
        };
        until(t0 + CH_D0);
        fetch(pph);
        if (CH_RP == 2) refill2();
        if (!NOX && CH_XB != 6) mbar_wait_hot(bXB, (s + 1) & 1);
        const uint32_t want = (tag & 1) * 0x10001, chk = opaque(ln < 4 ? 0x10001 : 0);
        uint4 sel;
        sel.x = opaque((ln >> 3) != (ln & 1) ? 0 : ln & 4 ? 0x3f800000u : 0x00003f80u);
        sel.z = opaque(sel.x); sel.y = opaque(ln); sel.w = opaque(ln + 1);
        uint8_t* mdst = p.pool + opaque(st * 32768 + rdst + (t4 & 1) * 64 + ln * 4);
        until(t0 + CH_D1);
        fetch(pph + 1);
        TM(5);
        if (CH_RP == 1) refill2();
        int n = 0;
        uint32_t u[16];
        float y[4][4];
        auto sum = [&]() {
#pragma unroll
          for (int i = 0; i < 16; i++) y[i >> 2][i & 3] = 0.f;
#pragma unroll
          for (int i = 0; i < 8; i++) mma16(y[i & 3], sel.x, sel.y, sel.z, sel.w, u[2 * i], u[2 * i + 1]);
        };
        auto check = [&](auto spec) {
          mbar_wait(bP + (pph & 1) * 8, pph >> 1 & 1);
          TM(14);
          TR(2, clk32());
#pragma unroll
          for (int i = 0; i < 4; i++) ldsm4t(&u[4 * i], l16 + (ps + (pph & 1) * 2048) + i * 512);
          pph++;
          if (spec.value) { pin(); sum(); }
          uint32_t bad = 0;
#pragma unroll
          for (int i = 0; i < 4; i++) bad = or3(bad, differ(u[4 * i], u[4 * i + 1], want), differ(u[4 * i + 2], u[4 * i + 3], want));
          return __any_sync(~0u, bad & chk);
        };
        if (CH_SP) {
          if (check(Int<0>())) {
            do { fetch(pph + 1); spin_guard(n); } while (check(Int<1>()));
          } else {
            sum();
          }
        } else {
          while (check(Int<0>())) { fetch(pph + 1); spin_guard(n); }
          sum();
        }
        TR(1, t0 + (n ? CH_D1 : CH_D0));
        TM(15);
        const uint32_t w = nz(pack2((y[0][0] + y[1][0]) + (y[2][0] + y[3][0]), (y[0][1] + y[1][1]) + (y[2][1] + y[3][1])));
        if (ln < 16) { stg_strong32(mdst, w); stg_strong32(mdst + 4096, w); }
        TMV(12, 32, n);
        TR(3, (clk32() & ~3u) | min(n, 3));
      } else {
        if (CH_XB == 6) { load_x(s, 10 * t4, 5, bXB); load_x(s, 10 * t4 + 5, 5, bXB); }
        if (CH_RP) refill2();
        if (!NOX) mbar_wait_hot(bXB, (s + 1) & 1);
        stg_strong32(p.pool + ((st == 2 ? 0 : st + 1) * 32768 + rdst + t4 * 4096) + ln * 4, 0u);
        if (t4 == 0 && cta < 40 && s + 4 < NSEG && elect())
          asm volatile("cp.async.bulk.prefetch.L2.global [%0], 1024;" :: "l"(p.xc + (s + 4) * 10240 + cta * 256) : "memory");
        if (t4 == 1 && (s & 3) == 0 && s > 0 && elect()) red_relaxed(p.sync + 2 * s - 4, 1);
        if (t4 == 1 && s == NSEG - 3 && cta == 95 && elect()) red_relaxed(p.sync + 2 * s + 2, 0x10000);
      }
      TM(10);
      bar_arrive(8, 256);
      tokens0(s + 1, Int<CH_R2>());
      if (CH_XB == 5 && s + 2 < NSEG) { bar_sync(7, 128); load_x(s + 1, 5 * t4, 5, bXB); }
      TM(2);
      TR(7, clk32());
    } else {
      if (s == NSEG - 1) {
        bar_arrive(1, 256);
        const uint4 v[2] = {lds128(lw + CH_VT), lds128(lw + CH_VT + 512)};
        bar_sync(10, 256);
        publish_v(s, v, memory_v(lds64(l8 + CH_VP), dv));
        bar_arrive(2, 256);
        break;
      }
      const uint32_t xo = l4 + (CH_SX - (t4 == 3 ? 128 : 0)), xr = CH_SX + 768 + min(t4, 2) * 256, x1 = l4 + (r1 + xr), x2 = l4 + (r2 + xr + 128);
      if (t4 < 2) {
        float ds[4][4] = {};
        uint32_t q[16];
        asm volatile("bar.sync 1, 256;" ::: "memory");
#pragma unroll
        for (int k = 0; k < 4; k++) ldsm4(&q[4 * k], qa + k * 512);
        pin();
        if (VK < 20) { finish_v(b, dv); pin(); }
#pragma unroll
        for (int k = 0; k < 4; k++) {
          mma16(ds[k & 1], kf[4 * k], kf[4 * k + 1], kf[4 * k + 2], kf[4 * k + 3], q[4 * k], q[4 * k + 1]);
          mma16(ds[2 + (k & 1)], kf[4 * k], kf[4 * k + 1], kf[4 * k + 2], kf[4 * k + 3], q[4 * k + 2], q[4 * k + 3]);
        }
        float t[4];
#pragma unroll
        for (int i = 0; i < 4; i++) t[i] = (ds[0][i] + ds[2][i]) + (ds[1][i] + ds[3][i]);
        const uint32_t w0 = pack2(t[0], t[1]), w1 = pack2(t[2], t[3]);
        st_async32(x1, w0, bX + r1); st_async32(x2, w0, bX + r2);
        st_async32(x1 + 256, w1, bX + r1); st_async32(x2 + 256, w1, bX + r2);
        sts32(xo, w0); sts32(xo + 128, w1);
      } else {
        float ds[4][4] = {};
        uint32_t q0[4], q1[4], a0[4], a1[4];
        asm volatile("bar.sync 1, 256; " ::: "memory");
        ldsm4(a0, ka); ldsm4(q0, qa); ldsm4(a1, ka + 512); ldsm4(q1, qa + 512);
        pin();
        if (VK < 20) { finish_v(b, dv); pin(); }
        mma16(ds[0], a0[0], a0[1], a0[2], a0[3], q0[0], q0[1]);
        mma16(ds[1], a0[0], a0[1], a0[2], a0[3], q0[2], q0[3]);
        mma16(ds[2], a1[0], a1[1], a1[2], a1[3], q1[0], q1[1]);
        mma16(ds[3], a1[0], a1[1], a1[2], a1[3], q1[2], q1[3]);
        float t[2];
#pragma unroll
        for (int i = 0; i < 2; i++)
          t[i] = ((ds[0][i] + ds[0][i + 2]) + (ds[1][i] + ds[1][i + 2])) + ((ds[2][i] + ds[2][i + 2]) + (ds[3][i] + ds[3][i + 2]));
        const uint32_t w0 = pack2(t[0], t[1]);
        st_async32(x1, w0, bX + r1);
        st_async32(x2, w0, bX + r2);
        sts32(xo, w0);
      }
      TM(3);
      const uint4 id = lds128(l16 + CH_ID);
      float sc[5][4] = {};
      uint4 v[2];
      sum_v(dv);
      bar_sync(4, 256);
      uint32_t r[12], wd[12], we[12] = {};
      ldsm4(&r[0], l16 + CH_SX); ldsm2(&r[4], l16 + CH_SX + 512);
      const uint2 vp = lds64(l8 + CH_VP);
      pin();
      v[0] = lds128(lw + CH_VT); v[1] = lds128(lw + CH_VT + 512);
#pragma unroll
      for (int u = 0; u < 3; u++) ldsm4t(&wd[4 * u], wo + u * 28672);
      pin();
#pragma unroll
      for (int q = 0; q < 4; q++) mma8(sc[q], id.x, id.y, r[q]);
      mma16(sc[4], id.x, id.y, id.z, id.w, r[4], r[5]);
      uint32_t big = absmax2(absmax2(absmax2(r[0], r[1]), absmax2(r[2], r[3])), absmax2(r[4], r[5]));
      const uint2 vm = memory_v(vp, dv);
      const uint32_t ones = 0x3f803f80u;
      pin();
      mbar_wait_hot(bX, s & 1);
      TM(4);
      ldsm4(&r[0], l16 + CH_SX + 768);
      __syncwarp();
      ldsm4(&r[4], l16 + CH_SX + 1280);
      __syncwarp();
      ldsm4(&r[8], l16 + CH_SX + 1792);
      bar_arrive(10, 256);
      pin();
#pragma unroll
      for (int q = 0; q < 4; q++) { mma16(sc[q], id.x, id.y, id.z, id.w, r[2 * q], r[2 * q + 1]); if (q & 1) pin(); }
      uint32_t pr[5], o0, o1;
      bool redo = false;
      auto attend = [&](auto first) {
        float o[2][4] = {}, om[2][4] = {}, e[10];
        auto exps = [&](int q) {
#pragma unroll
          for (int i = 0; i < 2; i++) asm volatile("ex2.approx.ftz.f32 %0, %1;" : "=f"(e[2 * q + i]) : "f"(sc[q][i]));
        };
        auto merge = [&](int q) { big = absmax2(big, absmax2(absmax2(r[4 * q], r[4 * q + 1]), absmax2(r[4 * q + 2], r[4 * q + 3]))); };
        exps(0);
        if (first.value) { merge(0); pin(); mma16(sc[4], id.x, id.y, id.z, id.w, r[8], r[9]); }
        exps(1);
        if (first.value) { merge(1); pin(); }
        exps(2);
        if (first.value) { mma16(sc[4], id.x, id.y, id.z, id.w, r[10], r[11]); merge(2); pin(); }
        pr[0] = pack2(e[0], e[1]); pr[1] = pack2(e[2], e[3]);
        mma16h(o[0], pr[0], pr[1], v[0].x, v[0].y);
        mma16h(o[1], pr[0], pr[1], v[0].z, v[0].w);
        exps(3);
        if (first.value) pin();
        exps(4);
        if (first.value) redo = __any_sync(~0u, (absmax2(big, big << 16) & 0x7fff0000u) >= 0x41800000u);
        const bool drop = first.value && redo;
        const uint32_t a1 = l4 + (drop ? CH_PS : r1 + CH_O), a2 = l4 + (drop ? CH_PS : r2 + CH_O + 2048);
        const uint32_t b1 = drop ? bWq : bO + r1, b2 = drop ? bWq : bO + r2;
        pr[2] = pack2(e[4], e[5]); pr[3] = pack2(e[6], e[7]); pr[4] = pack2(e[8], e[9]);
        mma16h(o[0], pr[2], pr[3], v[1].x, v[1].y);
        mma16h(o[1], pr[2], pr[3], v[1].z, v[1].w);
        mma8h(om[0], pr[4], vm.x);
        mma8h(om[1], pr[4], vm.y);
        o0 = pack2(o[0][0] + om[0][0], o[0][1] + om[0][1]); o1 = pack2(o[1][0] + om[1][0], o[1][1] + om[1][1]);
        st_async32(a1, o0, b1); st_async32(a2, o0, b2);
        st_async32(a1 + 128, o1, b1); st_async32(a2 + 128, o1, b2);
        sts32(l4 + CH_O + 1024, o0); sts32(l4 + CH_O + 1152, o1);
        asm volatile("{.reg .pred p; setp.eq.u32 p, %0, 0; @p bar.arrive 2, 256;}" :: "r"((uint32_t)drop) : "memory");
      };
      attend(Int<1>());
      pin();
      if (__builtin_expect(redo, 0)) {
        float mx = -INFINITY;
#pragma unroll
        for (int q = 0; q < 5; q++) mx = fmaxf(mx, fmaxf(sc[q][0], sc[q][1]));
        mx = fmaxf(mx, __shfl_xor_sync(~0u, mx, 1));
        mx = fmaxf(mx, __shfl_xor_sync(~0u, mx, 2));
#pragma unroll
        for (int q = 0; q < 5; q++) { sc[q][0] -= mx; sc[q][1] -= mx; }
        attend(Int<0>());
      }
      TM(6);
      float l[4] = {}, l2[4] = {};
      mma16h(l, pr[0], pr[1], ones, ones);
      mma16h(l2, pr[2], pr[3], ones, ones);
      mma8h(l, pr[4], ones);
      l[0] += l2[0];
      float inv;
      asm("rcp.approx.ftz.f32 %0, %1;" : "=f"(inv) : "f"(l[0]));
      sts32((l8 & ~0xffu) + (lane & 28) + CH_VP, __float_as_uint(inv));
      __syncwarp();
      if (elect()) mbar_arrive(bO);
      {
        float z[2][4] = {}, y[2][4] = {};
        mma16(z[0], wd[0], wd[1], wd[2], wd[3], o0, o1);
        if (j == 0) {
#pragma unroll
          for (int u = 0; u < 3; u++) ldsm4t(&we[4 * u], (wo ^ 32) + u * 28672);
          mma16(y[0], we[0], we[1], we[2], we[3], o0, o1);
        }
        const float2 iv = lds64f((l8 & ~0xe0u) + CH_VP);
        uint8_t* dst = pool(pdst[0]);
        const uint32_t mask = ((l16 ^ tag) & 48) == 0;
        const uint32_t oa = qa + ((tag & 0xfffe) + CH_O - CH_QK + t4 * 256 - (t4 == 3 ? 1024 : 0));
        const uint32_t za = l16 + ((tag & 0xfffe) + (t4 >> 1) * 512 + (t4 & 1) * 8);
        pin();
        mbar_wait(bO, s & 1);
        uint32_t a[4];
        ldsm4(a, oa);
        mma16(z[0], wd[4], wd[5], wd[6], wd[7], a[0], a[1]);
        mma16(z[1], wd[8], wd[9], wd[10], wd[11], a[2], a[3]);
        if (j == 0) {
          mma16(y[0], we[4], we[5], we[6], we[7], a[0], a[1]);
          mma16(y[1], we[8], we[9], we[10], we[11], a[2], a[3]);
          sts128f(lw + CH_VT + 512, y[0][0] + y[1][0], y[0][1] + y[1][1], y[0][2] + y[1][2], y[0][3] + y[1][3]);
        }
        sts128f(lw + CH_VT, z[0][0] + z[1][0], z[0][1] + z[1][1], z[0][2] + z[1][2], z[0][3] + z[1][3]);
        bar_sync(3, 128);
        if (j == 0 || t4 < 2) {
          float2 q[4];
#pragma unroll
          for (int i = 0; i < 4; i++) q[i] = lds64f(za + CH_VT + i * 1024);
          stg_strong32(dst, pack_tag(((q[0].x + q[1].x) + (q[2].x + q[3].x)) * iv.x, ((q[0].y + q[1].y) + (q[2].y + q[3].y)) * iv.y, tag, mask));
        }
      }
      TM(2);
      if (!NOX) mbar_wait_hot(bXA, (s + 1) & 1);
      if (CH_KP == 2) bulk_wait_read<0>();
      float dk[16], dw[16];
      bar_sync(5, 256);
      wg_fence();
      pass(dk, ak, Int<0>(), Int<20>());
      pass(dw, av, Int<0>(), Int<20>());
      TM(5);
      pin();
      if (CH_EX == 0) publish_v(s, v, vm);
      if (elect()) {
        mbar_expect(bG + t4 * 8, 2560);
        if (t4 == 1 && s + 2 < NSEG) { mbar_expect(bX, 1536); mbar_expect(bO, 2048); }
      }
      if (CH_KD == 0) { wg_wait<1>(); dump(dk, lw + CH_KT); }
      wg_wait<0>();
      if (CH_KD == 1) dump(dk, lw + CH_KT);
      TM(7);
      dump(dw, lw + CH_VT);
      bar_arrive(9, 256);
      pin();
#pragma unroll
      for (int k = 0; k < CH_RB; k++) ldsm4t(&tw[4 * k], wq + k * 2048);
      if (t4 < 2) {
        if (CH_EX == 2) { publish_v(s, v, vm); pin(); }
#pragma unroll
        for (int k = CH_RB; k < CH_RC; k++) ldsm4t(&tw[4 * k], wq + k * 2048);
        const int q = t4 ? 3 : j, o = t4 ? j * 896 : 0;
        const uint8_t* src = p.pool + ((80 + st * 4 + q) * 8192 + (pages >> (st * 4 + q) & 1) * 4096 + o);
        asm volatile("bar.sync 8, 256;" ::: "memory");
        const uint32_t t1 = clk32() + CH_D2;
        if (CH_EX == 1) publish_v(s, v, vm);
        auto fetch = [&](auto n) {
          mbar_wait(bH, s & 1);
          until(t1);
          TR(4, clk32());
          if (elect())
            asm volatile("cp.async.bulk.shared::cluster.global.mbarrier::complete_tx::bytes.multicast::cluster [%0], [%1], %2, [%3], 7;"
                         :: "r"(sb + CH_M + q * 2560 + o), "l"(src), "n"(n.value), "r"(bG + q * 8) : "memory");
        };
        if (!t4) fetch(Int<2560>()); else if (j == 2) fetch(Int<768>()); else fetch(Int<896>());
      } else {
        asm volatile("bar.sync 8, 256; " ::: "memory");
        if (elect()) asm volatile("mbarrier.arrive.relaxed.cluster.shared::cluster.b64 _, [%0];" :: "r"(bH + (t4 == 2 ? r1 : r2)) : "memory");
        pin();
        if (CH_EX) publish_v(s, v, vm);
#pragma unroll
        for (int k = CH_RB; k < CH_RC; k++) ldsm4t(&tw[4 * k], wq + k * 2048);
      }
      TM(9);
      pin();
#pragma unroll
      for (int k = CH_RC; k < CH_TW; k++) ldsm4t(&tw[4 * k], wq + k * 2048);
      if (CH_KP == 2 && t4 == CH_KW) { bar_sync(7, 160); publish_k(s + 1); }
      TM(10);
    }
    if (++st == 3) st = 0;
    tag ^= 0x10001;
  }
}

__global__ void __launch_bounds__(256, 1) chain_kernel(const __grid_constant__ ChainParams p) {
  extern __shared__ __align__(1024) uint8_t smem_raw[];
  const uint32_t sb = s2u(smem_raw);
  const int tid = threadIdx.x, warp = __shfl_sync(~0u, tid >> 5, 0), lane = tid & 31;
  const int cta = blockIdx.x, h = cta / 3, j = cta - 3 * h, colbase = cta * 64;
  const uint32_t bWo = sb + CH_BAR, bWq = bWo + 8, bXA = bWo + 24, bWk = bWo + 80, bWv = bWo + 88;
  uint32_t smid; asm("mov.u32 %0, %%smid;" : "=r"(smid));
  PRO(0);
  if (sb != mapa(CH_BASE, j)) __trap();
  uint32_t entry = 0;
  auto place = [&]() {
    const int i = tid - 128;
    if (i >= 0 && i <= NSLOT) {
      const uint32_t side = ldg_strong32(g_smpart + (smid & 255));
      if (i < NSLOT) {
        entry = i * 8192 + (ldg_strong32(g_orient + i) == (i < 80 ? i & 1 : side) ? 0 : 4096);
      } else {
        entry = 2 * (atomicAdd(g_bo + p.layer * 128 + 1, 1 << 8 * side) >> 8 * side & 255) + side;
      }
    }
    __syncwarp();
  };
  if (warp == 2 && lane < 4) asm volatile("prefetch.tensormap [%0];" :: "l"(&p.wq + lane) : "memory");
  if (p.layer) place();
  if (warp == 0 && elect()) {
#pragma unroll 1
    for (int i = 0; i < 17; i++) mbar_init(bWo + 8 * i, i == 5 ? 5 : i == 3 || i == 4 ? 4 : i == 12 ? 2 : 1);
    asm volatile("fence.mbarrier_init.release.cluster;" ::: "memory");
    mbar_expect(bWk, 81920);
    tma_load3<(WEF & 1) != 0>(sb + CH_WQ, &p.wk, colbase, 0, bWk);
    mbar_expect(bWv, 81920);
    tma_load3<(WEF & 1) != 0>(sb + CH_WO, &p.wv, colbase, 0, bWv);
    mbar_expect(bWo + 16, 1536);
    mbar_expect(bWo + 40, 2048);
    mbar_expect(bWo, 86016); mbar_expect(bWq, 81920);
#pragma unroll 1
    for (int i = 0; i < 8; i++) mbar_expect(bXA + 8 * (i & 1), 5120);
  }
  if (warp == 1) {
    const uint32_t id = (lane >> 3) == (lane & 3) ? ((lane & 4) ? 0x3f800000u : 0x00003f80u) : 0u;
    sts128(sb + CH_ID + lane * 16, make_uint4(id, 0, id, 0));
  }
  __syncthreads();
  asm volatile("barrier.cluster.arrive.relaxed.aligned;" ::: "memory");
  uint32_t ak[80], av[80];
  const uint32_t wq = opaque(sb + CH_WQ + ((warp >> 2) * 320 + (lane & 7) + (lane >> 4) * 8) * 128 + (((2 * (warp & 3) + ((lane >> 3) & 1)) ^ (lane & 7)) << 4));
  pdl_wait();
  if (tid == 32) stg_strong32(g_smuse + (smid & 255), p.layer + 1);
  pdl_launch();
  PRO(1);
  if (warp == 0 && elect()) {
    bulk_load(sb + CH_X + 20480, p.xc + 5120, 20480, bXA);
    bulk_load(sb + CH_X, p.xc, 20480, bXA + 8);
  }
  if (!p.layer) place();
  __syncwarp();
  PRO(2);
  mbar_wait(bWk, 0);
  PRO(3);
#pragma unroll
  for (int k = 0; k < 20; k++) ldsm4t(&ak[4 * k], wq + k * 2048);
  bar_sync(6, 256);
  if (warp == 0 && elect()) tma_load3<(WEF & 2) != 0>(sb + CH_WQ, &p.wq, colbase, 0, bWq);
  __syncwarp();
  PRO(4);
  mbar_wait(bWv, 0);
  PRO(5);
#pragma unroll
  for (int k = 0; k < 20; k++) ldsm4t(&av[4 * k], wq + CH_WO + k * 2048);
  bar_sync(6, 256);
  PRO(6);
  if (warp >= 5 && elect()) tma_load3<(WEF & 2) != 0>(sb + CH_WO + (warp - 5) * 28672, &p.wo, j == 0 ? 0 : 32 + j * 192, h * 192 + (j + 8 - warp) % 3 * 64, bWo);
  if (tid == 128 + NSLOT && entry >= 80) {
    uint32_t c;
    int n = 0;
    do { c = ldg_strong32(g_bo + p.layer * 128 + 1); spin_guard(n); } while ((c & 255) + (c >> 8) < 96);
    const uint32_t other = (c >> 8 * (~entry & 1) & 255) + (entry >> 1) - 40;
    entry = other < 40 ? 2 * other + (~entry & 1) : entry % 80;
  }
  if (tid >= 128 && tid <= 128 + NSLOT) sts32(sb + CH_O + (tid - 128) * 4, entry);
  PRO(7);
  __syncthreads();
  if (__shfl_sync(~0u, tid >> 7, 0) == 0) chain_body<0>(p, wq, ak, av); else chain_body<1>(p, wq, ak, av);
}

struct PostParams { CUtensorMap wq, wo, wb, wo2, wb2; int gap, share, layer, look, gap2, pol, slow_n, slow_gap; };
constexpr int PS = 8, PB = 28672;
constexpr int OP_SMEM = PS * PB + 512 + 2048;
enum { IT_ATT = 0, IT_OP = 1, IT_FIN = 2, IT_BQ = 3, IT_Q = 4 };

__device__ __forceinline__ uint32_t item_count(int type, int b) {
  return type == IT_ATT ? 32 : type == IT_OP ? op_split(b) * (b < OP_160 ? 2 : 4) : type == IT_FIN ? 16 : b < BQ_160 ? 6 : b < BQ_80 ? 12 : 24; }
__device__ __forceinline__ uint32_t item_need(int type, int b) { return type == IT_ATT ? 96 : item_count(type - 1, b); }

struct Ring {
  uint32_t sb, bars; int st; uint32_t ph;
  __device__ __forceinline__ uint32_t wait() const { mbar_wait(bars + 8 * st, ph); return sb + st * PB; }
  __device__ __forceinline__ void next() { if (++st == PS) { st = 0; ph ^= 1; } }
  __device__ __forceinline__ void release(int s) const { if ((threadIdx.x & 31) == 0) mbar_arrive(bars + 8 * (PS + s)); }
  __device__ __forceinline__ void pop() { __syncwarp(); release(st); next(); }
};

template <int N>
__device__ __forceinline__ void gemm_item(Ring& r, float* d, int nst, uint32_t go, int go_at, uint32_t wg) {
  auto desc = [](uint32_t lo, uint32_t hi) { uint64_t x; asm("mov.b64 %0, {%1, %2};" : "=l"(x) : "r"(lo), "r"(hi)); return x; };
  auto stage = [&](auto first) {
    const uint32_t base = (r.wait() & 0x3ffff) >> 4, a = base + wg * 256 + (8 << 16), w = base + 512 + (256 << 16);
    wg_fence();
#pragma unroll
    for (int kk = 0; kk < 2; kk++) {
      const uint64_t da = desc(a + kk * 16, 32), db = desc(w + kk * 128, 64 | 1 << 30);
      const int acc = kk || !first.value;
      if (N == 80) wg_ss80_01(d, da, db, acc);
      if (N == 160) wg_ss160_01(d, da, db, acc);
      if (N >= 192) wg_ss192_01(d, da, db, acc);
      if (N == 320) wg_ss128_01(d + 96, da, desc(w + kk * 128 + 768, 64 | 1 << 30), acc);
    }
    wg_commit();
  };
  stage(Int<1>());
  int prev = r.st;
  r.next();
#pragma unroll 1
  for (int kb = 1; kb < nst; kb++) {
    stage(Int<0>());
    if (kb == go_at && threadIdx.x == 0) mbar_arrive(go);
    wg_wait<1>();
    r.release(prev);
    prev = r.st;
    r.next();
  }
  wg_wait<0>();
  reg_fence<N / 2>(d);
  r.release(prev);
}

template <int HALF>
__device__ __forceinline__ void attn_a_warp(Ring& r, const uint32_t (&q)[48], int b, int h) {
  constexpr int NT = HALF ? 5 : 3, NF = 8 * NT;
  const int lane = threadIdx.x & 31, g = lane >> 2, c = lane & 3, seg = (threadIdx.x >> 5) & 3;
  uint32_t f[6][NF];
  int slot[6];
  auto fetch = [&](int u) {
    const uint32_t kv = r.wait() + seg * KV_BYTES;
    slot[u] = r.st;
    r.next();
#pragma unroll
    for (int w = 0; w < 4; w++) {
      uint32_t* d = &f[u][2 * NT * w];
#pragma unroll
      for (int t = 0; t <= HALF; t++) {
        if (u < 3) {
          ldsm4(d + 4 * t, kv + w * 1024 + t * 512 + (lane & 8) * 32 + (lane & 16) * 8 + (lane & 7) * 16);
        } else {
          const uint4 v = lds128(kv + w * 1024 + t * 512 + lane * 16);
          d[4 * t] = v.x; d[4 * t + 1] = v.y; d[4 * t + 2] = v.z; d[4 * t + 3] = v.w;
        }
      }
      const uint2 m = lds64(kv + KV_M + w * 256 + lane * 8);
      d[2 * NT - 2] = m.x; d[2 * NT - 1] = m.y;
    }
    pdl_launch();
  };
  float s[NT][4] = {};
  fetch(0);
#pragma unroll
  for (int u = 0; u < 3; u++) {
    fetch(u + 1);
#pragma unroll
    for (int kk = 0; kk < 4; kk++) {
      const uint32_t* a = &q[16 * u + 4 * kk];
#pragma unroll
      for (int n = 0; n < NT; n++) mma16(s[(n + 1) % NT], a[0], a[1], a[2], a[3], f[u][2 * NT * kk + 2 * n], f[u][2 * NT * kk + 2 * n + 1]);
    }
    r.release(slot[u]);
    pdl_launch();
  }
  fetch(4);
  const float k2 = 0.07216878364870322f * 1.44269504089f, NEG = -INFINITY;
  if (2 * c > g) { s[NT - 2][0] = NEG; s[NT - 1][2] = NEG; }
  if (2 * c + 1 > g) { s[NT - 2][1] = NEG; s[NT - 1][3] = NEG; }
  s[NT - 1][0] = s[NT - 1][1] = NEG;
  uint32_t pp[NT][2]; float inv[2];
#pragma unroll
  for (int hh = 0; hh < 2; hh++) {
    float m = NEG, l = 0.f;
#pragma unroll
    for (int n = 0; n < NT; n++) m = fmaxf(m, fmaxf(s[n][2 * hh], s[n][2 * hh + 1]));
    m = fmaxf(m, __shfl_xor_sync(~0u, m, 1)); m = fmaxf(m, __shfl_xor_sync(~0u, m, 2));
#pragma unroll
    for (int n = 0; n < NT; n++) { const float x = ex2((s[n][2 * hh] - m) * k2), y = ex2((s[n][2 * hh + 1] - m) * k2); l += x + y; pp[n][hh] = pack2(x, y); }
    l += __shfl_xor_sync(~0u, l, 1); l += __shfl_xor_sync(~0u, l, 2);
    asm("rcp.approx.ftz.f32 %0, %1;" : "=f"(inv[hh]) : "f"(l));
  }
  uint32_t* dst = g_o + ((b * 192 + h * 6) * 16 + seg * 4 + HALF * 2) * 128 + lane;
#pragma unroll
  for (int u = 3; u < 6; u++) {
    float o[8][4] = {};
#pragma unroll
    for (int n = 0; n < 8; n++) mma8(o[n], pp[0][0], pp[0][1], f[u][2 * NT * (n >> 1) + 2 * NT - 2 + (n & 1)]);
#pragma unroll
    for (int t = 0; t <= HALF; t++)
#pragma unroll
      for (int n = 0; n < 8; n++) {
        const uint32_t* v = &f[u][2 * NT * (n >> 1) + 4 * t + 2 * (n & 1)];
        mma16(o[n], pp[1 + 2 * t][0], pp[1 + 2 * t][1], pp[2 + 2 * t][0], pp[2 + 2 * t][1], v[0], v[1]);
      }
    r.release(slot[u]);
    if (u == 3) fetch(5);
#pragma unroll
    for (int n = 0; n < 8; n++) {
      dst[(u - 3) * 4096 + (n >> 2) * 2048 + (n & 3) * 32] = pack2(o[n][0] * inv[0], o[n][1] * inv[0]);
      dst[(u - 3) * 4096 + (n >> 2) * 2048 + (n & 3) * 32 + 128] = pack2(o[n][2] * inv[1], o[n][3] * inv[1]);
    }
  }
}

__device__ __forceinline__ void fin_item(Ring& r, uint32_t scratch, int b, int idx) {
  const int warp = threadIdx.x >> 5, lane = threadIdx.x & 31;
  float4 v[1][5];
  {
    const uint32_t base = r.wait();
#pragma unroll
    for (int i = 0; i < 5; i++) v[0][i] = unpack4(lds64(base + ((warp * 5 + i) * 32 + lane) * 8));
    r.pop();
  }
#pragma unroll 1
  for (int k = 0; k < op_split(b); k += 2) {
    const uint32_t base = r.wait();
#pragma unroll
    for (int i = 0; i < 10; i++) {
      const uint2 q = lds64(base + ((i / 5 * 40 + warp * 5 + i % 5) * 32 + lane) * 8);
      float4& t = v[0][i % 5];
      t.x += bf_lo(q.x); t.y += bf_hi(q.x); t.z += bf_lo(q.y); t.w += bf_hi(q.y);
    }
    r.pop();
  }
#pragma unroll
  for (int i = 0; i < 5; i++) g_x[((b * 16 + idx) * 40 + warp * 5 + i) * 32 + lane] = pack4(v[0][i]);
  float mean[1], rs[1];
  ln_stats<1>(v, scratch, mean, rs);
#pragma unroll
  for (int i = 0; i < 5; i++) {
    const int u = warp * 5 + i;
    uint32_t* xn = g_xn + ((b * 20 + (u >> 1)) * 16 + idx) * 128 + (u & 1) * 64 + lane;
    xn[0] = pack2((v[0][i].x - mean[0]) * rs[0], (v[0][i].y - mean[0]) * rs[0]);
    xn[32] = pack2((v[0][i].z - mean[0]) * rs[0], (v[0][i].w - mean[0]) * rs[0]);
  }
}

__global__ void __launch_bounds__(384, 1) post_kernel(const __grid_constant__ PostParams p) {
  extern __shared__ __align__(1024) uint8_t smem_raw[];
  const uint32_t sb = s2u(smem_raw), bars = sb + PS * PB;
  const uint32_t bIF = bars + 128, bIE = bars + 160, done = bars + 192, bGo = bars + 224, slots = bars + 240, scratch = bars + 512;
  const int warp = __shfl_sync(~0u, threadIdx.x >> 5, 0), lane = threadIdx.x & 31;
  if (warp == 9) PST(0);
  if (warp == 0 && blockIdx.x < 36) TRACE(0);
  if (warp >= 8) {
    asm volatile("setmaxnreg.dec.sync.aligned.u32 56;");
    if (warp == 10) {
      pdl_launch();
      if (sb & 1023) __trap();
      if (lane < 29) mbar_init(bars + 8 * lane, lane < 8 ? 1 : lane < 16 ? 8 : lane < 20 ? 1 : lane < 24 ? 2 : lane < 28 ? 8 : 1);
      if (lane == 0) sts32(slots + 16, p.gap);
      fence_async();
    }
    if (warp == 8 && lane < 5) asm volatile("prefetch.tensormap [%0];" :: "l"(&p.wq + lane) : "memory");
    if (warp != 9) bar_sync(2, 384);
    if (warp == 9) {
      PST(1);
      const int b = lane & 15;
      bool queries = QA_END < 16 && blockIdx.x < 36;
      for (int n = 0;; n++) {
        if (n > 0) { mbar_wait(bGo, (n - 1) & 1); mbar_wait(bIE + 8 * (n & 3), ((n >> 2) & 1) ^ 1); }
        int code = -1, spin = 0, ticket = 0;
        if (queries) {
          if (lane == 0) ticket = n == 0 ? blockIdx.x : 36 + atomicAdd(g_sync + SY_QC, 1);
          ticket = __shfl_sync(~0u, ticket, 0);
          queries = ticket < (16 - QA_END) * 32;
          if (queries) code = IT_Q << 16 | (QA_END + ticket % (16 - QA_END)) << 8 | ticket / (16 - QA_END);
        }
        if (!queries && lane == 0) asm volatile("atom.relaxed.gpu.global.add.u32 %0, [%1], 1;" : "=r"(ticket) : "l"(g_sync + SY_T) : "memory");
        while (!queries) {
          const uint4 hd = ldg_strong128(g_sync + b * 8), pr = ldg_strong128(g_sync + b * 8 + 4);
          if (n == 0 && spin == 0 && hd.x != 0x7fffffff) PST(2);
          const uint32_t hv[4] = {hd.x, hd.y, hd.z, hd.w}, pv[4] = {pr.x, pr.y, pr.z, pr.w};
          const uint32_t chain_done = __ballot_sync(~0u, (pr.x & 0xffff) >= 96) & 0xffff;
          int left[4], avail[4], rdy = 0, claimed = 0, upstream = 0;
#pragma unroll
          for (int t = 0; t < 4; t++) {
            const int cnt = lane < 16 ? item_count(t, b) : 0;
            left[t] = max(cnt - (int)hv[t], 0);
            claimed += cnt - left[t];
            const bool ready = (pv[t] & 0xffff) >= item_need(t, b);
            rdy |= ready << t;
            bool ok = ready || (t == IT_ATT ? pr.x >= 0x10000 : !upstream || (t == IT_OP && (chain_done >> 15 & 1)));
            if (t == IT_BQ && (chain_done >> BQ_HOLD & 1) && !(chain_done >> 15)) ok = false;
            avail[t] = ok ? left[t] : 0;
            upstream |= __any_sync(~0u, left[t] > 0);
          }
          if (!upstream) break;
          int rank = max(__shfl_sync(~0u, ticket, 0) - __reduce_add_sync(~0u, claimed), 0), type = -1, mine = 0;
          {
            const int a = b >= BQ_RUSH && (rdy >> IT_BQ & 1) ? avail[IT_BQ] : 0, tot = __reduce_add_sync(~0u, a);
            if (rank < tot) { type = IT_BQ; mine = a; } else rank -= tot;
            avail[IT_BQ] -= a;
          }
#pragma unroll
          for (int c = 0; c < 8; c++) {
            const int t = c == PR_FIN || c == 5 ? IT_FIN : c == PR_ATT || c == 7 ? IT_ATT : c == PR_OP || c == 4 ? IT_OP : IT_BQ;
            int a = c == PR_ATT || ((rdy >> t & 1) == (c < 4)) ? avail[t] : 0;
            if (t == IT_OP && OP_EARLY) a = c == PR_OP ? avail[t] : 0;
            if (c == 7) a = b < QA_END && !(rdy & 1) && ((chain_done << 1 | 1) >> b & 1) ? left[t] : 0;
            const int tot = __reduce_add_sync(~0u, a);
            if (type < 0) { if (rank < tot) { type = t; mine = a; } else rank -= tot; }
          }
          if (type >= 0) {
#pragma unroll
            for (int o = 1; o < 16; o <<= 1) { const int y = __shfl_up_sync(~0u, mine, o); if (lane >= o) mine += y; }
            const int blk = __ffs(__ballot_sync(~0u, mine > rank)) - 1;
            const int early = !(__shfl_sync(~0u, rdy, blk) >> type & 1);
            uint32_t idx = 0;
            if (n == 0 && spin == 0) PST(3);
            if (lane == 0) asm volatile("atom.relaxed.gpu.global.add.u32 %0, [%1], 1;" : "=r"(idx) : "l"(g_sync + blk * 8 + type) : "memory");
            ld_acquire(g_sync + blk * 8 + 4 + type);
            idx = __shfl_sync(~0u, idx, 0);
            if (idx < item_count(type, blk)) { code = (__shfl_sync(~0u, pr.y, 15) < 32) << 23 | (chain_done >> 15 & 1) << 22 | (chain_done >> p.look & 1) << 21 | early << 20 | type << 16 | blk << 8 | idx; break; }
          } else {
            __nanosleep(50);
          }
          spin_guard(spin);
        }
        if (n == 0) bar_sync(2, 384);
        if (lane == 0) {
          fence_async_global();
          sts32(slots + 4 * (n & 3), code);
          mbar_arrive(bIF + 8 * (n & 3));
        }
        __syncwarp();
        if (code < 0) break;
      }
    } else if (warp == 8) {
      if (elect()) {
        uint32_t dst = sb, bar = bars, ph = 1, next = clk32(), gap = 0;
        auto acquire = [&](uint32_t kb) {
          mbar_wait(bar + 8 * PS, ph);
          mbar_expect(bar, kb * 1024);
          if (gap) {
            uint32_t now;
            do now = clk32(); while ((int)(now - next) < 0);
            next = ((int)(now - next) > 100 ? now - 100 : next) + kb * gap;
          }
        };
        auto advance = [&]() { dst += PB; bar += 8; if (dst == bars) { dst = sb; bar = bars; ph ^= 1; } };
        auto depend = [&](const uint32_t* c, uint32_t need) { wait_count(c, need); fence_async_global(); };
#pragma unroll 1
        for (int n = 0;; n++) {
          mbar_wait(bIF + 8 * (n & 3), (n >> 2) & 1);
          const int code = (int)lds32(slots + 4 * (n & 3));
          if (code < 0) break;
          const int type = (code >> 16) & 15, b = (code >> 8) & 255, idx = code & 255;
          const bool early = code >> 20 & 1, go = !(code >> 21 & 1);
          mbar_arrive(bIE + 8 * (n & 3));
          gap = !(code >> 22 & 1) ? lds32(slots + 16) : type == IT_ATT || type == IT_FIN ? 0 : p.gap2;
          const uint32_t* progress = g_sync + b * 8 + 4 + type;
          if (type == IT_ATT && b >= QA_END) {
            depend(g_sync + SY_Q, (16 - QA_END) * 32);
#pragma unroll 1
            for (int u = 0; u < 2; u++) { acquire(24); bulk_load_last(dst, g_q + (((b - QA_END) * 32 + idx) * 2 + u) * 1536, 24576, bar); advance(); }
          } else if (type == IT_FIN) {
            acquire(10);
            bulk_load(dst, g_x + (b * 16 + idx) * 1280, 10240, bar);
            advance();
            if (early) depend(progress, item_need(type, b));
            if (go) mbar_arrive(bGo);
            const uint2* src = g_part + (b * 16 + idx) * 16 * 1280;
#pragma unroll 1
            for (int i = 0; i < op_split(b); i += 2) { acquire(20); bulk_load_last(dst, src + i * 1280, 20480, bar); advance(); }
            if (!go && p.pol) mbar_arrive(bGo);
          } else {
            const bool op = type == IT_OP, bq = type == IT_BQ;
            const int width = op ? op_width(b) : bq ? bq_width(b) : 192, nb = (width + 63) >> 6, lt = width == 320 ? 1 : 2;
            const int nst = op ? 192 / op_split(b) : 20, kb0 = op ? (idx >> lt) * nst : 0;
            const int col = (op ? idx & ((1 << lt) - 1) : idx) * width;
            const bool whole = !(width & 63);
            const CUtensorMap* m = op ? (whole ? &p.wo : &p.wo2) : bq ? (whole ? &p.wb : &p.wb2) : &p.wq;
            const uint32_t* a = op ? g_o + (b * 192 + kb0) * 2048 : g_xn + b * 20 * 2048;
            int row = kb0 * 32, pre = early && (op || bq) ? min(nst, PRE_MAX) : 0;
            int slow = (code >> 22 & 3) == 3 ? p.slow_n : 0;
            if (slow) gap = p.slow_gap;
            auto weights = [&]() {
              if (slow && --slow == 0) gap = 0;
              acquire(8 + nb * 4);
              if (whole) {
                tma_load3z(dst + 8192, m, row, col >> 6, bar);
              } else {
                tma_load(dst + 8192, m, col, row, bar); tma_load(dst + 12288, m, col + 64, row, bar);
                if (nb == 3) tma_load(dst + 16384, m, col + 128, row, bar);
              }
              row += 32;
            };
            if (pre) {
              uint32_t da = dst, ba = bar;
#pragma unroll 1
              for (int kb = 0; kb < pre; kb++) { weights(); advance(); }
              depend(progress, item_need(type, b));
#pragma unroll 1
              for (int kb = 0; kb < pre; kb++) {
                bulk_load(da, a, 8192, ba);
                a += 2048; da += PB; ba += 8;
                if (da == bars) { da = sb; ba = bars; }
              }
            }
#pragma unroll 1
            for (int kb = pre; kb < nst; kb++) { weights(); if (op && OEF) bulk_load_last(dst, a, 8192, bar); else bulk_load(dst, a, 8192, bar); a += 2048; advance(); }
          }
          if (type == IT_ATT) {
            if (early) depend(progress, 96);
            if (go) mbar_arrive(bGo);
            const uint8_t* src = g_kv + (size_t)(idx * 6 * NSEG + b * 4) * KV_BYTES;
#pragma unroll 1
            for (int u = 0; u < 6; u++) {
              acquire(20);
              bulk_load_last(dst, src, 20480, bar);
              src += u == 2 ? -3 * KV_V : 2 * KV_V;
              advance();
            }
            if (!go && p.pol && ATT_LOOK) mbar_arrive(bGo);
          }
        }
      }
    } else if (warp == 11) {
      uint32_t smid, nsm, used = 0;
      asm("mov.u32 %0, %%smid;" : "=r"(smid)); asm("mov.u32 %0, %%nsmid;" : "=r"(nsm));
      for (int n = 0; n < 64 && used < 96; n++) {
        uint32_t peers = 0;
        used = 0;
        for (uint32_t i = lane; i < min(nsm, 256u); i += 32) {
          const bool taken = ldg_strong32(g_smuse + i) == p.layer + 1;
          used += taken;
          peers += abs((int)(g_smclk[i] - g_smclk[smid & 255])) < 4000 && !taken;
        }
        used = __reduce_add_sync(~0u, used);
        sts32(slots + 16, max(p.gap, (int)min(__reduce_add_sync(~0u, peers), 18u) * p.share >> 3));
      }
    } else if (warp == 10 && lane == 0) {
      for (int n = 0;; n++) {
        mbar_wait(bIF + 8 * (n & 3), (n >> 2) & 1);
        const int code = (int)lds32(slots + 4 * (n & 3));
        if (code < 0) break;
        const int type = (code >> 16) & 15, b = (code >> 8) & 255;
        mbar_wait(done + 8 * (n & 3), (n >> 2) & 1);
        if (type != IT_BQ) red_release(type == IT_Q ? g_sync + SY_Q : g_sync + b * 8 + 5 + type, 1);
        mbar_arrive(bIE + 8 * (n & 3));
      }
    }
  } else {
    asm volatile("setmaxnreg.inc.sync.aligned.u32 224;");
    bar_sync(2, 384);
    const int g = lane >> 2, c = lane & 3;
    Ring r = {sb, bars, 0, 0};
#pragma unroll 1
    for (int n = 0;; n++) {
      mbar_wait(bIF + 8 * (n & 3), (n >> 2) & 1);
      const int code = __shfl_sync(~0u, (int)lds32(slots + 4 * (n & 3)), 0);
      if (code < 0) { TRACE(2); break; }
      const int type = (code >> 16) & 15, b = (code >> 8) & 255, idx = code & 255;
      ITEM(code & 0xfffff, 0);
      if (type == IT_ATT || type == IT_Q) {
        uint32_t q[48];
        if (type == IT_Q || b < QA_END) {
          float d[96];
          gemm_item<192>(r, d, 20, bGo, type == IT_Q ? 12 : -1, warp >> 2);
#pragma unroll
          for (int i = 0; i < 48; i++) q[i] = pack2(d[2 * i], d[2 * i + 1]);
        } else {
#pragma unroll
          for (int u = 0; u < 2; u++) {
            const uint32_t base = r.wait() + threadIdx.x * 16;
#pragma unroll
            for (int i = 0; i < 6; i++) {
              const uint4 v = lds128(base + i * 4096);
              q[24 * u + 4 * i] = v.x; q[24 * u + 4 * i + 1] = v.y; q[24 * u + 4 * i + 2] = v.z; q[24 * u + 4 * i + 3] = v.w;
            }
            r.pop();
          }
        }
        if (type == IT_Q) {
          uint4* dst = g_q + ((b - QA_END) * 32 + idx) * 3072 + threadIdx.x;
#pragma unroll
          for (int i = 0; i < 12; i++) dst[i * 256] = make_uint4(q[4 * i], q[4 * i + 1], q[4 * i + 2], q[4 * i + 3]);
        } else if (warp < 4) {
          attn_a_warp<0>(r, q, b, idx);
        } else {
          attn_a_warp<1>(r, q, b, idx);
        }
      } else if (type == IT_FIN) {
        fin_item(r, scratch, b, idx);
      } else {
        float d[160];
        const int width = type == IT_OP ? op_width(b) : bq_width(b), nst = type == IT_OP ? 192 / op_split(b) : 20;
        const int go_at = max(nst - (code >> 21 & 1 ? p.pol : 6), 1);
        if (width == 320) {
          gemm_item<320>(r, d, nst, bGo, go_at, warp >> 2);
        } else if (width == 160 || BQ_80 == 16) {
          gemm_item<160>(r, d, nst, bGo, go_at, warp >> 2);
#pragma unroll
          for (int i = 80; i < 160; i++) d[i] = 0.f;
        } else {
          gemm_item<80>(r, d, nst, bGo, go_at, warp >> 2);
#pragma unroll
          for (int i = 40; i < 160; i++) d[i] = 0.f;
        }
        if (type == IT_OP) {
          const int tiles = DM / width;
          uint2* dst = g_part + (((b * 16 + warp * 2) * 16 + idx / tiles) * 40 + idx % tiles * (width / 16)) * 32 + lane;
#pragma unroll
          for (int u = 0; u < 20; u++) {
            if (u % 5 == 0 && u * 16 >= width) break;
            dst[u * 32] = make_uint2(pack2(d[8 * u], d[8 * u + 1]), pack2(d[8 * u + 4], d[8 * u + 5]));
            dst[(640 + u) * 32] = make_uint2(pack2(d[8 * u + 2], d[8 * u + 3]), pack2(d[8 * u + 6], d[8 * u + 7]));
          }
        } else {
          const int row = b * 128 + warp * 16 + g;
          const int h0 = idx * (width / 20);
          const float sc = h0 < 32 ? 0.22360679775f * 1.44269504089f : 1.f;
          const bool lo = c < 2;
          uint32_t* da = g_bqkv + (h0 * 256 + (row >> 3)) * 96 + lane;
          uint32_t* db = da + 256 * 96 + (lo ? 2 : -2);
          uint32_t pad[2];
#pragma unroll
          for (int rr = 0; rr < 2; rr++) pad[rr] = c & 1 || h0 < 32 ? 0u : h0 >= 64 ? 0x00003f80u : poly_group((row >> 3) + rr) ? 0x3f803f80u : 0u;
#pragma unroll
          for (int q = 0; q < 8; q++) {
            if (!(q & 1) && q * 40 >= width) break;
#pragma unroll
            for (int rr = 0; rr < 2; rr++) {
              uint32_t w[5];
#pragma unroll
              for (int i = 0; i < 5; i++) w[i] = pack2(d[20 * q + 4 * i + 2 * rr] * sc, d[20 * q + 4 * i + 2 * rr + 1] * sc);
              const int o = q * 2 * 256 * 96 + rr * 96;
              da[o] = w[0]; da[o + 32] = w[1]; da[o + 64] = lo ? w[2] : pad[rr];
              db[o] = lo ? w[3] : w[2]; db[o + 32] = lo ? w[4] : w[3]; db[o + 64] = lo ? pad[rr] : w[4];
            }
          }
        }
      }
      __syncwarp();
      if (lane == 0) mbar_arrive(done + 8 * (n & 3));
      if ((code >> 21 & 1) && (p.pol == 0 || (type == IT_ATT && !ATT_LOOK)) && threadIdx.x == 128) mbar_arrive(bGo);
      ITEM(code & 0xfffff, 1);
    }
  }
}

constexpr int AB_SMEM = 1024 + 98304 + 51200 + 4 * 16384 + 256 + 10240;
#define AB_LW 1
#define AB_U 8
#define AB_WG 4
constexpr int AB_T = AB_WG * 128, AB_PASS = 8 / AB_WG;
__device__ __forceinline__ uint32_t fma2(uint32_t a, uint32_t b, uint32_t c) { uint32_t r; asm("fma.rn.bf16x2 %0, %1, %2, %3;" : "=r"(r) : "r"(a), "r"(b), "r"(c)); return r; }
__device__ __forceinline__ uint32_t ex2_pair(float a, float b, uint32_t one, uint32_t c0) {
  const uint32_t e = __byte_perm(__float_as_uint(a), __float_as_uint(b), 0x6521);
  uint32_t x, r;
  asm("lop3.b32 %0, %1, 0x007f007f, %2, 0xEA;" : "=r"(x) : "r"(e), "r"(one));
  const uint32_t m = fma2(fma2(c0, x, 0x3c0d3c0du), x, 0x3f2b3f2bu);
  asm("lop3.b32 %0, %1, %2, 0x7f807f80, 0xE4;" : "=r"(r) : "r"(e), "r"(m));
  return r;
}
__device__ __forceinline__ float sq2(uint32_t w) { const float a = bf_lo(w), b = bf_hi(w); return fmaf(a, a, b * b); }

__device__ __forceinline__ void attn_b_store(const float* o, int h, int row0, int lane) {
  const int g = lane >> 2, c = lane & 3;
  const float i0 = __frcp_rn(__shfl_sync(~0u, o[8], (lane & ~3) | 2)), i1 = __frcp_rn(__shfl_sync(~0u, o[10], (lane & ~3) | 2));
#pragma unroll
  for (int jj = 0; jj < 3; jj++) {
    if (jj < 2 || c < 2) {
      const int col = h * 20 + 8 * jj + 2 * c;
      uint32_t* dst = g_of + (((row0 >> 7) * 10 + (col >> 6)) * 16 + (row0 >> 3 & 15)) * 256 + (col >> 3 & 7) * 32 + g * 4 + (col >> 1 & 3);
      dst[0] = pack2(o[4 * jj] * i0, o[4 * jj + 1] * i0);
      dst[256] = pack2(o[4 * jj + 2] * i1, o[4 * jj + 3] * i1);
    }
  }
}

struct AbParams { Weights next; uint32_t* done; uint32_t* out; };
__global__ void __launch_bounds__(AB_T + 32, 1) attn_b_kernel(const __grid_constant__ AbParams p) {
  extern __shared__ uint8_t smem_raw[];
  const uint32_t sb = (s2u(smem_raw) + 1023) & ~1023u, sK = sb, sV = sb + 98304, bars = sV + 51200 + 4 * 16384;
  const uint32_t bF = bars + 64, bW = bars + 72, bA = bars + 80, bE = bars + 128, smax = bars + 176;
  auto ring = [&](int i) { return i < 2 ? sK + 51200 + i * 16384 : sV + 51200 + (i - 2) * 16384; };
  const int warp = __shfl_sync(~0u, threadIdx.x >> 5, 0), lane = threadIdx.x & 31;
  const int h = blockIdx.x >> 2, quarter = blockIdx.x & 3;
  TRACE(0);
  pdl_launch();
  if (threadIdx.x < 22) mbar_init(bars + 8 * threadIdx.x, threadIdx.x == 8 ? AB_T / 32 : threadIdx.x >= 16 ? 8 : 1);
  if (threadIdx.x == 32) sts64(smax, 0, 0);
  fence_async();
  __syncthreads();
  pdl_wait();
  const int blk = quarter * 4 + (h >> 3), cg = h & 7;
  auto unsafe = [&]() { const float2 m = lds64f(smax); return !(m.x * m.y <= 10000.f); };
  if (warp == AB_T / 32) {
    auto load_w = [&]() {
      mbar_expect(bW, 102400);
      for (int i = 0; i < 4; i++) bulk_load((i < 2 ? sK : sV) + (i & 1) * 25600, g_wb + cg * 6400 + i * 1600, 25600, bW);
    };
    if (elect()) {
      const uint32_t* gk = g_bqkv + (32 + h) * 256 * 96;
#pragma unroll 1
      for (int i = 0; i < 8; i++) {
        if (i >= AB_LW) mbar_wait(bars + 8 * (i - AB_LW), 0);
        mbar_expect(bars + 8 * i, 24576);
        bulk_load_last(sK + i * 12288, gk + i * 3072, 12288, bars + 8 * i);
        bulk_load_last(sV + i * 12288, gk + 32 * 256 * 96 + i * 3072, 12288, bars + 8 * i);
      }
    }
    __syncwarp();
    if (blockIdx.x < NSLOT) for (int i = lane; i < 512; i += 32) reinterpret_cast<uint4*>(pool_at(blockIdx.x * 8192))[i] = make_uint4(0, 0, 0, 0);
    if (blockIdx.x == 127) for (int i = lane; i < SY_N; i += 32) g_sync[i] = 0;
    if (p.next.w[0] && lane == 0) {
      for (int i = 0; i < AB_PF; i++) { const uint32_t t0 = clk32(); while (clk32() - t0 < (i ? AB_PFD : AB_PF0)) __nanosleep(200); prefetch_weights(p.next, i); }
    }
    __syncwarp();
    mbar_wait(bF, 0);
    const bool redo = unsafe();
    if (!redo && lane == 0) load_w();
    if (lane < 16) asm volatile("cp.async.bulk.prefetch.L2.global [%0], 1280;" :: "l"(g_x + ((blk * 16 + lane) * 40 + cg * 5) * 32) : "memory");
    __syncwarp();
    bar_sync(1, AB_T + 32);
    if (lane == 0) {
      ABT(!!p.out, 1);
      red_release(p.done + quarter * 32, 1);
      ABT(!!p.out, 2);
      if (redo) load_w();
      wait_count(p.done + quarter * 32, 32);
      fence_async_global();
      ABT(!!p.out, 3);
      for (int kb = 0; kb < 10; kb++) {
        const int i = kb < 6 ? kb : kb - 6;
        if (kb >= 6) mbar_wait(bE + 8 * i, 0);
        mbar_expect(bA + 8 * i, 16384);
        bulk_load(ring(i), g_of + (blk * 10 + kb) * 4096, 16384, bA + 8 * i);
      }
    }
    return;
  }
  float qmax = 0.f;
  const uint32_t one = opaque(0x3f803f80u + (threadIdx.x >> 10)), c0 = opaque(0x3ea83ea8u + (threadIdx.x >> 10));
#pragma unroll 1
  for (int pass = 0; pass < AB_PASS; pass++) {
    const int row0 = quarter * 512 + ((warp >> 2) * AB_PASS + pass) * 64 + (warp & 3) * 16;
    const uint32_t* gq = g_bqkv + (h * 256 + (row0 >> 3)) * 96 + lane;
    const uint32_t q0 = gq[0], q1 = gq[96], q2 = gq[32], q3 = gq[128];
    uint32_t q4 = gq[64], q5 = gq[160];
    const uint32_t z0 = gq[64 + 3 - (lane & 3)], z1 = gq[160 + 3 - (lane & 3)];
    {
      float n0 = sq2(q0) + sq2(q2) + sq2(q4), n1 = sq2(q1) + sq2(q3) + sq2(q5);
      n0 += __shfl_xor_sync(~0u, n0, 1); n1 += __shfl_xor_sync(~0u, n1, 1);
      n0 += __shfl_xor_sync(~0u, n0, 2); n1 += __shfl_xor_sync(~0u, n1, 2);
      qmax = (n0 > qmax || n0 != n0) ? n0 : qmax;
      qmax = (n1 > qmax || n1 != n1) ? n1 : qmax;
    }
    if (pass == AB_PASS - 1) {
      float kmax = 0.f;
#pragma unroll
      for (int i = 0; i < SEQ / AB_T; i++) {
        const int key = threadIdx.x + AB_T * i;
        const uint32_t a = sK + (key >> 3) * 384 + (key & 7) * 16;
        const uint4 x = lds128(a), y = lds128(a + 128);
        const uint2 z = lds64(a + 256);
        const float n = ((sq2(x.x) + sq2(x.y)) + (sq2(x.z) + sq2(x.w))) + ((sq2(y.x) + sq2(y.y)) + (sq2(y.z) + sq2(y.w))) + (sq2(z.x) + sq2(z.y));
        kmax = (n > kmax || n != n) ? n : kmax;
      }
      const uint32_t kb = __reduce_max_sync(~0u, __float_as_uint(kmax) & 0x7fffffffu), qb = __reduce_max_sync(~0u, __float_as_uint(qmax) & 0x7fffffffu);
      if (lane < 2) asm volatile("red.shared.max.u32 [%0], %1;" :: "r"(smax + 4 * lane), "r"(lane ? kb : qb) : "memory");
      __syncwarp();
    }
    if ((lane & 3) == 2) { q4 = 0xBF8043C0u; q5 = 0xBF8043C0u; }
    float o[12];
    auto desc = [](uint32_t lo, uint32_t hi) { uint64_t d; asm("mov.b64 %0, {%1, %2};" : "=l"(d) : "r"(lo), "r"(hi)); return d; };
    const uint32_t k0 = (uint32_t)mkdesc(sK, 128, 0, 0), k1 = (uint32_t)mkdesc(sK + 256, 0, 0, 0), v0 = (uint32_t)mkdesc(sV, 384, 0, 0);
    float sa[16], sb2[16];
    uint32_t pa[8], pb[8];
    auto qk = [&](float* s, uint32_t t) {
      wg_rs32_00(s, q0, q1, q2, q3, desc(k0 + t, 24), 0);
      wg_rs32_00(s, q4, q5, z0, z1, desc(k1 + t, 24), 1);
      wg_commit();
    };
    auto step = [&](float* s, uint32_t* pp, int g0, uint32_t t, uint32_t nx, int acc) {
      wg_wait<1>();
      reg_fence<16>(s);
#pragma unroll
      for (int i = 0; i < 8; i++) pp[i] = poly_group(g0 + (i >> 1)) ? ex2_pair(s[2 * i], s[2 * i + 1], one, c0) : pack2(ex2(s[2 * i]), ex2(s[2 * i + 1]));
      wg_fence();
      wg_rs24_01(o, pp[0], pp[1], pp[2], pp[3], desc(v0 + t, 8), acc);
      wg_rs24_01(o, pp[4], pp[5], pp[6], pp[7], desc(v0 + t + 48, 8), 1);
      qk(s, nx);
    };
    if (pass == 0) mbar_wait(bars, 0);
    wg_fence();
    qk(sa, 0);
    qk(sb2, 96);
#pragma unroll 1
    for (uint32_t t = 0; t < 64 * 96; t += AB_U * 96) {
      const uint32_t nx = t + AB_U * 96 < 64 * 96 ? t + AB_U * 96 : 0;
      if (pass == AB_PASS - 1 && t == 40 * 96 && lane == 0) mbar_arrive(bF);
#pragma unroll
      for (int u = 0; u < AB_U; u += 2) {
        if (u == AB_U - 2 && pass == 0) mbar_wait(bars + 8 * (nx / 768), 0);
        step(sa, pa, 0, t + u * 96, u + 2 < AB_U ? t + (u + 2) * 96 : nx, u | t);
        step(sb2, pb, 4, t + u * 96 + 96, (u + 2 < AB_U ? t + (u + 2) * 96 : nx) + 96, 1);
      }
    }
    wg_wait<0>();
    reg_fence<12>(o); reg_fence<16>(sa); reg_fence<16>(sb2);
    attn_b_store(o, h, row0, lane);
  }
  mbar_wait(bF, 0);
  if (unsafe())
#pragma unroll 1
  for (int pass = 0; pass < AB_PASS; pass++) {
    const int row0 = quarter * 512 + ((warp >> 2) * AB_PASS + pass) * 64 + (warp & 3) * 16;
    const uint32_t* gq = g_bqkv + (h * 256 + (row0 >> 3)) * 96 + lane;
    const uint32_t q0 = gq[0], q1 = gq[96], q2 = gq[32], q3 = gq[128], q4 = gq[64], q5 = gq[160];
    float o[12];
#pragma unroll
    for (int i = 0; i < 12; i++) o[i] = 0.f;
    float m0 = -INFINITY, m1 = -INFINITY;
#pragma unroll 1
    for (int kt = 0; kt < 32; kt++) {
      float s[32];
      const uint64_t dk = mkdesc(sK + kt * 3072, 128, 384, 0), dk2 = mkdesc(sK + kt * 3072 + 256, 0, 384, 0);
      wg_fence();
      wg_rs64_00(s, q0, q1, q2, q3, dk, 0);
      wg_rs64_00(s, q4, q5, 0, 0, dk2, 1);
      wg_commit();
      wg_wait<0>();
      reg_fence<32>(s); reg_fence<12>(o);
      float n0 = m0, n1 = m1;
#pragma unroll
      for (int jj = 0; jj < 8; jj++) { n0 = fmaxf(n0, fmaxf(s[4 * jj], s[4 * jj + 1])); n1 = fmaxf(n1, fmaxf(s[4 * jj + 2], s[4 * jj + 3])); }
      n0 = fmaxf(n0, __shfl_xor_sync(~0u, n0, 1)); n0 = fmaxf(n0, __shfl_xor_sync(~0u, n0, 2));
      n1 = fmaxf(n1, __shfl_xor_sync(~0u, n1, 1)); n1 = fmaxf(n1, __shfl_xor_sync(~0u, n1, 2));
      const float r0 = ex2(m0 - n0), r1 = ex2(m1 - n1);
      m0 = n0; m1 = n1;
#pragma unroll
      for (int jj = 0; jj < 3; jj++) { o[4 * jj] *= r0; o[4 * jj + 1] *= r0; o[4 * jj + 2] *= r1; o[4 * jj + 3] *= r1; }
      uint32_t pp[16];
#pragma unroll
      for (int jj = 0; jj < 8; jj++) {
        pp[2 * jj] = pack2(ex2(s[4 * jj] - m0), ex2(s[4 * jj + 1] - m0));
        pp[2 * jj + 1] = pack2(ex2(s[4 * jj + 2] - m1), ex2(s[4 * jj + 3] - m1));
      }
      const uint64_t dv = mkdesc(sV + kt * 3072, 384, 128, 0);
      wg_fence();
#pragma unroll
      for (int kk = 0; kk < 4; kk++) wg_rs24_01(o, pp[4 * kk], pp[4 * kk + 1], pp[4 * kk + 2], pp[4 * kk + 3], dv + kk * 48, 1);
      wg_commit();
    }
    wg_wait<0>();
    reg_fence<12>(o);
    attn_b_store(o, h, row0, lane);
  }
  ABT(!!p.out, 0);
  bar_arrive(1, AB_T + 32);
  if (warp >= 12) return;
  const int g = lane >> 2, c = lane & 3;
  const bool live = opaque(threadIdx.x) < 256;
  float d[40] = {};
  uint2* x = g_x + ((blk * 16 + warp * 2) * 40 + cg * 5) * 32 + lane;
  if (warp < 8) {
#pragma unroll
  for (int i = 0; i < 10; i++) {
    const int r = i / 5, u = i % 5;
    const float4 t = unpack4(x[(r * 40 + u) * 32]);
    d[8 * u + 2 * r] = t.x; d[8 * u + 2 * r + 1] = t.y; d[8 * u + 4 + 2 * r] = t.z; d[8 * u + 5 + 2 * r] = t.w;
  }
  mbar_wait(bW, 0);
  reg_fence<40>(d);
  ABT(!!p.out, 4);
#pragma unroll 1
  for (int kb = 0; kb < 10; kb++) {
    const int i = kb < 6 ? kb : kb - 6;
    mbar_wait(bA + 8 * i, kb >= 6);
    const uint64_t da = mkdesc(ring(i) + (warp >> 2) * 8192, 128, 1024, 0), db = mkdesc(kb < 5 ? sK + kb * 10240 : sV + (kb - 5) * 10240, 1280, 128, 0);
    wg_fence();
#pragma unroll
    for (int kk = 0; kk < 4; kk++) wg_ss80_01(d, da + kk * 16, db + kk * 160, 1);
    wg_commit();
    if (kb > 0 && kb < 5) { wg_wait<1>(); if (lane == 0) mbar_arrive(bE + 8 * (kb - 1)); }
  }
  wg_wait<0>();
  reg_fence<40>(d);
  }
  ABT(!!p.out, 5);
  if (p.out) {
    if (warp >= 8) return;
    const uint32_t stage = sK + 83968 + warp * 2560 + (warp < 4 ? 0 : 131328 - 10240);
#pragma unroll
    for (int u = 0; u < 5; u++)
      stsm4(stage + (lane & 15) * 160 + u * 32 + (lane >> 4) * 16, pack2(d[8 * u], d[8 * u + 1]), pack2(d[8 * u + 2], d[8 * u + 3]),
            pack2(d[8 * u + 4], d[8 * u + 5]), pack2(d[8 * u + 6], d[8 * u + 7]));
    __syncwarp();
    uint4* out = reinterpret_cast<uint4*>(p.out + (blk * 128 + warp * 16) * (DM / 2) + cg * 40);
#pragma unroll
    for (int i = 0; i < 5; i++) { const int e = i * 32 + lane, r = e / 10; out[r * (DM / 8) + e - r * 10] = lds128(stage + e * 16); }
  } else {
    float2* stat = g_stat + blk * 1024 + (warp & 7) * 16 + g;
    float mean[2], rs[2];
#pragma unroll
    for (int r = 0; r < 2; r++) {
      float t = 0.f, q = 0.f;
#pragma unroll
      for (int i = 0; i < 10; i++) t += d[4 * i + 2 * r] + d[4 * i + 2 * r + 1];
      t += __shfl_xor_sync(~0u, t, 1); t += __shfl_xor_sync(~0u, t, 2);
      t *= 1.f / 80;
#pragma unroll
      for (int i = 0; i < 10; i++) { const float a = d[4 * i + 2 * r] - t, b = d[4 * i + 2 * r + 1] - t; q += a * a + b * b; }
      q += __shfl_xor_sync(~0u, q, 1); q += __shfl_xor_sync(~0u, q, 2);
      if (c == r && live) asm volatile("st.relaxed.gpu.global.v2.b32 [%0], {%1, %2};" :: "l"(stat + cg * 128 + r * 8), "r"(__float_as_uint(t)), "r"(nz(__float_as_uint(q))) : "memory");
    }
#pragma unroll
    for (int i = 0; i < 10; i++) {
      const int r = i / 5, u = i % 5;
      if (live) x[(r * 40 + u) * 32] = make_uint2(pack2(d[8 * u + 2 * r], d[8 * u + 2 * r + 1]), pack2(d[8 * u + 4 + 2 * r], d[8 * u + 5 + 2 * r]));
    }
    ABT(0, 6);
    uint2 e[4];
    int n = 0;
    do {
#pragma unroll
      for (int i = 0; i < 4; i++)
        asm volatile("ld.relaxed.gpu.global.v2.b32 {%0, %1}, [%2];" : "=r"(e[i].x), "=r"(e[i].y) : "l"(stat + (2 * c + (i & 1)) * 128 + (i >> 1) * 8) : "memory");
      spin_guard(n);
    } while (__any_sync(~0u, min(min(e[0].y, e[1].y), min(e[2].y, e[3].y)) == 0 && live));
#pragma unroll
    for (int r = 0; r < 2; r++) {
      const float m0 = __uint_as_float(e[2 * r].x), m1 = __uint_as_float(e[2 * r + 1].x);
      float t = m0 + m1;
      t += __shfl_xor_sync(~0u, t, 1); t += __shfl_xor_sync(~0u, t, 2);
      t *= 0.125f;
      float q = __uint_as_float(e[2 * r].y) + __uint_as_float(e[2 * r + 1].y) + 80.f * ((m0 - t) * (m0 - t) + (m1 - t) * (m1 - t));
      q += __shfl_xor_sync(~0u, q, 1); q += __shfl_xor_sync(~0u, q, 2);
      mean[r] = t; rs[r] = rsqrtf(q * (1.f / DM) + 1e-5f);
    }
    ABT(0, 7);
    uint32_t w[2][5][2];
#pragma unroll
    for (int i = 0; i < 20; i++) w[i & 1][i >> 2][i >> 1 & 1] = pack2((d[2 * i] - mean[i & 1]) * rs[i & 1], (d[2 * i + 1] - mean[i & 1]) * rs[i & 1]);
    ln_store(w, blk * 8 + warp, cg * 5, live);
  }
  ABT(!!p.out, 8);
  TRACE(2);
}

typedef CUresult (*EncodeFn)(CUtensorMap*, CUtensorMapDataType, cuuint32_t, void*, const cuuint64_t*, const cuuint64_t*,
                             const cuuint32_t*, const cuuint32_t*, CUtensorMapInterleave, CUtensorMapSwizzle,
                             CUtensorMapL2promotion, CUtensorMapFloatOOBfill);

void make_map(EncodeFn enc, CUtensorMap* m, const void* ptr, int cols, int rows, int nb) {
  const cuuint64_t dims[3] = {(cuuint64_t)(nb ? 64 : cols), (cuuint64_t)rows, (cuuint64_t)cols / 64};
  const cuuint64_t strides[2] = {(cuuint64_t)cols * 2, 128};
  const cuuint32_t box[3] = {64, 32, (cuuint32_t)nb}, es[3] = {1, 1, 1};
  enc(m, CU_TENSOR_MAP_DATA_TYPE_BFLOAT16, nb ? 3 : 2, const_cast<void*>(ptr), dims, strides, box, es, CU_TENSOR_MAP_INTERLEAVE_NONE,
      CU_TENSOR_MAP_SWIZZLE_128B, CU_TENSOR_MAP_L2_PROMOTION_L2_128B, CU_TENSOR_MAP_FLOAT_OOB_FILL_NONE);
}
template <class... KA, class... A>
void launch(void (*kern)(KA...), int grid, int block, int smem, int cluster, bool pdl, A... args) {
  cudaFuncSetAttribute(kern, cudaFuncAttributeMaxDynamicSharedMemorySize, smem);
  cudaLaunchConfig_t cfg = {};
  cfg.gridDim = dim3(grid); cfg.blockDim = dim3(block); cfg.dynamicSmemBytes = smem; cfg.stream = cudaStreamPerThread;
  cudaLaunchAttribute at[2];
  int n = 0;
  if (cluster > 1) { at[n].id = cudaLaunchAttributeClusterDimension; at[n].val.clusterDim.x = cluster; at[n].val.clusterDim.y = 1; at[n].val.clusterDim.z = 1; n++; }
  if (pdl) { at[n].id = cudaLaunchAttributeProgrammaticStreamSerialization; at[n].val.programmaticStreamSerializationAllowed = 1; n++; }
  cfg.attrs = at; cfg.numAttrs = n;
  cudaLaunchKernelEx(&cfg, kern, args...);
}
template <class T> void* sym(T& s) { void* p = nullptr; cudaGetSymbolAddress(&p, s); return p; }

}

#define MODE(b) 0
extern "C" void kernel_launch(void* const* d_in, const int* in_sizes, int n_in, void* d_out, int out_size) {
  const __nv_bfloat16* x = (const __nv_bfloat16*)d_in[0];
  void* fn = nullptr; cudaDriverEntryPointQueryResult qr;
  cudaGetDriverEntryPoint("cuTensorMapEncodeTiled", &fn, cudaEnableDefault, &qr);
  EncodeFn enc = (EncodeFn)fn;

  ChainParams ch = {};
  PostParams op = {};
  for (int i = 0; i < 3; i++) {
    const cuuint64_t dims[3] = {HD, 128, 5}, strides[2] = {HD * 2, HD * 256};
    const cuuint32_t box[3] = {64, 128, 5}, es[3] = {1, 1, 1};
    enc(i == 0 ? &ch.wq : i == 1 ? &ch.wk : &ch.wv, CU_TENSOR_MAP_DATA_TYPE_BFLOAT16, 3, d_in[2 + i], dims, strides, box, es, CU_TENSOR_MAP_INTERLEAVE_NONE,
        CU_TENSOR_MAP_SWIZZLE_128B, W_PROMO, CU_TENSOR_MAP_FLOAT_OOB_FILL_NONE);
  }
  {
    const cuuint64_t dims[3] = {DM, HD, 7}, strides[2] = {DM * 2, 64};
    const cuuint32_t box[3] = {32, 64, 7}, es[3] = {1, 1, 1};
    enc(&ch.wo, CU_TENSOR_MAP_DATA_TYPE_BFLOAT16, 3, d_in[5], dims, strides, box, es, CU_TENSOR_MAP_INTERLEAVE_NONE,
        CU_TENSOR_MAP_SWIZZLE_64B, CU_TENSOR_MAP_L2_PROMOTION_L2_128B, CU_TENSOR_MAP_FLOAT_OOB_FILL_NONE);
  }
  ch.mem0 = (const __nv_bfloat16*)d_in[1];
  ch.pool = (uint8_t*)(((uintptr_t)sym(g_pool) + 8191) & ~(uintptr_t)8191); ch.kv = (uint8_t*)sym(g_kv); ch.xc = (const uint32_t*)sym(g_xc); ch.sync = (uint32_t*)sym(g_sync);
  ch.d1 = 0; ch.d1b = 0; ch.d2 = 0; ch.d2b = 0;
  make_map(enc, &op.wq, d_in[2], HD, DM, 3);
  make_map(enc, &op.wo, d_in[5], DM, HD, 5); make_map(enc, &op.wo2, d_in[5], DM, HD, 0);
  make_map(enc, &op.wb, d_in[8], 1920, DM, 5); make_map(enc, &op.wb2, d_in[8], 1920, DM, 0);
  op.gap = 17; op.share = 20; op.look = 20; op.gap2 = 0; op.pol = 1; op.slow_n = 8; op.slow_gap = 23;

  const Weights wa = {{(const uint8_t*)d_in[3], (const uint8_t*)d_in[4], (const uint8_t*)d_in[2], (const uint8_t*)d_in[5]}}, none = {};
  launch(first_kernel, 132, 384, 128 * 1024, 1, false, x, (const uint4*)d_in[9], wa);
  for (int layer = 0; layer < (MODE(4) ? 1 : 2); layer++) {
    ch.layer = ch.d2b = op.layer = layer;
    launch(chain_kernel, 96, 256, CH_SMEM, 3, true, ch);
    launch(post_kernel, MODE(3) ? 36 : 132, 384, OP_SMEM, 1, !MODE(1), op);
    const AbParams ab = {layer == 0 ? wa : none, (uint32_t*)sym(g_bo) + layer * 128, layer == 0 ? nullptr : (uint32_t*)d_out};
    launch(attn_b_kernel, 128, AB_T + 32, AB_SMEM, 1, true, ab);
  }
}
```

```cpp
#include <cuda_runtime.h>
#include <cuda_bf16.h>
#include <cuda.h>
#include <stdint.h>

namespace {

constexpr int SEQ = 2048, DM = 640, HD = 6144, NSEG = 64;
constexpr int SPIN_LIMIT = 1 << 20;

__device__ __align__(128) uint2 g_x[SEQ * DM / 4];
__device__ __align__(128) uint32_t g_of[SEQ * DM / 2];
__device__ __align__(128) uint4 g_wb[DM * DM / 8];
__device__ __align__(16) float2 g_stat[16 * 8 * 128];
__device__ uint32_t g_bo[8 * 32];
__device__ __align__(128) uint4 g_q[SEQ * HD / 8];
__device__ __align__(128) uint32_t g_o[SEQ * HD / 2];
constexpr int KV_BYTES = 5120, KV_M = 4096, KV_V = NSEG * KV_BYTES;
__device__ __align__(128) uint8_t g_kv[96 * 2 * NSEG * KV_BYTES];
__device__ __align__(128) uint32_t g_xc[SEQ * DM / 2];
#define OP_B4 7
#define OP_B8 10
#define OP_B16 16
#define QA_END 11
__host__ __device__ constexpr int op_split(int b) { return b < OP_B4 ? 2 : b < OP_B8 ? 4 : b < OP_B16 ? 8 : 16; }
#define AB_PF 3
#define AB_PF0 0
#define AB_PFD 5000
#define W_PROMO CU_TENSOR_MAP_L2_PROMOTION_L2_128B
#define OP_EARLY 1
#define ATT_LOOK 1
#define PR_FIN 1
#define PR_ATT 0
#define PR_OP 2
#define PRE_MAX PS
#define BQ_RUSH 16
#define OEF 0
#define BQ_HOLD 6
#define WEF 1
#define FK_REP 4
#define FK_PF 1
#define BQ_160 10
#define BQ_80 16
#define OP_160 14
__host__ __device__ constexpr int op_width(int b) { return b < OP_160 ? 320 : 160; }
__host__ __device__ constexpr int bq_width(int b) { return b < BQ_160 ? 320 : b < BQ_80 ? 160 : 80; }
__device__ __align__(128) uint2 g_part[16 * 16 * 16 * 40 * 32];
__device__ __align__(128) uint32_t g_xn[SEQ * DM / 2];
constexpr int SY_Q = 128, SY_T = 160, SY_QC = 192, SY_N = 193;
__device__ __align__(16) uint32_t g_sync[SY_N];
constexpr int NSLOT = 92;
__device__ uint32_t g_pool[(NSLOT + 2) * 2048];
__device__ int g_smpart[256], g_orient[NSLOT];
__device__ uint32_t g_smclk[256], g_smuse[256];
__device__ uint32_t g_bqkv[3 * 32 * 256 * 96];

#define ABT(L, i)
#define PST(i)
#define MODE_D(b) 0
#define DELAY(d)
#define XT(i)
#define MISS(k, n)
#define PRO(i)
#define TRACE(w)
#define ITEM(code, w)
#define TR(i, v)
#define TM(i)
#define TM1(i)
#define TMD(i, dep)
#define TMV(i, at, v)

__device__ __forceinline__ uint32_t gtime() { uint32_t c; asm volatile("mov.u32 %0, %%globaltimer_lo;" : "=r"(c) :: "memory"); return c; }
__device__ __forceinline__ uint32_t clk32() { uint32_t c; asm volatile("mov.u32 %0, %%clock;" : "=r"(c) :: "memory"); return c; }
__device__ __forceinline__ uint32_t s2u(const void* p) { return (uint32_t)__cvta_generic_to_shared(p); }
__device__ __forceinline__ uint32_t pack2(float a, float b) {
  uint32_t r; asm("cvt.rn.bf16x2.f32 %0, %1, %2;" : "=r"(r) : "f"(b), "f"(a)); return r; }
__device__ __forceinline__ float bf_lo(uint32_t w) { return __uint_as_float(w << 16); }
__device__ __forceinline__ float bf_hi(uint32_t w) { return __uint_as_float(w & 0xffff0000u); }
__device__ __forceinline__ uint2 pack4(float4 v) { return make_uint2(pack2(v.x, v.y), pack2(v.z, v.w)); }
__device__ __forceinline__ float4 unpack4(uint2 w) { return make_float4(bf_lo(w.x), bf_hi(w.x), bf_lo(w.y), bf_hi(w.y)); }
__device__ __forceinline__ float ex2(float x) { float y; asm("ex2.approx.ftz.f32 %0, %1;" : "=f"(y) : "f"(x)); return y; }

__device__ __forceinline__ void mbar_init(uint32_t bar, uint32_t n) {
  asm volatile("mbarrier.init.shared::cta.b64 [%0], %1;" :: "r"(bar), "r"(n) : "memory"); }
__device__ __forceinline__ void mbar_expect(uint32_t bar, uint32_t bytes) {
  asm volatile("mbarrier.arrive.expect_tx.shared::cta.b64 _, [%0], %1;" :: "r"(bar), "r"(bytes) : "memory"); }
__device__ __forceinline__ void mbar_arrive(uint32_t bar) {
  asm volatile("mbarrier.arrive.shared::cta.b64 _, [%0];" :: "r"(bar) : "memory"); }
__device__ __forceinline__ void mbar_wait(uint32_t bar, uint32_t ph) {
  asm volatile("{.reg .pred p; .reg .u32 n; mov.u32 n, 0;\n"
               "W: mbarrier.try_wait.parity.shared::cta.b64 p, [%0], %1; @p bra D;\n"
               "add.u32 n, n, 1; setp.gt.u32 p, n, %2; @p trap; bra W;\n"
               "D: }" :: "r"(bar), "r"(ph), "n"(SPIN_LIMIT) : "memory");
}
__device__ __forceinline__ void mbar_wait_cluster(uint32_t bar, uint32_t ph) {
  asm volatile("{.reg .pred p; .reg .u32 n; mov.u32 n, 0;\n"
               "W: mbarrier.try_wait.parity.acquire.cluster.shared::cta.b64 p, [%0], %1; @p bra D;\n"
               "add.u32 n, n, 1; setp.gt.u32 p, n, %2; @p trap; bra W;\n"
               "D: }" :: "r"(bar), "r"(ph), "n"(SPIN_LIMIT) : "memory");
}
__device__ __forceinline__ void spin_guard(int& n) {
  asm volatile("{.reg .pred p; add.s32 %0, %0, 1; setp.gt.s32 p, %0, %1; @p trap;}" : "+r"(n) : "n"(SPIN_LIMIT));
}
__device__ __forceinline__ void pdl_wait() { asm volatile("griddepcontrol.wait;" ::: "memory"); TRACE(1); }
__device__ __forceinline__ void pdl_launch() { asm volatile("griddepcontrol.launch_dependents;" ::: "memory"); }
__device__ __forceinline__ uint32_t ld_acquire(const uint32_t* p) { uint32_t v; asm volatile("ld.acquire.gpu.global.u32 %0, [%1];" : "=r"(v) : "l"(p) : "memory"); return v; }
__device__ __forceinline__ void red_release(uint32_t* p, uint32_t v) { asm volatile("red.release.gpu.global.add.u32 [%0], %1;" :: "l"(p), "r"(v) : "memory"); }
__device__ __forceinline__ void red_relaxed(uint32_t* p, uint32_t v) { asm volatile("red.relaxed.gpu.global.add.u32 [%0], %1;" :: "l"(p), "r"(v) : "memory"); }
__device__ __forceinline__ void fence_async_global() { asm volatile("fence.proxy.async.global;" ::: "memory"); }
__device__ __forceinline__ void fence_async() { asm volatile("fence.proxy.async.shared::cta;" ::: "memory"); }
__device__ __forceinline__ void bar_sync(int id, int n) { asm volatile("bar.sync %0, %1;" :: "r"(id), "r"(n) : "memory"); }
__device__ __forceinline__ void bar_arrive(int id, int n) { asm volatile("bar.arrive %0, %1;" :: "r"(id), "r"(n) : "memory"); }
__device__ __forceinline__ void tma_load(uint32_t dst, const CUtensorMap* m, int c0, int c1, uint32_t bar) {
  asm volatile("cp.async.bulk.tensor.2d.shared::cluster.global.mbarrier::complete_tx::bytes [%0], [%1, {%3, %4}], [%2];"
               :: "r"(dst), "l"(m), "r"(bar), "r"(c0), "r"(c1) : "memory"); }
template <bool STREAM = false>
__device__ __forceinline__ void tma_load3(uint32_t dst, const CUtensorMap* m, int c0, int c1, uint32_t bar) {
  if (STREAM)
    asm volatile("{.reg .b64 pol; createpolicy.fractional.L2::evict_first.b64 pol, 1.0;\n"
                 "cp.async.bulk.tensor.3d.shared::cluster.global.mbarrier::complete_tx::bytes.L2::cache_hint [%0], [%1, {%3, %4, 0}], [%2], pol;}"
                 :: "r"(dst), "l"(m), "r"(bar), "r"(c0), "r"(c1) : "memory");
  else
  asm volatile("cp.async.bulk.tensor.3d.shared::cluster.global.mbarrier::complete_tx::bytes [%0], [%1, {%3, %4, 0}], [%2];"
               :: "r"(dst), "l"(m), "r"(bar), "r"(c0), "r"(c1) : "memory"); }
__device__ __forceinline__ void tma_load3z(uint32_t dst, const CUtensorMap* m, int c1, int c2, uint32_t bar) {
  asm volatile("cp.async.bulk.tensor.3d.shared::cluster.global.mbarrier::complete_tx::bytes [%0], [%1, {0, %3, %4}], [%2];"
               :: "r"(dst), "l"(m), "r"(bar), "r"(c1), "r"(c2) : "memory"); }
__device__ __forceinline__ void tma_store(const CUtensorMap* m, uint32_t src, int c0, int c1) {
  asm volatile("cp.async.bulk.tensor.2d.global.shared::cta.bulk_group [%0, {%2, %3}], [%1];"
               :: "l"(m), "r"(src), "r"(c0), "r"(c1) : "memory"); }
__device__ __forceinline__ void tma_store_stream(const CUtensorMap* m, uint32_t src, int c0, int c1) {
  asm volatile("{.reg .b64 pol; createpolicy.fractional.L2::evict_first.b64 pol, 1.0;\n"
               "cp.async.bulk.tensor.2d.global.shared::cta.bulk_group.L2::cache_hint [%0, {%2, %3}], [%1], pol;}"
               :: "l"(m), "r"(src), "r"(c0), "r"(c1) : "memory"); }
__device__ __forceinline__ void bulk_load(uint32_t dst, const void* src, uint32_t bytes, uint32_t bar) {
  asm volatile("cp.async.bulk.shared::cluster.global.mbarrier::complete_tx::bytes [%0], [%1], %2, [%3];"
               :: "r"(dst), "l"(src), "r"(bytes), "r"(bar) : "memory"); }
__device__ __forceinline__ void bulk_load_last(uint32_t dst, const void* src, uint32_t bytes, uint32_t bar) {
  asm volatile("{.reg .b64 pol; createpolicy.fractional.L2::evict_first.b64 pol, 1.0;\n"
               "cp.async.bulk.shared::cluster.global.mbarrier::complete_tx::bytes.L2::cache_hint [%0], [%1], %2, [%3], pol;}"
               :: "r"(dst), "l"(src), "r"(bytes), "r"(bar) : "memory"); }
__device__ __forceinline__ void tma_load_last(uint32_t dst, const CUtensorMap* m, int c0, int c1, uint32_t bar) {
  asm volatile("{.reg .b64 pol; createpolicy.fractional.L2::evict_first.b64 pol, 1.0;\n"
               "cp.async.bulk.tensor.2d.shared::cluster.global.mbarrier::complete_tx::bytes.L2::cache_hint [%0], [%1, {%3, %4}], [%2], pol;}"
               :: "r"(dst), "l"(m), "r"(bar), "r"(c0), "r"(c1) : "memory"); }
__device__ __forceinline__ void bulk_send(uint32_t dst, uint32_t src, uint32_t bytes, uint32_t bar) {
  asm volatile("cp.async.bulk.shared::cluster.shared::cta.mbarrier::complete_tx::bytes [%0], [%1], %2, [%3];"
               :: "r"(dst), "r"(src), "r"(bytes), "r"(bar) : "memory"); }
__device__ __forceinline__ void bulk_store(void* dst, uint32_t src, uint32_t bytes) {
  asm volatile("cp.async.bulk.global.shared::cta.bulk_group [%0], [%1], %2;" :: "l"(dst), "r"(src), "r"(bytes) : "memory"); }
__device__ __forceinline__ void bulk_commit() { asm volatile("cp.async.bulk.commit_group;" ::: "memory"); }
template <int N> __device__ __forceinline__ void bulk_wait_read() { asm volatile("cp.async.bulk.wait_group.read %0;" :: "n"(N) : "memory"); }
template <int N> __device__ __forceinline__ void bulk_wait() { asm volatile("cp.async.bulk.wait_group %0;" :: "n"(N) : "memory"); }

__device__ __forceinline__ uint64_t mkdesc(uint32_t addr, uint32_t lbo, uint32_t sbo, uint32_t sw) {
  return (uint64_t)((addr & 0x3FFFF) >> 4) | ((uint64_t)(lbo >> 4) << 16) | ((uint64_t)(sbo >> 4) << 32) | ((uint64_t)sw << 62); }
__device__ __forceinline__ void wg_fence() { asm volatile("wgmma.fence.sync.aligned;" ::: "memory"); }
__device__ __forceinline__ void wg_commit() { asm volatile("wgmma.commit_group.sync.aligned;" ::: "memory"); }
template <int N> __device__ __forceinline__ void wg_wait() { asm volatile("wgmma.wait_group.sync.aligned %0;" :: "n"(N) : "memory"); }
template <int N> __device__ __forceinline__ void reg_fence(float* d) {
#pragma unroll
  for (int i = 0; i < N; i++) asm volatile("" : "+f"(d[i]) :: "memory");
}

__device__ __forceinline__ void mma16(float* d, uint32_t a0, uint32_t a1, uint32_t a2, uint32_t a3, uint32_t b0, uint32_t b1) {
  asm volatile("mma.sync.aligned.m16n8k16.row.col.f32.bf16.bf16.f32 {%0,%1,%2,%3},{%4,%5,%6,%7},{%8,%9},{%0,%1,%2,%3};"
               : "+f"(d[0]), "+f"(d[1]), "+f"(d[2]), "+f"(d[3]) : "r"(a0), "r"(a1), "r"(a2), "r"(a3), "r"(b0), "r"(b1)); }
__device__ __forceinline__ void mma8(float* d, uint32_t a0, uint32_t a1, uint32_t b0) {
  asm volatile("mma.sync.aligned.m16n8k8.row.col.f32.bf16.bf16.f32 {%0,%1,%2,%3},{%4,%5},{%6},{%0,%1,%2,%3};"
               : "+f"(d[0]), "+f"(d[1]), "+f"(d[2]), "+f"(d[3]) : "r"(a0), "r"(a1), "r"(b0)); }
__device__ __forceinline__ void ldsm4(uint32_t* r, uint32_t a) {
  asm volatile("ldmatrix.sync.aligned.m8n8.x4.shared.b16 {%0,%1,%2,%3},[%4];" : "=r"(r[0]), "=r"(r[1]), "=r"(r[2]), "=r"(r[3]) : "r"(a) : "memory"); }
__device__ __forceinline__ void ldsm4t(uint32_t* r, uint32_t a) {
  asm volatile("ldmatrix.sync.aligned.m8n8.x4.trans.shared.b16 {%0,%1,%2,%3},[%4];" : "=r"(r[0]), "=r"(r[1]), "=r"(r[2]), "=r"(r[3]) : "r"(a) : "memory"); }
__device__ __forceinline__ void ldsm2(uint32_t* r, uint32_t a) {
  asm volatile("ldmatrix.sync.aligned.m8n8.x2.shared.b16 {%0,%1},[%2];" : "=r"(r[0]), "=r"(r[1]) : "r"(a) : "memory"); }
__device__ __forceinline__ void stsm4(uint32_t a, uint32_t r0, uint32_t r1, uint32_t r2, uint32_t r3) {
  asm volatile("stmatrix.sync.aligned.m8n8.x4.shared.b16 [%0], {%1,%2,%3,%4};" :: "r"(a), "r"(r0), "r"(r1), "r"(r2), "r"(r3) : "memory"); }
__device__ __forceinline__ void stsm2t(uint32_t a, uint32_t r0, uint32_t r1) {
  asm volatile("stmatrix.sync.aligned.m8n8.x2.trans.shared.b16 [%0], {%1,%2};" :: "r"(a), "r"(r0), "r"(r1) : "memory"); }
__device__ __forceinline__ void stsm4t(uint32_t a, uint32_t r0, uint32_t r1, uint32_t r2, uint32_t r3) {
  asm volatile("stmatrix.sync.aligned.m8n8.x4.trans.shared.b16 [%0], {%1,%2,%3,%4};" :: "r"(a), "r"(r0), "r"(r1), "r"(r2), "r"(r3) : "memory"); }
__device__ __forceinline__ void st_async128(uint32_t a, uint4 v, uint32_t bar) {
  asm volatile("st.async.shared::cluster.mbarrier::complete_tx::bytes.v4.b32 [%0], {%1,%2,%3,%4}, [%5];" :: "r"(a), "r"(v.x), "r"(v.y), "r"(v.z), "r"(v.w), "r"(bar) : "memory"); }
__device__ __forceinline__ void sts32(uint32_t a, uint32_t v) { asm volatile("st.shared.b32 [%0], %1;" :: "r"(a), "r"(v) : "memory"); }
__device__ __forceinline__ void sts64f(uint32_t a, float x, float y) { asm volatile("st.shared.v2.f32 [%0], {%1,%2};" :: "r"(a), "f"(x), "f"(y) : "memory"); }
__device__ __forceinline__ void sts128(uint32_t a, uint4 v) {
  asm volatile("st.shared.v4.b32 [%0], {%1,%2,%3,%4};" :: "r"(a), "r"(v.x), "r"(v.y), "r"(v.z), "r"(v.w) : "memory"); }
__device__ __forceinline__ void sts128f(uint32_t a, float x, float y, float z, float w) {
  asm volatile("st.shared.v4.f32 [%0], {%1,%2,%3,%4};" :: "r"(a), "f"(x), "f"(y), "f"(z), "f"(w) : "memory"); }
__device__ __forceinline__ float lds32f(uint32_t a) { float v; asm volatile("ld.shared.f32 %0, [%1];" : "=f"(v) : "r"(a) : "memory"); return v; }
__device__ __forceinline__ float2 lds64f(uint32_t a) { float2 v; asm volatile("ld.shared.v2.f32 {%0,%1}, [%2];" : "=f"(v.x), "=f"(v.y) : "r"(a) : "memory"); return v; }
__device__ __forceinline__ float4 lds128f(uint32_t a) {
  float4 v; asm volatile("ld.shared.v4.f32 {%0,%1,%2,%3}, [%4];" : "=f"(v.x), "=f"(v.y), "=f"(v.z), "=f"(v.w) : "r"(a) : "memory"); return v; }
__device__ __forceinline__ uint4 lds128(uint32_t a) {
  uint4 v; asm volatile("ld.shared.v4.b32 {%0,%1,%2,%3}, [%4];" : "=r"(v.x), "=r"(v.y), "=r"(v.z), "=r"(v.w) : "r"(a) : "memory"); return v; }
__device__ __forceinline__ uint4 ldg_strong128(const void* p) {
  uint4 v; asm volatile("ld.relaxed.gpu.global.v4.u32 {%0,%1,%2,%3}, [%4];" : "=r"(v.x), "=r"(v.y), "=r"(v.z), "=r"(v.w) : "l"(p) : "memory"); return v; }
__device__ __forceinline__ void stg_strong32(void* p, uint32_t v) { asm volatile("st.relaxed.gpu.global.u32 [%0], %1;" :: "l"(p), "r"(v) : "memory"); }
__device__ __forceinline__ void stg_strong16(void* p, uint32_t v) { asm volatile("st.relaxed.gpu.global.u16 [%0], %1;" :: "l"(p), "h"((uint16_t)v) : "memory"); }
__device__ __forceinline__ void stg_strong128(void* p, uint4 v) {
  asm volatile("st.relaxed.gpu.global.v4.u32 [%0], {%1,%2,%3,%4};" :: "l"(p), "r"(v.x), "r"(v.y), "r"(v.z), "r"(v.w) : "memory"); }
__device__ __forceinline__ uint32_t mapa(uint32_t a, uint32_t r) {
  uint32_t o; asm("mapa.shared::cluster.u32 %0, %1, %2;" : "=r"(o) : "r"(a), "r"(r)); return o; }
__device__ __forceinline__ void st_async2f(uint32_t a, float x, float y, uint32_t bar) {
  asm volatile("st.async.shared::cluster.mbarrier::complete_tx::bytes.v2.f32 [%0], {%1,%2}, [%3];" :: "r"(a), "f"(x), "f"(y), "r"(bar) : "memory"); }
__device__ __forceinline__ void st_async32(uint32_t a, uint32_t x, uint32_t bar) {
  asm volatile("st.async.shared::cluster.mbarrier::complete_tx::bytes.b32 [%0], %1, [%2];" :: "r"(a), "r"(x), "r"(bar) : "memory"); }
__device__ __forceinline__ uint32_t lds32(uint32_t a) { uint32_t v; asm volatile("ld.shared.b32 %0, [%1];" : "=r"(v) : "r"(a) : "memory"); return v; }
__device__ __forceinline__ void st_async64(uint32_t a, uint32_t x, uint32_t y, uint32_t bar) {
  asm volatile("st.async.shared::cluster.mbarrier::complete_tx::bytes.v2.b32 [%0], {%1,%2}, [%3];" :: "r"(a), "r"(x), "r"(y), "r"(bar) : "memory"); }
__device__ __forceinline__ uint2 lds64(uint32_t a) { uint2 v; asm volatile("ld.shared.v2.b32 {%0,%1}, [%2];" : "=r"(v.x), "=r"(v.y) : "r"(a) : "memory"); return v; }
__device__ __forceinline__ void sts64(uint32_t a, uint32_t x, uint32_t y) { asm volatile("st.shared.v2.b32 [%0], {%1,%2};" :: "r"(a), "r"(x), "r"(y) : "memory"); }
__device__ __forceinline__ uint32_t ldg_strong32(const void* p) { uint32_t v; asm volatile("ld.relaxed.gpu.global.u32 %0, [%1];" : "=r"(v) : "l"(p) : "memory"); return v; }
__device__ __forceinline__ uint32_t transpose8(uint32_t x) { uint32_t r; asm volatile("movmatrix.sync.aligned.m8n8.trans.b16 %0, %1;" : "=r"(r) : "r"(x)); return r; }
__device__ __forceinline__ uint32_t hadd2(uint32_t a, uint32_t b) { uint32_t r; asm("add.rn.bf16x2 %0, %1, %2;" : "=r"(r) : "r"(a), "r"(b)); return r; }
__device__ __forceinline__ uint32_t min4(uint4 v) { return min(__vimin3_u32(v.x, v.y, v.z), v.w); }

__device__ __forceinline__ void wg_ss192_01(float* d, uint64_t da, uint64_t db, int sd) {
  asm volatile("{.reg .pred p; setp.ne.b32 p, %98, 0;\n"
    "wgmma.mma_async.sync.aligned.m64n192k16.f32.bf16.bf16 {%0,%1,%2,%3,%4,%5,%6,%7,%8,%9,%10,%11,%12,%13,%14,%15,%16,%17,%18,%19,%20,%21,%22,%23,%24,%25,%26,%27,%28,%29,%30,%31,%32,%33,%34,%35,%36,%37,%38,%39,%40,%41,%42,%43,%44,%45,%46,%47,%48,%49,%50,%51,%52,%53,%54,%55,%56,%57,%58,%59,%60,%61,%62,%63,%64,%65,%66,%67,%68,%69,%70,%71,%72,%73,%74,%75,%76,%77,%78,%79,%80,%81,%82,%83,%84,%85,%86,%87,%88,%89,%90,%91,%92,%93,%94,%95}, %96, %97, p, 1, 1, 0, 1;}"
    : "+f"(d[0]),"+f"(d[1]),"+f"(d[2]),"+f"(d[3]),"+f"(d[4]),"+f"(d[5]),"+f"(d[6]),"+f"(d[7]),"+f"(d[8]),"+f"(d[9]),"+f"(d[10]),"+f"(d[11]),"+f"(d[12]),"+f"(d[13]),"+f"(d[14]),"+f"(d[15]),"+f"(d[16]),"+f"(d[17]),"+f"(d[18]),"+f"(d[19]),"+f"(d[20]),"+f"(d[21]),"+f"(d[22]),"+f"(d[23]),"+f"(d[24]),"+f"(d[25]),"+f"(d[26]),"+f"(d[27]),"+f"(d[28]),"+f"(d[29]),"+f"(d[30]),"+f"(d[31]),"+f"(d[32]),"+f"(d[33]),"+f"(d[34]),"+f"(d[35]),"+f"(d[36]),"+f"(d[37]),"+f"(d[38]),"+f"(d[39]),"+f"(d[40]),"+f"(d[41]),"+f"(d[42]),"+f"(d[43]),"+f"(d[44]),"+f"(d[45]),"+f"(d[46]),"+f"(d[47]),"+f"(d[48]),"+f"(d[49]),"+f"(d[50]),"+f"(d[51]),"+f"(d[52]),"+f"(d[53]),"+f"(d[54]),"+f"(d[55]),"+f"(d[56]),"+f"(d[57]),"+f"(d[58]),"+f"(d[59]),"+f"(d[60]),"+f"(d[61]),"+f"(d[62]),"+f"(d[63]),"+f"(d[64]),"+f"(d[65]),"+f"(d[66]),"+f"(d[67]),"+f"(d[68]),"+f"(d[69]),"+f"(d[70]),"+f"(d[71]),"+f"(d[72]),"+f"(d[73]),"+f"(d[74]),"+f"(d[75]),"+f"(d[76]),"+f"(d[77]),"+f"(d[78]),"+f"(d[79]),"+f"(d[80]),"+f"(d[81]),"+f"(d[82]),"+f"(d[83]),"+f"(d[84]),"+f"(d[85]),"+f"(d[86]),"+f"(d[87]),"+f"(d[88]),"+f"(d[89]),"+f"(d[90]),"+f"(d[91]),"+f"(d[92]),"+f"(d[93]),"+f"(d[94]),"+f"(d[95])
    : "l"(da), "l"(db), "r"(sd));
}
__device__ __forceinline__ void wg_ss128_01(float* d, uint64_t da, uint64_t db, int sd) {
  asm volatile("{.reg .pred p; setp.ne.b32 p, %66, 0;\n"
    "wgmma.mma_async.sync.aligned.m64n128k16.f32.bf16.bf16 {%0,%1,%2,%3,%4,%5,%6,%7,%8,%9,%10,%11,%12,%13,%14,%15,%16,%17,%18,%19,%20,%21,%22,%23,%24,%25,%26,%27,%28,%29,%30,%31,%32,%33,%34,%35,%36,%37,%38,%39,%40,%41,%42,%43,%44,%45,%46,%47,%48,%49,%50,%51,%52,%53,%54,%55,%56,%57,%58,%59,%60,%61,%62,%63}, %64, %65, p, 1, 1, 0, 1;}"
    : "+f"(d[0]),"+f"(d[1]),"+f"(d[2]),"+f"(d[3]),"+f"(d[4]),"+f"(d[5]),"+f"(d[6]),"+f"(d[7]),"+f"(d[8]),"+f"(d[9]),"+f"(d[10]),"+f"(d[11]),"+f"(d[12]),"+f"(d[13]),"+f"(d[14]),"+f"(d[15]),"+f"(d[16]),"+f"(d[17]),"+f"(d[18]),"+f"(d[19]),"+f"(d[20]),"+f"(d[21]),"+f"(d[22]),"+f"(d[23]),"+f"(d[24]),"+f"(d[25]),"+f"(d[26]),"+f"(d[27]),"+f"(d[28]),"+f"(d[29]),"+f"(d[30]),"+f"(d[31]),"+f"(d[32]),"+f"(d[33]),"+f"(d[34]),"+f"(d[35]),"+f"(d[36]),"+f"(d[37]),"+f"(d[38]),"+f"(d[39]),"+f"(d[40]),"+f"(d[41]),"+f"(d[42]),"+f"(d[43]),"+f"(d[44]),"+f"(d[45]),"+f"(d[46]),"+f"(d[47]),"+f"(d[48]),"+f"(d[49]),"+f"(d[50]),"+f"(d[51]),"+f"(d[52]),"+f"(d[53]),"+f"(d[54]),"+f"(d[55]),"+f"(d[56]),"+f"(d[57]),"+f"(d[58]),"+f"(d[59]),"+f"(d[60]),"+f"(d[61]),"+f"(d[62]),"+f"(d[63])
    : "l"(da), "l"(db), "r"(sd));
}
__device__ __forceinline__ void wg_ss160_01(float* d, uint64_t da, uint64_t db, int sd) {
  asm volatile("{.reg .pred p; setp.ne.b32 p, %82, 0;\n"
    "wgmma.mma_async.sync.aligned.m64n160k16.f32.bf16.bf16 {%0,%1,%2,%3,%4,%5,%6,%7,%8,%9,%10,%11,%12,%13,%14,%15,%16,%17,%18,%19,%20,%21,%22,%23,%24,%25,%26,%27,%28,%29,%30,%31,%32,%33,%34,%35,%36,%37,%38,%39,%40,%41,%42,%43,%44,%45,%46,%47,%48,%49,%50,%51,%52,%53,%54,%55,%56,%57,%58,%59,%60,%61,%62,%63,%64,%65,%66,%67,%68,%69,%70,%71,%72,%73,%74,%75,%76,%77,%78,%79}, %80, %81, p, 1, 1, 0, 1;}"
    : "+f"(d[0]),"+f"(d[1]),"+f"(d[2]),"+f"(d[3]),"+f"(d[4]),"+f"(d[5]),"+f"(d[6]),"+f"(d[7]),"+f"(d[8]),"+f"(d[9]),"+f"(d[10]),"+f"(d[11]),"+f"(d[12]),"+f"(d[13]),"+f"(d[14]),"+f"(d[15]),"+f"(d[16]),"+f"(d[17]),"+f"(d[18]),"+f"(d[19]),"+f"(d[20]),"+f"(d[21]),"+f"(d[22]),"+f"(d[23]),"+f"(d[24]),"+f"(d[25]),"+f"(d[26]),"+f"(d[27]),"+f"(d[28]),"+f"(d[29]),"+f"(d[30]),"+f"(d[31]),"+f"(d[32]),"+f"(d[33]),"+f"(d[34]),"+f"(d[35]),"+f"(d[36]),"+f"(d[37]),"+f"(d[38]),"+f"(d[39]),"+f"(d[40]),"+f"(d[41]),"+f"(d[42]),"+f"(d[43]),"+f"(d[44]),"+f"(d[45]),"+f"(d[46]),"+f"(d[47]),"+f"(d[48]),"+f"(d[49]),"+f"(d[50]),"+f"(d[51]),"+f"(d[52]),"+f"(d[53]),"+f"(d[54]),"+f"(d[55]),"+f"(d[56]),"+f"(d[57]),"+f"(d[58]),"+f"(d[59]),"+f"(d[60]),"+f"(d[61]),"+f"(d[62]),"+f"(d[63]),"+f"(d[64]),"+f"(d[65]),"+f"(d[66]),"+f"(d[67]),"+f"(d[68]),"+f"(d[69]),"+f"(d[70]),"+f"(d[71]),"+f"(d[72]),"+f"(d[73]),"+f"(d[74]),"+f"(d[75]),"+f"(d[76]),"+f"(d[77]),"+f"(d[78]),"+f"(d[79])
    : "l"(da), "l"(db), "r"(sd));
}
__device__ __forceinline__ void wg_ss80_01(float* d, uint64_t da, uint64_t db, int sd) {
  asm volatile("{.reg .pred p; setp.ne.b32 p, %42, 0;\n"
    "wgmma.mma_async.sync.aligned.m64n80k16.f32.bf16.bf16 {%0,%1,%2,%3,%4,%5,%6,%7,%8,%9,%10,%11,%12,%13,%14,%15,%16,%17,%18,%19,%20,%21,%22,%23,%24,%25,%26,%27,%28,%29,%30,%31,%32,%33,%34,%35,%36,%37,%38,%39}, %40, %41, p, 1, 1, 0, 1;}"
    : "+f"(d[0]),"+f"(d[1]),"+f"(d[2]),"+f"(d[3]),"+f"(d[4]),"+f"(d[5]),"+f"(d[6]),"+f"(d[7]),"+f"(d[8]),"+f"(d[9]),"+f"(d[10]),"+f"(d[11]),"+f"(d[12]),"+f"(d[13]),"+f"(d[14]),"+f"(d[15]),"+f"(d[16]),"+f"(d[17]),"+f"(d[18]),"+f"(d[19]),"+f"(d[20]),"+f"(d[21]),"+f"(d[22]),"+f"(d[23]),"+f"(d[24]),"+f"(d[25]),"+f"(d[26]),"+f"(d[27]),"+f"(d[28]),"+f"(d[29]),"+f"(d[30]),"+f"(d[31]),"+f"(d[32]),"+f"(d[33]),"+f"(d[34]),"+f"(d[35]),"+f"(d[36]),"+f"(d[37]),"+f"(d[38]),"+f"(d[39])
    : "l"(da), "l"(db), "r"(sd));
}
__device__ __forceinline__ void wg_rs32_00(float* d, uint32_t a0, uint32_t a1, uint32_t a2, uint32_t a3, uint64_t db, int sd) {
  asm volatile("{.reg .pred p; setp.ne.b32 p, %21, 0;\n"
    "wgmma.mma_async.sync.aligned.m64n32k16.f32.bf16.bf16 {%0,%1,%2,%3,%4,%5,%6,%7,%8,%9,%10,%11,%12,%13,%14,%15}, {%16,%17,%18,%19}, %20, p, 1, 1, 0;}"
    : "+f"(d[0]),"+f"(d[1]),"+f"(d[2]),"+f"(d[3]),"+f"(d[4]),"+f"(d[5]),"+f"(d[6]),"+f"(d[7]),"+f"(d[8]),"+f"(d[9]),"+f"(d[10]),"+f"(d[11]),"+f"(d[12]),"+f"(d[13]),"+f"(d[14]),"+f"(d[15])
    : "r"(a0), "r"(a1), "r"(a2), "r"(a3), "l"(db), "r"(sd));
}
__device__ __forceinline__ void wg_rs64_00(float* d, uint32_t a0, uint32_t a1, uint32_t a2, uint32_t a3, uint64_t db, int sd) {
  asm volatile("{.reg .pred p; setp.ne.b32 p, %37, 0;\n"
    "wgmma.mma_async.sync.aligned.m64n64k16.f32.bf16.bf16 {%0,%1,%2,%3,%4,%5,%6,%7,%8,%9,%10,%11,%12,%13,%14,%15,%16,%17,%18,%19,%20,%21,%22,%23,%24,%25,%26,%27,%28,%29,%30,%31}, {%32,%33,%34,%35}, %36, p, 1, 1, 0;}"
    : "+f"(d[0]),"+f"(d[1]),"+f"(d[2]),"+f"(d[3]),"+f"(d[4]),"+f"(d[5]),"+f"(d[6]),"+f"(d[7]),"+f"(d[8]),"+f"(d[9]),"+f"(d[10]),"+f"(d[11]),"+f"(d[12]),"+f"(d[13]),"+f"(d[14]),"+f"(d[15]),"+f"(d[16]),"+f"(d[17]),"+f"(d[18]),"+f"(d[19]),"+f"(d[20]),"+f"(d[21]),"+f"(d[22]),"+f"(d[23]),"+f"(d[24]),"+f"(d[25]),"+f"(d[26]),"+f"(d[27]),"+f"(d[28]),"+f"(d[29]),"+f"(d[30]),"+f"(d[31])
    : "r"(a0), "r"(a1), "r"(a2), "r"(a3), "l"(db), "r"(sd));
}
__device__ __forceinline__ void wg_rs24_01(float* d, uint32_t a0, uint32_t a1, uint32_t a2, uint32_t a3, uint64_t db, int sd) {
  asm volatile("{.reg .pred p; setp.ne.b32 p, %17, 0;\n"
    "wgmma.mma_async.sync.aligned.m64n24k16.f32.bf16.bf16 {%0,%1,%2,%3,%4,%5,%6,%7,%8,%9,%10,%11}, {%12,%13,%14,%15}, %16, p, 1, 1, 1;}"
    : "+f"(d[0]),"+f"(d[1]),"+f"(d[2]),"+f"(d[3]),"+f"(d[4]),"+f"(d[5]),"+f"(d[6]),"+f"(d[7]),"+f"(d[8]),"+f"(d[9]),"+f"(d[10]),"+f"(d[11])
    : "r"(a0), "r"(a1), "r"(a2), "r"(a3), "l"(db), "r"(sd));
}

#define AB_POLY 0xae
__device__ __forceinline__ constexpr bool poly_group(int group) { return (AB_POLY >> (group & 7)) & 1; }

template <int V> struct Int { static constexpr int value = V; };

template <int NG>
__device__ __forceinline__ void ln_stats(const float4 (&v)[NG][5], uint32_t scratch, float (&mean)[NG], float (&rs)[NG]) {
  const int warp = threadIdx.x >> 5, lane = threadIdx.x & 31;
#pragma unroll
  for (int r = 0; r < NG; r++) {
    float s = 0.f, q = 0.f;
#pragma unroll
    for (int i = 0; i < 5; i++) s += (v[r][i].x + v[r][i].y) + (v[r][i].z + v[r][i].w);
    s += __shfl_xor_sync(~0u, s, 1); s += __shfl_xor_sync(~0u, s, 2);
    s *= 1.f / 80;
#pragma unroll
    for (int i = 0; i < 5; i++) {
      const float x = v[r][i].x - s, y = v[r][i].y - s, z = v[r][i].z - s, w = v[r][i].w - s;
      q += (x * x + y * y) + (z * z + w * w);
    }
    q += __shfl_xor_sync(~0u, q, 1); q += __shfl_xor_sync(~0u, q, 2);
    mean[r] = s; rs[r] = q;
  }
  bar_sync(1, 256);
  if ((lane & 3) == 0) {
#pragma unroll
    for (int r = 0; r < NG; r++) sts64f(scratch + r * 512 + lane * 16 + warp * 8, mean[r], rs[r]);
  }
  bar_sync(1, 256);
#pragma unroll
  for (int r = 0; r < NG; r++) {
    const float4 e = lds128f(scratch + r * 512 + lane * 16);
    float t = e.x + e.z;
    t += __shfl_xor_sync(~0u, t, 1); t += __shfl_xor_sync(~0u, t, 2);
    t *= 0.125f;
    float q = e.y + e.w + 80.f * ((e.x - t) * (e.x - t) + (e.z - t) * (e.z - t));
    q += __shfl_xor_sync(~0u, q, 1); q += __shfl_xor_sync(~0u, q, 2);
    mean[r] = t; rs[r] = rsqrtf(q * (1.f / DM) + 1e-5f);
  }
}

__device__ __forceinline__ void ln_store(const uint32_t (&w)[2][5][2], int tile, int u0, bool live = true) {
  const int lane = threadIdx.x & 31;
  uint32_t* xc = g_xc + ((tile >> 1) * 40 + u0) * 256 + (tile & 1) * 64 + lane;
#pragma unroll
  for (int i = 0; i < 20; i++) if (live) xc[(i >> 1) * 128 + (i & 1) * 32] = w[i & 1][i >> 2][i >> 1 & 1];
#pragma unroll
  for (int i = 0; i < 5; i++) {
    const int u = u0 + i;
    uint32_t* xn = g_xn + (((tile >> 3) * 20 + (u >> 1)) * 16 + (tile & 1) * 8 + (tile & 6)) * 128 + (u & 1) * 64 + lane;
#pragma unroll
    for (int r = 0; r < 2; r++) if (live) { xn[r * 128] = w[r][i][0]; xn[r * 128 + 32] = w[r][i][1]; }
  }
}
__device__ __forceinline__ void wait_count(const uint32_t* c, uint32_t n) {
  int spin = 0;
  while ((ld_acquire(c) & 0xffff) < n) { __nanosleep(32); spin_guard(spin); }
}

__device__ __forceinline__ uint8_t* pool_at(uint32_t off) {
  return reinterpret_cast<uint8_t*>((reinterpret_cast<uintptr_t>(g_pool) + 8191) & ~(uintptr_t)8191) + off; }
struct Weights { const uint8_t* w[4]; };
__device__ __forceinline__ void prefetch_weights(const Weights& p, int i) {
  if (blockIdx.x < 128) asm volatile("cp.async.bulk.prefetch.L2.global [%0], 61440;" :: "l"(p.w[i] + (size_t)blockIdx.x * 61440) : "memory");
}
__global__ void __launch_bounds__(384) first_kernel(const __nv_bfloat16* __restrict__ xin, const uint4* __restrict__ wb, const __grid_constant__ Weights wa) {
  __shared__ __align__(16) float scratch[256];
  __shared__ uint32_t lat[4];
  const int warp = threadIdx.x >> 5, lane = threadIdx.x & 31, cta = blockIdx.x;
  TRACE(0);
  pdl_launch();
  if (warp >= 8) {
    if (warp < 10 || cta < NSLOT) {
      uint32_t* q = reinterpret_cast<uint32_t*>(pool_at((warp < 10 ? NSLOT : cta) * 8192 + (warp & 1) * 4096)) + (warp < 10 ? (cta & 127) * 8 : 0);
      if (lane < 8) stg_strong32(q + lane, 0u);
      uint32_t best = ~0u;
      if (lane == 0) {
        for (int r = 0; r < FK_REP; r++) {
          uint32_t t0, t1, v;
          asm volatile("mov.u32 %0, %%clock;" : "=r"(t0) :: "memory");
          asm volatile("atom.relaxed.gpu.global.exch.b32 %0, [%1], 0;" : "=r"(v) : "l"(q) : "memory");
          asm volatile("{.reg .u32 t; add.u32 t, %1, 1; mov.u32 %0, %%clock; sub.u32 %0, %0, %1;}" : "=r"(t1) : "r"(__shfl_sync(1u, v, 0)) : "memory");
          best = min(best, t1 - t0);
        }
        lat[warp - 8] = best;
      }
    }
    __syncwarp();
    bar_sync(2, cta < 128 ? 384 : 128);
    if (threadIdx.x == 288) for (int i = 0; i < FK_PF; i++) prefetch_weights(wa, i);
    if (threadIdx.x == 256) {
      const int part = lat[0] < lat[1] ? 0 : 1;
      uint32_t smid; asm("mov.u32 %0, %%smid;" : "=r"(smid));
      g_smpart[smid & 255] = part;
      g_smclk[smid & 255] = clk32() - gtime() * 2;
      g_smuse[smid & 255] = 0;
      if (cta < NSLOT) g_orient[cta] = lat[2] < lat[3] ? part : 1 - part;
    }
  } else if (cta < 128) {
    float4 v[2][5];
#pragma unroll
    for (int r = 0; r < 2; r++)
#pragma unroll
      for (int i = 0; i < 5; i++) {
        const uint32_t* src = reinterpret_cast<const uint32_t*>(xin) + (cta * 16 + r * 8 + (lane >> 2)) * (DM / 2) + warp * 40 + i * 8 + (lane & 3);
        const uint32_t a = src[0], b = src[4];
        v[r][i] = make_float4(bf_lo(a), bf_hi(a), bf_lo(b), bf_hi(b));
      }
    uint4 w8[2];
#pragma unroll
    for (int i = 0; i < 2; i++) w8[i] = wb[cta * 400 + min(i * 256 + threadIdx.x, 399)];
    float mean[2], rs[2];
    ln_stats<2>(v, s2u(scratch), mean, rs);
    bar_sync(2, 384);
    ABT(2, 2);
    if (threadIdx.x < 128) g_stat[cta * 128 + threadIdx.x] = make_float2(0.f, 0.f);
#pragma unroll
    for (int i = 0; i < 10; i++) g_x[((cta * 2 + i / 5) * 40 + warp * 5 + i % 5) * 32 + lane] = pack4(v[i / 5][i % 5]);
    uint32_t w[2][5][2];
#pragma unroll
    for (int i = 0; i < 10; i++) {
      const float4 t = v[i / 5][i % 5];
      const float m = mean[i / 5], q = rs[i / 5];
      w[i / 5][i % 5][0] = pack2((t.x - m) * q, (t.y - m) * q); w[i / 5][i % 5][1] = pack2((t.z - m) * q, (t.w - m) * q);
    }
    ln_store(w, cta, warp * 5);
    ABT(2, 3);
#pragma unroll
    for (int i = 0; i < 2; i++) {
      const int e = cta * 400 + min(i * 256 + threadIdx.x, 399), k = e / 80, n = e - k * 80, cg = n / 10;
      g_wb[((cg * 80 + (k >> 3)) * 10 + n - cg * 10) * 8 + (k & 7)] = w8[i];
    }
  } else if (cta == 128) {
    g_bo[threadIdx.x] = 0;
  }
  TRACE(2);
}

struct ChainParams {
  CUtensorMap wq, wk, wv, wo;
  const __nv_bfloat16* mem0;
  uint8_t *pool, *kv;
  const uint32_t* xc;
  uint32_t* sync;
  int layer;
  int d0, d3, d1, d1b, d2, d2b, mode;
};
constexpr int CH_WQ = 0, CH_WO = 81920, CH_X = CH_WO + 86016, CH_M = CH_X + 20480, CH_KT = CH_X + 40960, CH_VT = CH_KT + 4096,
              CH_PS = CH_VT + 4096, CH_QK = CH_PS + 4096, CH_VP = CH_QK + 4096, CH_SX = CH_VP + 1024, CH_O = CH_SX + 2304, CH_ID = CH_O + 3072,
              CH_BAR = CH_ID + 512;
constexpr int CH_SMEM = CH_BAR + 256;
constexpr int CH_BASE = 1024;
#define CH_VK0 8
#define CH_VK1 20
#define CH_L0 4
#define CH_LR 4
#define NOX 0
#define CH_XA 1
#define CH_XB 4
#define CH_W1 5
#define CH_W2 17
#define CH_W3 26
#define CH_R2 8
#define CH_VA 16
#define CH_EX 2
#define CH_KD 0
#define CH_RP 1
#define CH_KF 10
#define CH_LO 0
#define CH_LR1 4
#define CH_KP 0
#define CH_KM 0
#define CH_SP 1
#define CH_VC 2
#define CH_W0 5
#define CH_WA 3
#define CH_P1 4
#define CH_KW 3
#define CH_RB 0
#define CH_RC 8
#define CH_D0 200
#define CH_D1 400
#define CH_D2 270
#define CH_R1 4
#define CH_TW 12
__device__ __forceinline__ uint32_t opaque(uint32_t x) { return __shfl_sync(~0u, x, threadIdx.x & 31); }
__device__ __forceinline__ uint32_t nz(uint32_t x) { uint32_t r; asm("max.u32 %0, %1, 1;" : "=r"(r) : "r"(x)); return r; }
__device__ __forceinline__ uint32_t pack_tag(float lo, float hi, uint32_t tag, uint32_t mask) {
  uint32_t r;
  asm("lop3.b32 %0, %1, %2, %3, 0xD8;" : "=r"(r) : "r"(pack2(lo, hi)), "r"(tag), "r"(mask));
  return r;
}
__device__ __forceinline__ uint32_t differ(uint32_t a, uint32_t b, uint32_t t) { uint32_t r; asm("lop3.b32 %0, %1, %2, %3, 0x7E;" : "=r"(r) : "r"(a), "r"(b), "r"(t)); return r; }
__device__ __forceinline__ void mbar_wait_hot(uint32_t bar, uint32_t ph) {
  uint32_t ok;
  asm volatile("{.reg .pred p; mbarrier.try_wait.parity.shared::cta.b64 p, [%1], %2; selp.u32 %0, 1, 0, p;}" : "=r"(ok) : "r"(bar), "r"(ph) : "memory");
  if (__builtin_expect(!ok, 0)) mbar_wait(bar, ph);
}
__device__ __forceinline__ bool elect() {
  uint32_t r; asm volatile("{.reg .pred p; elect.sync _|p, 0xffffffff; selp.u32 %0, 1, 0, p;}" : "=r"(r)); return r; }
__device__ __forceinline__ uint32_t or3(uint32_t a, uint32_t b, uint32_t c) { uint32_t r; asm("lop3.b32 %0, %1, %2, %3, 0xFE;" : "=r"(r) : "r"(a), "r"(b), "r"(c)); return r; }
__device__ __forceinline__ void pin() { pdl_launch(); }
__device__ __forceinline__ void mma16h(float* d, uint32_t a0, uint32_t a2, uint32_t b0, uint32_t b1) {
  asm volatile("{.reg .b32 u, v; mma.sync.aligned.m16n8k16.row.col.f32.bf16.bf16.f32 {%0,%1,%2,%3},{%4,u,%5,v},{%6,%7},{%0,%1,%2,%3};}"
               : "+f"(d[0]), "+f"(d[1]), "+f"(d[2]), "+f"(d[3]) : "r"(a0), "r"(a2), "r"(b0), "r"(b1)); }
__device__ __forceinline__ void mma8h(float* d, uint32_t a0, uint32_t b0) {
  asm volatile("{.reg .b32 u; mma.sync.aligned.m16n8k8.row.col.f32.bf16.bf16.f32 {%0,%1,%2,%3},{%4,u},{%5},{%0,%1,%2,%3};}"
               : "+f"(d[0]), "+f"(d[1]), "+f"(d[2]), "+f"(d[3]) : "r"(a0), "r"(b0)); }
__device__ __forceinline__ uint32_t absmax2(uint32_t a, uint32_t b) { uint32_t r; asm("max.xorsign.abs.bf16x2 %0, %1, %2;" : "=r"(r) : "r"(a), "r"(b)); return r; }
__device__ __forceinline__ void until(uint32_t t) { while ((int)(clk32() - t) < 0) {} }
__device__ __forceinline__ uint4 pack8(const float* d) { return make_uint4(pack2(d[0], d[1]), pack2(d[2], d[3]), pack2(d[4], d[5]), pack2(d[6], d[7])); }
__device__ __forceinline__ void add8(float* d, uint4 v) {
  d[0] += bf_lo(v.x); d[1] += bf_hi(v.x); d[2] += bf_lo(v.y); d[3] += bf_hi(v.y);
  d[4] += bf_lo(v.z); d[5] += bf_hi(v.z); d[6] += bf_lo(v.w); d[7] += bf_hi(v.w);
}

template <int WG>
__device__ __forceinline__ void chain_body(const ChainParams& p, const uint32_t wq, const uint32_t (&ak)[80], const uint32_t (&av)[80]) {
  const int tid = threadIdx.x & 127, t4 = __shfl_sync(~0u, tid >> 5, 0), lane = tid & 31;
  const int cta = blockIdx.x, h = cta / 3, j = cta - 3 * h;
  const uint32_t sb = mapa(CH_BASE, j);
  const uint32_t bWo = sb + CH_BAR, bWq = bWo + 8, bX = bWo + 16, bXA = bWo + 24, bXB = bWo + 32, bO = bWo + 40, bG = bWo + 48, bH = bWo + 96;
  uint32_t tw[4 * CH_TW];
  auto refill = [&]() {
#pragma unroll
    for (int k = 0; k < CH_TW; k++) ldsm4t(&tw[4 * k], wq + k * 2048);
  };
  const uint32_t wo = opaque((sb + CH_WO + (WG == 0 ? (t4 + (j == 2)) * 4096 : (j == 2 ? 0 : 24576) + t4 * 1024) + ((lane & 7) + (lane >> 4) * 8) * 64 +
                              ((((lane >> 3) & 1) ^ ((lane >> 1) & 3)) << 4)) ^ (WG == 1 && j == 2 ? 32 : 0));
  const uint32_t wo2 = opaque((wo ^ ((t4 & 1) * 32)) + (4 + (t4 >> 1) - t4) * 4096);
  const uint32_t l16 = opaque(sb + lane * 16);
  const uint32_t l8 = opaque(sb + t4 * 256 + lane * 8);
  const uint32_t lw = opaque(sb + t4 * 1024 + lane * 16);
  const uint32_t qs = opaque(sb + CH_QK + WG * 2048 + t4 * 512 + lane * 16);
  const uint32_t qa = opaque(sb + CH_QK + (lane >> 4) * 2048 + (lane & 15) * 16 + (WG == 0 ? t4 * 512 + 256 : t4 == 3 ? 1024 : 0));
  const uint32_t ka = opaque(t4 < 2 ? sb + CH_KT + t4 * 512 + lane * 16
                                    : sb + CH_QK + 256 + (t4 - 2) * 1024 + ((lane >> 3) & 1) * 2048 + (lane >> 4) * 128 + (lane & 7) * 16);
  const uint32_t l4 = opaque(sb + t4 * 256 + lane * 4);
  uint32_t pdst[1], pages = 0;
  auto line0 = [&](int i) { return 28 * j + (i < 4 ? 4 * t4 + i : 12 + 2 * t4 + i); };
  const uint32_t plane = opaque((lane >> 4) * 2048 + h * 64 + (lane & 15) * 4);
  if (WG == 0) {
    pages = __ballot_sync(~0u, lds32(sb + CH_O + line0(min(lane, 5)) * 4) & 4096);
  } else {
    pages = __ballot_sync(~0u, lds32(sb + CH_O + (80 + min(lane, 11)) * 4) & 4096);
    pdst[0] = opaque(lds32(sb + CH_O + (j == 0 ? 24 + t4 : 50 + 2 * j + (t4 & 1)) * 4) + plane);
  }
  const uint32_t role = lds32(sb + CH_O + NSLOT * 4), rsrc = lds32(sb + CH_O + role * 4), rdst = (80 + role / 20) * 8192 + role % 20 * 128;
  const uint32_t r1 = mapa(CH_BASE, j == 2 ? 0 : j + 1) - sb, r2 = mapa(CH_BASE, j == 0 ? 2 : j - 1) - sb;
  uint32_t tag = opaque(1);
  auto pool = [&](uint32_t off) { return p.pool + ((tag & 0xfffe) + off); };
  auto after = [&](uint32_t x) { return x & tag & 0xfffe; };
  auto kv = [&](int s, uint32_t a) { return p.kv + (a + ((cta * 2 * NSEG + s) * KV_BYTES - sb)); };
  auto pass = [&](float (&d)[16], const uint32_t (&a)[80], auto k0, auto k1) {
    const uint64_t db = mkdesc(CH_BASE + CH_X + WG * 20480, 512, 128, 0);
#pragma unroll
    for (int k = k0.value; k < k1.value; k++) wg_rs32_00(d, a[4 * k], a[4 * k + 1], a[4 * k + 2], a[4 * k + 3], db + k * 64, k);
    wg_commit();
  };
  auto dump = [&](float (&d)[16], uint32_t a) {
    reg_fence<16>(d);
    sts128(a, pack8(d)); sts128(a + 512, pack8(d + 8));
  };
  uint32_t pph = 0;
  auto tokens0 = [&](int s, auto k0) {
    float dk[16], dv[16];
    bar_sync(9, 256);
    wg_fence();
    pass(dk, ak, Int<0>(), Int<4>());
    const uint4 a0 = lds128(lw + CH_KT), a1 = lds128(lw + CH_KT + 512);
    pin();
    pass(dk, ak, Int<4>(), Int<20>());
    pass(dv, av, Int<0>(), Int<CH_VA>());
    pin();
    wg_wait<1>();
    reg_fence<16>(dk);
    add8(dk, a0); add8(dk + 8, a1);
    const uint4 w0 = pack8(dk), w1 = pack8(dk + 8);
    const uint4 b0 = lds128(lw + CH_VT), b1 = lds128(lw + CH_VT + 512);
    stsm4t(lw + CH_KT, w0.x, w0.z, w0.y, w0.w); stsm4t(lw + CH_KT + 512, w1.x, w1.z, w1.y, w1.w);
    if (CH_KP == 2) bar_arrive(7, 160);
    TM1(6);
    pin();
    if (CH_VA < 20) pass(dv, av, Int<CH_VA>(), Int<20>());
    pin();
#pragma unroll
    for (int k = k0.value; k < CH_TW; k++) ldsm4t(&tw[4 * k], wq + k * 2048);
    TM1(9);
    if (k0.value < CH_TW && t4 >= 2) { mbar_wait_hot(bH + t4 * 16 - 24 + (pph & 1) * 8, pph >> 1 & 1); pph++; }
    __syncwarp();
    wg_wait<0>();
    reg_fence<16>(dv);
    add8(dv, b0); add8(dv + 8, b1);
#pragma unroll
    for (int e = 0; e < 2; e++) { const uint4 v = pack8(dv + 8 * e); sts128(lw + CH_VT + e * 512, make_uint4(v.x, v.z, v.y, v.w)); }
  };
  auto publish_k = [&](int s) {
    if (t4 == CH_KW && elect()) { fence_async(); bulk_store(p.kv + (size_t)(cta * 2 * NSEG + s) * KV_BYTES, sb + CH_KT, 4096); bulk_commit(); }
    __syncwarp();
  };
  auto load_x = [&](int s, int k0, int n, uint32_t bar) {
    if (!NOX && elect()) { mbar_expect(bar, n * 1024); bulk_load(sb + CH_X + k0 * 1024, p.xc + (s + 1) * 10240 + k0 * 256, n * 1024, bar); }
  };
  if (WG == 0) {
    mbar_wait(bXB, 0);
    tokens0(0, Int<CH_TW>());
    if (CH_XB == 5) { bar_sync(7, 128); load_x(0, 5 * t4, 5, bXB); }
  } else {
    const uint32_t* m0 = reinterpret_cast<const uint32_t*>(p.mem0) + (lane >> 2) * 320 + t4 * 80 + (lane & 3);
    uint32_t a[20];
#pragma unroll
    for (int i = 0; i < 20; i++) a[i] = m0[4 * i];
    pin();
    float dk[16], dv[16];
    mbar_wait(bXA, 0);
    wg_fence();
    pass(dk, ak, Int<0>(), Int<20>());
    pass(dv, av, Int<0>(), Int<20>());
    wg_wait<0>();
    dump(dk, lw + CH_KT);
    dump(dv, lw + CH_VT);
    bar_sync(9, 256);
    if (CH_KP == 2 && t4 == CH_KW) { bar_sync(7, 160); publish_k(0); }
#pragma unroll
    for (int i = 0; i < 20; i++) sts32(sb + CH_M + (t4 * 20 + i) * 128 + lane * 4, nz(transpose8(a[i])));
    __syncwarp();
    if (elect()) mbar_arrive(bG + t4 * 8);
  }
  PRO(8);
  mbar_wait(bWq, 0);
  refill();
  PRO(9);
  mbar_wait(bWo, 0);
  asm volatile("barrier.cluster.wait.aligned;" ::: "memory");
  PRO(10);
  constexpr int VK = WG == 0 ? CH_VK0 : CH_VK1;
  uint32_t gph = 0;
  int st = 0;
  const uint32_t ca = opaque(sb + CH_M + t4 * 2560 + lane * 32 + (lane >> 2) * 4);
  auto project = [&](int s, uint32_t (&b)[40], float (&dv)[16], uint32_t (&kf)[16]) {
    float dq[4] = {}, dk[4] = {};
    uint32_t w[80];
#pragma unroll
    for (int i = 0; i < 4 * CH_TW; i++) w[i] = tw[i];
    constexpr int LR = WG == 1 ? CH_LR1 : CH_LR;
    auto load = [&](int n) {
      int c = 0;
#pragma unroll
      for (int i = 0; i < 10; i++) {
        if (i == CH_KF) {
#pragma unroll
          for (int q = 0; q < 4; q++)
            if (WG == 1 && c++ == n) ldsm4(&kf[4 * q], ka + q * 1024);
        }
        if (c++ == n) ldsm4t(&b[4 * i], l16 + CH_M + WG * 5120 + i * 512);
#pragma unroll
        for (int k = 2 * i; k < 2 * i + 2; k++)
          if (k >= CH_TW && c++ == n) ldsm4t(&w[4 * k], wq + k * 2048);
      }
#pragma unroll
      for (int i = 0; i < 4; i++)
        if (WG == 1 && CH_KF >= 10 && c++ == n) ldsm4(&kf[4 * i], ka + i * 1024);
    };
    if (WG == 1) {
      for (int n = 0;;) {
        mbar_wait(bG + t4 * 8, gph);
        TR(5, (clk32() & ~3u) | min(n, 3));
        gph ^= 1;
        if (__builtin_expect(!__any_sync(~0u, __vimin3_u32(lds32(ca), lds32(ca + 1024), lds32(ca + 1536)) == 0), 1)) break;
        if (elect()) {
          const int q = (st == 0 ? 8 : st * 4 - 4) + t4;
          mbar_expect(bG + t4 * 8, 2560);
          bulk_load(sb + CH_M + t4 * 2560, p.pool + ((80 + q) * 8192 + (pages >> q & 1) * 4096), 2560, bG + t4 * 8);
        }
        spin_guard(n);
      }
    }
    bar_sync(6, 256);
#pragma unroll
    for (int i = 0; i < CH_L0; i++) load(i);
    if (WG == 0 && CH_XB == 4) load_x(min(s, NSEG - 2), 5 * t4, 5, bXB);
    TM(0);
    TM1(11);
    if (WG == 1) TR(6, clk32());
#pragma unroll
    for (int k = 0; k < 20; k += 2) {
      if (k > 0) {
#pragma unroll
        for (int n = (k == 18 ? 40 : CH_L0 + k * LR / 4) - 1; n >= CH_L0 + (k - 2) * LR / 4; n--) { load(n); if (CH_LO) __syncwarp(); }
      }
      if (WG == 0 && CH_XB >= 10 && k == CH_XB - 10 && s + 1 < NSEG) load_x(s, 5 * t4, 5, bXB);
      pin();
#pragma unroll
      for (int kk = k; kk < k + 2; kk++) {
        mma16(dk, ak[4 * kk], ak[4 * kk + 1], ak[4 * kk + 2], ak[4 * kk + 3], b[2 * kk], b[2 * kk + 1]);
        mma16(dq, w[4 * kk], w[4 * kk + 1], w[4 * kk + 2], w[4 * kk + 3], b[2 * kk], b[2 * kk + 1]);
        if (kk < VK) mma16(dv, av[4 * kk], av[4 * kk + 1], av[4 * kk + 2], av[4 * kk + 3], b[2 * kk], b[2 * kk + 1]);
      }
    }
    const float k2 = 0.07216878364870322f * 1.44269504089f;
    stsm4t(qs, pack2(dq[0] * k2, dq[1] * k2), pack2(dq[2] * k2, dq[3] * k2), pack2(dk[0], dk[1]), pack2(dk[2], dk[3]));
    TM(1);
  };
  static_assert(CH_VK1 == 20 && CH_KP == 0 && true, "last step");
  constexpr int VC = VK == 20 ? 1 : CH_VC;
  auto finish_v = [&](const uint32_t (&b)[40], float (&dv)[16]) {
#pragma unroll
    for (int kk = VK; kk < 20; kk++) mma16(dv + 4 * ((kk - VK) % VC), av[4 * kk], av[4 * kk + 1], av[4 * kk + 2], av[4 * kk + 3], b[2 * kk], b[2 * kk + 1]);
  };
  auto sum_v = [&](float (&dv)[16]) {
#pragma unroll
    for (int i = 4; i < 4 * VC; i++) dv[i & 3] += dv[i];
  };
  auto publish_km = [&](int s) {
    uint32_t a[4];
    ldsm4(a, qa);
    *reinterpret_cast<uint2*>(kv(s, l8) + KV_M) = make_uint2(hadd2(a[0], a[2]), hadd2(a[1], a[3]));
  };
  auto memory_v = [&](uint2 x, const float (&dv)[16]) {
    return make_uint2(pack2(dv[0] + bf_lo(x.x), dv[1] + bf_hi(x.x)), pack2(dv[2] + bf_lo(x.y), dv[3] + bf_hi(x.y)));
  };
  auto publish_v = [&](int s, const uint4 (&v)[2], uint2 vm) {
#pragma unroll
    for (int e = 0; e < 2; e++) reinterpret_cast<uint4*>(kv(s, lw) + KV_V)[e * 32] = v[e];
    *reinterpret_cast<uint2*>(kv(s, l8) + KV_V + KV_M) = vm;
  };
#pragma unroll 1
  for (int s = 0;; s++) {
    float dv[16] = {};
    uint32_t b[40], kf[16];
    project(s, b, dv, kf);
    if (WG == 0) {
      bar_sync(1, 256);
      if (CH_XA == 0 && s + 1 < NSEG) load_x(s, 20 + 5 * t4, 5, bXA);
      if (CH_XB == 0 && s + 1 < NSEG) load_x(s, 5 * t4, 5, bXB);
      pin();
      uint32_t w[144];
      auto wload = [&](int i) { ldsm4t(&w[4 * i], (i % 3 == 0 ? wo : i % 3 == 1 ? wo ^ 32 : wo2) + i / 12 * 28672 + i / 3 % 4 * 1024); };
#pragma unroll
      for (int kk = VK; kk < 20; kk++) {
        mma16(dv + 4 * ((kk - VK) % VC), av[4 * kk], av[4 * kk + 1], av[4 * kk + 2], av[4 * kk + 3], b[2 * kk], b[2 * kk + 1]);
        if (kk == VK + CH_WA && CH_W0) {
          pin();
#pragma unroll
          for (int i = 0; i < CH_W0; i++) wload(i);
          pin();
        }
      }
      sum_v(dv);
      sts64(l8 + CH_VP, pack2(dv[0], dv[1]), pack2(dv[2], dv[3]));
      if (s == NSEG - 1) {
        bar_arrive(10, 256);
        if (CH_XB == 4) mbar_wait(bXB, 0);
        publish_k(s);
        publish_km(s);
        bulk_wait<0>();
        fence_async_global();
        bar_sync(2, 256);
        if (tid == 0) red_release(p.sync + 15 * 8 + 4, 1);
        break;
      }
      bar_arrive(4, 256);
      if (CH_XA == 1) load_x(s, 20 + 5 * t4, 5, bXA);
      if (CH_XB == 1) load_x(s, 5 * t4, 5, bXB);
      TM(3);
      if (CH_KP == 0) publish_k(s);
#pragma unroll
      for (int i = CH_W0; i < CH_W1; i++) wload(i);
      bar_sync(10, 256);
      uint32_t km[4];
      ldsm4(km, qa);
      pin();
#pragma unroll
      for (int i = CH_W1; i < CH_W2; i++) wload(i);
      pin();
      const uint2 kms = make_uint2(hadd2(km[0], km[2]), hadd2(km[1], km[3]));
      if (CH_KM == 0) *reinterpret_cast<uint2*>(kv(s, l8) + KV_M) = kms;
      if (CH_KP == 0) bulk_wait_read<0>();
      if (CH_XA == 2) load_x(s, 20 + 5 * t4, 5, bXA);
      if (CH_XB == 2) load_x(s, 5 * t4, 5, bXB);
      bar_sync(2, 256);
      {
        float y[3][4] = {};
        uint32_t ob[24];
        ldsm4(&ob[0], l16 + CH_O + 1024); ldsm4(&ob[4], l16 + CH_O + 1536);
        TM(7);
        auto step = [&](int i) {
          const int k = i / 3;
          mma16(y[i % 3], w[4 * i], w[4 * i + 1], w[4 * i + 2], w[4 * i + 3], ob[2 * k], ob[2 * k + 1]);
        };
#pragma unroll
        for (int i = 0; i < 12; i++) {
          step(i);
          if (i >= 12 - (CH_W3 - CH_W2)) wload(CH_W3 - 12 + i);
          if (i % 3 == 2) pin();
        }
        if (CH_XB == 3) load_x(s, 5 * t4, 5, bXB);
        if (CH_KM == 1) *reinterpret_cast<uint2*>(kv(s, l8) + KV_M) = kms;
        pin();
        mbar_wait(bO, s & 1);
        TM(4);
        ldsm4(&ob[8], l16 + CH_O); ldsm4(&ob[12], l16 + CH_O + 512);
        pin();
        float2 inv;
        uint8_t* dst[6];
        uint32_t mask;
#pragma unroll
        for (int i = 12; i < 36; i++) {
          step(i);
          static_assert(CH_W3 == 26, "load order");
          if (i == 14) ldsm4(&ob[16], l16 + after(w[4 * CH_W3 - 1] | w[4 * CH_W3 - 5] | w[4 * CH_W3 - 9] | ob[8]) + CH_O + 2048);
          else if (i == 15) ldsm4(&ob[20], l16 + CH_O + 2560);
          else if (i < 24) wload(i < 14 ? 39 - i : i < 18 ? 45 - i : i < 21 ? 50 - i : 56 - i);
          if (i == 21) inv = lds64f((l8 & ~0xe0u) + CH_VP);
          if (i < 24) __syncwarp();
          if (i == 24) mask = ((l16 ^ tag) & 48) == 0;
          if (i >= 24 && i < 30) dst[i - 24] = pool(line0(i - 24) * 8192 + (pages >> (i - 24) & 1) * 4096) + plane;
          if (i % 3 == 2) pin();
        }
#pragma unroll
        for (int k = 0; k < CH_R1; k++) ldsm4t(&tw[4 * k], wq + k * 2048);
        pin();
#pragma unroll
        for (int i = 0; i < 6; i++) stg_strong32(dst[i], pack_tag(y[i >> 1][2 * (i & 1)] * inv.x, y[i >> 1][2 * (i & 1) + 1] * inv.y, tag, mask));
        TM(8);
        TR(0, clk32());
        bar_arrive(5, 256);
        pin();
      }
      const uint32_t t0 = clk32();
      auto refill2 = [&]() {
#pragma unroll
        for (int k = CH_R1; k < CH_R2; k++) ldsm4t(&tw[4 * k], wq + k * 2048);
      };
      if (CH_RP == 0) refill2();
      const uint32_t ln = (l16 ^ tag) >> 4 & 31;
      if (t4 >= 2) {
        const uint32_t bP = bH + t4 * 16 - 24, ps = CH_PS + (t4 & 1) * 4096;
        auto fetch = [&](uint32_t k) {
          if (elect()) { mbar_expect(bP + (k & 1) * 8, 2048); bulk_load(sb + ps + (k & 1) * 2048, p.pool + (rsrc + (t4 & 1) * 2048), 2048, bP + (k & 1) * 8); }
        };
        until(t0 + CH_D0);
        fetch(pph);
        if (CH_RP == 2) refill2();
        if (!NOX && CH_XB != 6) mbar_wait_hot(bXB, (s + 1) & 1);
        const uint32_t want = (tag & 1) * 0x10001, chk = opaque(ln < 4 ? 0x10001 : 0);
        uint4 sel;
        sel.x = opaque((ln >> 3) != (ln & 1) ? 0 : ln & 4 ? 0x3f800000u : 0x00003f80u);
        sel.z = opaque(sel.x); sel.y = opaque(ln); sel.w = opaque(ln + 1);
        uint8_t* mdst = p.pool + opaque(st * 32768 + rdst + (t4 & 1) * 64 + ln * 4);
        until(t0 + CH_D1);
        fetch(pph + 1);
        TM(5);
        if (CH_RP == 1) refill2();
        int n = 0;
        uint32_t u[16];
        float y[4][4];
        auto sum = [&]() {
#pragma unroll
          for (int i = 0; i < 16; i++) y[i >> 2][i & 3] = 0.f;
#pragma unroll
          for (int i = 0; i < 8; i++) mma16(y[i & 3], sel.x, sel.y, sel.z, sel.w, u[2 * i], u[2 * i + 1]);
        };
        auto check = [&](auto spec) {
          mbar_wait(bP + (pph & 1) * 8, pph >> 1 & 1);
          TM(14);
          TR(2, clk32());
#pragma unroll
          for (int i = 0; i < 4; i++) ldsm4t(&u[4 * i], l16 + (ps + (pph & 1) * 2048) + i * 512);
          pph++;
          if (spec.value) { pin(); sum(); }
          uint32_t bad = 0;
#pragma unroll
          for (int i = 0; i < 4; i++) bad = or3(bad, differ(u[4 * i], u[4 * i + 1], want), differ(u[4 * i + 2], u[4 * i + 3], want));
          return __any_sync(~0u, bad & chk);
        };
        if (CH_SP) {
          if (check(Int<0>())) {
            do { fetch(pph + 1); spin_guard(n); } while (check(Int<1>()));
          } else {
            sum();
          }
        } else {
          while (check(Int<0>())) { fetch(pph + 1); spin_guard(n); }
          sum();
        }
        TR(1, t0 + (n ? CH_D1 : CH_D0));
        TM(15);
        const uint32_t w = nz(pack2((y[0][0] + y[1][0]) + (y[2][0] + y[3][0]), (y[0][1] + y[1][1]) + (y[2][1] + y[3][1])));
        if (ln < 16) { stg_strong32(mdst, w); stg_strong32(mdst + 4096, w); }
        TMV(12, 32, n);
        TR(3, (clk32() & ~3u) | min(n, 3));
      } else {
        if (CH_XB == 6) { load_x(s, 10 * t4, 5, bXB); load_x(s, 10 * t4 + 5, 5, bXB); }
        if (CH_RP) refill2();
        if (!NOX) mbar_wait_hot(bXB, (s + 1) & 1);
        stg_strong32(p.pool + ((st == 2 ? 0 : st + 1) * 32768 + rdst + t4 * 4096) + ln * 4, 0u);
        if (t4 == 0 && cta < 40 && s + 4 < NSEG && elect())
          asm volatile("cp.async.bulk.prefetch.L2.global [%0], 1024;" :: "l"(p.xc + (s + 4) * 10240 + cta * 256) : "memory");
        if (t4 == 1 && (s & 3) == 0 && s > 0 && elect()) red_relaxed(p.sync + 2 * s - 4, 1);
        if (t4 == 1 && s == NSEG - 3 && cta == 95 && elect()) red_relaxed(p.sync + 2 * s + 2, 0x10000);
      }
      TM(10);
      bar_arrive(8, 256);
      tokens0(s + 1, Int<CH_R2>());
      if (CH_XB == 5 && s + 2 < NSEG) { bar_sync(7, 128); load_x(s + 1, 5 * t4, 5, bXB); }
      TM(2);
      TR(7, clk32());
    } else {
      if (s == NSEG - 1) {
        bar_arrive(1, 256);
        const uint4 v[2] = {lds128(lw + CH_VT), lds128(lw + CH_VT + 512)};
        bar_sync(10, 256);
        publish_v(s, v, memory_v(lds64(l8 + CH_VP), dv));
        bar_arrive(2, 256);
        break;
      }
      const uint32_t xo = l4 + (CH_SX - (t4 == 3 ? 128 : 0)), xr = CH_SX + 768 + min(t4, 2) * 256, x1 = l4 + (r1 + xr), x2 = l4 + (r2 + xr + 128);
      if (t4 < 2) {
        float ds[4][4] = {};
        uint32_t q[16];
        asm volatile("bar.sync 1, 256;" ::: "memory");
#pragma unroll
        for (int k = 0; k < 4; k++) ldsm4(&q[4 * k], qa + k * 512);
        pin();
        if (VK < 20) { finish_v(b, dv); pin(); }
#pragma unroll
        for (int k = 0; k < 4; k++) {
          mma16(ds[k & 1], kf[4 * k], kf[4 * k + 1], kf[4 * k + 2], kf[4 * k + 3], q[4 * k], q[4 * k + 1]);
          mma16(ds[2 + (k & 1)], kf[4 * k], kf[4 * k + 1], kf[4 * k + 2], kf[4 * k + 3], q[4 * k + 2], q[4 * k + 3]);
        }
        float t[4];
#pragma unroll
        for (int i = 0; i < 4; i++) t[i] = (ds[0][i] + ds[2][i]) + (ds[1][i] + ds[3][i]);
        const uint32_t w0 = pack2(t[0], t[1]), w1 = pack2(t[2], t[3]);
        st_async32(x1, w0, bX + r1); st_async32(x2, w0, bX + r2);
        st_async32(x1 + 256, w1, bX + r1); st_async32(x2 + 256, w1, bX + r2);
        sts32(xo, w0); sts32(xo + 128, w1);
      } else {
        float ds[4][4] = {};
        uint32_t q0[4], q1[4], a0[4], a1[4];
        asm volatile("bar.sync 1, 256; " ::: "memory");
        ldsm4(a0, ka); ldsm4(q0, qa); ldsm4(a1, ka + 512); ldsm4(q1, qa + 512);
        pin();
        if (VK < 20) { finish_v(b, dv); pin(); }
        mma16(ds[0], a0[0], a0[1], a0[2], a0[3], q0[0], q0[1]);
        mma16(ds[1], a0[0], a0[1], a0[2], a0[3], q0[2], q0[3]);
        mma16(ds[2], a1[0], a1[1], a1[2], a1[3], q1[0], q1[1]);
        mma16(ds[3], a1[0], a1[1], a1[2], a1[3], q1[2], q1[3]);
        float t[2];
#pragma unroll
        for (int i = 0; i < 2; i++)
          t[i] = ((ds[0][i] + ds[0][i + 2]) + (ds[1][i] + ds[1][i + 2])) + ((ds[2][i] + ds[2][i + 2]) + (ds[3][i] + ds[3][i + 2]));
        const uint32_t w0 = pack2(t[0], t[1]);
        st_async32(x1, w0, bX + r1);
        st_async32(x2, w0, bX + r2);
        sts32(xo, w0);
      }
      TM(3);
      const uint4 id = lds128(l16 + CH_ID);
      float sc[5][4] = {};
      uint4 v[2];
      sum_v(dv);
      bar_sync(4, 256);
      uint32_t r[12], wd[12], we[12] = {};
      ldsm4(&r[0], l16 + CH_SX); ldsm2(&r[4], l16 + CH_SX + 512);
      const uint2 vp = lds64(l8 + CH_VP);
      pin();
      v[0] = lds128(lw + CH_VT); v[1] = lds128(lw + CH_VT + 512);
#pragma unroll
      for (int u = 0; u < 3; u++) ldsm4t(&wd[4 * u], wo + u * 28672);
      pin();
#pragma unroll
      for (int q = 0; q < 4; q++) mma8(sc[q], id.x, id.y, r[q]);
      mma16(sc[4], id.x, id.y, id.z, id.w, r[4], r[5]);
      uint32_t big = absmax2(absmax2(absmax2(r[0], r[1]), absmax2(r[2], r[3])), absmax2(r[4], r[5]));
      const uint2 vm = memory_v(vp, dv);
      const uint32_t ones = 0x3f803f80u;
      pin();
      mbar_wait_hot(bX, s & 1);
      TM(4);
      ldsm4(&r[0], l16 + CH_SX + 768);
      __syncwarp();
      ldsm4(&r[8], l16 + CH_SX + 1792);
      __syncwarp();
      ldsm4(&r[4], l16 + CH_SX + 1280);
      bar_arrive(10, 256);
      pin();
      auto add = [&](int q) { mma16(sc[min(q, 4)], id.x, id.y, id.z, id.w, r[2 * q], r[2 * q + 1]); };
      add(0); add(1);
      pin();
      add(4);
      pin();
      uint32_t pr[5], o0, o1;
      bool redo = false;
      auto attend = [&](auto first) {
        float o[2][4] = {}, e[10];
        auto exps = [&](int q) {
#pragma unroll
          for (int i = 0; i < 2; i++) asm volatile("ex2.approx.ftz.f32 %0, %1;" : "=f"(e[2 * q + i]) : "f"(sc[q][i]));
        };
        auto merge = [&](int q) { big = absmax2(big, absmax2(absmax2(r[4 * q], r[4 * q + 1]), absmax2(r[4 * q + 2], r[4 * q + 3]))); };
        exps(0);
        if (first.value) { merge(0); pin(); add(2); add(5); add(3); }
        exps(1);
        if (first.value) { merge(2); pin(); }
        exps(2);
        if (first.value) { merge(1); pin(); }
        pr[0] = pack2(e[0], e[1]); pr[1] = pack2(e[2], e[3]);
        mma16h(o[0], pr[0], pr[1], v[0].x, v[0].y);
        mma16h(o[1], pr[0], pr[1], v[0].z, v[0].w);
        exps(4);
        if (first.value) pin();
        exps(3);
        if (first.value) redo = __any_sync(~0u, (absmax2(big, big << 16) & 0x7fff0000u) >= 0x41800000u);
        const bool drop = first.value && redo;
        const uint32_t a1 = l4 + (drop ? CH_PS : r1 + CH_O), a2 = l4 + (drop ? CH_PS : r2 + CH_O + 2048);
        const uint32_t b1 = drop ? bWq : bO + r1, b2 = drop ? bWq : bO + r2;
        pr[2] = pack2(e[4], e[5]); pr[3] = pack2(e[6], e[7]); pr[4] = pack2(e[8], e[9]);
        mma8h(o[0], pr[4], vm.x);
        mma8h(o[1], pr[4], vm.y);
        mma16h(o[0], pr[2], pr[3], v[1].x, v[1].y);
        mma16h(o[1], pr[2], pr[3], v[1].z, v[1].w);
        o0 = pack2(o[0][0], o[0][1]); o1 = pack2(o[1][0], o[1][1]);
        st_async32(a1, o0, b1); st_async32(a2, o0, b2);
        st_async32(a1 + 128, o1, b1); st_async32(a2 + 128, o1, b2);
        sts32(l4 + CH_O + 1024, o0); sts32(l4 + CH_O + 1152, o1);
        asm volatile("{.reg .pred p; setp.eq.u32 p, %0, 0; @p bar.arrive 2, 256;}" :: "r"((uint32_t)drop) : "memory");
      };
      attend(Int<1>());
      pin();
      if (__builtin_expect(redo, 0)) {
        float mx = -INFINITY;
#pragma unroll
        for (int q = 0; q < 5; q++) mx = fmaxf(mx, fmaxf(sc[q][0], sc[q][1]));
        mx = fmaxf(mx, __shfl_xor_sync(~0u, mx, 1));
        mx = fmaxf(mx, __shfl_xor_sync(~0u, mx, 2));
#pragma unroll
        for (int q = 0; q < 5; q++) { sc[q][0] -= mx; sc[q][1] -= mx; }
        attend(Int<0>());
      }
      TM(6);
      float l[4] = {}, l2[4] = {};
      mma16h(l, pr[0], pr[1], ones, ones);
      mma16h(l2, pr[2], pr[3], ones, ones);
      mma8h(l, pr[4], ones);
      l[0] += l2[0];
      float inv;
      asm("rcp.approx.ftz.f32 %0, %1;" : "=f"(inv) : "f"(l[0]));
      sts32((l8 & ~0xffu) + (lane & 28) + CH_VP, __float_as_uint(inv));
      __syncwarp();
      if (elect()) mbar_arrive(bO);
      {
        float z[2][4] = {}, y[2][4] = {};
        mma16(z[0], wd[0], wd[1], wd[2], wd[3], o0, o1);
        if (j == 0) {
#pragma unroll
          for (int u = 0; u < 3; u++) ldsm4t(&we[4 * u], (wo ^ 32) + u * 28672);
          mma16(y[0], we[0], we[1], we[2], we[3], o0, o1);
        }
        const float2 iv = lds64f((l8 & ~0xe0u) + CH_VP);
        uint8_t* dst = pool(pdst[0]);
        const uint32_t mask = ((l16 ^ tag) & 48) == 0;
        const uint32_t oa = qa + ((tag & 0xfffe) + CH_O - CH_QK + t4 * 256 - (t4 == 3 ? 1024 : 0));
        const uint32_t za = l16 + ((tag & 0xfffe) + (t4 >> 1) * 512 + (t4 & 1) * 8);
        pin();
        mbar_wait(bO, s & 1);
        uint32_t a[4];
        ldsm4(a, oa);
        mma16(z[0], wd[4], wd[5], wd[6], wd[7], a[0], a[1]);
        mma16(z[1], wd[8], wd[9], wd[10], wd[11], a[2], a[3]);
        if (j == 0) {
          mma16(y[0], we[4], we[5], we[6], we[7], a[0], a[1]);
          mma16(y[1], we[8], we[9], we[10], we[11], a[2], a[3]);
          sts128f(lw + CH_VT + 512, y[0][0] + y[1][0], y[0][1] + y[1][1], y[0][2] + y[1][2], y[0][3] + y[1][3]);
        }
        sts128f(lw + CH_VT, z[0][0] + z[1][0], z[0][1] + z[1][1], z[0][2] + z[1][2], z[0][3] + z[1][3]);
        bar_sync(3, 128);
        if (j == 0 || t4 < 2) {
          float2 q[4];
#pragma unroll
          for (int i = 0; i < 4; i++) q[i] = lds64f(za + CH_VT + i * 1024);
          stg_strong32(dst, pack_tag(((q[0].x + q[1].x) + (q[2].x + q[3].x)) * iv.x, ((q[0].y + q[1].y) + (q[2].y + q[3].y)) * iv.y, tag, mask));
        }
      }
      TM(2);
      if (!NOX) mbar_wait_hot(bXA, (s + 1) & 1);
      if (CH_KP == 2) bulk_wait_read<0>();
      float dk[16], dw[16];
      bar_sync(5, 256);
      wg_fence();
      pass(dk, ak, Int<0>(), Int<20>());
      pass(dw, av, Int<0>(), Int<20>());
      TM(5);
      pin();
      if (CH_EX == 0) publish_v(s, v, vm);
      if (elect()) {
        mbar_expect(bG + t4 * 8, 2560);
        if (t4 == 1 && s + 2 < NSEG) { mbar_expect(bX, 1536); mbar_expect(bO, 2048); }
      }
      if (CH_KD == 0) { wg_wait<1>(); dump(dk, lw + CH_KT); }
      wg_wait<0>();
      if (CH_KD == 1) dump(dk, lw + CH_KT);
      TM(7);
      dump(dw, lw + CH_VT);
      bar_arrive(9, 256);
      pin();
#pragma unroll
      for (int k = 0; k < CH_RB; k++) ldsm4t(&tw[4 * k], wq + k * 2048);
      if (t4 < 2) {
        if (CH_EX == 2) { publish_v(s, v, vm); pin(); }
#pragma unroll
        for (int k = CH_RB; k < CH_RC; k++) ldsm4t(&tw[4 * k], wq + k * 2048);
        const int q = t4 ? 3 : j, o = t4 ? j * 896 : 0;
        const uint8_t* src = p.pool + ((80 + st * 4 + q) * 8192 + (pages >> (st * 4 + q) & 1) * 4096 + o);
        asm volatile("bar.sync 8, 256;" ::: "memory");
        const uint32_t t1 = clk32() + CH_D2;
        if (CH_EX == 1) publish_v(s, v, vm);
        auto fetch = [&](auto n) {
          mbar_wait(bH, s & 1);
          until(t1);
          TR(4, clk32());
          if (elect())
            asm volatile("cp.async.bulk.shared::cluster.global.mbarrier::complete_tx::bytes.multicast::cluster [%0], [%1], %2, [%3], 7;"
                         :: "r"(sb + CH_M + q * 2560 + o), "l"(src), "n"(n.value), "r"(bG + q * 8) : "memory");
        };
        if (!t4) fetch(Int<2560>()); else if (j == 2) fetch(Int<768>()); else fetch(Int<896>());
      } else {
        asm volatile("bar.sync 8, 256; " ::: "memory");
        if (elect()) asm volatile("mbarrier.arrive.relaxed.cluster.shared::cluster.b64 _, [%0];" :: "r"(bH + (t4 == 2 ? r1 : r2)) : "memory");
        pin();
        if (CH_EX) publish_v(s, v, vm);
#pragma unroll
        for (int k = CH_RB; k < CH_RC; k++) ldsm4t(&tw[4 * k], wq + k * 2048);
      }
      TM(9);
      pin();
#pragma unroll
      for (int k = CH_RC; k < CH_TW - CH_P1; k++) ldsm4t(&tw[4 * k], wq + k * 2048);
      if (CH_KP == 2 && t4 == CH_KW) { bar_sync(7, 160); publish_k(s + 1); }
      TM(10);
    }
    if (++st == 3) st = 0;
    tag ^= 0x10001;
  }
}

__global__ void __launch_bounds__(256, 1) chain_kernel(const __grid_constant__ ChainParams p) {
  extern __shared__ __align__(1024) uint8_t smem_raw[];
  const uint32_t sb = s2u(smem_raw);
  const int tid = threadIdx.x, warp = __shfl_sync(~0u, tid >> 5, 0), lane = tid & 31;
  const int cta = blockIdx.x, h = cta / 3, j = cta - 3 * h, colbase = cta * 64;
  const uint32_t bWo = sb + CH_BAR, bWq = bWo + 8, bXA = bWo + 24, bWk = bWo + 80, bWv = bWo + 88;
  uint32_t smid; asm("mov.u32 %0, %%smid;" : "=r"(smid));
  PRO(0);
  if (sb != mapa(CH_BASE, j)) __trap();
  uint32_t entry = 0;
  auto place = [&]() {
    const int i = tid - 128;
    if (i >= 0 && i <= NSLOT) {
      const uint32_t side = ldg_strong32(g_smpart + (smid & 255));
      if (i < NSLOT) {
        entry = i * 8192 + (ldg_strong32(g_orient + i) == (i < 80 ? i & 1 : side) ? 0 : 4096);
      } else {
        entry = 2 * (atomicAdd(g_bo + p.layer * 128 + 1, 1 << 8 * side) >> 8 * side & 255) + side;
      }
    }
    __syncwarp();
  };
  if (warp == 2 && lane < 4) asm volatile("prefetch.tensormap [%0];" :: "l"(&p.wq + lane) : "memory");
  if (p.layer) place();
  if (warp == 0 && elect()) {
#pragma unroll 1
    for (int i = 0; i < 17; i++) mbar_init(bWo + 8 * i, i == 5 ? 5 : i == 3 || i == 4 ? 4 : i == 12 ? 2 : 1);
    asm volatile("fence.mbarrier_init.release.cluster;" ::: "memory");
    mbar_expect(bWk, 81920);
    tma_load3<(WEF & 1) != 0>(sb + CH_WQ, &p.wk, colbase, 0, bWk);
    mbar_expect(bWv, 81920);
    tma_load3<(WEF & 1) != 0>(sb + CH_WO, &p.wv, colbase, 0, bWv);
    mbar_expect(bWo + 16, 1536);
    mbar_expect(bWo + 40, 2048);
    mbar_expect(bWo, 86016); mbar_expect(bWq, 81920);
#pragma unroll 1
    for (int i = 0; i < 8; i++) mbar_expect(bXA + 8 * (i & 1), 5120);
  }
  if (warp == 1) {
    const uint32_t id = (lane >> 3) == (lane & 3) ? ((lane & 4) ? 0x3f800000u : 0x00003f80u) : 0u;
    sts128(sb + CH_ID + lane * 16, make_uint4(id, 0, id, 0));
  }
  __syncthreads();
  asm volatile("barrier.cluster.arrive.relaxed.aligned;" ::: "memory");
  uint32_t ak[80], av[80];
  const uint32_t wq = opaque(sb + CH_WQ + ((warp >> 2) * 320 + (lane & 7) + (lane >> 4) * 8) * 128 + (((2 * (warp & 3) + ((lane >> 3) & 1)) ^ (lane & 7)) << 4));
  pdl_wait();
  if (tid == 32) stg_strong32(g_smuse + (smid & 255), p.layer + 1);
  pdl_launch();
  PRO(1);
  if (warp == 0 && elect()) {
    bulk_load(sb + CH_X + 20480, p.xc + 5120, 20480, bXA);
    bulk_load(sb + CH_X, p.xc, 20480, bXA + 8);
  }
  if (!p.layer) place();
  __syncwarp();
  PRO(2);
  mbar_wait(bWk, 0);
  PRO(3);
#pragma unroll
  for (int k = 0; k < 20; k++) ldsm4t(&ak[4 * k], wq + k * 2048);
  bar_sync(6, 256);
  if (warp == 0 && elect()) tma_load3<(WEF & 2) != 0>(sb + CH_WQ, &p.wq, colbase, 0, bWq);
  __syncwarp();
  PRO(4);
  mbar_wait(bWv, 0);
  PRO(5);
#pragma unroll
  for (int k = 0; k < 20; k++) ldsm4t(&av[4 * k], wq + CH_WO + k * 2048);
  bar_sync(6, 256);
  PRO(6);
  if (warp >= 5 && elect()) tma_load3<(WEF & 2) != 0>(sb + CH_WO + (warp - 5) * 28672, &p.wo, j == 0 ? 0 : 32 + j * 192, h * 192 + (j + 8 - warp) % 3 * 64, bWo);
  if (tid == 128 + NSLOT && entry >= 80) {
    uint32_t c;
    int n = 0;
    do { c = ldg_strong32(g_bo + p.layer * 128 + 1); spin_guard(n); } while ((c & 255) + (c >> 8) < 96);
    const uint32_t other = (c >> 8 * (~entry & 1) & 255) + (entry >> 1) - 40;
    entry = other < 40 ? 2 * other + (~entry & 1) : entry % 80;
  }
  if (tid >= 128 && tid <= 128 + NSLOT) sts32(sb + CH_O + (tid - 128) * 4, entry);
  PRO(7);
  __syncthreads();
  if (__shfl_sync(~0u, tid >> 7, 0) == 0) chain_body<0>(p, wq, ak, av); else chain_body<1>(p, wq, ak, av);
}

struct PostParams { CUtensorMap wq, wo, wb, wo2, wb2; int gap, share, layer, look, gap2, pol, slow_n, slow_gap; };
constexpr int PS = 8, PB = 28672;
constexpr int OP_SMEM = PS * PB + 512 + 2048;
enum { IT_ATT = 0, IT_OP = 1, IT_FIN = 2, IT_BQ = 3, IT_Q = 4 };

__device__ __forceinline__ uint32_t item_count(int type, int b) {
  return type == IT_ATT ? 32 : type == IT_OP ? op_split(b) * (b < OP_160 ? 2 : 4) : type == IT_FIN ? 16 : b < BQ_160 ? 6 : b < BQ_80 ? 12 : 24; }
__device__ __forceinline__ uint32_t item_need(int type, int b) { return type == IT_ATT ? 96 : item_count(type - 1, b); }

struct Ring {
  uint32_t sb, bars; int st; uint32_t ph;
  __device__ __forceinline__ uint32_t wait() const { mbar_wait(bars + 8 * st, ph); return sb + st * PB; }
  __device__ __forceinline__ void next() { if (++st == PS) { st = 0; ph ^= 1; } }
  __device__ __forceinline__ void release(int s) const { if ((threadIdx.x & 31) == 0) mbar_arrive(bars + 8 * (PS + s)); }
  __device__ __forceinline__ void pop() { __syncwarp(); release(st); next(); }
};

template <int N>
__device__ __forceinline__ void gemm_item(Ring& r, float* d, int nst, uint32_t go, int go_at, uint32_t wg) {
  auto desc = [](uint32_t lo, uint32_t hi) { uint64_t x; asm("mov.b64 %0, {%1, %2};" : "=l"(x) : "r"(lo), "r"(hi)); return x; };
  auto stage = [&](auto first) {
    const uint32_t base = (r.wait() & 0x3ffff) >> 4, a = base + wg * 256 + (8 << 16), w = base + 512 + (256 << 16);
    wg_fence();
#pragma unroll
    for (int kk = 0; kk < 2; kk++) {
      const uint64_t da = desc(a + kk * 16, 32), db = desc(w + kk * 128, 64 | 1 << 30);
      const int acc = kk || !first.value;
      if (N == 80) wg_ss80_01(d, da, db, acc);
      if (N == 160) wg_ss160_01(d, da, db, acc);
      if (N >= 192) wg_ss192_01(d, da, db, acc);
      if (N == 320) wg_ss128_01(d + 96, da, desc(w + kk * 128 + 768, 64 | 1 << 30), acc);
    }
    wg_commit();
  };
  stage(Int<1>());
  int prev = r.st;
  r.next();
#pragma unroll 1
  for (int kb = 1; kb < nst; kb++) {
    stage(Int<0>());
    if (kb == go_at && threadIdx.x == 0) mbar_arrive(go);
    wg_wait<1>();
    r.release(prev);
    prev = r.st;
    r.next();
  }
  wg_wait<0>();
  reg_fence<N / 2>(d);
  r.release(prev);
}

template <int HALF>
__device__ __forceinline__ void attn_a_warp(Ring& r, const uint32_t (&q)[48], int b, int h) {
  constexpr int NT = HALF ? 5 : 3, NF = 8 * NT;
  const int lane = threadIdx.x & 31, g = lane >> 2, c = lane & 3, seg = (threadIdx.x >> 5) & 3;
  uint32_t f[6][NF];
  int slot[6];
  auto fetch = [&](int u) {
    const uint32_t kv = r.wait() + seg * KV_BYTES;
    slot[u] = r.st;
    r.next();
#pragma unroll
    for (int w = 0; w < 4; w++) {
      uint32_t* d = &f[u][2 * NT * w];
#pragma unroll
      for (int t = 0; t <= HALF; t++) {
        if (u < 3) {
          ldsm4(d + 4 * t, kv + w * 1024 + t * 512 + (lane & 8) * 32 + (lane & 16) * 8 + (lane & 7) * 16);
        } else {
          const uint4 v = lds128(kv + w * 1024 + t * 512 + lane * 16);
          d[4 * t] = v.x; d[4 * t + 1] = v.y; d[4 * t + 2] = v.z; d[4 * t + 3] = v.w;
        }
      }
      const uint2 m = lds64(kv + KV_M + w * 256 + lane * 8);
      d[2 * NT - 2] = m.x; d[2 * NT - 1] = m.y;
    }
    pdl_launch();
  };
  float s[NT][4] = {};
  fetch(0);
#pragma unroll
  for (int u = 0; u < 3; u++) {
    fetch(u + 1);
#pragma unroll
    for (int kk = 0; kk < 4; kk++) {
      const uint32_t* a = &q[16 * u + 4 * kk];
#pragma unroll
      for (int n = 0; n < NT; n++) mma16(s[(n + 1) % NT], a[0], a[1], a[2], a[3], f[u][2 * NT * kk + 2 * n], f[u][2 * NT * kk + 2 * n + 1]);
    }
    r.release(slot[u]);
    pdl_launch();
  }
  fetch(4);
  const float k2 = 0.07216878364870322f * 1.44269504089f, NEG = -INFINITY;
  if (2 * c > g) { s[NT - 2][0] = NEG; s[NT - 1][2] = NEG; }
  if (2 * c + 1 > g) { s[NT - 2][1] = NEG; s[NT - 1][3] = NEG; }
  s[NT - 1][0] = s[NT - 1][1] = NEG;
  uint32_t pp[NT][2]; float inv[2];
#pragma unroll
  for (int hh = 0; hh < 2; hh++) {
    float m = NEG, l = 0.f;
#pragma unroll
    for (int n = 0; n < NT; n++) m = fmaxf(m, fmaxf(s[n][2 * hh], s[n][2 * hh + 1]));
    m = fmaxf(m, __shfl_xor_sync(~0u, m, 1)); m = fmaxf(m, __shfl_xor_sync(~0u, m, 2));
#pragma unroll
    for (int n = 0; n < NT; n++) { const float x = ex2((s[n][2 * hh] - m) * k2), y = ex2((s[n][2 * hh + 1] - m) * k2); l += x + y; pp[n][hh] = pack2(x, y); }
    l += __shfl_xor_sync(~0u, l, 1); l += __shfl_xor_sync(~0u, l, 2);
    asm("rcp.approx.ftz.f32 %0, %1;" : "=f"(inv[hh]) : "f"(l));
  }
  uint32_t* dst = g_o + ((b * 192 + h * 6) * 16 + seg * 4 + HALF * 2) * 128 + lane;
#pragma unroll
  for (int u = 3; u < 6; u++) {
    float o[8][4] = {};
#pragma unroll
    for (int n = 0; n < 8; n++) mma8(o[n], pp[0][0], pp[0][1], f[u][2 * NT * (n >> 1) + 2 * NT - 2 + (n & 1)]);
#pragma unroll
    for (int t = 0; t <= HALF; t++)
#pragma unroll
      for (int n = 0; n < 8; n++) {
        const uint32_t* v = &f[u][2 * NT * (n >> 1) + 4 * t + 2 * (n & 1)];
        mma16(o[n], pp[1 + 2 * t][0], pp[1 + 2 * t][1], pp[2 + 2 * t][0], pp[2 + 2 * t][1], v[0], v[1]);
      }
    r.release(slot[u]);
    if (u == 3) fetch(5);
#pragma unroll
    for (int n = 0; n < 8; n++) {
      dst[(u - 3) * 4096 + (n >> 2) * 2048 + (n & 3) * 32] = pack2(o[n][0] * inv[0], o[n][1] * inv[0]);
      dst[(u - 3) * 4096 + (n >> 2) * 2048 + (n & 3) * 32 + 128] = pack2(o[n][2] * inv[1], o[n][3] * inv[1]);
    }
  }
}

__device__ __forceinline__ void fin_item(Ring& r, uint32_t scratch, int b, int idx) {
  const int warp = threadIdx.x >> 5, lane = threadIdx.x & 31;
  float4 v[1][5];
  {
    const uint32_t base = r.wait();
#pragma unroll
    for (int i = 0; i < 5; i++) v[0][i] = unpack4(lds64(base + ((warp * 5 + i) * 32 + lane) * 8));
    r.pop();
  }
#pragma unroll 1
  for (int k = 0; k < op_split(b); k += 2) {
    const uint32_t base = r.wait();
#pragma unroll
    for (int i = 0; i < 10; i++) {
      const uint2 q = lds64(base + ((i / 5 * 40 + warp * 5 + i % 5) * 32 + lane) * 8);
      float4& t = v[0][i % 5];
      t.x += bf_lo(q.x); t.y += bf_hi(q.x); t.z += bf_lo(q.y); t.w += bf_hi(q.y);
    }
    r.pop();
  }
#pragma unroll
  for (int i = 0; i < 5; i++) g_x[((b * 16 + idx) * 40 + warp * 5 + i) * 32 + lane] = pack4(v[0][i]);
  float mean[1], rs[1];
  ln_stats<1>(v, scratch, mean, rs);
#pragma unroll
  for (int i = 0; i < 5; i++) {
    const int u = warp * 5 + i;
    uint32_t* xn = g_xn + ((b * 20 + (u >> 1)) * 16 + idx) * 128 + (u & 1) * 64 + lane;
    xn[0] = pack2((v[0][i].x - mean[0]) * rs[0], (v[0][i].y - mean[0]) * rs[0]);
    xn[32] = pack2((v[0][i].z - mean[0]) * rs[0], (v[0][i].w - mean[0]) * rs[0]);
  }
}

__global__ void __launch_bounds__(384, 1) post_kernel(const __grid_constant__ PostParams p) {
  extern __shared__ __align__(1024) uint8_t smem_raw[];
  const uint32_t sb = s2u(smem_raw), bars = sb + PS * PB;
  const uint32_t bIF = bars + 128, bIE = bars + 160, done = bars + 192, bGo = bars + 224, slots = bars + 240, scratch = bars + 512;
  const int warp = __shfl_sync(~0u, threadIdx.x >> 5, 0), lane = threadIdx.x & 31;
  if (warp == 9) PST(0);
  if (warp == 0 && blockIdx.x < 36) TRACE(0);
  if (warp >= 8) {
    asm volatile("setmaxnreg.dec.sync.aligned.u32 56;");
    if (warp == 10) {
      pdl_launch();
      if (sb & 1023) __trap();
      if (lane < 29) mbar_init(bars + 8 * lane, lane < 8 ? 1 : lane < 16 ? 8 : lane < 20 ? 1 : lane < 24 ? 2 : lane < 28 ? 8 : 1);
      if (lane == 0) sts32(slots + 16, p.gap);
      fence_async();
    }
    if (warp == 8 && lane < 5) asm volatile("prefetch.tensormap [%0];" :: "l"(&p.wq + lane) : "memory");
    if (warp != 9) bar_sync(2, 384);
    if (warp == 9) {
      PST(1);
      const int b = lane & 15;
      bool queries = QA_END < 16 && blockIdx.x < 36;
      for (int n = 0;; n++) {
        if (n > 0) { mbar_wait(bGo, (n - 1) & 1); mbar_wait(bIE + 8 * (n & 3), ((n >> 2) & 1) ^ 1); }
        int code = -1, spin = 0, ticket = 0;
        if (queries) {
          if (lane == 0) ticket = n == 0 ? blockIdx.x : 36 + atomicAdd(g_sync + SY_QC, 1);
          ticket = __shfl_sync(~0u, ticket, 0);
          queries = ticket < (16 - QA_END) * 32;
          if (queries) code = IT_Q << 16 | (QA_END + ticket % (16 - QA_END)) << 8 | ticket / (16 - QA_END);
        }
        if (!queries && lane == 0) asm volatile("atom.relaxed.gpu.global.add.u32 %0, [%1], 1;" : "=r"(ticket) : "l"(g_sync + SY_T) : "memory");
        while (!queries) {
          const uint4 hd = ldg_strong128(g_sync + b * 8), pr = ldg_strong128(g_sync + b * 8 + 4);
          if (n == 0 && spin == 0 && hd.x != 0x7fffffff) PST(2);
          const uint32_t hv[4] = {hd.x, hd.y, hd.z, hd.w}, pv[4] = {pr.x, pr.y, pr.z, pr.w};
          const uint32_t chain_done = __ballot_sync(~0u, (pr.x & 0xffff) >= 96) & 0xffff;
          int left[4], avail[4], rdy = 0, claimed = 0, upstream = 0;
#pragma unroll
          for (int t = 0; t < 4; t++) {
            const int cnt = lane < 16 ? item_count(t, b) : 0;
            left[t] = max(cnt - (int)hv[t], 0);
            claimed += cnt - left[t];
            const bool ready = (pv[t] & 0xffff) >= item_need(t, b);
            rdy |= ready << t;
            bool ok = ready || (t == IT_ATT ? pr.x >= 0x10000 : !upstream || (t == IT_OP && (chain_done >> 15 & 1)));
            if (t == IT_BQ && (chain_done >> BQ_HOLD & 1) && !(chain_done >> 15)) ok = false;
            avail[t] = ok ? left[t] : 0;
            upstream |= __any_sync(~0u, left[t] > 0);
          }
          if (!upstream) break;
          int rank = max(__shfl_sync(~0u, ticket, 0) - __reduce_add_sync(~0u, claimed), 0), type = -1, mine = 0;
          {
            const int a = b >= BQ_RUSH && (rdy >> IT_BQ & 1) ? avail[IT_BQ] : 0, tot = __reduce_add_sync(~0u, a);
            if (rank < tot) { type = IT_BQ; mine = a; } else rank -= tot;
            avail[IT_BQ] -= a;
          }
#pragma unroll
          for (int c = 0; c < 8; c++) {
            const int t = c == PR_FIN || c == 5 ? IT_FIN : c == PR_ATT || c == 7 ? IT_ATT : c == PR_OP || c == 4 ? IT_OP : IT_BQ;
            int a = c == PR_ATT || ((rdy >> t & 1) == (c < 4)) ? avail[t] : 0;
            if (t == IT_OP && OP_EARLY) a = c == PR_OP ? avail[t] : 0;
            if (c == 7) a = b < QA_END && !(rdy & 1) && ((chain_done << 1 | 1) >> b & 1) ? left[t] : 0;
            const int tot = __reduce_add_sync(~0u, a);
            if (type < 0) { if (rank < tot) { type = t; mine = a; } else rank -= tot; }
          }
          if (type >= 0) {
#pragma unroll
            for (int o = 1; o < 16; o <<= 1) { const int y = __shfl_up_sync(~0u, mine, o); if (lane >= o) mine += y; }
            const int blk = __ffs(__ballot_sync(~0u, mine > rank)) - 1;
            const int early = !(__shfl_sync(~0u, rdy, blk) >> type & 1);
            uint32_t idx = 0;
            if (n == 0 && spin == 0) PST(3);
            if (lane == 0) asm volatile("atom.relaxed.gpu.global.add.u32 %0, [%1], 1;" : "=r"(idx) : "l"(g_sync + blk * 8 + type) : "memory");
            ld_acquire(g_sync + blk * 8 + 4 + type);
            idx = __shfl_sync(~0u, idx, 0);
            if (idx < item_count(type, blk)) { code = (__shfl_sync(~0u, pr.y, 15) < 32) << 23 | (chain_done >> 15 & 1) << 22 | (chain_done >> p.look & 1) << 21 | early << 20 | type << 16 | blk << 8 | idx; break; }
          } else {
            __nanosleep(50);
          }
          spin_guard(spin);
        }
        if (n == 0) bar_sync(2, 384);
        if (lane == 0) {
          fence_async_global();
          sts32(slots + 4 * (n & 3), code);
          mbar_arrive(bIF + 8 * (n & 3));
        }
        __syncwarp();
        if (code < 0) break;
      }
    } else if (warp == 8) {
      if (elect()) {
        uint32_t dst = sb, bar = bars, ph = 1, next = clk32(), gap = 0;
        auto acquire = [&](uint32_t kb) {
          mbar_wait(bar + 8 * PS, ph);
          mbar_expect(bar, kb * 1024);
          if (gap) {
            uint32_t now;
            do now = clk32(); while ((int)(now - next) < 0);
            next = ((int)(now - next) > 100 ? now - 100 : next) + kb * gap;
          }
        };
        auto advance = [&]() { dst += PB; bar += 8; if (dst == bars) { dst = sb; bar = bars; ph ^= 1; } };
        auto depend = [&](const uint32_t* c, uint32_t need) { wait_count(c, need); fence_async_global(); };
#pragma unroll 1
        for (int n = 0;; n++) {
          mbar_wait(bIF + 8 * (n & 3), (n >> 2) & 1);
          const int code = (int)lds32(slots + 4 * (n & 3));
          if (code < 0) break;
          const int type = (code >> 16) & 15, b = (code >> 8) & 255, idx = code & 255;
          const bool early = code >> 20 & 1, go = !(code >> 21 & 1);
          mbar_arrive(bIE + 8 * (n & 3));
          gap = !(code >> 22 & 1) ? lds32(slots + 16) : type == IT_ATT || type == IT_FIN ? 0 : p.gap2;
          const uint32_t* progress = g_sync + b * 8 + 4 + type;
          if (type == IT_ATT && b >= QA_END) {
            depend(g_sync + SY_Q, (16 - QA_END) * 32);
#pragma unroll 1
            for (int u = 0; u < 2; u++) { acquire(24); bulk_load_last(dst, g_q + (((b - QA_END) * 32 + idx) * 2 + u) * 1536, 24576, bar); advance(); }
          } else if (type == IT_FIN) {
            acquire(10);
            bulk_load(dst, g_x + (b * 16 + idx) * 1280, 10240, bar);
            advance();
            if (early) depend(progress, item_need(type, b));
            if (go) mbar_arrive(bGo);
            const uint2* src = g_part + (b * 16 + idx) * 16 * 1280;
#pragma unroll 1
            for (int i = 0; i < op_split(b); i += 2) { acquire(20); bulk_load_last(dst, src + i * 1280, 20480, bar); advance(); }
            if (!go && p.pol) mbar_arrive(bGo);
          } else {
            const bool op = type == IT_OP, bq = type == IT_BQ;
            const int width = op ? op_width(b) : bq ? bq_width(b) : 192, nb = (width + 63) >> 6, lt = width == 320 ? 1 : 2;
            const int nst = op ? 192 / op_split(b) : 20, kb0 = op ? (idx >> lt) * nst : 0;
            const int col = (op ? idx & ((1 << lt) - 1) : idx) * width;
            const bool whole = !(width & 63);
            const CUtensorMap* m = op ? (whole ? &p.wo : &p.wo2) : bq ? (whole ? &p.wb : &p.wb2) : &p.wq;
            const uint32_t* a = op ? g_o + (b * 192 + kb0) * 2048 : g_xn + b * 20 * 2048;
            int row = kb0 * 32, pre = early && (op || bq) ? min(nst, PRE_MAX) : 0;
            int slow = (code >> 22 & 3) == 3 ? p.slow_n : 0;
            if (slow) gap = p.slow_gap;
            auto weights = [&]() {
              if (slow && --slow == 0) gap = 0;
              acquire(8 + nb * 4);
              if (whole) {
                tma_load3z(dst + 8192, m, row, col >> 6, bar);
              } else {
                tma_load(dst + 8192, m, col, row, bar); tma_load(dst + 12288, m, col + 64, row, bar);
                if (nb == 3) tma_load(dst + 16384, m, col + 128, row, bar);
              }
              row += 32;
            };
            if (pre) {
              uint32_t da = dst, ba = bar;
#pragma unroll 1
              for (int kb = 0; kb < pre; kb++) { weights(); advance(); }
              depend(progress, item_need(type, b));
#pragma unroll 1
              for (int kb = 0; kb < pre; kb++) {
                bulk_load(da, a, 8192, ba);
                a += 2048; da += PB; ba += 8;
                if (da == bars) { da = sb; ba = bars; }
              }
            }
#pragma unroll 1
            for (int kb = pre; kb < nst; kb++) { weights(); if (op && OEF) bulk_load_last(dst, a, 8192, bar); else bulk_load(dst, a, 8192, bar); a += 2048; advance(); }
          }
          if (type == IT_ATT) {
            if (early) depend(progress, 96);
            if (go) mbar_arrive(bGo);
            const uint8_t* src = g_kv + (size_t)(idx * 6 * NSEG + b * 4) * KV_BYTES;
#pragma unroll 1
            for (int u = 0; u < 6; u++) {
              acquire(20);
              bulk_load_last(dst, src, 20480, bar);
              src += u == 2 ? -3 * KV_V : 2 * KV_V;
              advance();
            }
            if (!go && p.pol && ATT_LOOK) mbar_arrive(bGo);
          }
        }
      }
    } else if (warp == 11) {
      uint32_t smid, nsm, used = 0;
      asm("mov.u32 %0, %%smid;" : "=r"(smid)); asm("mov.u32 %0, %%nsmid;" : "=r"(nsm));
      for (int n = 0; n < 64 && used < 96; n++) {
        uint32_t peers = 0;
        used = 0;
        for (uint32_t i = lane; i < min(nsm, 256u); i += 32) {
          const bool taken = ldg_strong32(g_smuse + i) == p.layer + 1;
          used += taken;
          peers += abs((int)(g_smclk[i] - g_smclk[smid & 255])) < 4000 && !taken;
        }
        used = __reduce_add_sync(~0u, used);
        sts32(slots + 16, max(p.gap, (int)min(__reduce_add_sync(~0u, peers), 18u) * p.share >> 3));
      }
    } else if (warp == 10 && lane == 0) {
      for (int n = 0;; n++) {
        mbar_wait(bIF + 8 * (n & 3), (n >> 2) & 1);
        const int code = (int)lds32(slots + 4 * (n & 3));
        if (code < 0) break;
        const int type = (code >> 16) & 15, b = (code >> 8) & 255;
        mbar_wait(done + 8 * (n & 3), (n >> 2) & 1);
        if (type != IT_BQ) red_release(type == IT_Q ? g_sync + SY_Q : g_sync + b * 8 + 5 + type, 1);
        mbar_arrive(bIE + 8 * (n & 3));
      }
    }
  } else {
    asm volatile("setmaxnreg.inc.sync.aligned.u32 224;");
    bar_sync(2, 384);
    const int g = lane >> 2, c = lane & 3;
    Ring r = {sb, bars, 0, 0};
#pragma unroll 1
    for (int n = 0;; n++) {
      mbar_wait(bIF + 8 * (n & 3), (n >> 2) & 1);
      const int code = __shfl_sync(~0u, (int)lds32(slots + 4 * (n & 3)), 0);
      if (code < 0) { TRACE(2); break; }
      const int type = (code >> 16) & 15, b = (code >> 8) & 255, idx = code & 255;
      ITEM(code & 0xfffff, 0);
      if (type == IT_ATT || type == IT_Q) {
        uint32_t q[48];
        if (type == IT_Q || b < QA_END) {
          float d[96];
          gemm_item<192>(r, d, 20, bGo, type == IT_Q ? 12 : -1, warp >> 2);
#pragma unroll
          for (int i = 0; i < 48; i++) q[i] = pack2(d[2 * i], d[2 * i + 1]);
        } else {
#pragma unroll
          for (int u = 0; u < 2; u++) {
            const uint32_t base = r.wait() + threadIdx.x * 16;
#pragma unroll
            for (int i = 0; i < 6; i++) {
              const uint4 v = lds128(base + i * 4096);
              q[24 * u + 4 * i] = v.x; q[24 * u + 4 * i + 1] = v.y; q[24 * u + 4 * i + 2] = v.z; q[24 * u + 4 * i + 3] = v.w;
            }
            r.pop();
          }
        }
        if (type == IT_Q) {
          uint4* dst = g_q + ((b - QA_END) * 32 + idx) * 3072 + threadIdx.x;
#pragma unroll
          for (int i = 0; i < 12; i++) dst[i * 256] = make_uint4(q[4 * i], q[4 * i + 1], q[4 * i + 2], q[4 * i + 3]);
        } else if (warp < 4) {
          attn_a_warp<0>(r, q, b, idx);
        } else {
          attn_a_warp<1>(r, q, b, idx);
        }
      } else if (type == IT_FIN) {
        fin_item(r, scratch, b, idx);
      } else {
        float d[160];
        const int width = type == IT_OP ? op_width(b) : bq_width(b), nst = type == IT_OP ? 192 / op_split(b) : 20;
        const int go_at = max(nst - (code >> 21 & 1 ? p.pol : 6), 1);
        if (width == 320) {
          gemm_item<320>(r, d, nst, bGo, go_at, warp >> 2);
        } else if (width == 160 || BQ_80 == 16) {
          gemm_item<160>(r, d, nst, bGo, go_at, warp >> 2);
#pragma unroll
          for (int i = 80; i < 160; i++) d[i] = 0.f;
        } else {
          gemm_item<80>(r, d, nst, bGo, go_at, warp >> 2);
#pragma unroll
          for (int i = 40; i < 160; i++) d[i] = 0.f;
        }
        if (type == IT_OP) {
          const int tiles = DM / width;
          uint2* dst = g_part + (((b * 16 + warp * 2) * 16 + idx / tiles) * 40 + idx % tiles * (width / 16)) * 32 + lane;
#pragma unroll
          for (int u = 0; u < 20; u++) {
            if (u % 5 == 0 && u * 16 >= width) break;
            dst[u * 32] = make_uint2(pack2(d[8 * u], d[8 * u + 1]), pack2(d[8 * u + 4], d[8 * u + 5]));
            dst[(640 + u) * 32] = make_uint2(pack2(d[8 * u + 2], d[8 * u + 3]), pack2(d[8 * u + 6], d[8 * u + 7]));
          }
        } else {
          const int row = b * 128 + warp * 16 + g;
          const int h0 = idx * (width / 20);
          const float sc = h0 < 32 ? 0.22360679775f * 1.44269504089f : 1.f;
          const bool lo = c < 2;
          uint32_t* da = g_bqkv + (h0 * 256 + (row >> 3)) * 96 + lane;
          uint32_t* db = da + 256 * 96 + (lo ? 2 : -2);
          uint32_t pad[2];
#pragma unroll
          for (int rr = 0; rr < 2; rr++) pad[rr] = c & 1 || h0 < 32 ? 0u : h0 >= 64 ? 0x00003f80u : poly_group((row >> 3) + rr) ? 0x3f803f80u : 0u;
#pragma unroll
          for (int q = 0; q < 8; q++) {
            if (!(q & 1) && q * 40 >= width) break;
#pragma unroll
            for (int rr = 0; rr < 2; rr++) {
              uint32_t w[5];
#pragma unroll
              for (int i = 0; i < 5; i++) w[i] = pack2(d[20 * q + 4 * i + 2 * rr] * sc, d[20 * q + 4 * i + 2 * rr + 1] * sc);
              const int o = q * 2 * 256 * 96 + rr * 96;
              da[o] = w[0]; da[o + 32] = w[1]; da[o + 64] = lo ? w[2] : pad[rr];
              db[o] = lo ? w[3] : w[2]; db[o + 32] = lo ? w[4] : w[3]; db[o + 64] = lo ? pad[rr] : w[4];
            }
          }
        }
      }
      __syncwarp();
      if (lane == 0) mbar_arrive(done + 8 * (n & 3));
      if ((code >> 21 & 1) && (p.pol == 0 || (type == IT_ATT && !ATT_LOOK)) && threadIdx.x == 128) mbar_arrive(bGo);
      ITEM(code & 0xfffff, 1);
    }
  }
}

constexpr int AB_SMEM = 1024 + 98304 + 51200 + 4 * 16384 + 256 + 10240;
#define AB_LW 1
#define AB_U 8
#define AB_WG 4
constexpr int AB_T = AB_WG * 128, AB_PASS = 8 / AB_WG;
__device__ __forceinline__ uint32_t fma2(uint32_t a, uint32_t b, uint32_t c) { uint32_t r; asm("fma.rn.bf16x2 %0, %1, %2, %3;" : "=r"(r) : "r"(a), "r"(b), "r"(c)); return r; }
__device__ __forceinline__ uint32_t ex2_pair(float a, float b, uint32_t one, uint32_t c0) {
  const uint32_t e = __byte_perm(__float_as_uint(a), __float_as_uint(b), 0x6521);
  uint32_t x, r;
  asm("lop3.b32 %0, %1, 0x007f007f, %2, 0xEA;" : "=r"(x) : "r"(e), "r"(one));
  const uint32_t m = fma2(fma2(c0, x, 0x3c0d3c0du), x, 0x3f2b3f2bu);
  asm("lop3.b32 %0, %1, %2, 0x7f807f80, 0xE4;" : "=r"(r) : "r"(e), "r"(m));
  return r;
}
__device__ __forceinline__ float sq2(uint32_t w) { const float a = bf_lo(w), b = bf_hi(w); return fmaf(a, a, b * b); }

__device__ __forceinline__ void attn_b_store(const float* o, int h, int row0, int lane) {
  const int g = lane >> 2, c = lane & 3;
  const float i0 = __frcp_rn(__shfl_sync(~0u, o[8], (lane & ~3) | 2)), i1 = __frcp_rn(__shfl_sync(~0u, o[10], (lane & ~3) | 2));
#pragma unroll
  for (int jj = 0; jj < 3; jj++) {
    if (jj < 2 || c < 2) {
      const int col = h * 20 + 8 * jj + 2 * c;
      uint32_t* dst = g_of + (((row0 >> 7) * 10 + (col >> 6)) * 16 + (row0 >> 3 & 15)) * 256 + (col >> 3 & 7) * 32 + g * 4 + (col >> 1 & 3);
      dst[0] = pack2(o[4 * jj] * i0, o[4 * jj + 1] * i0);
      dst[256] = pack2(o[4 * jj + 2] * i1, o[4 * jj + 3] * i1);
    }
  }
}

struct AbParams { Weights next; uint32_t* done; uint32_t* out; };
__global__ void __launch_bounds__(AB_T + 32, 1) attn_b_kernel(const __grid_constant__ AbParams p) {
  extern __shared__ uint8_t smem_raw[];
  const uint32_t sb = (s2u(smem_raw) + 1023) & ~1023u, sK = sb, sV = sb + 98304, bars = sV + 51200 + 4 * 16384;
  const uint32_t bF = bars + 64, bW = bars + 72, bA = bars + 80, bE = bars + 128, smax = bars + 176;
  auto ring = [&](int i) { return i < 2 ? sK + 51200 + i * 16384 : sV + 51200 + (i - 2) * 16384; };
  const int warp = __shfl_sync(~0u, threadIdx.x >> 5, 0), lane = threadIdx.x & 31;
  const int h = blockIdx.x >> 2, quarter = blockIdx.x & 3;
  TRACE(0);
  pdl_launch();
  if (threadIdx.x < 22) mbar_init(bars + 8 * threadIdx.x, threadIdx.x == 8 ? AB_T / 32 : threadIdx.x >= 16 ? 8 : 1);
  if (threadIdx.x == 32) sts64(smax, 0, 0);
  fence_async();
  __syncthreads();
  pdl_wait();
  const int blk = quarter * 4 + (h >> 3), cg = h & 7;
  auto unsafe = [&]() { const float2 m = lds64f(smax); return !(m.x * m.y <= 10000.f); };
  if (warp == AB_T / 32) {
    auto load_w = [&]() {
      mbar_expect(bW, 102400);
      for (int i = 0; i < 4; i++) bulk_load((i < 2 ? sK : sV) + (i & 1) * 25600, g_wb + cg * 6400 + i * 1600, 25600, bW);
    };
    if (elect()) {
      const uint32_t* gk = g_bqkv + (32 + h) * 256 * 96;
#pragma unroll 1
      for (int i = 0; i < 8; i++) {
        if (i >= AB_LW) mbar_wait(bars + 8 * (i - AB_LW), 0);
        mbar_expect(bars + 8 * i, 24576);
        bulk_load_last(sK + i * 12288, gk + i * 3072, 12288, bars + 8 * i);
        bulk_load_last(sV + i * 12288, gk + 32 * 256 * 96 + i * 3072, 12288, bars + 8 * i);
      }
    }
    __syncwarp();
    if (blockIdx.x < NSLOT) for (int i = lane; i < 512; i += 32) reinterpret_cast<uint4*>(pool_at(blockIdx.x * 8192))[i] = make_uint4(0, 0, 0, 0);
    if (blockIdx.x == 127) for (int i = lane; i < SY_N; i += 32) g_sync[i] = 0;
    if (p.next.w[0] && lane == 0) {
      for (int i = 0; i < AB_PF; i++) { const uint32_t t0 = clk32(); while (clk32() - t0 < (i ? AB_PFD : AB_PF0)) __nanosleep(200); prefetch_weights(p.next, i); }
    }
    __syncwarp();
    mbar_wait(bF, 0);
    const bool redo = unsafe();
    if (!redo && lane == 0) load_w();
    if (lane < 16) asm volatile("cp.async.bulk.prefetch.L2.global [%0], 1280;" :: "l"(g_x + ((blk * 16 + lane) * 40 + cg * 5) * 32) : "memory");
    __syncwarp();
    bar_sync(1, AB_T + 32);
    if (lane == 0) {
      ABT(!!p.out, 1);
      red_release(p.done + quarter * 32, 1);
      ABT(!!p.out, 2);
      if (redo) load_w();
      wait_count(p.done + quarter * 32, 32);
      fence_async_global();
      ABT(!!p.out, 3);
      for (int kb = 0; kb < 10; kb++) {
        const int i = kb < 6 ? kb : kb - 6;
        if (kb >= 6) mbar_wait(bE + 8 * i, 0);
        mbar_expect(bA + 8 * i, 16384);
        bulk_load(ring(i), g_of + (blk * 10 + kb) * 4096, 16384, bA + 8 * i);
      }
    }
    return;
  }
  float qmax = 0.f;
  const uint32_t one = opaque(0x3f803f80u + (threadIdx.x >> 10)), c0 = opaque(0x3ea83ea8u + (threadIdx.x >> 10));
#pragma unroll 1
  for (int pass = 0; pass < AB_PASS; pass++) {
    const int row0 = quarter * 512 + ((warp >> 2) * AB_PASS + pass) * 64 + (warp & 3) * 16;
    const uint32_t* gq = g_bqkv + (h * 256 + (row0 >> 3)) * 96 + lane;
    const uint32_t q0 = gq[0], q1 = gq[96], q2 = gq[32], q3 = gq[128];
    uint32_t q4 = gq[64], q5 = gq[160];
    const uint32_t z0 = gq[64 + 3 - (lane & 3)], z1 = gq[160 + 3 - (lane & 3)];
    {
      float n0 = sq2(q0) + sq2(q2) + sq2(q4), n1 = sq2(q1) + sq2(q3) + sq2(q5);
      n0 += __shfl_xor_sync(~0u, n0, 1); n1 += __shfl_xor_sync(~0u, n1, 1);
      n0 += __shfl_xor_sync(~0u, n0, 2); n1 += __shfl_xor_sync(~0u, n1, 2);
      qmax = (n0 > qmax || n0 != n0) ? n0 : qmax;
      qmax = (n1 > qmax || n1 != n1) ? n1 : qmax;
    }
    if (pass == AB_PASS - 1) {
      float kmax = 0.f;
#pragma unroll
      for (int i = 0; i < SEQ / AB_T; i++) {
        const int key = threadIdx.x + AB_T * i;
        const uint32_t a = sK + (key >> 3) * 384 + (key & 7) * 16;
        const uint4 x = lds128(a), y = lds128(a + 128);
        const uint2 z = lds64(a + 256);
        const float n = ((sq2(x.x) + sq2(x.y)) + (sq2(x.z) + sq2(x.w))) + ((sq2(y.x) + sq2(y.y)) + (sq2(y.z) + sq2(y.w))) + (sq2(z.x) + sq2(z.y));
        kmax = (n > kmax || n != n) ? n : kmax;
      }
      const uint32_t kb = __reduce_max_sync(~0u, __float_as_uint(kmax) & 0x7fffffffu), qb = __reduce_max_sync(~0u, __float_as_uint(qmax) & 0x7fffffffu);
      if (lane < 2) asm volatile("red.shared.max.u32 [%0], %1;" :: "r"(smax + 4 * lane), "r"(lane ? kb : qb) : "memory");
      __syncwarp();
    }
    if ((lane & 3) == 2) { q4 = 0xBF8043C0u; q5 = 0xBF8043C0u; }
    float o[12];
    auto desc = [](uint32_t lo, uint32_t hi) { uint64_t d; asm("mov.b64 %0, {%1, %2};" : "=l"(d) : "r"(lo), "r"(hi)); return d; };
    const uint32_t k0 = (uint32_t)mkdesc(sK, 128, 0, 0), k1 = (uint32_t)mkdesc(sK + 256, 0, 0, 0), v0 = (uint32_t)mkdesc(sV, 384, 0, 0);
    float sa[16], sb2[16];
    uint32_t pa[8], pb[8];
    auto qk = [&](float* s, uint32_t t) {
      wg_rs32_00(s, q0, q1, q2, q3, desc(k0 + t, 24), 0);
      wg_rs32_00(s, q4, q5, z0, z1, desc(k1 + t, 24), 1);
      wg_commit();
    };
    auto step = [&](float* s, uint32_t* pp, int g0, uint32_t t, uint32_t nx, int acc) {
      wg_wait<1>();
      reg_fence<16>(s);
#pragma unroll
      for (int i = 0; i < 8; i++) pp[i] = poly_group(g0 + (i >> 1)) ? ex2_pair(s[2 * i], s[2 * i + 1], one, c0) : pack2(ex2(s[2 * i]), ex2(s[2 * i + 1]));
      wg_fence();
      wg_rs24_01(o, pp[0], pp[1], pp[2], pp[3], desc(v0 + t, 8), acc);
      wg_rs24_01(o, pp[4], pp[5], pp[6], pp[7], desc(v0 + t + 48, 8), 1);
      qk(s, nx);
    };
    if (pass == 0) mbar_wait(bars, 0);
    wg_fence();
    qk(sa, 0);
    qk(sb2, 96);
#pragma unroll 1
    for (uint32_t t = 0; t < 64 * 96; t += AB_U * 96) {
      const uint32_t nx = t + AB_U * 96 < 64 * 96 ? t + AB_U * 96 : 0;
      if (pass == AB_PASS - 1 && t == 40 * 96 && lane == 0) mbar_arrive(bF);
#pragma unroll
      for (int u = 0; u < AB_U; u += 2) {
        if (u == AB_U - 2 && pass == 0) mbar_wait(bars + 8 * (nx / 768), 0);
        step(sa, pa, 0, t + u * 96, u + 2 < AB_U ? t + (u + 2) * 96 : nx, u | t);
        step(sb2, pb, 4, t + u * 96 + 96, (u + 2 < AB_U ? t + (u + 2) * 96 : nx) + 96, 1);
      }
    }
    wg_wait<0>();
    reg_fence<12>(o); reg_fence<16>(sa); reg_fence<16>(sb2);
    attn_b_store(o, h, row0, lane);
  }
  mbar_wait(bF, 0);
  if (unsafe())
#pragma unroll 1
  for (int pass = 0; pass < AB_PASS; pass++) {
    const int row0 = quarter * 512 + ((warp >> 2) * AB_PASS + pass) * 64 + (warp & 3) * 16;
    const uint32_t* gq = g_bqkv + (h * 256 + (row0 >> 3)) * 96 + lane;
    const uint32_t q0 = gq[0], q1 = gq[96], q2 = gq[32], q3 = gq[128], q4 = gq[64], q5 = gq[160];
    float o[12];
#pragma unroll
    for (int i = 0; i < 12; i++) o[i] = 0.f;
    float m0 = -INFINITY, m1 = -INFINITY;
#pragma unroll 1
    for (int kt = 0; kt < 32; kt++) {
      float s[32];
      const uint64_t dk = mkdesc(sK + kt * 3072, 128, 384, 0), dk2 = mkdesc(sK + kt * 3072 + 256, 0, 384, 0);
      wg_fence();
      wg_rs64_00(s, q0, q1, q2, q3, dk, 0);
      wg_rs64_00(s, q4, q5, 0, 0, dk2, 1);
      wg_commit();
      wg_wait<0>();
      reg_fence<32>(s); reg_fence<12>(o);
      float n0 = m0, n1 = m1;
#pragma unroll
      for (int jj = 0; jj < 8; jj++) { n0 = fmaxf(n0, fmaxf(s[4 * jj], s[4 * jj + 1])); n1 = fmaxf(n1, fmaxf(s[4 * jj + 2], s[4 * jj + 3])); }
      n0 = fmaxf(n0, __shfl_xor_sync(~0u, n0, 1)); n0 = fmaxf(n0, __shfl_xor_sync(~0u, n0, 2));
      n1 = fmaxf(n1, __shfl_xor_sync(~0u, n1, 1)); n1 = fmaxf(n1, __shfl_xor_sync(~0u, n1, 2));
      const float r0 = ex2(m0 - n0), r1 = ex2(m1 - n1);
      m0 = n0; m1 = n1;
#pragma unroll
      for (int jj = 0; jj < 3; jj++) { o[4 * jj] *= r0; o[4 * jj + 1] *= r0; o[4 * jj + 2] *= r1; o[4 * jj + 3] *= r1; }
      uint32_t pp[16];
#pragma unroll
      for (int jj = 0; jj < 8; jj++) {
        pp[2 * jj] = pack2(ex2(s[4 * jj] - m0), ex2(s[4 * jj + 1] - m0));
        pp[2 * jj + 1] = pack2(ex2(s[4 * jj + 2] - m1), ex2(s[4 * jj + 3] - m1));
      }
      const uint64_t dv = mkdesc(sV + kt * 3072, 384, 128, 0);
      wg_fence();
#pragma unroll
      for (int kk = 0; kk < 4; kk++) wg_rs24_01(o, pp[4 * kk], pp[4 * kk + 1], pp[4 * kk + 2], pp[4 * kk + 3], dv + kk * 48, 1);
      wg_commit();
    }
    wg_wait<0>();
    reg_fence<12>(o);
    attn_b_store(o, h, row0, lane);
  }
  ABT(!!p.out, 0);
  bar_arrive(1, AB_T + 32);
  if (warp >= 12) return;
  const int g = lane >> 2, c = lane & 3;
  const bool live = opaque(threadIdx.x) < 256;
  float d[40] = {};
  uint2* x = g_x + ((blk * 16 + warp * 2) * 40 + cg * 5) * 32 + lane;
  if (warp < 8) {
#pragma unroll
  for (int i = 0; i < 10; i++) {
    const int r = i / 5, u = i % 5;
    const float4 t = unpack4(x[(r * 40 + u) * 32]);
    d[8 * u + 2 * r] = t.x; d[8 * u + 2 * r + 1] = t.y; d[8 * u + 4 + 2 * r] = t.z; d[8 * u + 5 + 2 * r] = t.w;
  }
  mbar_wait(bW, 0);
  reg_fence<40>(d);
  ABT(!!p.out, 4);
#pragma unroll 1
  for (int kb = 0; kb < 10; kb++) {
    const int i = kb < 6 ? kb : kb - 6;
    mbar_wait(bA + 8 * i, kb >= 6);
    const uint64_t da = mkdesc(ring(i) + (warp >> 2) * 8192, 128, 1024, 0), db = mkdesc(kb < 5 ? sK + kb * 10240 : sV + (kb - 5) * 10240, 1280, 128, 0);
    wg_fence();
#pragma unroll
    for (int kk = 0; kk < 4; kk++) wg_ss80_01(d, da + kk * 16, db + kk * 160, 1);
    wg_commit();
    if (kb > 0 && kb < 5) { wg_wait<1>(); if (lane == 0) mbar_arrive(bE + 8 * (kb - 1)); }
  }
  wg_wait<0>();
  reg_fence<40>(d);
  }
  ABT(!!p.out, 5);
  if (p.out) {
    if (warp >= 8) return;
    const uint32_t stage = sK + 83968 + warp * 2560 + (warp < 4 ? 0 : 131328 - 10240);
#pragma unroll
    for (int u = 0; u < 5; u++)
      stsm4(stage + (lane & 15) * 160 + u * 32 + (lane >> 4) * 16, pack2(d[8 * u], d[8 * u + 1]), pack2(d[8 * u + 2], d[8 * u + 3]),
            pack2(d[8 * u + 4], d[8 * u + 5]), pack2(d[8 * u + 6], d[8 * u + 7]));
    __syncwarp();
    uint4* out = reinterpret_cast<uint4*>(p.out + (blk * 128 + warp * 16) * (DM / 2) + cg * 40);
#pragma unroll
    for (int i = 0; i < 5; i++) { const int e = i * 32 + lane, r = e / 10; out[r * (DM / 8) + e - r * 10] = lds128(stage + e * 16); }
  } else {
    float2* stat = g_stat + blk * 1024 + (warp & 7) * 16 + g;
    float mean[2], rs[2];
#pragma unroll
    for (int r = 0; r < 2; r++) {
      float t = 0.f, q = 0.f;
#pragma unroll
      for (int i = 0; i < 10; i++) t += d[4 * i + 2 * r] + d[4 * i + 2 * r + 1];
      t += __shfl_xor_sync(~0u, t, 1); t += __shfl_xor_sync(~0u, t, 2);
      t *= 1.f / 80;
#pragma unroll
      for (int i = 0; i < 10; i++) { const float a = d[4 * i + 2 * r] - t, b = d[4 * i + 2 * r + 1] - t; q += a * a + b * b; }
      q += __shfl_xor_sync(~0u, q, 1); q += __shfl_xor_sync(~0u, q, 2);
      if (c == r && live) asm volatile("st.relaxed.gpu.global.v2.b32 [%0], {%1, %2};" :: "l"(stat + cg * 128 + r * 8), "r"(__float_as_uint(t)), "r"(nz(__float_as_uint(q))) : "memory");
    }
#pragma unroll
    for (int i = 0; i < 10; i++) {
      const int r = i / 5, u = i % 5;
      if (live) x[(r * 40 + u) * 32] = make_uint2(pack2(d[8 * u + 2 * r], d[8 * u + 2 * r + 1]), pack2(d[8 * u + 4 + 2 * r], d[8 * u + 5 + 2 * r]));
    }
    ABT(0, 6);
    uint2 e[4];
    int n = 0;
    do {
#pragma unroll
      for (int i = 0; i < 4; i++)
        asm volatile("ld.relaxed.gpu.global.v2.b32 {%0, %1}, [%2];" : "=r"(e[i].x), "=r"(e[i].y) : "l"(stat + (2 * c + (i & 1)) * 128 + (i >> 1) * 8) : "memory");
      spin_guard(n);
    } while (__any_sync(~0u, min(min(e[0].y, e[1].y), min(e[2].y, e[3].y)) == 0 && live));
#pragma unroll
    for (int r = 0; r < 2; r++) {
      const float m0 = __uint_as_float(e[2 * r].x), m1 = __uint_as_float(e[2 * r + 1].x);
      float t = m0 + m1;
      t += __shfl_xor_sync(~0u, t, 1); t += __shfl_xor_sync(~0u, t, 2);
      t *= 0.125f;
      float q = __uint_as_float(e[2 * r].y) + __uint_as_float(e[2 * r + 1].y) + 80.f * ((m0 - t) * (m0 - t) + (m1 - t) * (m1 - t));
      q += __shfl_xor_sync(~0u, q, 1); q += __shfl_xor_sync(~0u, q, 2);
      mean[r] = t; rs[r] = rsqrtf(q * (1.f / DM) + 1e-5f);
    }
    ABT(0, 7);
    uint32_t w[2][5][2];
#pragma unroll
    for (int i = 0; i < 20; i++) w[i & 1][i >> 2][i >> 1 & 1] = pack2((d[2 * i] - mean[i & 1]) * rs[i & 1], (d[2 * i + 1] - mean[i & 1]) * rs[i & 1]);
    ln_store(w, blk * 8 + warp, cg * 5, live);
  }
  ABT(!!p.out, 8);
  TRACE(2);
}

typedef CUresult (*EncodeFn)(CUtensorMap*, CUtensorMapDataType, cuuint32_t, void*, const cuuint64_t*, const cuuint64_t*,
                             const cuuint32_t*, const cuuint32_t*, CUtensorMapInterleave, CUtensorMapSwizzle,
                             CUtensorMapL2promotion, CUtensorMapFloatOOBfill);

void make_map(EncodeFn enc, CUtensorMap* m, const void* ptr, int cols, int rows, int nb) {
  const cuuint64_t dims[3] = {(cuuint64_t)(nb ? 64 : cols), (cuuint64_t)rows, (cuuint64_t)cols / 64};
  const cuuint64_t strides[2] = {(cuuint64_t)cols * 2, 128};
  const cuuint32_t box[3] = {64, 32, (cuuint32_t)nb}, es[3] = {1, 1, 1};
  enc(m, CU_TENSOR_MAP_DATA_TYPE_BFLOAT16, nb ? 3 : 2, const_cast<void*>(ptr), dims, strides, box, es, CU_TENSOR_MAP_INTERLEAVE_NONE,
      CU_TENSOR_MAP_SWIZZLE_128B, CU_TENSOR_MAP_L2_PROMOTION_L2_128B, CU_TENSOR_MAP_FLOAT_OOB_FILL_NONE);
}
template <class... KA, class... A>
void launch(void (*kern)(KA...), int grid, int block, int smem, int cluster, bool pdl, A... args) {
  cudaFuncSetAttribute(kern, cudaFuncAttributeMaxDynamicSharedMemorySize, smem);
  cudaLaunchConfig_t cfg = {};
  cfg.gridDim = dim3(grid); cfg.blockDim = dim3(block); cfg.dynamicSmemBytes = smem; cfg.stream = cudaStreamPerThread;
  cudaLaunchAttribute at[2];
  int n = 0;
  if (cluster > 1) { at[n].id = cudaLaunchAttributeClusterDimension; at[n].val.clusterDim.x = cluster; at[n].val.clusterDim.y = 1; at[n].val.clusterDim.z = 1; n++; }
  if (pdl) { at[n].id = cudaLaunchAttributeProgrammaticStreamSerialization; at[n].val.programmaticStreamSerializationAllowed = 1; n++; }
  cfg.attrs = at; cfg.numAttrs = n;
  cudaLaunchKernelEx(&cfg, kern, args...);
}
template <class T> void* sym(T& s) { void* p = nullptr; cudaGetSymbolAddress(&p, s); return p; }

}

#define MODE(b) 0
extern "C" void kernel_launch(void* const* d_in, const int* in_sizes, int n_in, void* d_out, int out_size) {
  const __nv_bfloat16* x = (const __nv_bfloat16*)d_in[0];
  void* fn = nullptr; cudaDriverEntryPointQueryResult qr;
  cudaGetDriverEntryPoint("cuTensorMapEncodeTiled", &fn, cudaEnableDefault, &qr);
  EncodeFn enc = (EncodeFn)fn;

  ChainParams ch = {};
  PostParams op = {};
  for (int i = 0; i < 3; i++) {
    const cuuint64_t dims[3] = {HD, 128, 5}, strides[2] = {HD * 2, HD * 256};
    const cuuint32_t box[3] = {64, 128, 5}, es[3] = {1, 1, 1};
    enc(i == 0 ? &ch.wq : i == 1 ? &ch.wk : &ch.wv, CU_TENSOR_MAP_DATA_TYPE_BFLOAT16, 3, d_in[2 + i], dims, strides, box, es, CU_TENSOR_MAP_INTERLEAVE_NONE,
        CU_TENSOR_MAP_SWIZZLE_128B, W_PROMO, CU_TENSOR_MAP_FLOAT_OOB_FILL_NONE);
  }
  {
    const cuuint64_t dims[3] = {DM, HD, 7}, strides[2] = {DM * 2, 64};
    const cuuint32_t box[3] = {32, 64, 7}, es[3] = {1, 1, 1};
    enc(&ch.wo, CU_TENSOR_MAP_DATA_TYPE_BFLOAT16, 3, d_in[5], dims, strides, box, es, CU_TENSOR_MAP_INTERLEAVE_NONE,
        CU_TENSOR_MAP_SWIZZLE_64B, CU_TENSOR_MAP_L2_PROMOTION_L2_128B, CU_TENSOR_MAP_FLOAT_OOB_FILL_NONE);
  }
  ch.mem0 = (const __nv_bfloat16*)d_in[1];
  ch.pool = (uint8_t*)(((uintptr_t)sym(g_pool) + 8191) & ~(uintptr_t)8191); ch.kv = (uint8_t*)sym(g_kv); ch.xc = (const uint32_t*)sym(g_xc); ch.sync = (uint32_t*)sym(g_sync);
  ch.d1 = 0; ch.d1b = 0; ch.d2 = 0; ch.d2b = 0;
  make_map(enc, &op.wq, d_in[2], HD, DM, 3);
  make_map(enc, &op.wo, d_in[5], DM, HD, 5); make_map(enc, &op.wo2, d_in[5], DM, HD, 0);
  make_map(enc, &op.wb, d_in[8], 1920, DM, 5); make_map(enc, &op.wb2, d_in[8], 1920, DM, 0);
  op.gap = 17; op.share = 20; op.look = 20; op.gap2 = 0; op.pol = 1; op.slow_n = 8; op.slow_gap = 23;

  const Weights wa = {{(const uint8_t*)d_in[3], (const uint8_t*)d_in[4], (const uint8_t*)d_in[2], (const uint8_t*)d_in[5]}}, none = {};
  launch(first_kernel, 132, 384, 128 * 1024, 1, false, x, (const uint4*)d_in[9], wa);
  for (int layer = 0; layer < (MODE(4) ? 1 : 2); layer++) {
    ch.layer = ch.d2b = op.layer = layer;
    launch(chain_kernel, 96, 256, CH_SMEM, 3, true, ch);
    launch(post_kernel, MODE(3) ? 36 : 132, 384, OP_SMEM, 1, !MODE(1), op);
    const AbParams ab = {layer == 0 ? wa : none, (uint32_t*)sym(g_bo) + layer * 128, layer == 0 ? nullptr : (uint32_t*)d_out};
    launch(attn_b_kernel, 128, AB_T + 32, AB_SMEM, 1, true, ab);
  }
}
```

```cpp
#include <cuda_runtime.h>
#include <cuda_bf16.h>
#include <cuda.h>
#include <stdint.h>

namespace {

constexpr int SEQ = 2048, DM = 640, HD = 6144, NSEG = 64;
constexpr int SPIN_LIMIT = 1 << 20;

__device__ __align__(128) uint2 g_x[SEQ * DM / 4];
__device__ __align__(128) uint32_t g_of[SEQ * DM / 2];
__device__ __align__(128) uint4 g_wb[DM * DM / 8];
__device__ __align__(16) float2 g_stat[16 * 8 * 128];
__device__ uint32_t g_bo[8 * 32];
__device__ __align__(128) uint4 g_q[SEQ * HD / 8];
__device__ __align__(128) uint32_t g_o[SEQ * HD / 2];
constexpr int KV_BYTES = 5120, KV_M = 4096, KV_V = NSEG * KV_BYTES;
__device__ __align__(128) uint8_t g_kv[96 * 2 * NSEG * KV_BYTES];
__device__ __align__(128) uint32_t g_xc[SEQ * DM / 2];
#define OP_B4 7
#define OP_B8 10
#define OP_B16 16
#define QA_END 11
__host__ __device__ constexpr int op_split(int b) { return b < OP_B4 ? 2 : b < OP_B8 ? 4 : b < OP_B16 ? 8 : 16; }
#define AB_PF 3
#define AB_PF0 0
#define AB_PFD 5000
#define W_PROMO CU_TENSOR_MAP_L2_PROMOTION_L2_128B
#define OP_EARLY 1
#define ATT_LOOK 1
#define PR_FIN 1
#define PR_ATT 0
#define PR_OP 2
#define PRE_MAX PS
#define BQ_RUSH 16
#define OEF 0
#define BQ_HOLD 6
#define WEF 1
#define FK_REP 4
#define FK_PF 1
#define BQ_160 10
#define BQ_80 16
#define OP_160 14
__host__ __device__ constexpr int op_width(int b) { return b < OP_160 ? 320 : 160; }
__host__ __device__ constexpr int bq_width(int b) { return b < BQ_160 ? 320 : b < BQ_80 ? 160 : 80; }
__device__ __align__(128) uint2 g_part[16 * 16 * 16 * 40 * 32];
__device__ __align__(128) uint32_t g_xn[SEQ * DM / 2];
constexpr int SY_Q = 128, SY_T = 160, SY_QC = 192, SY_N = 193;
__device__ __align__(16) uint32_t g_sync[SY_N];
constexpr int NSLOT = 92;
__device__ uint32_t g_pool[(NSLOT + 2) * 2048];
__device__ int g_smpart[256], g_orient[NSLOT];
__device__ uint32_t g_smclk[256], g_smuse[256];
__device__ uint32_t g_bqkv[3 * 32 * 256 * 96];

#define ABT(L, i)
#define PST(i)
#define MODE_D(b) 0
#define DELAY(d)
#define XT(i)
#define MISS(k, n)
#define PRO(i)
#define TRACE(w)
#define ITEM(code, w)
#define TR(i, v)
#define TM(i)
#define TM1(i)
#define TMD(i, dep)
#define TMV(i, at, v)

__device__ __forceinline__ uint32_t gtime() { uint32_t c; asm volatile("mov.u32 %0, %%globaltimer_lo;" : "=r"(c) :: "memory"); return c; }
__device__ __forceinline__ uint32_t clk32() { uint32_t c; asm volatile("mov.u32 %0, %%clock;" : "=r"(c) :: "memory"); return c; }
__device__ __forceinline__ uint32_t s2u(const void* p) { return (uint32_t)__cvta_generic_to_shared(p); }
__device__ __forceinline__ uint32_t pack2(float a, float b) {
  uint32_t r; asm("cvt.rn.bf16x2.f32 %0, %1, %2;" : "=r"(r) : "f"(b), "f"(a)); return r; }
__device__ __forceinline__ float bf_lo(uint32_t w) { return __uint_as_float(w << 16); }
__device__ __forceinline__ float bf_hi(uint32_t w) { return __uint_as_float(w & 0xffff0000u); }
__device__ __forceinline__ uint2 pack4(float4 v) { return make_uint2(pack2(v.x, v.y), pack2(v.z, v.w)); }
__device__ __forceinline__ float4 unpack4(uint2 w) { return make_float4(bf_lo(w.x), bf_hi(w.x), bf_lo(w.y), bf_hi(w.y)); }
__device__ __forceinline__ float ex2(float x) { float y; asm("ex2.approx.ftz.f32 %0, %1;" : "=f"(y) : "f"(x)); return y; }

__device__ __forceinline__ void mbar_init(uint32_t bar, uint32_t n) {
  asm volatile("mbarrier.init.shared::cta.b64 [%0], %1;" :: "r"(bar), "r"(n) : "memory"); }
__device__ __forceinline__ void mbar_expect(uint32_t bar, uint32_t bytes) {
  asm volatile("mbarrier.arrive.expect_tx.shared::cta.b64 _, [%0], %1;" :: "r"(bar), "r"(bytes) : "memory"); }
__device__ __forceinline__ void mbar_arrive(uint32_t bar) {
  asm volatile("mbarrier.arrive.shared::cta.b64 _, [%0];" :: "r"(bar) : "memory"); }
__device__ __forceinline__ void mbar_wait(uint32_t bar, uint32_t ph) {
  asm volatile("{.reg .pred p; .reg .u32 n; mov.u32 n, 0;\n"
               "W: mbarrier.try_wait.parity.shared::cta.b64 p, [%0], %1; @p bra D;\n"
               "add.u32 n, n, 1; setp.gt.u32 p, n, %2; @p trap; bra W;\n"
               "D: }" :: "r"(bar), "r"(ph), "n"(SPIN_LIMIT) : "memory");
}
__device__ __forceinline__ void mbar_wait_cluster(uint32_t bar, uint32_t ph) {
  asm volatile("{.reg .pred p; .reg .u32 n; mov.u32 n, 0;\n"
               "W: mbarrier.try_wait.parity.acquire.cluster.shared::cta.b64 p, [%0], %1; @p bra D;\n"
               "add.u32 n, n, 1; setp.gt.u32 p, n, %2; @p trap; bra W;\n"
               "D: }" :: "r"(bar), "r"(ph), "n"(SPIN_LIMIT) : "memory");
}
__device__ __forceinline__ void spin_guard(int& n) {
  asm volatile("{.reg .pred p; add.s32 %0, %0, 1; setp.gt.s32 p, %0, %1; @p trap;}" : "+r"(n) : "n"(SPIN_LIMIT));
}
__device__ __forceinline__ void pdl_wait() { asm volatile("griddepcontrol.wait;" ::: "memory"); TRACE(1); }
__device__ __forceinline__ void pdl_launch() { asm volatile("griddepcontrol.launch_dependents;" ::: "memory"); }
__device__ __forceinline__ uint32_t ld_acquire(const uint32_t* p) { uint32_t v; asm volatile("ld.acquire.gpu.global.u32 %0, [%1];" : "=r"(v) : "l"(p) : "memory"); return v; }
__device__ __forceinline__ void red_release(uint32_t* p, uint32_t v) { asm volatile("red.release.gpu.global.add.u32 [%0], %1;" :: "l"(p), "r"(v) : "memory"); }
__device__ __forceinline__ void red_relaxed(uint32_t* p, uint32_t v) { asm volatile("red.relaxed.gpu.global.add.u32 [%0], %1;" :: "l"(p), "r"(v) : "memory"); }
__device__ __forceinline__ void fence_async_global() { asm volatile("fence.proxy.async.global;" ::: "memory"); }
__device__ __forceinline__ void fence_async() { asm volatile("fence.proxy.async.shared::cta;" ::: "memory"); }
__device__ __forceinline__ void bar_sync(int id, int n) { asm volatile("bar.sync %0, %1;" :: "r"(id), "r"(n) : "memory"); }
__device__ __forceinline__ void bar_arrive(int id, int n) { asm volatile("bar.arrive %0, %1;" :: "r"(id), "r"(n) : "memory"); }
__device__ __forceinline__ void tma_load(uint32_t dst, const CUtensorMap* m, int c0, int c1, uint32_t bar) {
  asm volatile("cp.async.bulk.tensor.2d.shared::cluster.global.mbarrier::complete_tx::bytes [%0], [%1, {%3, %4}], [%2];"
               :: "r"(dst), "l"(m), "r"(bar), "r"(c0), "r"(c1) : "memory"); }
template <bool STREAM = false>
__device__ __forceinline__ void tma_load3(uint32_t dst, const CUtensorMap* m, int c0, int c1, uint32_t bar) {
  if (STREAM)
    asm volatile("{.reg .b64 pol; createpolicy.fractional.L2::evict_first.b64 pol, 1.0;\n"
                 "cp.async.bulk.tensor.3d.shared::cluster.global.mbarrier::complete_tx::bytes.L2::cache_hint [%0], [%1, {%3, %4, 0}], [%2], pol;}"
                 :: "r"(dst), "l"(m), "r"(bar), "r"(c0), "r"(c1) : "memory");
  else
  asm volatile("cp.async.bulk.tensor.3d.shared::cluster.global.mbarrier::complete_tx::bytes [%0], [%1, {%3, %4, 0}], [%2];"
               :: "r"(dst), "l"(m), "r"(bar), "r"(c0), "r"(c1) : "memory"); }
__device__ __forceinline__ void tma_load3z(uint32_t dst, const CUtensorMap* m, int c1, int c2, uint32_t bar) {
  asm volatile("cp.async.bulk.tensor.3d.shared::cluster.global.mbarrier::complete_tx::bytes [%0], [%1, {0, %3, %4}], [%2];"
               :: "r"(dst), "l"(m), "r"(bar), "r"(c1), "r"(c2) : "memory"); }
__device__ __forceinline__ void tma_store(const CUtensorMap* m, uint32_t src, int c0, int c1) {
  asm volatile("cp.async.bulk.tensor.2d.global.shared::cta.bulk_group [%0, {%2, %3}], [%1];"
               :: "l"(m), "r"(src), "r"(c0), "r"(c1) : "memory"); }
__device__ __forceinline__ void tma_store_stream(const CUtensorMap* m, uint32_t src, int c0, int c1) {
  asm volatile("{.reg .b64 pol; createpolicy.fractional.L2::evict_first.b64 pol, 1.0;\n"
               "cp.async.bulk.tensor.2d.global.shared::cta.bulk_group.L2::cache_hint [%0, {%2, %3}], [%1], pol;}"
               :: "l"(m), "r"(src), "r"(c0), "r"(c1) : "memory"); }
__device__ __forceinline__ void bulk_load(uint32_t dst, const void* src, uint32_t bytes, uint32_t bar) {
  asm volatile("cp.async.bulk.shared::cluster.global.mbarrier::complete_tx::bytes [%0], [%1], %2, [%3];"
               :: "r"(dst), "l"(src), "r"(bytes), "r"(bar) : "memory"); }
__device__ __forceinline__ void bulk_load_last(uint32_t dst, const void* src, uint32_t bytes, uint32_t bar) {
  asm volatile("{.reg .b64 pol; createpolicy.fractional.L2::evict_first.b64 pol, 1.0;\n"
               "cp.async.bulk.shared::cluster.global.mbarrier::complete_tx::bytes.L2::cache_hint [%0], [%1], %2, [%3], pol;}"
               :: "r"(dst), "l"(src), "r"(bytes), "r"(bar) : "memory"); }
__device__ __forceinline__ void tma_load_last(uint32_t dst, const CUtensorMap* m, int c0, int c1, uint32_t bar) {
  asm volatile("{.reg .b64 pol; createpolicy.fractional.L2::evict_first.b64 pol, 1.0;\n"
               "cp.async.bulk.tensor.2d.shared::cluster.global.mbarrier::complete_tx::bytes.L2::cache_hint [%0], [%1, {%3, %4}], [%2], pol;}"
               :: "r"(dst), "l"(m), "r"(bar), "r"(c0), "r"(c1) : "memory"); }
__device__ __forceinline__ void bulk_send(uint32_t dst, uint32_t src, uint32_t bytes, uint32_t bar) {
  asm volatile("cp.async.bulk.shared::cluster.shared::cta.mbarrier::complete_tx::bytes [%0], [%1], %2, [%3];"
               :: "r"(dst), "r"(src), "r"(bytes), "r"(bar) : "memory"); }
__device__ __forceinline__ void bulk_store(void* dst, uint32_t src, uint32_t bytes) {
  asm volatile("cp.async.bulk.global.shared::cta.bulk_group [%0], [%1], %2;" :: "l"(dst), "r"(src), "r"(bytes) : "memory"); }
__device__ __forceinline__ void bulk_commit() { asm volatile("cp.async.bulk.commit_group;" ::: "memory"); }
template <int N> __device__ __forceinline__ void bulk_wait_read() { asm volatile("cp.async.bulk.wait_group.read %0;" :: "n"(N) : "memory"); }
template <int N> __device__ __forceinline__ void bulk_wait() { asm volatile("cp.async.bulk.wait_group %0;" :: "n"(N) : "memory"); }

__device__ __forceinline__ uint64_t mkdesc(uint32_t addr, uint32_t lbo, uint32_t sbo, uint32_t sw) {
  return (uint64_t)((addr & 0x3FFFF) >> 4) | ((uint64_t)(lbo >> 4) << 16) | ((uint64_t)(sbo >> 4) << 32) | ((uint64_t)sw << 62); }
__device__ __forceinline__ void wg_fence() { asm volatile("wgmma.fence.sync.aligned;" ::: "memory"); }
__device__ __forceinline__ void wg_commit() { asm volatile("wgmma.commit_group.sync.aligned;" ::: "memory"); }
template <int N> __device__ __forceinline__ void wg_wait() { asm volatile("wgmma.wait_group.sync.aligned %0;" :: "n"(N) : "memory"); }
template <int N> __device__ __forceinline__ void reg_fence(float* d) {
#pragma unroll
  for (int i = 0; i < N; i++) asm volatile("" : "+f"(d[i]) :: "memory");
}

__device__ __forceinline__ void mma16(float* d, uint32_t a0, uint32_t a1, uint32_t a2, uint32_t a3, uint32_t b0, uint32_t b1) {
  asm volatile("mma.sync.aligned.m16n8k16.row.col.f32.bf16.bf16.f32 {%0,%1,%2,%3},{%4,%5,%6,%7},{%8,%9},{%0,%1,%2,%3};"
               : "+f"(d[0]), "+f"(d[1]), "+f"(d[2]), "+f"(d[3]) : "r"(a0), "r"(a1), "r"(a2), "r"(a3), "r"(b0), "r"(b1)); }
__device__ __forceinline__ void mma8(float* d, uint32_t a0, uint32_t a1, uint32_t b0) {
  asm volatile("mma.sync.aligned.m16n8k8.row.col.f32.bf16.bf16.f32 {%0,%1,%2,%3},{%4,%5},{%6},{%0,%1,%2,%3};"
               : "+f"(d[0]), "+f"(d[1]), "+f"(d[2]), "+f"(d[3]) : "r"(a0), "r"(a1), "r"(b0)); }
__device__ __forceinline__ void ldsm4(uint32_t* r, uint32_t a) {
  asm volatile("ldmatrix.sync.aligned.m8n8.x4.shared.b16 {%0,%1,%2,%3},[%4];" : "=r"(r[0]), "=r"(r[1]), "=r"(r[2]), "=r"(r[3]) : "r"(a) : "memory"); }
__device__ __forceinline__ void ldsm4t(uint32_t* r, uint32_t a) {
  asm volatile("ldmatrix.sync.aligned.m8n8.x4.trans.shared.b16 {%0,%1,%2,%3},[%4];" : "=r"(r[0]), "=r"(r[1]), "=r"(r[2]), "=r"(r[3]) : "r"(a) : "memory"); }
__device__ __forceinline__ void ldsm2(uint32_t* r, uint32_t a) {
  asm volatile("ldmatrix.sync.aligned.m8n8.x2.shared.b16 {%0,%1},[%2];" : "=r"(r[0]), "=r"(r[1]) : "r"(a) : "memory"); }
__device__ __forceinline__ void stsm4(uint32_t a, uint32_t r0, uint32_t r1, uint32_t r2, uint32_t r3) {
  asm volatile("stmatrix.sync.aligned.m8n8.x4.shared.b16 [%0], {%1,%2,%3,%4};" :: "r"(a), "r"(r0), "r"(r1), "r"(r2), "r"(r3) : "memory"); }
__device__ __forceinline__ void stsm2t(uint32_t a, uint32_t r0, uint32_t r1) {
  asm volatile("stmatrix.sync.aligned.m8n8.x2.trans.shared.b16 [%0], {%1,%2};" :: "r"(a), "r"(r0), "r"(r1) : "memory"); }
__device__ __forceinline__ void stsm4t(uint32_t a, uint32_t r0, uint32_t r1, uint32_t r2, uint32_t r3) {
  asm volatile("stmatrix.sync.aligned.m8n8.x4.trans.shared.b16 [%0], {%1,%2,%3,%4};" :: "r"(a), "r"(r0), "r"(r1), "r"(r2), "r"(r3) : "memory"); }
__device__ __forceinline__ void st_async128(uint32_t a, uint4 v, uint32_t bar) {
  asm volatile("st.async.shared::cluster.mbarrier::complete_tx::bytes.v4.b32 [%0], {%1,%2,%3,%4}, [%5];" :: "r"(a), "r"(v.x), "r"(v.y), "r"(v.z), "r"(v.w), "r"(bar) : "memory"); }
__device__ __forceinline__ void sts32(uint32_t a, uint32_t v) { asm volatile("st.shared.b32 [%0], %1;" :: "r"(a), "r"(v) : "memory"); }
__device__ __forceinline__ void sts64f(uint32_t a, float x, float y) { asm volatile("st.shared.v2.f32 [%0], {%1,%2};" :: "r"(a), "f"(x), "f"(y) : "memory"); }
__device__ __forceinline__ void sts128(uint32_t a, uint4 v) {
  asm volatile("st.shared.v4.b32 [%0], {%1,%2,%3,%4};" :: "r"(a), "r"(v.x), "r"(v.y), "r"(v.z), "r"(v.w) : "memory"); }
__device__ __forceinline__ void sts128f(uint32_t a, float x, float y, float z, float w) {
  asm volatile("st.shared.v4.f32 [%0], {%1,%2,%3,%4};" :: "r"(a), "f"(x), "f"(y), "f"(z), "f"(w) : "memory"); }
__device__ __forceinline__ float lds32f(uint32_t a) { float v; asm volatile("ld.shared.f32 %0, [%1];" : "=f"(v) : "r"(a) : "memory"); return v; }
__device__ __forceinline__ float2 lds64f(uint32_t a) { float2 v; asm volatile("ld.shared.v2.f32 {%0,%1}, [%2];" : "=f"(v.x), "=f"(v.y) : "r"(a) : "memory"); return v; }
__device__ __forceinline__ float4 lds128f(uint32_t a) {
  float4 v; asm volatile("ld.shared.v4.f32 {%0,%1,%2,%3}, [%4];" : "=f"(v.x), "=f"(v.y), "=f"(v.z), "=f"(v.w) : "r"(a) : "memory"); return v; }
__device__ __forceinline__ uint4 lds128(uint32_t a) {
  uint4 v; asm volatile("ld.shared.v4.b32 {%0,%1,%2,%3}, [%4];" : "=r"(v.x), "=r"(v.y), "=r"(v.z), "=r"(v.w) : "r"(a) : "memory"); return v; }
__device__ __forceinline__ uint4 ldg_strong128(const void* p) {
  uint4 v; asm volatile("ld.relaxed.gpu.global.v4.u32 {%0,%1,%2,%3}, [%4];" : "=r"(v.x), "=r"(v.y), "=r"(v.z), "=r"(v.w) : "l"(p) : "memory"); return v; }
__device__ __forceinline__ void stg_strong32(void* p, uint32_t v) { asm volatile("st.relaxed.gpu.global.u32 [%0], %1;" :: "l"(p), "r"(v) : "memory"); }
__device__ __forceinline__ void stg_strong16(void* p, uint32_t v) { asm volatile("st.relaxed.gpu.global.u16 [%0], %1;" :: "l"(p), "h"((uint16_t)v) : "memory"); }
__device__ __forceinline__ void stg_strong128(void* p, uint4 v) {
  asm volatile("st.relaxed.gpu.global.v4.u32 [%0], {%1,%2,%3,%4};" :: "l"(p), "r"(v.x), "r"(v.y), "r"(v.z), "r"(v.w) : "memory"); }
__device__ __forceinline__ uint32_t mapa(uint32_t a, uint32_t r) {
  uint32_t o; asm("mapa.shared::cluster.u32 %0, %1, %2;" : "=r"(o) : "r"(a), "r"(r)); return o; }
__device__ __forceinline__ void st_async2f(uint32_t a, float x, float y, uint32_t bar) {
  asm volatile("st.async.shared::cluster.mbarrier::complete_tx::bytes.v2.f32 [%0], {%1,%2}, [%3];" :: "r"(a), "f"(x), "f"(y), "r"(bar) : "memory"); }
__device__ __forceinline__ void st_async32(uint32_t a, uint32_t x, uint32_t bar) {
  asm volatile("st.async.shared::cluster.mbarrier::complete_tx::bytes.b32 [%0], %1, [%2];" :: "r"(a), "r"(x), "r"(bar) : "memory"); }
__device__ __forceinline__ uint32_t lds32(uint32_t a) { uint32_t v; asm volatile("ld.shared.b32 %0, [%1];" : "=r"(v) : "r"(a) : "memory"); return v; }
__device__ __forceinline__ void st_async64(uint32_t a, uint32_t x, uint32_t y, uint32_t bar) {
  asm volatile("st.async.shared::cluster.mbarrier::complete_tx::bytes.v2.b32 [%0], {%1,%2}, [%3];" :: "r"(a), "r"(x), "r"(y), "r"(bar) : "memory"); }
__device__ __forceinline__ uint2 lds64(uint32_t a) { uint2 v; asm volatile("ld.shared.v2.b32 {%0,%1}, [%2];" : "=r"(v.x), "=r"(v.y) : "r"(a) : "memory"); return v; }
__device__ __forceinline__ void sts64(uint32_t a, uint32_t x, uint32_t y) { asm volatile("st.shared.v2.b32 [%0], {%1,%2};" :: "r"(a), "r"(x), "r"(y) : "memory"); }
__device__ __forceinline__ uint32_t ldg_strong32(const void* p) { uint32_t v; asm volatile("ld.relaxed.gpu.global.u32 %0, [%1];" : "=r"(v) : "l"(p) : "memory"); return v; }
__device__ __forceinline__ uint32_t transpose8(uint32_t x) { uint32_t r; asm volatile("movmatrix.sync.aligned.m8n8.trans.b16 %0, %1;" : "=r"(r) : "r"(x)); return r; }
__device__ __forceinline__ uint32_t hadd2(uint32_t a, uint32_t b) { uint32_t r; asm("add.rn.bf16x2 %0, %1, %2;" : "=r"(r) : "r"(a), "r"(b)); return r; }
__device__ __forceinline__ uint32_t min4(uint4 v) { return min(__vimin3_u32(v.x, v.y, v.z), v.w); }

__device__ __forceinline__ void wg_ss192_01(float* d, uint64_t da, uint64_t db, int sd) {
  asm volatile("{.reg .pred p; setp.ne.b32 p, %98, 0;\n"
    "wgmma.mma_async.sync.aligned.m64n192k16.f32.bf16.bf16 {%0,%1,%2,%3,%4,%5,%6,%7,%8,%9,%10,%11,%12,%13,%14,%15,%16,%17,%18,%19,%20,%21,%22,%23,%24,%25,%26,%27,%28,%29,%30,%31,%32,%33,%34,%35,%36,%37,%38,%39,%40,%41,%42,%43,%44,%45,%46,%47,%48,%49,%50,%51,%52,%53,%54,%55,%56,%57,%58,%59,%60,%61,%62,%63,%64,%65,%66,%67,%68,%69,%70,%71,%72,%73,%74,%75,%76,%77,%78,%79,%80,%81,%82,%83,%84,%85,%86,%87,%88,%89,%90,%91,%92,%93,%94,%95}, %96, %97, p, 1, 1, 0, 1;}"
    : "+f"(d[0]),"+f"(d[1]),"+f"(d[2]),"+f"(d[3]),"+f"(d[4]),"+f"(d[5]),"+f"(d[6]),"+f"(d[7]),"+f"(d[8]),"+f"(d[9]),"+f"(d[10]),"+f"(d[11]),"+f"(d[12]),"+f"(d[13]),"+f"(d[14]),"+f"(d[15]),"+f"(d[16]),"+f"(d[17]),"+f"(d[18]),"+f"(d[19]),"+f"(d[20]),"+f"(d[21]),"+f"(d[22]),"+f"(d[23]),"+f"(d[24]),"+f"(d[25]),"+f"(d[26]),"+f"(d[27]),"+f"(d[28]),"+f"(d[29]),"+f"(d[30]),"+f"(d[31]),"+f"(d[32]),"+f"(d[33]),"+f"(d[34]),"+f"(d[35]),"+f"(d[36]),"+f"(d[37]),"+f"(d[38]),"+f"(d[39]),"+f"(d[40]),"+f"(d[41]),"+f"(d[42]),"+f"(d[43]),"+f"(d[44]),"+f"(d[45]),"+f"(d[46]),"+f"(d[47]),"+f"(d[48]),"+f"(d[49]),"+f"(d[50]),"+f"(d[51]),"+f"(d[52]),"+f"(d[53]),"+f"(d[54]),"+f"(d[55]),"+f"(d[56]),"+f"(d[57]),"+f"(d[58]),"+f"(d[59]),"+f"(d[60]),"+f"(d[61]),"+f"(d[62]),"+f"(d[63]),"+f"(d[64]),"+f"(d[65]),"+f"(d[66]),"+f"(d[67]),"+f"(d[68]),"+f"(d[69]),"+f"(d[70]),"+f"(d[71]),"+f"(d[72]),"+f"(d[73]),"+f"(d[74]),"+f"(d[75]),"+f"(d[76]),"+f"(d[77]),"+f"(d[78]),"+f"(d[79]),"+f"(d[80]),"+f"(d[81]),"+f"(d[82]),"+f"(d[83]),"+f"(d[84]),"+f"(d[85]),"+f"(d[86]),"+f"(d[87]),"+f"(d[88]),"+f"(d[89]),"+f"(d[90]),"+f"(d[91]),"+f"(d[92]),"+f"(d[93]),"+f"(d[94]),"+f"(d[95])
    : "l"(da), "l"(db), "r"(sd));
}
__device__ __forceinline__ void wg_ss128_01(float* d, uint64_t da, uint64_t db, int sd) {
  asm volatile("{.reg .pred p; setp.ne.b32 p, %66, 0;\n"
    "wgmma.mma_async.sync.aligned.m64n128k16.f32.bf16.bf16 {%0,%1,%2,%3,%4,%5,%6,%7,%8,%9,%10,%11,%12,%13,%14,%15,%16,%17,%18,%19,%20,%21,%22,%23,%24,%25,%26,%27,%28,%29,%30,%31,%32,%33,%34,%35,%36,%37,%38,%39,%40,%41,%42,%43,%44,%45,%46,%47,%48,%49,%50,%51,%52,%53,%54,%55,%56,%57,%58,%59,%60,%61,%62,%63}, %64, %65, p, 1, 1, 0, 1;}"
    : "+f"(d[0]),"+f"(d[1]),"+f"(d[2]),"+f"(d[3]),"+f"(d[4]),"+f"(d[5]),"+f"(d[6]),"+f"(d[7]),"+f"(d[8]),"+f"(d[9]),"+f"(d[10]),"+f"(d[11]),"+f"(d[12]),"+f"(d[13]),"+f"(d[14]),"+f"(d[15]),"+f"(d[16]),"+f"(d[17]),"+f"(d[18]),"+f"(d[19]),"+f"(d[20]),"+f"(d[21]),"+f"(d[22]),"+f"(d[23]),"+f"(d[24]),"+f"(d[25]),"+f"(d[26]),"+f"(d[27]),"+f"(d[28]),"+f"(d[29]),"+f"(d[30]),"+f"(d[31]),"+f"(d[32]),"+f"(d[33]),"+f"(d[34]),"+f"(d[35]),"+f"(d[36]),"+f"(d[37]),"+f"(d[38]),"+f"(d[39]),"+f"(d[40]),"+f"(d[41]),"+f"(d[42]),"+f"(d[43]),"+f"(d[44]),"+f"(d[45]),"+f"(d[46]),"+f"(d[47]),"+f"(d[48]),"+f"(d[49]),"+f"(d[50]),"+f"(d[51]),"+f"(d[52]),"+f"(d[53]),"+f"(d[54]),"+f"(d[55]),"+f"(d[56]),"+f"(d[57]),"+f"(d[58]),"+f"(d[59]),"+f"(d[60]),"+f"(d[61]),"+f"(d[62]),"+f"(d[63])
    : "l"(da), "l"(db), "r"(sd));
}
__device__ __forceinline__ void wg_ss160_01(float* d, uint64_t da, uint64_t db, int sd) {
  asm volatile("{.reg .pred p; setp.ne.b32 p, %82, 0;\n"
    "wgmma.mma_async.sync.aligned.m64n160k16.f32.bf16.bf16 {%0,%1,%2,%3,%4,%5,%6,%7,%8,%9,%10,%11,%12,%13,%14,%15,%16,%17,%18,%19,%20,%21,%22,%23,%24,%25,%26,%27,%28,%29,%30,%31,%32,%33,%34,%35,%36,%37,%38,%39,%40,%41,%42,%43,%44,%45,%46,%47,%48,%49,%50,%51,%52,%53,%54,%55,%56,%57,%58,%59,%60,%61,%62,%63,%64,%65,%66,%67,%68,%69,%70,%71,%72,%73,%74,%75,%76,%77,%78,%79}, %80, %81, p, 1, 1, 0, 1;}"
    : "+f"(d[0]),"+f"(d[1]),"+f"(d[2]),"+f"(d[3]),"+f"(d[4]),"+f"(d[5]),"+f"(d[6]),"+f"(d[7]),"+f"(d[8]),"+f"(d[9]),"+f"(d[10]),"+f"(d[11]),"+f"(d[12]),"+f"(d[13]),"+f"(d[14]),"+f"(d[15]),"+f"(d[16]),"+f"(d[17]),"+f"(d[18]),"+f"(d[19]),"+f"(d[20]),"+f"(d[21]),"+f"(d[22]),"+f"(d[23]),"+f"(d[24]),"+f"(d[25]),"+f"(d[26]),"+f"(d[27]),"+f"(d[28]),"+f"(d[29]),"+f"(d[30]),"+f"(d[31]),"+f"(d[32]),"+f"(d[33]),"+f"(d[34]),"+f"(d[35]),"+f"(d[36]),"+f"(d[37]),"+f"(d[38]),"+f"(d[39]),"+f"(d[40]),"+f"(d[41]),"+f"(d[42]),"+f"(d[43]),"+f"(d[44]),"+f"(d[45]),"+f"(d[46]),"+f"(d[47]),"+f"(d[48]),"+f"(d[49]),"+f"(d[50]),"+f"(d[51]),"+f"(d[52]),"+f"(d[53]),"+f"(d[54]),"+f"(d[55]),"+f"(d[56]),"+f"(d[57]),"+f"(d[58]),"+f"(d[59]),"+f"(d[60]),"+f"(d[61]),"+f"(d[62]),"+f"(d[63]),"+f"(d[64]),"+f"(d[65]),"+f"(d[66]),"+f"(d[67]),"+f"(d[68]),"+f"(d[69]),"+f"(d[70]),"+f"(d[71]),"+f"(d[72]),"+f"(d[73]),"+f"(d[74]),"+f"(d[75]),"+f"(d[76]),"+f"(d[77]),"+f"(d[78]),"+f"(d[79])
    : "l"(da), "l"(db), "r"(sd));
}
__device__ __forceinline__ void wg_ss80_01(float* d, uint64_t da, uint64_t db, int sd) {
  asm volatile("{.reg .pred p; setp.ne.b32 p, %42, 0;\n"
    "wgmma.mma_async.sync.aligned.m64n80k16.f32.bf16.bf16 {%0,%1,%2,%3,%4,%5,%6,%7,%8,%9,%10,%11,%12,%13,%14,%15,%16,%17,%18,%19,%20,%21,%22,%23,%24,%25,%26,%27,%28,%29,%30,%31,%32,%33,%34,%35,%36,%37,%38,%39}, %40, %41, p, 1, 1, 0, 1;}"
    : "+f"(d[0]),"+f"(d[1]),"+f"(d[2]),"+f"(d[3]),"+f"(d[4]),"+f"(d[5]),"+f"(d[6]),"+f"(d[7]),"+f"(d[8]),"+f"(d[9]),"+f"(d[10]),"+f"(d[11]),"+f"(d[12]),"+f"(d[13]),"+f"(d[14]),"+f"(d[15]),"+f"(d[16]),"+f"(d[17]),"+f"(d[18]),"+f"(d[19]),"+f"(d[20]),"+f"(d[21]),"+f"(d[22]),"+f"(d[23]),"+f"(d[24]),"+f"(d[25]),"+f"(d[26]),"+f"(d[27]),"+f"(d[28]),"+f"(d[29]),"+f"(d[30]),"+f"(d[31]),"+f"(d[32]),"+f"(d[33]),"+f"(d[34]),"+f"(d[35]),"+f"(d[36]),"+f"(d[37]),"+f"(d[38]),"+f"(d[39])
    : "l"(da), "l"(db), "r"(sd));
}
__device__ __forceinline__ void wg_rs32_00(float* d, uint32_t a0, uint32_t a1, uint32_t a2, uint32_t a3, uint64_t db, int sd) {
  asm volatile("{.reg .pred p; setp.ne.b32 p, %21, 0;\n"
    "wgmma.mma_async.sync.aligned.m64n32k16.f32.bf16.bf16 {%0,%1,%2,%3,%4,%5,%6,%7,%8,%9,%10,%11,%12,%13,%14,%15}, {%16,%17,%18,%19}, %20, p, 1, 1, 0;}"
    : "+f"(d[0]),"+f"(d[1]),"+f"(d[2]),"+f"(d[3]),"+f"(d[4]),"+f"(d[5]),"+f"(d[6]),"+f"(d[7]),"+f"(d[8]),"+f"(d[9]),"+f"(d[10]),"+f"(d[11]),"+f"(d[12]),"+f"(d[13]),"+f"(d[14]),"+f"(d[15])
    : "r"(a0), "r"(a1), "r"(a2), "r"(a3), "l"(db), "r"(sd));
}
__device__ __forceinline__ void wg_rs64_00(float* d, uint32_t a0, uint32_t a1, uint32_t a2, uint32_t a3, uint64_t db, int sd) {
  asm volatile("{.reg .pred p; setp.ne.b32 p, %37, 0;\n"
    "wgmma.mma_async.sync.aligned.m64n64k16.f32.bf16.bf16 {%0,%1,%2,%3,%4,%5,%6,%7,%8,%9,%10,%11,%12,%13,%14,%15,%16,%17,%18,%19,%20,%21,%22,%23,%24,%25,%26,%27,%28,%29,%30,%31}, {%32,%33,%34,%35}, %36, p, 1, 1, 0;}"
    : "+f"(d[0]),"+f"(d[1]),"+f"(d[2]),"+f"(d[3]),"+f"(d[4]),"+f"(d[5]),"+f"(d[6]),"+f"(d[7]),"+f"(d[8]),"+f"(d[9]),"+f"(d[10]),"+f"(d[11]),"+f"(d[12]),"+f"(d[13]),"+f"(d[14]),"+f"(d[15]),"+f"(d[16]),"+f"(d[17]),"+f"(d[18]),"+f"(d[19]),"+f"(d[20]),"+f"(d[21]),"+f"(d[22]),"+f"(d[23]),"+f"(d[24]),"+f"(d[25]),"+f"(d[26]),"+f"(d[27]),"+f"(d[28]),"+f"(d[29]),"+f"(d[30]),"+f"(d[31])
    : "r"(a0), "r"(a1), "r"(a2), "r"(a3), "l"(db), "r"(sd));
}
__device__ __forceinline__ void wg_rs24_01(float* d, uint32_t a0, uint32_t a1, uint32_t a2, uint32_t a3, uint64_t db, int sd) {
  asm volatile("{.reg .pred p; setp.ne.b32 p, %17, 0;\n"
    "wgmma.mma_async.sync.aligned.m64n24k16.f32.bf16.bf16 {%0,%1,%2,%3,%4,%5,%6,%7,%8,%9,%10,%11}, {%12,%13,%14,%15}, %16, p, 1, 1, 1;}"
    : "+f"(d[0]),"+f"(d[1]),"+f"(d[2]),"+f"(d[3]),"+f"(d[4]),"+f"(d[5]),"+f"(d[6]),"+f"(d[7]),"+f"(d[8]),"+f"(d[9]),"+f"(d[10]),"+f"(d[11])
    : "r"(a0), "r"(a1), "r"(a2), "r"(a3), "l"(db), "r"(sd));
}

#define AB_POLY 0xae
__device__ __forceinline__ constexpr bool poly_group(int group) { return (AB_POLY >> (group & 7)) & 1; }

template <int V> struct Int { static constexpr int value = V; };

template <int NG>
__device__ __forceinline__ void ln_stats(const float4 (&v)[NG][5], uint32_t scratch, float (&mean)[NG], float (&rs)[NG]) {
  const int warp = threadIdx.x >> 5, lane = threadIdx.x & 31;
#pragma unroll
  for (int r = 0; r < NG; r++) {
    float s = 0.f, q = 0.f;
#pragma unroll
    for (int i = 0; i < 5; i++) s += (v[r][i].x + v[r][i].y) + (v[r][i].z + v[r][i].w);
    s += __shfl_xor_sync(~0u, s, 1); s += __shfl_xor_sync(~0u, s, 2);
    s *= 1.f / 80;
#pragma unroll
    for (int i = 0; i < 5; i++) {
      const float x = v[r][i].x - s, y = v[r][i].y - s, z = v[r][i].z - s, w = v[r][i].w - s;
      q += (x * x + y * y) + (z * z + w * w);
    }
    q += __shfl_xor_sync(~0u, q, 1); q += __shfl_xor_sync(~0u, q, 2);
    mean[r] = s; rs[r] = q;
  }
  bar_sync(1, 256);
  if ((lane & 3) == 0) {
#pragma unroll
    for (int r = 0; r < NG; r++) sts64f(scratch + r * 512 + lane * 16 + warp * 8, mean[r], rs[r]);
  }
  bar_sync(1, 256);
#pragma unroll
  for (int r = 0; r < NG; r++) {
    const float4 e = lds128f(scratch + r * 512 + lane * 16);
    float t = e.x + e.z;
    t += __shfl_xor_sync(~0u, t, 1); t += __shfl_xor_sync(~0u, t, 2);
    t *= 0.125f;
    float q = e.y + e.w + 80.f * ((e.x - t) * (e.x - t) + (e.z - t) * (e.z - t));
    q += __shfl_xor_sync(~0u, q, 1); q += __shfl_xor_sync(~0u, q, 2);
    mean[r] = t; rs[r] = rsqrtf(q * (1.f / DM) + 1e-5f);
  }
}

__device__ __forceinline__ void ln_store(const uint32_t (&w)[2][5][2], int tile, int u0, bool live = true) {
  const int lane = threadIdx.x & 31;
  uint32_t* xc = g_xc + ((tile >> 1) * 40 + u0) * 256 + (tile & 1) * 64 + lane;
#pragma unroll
  for (int i = 0; i < 20; i++) if (live) xc[(i >> 1) * 128 + (i & 1) * 32] = w[i & 1][i >> 2][i >> 1 & 1];
#pragma unroll
  for (int i = 0; i < 5; i++) {
    const int u = u0 + i;
    uint32_t* xn = g_xn + (((tile >> 3) * 20 + (u >> 1)) * 16 + (tile & 1) * 8 + (tile & 6)) * 128 + (u & 1) * 64 + lane;
#pragma unroll
    for (int r = 0; r < 2; r++) if (live) { xn[r * 128] = w[r][i][0]; xn[r * 128 + 32] = w[r][i][1]; }
  }
}
__device__ __forceinline__ void wait_count(const uint32_t* c, uint32_t n) {
  int spin = 0;
  while ((ld_acquire(c) & 0xffff) < n) { __nanosleep(32); spin_guard(spin); }
}

__device__ __forceinline__ uint8_t* pool_at(uint32_t off) {
  return reinterpret_cast<uint8_t*>((reinterpret_cast<uintptr_t>(g_pool) + 8191) & ~(uintptr_t)8191) + off; }
struct Weights { const uint8_t* w[4]; };
__device__ __forceinline__ void prefetch_weights(const Weights& p, int i) {
  if (blockIdx.x < 128) asm volatile("cp.async.bulk.prefetch.L2.global [%0], 61440;" :: "l"(p.w[i] + (size_t)blockIdx.x * 61440) : "memory");
}
__global__ void __launch_bounds__(384) first_kernel(const __nv_bfloat16* __restrict__ xin, const uint4* __restrict__ wb, const __grid_constant__ Weights wa) {
  __shared__ __align__(16) float scratch[256];
  __shared__ uint32_t lat[4];
  const int warp = threadIdx.x >> 5, lane = threadIdx.x & 31, cta = blockIdx.x;
  TRACE(0);
  pdl_launch();
  if (warp >= 8) {
    if (warp < 10 || cta < NSLOT) {
      uint32_t* q = reinterpret_cast<uint32_t*>(pool_at((warp < 10 ? NSLOT : cta) * 8192 + (warp & 1) * 4096)) + (warp < 10 ? (cta & 127) * 8 : 0);
      if (lane < 8) stg_strong32(q + lane, 0u);
      uint32_t best = ~0u;
      if (lane == 0) {
        for (int r = 0; r < FK_REP; r++) {
          uint32_t t0, t1, v;
          asm volatile("mov.u32 %0, %%clock;" : "=r"(t0) :: "memory");
          asm volatile("atom.relaxed.gpu.global.exch.b32 %0, [%1], 0;" : "=r"(v) : "l"(q) : "memory");
          asm volatile("{.reg .u32 t; add.u32 t, %1, 1; mov.u32 %0, %%clock; sub.u32 %0, %0, %1;}" : "=r"(t1) : "r"(__shfl_sync(1u, v, 0)) : "memory");
          best = min(best, t1 - t0);
        }
        lat[warp - 8] = best;
      }
    }
    __syncwarp();
    bar_sync(2, cta < 128 ? 384 : 128);
    if (threadIdx.x == 288) for (int i = 0; i < FK_PF; i++) prefetch_weights(wa, i);
    if (threadIdx.x == 256) {
      const int part = lat[0] < lat[1] ? 0 : 1;
      uint32_t smid; asm("mov.u32 %0, %%smid;" : "=r"(smid));
      g_smpart[smid & 255] = part;
      g_smclk[smid & 255] = clk32() - gtime() * 2;
      g_smuse[smid & 255] = 0;
      if (cta < NSLOT) g_orient[cta] = lat[2] < lat[3] ? part : 1 - part;
    }
  } else if (cta < 128) {
    float4 v[2][5];
#pragma unroll
    for (int r = 0; r < 2; r++)
#pragma unroll
      for (int i = 0; i < 5; i++) {
        const uint32_t* src = reinterpret_cast<const uint32_t*>(xin) + (cta * 16 + r * 8 + (lane >> 2)) * (DM / 2) + warp * 40 + i * 8 + (lane & 3);
        const uint32_t a = src[0], b = src[4];
        v[r][i] = make_float4(bf_lo(a), bf_hi(a), bf_lo(b), bf_hi(b));
      }
    uint4 w8[2];
#pragma unroll
    for (int i = 0; i < 2; i++) w8[i] = wb[cta * 400 + min(i * 256 + threadIdx.x, 399)];
    float mean[2], rs[2];
    ln_stats<2>(v, s2u(scratch), mean, rs);
    bar_sync(2, 384);
    ABT(2, 2);
    if (threadIdx.x < 128) g_stat[cta * 128 + threadIdx.x] = make_float2(0.f, 0.f);
#pragma unroll
    for (int i = 0; i < 10; i++) g_x[((cta * 2 + i / 5) * 40 + warp * 5 + i % 5) * 32 + lane] = pack4(v[i / 5][i % 5]);
    uint32_t w[2][5][2];
#pragma unroll
    for (int i = 0; i < 10; i++) {
      const float4 t = v[i / 5][i % 5];
      const float m = mean[i / 5], q = rs[i / 5];
      w[i / 5][i % 5][0] = pack2((t.x - m) * q, (t.y - m) * q); w[i / 5][i % 5][1] = pack2((t.z - m) * q, (t.w - m) * q);
    }
    ln_store(w, cta, warp * 5);
    ABT(2, 3);
#pragma unroll
    for (int i = 0; i < 2; i++) {
      const int e = cta * 400 + min(i * 256 + threadIdx.x, 399), k = e / 80, n = e - k * 80, cg = n / 10;
      g_wb[((cg * 80 + (k >> 3)) * 10 + n - cg * 10) * 8 + (k & 7)] = w8[i];
    }
  } else if (cta == 128) {
    g_bo[threadIdx.x] = 0;
  }
  TRACE(2);
}

struct ChainParams {
  CUtensorMap wq, wk, wv, wo;
  const __nv_bfloat16* mem0;
  uint8_t *pool, *kv;
  const uint32_t* xc;
  uint32_t* sync;
  int layer;
  int d0, d3, d1, d1b, d2, d2b, mode;
};
constexpr int CH_WQ = 0, CH_WO = 81920, CH_X = CH_WO + 86016, CH_M = CH_X + 20480, CH_KT = CH_X + 40960, CH_VT = CH_KT + 4096,
              CH_PS = CH_VT + 4096, CH_QK = CH_PS + 4096, CH_VP = CH_QK + 4096, CH_SX = CH_VP + 1024, CH_O = CH_SX + 2304, CH_ID = CH_O + 3072,
              CH_BAR = CH_ID + 512;
constexpr int CH_SMEM = CH_BAR + 256, CH_PB = CH_WQ + 57344;
constexpr int CH_BASE = 1024;
#define CH_VK0 8
#define CH_VK1 20
#define CH_L0 4
#define CH_LR 4
#define NOX 0
#define CH_XA 1
#define CH_XB 4
#define CH_W1 5
#define CH_W2 18
#define CH_W3 26
#define CH_R2 8
#define CH_VA 20
#define CH_EX 2
#define CH_KD 0
#define CH_RP 1
#define CH_KF 10
#define CH_LO 0
#define CH_LR1 4
#define CH_KP 0
#define CH_KM 3
#define CH_SP 1
#define CH_VC 2
#define CH_W0 5
#define CH_WA 3
#define CH_P1 4
#define CH_PW 1
#define CH_KW 3
#define CH_RB 0
#define CH_RC 8
#define CH_D0 230
#define CH_D1 450
#define CH_D2 270
#define CH_R1 4
#define CH_TW 12
__device__ __forceinline__ uint32_t opaque(uint32_t x) { return __shfl_sync(~0u, x, threadIdx.x & 31); }
__device__ __forceinline__ uint32_t nz(uint32_t x) { uint32_t r; asm("max.u32 %0, %1, 1;" : "=r"(r) : "r"(x)); return r; }
__device__ __forceinline__ uint32_t pack_tag(float lo, float hi, uint32_t tag, uint32_t mask) {
  uint32_t r;
  asm("lop3.b32 %0, %1, %2, %3, 0xD8;" : "=r"(r) : "r"(pack2(lo, hi)), "r"(tag), "r"(mask));
  return r;
}
__device__ __forceinline__ uint32_t differ(uint32_t a, uint32_t b, uint32_t t) { uint32_t r; asm("lop3.b32 %0, %1, %2, %3, 0x7E;" : "=r"(r) : "r"(a), "r"(b), "r"(t)); return r; }
__device__ __forceinline__ void mbar_wait_hot(uint32_t bar, uint32_t ph) {
  uint32_t ok;
  asm volatile("{.reg .pred p; mbarrier.try_wait.parity.shared::cta.b64 p, [%1], %2; selp.u32 %0, 1, 0, p;}" : "=r"(ok) : "r"(bar), "r"(ph) : "memory");
  if (__builtin_expect(!ok, 0)) mbar_wait(bar, ph);
}
__device__ __forceinline__ bool elect() {
  uint32_t r; asm volatile("{.reg .pred p; elect.sync _|p, 0xffffffff; selp.u32 %0, 1, 0, p;}" : "=r"(r)); return r; }
__device__ __forceinline__ uint32_t or3(uint32_t a, uint32_t b, uint32_t c) { uint32_t r; asm("lop3.b32 %0, %1, %2, %3, 0xFE;" : "=r"(r) : "r"(a), "r"(b), "r"(c)); return r; }
__device__ __forceinline__ void pin() { pdl_launch(); }
__device__ __forceinline__ void mma16h(float* d, uint32_t a0, uint32_t a2, uint32_t b0, uint32_t b1) {
  asm volatile("{.reg .b32 u, v; mma.sync.aligned.m16n8k16.row.col.f32.bf16.bf16.f32 {%0,%1,%2,%3},{%4,u,%5,v},{%6,%7},{%0,%1,%2,%3};}"
               : "+f"(d[0]), "+f"(d[1]), "+f"(d[2]), "+f"(d[3]) : "r"(a0), "r"(a2), "r"(b0), "r"(b1)); }
__device__ __forceinline__ void mma8h(float* d, uint32_t a0, uint32_t b0) {
  asm volatile("{.reg .b32 u; mma.sync.aligned.m16n8k8.row.col.f32.bf16.bf16.f32 {%0,%1,%2,%3},{%4,u},{%5},{%0,%1,%2,%3};}"
               : "+f"(d[0]), "+f"(d[1]), "+f"(d[2]), "+f"(d[3]) : "r"(a0), "r"(b0)); }
__device__ __forceinline__ uint32_t absmax2(uint32_t a, uint32_t b) { uint32_t r; asm("max.xorsign.abs.bf16x2 %0, %1, %2;" : "=r"(r) : "r"(a), "r"(b)); return r; }
__device__ __forceinline__ void until(uint32_t t) { while ((int)(clk32() - t) < 0) {} }
__device__ __forceinline__ uint4 pack8(const float* d) { return make_uint4(pack2(d[0], d[1]), pack2(d[2], d[3]), pack2(d[4], d[5]), pack2(d[6], d[7])); }
__device__ __forceinline__ void add8(float* d, uint4 v) {
  d[0] += bf_lo(v.x); d[1] += bf_hi(v.x); d[2] += bf_lo(v.y); d[3] += bf_hi(v.y);
  d[4] += bf_lo(v.z); d[5] += bf_hi(v.z); d[6] += bf_lo(v.w); d[7] += bf_hi(v.w);
}

template <int WG>
__device__ __forceinline__ void chain_body(const ChainParams& p, const uint32_t wq, const uint32_t (&ak)[80], const uint32_t (&av)[80]) {
  const int tid = threadIdx.x & 127, t4 = __shfl_sync(~0u, tid >> 5, 0), lane = tid & 31;
  const int cta = blockIdx.x, h = cta / 3, j = cta - 3 * h;
  const uint32_t sb = mapa(CH_BASE, j);
  const uint32_t bWo = sb + CH_BAR, bWq = bWo + 8, bX = bWo + 16, bXA = bWo + 24, bXB = bWo + 32, bO = bWo + 40, bG = bWo + 48, bH = bWo + 96;
  uint32_t tw[4 * CH_TW];
  auto refill = [&]() {
#pragma unroll
    for (int k = 0; k < CH_TW; k++) ldsm4t(&tw[4 * k], wq + k * 2048);
  };
  const uint32_t wo = opaque((sb + CH_WO + (WG == 0 ? (t4 + (j == 2)) * 4096 : (j == 2 ? 0 : 24576) + t4 * 1024) + ((lane & 7) + (lane >> 4) * 8) * 64 +
                              ((((lane >> 3) & 1) ^ ((lane >> 1) & 3)) << 4)) ^ (WG == 1 && j == 2 ? 32 : 0));
  const uint32_t wo2 = opaque((wo ^ ((t4 & 1) * 32)) + (4 + (t4 >> 1) - t4) * 4096);
  const uint32_t l16 = opaque(sb + lane * 16);
  const uint32_t l8 = opaque(sb + t4 * 256 + lane * 8);
  const uint32_t lw = opaque(sb + t4 * 1024 + lane * 16);
  const uint32_t qs = opaque(sb + CH_QK + WG * 2048 + t4 * 512 + lane * 16);
  const uint32_t qa = opaque(sb + CH_QK + (lane >> 4) * 2048 + (lane & 15) * 16 + (WG == 0 ? t4 * 512 + 256 : t4 == 3 ? 1024 : 0));
  const uint32_t ka = opaque(t4 < 2 ? sb + CH_KT + t4 * 512 + lane * 16
                                    : sb + CH_QK + 256 + (t4 - 2) * 1024 + ((lane >> 3) & 1) * 2048 + (lane >> 4) * 128 + (lane & 7) * 16);
  const uint32_t l4 = opaque(sb + t4 * 256 + lane * 4);
  uint32_t pdst[1], pages = 0;
  auto line0 = [&](int i) { return 28 * j + (i < 4 ? 4 * t4 + i : 12 + 2 * t4 + i); };
  const uint32_t plane = opaque((lane >> 4) * 2048 + h * 64 + (lane & 15) * 4);
  if (WG == 0) {
    pages = __ballot_sync(~0u, lds32(sb + CH_O + line0(min(lane, 5)) * 4) & 4096);
  } else {
    pages = __ballot_sync(~0u, lds32(sb + CH_O + (80 + min(lane, 11)) * 4) & 4096);
    pdst[0] = opaque(lds32(sb + CH_O + (j == 0 ? 24 + t4 : 50 + 2 * j + (t4 & 1)) * 4) + plane);
  }
  const uint32_t role = lds32(sb + CH_O + NSLOT * 4), rsrc = lds32(sb + CH_O + role * 4), rdst = (80 + role / 20) * 8192 + role % 20 * 128;
  const uint32_t r1 = mapa(CH_BASE, j == 2 ? 0 : j + 1) - sb, r2 = mapa(CH_BASE, j == 0 ? 2 : j - 1) - sb;
  uint32_t tag = opaque(1);
  auto pool = [&](uint32_t off) { return p.pool + ((tag & 0xfffe) + off); };
  auto after = [&](uint32_t x) { return x & tag & 0xfffe; };
  auto kv = [&](int s, uint32_t a) { return p.kv + (a + ((cta * 2 * NSEG + s) * KV_BYTES - sb)); };
  auto pass = [&](float (&d)[16], const uint32_t (&a)[80], auto k0, auto k1) {
    const uint64_t db = mkdesc(CH_BASE + CH_X + WG * 20480, 512, 128, 0);
#pragma unroll
    for (int k = k0.value; k < k1.value; k++) wg_rs32_00(d, a[4 * k], a[4 * k + 1], a[4 * k + 2], a[4 * k + 3], db + k * 64, k);
    wg_commit();
  };
  auto dump = [&](float (&d)[16], uint32_t a) {
    reg_fence<16>(d);
    sts128(a, pack8(d)); sts128(a + 512, pack8(d + 8));
  };
  uint32_t pph = 0;
  auto tokens0 = [&](int s, auto k0) {
    float dk[16], dv[16];
    bar_sync(9, 256);
    wg_fence();
    pass(dk, ak, Int<0>(), Int<4>());
    const uint4 a0 = lds128(lw + CH_KT), a1 = lds128(lw + CH_KT + 512);
    pin();
    pass(dk, ak, Int<4>(), Int<20>());
    pass(dv, av, Int<0>(), Int<CH_VA>());
    pin();
    wg_wait<1>();
    reg_fence<16>(dk);
    add8(dk, a0); add8(dk + 8, a1);
    const uint4 w0 = pack8(dk), w1 = pack8(dk + 8);
    const uint4 b0 = lds128(lw + CH_VT), b1 = lds128(lw + CH_VT + 512);
    stsm4t(lw + CH_KT, w0.x, w0.z, w0.y, w0.w); stsm4t(lw + CH_KT + 512, w1.x, w1.z, w1.y, w1.w);
    if (CH_KP == 2) bar_arrive(7, 160);
    TM1(6);
    pin();
    if (CH_VA < 20) pass(dv, av, Int<CH_VA>(), Int<20>());
    pin();
#pragma unroll
    for (int k = k0.value; k < CH_TW; k++) ldsm4t(&tw[4 * k], wq + k * 2048);
    TM1(9);
    if (!CH_PW && k0.value < CH_TW && t4 >= 2) { mbar_wait_hot(bH + t4 * 16 - 24 + (pph & 1) * 8, pph >> 1 & 1); pph++; }
    __syncwarp();
    wg_wait<0>();
    reg_fence<16>(dv);
    add8(dv, b0); add8(dv + 8, b1);
#pragma unroll
    for (int e = 0; e < 2; e++) { const uint4 v = pack8(dv + 8 * e); sts128(lw + CH_VT + e * 512, make_uint4(v.x, v.z, v.y, v.w)); }
  };
  auto publish_k = [&](int s) {
    if (t4 == CH_KW && elect()) { fence_async(); bulk_store(p.kv + (size_t)(cta * 2 * NSEG + s) * KV_BYTES, sb + CH_KT, 4096); bulk_commit(); }
    __syncwarp();
  };
  auto load_x = [&](int s, int k0, int n, uint32_t bar) {
    if (!NOX && elect()) { mbar_expect(bar, n * 1024); bulk_load(sb + CH_X + k0 * 1024, p.xc + (s + 1) * 10240 + k0 * 256, n * 1024, bar); }
  };
  if (WG == 0) {
    mbar_wait(bXB, 0);
    tokens0(0, Int<CH_TW>());
    if (CH_XB == 5) { bar_sync(7, 128); load_x(0, 5 * t4, 5, bXB); }
  } else {
    const uint32_t* m0 = reinterpret_cast<const uint32_t*>(p.mem0) + (lane >> 2) * 320 + t4 * 80 + (lane & 3);
    uint32_t a[20];
#pragma unroll
    for (int i = 0; i < 20; i++) a[i] = m0[4 * i];
    pin();
    float dk[16], dv[16];
    mbar_wait(bXA, 0);
    wg_fence();
    pass(dk, ak, Int<0>(), Int<20>());
    pass(dv, av, Int<0>(), Int<20>());
    wg_wait<0>();
    dump(dk, lw + CH_KT);
    dump(dv, lw + CH_VT);
    bar_sync(9, 256);
    if (CH_KP == 2 && t4 == CH_KW) { bar_sync(7, 160); publish_k(0); }
#pragma unroll
    for (int i = 0; i < 20; i++) sts32(sb + CH_M + (t4 * 20 + i) * 128 + lane * 4, nz(transpose8(a[i])));
    __syncwarp();
    if (elect()) mbar_arrive(bG + t4 * 8);
  }
  PRO(8);
  mbar_wait(bWq, 0);
  refill();
  PRO(9);
  mbar_wait(bWo, 0);
  asm volatile("barrier.cluster.wait.aligned;" ::: "memory");
  PRO(10);
  constexpr int VK = WG == 0 ? CH_VK0 : CH_VK1;
  uint32_t gph = 0;
  int st = 0;
  const uint32_t ca = opaque(sb + CH_M + t4 * 2560 + lane * 32 + (lane >> 2) * 4);
  auto project = [&](int s, uint32_t (&b)[40], float (&dv)[16], uint32_t (&kf)[16]) {
    float dq[4] = {}, dk[4] = {};
    uint32_t w[80];
#pragma unroll
    for (int i = 0; i < 4 * CH_TW; i++) w[i] = tw[i];
    constexpr int LR = WG == 1 ? CH_LR1 : CH_LR;
    auto load = [&](int n) {
      int c = 0;
#pragma unroll
      for (int i = 0; i < 10; i++) {
        if (i == CH_KF) {
#pragma unroll
          for (int q = 0; q < 4; q++)
            if (WG == 1 && c++ == n) ldsm4(&kf[4 * q], ka + q * 1024);
        }
        if (c++ == n) ldsm4t(&b[4 * i], l16 + CH_M + WG * 5120 + i * 512);
#pragma unroll
        for (int k = 2 * i; k < 2 * i + 2; k++)
          if (k >= CH_TW && c++ == n) ldsm4t(&w[4 * k], wq + k * 2048);
      }
#pragma unroll
      for (int i = 0; i < 4; i++)
        if (WG == 1 && CH_KF >= 10 && c++ == n) ldsm4(&kf[4 * i], ka + i * 1024);
    };
    if (WG == 1) {
      for (int n = 0;;) {
        mbar_wait(bG + t4 * 8, gph);
        TR(5, (clk32() & ~3u) | min(n, 3));
        gph ^= 1;
        if (__builtin_expect(!__any_sync(~0u, __vimin3_u32(lds32(ca), lds32(ca + 1024), lds32(ca + 1536)) == 0), 1)) break;
        if (elect()) {
          const int q = (st == 0 ? 8 : st * 4 - 4) + t4;
          mbar_expect(bG + t4 * 8, 2560);
          bulk_load(sb + CH_M + t4 * 2560, p.pool + ((80 + q) * 8192 + (pages >> q & 1) * 4096), 2560, bG + t4 * 8);
        }
        spin_guard(n);
      }
    }
    bar_sync(6, 256);
#pragma unroll
    for (int i = 0; i < CH_L0; i++) load(i);
    if (WG == 0 && CH_XB == 4) load_x(min(s, NSEG - 2), 5 * t4, 5, bXB);
    TM(0);
    TM1(11);
    if (WG == 1) TR(6, clk32());
#pragma unroll
    for (int k = 0; k < 20; k += 2) {
      if (k > 0) {
#pragma unroll
        for (int n = (k == 18 ? 40 : CH_L0 + k * LR / 4) - 1; n >= CH_L0 + (k - 2) * LR / 4; n--) { load(n); if (CH_LO) __syncwarp(); }
      }
      if (WG == 0 && CH_XB >= 10 && k == CH_XB - 10 && s + 1 < NSEG) load_x(s, 5 * t4, 5, bXB);
      pin();
#pragma unroll
      for (int kk = k; kk < k + 2; kk++) {
        mma16(dk, ak[4 * kk], ak[4 * kk + 1], ak[4 * kk + 2], ak[4 * kk + 3], b[2 * kk], b[2 * kk + 1]);
        mma16(dq, w[4 * kk], w[4 * kk + 1], w[4 * kk + 2], w[4 * kk + 3], b[2 * kk], b[2 * kk + 1]);
        if (kk < VK) mma16(dv, av[4 * kk], av[4 * kk + 1], av[4 * kk + 2], av[4 * kk + 3], b[2 * kk], b[2 * kk + 1]);
      }
    }
    const float k2 = 0.07216878364870322f * 1.44269504089f;
    stsm4t(qs, pack2(dq[0] * k2, dq[1] * k2), pack2(dq[2] * k2, dq[3] * k2), pack2(dk[0], dk[1]), pack2(dk[2], dk[3]));
    TM(1);
  };
  static_assert(CH_P1 == 4 && CH_TW == 12 && CH_VK1 == 20 && CH_KP == 0 && true, "last step");
  constexpr int VC = VK == 20 ? 1 : CH_VC;
  auto finish_v = [&](const uint32_t (&b)[40], float (&dv)[16]) {
#pragma unroll
    for (int kk = VK; kk < 20; kk++) mma16(dv + 4 * ((kk - VK) % VC), av[4 * kk], av[4 * kk + 1], av[4 * kk + 2], av[4 * kk + 3], b[2 * kk], b[2 * kk + 1]);
  };
  auto sum_v = [&](float (&dv)[16]) {
#pragma unroll
    for (int i = 4; i < 4 * VC; i++) dv[i & 3] += dv[i];
  };
  auto publish_km = [&](int s, int w = 0) {
    uint32_t a[4];
    ldsm4(a, qa + w * 512);
    *reinterpret_cast<uint2*>(kv(s, l8) + KV_M + w * 256) = make_uint2(hadd2(a[0], a[2]), hadd2(a[1], a[3]));
  };
  auto memory_v = [&](uint2 x, const float (&dv)[16]) {
    return make_uint2(pack2(dv[0] + bf_lo(x.x), dv[1] + bf_hi(x.x)), pack2(dv[2] + bf_lo(x.y), dv[3] + bf_hi(x.y)));
  };
  auto publish_v = [&](int s, const uint4 (&v)[2], uint2 vm) {
#pragma unroll
    for (int e = 0; e < 2; e++) reinterpret_cast<uint4*>(kv(s, lw) + KV_V)[e * 32] = v[e];
    *reinterpret_cast<uint2*>(kv(s, l8) + KV_V + KV_M) = vm;
  };
#pragma unroll 1
  for (int s = 0;; s++) {
    float dv[16] = {};
    uint32_t b[40], kf[16];
    project(s, b, dv, kf);
    if (WG == 0) {
      bar_sync(1, 256);
      if (CH_XA == 0 && s + 1 < NSEG) load_x(s, 20 + 5 * t4, 5, bXA);
      if (CH_XB == 0 && s + 1 < NSEG) load_x(s, 5 * t4, 5, bXB);
      pin();
      uint32_t w[144];
      auto wload = [&](int i) { ldsm4t(&w[4 * i], (i % 3 == 0 ? wo : i % 3 == 1 ? wo ^ 32 : wo2) + i / 12 * 28672 + i / 3 % 4 * 1024); };
#pragma unroll
      for (int kk = VK; kk < 20; kk++) {
        mma16(dv + 4 * ((kk - VK) % VC), av[4 * kk], av[4 * kk + 1], av[4 * kk + 2], av[4 * kk + 3], b[2 * kk], b[2 * kk + 1]);
        if (kk == VK + CH_WA && CH_W0) {
          pin();
#pragma unroll
          for (int i = 0; i < CH_W0; i++) wload(i);
          pin();
        }
      }
      sum_v(dv);
      sts64(l8 + CH_VP, pack2(dv[0], dv[1]), pack2(dv[2], dv[3]));
      if (s == NSEG - 1) {
        bar_arrive(10, 256);
        mbar_wait(bXB, 0);
        if (CH_PW && t4 >= 2) mbar_wait(bH + t4 * 16 - 24 + (pph & 1) * 8, pph >> 1 & 1);
        publish_k(s);
        publish_km(s);
        bulk_wait<0>();
        fence_async_global();
        bar_sync(2, 256);
        if (t4 == 0 && elect()) red_release(p.sync + 15 * 8 + 4, 1);
        break;
      }
      bar_arrive(4, 256);
      if (CH_XA == 1) load_x(s, 20 + 5 * t4, 5, bXA);
      if (CH_XB == 1) load_x(s, 5 * t4, 5, bXB);
      TM(3);
      if (CH_KP == 0) publish_k(s);
#pragma unroll
      for (int i = CH_W0; i < CH_W1; i++) wload(i);
      bar_sync(10, 256);
      uint32_t km[4] = {};
      if (CH_KM < 2) ldsm4(km, qa);
      pin();
#pragma unroll
      for (int i = CH_W1; i < CH_W2; i++) wload(i);
      pin();
      const uint2 kms = make_uint2(hadd2(km[0], km[2]), hadd2(km[1], km[3]));
      if (CH_KM == 0) *reinterpret_cast<uint2*>(kv(s, l8) + KV_M) = kms;
      if (CH_KP == 0) bulk_wait_read<0>();
      if (CH_XA == 2) load_x(s, 20 + 5 * t4, 5, bXA);
      if (CH_XB == 2) load_x(s, 5 * t4, 5, bXB);
      bar_sync(2, 256);
      {
        float y[3][4] = {};
        uint32_t ob[24];
        ldsm4(&ob[0], l16 + CH_O + 1024); ldsm4(&ob[4], l16 + CH_O + 1536);
        TM(7);
        auto step = [&](int i) {
          const int k = i / 3;
          mma16(y[i % 3], w[4 * i], w[4 * i + 1], w[4 * i + 2], w[4 * i + 3], ob[2 * k], ob[2 * k + 1]);
        };
#pragma unroll
        for (int i = 0; i < 12; i++) {
          step(i);
          if (i >= 12 - (CH_W3 - CH_W2)) wload(CH_W3 - 12 + i);
          if (i % 3 == 2) pin();
        }
        if (CH_XB == 3) load_x(s, 5 * t4, 5, bXB);
        if (CH_KM == 1) *reinterpret_cast<uint2*>(kv(s, l8) + KV_M) = kms;
        pin();
        mbar_wait(bO, s & 1);
        TM(4);
        ldsm4(&ob[8], l16 + CH_O); ldsm4(&ob[12], l16 + CH_O + 512);
        pin();
        float2 inv;
        uint8_t* dst[6];
        uint32_t mask;
#pragma unroll
        for (int i = 12; i < 36; i++) {
          step(i);
          static_assert(CH_W3 == 26, "load order");
          if (i == 14) ldsm4(&ob[16], l16 + after(w[4 * CH_W3 - 1] | w[4 * CH_W3 - 5] | w[4 * CH_W3 - 9] | ob[8]) + CH_O + 2048);
          else if (i == 15) ldsm4(&ob[20], l16 + CH_O + 2560);
          else if (i < 24) wload(i < 14 ? 39 - i : i < 18 ? 45 - i : i < 21 ? 50 - i : 56 - i);
          if (i == 21) inv = lds64f((l8 & ~0xe0u) + CH_VP);
          if (i < 24) __syncwarp();
          if (i == 24) mask = ((l16 ^ tag) & 48) == 0;
          if (i >= 24 && i < 30) dst[i - 24] = pool(line0(i - 24) * 8192 + (pages >> (i - 24) & 1) * 4096) + plane;
          if (i % 3 == 2) pin();
        }
#pragma unroll
        for (int k = 0; k < CH_R1; k++) ldsm4t(&tw[4 * k], wq + k * 2048);
        pin();
#pragma unroll
        for (int i = 0; i < 6; i++) stg_strong32(dst[i], pack_tag(y[i >> 1][2 * (i & 1)] * inv.x, y[i >> 1][2 * (i & 1) + 1] * inv.y, tag, mask));
        TM(8);
        TR(0, clk32());
        bar_arrive(5, 256);
        pin();
      }
      const uint32_t t0 = clk32();
      auto refill2 = [&]() {
#pragma unroll
        for (int k = CH_R1; k < CH_R2; k++) ldsm4t(&tw[4 * k], wq + k * 2048);
      };
      if (CH_RP == 0) refill2();
      const uint32_t ln = (l16 ^ tag) >> 4 & 31;
      auto keep = [&](uint32_t x) { return __shfl_sync(~0u, x, ln); };
      if (t4 >= 2) {
        const uint32_t bP = bH + t4 * 16 - 24, ps = CH_PB + (t4 & 1) * 4096;
        auto fetch = [&](uint32_t k) {
          if (elect()) { mbar_expect(bP + (k & 1) * 8, 2048); bulk_load(sb + ps + (k & 1) * 2048, p.pool + (rsrc + (t4 & 1) * 2048), 2048, bP + (k & 1) * 8); }
        };
        if (CH_PW && s > 0) { mbar_wait_hot(bP + (pph & 1) * 8, pph >> 1 & 1); pph++; }
        until(t0 + CH_D0);
        fetch(pph);
        if (CH_RP == 2) refill2();
        if (!NOX && CH_XB != 6) mbar_wait_hot(bXB, (s + 1) & 1);
        const uint32_t want = (tag & 1) * 0x10001, chk = keep(ln < 4 ? 0x10001 : 0);
        uint4 sel;
        sel.x = keep((ln >> 3) != (ln & 1) ? 0 : ln & 4 ? 0x3f800000u : 0x00003f80u);
        sel.z = keep(sel.x); sel.y = keep(ln); sel.w = keep(ln + 1);
        uint8_t* mdst = p.pool + keep(st * 32768 + rdst + (t4 & 1) * 64 + ln * 4);
        until(t0 + CH_D1);
        fetch(pph + 1);
        TM(5);
        if (CH_RP == 1) refill2();
        if (CH_KM == 2) publish_km(s);
        int n = 0;
        uint32_t u[16];
        float y[4][4];
        auto sum = [&]() {
#pragma unroll
          for (int i = 0; i < 16; i++) y[i >> 2][i & 3] = 0.f;
#pragma unroll
          for (int i = 0; i < 8; i++) mma16(y[i & 3], sel.x, sel.y, sel.z, sel.w, u[2 * i], u[2 * i + 1]);
        };
        auto check = [&](auto spec) {
          mbar_wait(bP + (pph & 1) * 8, pph >> 1 & 1);
          TM(14);
          TR(2, clk32());
#pragma unroll
          for (int i = 0; i < 4; i++) ldsm4t(&u[4 * i], l16 + (ps + (pph & 1) * 2048) + i * 512);
          pph++;
          if (spec.value) { pin(); sum(); }
          uint32_t bad = 0;
#pragma unroll
          for (int i = 0; i < 4; i++) bad = or3(bad, differ(u[4 * i], u[4 * i + 1], want), differ(u[4 * i + 2], u[4 * i + 3], want));
          return __any_sync(~0u, bad & chk);
        };
        if (CH_SP) {
          if (check(Int<0>())) {
            do { fetch(pph + 1); spin_guard(n); } while (check(Int<1>()));
          } else {
            sum();
          }
        } else {
          while (check(Int<0>())) { fetch(pph + 1); spin_guard(n); }
          sum();
        }
        TR(1, t0 + (n ? CH_D1 : CH_D0));
        TM(15);
        const uint32_t w = nz(pack2((y[0][0] + y[1][0]) + (y[2][0] + y[3][0]), (y[0][1] + y[1][1]) + (y[2][1] + y[3][1])));
        if (ln < 16) { stg_strong32(mdst, w); stg_strong32(mdst + 4096, w); }
        TMV(12, 32, n);
        TR(3, (clk32() & ~3u) | min(n, 3));
      } else {
        if (CH_XB == 6) { load_x(s, 10 * t4, 5, bXB); load_x(s, 10 * t4 + 5, 5, bXB); }
        if (CH_RP) refill2();
        if (CH_KM == 2) publish_km(s);
        if (CH_KM == 3) { publish_km(s); publish_km(s, 2); }
        if (!NOX) mbar_wait_hot(bXB, (s + 1) & 1);
        stg_strong32(p.pool + ((st == 2 ? 0 : st + 1) * 32768 + rdst + t4 * 4096) + ln * 4, 0u);
        if (t4 == 0 && cta < 40 && s + 4 < NSEG && elect())
          asm volatile("cp.async.bulk.prefetch.L2.global [%0], 1024;" :: "l"(p.xc + (s + 4) * 10240 + cta * 256) : "memory");
        if (t4 == 1 && (s & 3) == 0 && s > 0 && elect()) red_relaxed(p.sync + 2 * s - 4, 1);
        if (t4 == 1 && s == NSEG - 3 && cta == 95 && elect()) red_relaxed(p.sync + 2 * s + 2, 0x10000);
      }
      TM(10);
      bar_arrive(8, 256);
      tokens0(s + 1, Int<CH_R2>());
      if (CH_XB == 5 && s + 2 < NSEG) { bar_sync(7, 128); load_x(s + 1, 5 * t4, 5, bXB); }
      TM(2);
      TR(7, clk32());
    } else {
      if (s == NSEG - 1) {
        bar_arrive(1, 256);
        const uint4 v[2] = {lds128(lw + CH_VT), lds128(lw + CH_VT + 512)};
        bar_sync(10, 256);
        publish_v(s, v, memory_v(lds64(l8 + CH_VP), dv));
        bar_arrive(2, 256);
        break;
      }
      const uint32_t xo = l4 + (CH_SX - (t4 == 3 ? 128 : 0)), xr = CH_SX + 768 + min(t4, 2) * 256, x1 = l4 + (r1 + xr), x2 = l4 + (r2 + xr + 128);
      if (t4 < 2) {
        float ds[4][4] = {};
        uint32_t q[16];
        asm volatile("bar.sync 1, 256;" ::: "memory");
#pragma unroll
        for (int k = 0; k < 4; k++) ldsm4(&q[4 * k], qa + k * 512);
        pin();
        if (VK < 20) { finish_v(b, dv); pin(); }
#pragma unroll
        for (int k = 0; k < 4; k++) {
          mma16(ds[k & 1], kf[4 * k], kf[4 * k + 1], kf[4 * k + 2], kf[4 * k + 3], q[4 * k], q[4 * k + 1]);
          mma16(ds[2 + (k & 1)], kf[4 * k], kf[4 * k + 1], kf[4 * k + 2], kf[4 * k + 3], q[4 * k + 2], q[4 * k + 3]);
        }
        float t[4];
#pragma unroll
        for (int i = 0; i < 4; i++) t[i] = (ds[0][i] + ds[2][i]) + (ds[1][i] + ds[3][i]);
        const uint32_t w0 = pack2(t[0], t[1]), w1 = pack2(t[2], t[3]);
        st_async32(x1, w0, bX + r1); st_async32(x2, w0, bX + r2);
        st_async32(x1 + 256, w1, bX + r1); st_async32(x2 + 256, w1, bX + r2);
        sts32(xo, w0); sts32(xo + 128, w1);
      } else {
        float ds[4][4] = {};
        uint32_t q0[4], q1[4], a0[4], a1[4];
        asm volatile("bar.sync 1, 256; " ::: "memory");
        ldsm4(a0, ka); ldsm4(q0, qa); ldsm4(a1, ka + 512); ldsm4(q1, qa + 512);
        pin();
        if (VK < 20) { finish_v(b, dv); pin(); }
        mma16(ds[0], a0[0], a0[1], a0[2], a0[3], q0[0], q0[1]);
        mma16(ds[1], a0[0], a0[1], a0[2], a0[3], q0[2], q0[3]);
        mma16(ds[2], a1[0], a1[1], a1[2], a1[3], q1[0], q1[1]);
        mma16(ds[3], a1[0], a1[1], a1[2], a1[3], q1[2], q1[3]);
        float t[2];
#pragma unroll
        for (int i = 0; i < 2; i++)
          t[i] = ((ds[0][i] + ds[0][i + 2]) + (ds[1][i] + ds[1][i + 2])) + ((ds[2][i] + ds[2][i + 2]) + (ds[3][i] + ds[3][i + 2]));
        const uint32_t w0 = pack2(t[0], t[1]);
        st_async32(x1, w0, bX + r1);
        st_async32(x2, w0, bX + r2);
        sts32(xo, w0);
      }
      TM(3);
      const uint4 id = lds128(l16 + CH_ID);
      float sc[5][4] = {};
      uint4 v[2];
      sum_v(dv);
      bar_sync(4, 256);
      uint32_t r[12], wd[12], we[12] = {};
      ldsm4(&r[0], l16 + CH_SX); ldsm2(&r[4], l16 + CH_SX + 512);
      const uint2 vp = lds64(l8 + CH_VP);
      pin();
      v[0] = lds128(lw + CH_VT); v[1] = lds128(lw + CH_VT + 512);
#pragma unroll
      for (int u = 0; u < 3; u++) ldsm4t(&wd[4 * u], wo + u * 28672);
      pin();
#pragma unroll
      for (int q = 0; q < 4; q++) mma8(sc[q], id.x, id.y, r[q]);
      mma16(sc[4], id.x, id.y, id.z, id.w, r[4], r[5]);
      uint32_t big = absmax2(absmax2(absmax2(r[0], r[1]), absmax2(r[2], r[3])), absmax2(r[4], r[5]));
      const uint2 vm = memory_v(vp, dv);
      const uint32_t ones = 0x3f803f80u;
      pin();
      mbar_wait_hot(bX, s & 1);
      TM(4);
      ldsm4(&r[0], l16 + CH_SX + 768);
      __syncwarp();
      ldsm4(&r[8], l16 + CH_SX + 1792);
      __syncwarp();
      ldsm4(&r[4], l16 + CH_SX + 1280);
      bar_arrive(10, 256);
      pin();
      auto add = [&](int q) { mma16(sc[min(q, 4)], id.x, id.y, id.z, id.w, r[2 * q], r[2 * q + 1]); };
      add(0); add(1);
      pin();
      add(4);
      pin();
      uint32_t pr[5], o0, o1;
      bool redo = false;
      auto attend = [&](auto first) {
        float o[2][4] = {}, e[10];
        auto exps = [&](int q) {
#pragma unroll
          for (int i = 0; i < 2; i++) asm volatile("ex2.approx.ftz.f32 %0, %1;" : "=f"(e[2 * q + i]) : "f"(sc[q][i]));
        };
        auto merge = [&](int q) { big = absmax2(big, absmax2(absmax2(r[4 * q], r[4 * q + 1]), absmax2(r[4 * q + 2], r[4 * q + 3]))); };
        exps(0);
        if (first.value) { merge(0); pin(); add(2); add(5); add(3); }
        exps(1);
        if (first.value) { merge(2); pin(); }
        exps(2);
        if (first.value) { merge(1); pin(); }
        pr[0] = pack2(e[0], e[1]); pr[1] = pack2(e[2], e[3]);
        mma16h(o[0], pr[0], pr[1], v[0].x, v[0].y);
        mma16h(o[1], pr[0], pr[1], v[0].z, v[0].w);
        exps(4);
        if (first.value) pin();
        exps(3);
        if (first.value) redo = __any_sync(~0u, (absmax2(big, big << 16) & 0x7fff0000u) >= 0x41800000u);
        const bool drop = first.value && redo;
        const uint32_t a1 = l4 + (drop ? CH_PS : r1 + CH_O), a2 = l4 + (drop ? CH_PS : r2 + CH_O + 2048);
        const uint32_t b1 = drop ? bWq : bO + r1, b2 = drop ? bWq : bO + r2;
        pr[2] = pack2(e[4], e[5]); pr[3] = pack2(e[6], e[7]); pr[4] = pack2(e[8], e[9]);
        mma8h(o[0], pr[4], vm.x);
        mma8h(o[1], pr[4], vm.y);
        mma16h(o[0], pr[2], pr[3], v[1].x, v[1].y);
        mma16h(o[1], pr[2], pr[3], v[1].z, v[1].w);
        o0 = pack2(o[0][0], o[0][1]); o1 = pack2(o[1][0], o[1][1]);
        st_async32(a1, o0, b1); st_async32(a2, o0, b2);
        st_async32(a1 + 128, o1, b1); st_async32(a2 + 128, o1, b2);
        sts32(l4 + CH_O + 1024, o0); sts32(l4 + CH_O + 1152, o1);
        asm volatile("{.reg .pred p; setp.eq.u32 p, %0, 0; @p bar.arrive 2, 256;}" :: "r"((uint32_t)drop) : "memory");
      };
      attend(Int<1>());
      pin();
      if (__builtin_expect(redo, 0)) {
        float mx = -INFINITY;
#pragma unroll
        for (int q = 0; q < 5; q++) mx = fmaxf(mx, fmaxf(sc[q][0], sc[q][1]));
        mx = fmaxf(mx, __shfl_xor_sync(~0u, mx, 1));
        mx = fmaxf(mx, __shfl_xor_sync(~0u, mx, 2));
#pragma unroll
        for (int q = 0; q < 5; q++) { sc[q][0] -= mx; sc[q][1] -= mx; }
        attend(Int<0>());
      }
      TM(6);
      float l[4] = {}, l2[4] = {};
      mma16h(l, pr[0], pr[1], ones, ones);
      mma16h(l2, pr[2], pr[3], ones, ones);
      mma8h(l, pr[4], ones);
      l[0] += l2[0];
      float inv;
      asm("rcp.approx.ftz.f32 %0, %1;" : "=f"(inv) : "f"(l[0]));
      sts32((l8 & ~0xffu) + ((l8 ^ tag) >> 3 & 28) + CH_VP, __float_as_uint(inv));
      __syncwarp();
      if (elect()) mbar_arrive(bO);
      {
        float z[2][4] = {}, y[2][4] = {};
        mma16(z[0], wd[0], wd[1], wd[2], wd[3], o0, o1);
        if (j == 0) {
#pragma unroll
          for (int u = 0; u < 3; u++) ldsm4t(&we[4 * u], (wo ^ 32) + u * 28672);
          mma16(y[0], we[0], we[1], we[2], we[3], o0, o1);
        }
        const float2 iv = lds64f((l8 & ~0xe0u) + CH_VP);
        uint8_t* dst = pool(pdst[0]);
        const uint32_t mask = ((l16 ^ tag) & 48) == 0;
        const uint32_t oa = qa + ((tag & 0xfffe) + CH_O - CH_QK + t4 * 256 - (t4 == 3 ? 1024 : 0));
        const uint32_t za = l16 + ((tag & 0xfffe) + (t4 >> 1) * 512 + (t4 & 1) * 8);
        pin();
        mbar_wait(bO, s & 1);
        uint32_t a[4];
        ldsm4(a, oa);
        mma16(z[0], wd[4], wd[5], wd[6], wd[7], a[0], a[1]);
        mma16(z[1], wd[8], wd[9], wd[10], wd[11], a[2], a[3]);
        if (j == 0) {
          mma16(y[0], we[4], we[5], we[6], we[7], a[0], a[1]);
          mma16(y[1], we[8], we[9], we[10], we[11], a[2], a[3]);
          sts128f(lw + CH_VT + 512, y[0][0] + y[1][0], y[0][1] + y[1][1], y[0][2] + y[1][2], y[0][3] + y[1][3]);
        }
        sts128f(lw + CH_VT, z[0][0] + z[1][0], z[0][1] + z[1][1], z[0][2] + z[1][2], z[0][3] + z[1][3]);
        bar_sync(3, 128);
        if (j == 0 || t4 < 2) {
          float2 q[4];
#pragma unroll
          for (int i = 0; i < 4; i++) q[i] = lds64f(za + CH_VT + i * 1024);
          stg_strong32(dst, pack_tag(((q[0].x + q[1].x) + (q[2].x + q[3].x)) * iv.x, ((q[0].y + q[1].y) + (q[2].y + q[3].y)) * iv.y, tag, mask));
        }
      }
      TM(2);
      if (!NOX) mbar_wait_hot(bXA, (s + 1) & 1);
      if (CH_KP == 2) bulk_wait_read<0>();
      float dk[16], dw[16];
      bar_sync(5, 256);
      wg_fence();
      pass(dk, ak, Int<0>(), Int<20>());
      pass(dw, av, Int<0>(), Int<20>());
      TM(5);
      pin();
      if (CH_EX == 0) publish_v(s, v, vm);
      if (elect()) {
        mbar_expect(bG + t4 * 8, 2560);
        if (t4 == 1 && s + 2 < NSEG) { mbar_expect(bX, 1536); mbar_expect(bO, 2048); }
      }
      if (CH_KD == 0) { wg_wait<1>(); dump(dk, lw + CH_KT); }
      wg_wait<0>();
      if (CH_KD == 1) dump(dk, lw + CH_KT);
      TM(7);
      dump(dw, lw + CH_VT);
      bar_arrive(9, 256);
      pin();
#pragma unroll
      for (int k = 0; k < CH_RB; k++) ldsm4t(&tw[4 * k], wq + k * 2048);
      if (t4 < 2) {
        if (CH_EX == 2) { publish_v(s, v, vm); pin(); }
#pragma unroll
        for (int k = CH_RB; k < CH_RC; k++) ldsm4t(&tw[4 * k], wq + k * 2048);
        const int q = t4 ? 3 : j, o = t4 ? j * 896 : 0;
        const uint8_t* src = p.pool + ((80 + st * 4 + q) * 8192 + (pages >> (st * 4 + q) & 1) * 4096 + o);
        asm volatile("bar.sync 8, 256;" ::: "memory");
        const uint32_t t1 = clk32() + CH_D2;
        if (CH_EX == 1) publish_v(s, v, vm);
        auto fetch = [&](auto n) {
          mbar_wait(bH, s & 1);
          until(t1);
          TR(4, clk32());
          if (elect())
            asm volatile("cp.async.bulk.shared::cluster.global.mbarrier::complete_tx::bytes.multicast::cluster [%0], [%1], %2, [%3], 7;"
                         :: "r"(sb + CH_M + q * 2560 + o), "l"(src), "n"(n.value), "r"(bG + q * 8) : "memory");
        };
        if (!t4) fetch(Int<2560>()); else if (j == 2) fetch(Int<768>()); else fetch(Int<896>());
      } else {
        asm volatile("bar.sync 8, 256; " ::: "memory");
        if (elect()) asm volatile("mbarrier.arrive.relaxed.cluster.shared::cluster.b64 _, [%0];" :: "r"(bH + (t4 == 2 ? r1 : r2)) : "memory");
        pin();
        if (CH_EX) publish_v(s, v, vm);
#pragma unroll
        for (int k = CH_RB; k < CH_RC; k++) ldsm4t(&tw[4 * k], wq + k * 2048);
      }
      TM(9);
      pin();
#pragma unroll
      for (int k = CH_RC; k < CH_TW - CH_P1; k++) ldsm4t(&tw[4 * k], wq + k * 2048);
      if (CH_KP == 2 && t4 == CH_KW) { bar_sync(7, 160); publish_k(s + 1); }
      TM(10);
    }
    if (++st == 3) st = 0;
    tag ^= 0x10001;
  }
}

__global__ void __launch_bounds__(256, 1) chain_kernel(const __grid_constant__ ChainParams p) {
  extern __shared__ __align__(1024) uint8_t smem_raw[];
  const uint32_t sb = s2u(smem_raw);
  const int tid = threadIdx.x, warp = __shfl_sync(~0u, tid >> 5, 0), lane = tid & 31;
  const int cta = blockIdx.x, h = cta / 3, j = cta - 3 * h, colbase = cta * 64;
  const uint32_t bWo = sb + CH_BAR, bWq = bWo + 8, bXA = bWo + 24, bWk = bWo + 80, bWv = bWo + 88;
  uint32_t smid; asm("mov.u32 %0, %%smid;" : "=r"(smid));
  PRO(0);
  if (sb != mapa(CH_BASE, j)) __trap();
  uint32_t entry = 0;
  auto place = [&]() {
    const int i = tid - 128;
    if (i >= 0 && i <= NSLOT) {
      const uint32_t side = ldg_strong32(g_smpart + (smid & 255));
      if (i < NSLOT) {
        entry = i * 8192 + (ldg_strong32(g_orient + i) == (i < 80 ? i & 1 : side) ? 0 : 4096);
      } else {
        entry = 2 * (atomicAdd(g_bo + p.layer * 128 + 1, 1 << 8 * side) >> 8 * side & 255) + side;
      }
    }
    __syncwarp();
  };
  if (warp == 2 && lane < 4) asm volatile("prefetch.tensormap [%0];" :: "l"(&p.wq + lane) : "memory");
  if (p.layer) place();
  if (warp == 0 && elect()) {
#pragma unroll 1
    for (int i = 0; i < 17; i++) mbar_init(bWo + 8 * i, i == 5 ? 5 : i == 3 || i == 4 ? 4 : i == 12 ? 2 : 1);
    asm volatile("fence.mbarrier_init.release.cluster;" ::: "memory");
    mbar_expect(bWk, 81920);
    tma_load3<(WEF & 1) != 0>(sb + CH_WQ, &p.wk, colbase, 0, bWk);
    mbar_expect(bWv, 81920);
    tma_load3<(WEF & 1) != 0>(sb + CH_WO, &p.wv, colbase, 0, bWv);
    mbar_expect(bWo + 16, 1536);
    mbar_expect(bWo + 40, 2048);
    mbar_expect(bWo, 86016); mbar_expect(bWq, 81920);
#pragma unroll 1
    for (int i = 0; i < 8; i++) mbar_expect(bXA + 8 * (i & 1), 5120);
  }
  if (warp == 1) {
    const uint32_t id = (lane >> 3) == (lane & 3) ? ((lane & 4) ? 0x3f800000u : 0x00003f80u) : 0u;
    sts128(sb + CH_ID + lane * 16, make_uint4(id, 0, id, 0));
  }
  __syncthreads();
  asm volatile("barrier.cluster.arrive.relaxed.aligned;" ::: "memory");
  uint32_t ak[80], av[80];
  const uint32_t wq = opaque(sb + CH_WQ + ((warp >> 2) * 320 + (lane & 7) + (lane >> 4) * 8) * 128 + (((2 * (warp & 3) + ((lane >> 3) & 1)) ^ (lane & 7)) << 4));
  pdl_wait();
  if (tid == 32) stg_strong32(g_smuse + (smid & 255), p.layer + 1);
  pdl_launch();
  PRO(1);
  if (warp == 0 && elect()) {
    bulk_load(sb + CH_X + 20480, p.xc + 5120, 20480, bXA);
    bulk_load(sb + CH_X, p.xc, 20480, bXA + 8);
  }
  if (!p.layer) place();
  __syncwarp();
  PRO(2);
  mbar_wait(bWk, 0);
  PRO(3);
#pragma unroll
  for (int k = 0; k < 20; k++) ldsm4t(&ak[4 * k], wq + k * 2048);
  bar_sync(6, 256);
  if (warp == 0 && elect()) tma_load3<(WEF & 2) != 0>(sb + CH_WQ, &p.wq, colbase, 0, bWq);
  __syncwarp();
  PRO(4);
  mbar_wait(bWv, 0);
  PRO(5);
#pragma unroll
  for (int k = 0; k < 20; k++) ldsm4t(&av[4 * k], wq + CH_WO + k * 2048);
  bar_sync(6, 256);
  PRO(6);
  if (warp >= 5 && elect()) tma_load3<(WEF & 2) != 0>(sb + CH_WO + (warp - 5) * 28672, &p.wo, j == 0 ? 0 : 32 + j * 192, h * 192 + (j + 8 - warp) % 3 * 64, bWo);
  if (tid == 128 + NSLOT && entry >= 80) {
    uint32_t c;
    int n = 0;
    do { c = ldg_strong32(g_bo + p.layer * 128 + 1); spin_guard(n); } while ((c & 255) + (c >> 8) < 96);
    const uint32_t other = (c >> 8 * (~entry & 1) & 255) + (entry >> 1) - 40;
    entry = other < 40 ? 2 * other + (~entry & 1) : entry % 80;
  }
  if (tid >= 128 && tid <= 128 + NSLOT) sts32(sb + CH_O + (tid - 128) * 4, entry);
  PRO(7);
  __syncthreads();
  if (__shfl_sync(~0u, tid >> 7, 0) == 0) chain_body<0>(p, wq, ak, av); else chain_body<1>(p, wq, ak, av);
}

struct PostParams { CUtensorMap wq, wo, wb, wo2, wb2; int gap, share, layer, look, gap2, pol, slow_n, slow_gap; };
constexpr int PS = 8, PB = 28672;
constexpr int OP_SMEM = PS * PB + 512 + 2048;
enum { IT_ATT = 0, IT_OP = 1, IT_FIN = 2, IT_BQ = 3, IT_Q = 4 };

__device__ __forceinline__ uint32_t item_count(int type, int b) {
  return type == IT_ATT ? 32 : type == IT_OP ? op_split(b) * (b < OP_160 ? 2 : 4) : type == IT_FIN ? 16 : b < BQ_160 ? 6 : b < BQ_80 ? 12 : 24; }
__device__ __forceinline__ uint32_t item_need(int type, int b) { return type == IT_ATT ? 96 : item_count(type - 1, b); }

struct Ring {
  uint32_t sb, bars; int st; uint32_t ph;
  __device__ __forceinline__ uint32_t wait() const { mbar_wait(bars + 8 * st, ph); return sb + st * PB; }
  __device__ __forceinline__ void next() { if (++st == PS) { st = 0; ph ^= 1; } }
  __device__ __forceinline__ void release(int s) const { if ((threadIdx.x & 31) == 0) mbar_arrive(bars + 8 * (PS + s)); }
  __device__ __forceinline__ void pop() { __syncwarp(); release(st); next(); }
};

template <int N>
__device__ __forceinline__ void gemm_item(Ring& r, float* d, int nst, uint32_t go, int go_at, uint32_t wg) {
  auto desc = [](uint32_t lo, uint32_t hi) { uint64_t x; asm("mov.b64 %0, {%1, %2};" : "=l"(x) : "r"(lo), "r"(hi)); return x; };
  auto stage = [&](auto first) {
    const uint32_t base = (r.wait() & 0x3ffff) >> 4, a = base + wg * 256 + (8 << 16), w = base + 512 + (256 << 16);
    wg_fence();
#pragma unroll
    for (int kk = 0; kk < 2; kk++) {
      const uint64_t da = desc(a + kk * 16, 32), db = desc(w + kk * 128, 64 | 1 << 30);
      const int acc = kk || !first.value;
      if (N == 80) wg_ss80_01(d, da, db, acc);
      if (N == 160) wg_ss160_01(d, da, db, acc);
      if (N >= 192) wg_ss192_01(d, da, db, acc);
      if (N == 320) wg_ss128_01(d + 96, da, desc(w + kk * 128 + 768, 64 | 1 << 30), acc);
    }
    wg_commit();
  };
  stage(Int<1>());
  int prev = r.st;
  r.next();
#pragma unroll 1
  for (int kb = 1; kb < nst; kb++) {
    stage(Int<0>());
    if (kb == go_at && threadIdx.x == 0) mbar_arrive(go);
    wg_wait<1>();
    r.release(prev);
    prev = r.st;
    r.next();
  }
  wg_wait<0>();
  reg_fence<N / 2>(d);
  r.release(prev);
}

template <int HALF>
__device__ __forceinline__ void attn_a_warp(Ring& r, const uint32_t (&q)[48], int b, int h) {
  constexpr int NT = HALF ? 5 : 3, NF = 8 * NT;
  const int lane = threadIdx.x & 31, g = lane >> 2, c = lane & 3, seg = (threadIdx.x >> 5) & 3;
  uint32_t f[6][NF];
  int slot[6];
  auto fetch = [&](int u) {
    const uint32_t kv = r.wait() + seg * KV_BYTES;
    slot[u] = r.st;
    r.next();
#pragma unroll
    for (int w = 0; w < 4; w++) {
      uint32_t* d = &f[u][2 * NT * w];
#pragma unroll
      for (int t = 0; t <= HALF; t++) {
        if (u < 3) {
          ldsm4(d + 4 * t, kv + w * 1024 + t * 512 + (lane & 8) * 32 + (lane & 16) * 8 + (lane & 7) * 16);
        } else {
          const uint4 v = lds128(kv + w * 1024 + t * 512 + lane * 16);
          d[4 * t] = v.x; d[4 * t + 1] = v.y; d[4 * t + 2] = v.z; d[4 * t + 3] = v.w;
        }
      }
      const uint2 m = lds64(kv + KV_M + w * 256 + lane * 8);
      d[2 * NT - 2] = m.x; d[2 * NT - 1] = m.y;
    }
    pdl_launch();
  };
  float s[NT][4] = {};
  fetch(0);
#pragma unroll
  for (int u = 0; u < 3; u++) {
    fetch(u + 1);
#pragma unroll
    for (int kk = 0; kk < 4; kk++) {
      const uint32_t* a = &q[16 * u + 4 * kk];
#pragma unroll
      for (int n = 0; n < NT; n++) mma16(s[(n + 1) % NT], a[0], a[1], a[2], a[3], f[u][2 * NT * kk + 2 * n], f[u][2 * NT * kk + 2 * n + 1]);
    }
    r.release(slot[u]);
    pdl_launch();
  }
  fetch(4);
  const float k2 = 0.07216878364870322f * 1.44269504089f, NEG = -INFINITY;
  if (2 * c > g) { s[NT - 2][0] = NEG; s[NT - 1][2] = NEG; }
  if (2 * c + 1 > g) { s[NT - 2][1] = NEG; s[NT - 1][3] = NEG; }
  s[NT - 1][0] = s[NT - 1][1] = NEG;
  uint32_t pp[NT][2]; float inv[2];
#pragma unroll
  for (int hh = 0; hh < 2; hh++) {
    float m = NEG, l = 0.f;
#pragma unroll
    for (int n = 0; n < NT; n++) m = fmaxf(m, fmaxf(s[n][2 * hh], s[n][2 * hh + 1]));
    m = fmaxf(m, __shfl_xor_sync(~0u, m, 1)); m = fmaxf(m, __shfl_xor_sync(~0u, m, 2));
#pragma unroll
    for (int n = 0; n < NT; n++) { const float x = ex2((s[n][2 * hh] - m) * k2), y = ex2((s[n][2 * hh + 1] - m) * k2); l += x + y; pp[n][hh] = pack2(x, y); }
    l += __shfl_xor_sync(~0u, l, 1); l += __shfl_xor_sync(~0u, l, 2);
    asm("rcp.approx.ftz.f32 %0, %1;" : "=f"(inv[hh]) : "f"(l));
  }
  uint32_t* dst = g_o + ((b * 192 + h * 6) * 16 + seg * 4 + HALF * 2) * 128 + lane;
#pragma unroll
  for (int u = 3; u < 6; u++) {
    float o[8][4] = {};
#pragma unroll
    for (int n = 0; n < 8; n++) mma8(o[n], pp[0][0], pp[0][1], f[u][2 * NT * (n >> 1) + 2 * NT - 2 + (n & 1)]);
#pragma unroll
    for (int t = 0; t <= HALF; t++)
#pragma unroll
      for (int n = 0; n < 8; n++) {
        const uint32_t* v = &f[u][2 * NT * (n >> 1) + 4 * t + 2 * (n & 1)];
        mma16(o[n], pp[1 + 2 * t][0], pp[1 + 2 * t][1], pp[2 + 2 * t][0], pp[2 + 2 * t][1], v[0], v[1]);
      }
    r.release(slot[u]);
    if (u == 3) fetch(5);
#pragma unroll
    for (int n = 0; n < 8; n++) {
      dst[(u - 3) * 4096 + (n >> 2) * 2048 + (n & 3) * 32] = pack2(o[n][0] * inv[0], o[n][1] * inv[0]);
      dst[(u - 3) * 4096 + (n >> 2) * 2048 + (n & 3) * 32 + 128] = pack2(o[n][2] * inv[1], o[n][3] * inv[1]);
    }
  }
}

__device__ __forceinline__ void fin_item(Ring& r, uint32_t scratch, int b, int idx) {
  const int warp = threadIdx.x >> 5, lane = threadIdx.x & 31;
  float4 v[1][5];
  {
    const uint32_t base = r.wait();
#pragma unroll
    for (int i = 0; i < 5; i++) v[0][i] = unpack4(lds64(base + ((warp * 5 + i) * 32 + lane) * 8));
    r.pop();
  }
#pragma unroll 1
  for (int k = 0; k < op_split(b); k += 2) {
    const uint32_t base = r.wait();
#pragma unroll
    for (int i = 0; i < 10; i++) {
      const uint2 q = lds64(base + ((i / 5 * 40 + warp * 5 + i % 5) * 32 + lane) * 8);
      float4& t = v[0][i % 5];
      t.x += bf_lo(q.x); t.y += bf_hi(q.x); t.z += bf_lo(q.y); t.w += bf_hi(q.y);
    }
    r.pop();
  }
#pragma unroll
  for (int i = 0; i < 5; i++) g_x[((b * 16 + idx) * 40 + warp * 5 + i) * 32 + lane] = pack4(v[0][i]);
  float mean[1], rs[1];
  ln_stats<1>(v, scratch, mean, rs);
#pragma unroll
  for (int i = 0; i < 5; i++) {
    const int u = warp * 5 + i;
    uint32_t* xn = g_xn + ((b * 20 + (u >> 1)) * 16 + idx) * 128 + (u & 1) * 64 + lane;
    xn[0] = pack2((v[0][i].x - mean[0]) * rs[0], (v[0][i].y - mean[0]) * rs[0]);
    xn[32] = pack2((v[0][i].z - mean[0]) * rs[0], (v[0][i].w - mean[0]) * rs[0]);
  }
}

__global__ void __launch_bounds__(384, 1) post_kernel(const __grid_constant__ PostParams p) {
  extern __shared__ __align__(1024) uint8_t smem_raw[];
  const uint32_t sb = s2u(smem_raw), bars = sb + PS * PB;
  const uint32_t bIF = bars + 128, bIE = bars + 160, done = bars + 192, bGo = bars + 224, slots = bars + 240, scratch = bars + 512;
  const int warp = __shfl_sync(~0u, threadIdx.x >> 5, 0), lane = threadIdx.x & 31;
  if (warp == 9) PST(0);
  if (warp == 0 && blockIdx.x < 36) TRACE(0);
  if (warp >= 8) {
    asm volatile("setmaxnreg.dec.sync.aligned.u32 56;");
    if (warp == 10) {
      pdl_launch();
      if (sb & 1023) __trap();
      if (lane < 29) mbar_init(bars + 8 * lane, lane < 8 ? 1 : lane < 16 ? 8 : lane < 20 ? 1 : lane < 24 ? 2 : lane < 28 ? 8 : 1);
      if (lane == 0) sts32(slots + 16, p.gap);
      fence_async();
    }
    if (warp == 8 && lane < 5) asm volatile("prefetch.tensormap [%0];" :: "l"(&p.wq + lane) : "memory");
    if (warp != 9) bar_sync(2, 384);
    if (warp == 9) {
      PST(1);
      const int b = lane & 15;
      bool queries = QA_END < 16 && blockIdx.x < 36;
      for (int n = 0;; n++) {
        if (n > 0) { mbar_wait(bGo, (n - 1) & 1); mbar_wait(bIE + 8 * (n & 3), ((n >> 2) & 1) ^ 1); }
        int code = -1, spin = 0, ticket = 0;
        if (queries) {
          if (lane == 0) ticket = n == 0 ? blockIdx.x : 36 + atomicAdd(g_sync + SY_QC, 1);
          ticket = __shfl_sync(~0u, ticket, 0);
          queries = ticket < (16 - QA_END) * 32;
          if (queries) code = IT_Q << 16 | (QA_END + ticket % (16 - QA_END)) << 8 | ticket / (16 - QA_END);
        }
        if (!queries && lane == 0) asm volatile("atom.relaxed.gpu.global.add.u32 %0, [%1], 1;" : "=r"(ticket) : "l"(g_sync + SY_T) : "memory");
        while (!queries) {
          const uint4 hd = ldg_strong128(g_sync + b * 8), pr = ldg_strong128(g_sync + b * 8 + 4);
          if (n == 0 && spin == 0 && hd.x != 0x7fffffff) PST(2);
          const uint32_t hv[4] = {hd.x, hd.y, hd.z, hd.w}, pv[4] = {pr.x, pr.y, pr.z, pr.w};
          const uint32_t chain_done = __ballot_sync(~0u, (pr.x & 0xffff) >= 96) & 0xffff;
          int left[4], avail[4], rdy = 0, claimed = 0, upstream = 0;
#pragma unroll
          for (int t = 0; t < 4; t++) {
            const int cnt = lane < 16 ? item_count(t, b) : 0;
            left[t] = max(cnt - (int)hv[t], 0);
            claimed += cnt - left[t];
            const bool ready = (pv[t] & 0xffff) >= item_need(t, b);
            rdy |= ready << t;
            bool ok = ready || (t == IT_ATT ? pr.x >= 0x10000 : !upstream || (t == IT_OP && (chain_done >> 15 & 1)));
            if (t == IT_BQ && (chain_done >> BQ_HOLD & 1) && !(chain_done >> 15)) ok = false;
            avail[t] = ok ? left[t] : 0;
            upstream |= __any_sync(~0u, left[t] > 0);
          }
          if (!upstream) break;
          int rank = max(__shfl_sync(~0u, ticket, 0) - __reduce_add_sync(~0u, claimed), 0), type = -1, mine = 0;
          {
            const int a = b >= BQ_RUSH && (rdy >> IT_BQ & 1) ? avail[IT_BQ] : 0, tot = __reduce_add_sync(~0u, a);
            if (rank < tot) { type = IT_BQ; mine = a; } else rank -= tot;
            avail[IT_BQ] -= a;
          }
#pragma unroll
          for (int c = 0; c < 8; c++) {
            const int t = c == PR_FIN || c == 5 ? IT_FIN : c == PR_ATT || c == 7 ? IT_ATT : c == PR_OP || c == 4 ? IT_OP : IT_BQ;
            int a = c == PR_ATT || ((rdy >> t & 1) == (c < 4)) ? avail[t] : 0;
            if (t == IT_OP && OP_EARLY) a = c == PR_OP ? avail[t] : 0;
            if (c == 7) a = b < QA_END && !(rdy & 1) && ((chain_done << 1 | 1) >> b & 1) ? left[t] : 0;
            const int tot = __reduce_add_sync(~0u, a);
            if (type < 0) { if (rank < tot) { type = t; mine = a; } else rank -= tot; }
          }
          if (type >= 0) {
#pragma unroll
            for (int o = 1; o < 16; o <<= 1) { const int y = __shfl_up_sync(~0u, mine, o); if (lane >= o) mine += y; }
            const int blk = __ffs(__ballot_sync(~0u, mine > rank)) - 1;
            const int early = !(__shfl_sync(~0u, rdy, blk) >> type & 1);
            uint32_t idx = 0;
            if (n == 0 && spin == 0) PST(3);
            if (lane == 0) asm volatile("atom.relaxed.gpu.global.add.u32 %0, [%1], 1;" : "=r"(idx) : "l"(g_sync + blk * 8 + type) : "memory");
            ld_acquire(g_sync + blk * 8 + 4 + type);
            idx = __shfl_sync(~0u, idx, 0);
            if (idx < item_count(type, blk)) { code = (__shfl_sync(~0u, pr.y, 15) < 32) << 23 | (chain_done >> 15 & 1) << 22 | (chain_done >> p.look & 1) << 21 | early << 20 | type << 16 | blk << 8 | idx; break; }
          } else {
            __nanosleep(50);
          }
          spin_guard(spin);
        }
        if (n == 0) bar_sync(2, 384);
        if (lane == 0) {
          fence_async_global();
          sts32(slots + 4 * (n & 3), code);
          mbar_arrive(bIF + 8 * (n & 3));
        }
        __syncwarp();
        if (code < 0) break;
      }
    } else if (warp == 8) {
      if (elect()) {
        uint32_t dst = sb, bar = bars, ph = 1, next = clk32(), gap = 0;
        auto acquire = [&](uint32_t kb) {
          mbar_wait(bar + 8 * PS, ph);
          mbar_expect(bar, kb * 1024);
          if (gap) {
            uint32_t now;
            do now = clk32(); while ((int)(now - next) < 0);
            next = ((int)(now - next) > 100 ? now - 100 : next) + kb * gap;
          }
        };
        auto advance = [&]() { dst += PB; bar += 8; if (dst == bars) { dst = sb; bar = bars; ph ^= 1; } };
        auto depend = [&](const uint32_t* c, uint32_t need) { wait_count(c, need); fence_async_global(); };
#pragma unroll 1
        for (int n = 0;; n++) {
          mbar_wait(bIF + 8 * (n & 3), (n >> 2) & 1);
          const int code = (int)lds32(slots + 4 * (n & 3));
          if (code < 0) break;
          const int type = (code >> 16) & 15, b = (code >> 8) & 255, idx = code & 255;
          const bool early = code >> 20 & 1, go = !(code >> 21 & 1);
          mbar_arrive(bIE + 8 * (n & 3));
          gap = !(code >> 22 & 1) ? lds32(slots + 16) : type == IT_ATT || type == IT_FIN ? 0 : p.gap2;
          const uint32_t* progress = g_sync + b * 8 + 4 + type;
          if (type == IT_ATT && b >= QA_END) {
            depend(g_sync + SY_Q, (16 - QA_END) * 32);
#pragma unroll 1
            for (int u = 0; u < 2; u++) { acquire(24); bulk_load_last(dst, g_q + (((b - QA_END) * 32 + idx) * 2 + u) * 1536, 24576, bar); advance(); }
          } else if (type == IT_FIN) {
            acquire(10);
            bulk_load(dst, g_x + (b * 16 + idx) * 1280, 10240, bar);
            advance();
            if (early) depend(progress, item_need(type, b));
            if (go) mbar_arrive(bGo);
            const uint2* src = g_part + (b * 16 + idx) * 16 * 1280;
#pragma unroll 1
            for (int i = 0; i < op_split(b); i += 2) { acquire(20); bulk_load_last(dst, src + i * 1280, 20480, bar); advance(); }
            if (!go && p.pol) mbar_arrive(bGo);
          } else {
            const bool op = type == IT_OP, bq = type == IT_BQ;
            const int width = op ? op_width(b) : bq ? bq_width(b) : 192, nb = (width + 63) >> 6, lt = width == 320 ? 1 : 2;
            const int nst = op ? 192 / op_split(b) : 20, kb0 = op ? (idx >> lt) * nst : 0;
            const int col = (op ? idx & ((1 << lt) - 1) : idx) * width;
            const bool whole = !(width & 63);
            const CUtensorMap* m = op ? (whole ? &p.wo : &p.wo2) : bq ? (whole ? &p.wb : &p.wb2) : &p.wq;
            const uint32_t* a = op ? g_o + (b * 192 + kb0) * 2048 : g_xn + b * 20 * 2048;
            int row = kb0 * 32, pre = early && (op || bq) ? min(nst, PRE_MAX) : 0;
            int slow = (code >> 22 & 3) == 3 ? p.slow_n : 0;
            if (slow) gap = p.slow_gap;
            auto weights = [&]() {
              if (slow && --slow == 0) gap = 0;
              acquire(8 + nb * 4);
              if (whole) {
                tma_load3z(dst + 8192, m, row, col >> 6, bar);
              } else {
                tma_load(dst + 8192, m, col, row, bar); tma_load(dst + 12288, m, col + 64, row, bar);
                if (nb == 3) tma_load(dst + 16384, m, col + 128, row, bar);
              }
              row += 32;
            };
            if (pre) {
              uint32_t da = dst, ba = bar;
#pragma unroll 1
              for (int kb = 0; kb < pre; kb++) { weights(); advance(); }
              depend(progress, item_need(type, b));
#pragma unroll 1
              for (int kb = 0; kb < pre; kb++) {
                bulk_load(da, a, 8192, ba);
                a += 2048; da += PB; ba += 8;
                if (da == bars) { da = sb; ba = bars; }
              }
            }
#pragma unroll 1
            for (int kb = pre; kb < nst; kb++) { weights(); if (op && OEF) bulk_load_last(dst, a, 8192, bar); else bulk_load(dst, a, 8192, bar); a += 2048; advance(); }
          }
          if (type == IT_ATT) {
            if (early) depend(progress, 96);
            if (go) mbar_arrive(bGo);
            const uint8_t* src = g_kv + (size_t)(idx * 6 * NSEG + b * 4) * KV_BYTES;
#pragma unroll 1
            for (int u = 0; u < 6; u++) {
              acquire(20);
              bulk_load_last(dst, src, 20480, bar);
              src += u == 2 ? -3 * KV_V : 2 * KV_V;
              advance();
            }
            if (!go && p.pol && ATT_LOOK) mbar_arrive(bGo);
          }
        }
      }
    } else if (warp == 11) {
      uint32_t smid, nsm, used = 0;
      asm("mov.u32 %0, %%smid;" : "=r"(smid)); asm("mov.u32 %0, %%nsmid;" : "=r"(nsm));
      for (int n = 0; n < 64 && used < 96; n++) {
        uint32_t peers = 0;
        used = 0;
        for (uint32_t i = lane; i < min(nsm, 256u); i += 32) {
          const bool taken = ldg_strong32(g_smuse + i) == p.layer + 1;
          used += taken;
          peers += abs((int)(g_smclk[i] - g_smclk[smid & 255])) < 4000 && !taken;
        }
        used = __reduce_add_sync(~0u, used);
        sts32(slots + 16, max(p.gap, (int)min(__reduce_add_sync(~0u, peers), 18u) * p.share >> 3));
      }
    } else if (warp == 10 && lane == 0) {
      for (int n = 0;; n++) {
        mbar_wait(bIF + 8 * (n & 3), (n >> 2) & 1);
        const int code = (int)lds32(slots + 4 * (n & 3));
        if (code < 0) break;
        const int type = (code >> 16) & 15, b = (code >> 8) & 255;
        mbar_wait(done + 8 * (n & 3), (n >> 2) & 1);
        if (type != IT_BQ) red_release(type == IT_Q ? g_sync + SY_Q : g_sync + b * 8 + 5 + type, 1);
        mbar_arrive(bIE + 8 * (n & 3));
      }
    }
  } else {
    asm volatile("setmaxnreg.inc.sync.aligned.u32 224;");
    bar_sync(2, 384);
    const int g = lane >> 2, c = lane & 3;
    Ring r = {sb, bars, 0, 0};
#pragma unroll 1
    for (int n = 0;; n++) {
      mbar_wait(bIF + 8 * (n & 3), (n >> 2) & 1);
      const int code = __shfl_sync(~0u, (int)lds32(slots + 4 * (n & 3)), 0);
      if (code < 0) { TRACE(2); break; }
      const int type = (code >> 16) & 15, b = (code >> 8) & 255, idx = code & 255;
      ITEM(code & 0xfffff, 0);
      if (type == IT_ATT || type == IT_Q) {
        uint32_t q[48];
        if (type == IT_Q || b < QA_END) {
          float d[96];
          gemm_item<192>(r, d, 20, bGo, type == IT_Q ? 12 : -1, warp >> 2);
#pragma unroll
          for (int i = 0; i < 48; i++) q[i] = pack2(d[2 * i], d[2 * i + 1]);
        } else {
#pragma unroll
          for (int u = 0; u < 2; u++) {
            const uint32_t base = r.wait() + threadIdx.x * 16;
#pragma unroll
            for (int i = 0; i < 6; i++) {
              const uint4 v = lds128(base + i * 4096);
              q[24 * u + 4 * i] = v.x; q[24 * u + 4 * i + 1] = v.y; q[24 * u + 4 * i + 2] = v.z; q[24 * u + 4 * i + 3] = v.w;
            }
            r.pop();
          }
        }
        if (type == IT_Q) {
          uint4* dst = g_q + ((b - QA_END) * 32 + idx) * 3072 + threadIdx.x;
#pragma unroll
          for (int i = 0; i < 12; i++) dst[i * 256] = make_uint4(q[4 * i], q[4 * i + 1], q[4 * i + 2], q[4 * i + 3]);
        } else if (warp < 4) {
          attn_a_warp<0>(r, q, b, idx);
        } else {
          attn_a_warp<1>(r, q, b, idx);
        }
      } else if (type == IT_FIN) {
        fin_item(r, scratch, b, idx);
      } else {
        float d[160];
        const int width = type == IT_OP ? op_width(b) : bq_width(b), nst = type == IT_OP ? 192 / op_split(b) : 20;
        const int go_at = max(nst - (code >> 21 & 1 ? p.pol : 6), 1);
        if (width == 320) {
          gemm_item<320>(r, d, nst, bGo, go_at, warp >> 2);
        } else if (width == 160 || BQ_80 == 16) {
          gemm_item<160>(r, d, nst, bGo, go_at, warp >> 2);
#pragma unroll
          for (int i = 80; i < 160; i++) d[i] = 0.f;
        } else {
          gemm_item<80>(r, d, nst, bGo, go_at, warp >> 2);
#pragma unroll
          for (int i = 40; i < 160; i++) d[i] = 0.f;
        }
        if (type == IT_OP) {
          const int tiles = DM / width;
          uint2* dst = g_part + (((b * 16 + warp * 2) * 16 + idx / tiles) * 40 + idx % tiles * (width / 16)) * 32 + lane;
#pragma unroll
          for (int u = 0; u < 20; u++) {
            if (u % 5 == 0 && u * 16 >= width) break;
            dst[u * 32] = make_uint2(pack2(d[8 * u], d[8 * u + 1]), pack2(d[8 * u + 4], d[8 * u + 5]));
            dst[(640 + u) * 32] = make_uint2(pack2(d[8 * u + 2], d[8 * u + 3]), pack2(d[8 * u + 6], d[8 * u + 7]));
          }
        } else {
          const int row = b * 128 + warp * 16 + g;
          const int h0 = idx * (width / 20);
          const float sc = h0 < 32 ? 0.22360679775f * 1.44269504089f : 1.f;
          const bool lo = c < 2;
          uint32_t* da = g_bqkv + (h0 * 256 + (row >> 3)) * 96 + lane;
          uint32_t* db = da + 256 * 96 + (lo ? 2 : -2);
          uint32_t pad[2];
#pragma unroll
          for (int rr = 0; rr < 2; rr++) pad[rr] = c & 1 || h0 < 32 ? 0u : h0 >= 64 ? 0x00003f80u : poly_group((row >> 3) + rr) ? 0x3f803f80u : 0u;
#pragma unroll
          for (int q = 0; q < 8; q++) {
            if (!(q & 1) && q * 40 >= width) break;
#pragma unroll
            for (int rr = 0; rr < 2; rr++) {
              uint32_t w[5];
#pragma unroll
              for (int i = 0; i < 5; i++) w[i] = pack2(d[20 * q + 4 * i + 2 * rr] * sc, d[20 * q + 4 * i + 2 * rr + 1] * sc);
              const int o = q * 2 * 256 * 96 + rr * 96;
              da[o] = w[0]; da[o + 32] = w[1]; da[o + 64] = lo ? w[2] : pad[rr];
              db[o] = lo ? w[3] : w[2]; db[o + 32] = lo ? w[4] : w[3]; db[o + 64] = lo ? pad[rr] : w[4];
            }
          }
        }
      }
      __syncwarp();
      if (lane == 0) mbar_arrive(done + 8 * (n & 3));
      if ((code >> 21 & 1) && (p.pol == 0 || (type == IT_ATT && !ATT_LOOK)) && threadIdx.x == 128) mbar_arrive(bGo);
      ITEM(code & 0xfffff, 1);
    }
  }
}

constexpr int AB_SMEM = 1024 + 98304 + 51200 + 4 * 16384 + 256 + 10240;
#define AB_LW 1
#define AB_U 8
#define AB_WG 4
constexpr int AB_T = AB_WG * 128, AB_PASS = 8 / AB_WG;
__device__ __forceinline__ uint32_t fma2(uint32_t a, uint32_t b, uint32_t c) { uint32_t r; asm("fma.rn.bf16x2 %0, %1, %2, %3;" : "=r"(r) : "r"(a), "r"(b), "r"(c)); return r; }
__device__ __forceinline__ uint32_t ex2_pair(float a, float b, uint32_t one, uint32_t c0) {
  const uint32_t e = __byte_perm(__float_as_uint(a), __float_as_uint(b), 0x6521);
  uint32_t x, r;
  asm("lop3.b32 %0, %1, 0x007f007f, %2, 0xEA;" : "=r"(x) : "r"(e), "r"(one));
  const uint32_t m = fma2(fma2(c0, x, 0x3c0d3c0du), x, 0x3f2b3f2bu);
  asm("lop3.b32 %0, %1, %2, 0x7f807f80, 0xE4;" : "=r"(r) : "r"(e), "r"(m));
  return r;
}
__device__ __forceinline__ float sq2(uint32_t w) { const float a = bf_lo(w), b = bf_hi(w); return fmaf(a, a, b * b); }

__device__ __forceinline__ void attn_b_store(const float* o, int h, int row0, int lane) {
  const int g = lane >> 2, c = lane & 3;
  const float i0 = __frcp_rn(__shfl_sync(~0u, o[8], (lane & ~3) | 2)), i1 = __frcp_rn(__shfl_sync(~0u, o[10], (lane & ~3) | 2));
#pragma unroll
  for (int jj = 0; jj < 3; jj++) {
    if (jj < 2 || c < 2) {
      const int col = h * 20 + 8 * jj + 2 * c;
      uint32_t* dst = g_of + (((row0 >> 7) * 10 + (col >> 6)) * 16 + (row0 >> 3 & 15)) * 256 + (col >> 3 & 7) * 32 + g * 4 + (col >> 1 & 3);
      dst[0] = pack2(o[4 * jj] * i0, o[4 * jj + 1] * i0);
      dst[256] = pack2(o[4 * jj + 2] * i1, o[4 * jj + 3] * i1);
    }
  }
}

struct AbParams { Weights next; uint32_t* done; uint32_t* out; };
__global__ void __launch_bounds__(AB_T + 32, 1) attn_b_kernel(const __grid_constant__ AbParams p) {
  extern __shared__ uint8_t smem_raw[];
  const uint32_t sb = (s2u(smem_raw) + 1023) & ~1023u, sK = sb, sV = sb + 98304, bars = sV + 51200 + 4 * 16384;
  const uint32_t bF = bars + 64, bW = bars + 72, bA = bars + 80, bE = bars + 128, smax = bars + 176;
  auto ring = [&](int i) { return i < 2 ? sK + 51200 + i * 16384 : sV + 51200 + (i - 2) * 16384; };
  const int warp = __shfl_sync(~0u, threadIdx.x >> 5, 0), lane = threadIdx.x & 31;
  const int h = blockIdx.x >> 2, quarter = blockIdx.x & 3;
  TRACE(0);
  pdl_launch();
  if (threadIdx.x < 22) mbar_init(bars + 8 * threadIdx.x, threadIdx.x == 8 ? AB_T / 32 : threadIdx.x >= 16 ? 8 : 1);
  if (threadIdx.x == 32) sts64(smax, 0, 0);
  fence_async();
  __syncthreads();
  pdl_wait();
  const int blk = quarter * 4 + (h >> 3), cg = h & 7;
  auto unsafe = [&]() { const float2 m = lds64f(smax); return !(m.x * m.y <= 10000.f); };
  if (warp == AB_T / 32) {
    auto load_w = [&]() {
      mbar_expect(bW, 102400);
      for (int i = 0; i < 4; i++) bulk_load((i < 2 ? sK : sV) + (i & 1) * 25600, g_wb + cg * 6400 + i * 1600, 25600, bW);
    };
    if (elect()) {
      const uint32_t* gk = g_bqkv + (32 + h) * 256 * 96;
#pragma unroll 1
      for (int i = 0; i < 8; i++) {
        if (i >= AB_LW) mbar_wait(bars + 8 * (i - AB_LW), 0);
        mbar_expect(bars + 8 * i, 24576);
        bulk_load_last(sK + i * 12288, gk + i * 3072, 12288, bars + 8 * i);
        bulk_load_last(sV + i * 12288, gk + 32 * 256 * 96 + i * 3072, 12288, bars + 8 * i);
      }
    }
    __syncwarp();
    if (blockIdx.x < NSLOT) for (int i = lane; i < 512; i += 32) reinterpret_cast<uint4*>(pool_at(blockIdx.x * 8192))[i] = make_uint4(0, 0, 0, 0);
    if (blockIdx.x == 127) for (int i = lane; i < SY_N; i += 32) g_sync[i] = 0;
    if (p.next.w[0] && lane == 0) {
      for (int i = 0; i < AB_PF; i++) { const uint32_t t0 = clk32(); while (clk32() - t0 < (i ? AB_PFD : AB_PF0)) __nanosleep(200); prefetch_weights(p.next, i); }
    }
    __syncwarp();
    mbar_wait(bF, 0);
    const bool redo = unsafe();
    if (!redo && lane == 0) load_w();
    if (lane < 16) asm volatile("cp.async.bulk.prefetch.L2.global [%0], 1280;" :: "l"(g_x + ((blk * 16 + lane) * 40 + cg * 5) * 32) : "memory");
    __syncwarp();
    bar_sync(1, AB_T + 32);
    if (lane == 0) {
      ABT(!!p.out, 1);
      red_release(p.done + quarter * 32, 1);
      ABT(!!p.out, 2);
      if (redo) load_w();
      wait_count(p.done + quarter * 32, 32);
      fence_async_global();
      ABT(!!p.out, 3);
      for (int kb = 0; kb < 10; kb++) {
        const int i = kb < 6 ? kb : kb - 6;
        if (kb >= 6) mbar_wait(bE + 8 * i, 0);
        mbar_expect(bA + 8 * i, 16384);
        bulk_load(ring(i), g_of + (blk * 10 + kb) * 4096, 16384, bA + 8 * i);
      }
    }
    return;
  }
  float qmax = 0.f;
  const uint32_t one = opaque(0x3f803f80u + (threadIdx.x >> 10)), c0 = opaque(0x3ea83ea8u + (threadIdx.x >> 10));
#pragma unroll 1
  for (int pass = 0; pass < AB_PASS; pass++) {
    const int row0 = quarter * 512 + ((warp >> 2) * AB_PASS + pass) * 64 + (warp & 3) * 16;
    const uint32_t* gq = g_bqkv + (h * 256 + (row0 >> 3)) * 96 + lane;
    const uint32_t q0 = gq[0], q1 = gq[96], q2 = gq[32], q3 = gq[128];
    uint32_t q4 = gq[64], q5 = gq[160];
    const uint32_t z0 = gq[64 + 3 - (lane & 3)], z1 = gq[160 + 3 - (lane & 3)];
    {
      float n0 = sq2(q0) + sq2(q2) + sq2(q4), n1 = sq2(q1) + sq2(q3) + sq2(q5);
      n0 += __shfl_xor_sync(~0u, n0, 1); n1 += __shfl_xor_sync(~0u, n1, 1);
      n0 += __shfl_xor_sync(~0u, n0, 2); n1 += __shfl_xor_sync(~0u, n1, 2);
      qmax = (n0 > qmax || n0 != n0) ? n0 : qmax;
      qmax = (n1 > qmax || n1 != n1) ? n1 : qmax;
    }
    if (pass == AB_PASS - 1) {
      float kmax = 0.f;
#pragma unroll
      for (int i = 0; i < SEQ / AB_T; i++) {
        const int key = threadIdx.x + AB_T * i;
        const uint32_t a = sK + (key >> 3) * 384 + (key & 7) * 16;
        const uint4 x = lds128(a), y = lds128(a + 128);
        const uint2 z = lds64(a + 256);
        const float n = ((sq2(x.x) + sq2(x.y)) + (sq2(x.z) + sq2(x.w))) + ((sq2(y.x) + sq2(y.y)) + (sq2(y.z) + sq2(y.w))) + (sq2(z.x) + sq2(z.y));
        kmax = (n > kmax || n != n) ? n : kmax;
      }
      const uint32_t kb = __reduce_max_sync(~0u, __float_as_uint(kmax) & 0x7fffffffu), qb = __reduce_max_sync(~0u, __float_as_uint(qmax) & 0x7fffffffu);
      if (lane < 2) asm volatile("red.shared.max.u32 [%0], %1;" :: "r"(smax + 4 * lane), "r"(lane ? kb : qb) : "memory");
      __syncwarp();
    }
    if ((lane & 3) == 2) { q4 = 0xBF8043C0u; q5 = 0xBF8043C0u; }
    float o[12];
    auto desc = [](uint32_t lo, uint32_t hi) { uint64_t d; asm("mov.b64 %0, {%1, %2};" : "=l"(d) : "r"(lo), "r"(hi)); return d; };
    const uint32_t k0 = (uint32_t)mkdesc(sK, 128, 0, 0), k1 = (uint32_t)mkdesc(sK + 256, 0, 0, 0), v0 = (uint32_t)mkdesc(sV, 384, 0, 0);
    float sa[16], sb2[16];
    uint32_t pa[8], pb[8];
    auto qk = [&](float* s, uint32_t t) {
      wg_rs32_00(s, q0, q1, q2, q3, desc(k0 + t, 24), 0);
      wg_rs32_00(s, q4, q5, z0, z1, desc(k1 + t, 24), 1);
      wg_commit();
    };
    auto step = [&](float* s, uint32_t* pp, int g0, uint32_t t, uint32_t nx, int acc) {
      wg_wait<1>();
      reg_fence<16>(s);
#pragma unroll
      for (int i = 0; i < 8; i++) pp[i] = poly_group(g0 + (i >> 1)) ? ex2_pair(s[2 * i], s[2 * i + 1], one, c0) : pack2(ex2(s[2 * i]), ex2(s[2 * i + 1]));
      wg_fence();
      wg_rs24_01(o, pp[0], pp[1], pp[2], pp[3], desc(v0 + t, 8), acc);
      wg_rs24_01(o, pp[4], pp[5], pp[6], pp[7], desc(v0 + t + 48, 8), 1);
      qk(s, nx);
    };
    if (pass == 0) mbar_wait(bars, 0);
    wg_fence();
    qk(sa, 0);
    qk(sb2, 96);
#pragma unroll 1
    for (uint32_t t = 0; t < 64 * 96; t += AB_U * 96) {
      const uint32_t nx = t + AB_U * 96 < 64 * 96 ? t + AB_U * 96 : 0;
      if (pass == AB_PASS - 1 && t == 40 * 96 && lane == 0) mbar_arrive(bF);
#pragma unroll
      for (int u = 0; u < AB_U; u += 2) {
        if (u == AB_U - 2 && pass == 0) mbar_wait(bars + 8 * (nx / 768), 0);
        step(sa, pa, 0, t + u * 96, u + 2 < AB_U ? t + (u + 2) * 96 : nx, u | t);
        step(sb2, pb, 4, t + u * 96 + 96, (u + 2 < AB_U ? t + (u + 2) * 96 : nx) + 96, 1);
      }
    }
    wg_wait<0>();
    reg_fence<12>(o); reg_fence<16>(sa); reg_fence<16>(sb2);
    attn_b_store(o, h, row0, lane);
  }
  mbar_wait(bF, 0);
  if (unsafe())
#pragma unroll 1
  for (int pass = 0; pass < AB_PASS; pass++) {
    const int row0 = quarter * 512 + ((warp >> 2) * AB_PASS + pass) * 64 + (warp & 3) * 16;
    const uint32_t* gq = g_bqkv + (h * 256 + (row0 >> 3)) * 96 + lane;
    const uint32_t q0 = gq[0], q1 = gq[96], q2 = gq[32], q3 = gq[128], q4 = gq[64], q5 = gq[160];
    float o[12];
#pragma unroll
    for (int i = 0; i < 12; i++) o[i] = 0.f;
    float m0 = -INFINITY, m1 = -INFINITY;
#pragma unroll 1
    for (int kt = 0; kt < 32; kt++) {
      float s[32];
      const uint64_t dk = mkdesc(sK + kt * 3072, 128, 384, 0), dk2 = mkdesc(sK + kt * 3072 + 256, 0, 384, 0);
      wg_fence();
      wg_rs64_00(s, q0, q1, q2, q3, dk, 0);
      wg_rs64_00(s, q4, q5, 0, 0, dk2, 1);
      wg_commit();
      wg_wait<0>();
      reg_fence<32>(s); reg_fence<12>(o);
      float n0 = m0, n1 = m1;
#pragma unroll
      for (int jj = 0; jj < 8; jj++) { n0 = fmaxf(n0, fmaxf(s[4 * jj], s[4 * jj + 1])); n1 = fmaxf(n1, fmaxf(s[4 * jj + 2], s[4 * jj + 3])); }
      n0 = fmaxf(n0, __shfl_xor_sync(~0u, n0, 1)); n0 = fmaxf(n0, __shfl_xor_sync(~0u, n0, 2));
      n1 = fmaxf(n1, __shfl_xor_sync(~0u, n1, 1)); n1 = fmaxf(n1, __shfl_xor_sync(~0u, n1, 2));
      const float r0 = ex2(m0 - n0), r1 = ex2(m1 - n1);
      m0 = n0; m1 = n1;
#pragma unroll
      for (int jj = 0; jj < 3; jj++) { o[4 * jj] *= r0; o[4 * jj + 1] *= r0; o[4 * jj + 2] *= r1; o[4 * jj + 3] *= r1; }
      uint32_t pp[16];
#pragma unroll
      for (int jj = 0; jj < 8; jj++) {
        pp[2 * jj] = pack2(ex2(s[4 * jj] - m0), ex2(s[4 * jj + 1] - m0));
        pp[2 * jj + 1] = pack2(ex2(s[4 * jj + 2] - m1), ex2(s[4 * jj + 3] - m1));
      }
      const uint64_t dv = mkdesc(sV + kt * 3072, 384, 128, 0);
      wg_fence();
#pragma unroll
      for (int kk = 0; kk < 4; kk++) wg_rs24_01(o, pp[4 * kk], pp[4 * kk + 1], pp[4 * kk + 2], pp[4 * kk + 3], dv + kk * 48, 1);
      wg_commit();
    }
    wg_wait<0>();
    reg_fence<12>(o);
    attn_b_store(o, h, row0, lane);
  }
  ABT(!!p.out, 0);
  bar_arrive(1, AB_T + 32);
  if (warp >= 12) return;
  const int g = lane >> 2, c = lane & 3;
  const bool live = opaque(threadIdx.x) < 256;
  float d[40] = {};
  uint2* x = g_x + ((blk * 16 + warp * 2) * 40 + cg * 5) * 32 + lane;
  if (warp < 8) {
#pragma unroll
  for (int i = 0; i < 10; i++) {
    const int r = i / 5, u = i % 5;
    const float4 t = unpack4(x[(r * 40 + u) * 32]);
    d[8 * u + 2 * r] = t.x; d[8 * u + 2 * r + 1] = t.y; d[8 * u + 4 + 2 * r] = t.z; d[8 * u + 5 + 2 * r] = t.w;
  }
  mbar_wait(bW, 0);
  reg_fence<40>(d);
  ABT(!!p.out, 4);
#pragma unroll 1
  for (int kb = 0; kb < 10; kb++) {
    const int i = kb < 6 ? kb : kb - 6;
    mbar_wait(bA + 8 * i, kb >= 6);
    const uint64_t da = mkdesc(ring(i) + (warp >> 2) * 8192, 128, 1024, 0), db = mkdesc(kb < 5 ? sK + kb * 10240 : sV + (kb - 5) * 10240, 1280, 128, 0);
    wg_fence();
#pragma unroll
    for (int kk = 0; kk < 4; kk++) wg_ss80_01(d, da + kk * 16, db + kk * 160, 1);
    wg_commit();
    if (kb > 0 && kb < 5) { wg_wait<1>(); if (lane == 0) mbar_arrive(bE + 8 * (kb - 1)); }
  }
  wg_wait<0>();
  reg_fence<40>(d);
  }
  ABT(!!p.out, 5);
  if (p.out) {
    if (warp >= 8) return;
    const uint32_t stage = sK + 83968 + warp * 2560 + (warp < 4 ? 0 : 131328 - 10240);
#pragma unroll
    for (int u = 0; u < 5; u++)
      stsm4(stage + (lane & 15) * 160 + u * 32 + (lane >> 4) * 16, pack2(d[8 * u], d[8 * u + 1]), pack2(d[8 * u + 2], d[8 * u + 3]),
            pack2(d[8 * u + 4], d[8 * u + 5]), pack2(d[8 * u + 6], d[8 * u + 7]));
    __syncwarp();
    uint4* out = reinterpret_cast<uint4*>(p.out + (blk * 128 + warp * 16) * (DM / 2) + cg * 40);
#pragma unroll
    for (int i = 0; i < 5; i++) { const int e = i * 32 + lane, r = e / 10; out[r * (DM / 8) + e - r * 10] = lds128(stage + e * 16); }
  } else {
    float2* stat = g_stat + blk * 1024 + (warp & 7) * 16 + g;
    float mean[2], rs[2];
#pragma unroll
    for (int r = 0; r < 2; r++) {
      float t = 0.f, q = 0.f;
#pragma unroll
      for (int i = 0; i < 10; i++) t += d[4 * i + 2 * r] + d[4 * i + 2 * r + 1];
      t += __shfl_xor_sync(~0u, t, 1); t += __shfl_xor_sync(~0u, t, 2);
      t *= 1.f / 80;
#pragma unroll
      for (int i = 0; i < 10; i++) { const float a = d[4 * i + 2 * r] - t, b = d[4 * i + 2 * r + 1] - t; q += a * a + b * b; }
      q += __shfl_xor_sync(~0u, q, 1); q += __shfl_xor_sync(~0u, q, 2);
      if (c == r && live) asm volatile("st.relaxed.gpu.global.v2.b32 [%0], {%1, %2};" :: "l"(stat + cg * 128 + r * 8), "r"(__float_as_uint(t)), "r"(nz(__float_as_uint(q))) : "memory");
    }
#pragma unroll
    for (int i = 0; i < 10; i++) {
      const int r = i / 5, u = i % 5;
      if (live) x[(r * 40 + u) * 32] = make_uint2(pack2(d[8 * u + 2 * r], d[8 * u + 2 * r + 1]), pack2(d[8 * u + 4 + 2 * r], d[8 * u + 5 + 2 * r]));
    }
    ABT(0, 6);
    uint2 e[4];
    int n = 0;
    do {
#pragma unroll
      for (int i = 0; i < 4; i++)
        asm volatile("ld.relaxed.gpu.global.v2.b32 {%0, %1}, [%2];" : "=r"(e[i].x), "=r"(e[i].y) : "l"(stat + (2 * c + (i & 1)) * 128 + (i >> 1) * 8) : "memory");
      spin_guard(n);
    } while (__any_sync(~0u, min(min(e[0].y, e[1].y), min(e[2].y, e[3].y)) == 0 && live));
#pragma unroll
    for (int r = 0; r < 2; r++) {
      const float m0 = __uint_as_float(e[2 * r].x), m1 = __uint_as_float(e[2 * r + 1].x);
      float t = m0 + m1;
      t += __shfl_xor_sync(~0u, t, 1); t += __shfl_xor_sync(~0u, t, 2);
      t *= 0.125f;
      float q = __uint_as_float(e[2 * r].y) + __uint_as_float(e[2 * r + 1].y) + 80.f * ((m0 - t) * (m0 - t) + (m1 - t) * (m1 - t));
      q += __shfl_xor_sync(~0u, q, 1); q += __shfl_xor_sync(~0u, q, 2);
      mean[r] = t; rs[r] = rsqrtf(q * (1.f / DM) + 1e-5f);
    }
    ABT(0, 7);
    uint32_t w[2][5][2];
#pragma unroll
    for (int i = 0; i < 20; i++) w[i & 1][i >> 2][i >> 1 & 1] = pack2((d[2 * i] - mean[i & 1]) * rs[i & 1], (d[2 * i + 1] - mean[i & 1]) * rs[i & 1]);
    ln_store(w, blk * 8 + warp, cg * 5, live);
  }
  ABT(!!p.out, 8);
  TRACE(2);
}

typedef CUresult (*EncodeFn)(CUtensorMap*, CUtensorMapDataType, cuuint32_t, void*, const cuuint64_t*, const cuuint64_t*,
                             const cuuint32_t*, const cuuint32_t*, CUtensorMapInterleave, CUtensorMapSwizzle,
                             CUtensorMapL2promotion, CUtensorMapFloatOOBfill);

void make_map(EncodeFn enc, CUtensorMap* m, const void* ptr, int cols, int rows, int nb) {
  const cuuint64_t dims[3] = {(cuuint64_t)(nb ? 64 : cols), (cuuint64_t)rows, (cuuint64_t)cols / 64};
  const cuuint64_t strides[2] = {(cuuint64_t)cols * 2, 128};
  const cuuint32_t box[3] = {64, 32, (cuuint32_t)nb}, es[3] = {1, 1, 1};
  enc(m, CU_TENSOR_MAP_DATA_TYPE_BFLOAT16, nb ? 3 : 2, const_cast<void*>(ptr), dims, strides, box, es, CU_TENSOR_MAP_INTERLEAVE_NONE,
      CU_TENSOR_MAP_SWIZZLE_128B, CU_TENSOR_MAP_L2_PROMOTION_L2_128B, CU_TENSOR_MAP_FLOAT_OOB_FILL_NONE);
}
template <class... KA, class... A>
void launch(void (*kern)(KA...), int grid, int block, int smem, int cluster, bool pdl, A... args) {
  cudaFuncSetAttribute(kern, cudaFuncAttributeMaxDynamicSharedMemorySize, smem);
  cudaLaunchConfig_t cfg = {};
  cfg.gridDim = dim3(grid); cfg.blockDim = dim3(block); cfg.dynamicSmemBytes = smem; cfg.stream = cudaStreamPerThread;
  cudaLaunchAttribute at[2];
  int n = 0;
  if (cluster > 1) { at[n].id = cudaLaunchAttributeClusterDimension; at[n].val.clusterDim.x = cluster; at[n].val.clusterDim.y = 1; at[n].val.clusterDim.z = 1; n++; }
  if (pdl) { at[n].id = cudaLaunchAttributeProgrammaticStreamSerialization; at[n].val.programmaticStreamSerializationAllowed = 1; n++; }
  cfg.attrs = at; cfg.numAttrs = n;
  cudaLaunchKernelEx(&cfg, kern, args...);
}
template <class T> void* sym(T& s) { void* p = nullptr; cudaGetSymbolAddress(&p, s); return p; }

}

#define MODE(b) 0
extern "C" void kernel_launch(void* const* d_in, const int* in_sizes, int n_in, void* d_out, int out_size) {
  const __nv_bfloat16* x = (const __nv_bfloat16*)d_in[0];
  void* fn = nullptr; cudaDriverEntryPointQueryResult qr;
  cudaGetDriverEntryPoint("cuTensorMapEncodeTiled", &fn, cudaEnableDefault, &qr);
  EncodeFn enc = (EncodeFn)fn;

  ChainParams ch = {};
  PostParams op = {};
  for (int i = 0; i < 3; i++) {
    const cuuint64_t dims[3] = {HD, 128, 5}, strides[2] = {HD * 2, HD * 256};
    const cuuint32_t box[3] = {64, 128, 5}, es[3] = {1, 1, 1};
    enc(i == 0 ? &ch.wq : i == 1 ? &ch.wk : &ch.wv, CU_TENSOR_MAP_DATA_TYPE_BFLOAT16, 3, d_in[2 + i], dims, strides, box, es, CU_TENSOR_MAP_INTERLEAVE_NONE,
        CU_TENSOR_MAP_SWIZZLE_128B, W_PROMO, CU_TENSOR_MAP_FLOAT_OOB_FILL_NONE);
  }
  {
    const cuuint64_t dims[3] = {DM, HD, 7}, strides[2] = {DM * 2, 64};
    const cuuint32_t box[3] = {32, 64, 7}, es[3] = {1, 1, 1};
    enc(&ch.wo, CU_TENSOR_MAP_DATA_TYPE_BFLOAT16, 3, d_in[5], dims, strides, box, es, CU_TENSOR_MAP_INTERLEAVE_NONE,
        CU_TENSOR_MAP_SWIZZLE_64B, CU_TENSOR_MAP_L2_PROMOTION_L2_128B, CU_TENSOR_MAP_FLOAT_OOB_FILL_NONE);
  }
  ch.mem0 = (const __nv_bfloat16*)d_in[1];
  ch.pool = (uint8_t*)(((uintptr_t)sym(g_pool) + 8191) & ~(uintptr_t)8191); ch.kv = (uint8_t*)sym(g_kv); ch.xc = (const uint32_t*)sym(g_xc); ch.sync = (uint32_t*)sym(g_sync);
  ch.d1 = 0; ch.d1b = 0; ch.d2 = 0; ch.d2b = 0;
  make_map(enc, &op.wq, d_in[2], HD, DM, 3);
  make_map(enc, &op.wo, d_in[5], DM, HD, 5); make_map(enc, &op.wo2, d_in[5], DM, HD, 0);
  make_map(enc, &op.wb, d_in[8], 1920, DM, 5); make_map(enc, &op.wb2, d_in[8], 1920, DM, 0);
  op.gap = 17; op.share = 20; op.look = 20; op.gap2 = 0; op.pol = 1; op.slow_n = 8; op.slow_gap = 23;

  const Weights wa = {{(const uint8_t*)d_in[3], (const uint8_t*)d_in[4], (const uint8_t*)d_in[2], (const uint8_t*)d_in[5]}}, none = {};
  launch(first_kernel, 132, 384, 128 * 1024, 1, false, x, (const uint4*)d_in[9], wa);
  for (int layer = 0; layer < (MODE(4) ? 1 : 2); layer++) {
    ch.layer = ch.d2b = op.layer = layer;
    launch(chain_kernel, 96, 256, CH_SMEM, 3, true, ch);
    launch(post_kernel, MODE(3) ? 36 : 132, 384, OP_SMEM, 1, !MODE(1), op);
    const AbParams ab = {layer == 0 ? wa : none, (uint32_t*)sym(g_bo) + layer * 128, layer == 0 ? nullptr : (uint32_t*)d_out};
    launch(attn_b_kernel, 128, AB_T + 32, AB_SMEM, 1, true, ab);
  }
}
```

```cpp
#include <cuda_runtime.h>
#include <cuda_bf16.h>
#include <cuda.h>
#include <stdint.h>

namespace {

constexpr int SEQ = 2048, DM = 640, HD = 6144, NSEG = 64;
constexpr int SPIN_LIMIT = 1 << 20;

__device__ __align__(128) uint2 g_x[SEQ * DM / 4];
__device__ __align__(128) uint32_t g_of[SEQ * DM / 2];
__device__ __align__(128) uint4 g_wb[DM * DM / 8];
__device__ __align__(16) float2 g_stat[16 * 8 * 128];
__device__ uint32_t g_bo[8 * 32];
__device__ __align__(128) uint4 g_q[SEQ * HD / 8];
__device__ __align__(128) uint32_t g_o[SEQ * HD / 2];
constexpr int KV_BYTES = 5120, KV_M = 4096, KV_V = NSEG * KV_BYTES;
__device__ __align__(128) uint8_t g_kv[96 * 2 * NSEG * KV_BYTES];
__device__ __align__(128) uint32_t g_xc[SEQ * DM / 2];
#define OP_B4 7
#define OP_B8 10
#define OP_B16 16
#define QA_END 11
__host__ __device__ constexpr int op_split(int b) { return b < OP_B4 ? 2 : b < OP_B8 ? 4 : b < OP_B16 ? 8 : 16; }
#define AB_PF 3
#define AB_PF0 0
#define AB_PFD 5000
#define W_PROMO CU_TENSOR_MAP_L2_PROMOTION_L2_128B
#define OP_EARLY 1
#define ATT_LOOK 1
#define PR_FIN 1
#define PR_ATT 0
#define PR_OP 2
#define PRE_MAX PS
#define BQ_RUSH 16
#define MIXP 0
#define OEF 0
#define BQ_HOLD 6
#define WEF 1
#define FK_REP 4
#define CH_PDL 3
#define TRIG 0
#define FK_PF 1
#define BQ_160 10
#define BQ_80 16
#define OP_160 14
__host__ __device__ constexpr int op_width(int b) { return b < OP_160 ? 320 : 160; }
__host__ __device__ constexpr int bq_width(int b) { return b < BQ_160 ? 320 : b < BQ_80 ? 160 : 80; }
__device__ __align__(128) uint2 g_part[16 * 16 * 16 * 40 * 32];
__device__ __align__(128) uint32_t g_xn[SEQ * DM / 2];
constexpr int SY_Q = 128, SY_T = 160, SY_QC = 192, SY_N = 193;
__device__ __align__(16) uint32_t g_sync[SY_N];
constexpr int NSLOT = 92;
__device__ uint32_t g_pool[(NSLOT + 2) * 2048];
__device__ int g_smpart[256], g_orient[NSLOT];
__device__ uint32_t g_smclk[256], g_smuse[256];
__device__ uint32_t g_bqkv[3 * 32 * 256 * 96];

#define ABT(L, i)
#define PST(i)
#define MODE_D(b) 0
#define DELAY(d)
#define XT(i)
#define MISS(k, n)
#define PRO(i)
#define TRACE(w)
#define ITEM(code, w)
#define TR(i, v)
#define TM(i)
#define TM1(i)
#define TMD(i, dep)
#define TMV(i, at, v)

__device__ __forceinline__ uint32_t gtime() { uint32_t c; asm volatile("mov.u32 %0, %%globaltimer_lo;" : "=r"(c) :: "memory"); return c; }
__device__ __forceinline__ uint32_t clk32() { uint32_t c; asm volatile("mov.u32 %0, %%clock;" : "=r"(c) :: "memory"); return c; }
__device__ __forceinline__ uint32_t s2u(const void* p) { return (uint32_t)__cvta_generic_to_shared(p); }
__device__ __forceinline__ uint32_t pack2(float a, float b) {
  uint32_t r; asm("cvt.rn.bf16x2.f32 %0, %1, %2;" : "=r"(r) : "f"(b), "f"(a)); return r; }
__device__ __forceinline__ float bf_lo(uint32_t w) { return __uint_as_float(w << 16); }
__device__ __forceinline__ float bf_hi(uint32_t w) { return __uint_as_float(w & 0xffff0000u); }
__device__ __forceinline__ uint2 pack4(float4 v) { return make_uint2(pack2(v.x, v.y), pack2(v.z, v.w)); }
__device__ __forceinline__ float4 unpack4(uint2 w) { return make_float4(bf_lo(w.x), bf_hi(w.x), bf_lo(w.y), bf_hi(w.y)); }
__device__ __forceinline__ float ex2(float x) { float y; asm("ex2.approx.ftz.f32 %0, %1;" : "=f"(y) : "f"(x)); return y; }

__device__ __forceinline__ void mbar_init(uint32_t bar, uint32_t n) {
  asm volatile("mbarrier.init.shared::cta.b64 [%0], %1;" :: "r"(bar), "r"(n) : "memory"); }
__device__ __forceinline__ void mbar_expect(uint32_t bar, uint32_t bytes) {
  asm volatile("mbarrier.arrive.expect_tx.shared::cta.b64 _, [%0], %1;" :: "r"(bar), "r"(bytes) : "memory"); }
__device__ __forceinline__ void mbar_arrive(uint32_t bar) {
  asm volatile("mbarrier.arrive.shared::cta.b64 _, [%0];" :: "r"(bar) : "memory"); }
__device__ __forceinline__ void mbar_wait(uint32_t bar, uint32_t ph) {
  asm volatile("{.reg .pred p; .reg .u32 n; mov.u32 n, 0;\n"
               "W: mbarrier.try_wait.parity.shared::cta.b64 p, [%0], %1; @p bra D;\n"
               "add.u32 n, n, 1; setp.gt.u32 p, n, %2; @p trap; bra W;\n"
               "D: }" :: "r"(bar), "r"(ph), "n"(SPIN_LIMIT) : "memory");
}
__device__ __forceinline__ void mbar_wait_cluster(uint32_t bar, uint32_t ph) {
  asm volatile("{.reg .pred p; .reg .u32 n; mov.u32 n, 0;\n"
               "W: mbarrier.try_wait.parity.acquire.cluster.shared::cta.b64 p, [%0], %1; @p bra D;\n"
               "add.u32 n, n, 1; setp.gt.u32 p, n, %2; @p trap; bra W;\n"
               "D: }" :: "r"(bar), "r"(ph), "n"(SPIN_LIMIT) : "memory");
}
__device__ __forceinline__ void spin_guard(int& n) {
  asm volatile("{.reg .pred p; add.s32 %0, %0, 1; setp.gt.s32 p, %0, %1; @p trap;}" : "+r"(n) : "n"(SPIN_LIMIT));
}
__device__ __forceinline__ void pdl_wait() { asm volatile("griddepcontrol.wait;" ::: "memory"); TRACE(1); }
__device__ __forceinline__ void pdl_launch() { asm volatile("griddepcontrol.launch_dependents;" ::: "memory"); }
__device__ __forceinline__ uint32_t ld_acquire(const uint32_t* p) { uint32_t v; asm volatile("ld.acquire.gpu.global.u32 %0, [%1];" : "=r"(v) : "l"(p) : "memory"); return v; }
__device__ __forceinline__ void red_release(uint32_t* p, uint32_t v) { asm volatile("red.release.gpu.global.add.u32 [%0], %1;" :: "l"(p), "r"(v) : "memory"); }
__device__ __forceinline__ void red_relaxed(uint32_t* p, uint32_t v) { asm volatile("red.relaxed.gpu.global.add.u32 [%0], %1;" :: "l"(p), "r"(v) : "memory"); }
__device__ __forceinline__ void fence_async_global() { asm volatile("fence.proxy.async.global;" ::: "memory"); }
__device__ __forceinline__ void fence_async() { asm volatile("fence.proxy.async.shared::cta;" ::: "memory"); }
__device__ __forceinline__ void bar_sync(int id, int n) { asm volatile("bar.sync %0, %1;" :: "r"(id), "r"(n) : "memory"); }
__device__ __forceinline__ void bar_arrive(int id, int n) { asm volatile("bar.arrive %0, %1;" :: "r"(id), "r"(n) : "memory"); }
__device__ __forceinline__ void tma_load(uint32_t dst, const CUtensorMap* m, int c0, int c1, uint32_t bar) {
  asm volatile("cp.async.bulk.tensor.2d.shared::cluster.global.mbarrier::complete_tx::bytes [%0], [%1, {%3, %4}], [%2];"
               :: "r"(dst), "l"(m), "r"(bar), "r"(c0), "r"(c1) : "memory"); }
template <bool STREAM = false>
__device__ __forceinline__ void tma_load3(uint32_t dst, const CUtensorMap* m, int c0, int c1, uint32_t bar) {
  if (STREAM)
    asm volatile("{.reg .b64 pol; createpolicy.fractional.L2::evict_first.b64 pol, 1.0;\n"
                 "cp.async.bulk.tensor.3d.shared::cluster.global.mbarrier::complete_tx::bytes.L2::cache_hint [%0], [%1, {%3, %4, 0}], [%2], pol;}"
                 :: "r"(dst), "l"(m), "r"(bar), "r"(c0), "r"(c1) : "memory");
  else
  asm volatile("cp.async.bulk.tensor.3d.shared::cluster.global.mbarrier::complete_tx::bytes [%0], [%1, {%3, %4, 0}], [%2];"
               :: "r"(dst), "l"(m), "r"(bar), "r"(c0), "r"(c1) : "memory"); }
__device__ __forceinline__ void tma_load3z(uint32_t dst, const CUtensorMap* m, int c1, int c2, uint32_t bar) {
  asm volatile("cp.async.bulk.tensor.3d.shared::cluster.global.mbarrier::complete_tx::bytes [%0], [%1, {0, %3, %4}], [%2];"
               :: "r"(dst), "l"(m), "r"(bar), "r"(c1), "r"(c2) : "memory"); }
__device__ __forceinline__ void tma_store(const CUtensorMap* m, uint32_t src, int c0, int c1) {
  asm volatile("cp.async.bulk.tensor.2d.global.shared::cta.bulk_group [%0, {%2, %3}], [%1];"
               :: "l"(m), "r"(src), "r"(c0), "r"(c1) : "memory"); }
__device__ __forceinline__ void tma_store_stream(const CUtensorMap* m, uint32_t src, int c0, int c1) {
  asm volatile("{.reg .b64 pol; createpolicy.fractional.L2::evict_first.b64 pol, 1.0;\n"
               "cp.async.bulk.tensor.2d.global.shared::cta.bulk_group.L2::cache_hint [%0, {%2, %3}], [%1], pol;}"
               :: "l"(m), "r"(src), "r"(c0), "r"(c1) : "memory"); }
__device__ __forceinline__ void bulk_load(uint32_t dst, const void* src, uint32_t bytes, uint32_t bar) {
  asm volatile("cp.async.bulk.shared::cluster.global.mbarrier::complete_tx::bytes [%0], [%1], %2, [%3];"
               :: "r"(dst), "l"(src), "r"(bytes), "r"(bar) : "memory"); }
__device__ __forceinline__ void bulk_load_last(uint32_t dst, const void* src, uint32_t bytes, uint32_t bar) {
  asm volatile("{.reg .b64 pol; createpolicy.fractional.L2::evict_first.b64 pol, 1.0;\n"
               "cp.async.bulk.shared::cluster.global.mbarrier::complete_tx::bytes.L2::cache_hint [%0], [%1], %2, [%3], pol;}"
               :: "r"(dst), "l"(src), "r"(bytes), "r"(bar) : "memory"); }
__device__ __forceinline__ void tma_load_last(uint32_t dst, const CUtensorMap* m, int c0, int c1, uint32_t bar) {
  asm volatile("{.reg .b64 pol; createpolicy.fractional.L2::evict_first.b64 pol, 1.0;\n"
               "cp.async.bulk.tensor.2d.shared::cluster.global.mbarrier::complete_tx::bytes.L2::cache_hint [%0], [%1, {%3, %4}], [%2], pol;}"
               :: "r"(dst), "l"(m), "r"(bar), "r"(c0), "r"(c1) : "memory"); }
__device__ __forceinline__ void bulk_send(uint32_t dst, uint32_t src, uint32_t bytes, uint32_t bar) {
  asm volatile("cp.async.bulk.shared::cluster.shared::cta.mbarrier::complete_tx::bytes [%0], [%1], %2, [%3];"
               :: "r"(dst), "r"(src), "r"(bytes), "r"(bar) : "memory"); }
__device__ __forceinline__ void bulk_store(void* dst, uint32_t src, uint32_t bytes) {
  asm volatile("cp.async.bulk.global.shared::cta.bulk_group [%0], [%1], %2;" :: "l"(dst), "r"(src), "r"(bytes) : "memory"); }
__device__ __forceinline__ void bulk_commit() { asm volatile("cp.async.bulk.commit_group;" ::: "memory"); }
template <int N> __device__ __forceinline__ void bulk_wait_read() { asm volatile("cp.async.bulk.wait_group.read %0;" :: "n"(N) : "memory"); }
template <int N> __device__ __forceinline__ void bulk_wait() { asm volatile("cp.async.bulk.wait_group %0;" :: "n"(N) : "memory"); }

__device__ __forceinline__ uint64_t mkdesc(uint32_t addr, uint32_t lbo, uint32_t sbo, uint32_t sw) {
  return (uint64_t)((addr & 0x3FFFF) >> 4) | ((uint64_t)(lbo >> 4) << 16) | ((uint64_t)(sbo >> 4) << 32) | ((uint64_t)sw << 62); }
__device__ __forceinline__ void wg_fence() { asm volatile("wgmma.fence.sync.aligned;" ::: "memory"); }
__device__ __forceinline__ void wg_commit() { asm volatile("wgmma.commit_group.sync.aligned;" ::: "memory"); }
template <int N> __device__ __forceinline__ void wg_wait() { asm volatile("wgmma.wait_group.sync.aligned %0;" :: "n"(N) : "memory"); }
template <int N> __device__ __forceinline__ void reg_fence(float* d) {
#pragma unroll
  for (int i = 0; i < N; i++) asm volatile("" : "+f"(d[i]) :: "memory");
}

__device__ __forceinline__ void mma16(float* d, uint32_t a0, uint32_t a1, uint32_t a2, uint32_t a3, uint32_t b0, uint32_t b1) {
  asm volatile("mma.sync.aligned.m16n8k16.row.col.f32.bf16.bf16.f32 {%0,%1,%2,%3},{%4,%5,%6,%7},{%8,%9},{%0,%1,%2,%3};"
               : "+f"(d[0]), "+f"(d[1]), "+f"(d[2]), "+f"(d[3]) : "r"(a0), "r"(a1), "r"(a2), "r"(a3), "r"(b0), "r"(b1)); }
__device__ __forceinline__ void mma8(float* d, uint32_t a0, uint32_t a1, uint32_t b0) {
  asm volatile("mma.sync.aligned.m16n8k8.row.col.f32.bf16.bf16.f32 {%0,%1,%2,%3},{%4,%5},{%6},{%0,%1,%2,%3};"
               : "+f"(d[0]), "+f"(d[1]), "+f"(d[2]), "+f"(d[3]) : "r"(a0), "r"(a1), "r"(b0)); }
__device__ __forceinline__ void ldsm4(uint32_t* r, uint32_t a) {
  asm volatile("ldmatrix.sync.aligned.m8n8.x4.shared.b16 {%0,%1,%2,%3},[%4];" : "=r"(r[0]), "=r"(r[1]), "=r"(r[2]), "=r"(r[3]) : "r"(a) : "memory"); }
__device__ __forceinline__ void ldsm4t(uint32_t* r, uint32_t a) {
  asm volatile("ldmatrix.sync.aligned.m8n8.x4.trans.shared.b16 {%0,%1,%2,%3},[%4];" : "=r"(r[0]), "=r"(r[1]), "=r"(r[2]), "=r"(r[3]) : "r"(a) : "memory"); }
__device__ __forceinline__ void ldsm2(uint32_t* r, uint32_t a) {
  asm volatile("ldmatrix.sync.aligned.m8n8.x2.shared.b16 {%0,%1},[%2];" : "=r"(r[0]), "=r"(r[1]) : "r"(a) : "memory"); }
__device__ __forceinline__ void stsm4(uint32_t a, uint32_t r0, uint32_t r1, uint32_t r2, uint32_t r3) {
  asm volatile("stmatrix.sync.aligned.m8n8.x4.shared.b16 [%0], {%1,%2,%3,%4};" :: "r"(a), "r"(r0), "r"(r1), "r"(r2), "r"(r3) : "memory"); }
__device__ __forceinline__ void stsm2t(uint32_t a, uint32_t r0, uint32_t r1) {
  asm volatile("stmatrix.sync.aligned.m8n8.x2.trans.shared.b16 [%0], {%1,%2};" :: "r"(a), "r"(r0), "r"(r1) : "memory"); }
__device__ __forceinline__ void stsm4t(uint32_t a, uint32_t r0, uint32_t r1, uint32_t r2, uint32_t r3) {
  asm volatile("stmatrix.sync.aligned.m8n8.x4.trans.shared.b16 [%0], {%1,%2,%3,%4};" :: "r"(a), "r"(r0), "r"(r1), "r"(r2), "r"(r3) : "memory"); }
__device__ __forceinline__ void st_async128(uint32_t a, uint4 v, uint32_t bar) {
  asm volatile("st.async.shared::cluster.mbarrier::complete_tx::bytes.v4.b32 [%0], {%1,%2,%3,%4}, [%5];" :: "r"(a), "r"(v.x), "r"(v.y), "r"(v.z), "r"(v.w), "r"(bar) : "memory"); }
__device__ __forceinline__ void sts32(uint32_t a, uint32_t v) { asm volatile("st.shared.b32 [%0], %1;" :: "r"(a), "r"(v) : "memory"); }
__device__ __forceinline__ void sts64f(uint32_t a, float x, float y) { asm volatile("st.shared.v2.f32 [%0], {%1,%2};" :: "r"(a), "f"(x), "f"(y) : "memory"); }
__device__ __forceinline__ void sts128(uint32_t a, uint4 v) {
  asm volatile("st.shared.v4.b32 [%0], {%1,%2,%3,%4};" :: "r"(a), "r"(v.x), "r"(v.y), "r"(v.z), "r"(v.w) : "memory"); }
__device__ __forceinline__ void sts128f(uint32_t a, float x, float y, float z, float w) {
  asm volatile("st.shared.v4.f32 [%0], {%1,%2,%3,%4};" :: "r"(a), "f"(x), "f"(y), "f"(z), "f"(w) : "memory"); }
__device__ __forceinline__ float lds32f(uint32_t a) { float v; asm volatile("ld.shared.f32 %0, [%1];" : "=f"(v) : "r"(a) : "memory"); return v; }
__device__ __forceinline__ float2 lds64f(uint32_t a) { float2 v; asm volatile("ld.shared.v2.f32 {%0,%1}, [%2];" : "=f"(v.x), "=f"(v.y) : "r"(a) : "memory"); return v; }
__device__ __forceinline__ float4 lds128f(uint32_t a) {
  float4 v; asm volatile("ld.shared.v4.f32 {%0,%1,%2,%3}, [%4];" : "=f"(v.x), "=f"(v.y), "=f"(v.z), "=f"(v.w) : "r"(a) : "memory"); return v; }
__device__ __forceinline__ uint4 lds128(uint32_t a) {
  uint4 v; asm volatile("ld.shared.v4.b32 {%0,%1,%2,%3}, [%4];" : "=r"(v.x), "=r"(v.y), "=r"(v.z), "=r"(v.w) : "r"(a) : "memory"); return v; }
__device__ __forceinline__ uint4 ldg_strong128(const void* p) {
  uint4 v; asm volatile("ld.relaxed.gpu.global.v4.u32 {%0,%1,%2,%3}, [%4];" : "=r"(v.x), "=r"(v.y), "=r"(v.z), "=r"(v.w) : "l"(p) : "memory"); return v; }
__device__ __forceinline__ void stg_strong32(void* p, uint32_t v) { asm volatile("st.relaxed.gpu.global.u32 [%0], %1;" :: "l"(p), "r"(v) : "memory"); }
__device__ __forceinline__ void stg_strong16(void* p, uint32_t v) { asm volatile("st.relaxed.gpu.global.u16 [%0], %1;" :: "l"(p), "h"((uint16_t)v) : "memory"); }
__device__ __forceinline__ void stg_strong128(void* p, uint4 v) {
  asm volatile("st.relaxed.gpu.global.v4.u32 [%0], {%1,%2,%3,%4};" :: "l"(p), "r"(v.x), "r"(v.y), "r"(v.z), "r"(v.w) : "memory"); }
__device__ __forceinline__ uint32_t mapa(uint32_t a, uint32_t r) {
  uint32_t o; asm("mapa.shared::cluster.u32 %0, %1, %2;" : "=r"(o) : "r"(a), "r"(r)); return o; }
__device__ __forceinline__ void st_async2f(uint32_t a, float x, float y, uint32_t bar) {
  asm volatile("st.async.shared::cluster.mbarrier::complete_tx::bytes.v2.f32 [%0], {%1,%2}, [%3];" :: "r"(a), "f"(x), "f"(y), "r"(bar) : "memory"); }
__device__ __forceinline__ void st_async32(uint32_t a, uint32_t x, uint32_t bar) {
  asm volatile("st.async.shared::cluster.mbarrier::complete_tx::bytes.b32 [%0], %1, [%2];" :: "r"(a), "r"(x), "r"(bar) : "memory"); }
__device__ __forceinline__ uint32_t lds32(uint32_t a) { uint32_t v; asm volatile("ld.shared.b32 %0, [%1];" : "=r"(v) : "r"(a) : "memory"); return v; }
__device__ __forceinline__ void st_async64(uint32_t a, uint32_t x, uint32_t y, uint32_t bar) {
  asm volatile("st.async.shared::cluster.mbarrier::complete_tx::bytes.v2.b32 [%0], {%1,%2}, [%3];" :: "r"(a), "r"(x), "r"(y), "r"(bar) : "memory"); }
__device__ __forceinline__ uint2 lds64(uint32_t a) { uint2 v; asm volatile("ld.shared.v2.b32 {%0,%1}, [%2];" : "=r"(v.x), "=r"(v.y) : "r"(a) : "memory"); return v; }
__device__ __forceinline__ void sts64(uint32_t a, uint32_t x, uint32_t y) { asm volatile("st.shared.v2.b32 [%0], {%1,%2};" :: "r"(a), "r"(x), "r"(y) : "memory"); }
__device__ __forceinline__ uint32_t ldg_strong32(const void* p) { uint32_t v; asm volatile("ld.relaxed.gpu.global.u32 %0, [%1];" : "=r"(v) : "l"(p) : "memory"); return v; }
__device__ __forceinline__ uint32_t transpose8(uint32_t x) { uint32_t r; asm volatile("movmatrix.sync.aligned.m8n8.trans.b16 %0, %1;" : "=r"(r) : "r"(x)); return r; }
__device__ __forceinline__ uint32_t hadd2(uint32_t a, uint32_t b) { uint32_t r; asm("add.rn.bf16x2 %0, %1, %2;" : "=r"(r) : "r"(a), "r"(b)); return r; }
__device__ __forceinline__ uint32_t min4(uint4 v) { return min(__vimin3_u32(v.x, v.y, v.z), v.w); }

__device__ __forceinline__ void wg_ss192_01(float* d, uint64_t da, uint64_t db, int sd) {
  asm volatile("{.reg .pred p; setp.ne.b32 p, %98, 0;\n"
    "wgmma.mma_async.sync.aligned.m64n192k16.f32.bf16.bf16 {%0,%1,%2,%3,%4,%5,%6,%7,%8,%9,%10,%11,%12,%13,%14,%15,%16,%17,%18,%19,%20,%21,%22,%23,%24,%25,%26,%27,%28,%29,%30,%31,%32,%33,%34,%35,%36,%37,%38,%39,%40,%41,%42,%43,%44,%45,%46,%47,%48,%49,%50,%51,%52,%53,%54,%55,%56,%57,%58,%59,%60,%61,%62,%63,%64,%65,%66,%67,%68,%69,%70,%71,%72,%73,%74,%75,%76,%77,%78,%79,%80,%81,%82,%83,%84,%85,%86,%87,%88,%89,%90,%91,%92,%93,%94,%95}, %96, %97, p, 1, 1, 0, 1;}"
    : "+f"(d[0]),"+f"(d[1]),"+f"(d[2]),"+f"(d[3]),"+f"(d[4]),"+f"(d[5]),"+f"(d[6]),"+f"(d[7]),"+f"(d[8]),"+f"(d[9]),"+f"(d[10]),"+f"(d[11]),"+f"(d[12]),"+f"(d[13]),"+f"(d[14]),"+f"(d[15]),"+f"(d[16]),"+f"(d[17]),"+f"(d[18]),"+f"(d[19]),"+f"(d[20]),"+f"(d[21]),"+f"(d[22]),"+f"(d[23]),"+f"(d[24]),"+f"(d[25]),"+f"(d[26]),"+f"(d[27]),"+f"(d[28]),"+f"(d[29]),"+f"(d[30]),"+f"(d[31]),"+f"(d[32]),"+f"(d[33]),"+f"(d[34]),"+f"(d[35]),"+f"(d[36]),"+f"(d[37]),"+f"(d[38]),"+f"(d[39]),"+f"(d[40]),"+f"(d[41]),"+f"(d[42]),"+f"(d[43]),"+f"(d[44]),"+f"(d[45]),"+f"(d[46]),"+f"(d[47]),"+f"(d[48]),"+f"(d[49]),"+f"(d[50]),"+f"(d[51]),"+f"(d[52]),"+f"(d[53]),"+f"(d[54]),"+f"(d[55]),"+f"(d[56]),"+f"(d[57]),"+f"(d[58]),"+f"(d[59]),"+f"(d[60]),"+f"(d[61]),"+f"(d[62]),"+f"(d[63]),"+f"(d[64]),"+f"(d[65]),"+f"(d[66]),"+f"(d[67]),"+f"(d[68]),"+f"(d[69]),"+f"(d[70]),"+f"(d[71]),"+f"(d[72]),"+f"(d[73]),"+f"(d[74]),"+f"(d[75]),"+f"(d[76]),"+f"(d[77]),"+f"(d[78]),"+f"(d[79]),"+f"(d[80]),"+f"(d[81]),"+f"(d[82]),"+f"(d[83]),"+f"(d[84]),"+f"(d[85]),"+f"(d[86]),"+f"(d[87]),"+f"(d[88]),"+f"(d[89]),"+f"(d[90]),"+f"(d[91]),"+f"(d[92]),"+f"(d[93]),"+f"(d[94]),"+f"(d[95])
    : "l"(da), "l"(db), "r"(sd));
}
__device__ __forceinline__ void wg_ss128_01(float* d, uint64_t da, uint64_t db, int sd) {
  asm volatile("{.reg .pred p; setp.ne.b32 p, %66, 0;\n"
    "wgmma.mma_async.sync.aligned.m64n128k16.f32.bf16.bf16 {%0,%1,%2,%3,%4,%5,%6,%7,%8,%9,%10,%11,%12,%13,%14,%15,%16,%17,%18,%19,%20,%21,%22,%23,%24,%25,%26,%27,%28,%29,%30,%31,%32,%33,%34,%35,%36,%37,%38,%39,%40,%41,%42,%43,%44,%45,%46,%47,%48,%49,%50,%51,%52,%53,%54,%55,%56,%57,%58,%59,%60,%61,%62,%63}, %64, %65, p, 1, 1, 0, 1;}"
    : "+f"(d[0]),"+f"(d[1]),"+f"(d[2]),"+f"(d[3]),"+f"(d[4]),"+f"(d[5]),"+f"(d[6]),"+f"(d[7]),"+f"(d[8]),"+f"(d[9]),"+f"(d[10]),"+f"(d[11]),"+f"(d[12]),"+f"(d[13]),"+f"(d[14]),"+f"(d[15]),"+f"(d[16]),"+f"(d[17]),"+f"(d[18]),"+f"(d[19]),"+f"(d[20]),"+f"(d[21]),"+f"(d[22]),"+f"(d[23]),"+f"(d[24]),"+f"(d[25]),"+f"(d[26]),"+f"(d[27]),"+f"(d[28]),"+f"(d[29]),"+f"(d[30]),"+f"(d[31]),"+f"(d[32]),"+f"(d[33]),"+f"(d[34]),"+f"(d[35]),"+f"(d[36]),"+f"(d[37]),"+f"(d[38]),"+f"(d[39]),"+f"(d[40]),"+f"(d[41]),"+f"(d[42]),"+f"(d[43]),"+f"(d[44]),"+f"(d[45]),"+f"(d[46]),"+f"(d[47]),"+f"(d[48]),"+f"(d[49]),"+f"(d[50]),"+f"(d[51]),"+f"(d[52]),"+f"(d[53]),"+f"(d[54]),"+f"(d[55]),"+f"(d[56]),"+f"(d[57]),"+f"(d[58]),"+f"(d[59]),"+f"(d[60]),"+f"(d[61]),"+f"(d[62]),"+f"(d[63])
    : "l"(da), "l"(db), "r"(sd));
}
__device__ __forceinline__ void wg_ss160_01(float* d, uint64_t da, uint64_t db, int sd) {
  asm volatile("{.reg .pred p; setp.ne.b32 p, %82, 0;\n"
    "wgmma.mma_async.sync.aligned.m64n160k16.f32.bf16.bf16 {%0,%1,%2,%3,%4,%5,%6,%7,%8,%9,%10,%11,%12,%13,%14,%15,%16,%17,%18,%19,%20,%21,%22,%23,%24,%25,%26,%27,%28,%29,%30,%31,%32,%33,%34,%35,%36,%37,%38,%39,%40,%41,%42,%43,%44,%45,%46,%47,%48,%49,%50,%51,%52,%53,%54,%55,%56,%57,%58,%59,%60,%61,%62,%63,%64,%65,%66,%67,%68,%69,%70,%71,%72,%73,%74,%75,%76,%77,%78,%79}, %80, %81, p, 1, 1, 0, 1;}"
    : "+f"(d[0]),"+f"(d[1]),"+f"(d[2]),"+f"(d[3]),"+f"(d[4]),"+f"(d[5]),"+f"(d[6]),"+f"(d[7]),"+f"(d[8]),"+f"(d[9]),"+f"(d[10]),"+f"(d[11]),"+f"(d[12]),"+f"(d[13]),"+f"(d[14]),"+f"(d[15]),"+f"(d[16]),"+f"(d[17]),"+f"(d[18]),"+f"(d[19]),"+f"(d[20]),"+f"(d[21]),"+f"(d[22]),"+f"(d[23]),"+f"(d[24]),"+f"(d[25]),"+f"(d[26]),"+f"(d[27]),"+f"(d[28]),"+f"(d[29]),"+f"(d[30]),"+f"(d[31]),"+f"(d[32]),"+f"(d[33]),"+f"(d[34]),"+f"(d[35]),"+f"(d[36]),"+f"(d[37]),"+f"(d[38]),"+f"(d[39]),"+f"(d[40]),"+f"(d[41]),"+f"(d[42]),"+f"(d[43]),"+f"(d[44]),"+f"(d[45]),"+f"(d[46]),"+f"(d[47]),"+f"(d[48]),"+f"(d[49]),"+f"(d[50]),"+f"(d[51]),"+f"(d[52]),"+f"(d[53]),"+f"(d[54]),"+f"(d[55]),"+f"(d[56]),"+f"(d[57]),"+f"(d[58]),"+f"(d[59]),"+f"(d[60]),"+f"(d[61]),"+f"(d[62]),"+f"(d[63]),"+f"(d[64]),"+f"(d[65]),"+f"(d[66]),"+f"(d[67]),"+f"(d[68]),"+f"(d[69]),"+f"(d[70]),"+f"(d[71]),"+f"(d[72]),"+f"(d[73]),"+f"(d[74]),"+f"(d[75]),"+f"(d[76]),"+f"(d[77]),"+f"(d[78]),"+f"(d[79])
    : "l"(da), "l"(db), "r"(sd));
}
__device__ __forceinline__ void wg_ss80_01(float* d, uint64_t da, uint64_t db, int sd) {
  asm volatile("{.reg .pred p; setp.ne.b32 p, %42, 0;\n"
    "wgmma.mma_async.sync.aligned.m64n80k16.f32.bf16.bf16 {%0,%1,%2,%3,%4,%5,%6,%7,%8,%9,%10,%11,%12,%13,%14,%15,%16,%17,%18,%19,%20,%21,%22,%23,%24,%25,%26,%27,%28,%29,%30,%31,%32,%33,%34,%35,%36,%37,%38,%39}, %40, %41, p, 1, 1, 0, 1;}"
    : "+f"(d[0]),"+f"(d[1]),"+f"(d[2]),"+f"(d[3]),"+f"(d[4]),"+f"(d[5]),"+f"(d[6]),"+f"(d[7]),"+f"(d[8]),"+f"(d[9]),"+f"(d[10]),"+f"(d[11]),"+f"(d[12]),"+f"(d[13]),"+f"(d[14]),"+f"(d[15]),"+f"(d[16]),"+f"(d[17]),"+f"(d[18]),"+f"(d[19]),"+f"(d[20]),"+f"(d[21]),"+f"(d[22]),"+f"(d[23]),"+f"(d[24]),"+f"(d[25]),"+f"(d[26]),"+f"(d[27]),"+f"(d[28]),"+f"(d[29]),"+f"(d[30]),"+f"(d[31]),"+f"(d[32]),"+f"(d[33]),"+f"(d[34]),"+f"(d[35]),"+f"(d[36]),"+f"(d[37]),"+f"(d[38]),"+f"(d[39])
    : "l"(da), "l"(db), "r"(sd));
}
__device__ __forceinline__ void wg_rs32_00(float* d, uint32_t a0, uint32_t a1, uint32_t a2, uint32_t a3, uint64_t db, int sd) {
  asm volatile("{.reg .pred p; setp.ne.b32 p, %21, 0;\n"
    "wgmma.mma_async.sync.aligned.m64n32k16.f32.bf16.bf16 {%0,%1,%2,%3,%4,%5,%6,%7,%8,%9,%10,%11,%12,%13,%14,%15}, {%16,%17,%18,%19}, %20, p, 1, 1, 0;}"
    : "+f"(d[0]),"+f"(d[1]),"+f"(d[2]),"+f"(d[3]),"+f"(d[4]),"+f"(d[5]),"+f"(d[6]),"+f"(d[7]),"+f"(d[8]),"+f"(d[9]),"+f"(d[10]),"+f"(d[11]),"+f"(d[12]),"+f"(d[13]),"+f"(d[14]),"+f"(d[15])
    : "r"(a0), "r"(a1), "r"(a2), "r"(a3), "l"(db), "r"(sd));
}
__device__ __forceinline__ void wg_rs64_00(float* d, uint32_t a0, uint32_t a1, uint32_t a2, uint32_t a3, uint64_t db, int sd) {
  asm volatile("{.reg .pred p; setp.ne.b32 p, %37, 0;\n"
    "wgmma.mma_async.sync.aligned.m64n64k16.f32.bf16.bf16 {%0,%1,%2,%3,%4,%5,%6,%7,%8,%9,%10,%11,%12,%13,%14,%15,%16,%17,%18,%19,%20,%21,%22,%23,%24,%25,%26,%27,%28,%29,%30,%31}, {%32,%33,%34,%35}, %36, p, 1, 1, 0;}"
    : "+f"(d[0]),"+f"(d[1]),"+f"(d[2]),"+f"(d[3]),"+f"(d[4]),"+f"(d[5]),"+f"(d[6]),"+f"(d[7]),"+f"(d[8]),"+f"(d[9]),"+f"(d[10]),"+f"(d[11]),"+f"(d[12]),"+f"(d[13]),"+f"(d[14]),"+f"(d[15]),"+f"(d[16]),"+f"(d[17]),"+f"(d[18]),"+f"(d[19]),"+f"(d[20]),"+f"(d[21]),"+f"(d[22]),"+f"(d[23]),"+f"(d[24]),"+f"(d[25]),"+f"(d[26]),"+f"(d[27]),"+f"(d[28]),"+f"(d[29]),"+f"(d[30]),"+f"(d[31])
    : "r"(a0), "r"(a1), "r"(a2), "r"(a3), "l"(db), "r"(sd));
}
__device__ __forceinline__ void wg_rs24_01(float* d, uint32_t a0, uint32_t a1, uint32_t a2, uint32_t a3, uint64_t db, int sd) {
  asm volatile("{.reg .pred p; setp.ne.b32 p, %17, 0;\n"
    "wgmma.mma_async.sync.aligned.m64n24k16.f32.bf16.bf16 {%0,%1,%2,%3,%4,%5,%6,%7,%8,%9,%10,%11}, {%12,%13,%14,%15}, %16, p, 1, 1, 1;}"
    : "+f"(d[0]),"+f"(d[1]),"+f"(d[2]),"+f"(d[3]),"+f"(d[4]),"+f"(d[5]),"+f"(d[6]),"+f"(d[7]),"+f"(d[8]),"+f"(d[9]),"+f"(d[10]),"+f"(d[11])
    : "r"(a0), "r"(a1), "r"(a2), "r"(a3), "l"(db), "r"(sd));
}

#define AB_POLY 0xae
__device__ __forceinline__ constexpr bool poly_group(int group) { return (AB_POLY >> (group & 7)) & 1; }

template <int V> struct Int { static constexpr int value = V; };

template <int NG>
__device__ __forceinline__ void ln_stats(const float4 (&v)[NG][5], uint32_t scratch, float (&mean)[NG], float (&rs)[NG]) {
  const int warp = threadIdx.x >> 5, lane = threadIdx.x & 31;
#pragma unroll
  for (int r = 0; r < NG; r++) {
    float s = 0.f, q = 0.f;
#pragma unroll
    for (int i = 0; i < 5; i++) s += (v[r][i].x + v[r][i].y) + (v[r][i].z + v[r][i].w);
    s += __shfl_xor_sync(~0u, s, 1); s += __shfl_xor_sync(~0u, s, 2);
    s *= 1.f / 80;
#pragma unroll
    for (int i = 0; i < 5; i++) {
      const float x = v[r][i].x - s, y = v[r][i].y - s, z = v[r][i].z - s, w = v[r][i].w - s;
      q += (x * x + y * y) + (z * z + w * w);
    }
    q += __shfl_xor_sync(~0u, q, 1); q += __shfl_xor_sync(~0u, q, 2);
    mean[r] = s; rs[r] = q;
  }
  bar_sync(1, 256);
  if ((lane & 3) == 0) {
#pragma unroll
    for (int r = 0; r < NG; r++) sts64f(scratch + r * 512 + lane * 16 + warp * 8, mean[r], rs[r]);
  }
  bar_sync(1, 256);
#pragma unroll
  for (int r = 0; r < NG; r++) {
    const float4 e = lds128f(scratch + r * 512 + lane * 16);
    float t = e.x + e.z;
    t += __shfl_xor_sync(~0u, t, 1); t += __shfl_xor_sync(~0u, t, 2);
    t *= 0.125f;
    float q = e.y + e.w + 80.f * ((e.x - t) * (e.x - t) + (e.z - t) * (e.z - t));
    q += __shfl_xor_sync(~0u, q, 1); q += __shfl_xor_sync(~0u, q, 2);
    mean[r] = t; rs[r] = rsqrtf(q * (1.f / DM) + 1e-5f);
  }
}

__device__ __forceinline__ void ln_store(const uint32_t (&w)[2][5][2], int tile, int u0, bool live = true) {
  const int lane = threadIdx.x & 31;
  uint32_t* xc = g_xc + ((tile >> 1) * 40 + u0) * 256 + (tile & 1) * 64 + lane;
#pragma unroll
  for (int i = 0; i < 20; i++) if (live) xc[(i >> 1) * 128 + (i & 1) * 32] = w[i & 1][i >> 2][i >> 1 & 1];
#pragma unroll
  for (int i = 0; i < 5; i++) {
    const int u = u0 + i;
    uint32_t* xn = g_xn + (((tile >> 3) * 20 + (u >> 1)) * 16 + (tile & 1) * 8 + (tile & 6)) * 128 + (u & 1) * 64 + lane;
#pragma unroll
    for (int r = 0; r < 2; r++) if (live) { xn[r * 128] = w[r][i][0]; xn[r * 128 + 32] = w[r][i][1]; }
  }
}
__device__ __forceinline__ void wait_count(const uint32_t* c, uint32_t n) {
  int spin = 0;
  while ((ld_acquire(c) & 0xffff) < n) { __nanosleep(32); spin_guard(spin); }
}

__device__ __forceinline__ uint8_t* pool_at(uint32_t off) {
  return reinterpret_cast<uint8_t*>((reinterpret_cast<uintptr_t>(g_pool) + 8191) & ~(uintptr_t)8191) + off; }
struct Weights { const uint8_t* w[4]; };
__device__ __forceinline__ void prefetch_weights(const Weights& p, int i) {
  if (blockIdx.x < 128) asm volatile("cp.async.bulk.prefetch.L2.global [%0], 61440;" :: "l"(p.w[i] + (size_t)blockIdx.x * 61440) : "memory");
}
__global__ void __launch_bounds__(384) first_kernel(const __nv_bfloat16* __restrict__ xin, const uint4* __restrict__ wb, const __grid_constant__ Weights wa) {
  __shared__ __align__(16) float scratch[256];
  __shared__ uint32_t lat[4];
  const int warp = threadIdx.x >> 5, lane = threadIdx.x & 31, cta = blockIdx.x;
  TRACE(0);
  if (warp >= 8) {
    if (warp < 10 || cta < NSLOT) {
      uint32_t* q = reinterpret_cast<uint32_t*>(pool_at((warp < 10 ? NSLOT : cta) * 8192 + (warp & 1) * 4096)) + (warp < 10 ? (cta & 127) * 8 : 0);
      if (lane < 8) stg_strong32(q + lane, 0u);
      uint32_t best = ~0u;
      if (lane == 0) {
        for (int r = 0; r < FK_REP; r++) {
          uint32_t t0, t1, v;
          asm volatile("mov.u32 %0, %%clock;" : "=r"(t0) :: "memory");
          asm volatile("atom.relaxed.gpu.global.exch.b32 %0, [%1], 0;" : "=r"(v) : "l"(q) : "memory");
          asm volatile("{.reg .u32 t; add.u32 t, %1, 1; mov.u32 %0, %%clock; sub.u32 %0, %0, %1;}" : "=r"(t1) : "r"(__shfl_sync(1u, v, 0)) : "memory");
          best = min(best, t1 - t0);
        }
        lat[warp - 8] = best;
      }
    }
    __syncwarp();
    bar_sync(2, cta < 128 ? 384 : 128);
    if (threadIdx.x == 288) for (int i = 0; i < FK_PF; i++) prefetch_weights(wa, i);
    if (threadIdx.x == 256) {
      const int part = lat[0] < lat[1] ? 0 : 1;
      uint32_t smid; asm("mov.u32 %0, %%smid;" : "=r"(smid));
      g_smpart[smid & 255] = part;
      g_smclk[smid & 255] = clk32() - gtime() * 2;
      g_smuse[smid & 255] = 0;
      if (cta < NSLOT) g_orient[cta] = lat[2] < lat[3] ? part : 1 - part;
    }
  } else if (cta < 128) {
    float4 v[2][5];
#pragma unroll
    for (int r = 0; r < 2; r++)
#pragma unroll
      for (int i = 0; i < 5; i++) {
        const uint32_t* src = reinterpret_cast<const uint32_t*>(xin) + (cta * 16 + r * 8 + (lane >> 2)) * (DM / 2) + warp * 40 + i * 8 + (lane & 3);
        const uint32_t a = src[0], b = src[4];
        v[r][i] = make_float4(bf_lo(a), bf_hi(a), bf_lo(b), bf_hi(b));
      }
    uint4 w8[2];
#pragma unroll
    for (int i = 0; i < 2; i++) w8[i] = wb[cta * 400 + min(i * 256 + threadIdx.x, 399)];
    float mean[2], rs[2];
    ln_stats<2>(v, s2u(scratch), mean, rs);
    bar_sync(2, 384);
    ABT(2, 2);
    if (threadIdx.x < 128) g_stat[cta * 128 + threadIdx.x] = make_float2(0.f, 0.f);
#pragma unroll
    for (int i = 0; i < 10; i++) g_x[((cta * 2 + i / 5) * 40 + warp * 5 + i % 5) * 32 + lane] = pack4(v[i / 5][i % 5]);
    uint32_t w[2][5][2];
#pragma unroll
    for (int i = 0; i < 10; i++) {
      const float4 t = v[i / 5][i % 5];
      const float m = mean[i / 5], q = rs[i / 5];
      w[i / 5][i % 5][0] = pack2((t.x - m) * q, (t.y - m) * q); w[i / 5][i % 5][1] = pack2((t.z - m) * q, (t.w - m) * q);
    }
    if (TRIG == 2) pdl_launch();
    ln_store(w, cta, warp * 5);
    if (TRIG == 1) pdl_launch();
    ABT(2, 3);
#pragma unroll
    for (int i = 0; i < 2; i++) {
      const int e = cta * 400 + min(i * 256 + threadIdx.x, 399), k = e / 80, n = e - k * 80, cg = n / 10;
      g_wb[((cg * 80 + (k >> 3)) * 10 + n - cg * 10) * 8 + (k & 7)] = w8[i];
    }
  } else if (cta == 128) {
    g_bo[threadIdx.x] = 0;
  }
  TRACE(2);
}

struct ChainParams {
  CUtensorMap wq, wk, wv, wo;
  const __nv_bfloat16* mem0;
  uint8_t *pool, *kv;
  const uint32_t* xc;
  uint32_t* sync;
  int layer;
  int d0, d3, d1, d1b, d2, d2b, mode;
};
constexpr int CH_WQ = 0, CH_WO = 81920, CH_X = CH_WO + 86016, CH_M = CH_X + 20480, CH_KT = CH_X + 40960, CH_VT = CH_KT + 4096,
              CH_PS = CH_VT + 4096, CH_QK = CH_PS + 4096, CH_VP = CH_QK + 4096, CH_SX = CH_VP + 1024, CH_O = CH_SX + 2304, CH_ID = CH_O + 3072,
              CH_BAR = CH_ID + 512;
constexpr int CH_SMEM = CH_BAR + 256, CH_PB = CH_WQ + 57344;
constexpr int CH_BASE = 1024;
#define CH_VK0 8
#define CH_VK1 20
#define CH_L0 4
#define CH_LR 4
#define NOX 0
#define CH_XA 1
#define CH_XB 4
#define CH_W1 5
#define CH_W2 18
#define CH_W3 26
#define CH_R2 8
#define CH_VA 20
#define CH_EX 2
#define CH_KD 0
#define CH_RP 1
#define CH_KF 10
#define CH_LO 0
#define CH_LR1 4
#define CH_KP 0
#define CH_KM 3
#define CH_SP 1
#define CH_VC 2
#define CH_W0 5
#define CH_WA 3
#define CH_P1 4
#define CH_PW 1
#define CH_KW 3
#define CH_RB 0
#define CH_RC 8
#define CH_D0 230
#define CH_D1 450
#define CH_D2 270
#define CH_R1 4
#define CH_TW 12
__device__ __forceinline__ uint32_t opaque(uint32_t x) { return __shfl_sync(~0u, x, threadIdx.x & 31); }
__device__ __forceinline__ uint32_t nz(uint32_t x) { uint32_t r; asm("max.u32 %0, %1, 1;" : "=r"(r) : "r"(x)); return r; }
__device__ __forceinline__ uint32_t pack_tag(float lo, float hi, uint32_t tag, uint32_t mask) {
  uint32_t r;
  asm("lop3.b32 %0, %1, %2, %3, 0xD8;" : "=r"(r) : "r"(pack2(lo, hi)), "r"(tag), "r"(mask));
  return r;
}
__device__ __forceinline__ uint32_t differ(uint32_t a, uint32_t b, uint32_t t) { uint32_t r; asm("lop3.b32 %0, %1, %2, %3, 0x7E;" : "=r"(r) : "r"(a), "r"(b), "r"(t)); return r; }
__device__ __forceinline__ void mbar_wait_hot(uint32_t bar, uint32_t ph) {
  uint32_t ok;
  asm volatile("{.reg .pred p; mbarrier.try_wait.parity.shared::cta.b64 p, [%1], %2; selp.u32 %0, 1, 0, p;}" : "=r"(ok) : "r"(bar), "r"(ph) : "memory");
  if (__builtin_expect(!ok, 0)) mbar_wait(bar, ph);
}
__device__ __forceinline__ bool elect() {
  uint32_t r; asm volatile("{.reg .pred p; elect.sync _|p, 0xffffffff; selp.u32 %0, 1, 0, p;}" : "=r"(r)); return r; }
__device__ __forceinline__ uint32_t or3(uint32_t a, uint32_t b, uint32_t c) { uint32_t r; asm("lop3.b32 %0, %1, %2, %3, 0xFE;" : "=r"(r) : "r"(a), "r"(b), "r"(c)); return r; }
__device__ __forceinline__ void pin() { pdl_launch(); }
__device__ __forceinline__ void mma16h(float* d, uint32_t a0, uint32_t a2, uint32_t b0, uint32_t b1) {
  asm volatile("{.reg .b32 u, v; mma.sync.aligned.m16n8k16.row.col.f32.bf16.bf16.f32 {%0,%1,%2,%3},{%4,u,%5,v},{%6,%7},{%0,%1,%2,%3};}"
               : "+f"(d[0]), "+f"(d[1]), "+f"(d[2]), "+f"(d[3]) : "r"(a0), "r"(a2), "r"(b0), "r"(b1)); }
__device__ __forceinline__ void mma8h(float* d, uint32_t a0, uint32_t b0) {
  asm volatile("{.reg .b32 u; mma.sync.aligned.m16n8k8.row.col.f32.bf16.bf16.f32 {%0,%1,%2,%3},{%4,u},{%5},{%0,%1,%2,%3};}"
               : "+f"(d[0]), "+f"(d[1]), "+f"(d[2]), "+f"(d[3]) : "r"(a0), "r"(b0)); }
__device__ __forceinline__ uint32_t absmax2(uint32_t a, uint32_t b) { uint32_t r; asm("max.xorsign.abs.bf16x2 %0, %1, %2;" : "=r"(r) : "r"(a), "r"(b)); return r; }
__device__ __forceinline__ void until(uint32_t t) { while ((int)(clk32() - t) < 0) {} }
__device__ __forceinline__ uint4 pack8(const float* d) { return make_uint4(pack2(d[0], d[1]), pack2(d[2], d[3]), pack2(d[4], d[5]), pack2(d[6], d[7])); }
__device__ __forceinline__ void add8(float* d, uint4 v) {
  d[0] += bf_lo(v.x); d[1] += bf_hi(v.x); d[2] += bf_lo(v.y); d[3] += bf_hi(v.y);
  d[4] += bf_lo(v.z); d[5] += bf_hi(v.z); d[6] += bf_lo(v.w); d[7] += bf_hi(v.w);
}

template <int WG>
__device__ __forceinline__ void chain_body(const ChainParams& p, const uint32_t wq, const uint32_t (&ak)[80], const uint32_t (&av)[80]) {
  const int tid = threadIdx.x & 127, t4 = __shfl_sync(~0u, tid >> 5, 0), lane = tid & 31;
  const int cta = blockIdx.x, h = cta / 3, j = cta - 3 * h;
  const uint32_t sb = mapa(CH_BASE, j);
  const uint32_t bWo = sb + CH_BAR, bWq = bWo + 8, bX = bWo + 16, bXA = bWo + 24, bXB = bWo + 32, bO = bWo + 40, bG = bWo + 48, bH = bWo + 96;
  uint32_t tw[4 * CH_TW];
  auto refill = [&]() {
#pragma unroll
    for (int k = 0; k < CH_TW; k++) ldsm4t(&tw[4 * k], wq + k * 2048);
  };
  const uint32_t wo = opaque((sb + CH_WO + (WG == 0 ? (t4 + (j == 2)) * 4096 : (j == 2 ? 0 : 24576) + t4 * 1024) + ((lane & 7) + (lane >> 4) * 8) * 64 +
                              ((((lane >> 3) & 1) ^ ((lane >> 1) & 3)) << 4)) ^ (WG == 1 && j == 2 ? 32 : 0));
  const uint32_t wo2 = opaque((wo ^ ((t4 & 1) * 32)) + (4 + (t4 >> 1) - t4) * 4096);
  const uint32_t l16 = opaque(sb + lane * 16);
  const uint32_t l8 = opaque(sb + t4 * 256 + lane * 8);
  const uint32_t lw = opaque(sb + t4 * 1024 + lane * 16);
  const uint32_t qs = opaque(sb + CH_QK + WG * 2048 + t4 * 512 + lane * 16);
  const uint32_t qa = opaque(sb + CH_QK + (lane >> 4) * 2048 + (lane & 15) * 16 + (WG == 0 ? t4 * 512 + 256 : t4 == 3 ? 1024 : 0));
  const uint32_t ka = opaque(t4 < 2 ? sb + CH_KT + t4 * 512 + lane * 16
                                    : sb + CH_QK + 256 + (t4 - 2) * 1024 + ((lane >> 3) & 1) * 2048 + (lane >> 4) * 128 + (lane & 7) * 16);
  const uint32_t l4 = opaque(sb + t4 * 256 + lane * 4);
  uint32_t pdst[1], pages = 0;
  auto line0 = [&](int i) { return 28 * j + (i < 4 ? 4 * t4 + i : 12 + 2 * t4 + i); };
  const uint32_t plane = opaque((lane >> 4) * 2048 + h * 64 + (lane & 15) * 4);
  if (WG == 0) {
    pages = __ballot_sync(~0u, lds32(sb + CH_O + line0(min(lane, 5)) * 4) & 4096);
  } else {
    pages = __ballot_sync(~0u, lds32(sb + CH_O + (80 + min(lane, 11)) * 4) & 4096);
    pdst[0] = opaque(lds32(sb + CH_O + (j == 0 ? 24 + t4 : 50 + 2 * j + (t4 & 1)) * 4) + plane);
  }
  const uint32_t role = lds32(sb + CH_O + NSLOT * 4), rsrc = lds32(sb + CH_O + role * 4), rdst = (80 + role / 20) * 8192 + role % 20 * 128;
  const uint32_t r1 = mapa(CH_BASE, j == 2 ? 0 : j + 1) - sb, r2 = mapa(CH_BASE, j == 0 ? 2 : j - 1) - sb;
  uint32_t tag = opaque(1);
  auto pool = [&](uint32_t off) { return p.pool + ((tag & 0xfffe) + off); };
  auto after = [&](uint32_t x) { return x & tag & 0xfffe; };
  auto kv = [&](int s, uint32_t a) { return p.kv + (a + ((cta * 2 * NSEG + s) * KV_BYTES - sb)); };
  auto pass = [&](float (&d)[16], const uint32_t (&a)[80], auto k0, auto k1) {
    const uint64_t db = mkdesc(CH_BASE + CH_X + WG * 20480, 512, 128, 0);
#pragma unroll
    for (int k = k0.value; k < k1.value; k++) wg_rs32_00(d, a[4 * k], a[4 * k + 1], a[4 * k + 2], a[4 * k + 3], db + k * 64, k);
    wg_commit();
  };
  auto dump = [&](float (&d)[16], uint32_t a) {
    reg_fence<16>(d);
    sts128(a, pack8(d)); sts128(a + 512, pack8(d + 8));
  };
  uint32_t pph = 0;
  auto tokens0 = [&](int s, auto k0) {
    float dk[16], dv[16];
    bar_sync(9, 256);
    wg_fence();
    pass(dk, ak, Int<0>(), Int<4>());
    const uint4 a0 = lds128(lw + CH_KT), a1 = lds128(lw + CH_KT + 512);
    pin();
    pass(dk, ak, Int<4>(), Int<20>());
    pass(dv, av, Int<0>(), Int<CH_VA>());
    pin();
    wg_wait<1>();
    reg_fence<16>(dk);
    add8(dk, a0); add8(dk + 8, a1);
    const uint4 w0 = pack8(dk), w1 = pack8(dk + 8);
    const uint4 b0 = lds128(lw + CH_VT), b1 = lds128(lw + CH_VT + 512);
    stsm4t(lw + CH_KT, w0.x, w0.z, w0.y, w0.w); stsm4t(lw + CH_KT + 512, w1.x, w1.z, w1.y, w1.w);
    if (CH_KP == 2) bar_arrive(7, 160);
    TM1(6);
    pin();
    if (CH_VA < 20) pass(dv, av, Int<CH_VA>(), Int<20>());
    pin();
#pragma unroll
    for (int k = k0.value; k < CH_TW; k++) ldsm4t(&tw[4 * k], wq + k * 2048);
    TM1(9);
    if (!CH_PW && k0.value < CH_TW && t4 >= 2) { mbar_wait_hot(bH + t4 * 16 - 24 + (pph & 1) * 8, pph >> 1 & 1); pph++; }
    __syncwarp();
    wg_wait<0>();
    reg_fence<16>(dv);
    add8(dv, b0); add8(dv + 8, b1);
#pragma unroll
    for (int e = 0; e < 2; e++) { const uint4 v = pack8(dv + 8 * e); sts128(lw + CH_VT + e * 512, make_uint4(v.x, v.z, v.y, v.w)); }
  };
  auto publish_k = [&](int s) {
    if (t4 == CH_KW && elect()) { fence_async(); bulk_store(p.kv + (size_t)(cta * 2 * NSEG + s) * KV_BYTES, sb + CH_KT, 4096); bulk_commit(); }
    __syncwarp();
  };
  auto load_x = [&](int s, int k0, int n, uint32_t bar) {
    if (!NOX && elect()) { mbar_expect(bar, n * 1024); bulk_load(sb + CH_X + k0 * 1024, p.xc + (s + 1) * 10240 + k0 * 256, n * 1024, bar); }
  };
  if (WG == 0) {
    mbar_wait(bXB, 0);
    tokens0(0, Int<CH_TW>());
    if (CH_XB == 5) { bar_sync(7, 128); load_x(0, 5 * t4, 5, bXB); }
  } else {
    const uint32_t* m0 = reinterpret_cast<const uint32_t*>(p.mem0) + (lane >> 2) * 320 + t4 * 80 + (lane & 3);
    uint32_t a[20];
#pragma unroll
    for (int i = 0; i < 20; i++) a[i] = m0[4 * i];
    pin();
    float dk[16], dv[16];
    mbar_wait(bXA, 0);
    wg_fence();
    pass(dk, ak, Int<0>(), Int<20>());
    pass(dv, av, Int<0>(), Int<20>());
    wg_wait<0>();
    dump(dk, lw + CH_KT);
    dump(dv, lw + CH_VT);
    bar_sync(9, 256);
    if (CH_KP == 2 && t4 == CH_KW) { bar_sync(7, 160); publish_k(0); }
#pragma unroll
    for (int i = 0; i < 20; i++) sts32(sb + CH_M + (t4 * 20 + i) * 128 + lane * 4, nz(transpose8(a[i])));
    __syncwarp();
    if (elect()) mbar_arrive(bG + t4 * 8);
  }
  PRO(8);
  mbar_wait(bWq, 0);
  refill();
  PRO(9);
  mbar_wait(bWo, 0);
  asm volatile("barrier.cluster.wait.aligned;" ::: "memory");
  PRO(10);
  constexpr int VK = WG == 0 ? CH_VK0 : CH_VK1;
  uint32_t gph = 0;
  int st = 0;
  const uint32_t ca = opaque(sb + CH_M + t4 * 2560 + lane * 32 + (lane >> 2) * 4);
  auto project = [&](int s, uint32_t (&b)[40], float (&dv)[16], uint32_t (&kf)[16]) {
    float dq[4] = {}, dk[4] = {};
    uint32_t w[80];
#pragma unroll
    for (int i = 0; i < 4 * CH_TW; i++) w[i] = tw[i];
    constexpr int LR = WG == 1 ? CH_LR1 : CH_LR;
    auto load = [&](int n) {
      int c = 0;
#pragma unroll
      for (int i = 0; i < 10; i++) {
        if (i == CH_KF) {
#pragma unroll
          for (int q = 0; q < 4; q++)
            if (WG == 1 && c++ == n) ldsm4(&kf[4 * q], ka + q * 1024);
        }
        if (c++ == n) ldsm4t(&b[4 * i], l16 + CH_M + WG * 5120 + i * 512);
#pragma unroll
        for (int k = 2 * i; k < 2 * i + 2; k++)
          if (k >= CH_TW && c++ == n) ldsm4t(&w[4 * k], wq + k * 2048);
      }
#pragma unroll
      for (int i = 0; i < 4; i++)
        if (WG == 1 && CH_KF >= 10 && c++ == n) ldsm4(&kf[4 * i], ka + i * 1024);
    };
    if (WG == 1) {
      for (int n = 0;;) {
        mbar_wait(bG + t4 * 8, gph);
        TR(5, (clk32() & ~3u) | min(n, 3));
        gph ^= 1;
        if (__builtin_expect(!__any_sync(~0u, __vimin3_u32(lds32(ca), lds32(ca + 1024), lds32(ca + 1536)) == 0), 1)) break;
        if (elect()) {
          const int q = (st == 0 ? 8 : st * 4 - 4) + t4;
          mbar_expect(bG + t4 * 8, 2560);
          bulk_load(sb + CH_M + t4 * 2560, p.pool + ((80 + q) * 8192 + (pages >> q & 1) * 4096), 2560, bG + t4 * 8);
        }
        spin_guard(n);
      }
    }
    bar_sync(6, 256);
#pragma unroll
    for (int i = 0; i < CH_L0; i++) load(i);
    if (WG == 0 && CH_XB == 4) load_x(min(s, NSEG - 2), 5 * t4, 5, bXB);
    TM(0);
    TM1(11);
    if (WG == 1) TR(6, clk32());
#pragma unroll
    for (int k = 0; k < 20; k += 2) {
      if (k > 0) {
#pragma unroll
        for (int n = (k == 18 ? 40 : CH_L0 + k * LR / 4) - 1; n >= CH_L0 + (k - 2) * LR / 4; n--) { load(n); if (CH_LO) __syncwarp(); }
      }
      if (WG == 0 && CH_XB >= 10 && k == CH_XB - 10 && s + 1 < NSEG) load_x(s, 5 * t4, 5, bXB);
      pin();
#pragma unroll
      for (int kk = k; kk < k + 2; kk++) {
        mma16(dk, ak[4 * kk], ak[4 * kk + 1], ak[4 * kk + 2], ak[4 * kk + 3], b[2 * kk], b[2 * kk + 1]);
        mma16(dq, w[4 * kk], w[4 * kk + 1], w[4 * kk + 2], w[4 * kk + 3], b[2 * kk], b[2 * kk + 1]);
        if (kk < VK) mma16(dv, av[4 * kk], av[4 * kk + 1], av[4 * kk + 2], av[4 * kk + 3], b[2 * kk], b[2 * kk + 1]);
      }
    }
    const float k2 = 0.07216878364870322f * 1.44269504089f;
    stsm4t(qs, pack2(dq[0] * k2, dq[1] * k2), pack2(dq[2] * k2, dq[3] * k2), pack2(dk[0], dk[1]), pack2(dk[2], dk[3]));
    TM(1);
  };
  static_assert(CH_P1 == 4 && CH_TW == 12 && CH_VK1 == 20 && CH_KP == 0 && true, "last step");
  constexpr int VC = VK == 20 ? 1 : CH_VC;
  auto finish_v = [&](const uint32_t (&b)[40], float (&dv)[16]) {
#pragma unroll
    for (int kk = VK; kk < 20; kk++) mma16(dv + 4 * ((kk - VK) % VC), av[4 * kk], av[4 * kk + 1], av[4 * kk + 2], av[4 * kk + 3], b[2 * kk], b[2 * kk + 1]);
  };
  auto sum_v = [&](float (&dv)[16]) {
#pragma unroll
    for (int i = 4; i < 4 * VC; i++) dv[i & 3] += dv[i];
  };
  auto publish_km = [&](int s, int w = 0) {
    uint32_t a[4];
    ldsm4(a, qa + w * 512);
    *reinterpret_cast<uint2*>(kv(s, l8) + KV_M + w * 256) = make_uint2(hadd2(a[0], a[2]), hadd2(a[1], a[3]));
  };
  auto memory_v = [&](uint2 x, const float (&dv)[16]) {
    return make_uint2(pack2(dv[0] + bf_lo(x.x), dv[1] + bf_hi(x.x)), pack2(dv[2] + bf_lo(x.y), dv[3] + bf_hi(x.y)));
  };
  auto publish_v = [&](int s, const uint4 (&v)[2], uint2 vm) {
#pragma unroll
    for (int e = 0; e < 2; e++) reinterpret_cast<uint4*>(kv(s, lw) + KV_V)[e * 32] = v[e];
    *reinterpret_cast<uint2*>(kv(s, l8) + KV_V + KV_M) = vm;
  };
#pragma unroll 1
  for (int s = 0;; s++) {
    float dv[16] = {};
    uint32_t b[40], kf[16];
    project(s, b, dv, kf);
    if (WG == 0) {
      bar_sync(1, 256);
      if (CH_XA == 0 && s + 1 < NSEG) load_x(s, 20 + 5 * t4, 5, bXA);
      if (CH_XB == 0 && s + 1 < NSEG) load_x(s, 5 * t4, 5, bXB);
      pin();
      uint32_t w[144];
      auto wload = [&](int i) { ldsm4t(&w[4 * i], (i % 3 == 0 ? wo : i % 3 == 1 ? wo ^ 32 : wo2) + i / 12 * 28672 + i / 3 % 4 * 1024); };
#pragma unroll
      for (int kk = VK; kk < 20; kk++) {
        mma16(dv + 4 * ((kk - VK) % VC), av[4 * kk], av[4 * kk + 1], av[4 * kk + 2], av[4 * kk + 3], b[2 * kk], b[2 * kk + 1]);
        if (kk == VK + CH_WA && CH_W0) {
          pin();
#pragma unroll
          for (int i = 0; i < CH_W0; i++) wload(i);
          pin();
        }
      }
      sum_v(dv);
      sts64(l8 + CH_VP, pack2(dv[0], dv[1]), pack2(dv[2], dv[3]));
      if (s == NSEG - 1) {
        bar_arrive(10, 256);
        mbar_wait(bXB, 0);
        if (CH_PW && t4 >= 2) mbar_wait(bH + t4 * 16 - 24 + (pph & 1) * 8, pph >> 1 & 1);
        publish_k(s);
        publish_km(s);
        bulk_wait<0>();
        fence_async_global();
        bar_sync(2, 256);
        if (t4 == 0 && elect()) red_release(p.sync + 15 * 8 + 4, 1);
        break;
      }
      bar_arrive(4, 256);
      if (CH_XA == 1) load_x(s, 20 + 5 * t4, 5, bXA);
      if (CH_XB == 1) load_x(s, 5 * t4, 5, bXB);
      TM(3);
      if (CH_KP == 0) publish_k(s);
#pragma unroll
      for (int i = CH_W0; i < CH_W1; i++) wload(i);
      bar_sync(10, 256);
      uint32_t km[4] = {};
      if (CH_KM < 2) ldsm4(km, qa);
      pin();
#pragma unroll
      for (int i = CH_W1; i < CH_W2; i++) wload(i);
      pin();
      const uint2 kms = make_uint2(hadd2(km[0], km[2]), hadd2(km[1], km[3]));
      if (CH_KM == 0) *reinterpret_cast<uint2*>(kv(s, l8) + KV_M) = kms;
      if (CH_KP == 0) bulk_wait_read<0>();
      if (CH_XA == 2) load_x(s, 20 + 5 * t4, 5, bXA);
      if (CH_XB == 2) load_x(s, 5 * t4, 5, bXB);
      bar_sync(2, 256);
      {
        float y[3][4] = {};
        uint32_t ob[24];
        ldsm4(&ob[0], l16 + CH_O + 1024); ldsm4(&ob[4], l16 + CH_O + 1536);
        TM(7);
        auto step = [&](int i) {
          const int k = i / 3;
          mma16(y[i % 3], w[4 * i], w[4 * i + 1], w[4 * i + 2], w[4 * i + 3], ob[2 * k], ob[2 * k + 1]);
        };
#pragma unroll
        for (int i = 0; i < 12; i++) {
          step(i);
          if (i >= 12 - (CH_W3 - CH_W2)) wload(CH_W3 - 12 + i);
          if (i % 3 == 2) pin();
        }
        if (CH_XB == 3) load_x(s, 5 * t4, 5, bXB);
        if (CH_KM == 1) *reinterpret_cast<uint2*>(kv(s, l8) + KV_M) = kms;
        pin();
        mbar_wait(bO, s & 1);
        TM(4);
        ldsm4(&ob[8], l16 + CH_O); ldsm4(&ob[12], l16 + CH_O + 512);
        pin();
        float2 inv;
        uint8_t* dst[6];
        uint32_t mask;
#pragma unroll
        for (int i = 12; i < 36; i++) {
          step(i);
          static_assert(CH_W3 == 26, "load order");
          if (i == 14) ldsm4(&ob[16], l16 + after(w[4 * CH_W3 - 1] | w[4 * CH_W3 - 5] | w[4 * CH_W3 - 9] | ob[8]) + CH_O + 2048);
          else if (i == 15) ldsm4(&ob[20], l16 + CH_O + 2560);
          else if (i < 24) wload(i < 14 ? 39 - i : i < 18 ? 45 - i : i < 21 ? 50 - i : 56 - i);
          if (i == 21) inv = lds64f((l8 & ~0xe0u) + CH_VP);
          if (i < 24) __syncwarp();
          if (i == 24) mask = ((l16 ^ tag) & 48) == 0;
          if (i >= 24 && i < 30) dst[i - 24] = pool(line0(i - 24) * 8192 + (pages >> (i - 24) & 1) * 4096) + plane;
          if (i % 3 == 2) pin();
        }
#pragma unroll
        for (int k = 0; k < CH_R1; k++) ldsm4t(&tw[4 * k], wq + k * 2048);
        pin();
#pragma unroll
        for (int i = 0; i < 6; i++) stg_strong32(dst[i], pack_tag(y[i >> 1][2 * (i & 1)] * inv.x, y[i >> 1][2 * (i & 1) + 1] * inv.y, tag, mask));
        TM(8);
        TR(0, clk32());
        bar_arrive(5, 256);
        pin();
      }
      const uint32_t t0 = clk32();
      auto refill2 = [&]() {
#pragma unroll
        for (int k = CH_R1; k < CH_R2; k++) ldsm4t(&tw[4 * k], wq + k * 2048);
      };
      if (CH_RP == 0) refill2();
      const uint32_t ln = (l16 ^ tag) >> 4 & 31;
      auto keep = [&](uint32_t x) { return __shfl_sync(~0u, x, ln); };
      if (t4 >= 2) {
        const uint32_t bP = bH + t4 * 16 - 24, ps = CH_PB + (t4 & 1) * 4096;
        auto fetch = [&](uint32_t k) {
          if (elect()) { mbar_expect(bP + (k & 1) * 8, 2048); bulk_load(sb + ps + (k & 1) * 2048, p.pool + (rsrc + (t4 & 1) * 2048), 2048, bP + (k & 1) * 8); }
        };
        if (CH_PW && s > 0) { mbar_wait_hot(bP + (pph & 1) * 8, pph >> 1 & 1); pph++; }
        until(t0 + CH_D0);
        fetch(pph);
        if (CH_RP == 2) refill2();
        if (!NOX && CH_XB != 6) mbar_wait_hot(bXB, (s + 1) & 1);
        const uint32_t want = (tag & 1) * 0x10001, chk = keep(ln < 4 ? 0x10001 : 0);
        uint4 sel;
        sel.x = keep((ln >> 3) != (ln & 1) ? 0 : ln & 4 ? 0x3f800000u : 0x00003f80u);
        sel.z = keep(sel.x); sel.y = keep(ln); sel.w = keep(ln + 1);
        uint8_t* mdst = p.pool + keep(st * 32768 + rdst + (t4 & 1) * 64 + ln * 4);
        until(t0 + CH_D1);
        fetch(pph + 1);
        TM(5);
        if (CH_RP == 1) refill2();
        if (CH_KM == 2) publish_km(s);
        int n = 0;
        uint32_t u[16];
        float y[4][4];
        auto sum = [&]() {
#pragma unroll
          for (int i = 0; i < 16; i++) y[i >> 2][i & 3] = 0.f;
#pragma unroll
          for (int i = 0; i < 8; i++) mma16(y[i & 3], sel.x, sel.y, sel.z, sel.w, u[2 * i], u[2 * i + 1]);
        };
        auto check = [&](auto spec) {
          mbar_wait(bP + (pph & 1) * 8, pph >> 1 & 1);
          TM(14);
          TR(2, clk32());
#pragma unroll
          for (int i = 0; i < 4; i++) ldsm4t(&u[4 * i], l16 + (ps + (pph & 1) * 2048) + i * 512);
          pph++;
          if (spec.value) { pin(); sum(); }
          uint32_t bad = 0;
#pragma unroll
          for (int i = 0; i < 4; i++) bad = or3(bad, differ(u[4 * i], u[4 * i + 1], want), differ(u[4 * i + 2], u[4 * i + 3], want));
          return __any_sync(~0u, bad & chk);
        };
        if (CH_SP) {
          if (check(Int<0>())) {
            do { fetch(pph + 1); spin_guard(n); } while (check(Int<1>()));
          } else {
            sum();
          }
        } else {
          while (check(Int<0>())) { fetch(pph + 1); spin_guard(n); }
          sum();
        }
        TR(1, t0 + (n ? CH_D1 : CH_D0));
        TM(15);
        const uint32_t w = nz(pack2((y[0][0] + y[1][0]) + (y[2][0] + y[3][0]), (y[0][1] + y[1][1]) + (y[2][1] + y[3][1])));
        if (ln < 16) { stg_strong32(mdst, w); stg_strong32(mdst + 4096, w); }
        TMV(12, 32, n);
        TR(3, (clk32() & ~3u) | min(n, 3));
      } else {
        if (CH_XB == 6) { load_x(s, 10 * t4, 5, bXB); load_x(s, 10 * t4 + 5, 5, bXB); }
        if (CH_RP) refill2();
        if (CH_KM == 2) publish_km(s);
        if (CH_KM == 3) { publish_km(s); publish_km(s, 2); }
        if (!NOX) mbar_wait_hot(bXB, (s + 1) & 1);
        stg_strong32(p.pool + ((st == 2 ? 0 : st + 1) * 32768 + rdst + t4 * 4096) + ln * 4, 0u);
        if (t4 == 0 && cta < 40 && s + 4 < NSEG && elect())
          asm volatile("cp.async.bulk.prefetch.L2.global [%0], 1024;" :: "l"(p.xc + (s + 4) * 10240 + cta * 256) : "memory");
        if (t4 == 1 && (s & 3) == 0 && s > 0 && elect()) red_relaxed(p.sync + 2 * s - 4, 1);
        if (t4 == 1 && s == NSEG - 3 && cta == 95 && elect()) red_relaxed(p.sync + 2 * s + 2, 0x10000);
      }
      TM(10);
      bar_arrive(8, 256);
      tokens0(s + 1, Int<CH_R2>());
      if (CH_XB == 5 && s + 2 < NSEG) { bar_sync(7, 128); load_x(s + 1, 5 * t4, 5, bXB); }
      TM(2);
      TR(7, clk32());
    } else {
      if (s == NSEG - 1) {
        bar_arrive(1, 256);
        const uint4 v[2] = {lds128(lw + CH_VT), lds128(lw + CH_VT + 512)};
        bar_sync(10, 256);
        publish_v(s, v, memory_v(lds64(l8 + CH_VP), dv));
        bar_arrive(2, 256);
        break;
      }
      const uint32_t xo = l4 + (CH_SX - (t4 == 3 ? 128 : 0)), xr = CH_SX + 768 + min(t4, 2) * 256, x1 = l4 + (r1 + xr), x2 = l4 + (r2 + xr + 128);
      if (t4 < 2) {
        float ds[4][4] = {};
        uint32_t q[16];
        asm volatile("bar.sync 1, 256;" ::: "memory");
#pragma unroll
        for (int k = 0; k < 4; k++) ldsm4(&q[4 * k], qa + k * 512);
        pin();
        if (VK < 20) { finish_v(b, dv); pin(); }
#pragma unroll
        for (int k = 0; k < 4; k++) {
          mma16(ds[k & 1], kf[4 * k], kf[4 * k + 1], kf[4 * k + 2], kf[4 * k + 3], q[4 * k], q[4 * k + 1]);
          mma16(ds[2 + (k & 1)], kf[4 * k], kf[4 * k + 1], kf[4 * k + 2], kf[4 * k + 3], q[4 * k + 2], q[4 * k + 3]);
        }
        float t[4];
#pragma unroll
        for (int i = 0; i < 4; i++) t[i] = (ds[0][i] + ds[2][i]) + (ds[1][i] + ds[3][i]);
        const uint32_t w0 = pack2(t[0], t[1]), w1 = pack2(t[2], t[3]);
        st_async32(x1, w0, bX + r1); st_async32(x2, w0, bX + r2);
        st_async32(x1 + 256, w1, bX + r1); st_async32(x2 + 256, w1, bX + r2);
        sts32(xo, w0); sts32(xo + 128, w1);
      } else {
        float ds[4][4] = {};
        uint32_t q0[4], q1[4], a0[4], a1[4];
        asm volatile("bar.sync 1, 256; " ::: "memory");
        ldsm4(a0, ka); ldsm4(q0, qa); ldsm4(a1, ka + 512); ldsm4(q1, qa + 512);
        pin();
        if (VK < 20) { finish_v(b, dv); pin(); }
        mma16(ds[0], a0[0], a0[1], a0[2], a0[3], q0[0], q0[1]);
        mma16(ds[1], a0[0], a0[1], a0[2], a0[3], q0[2], q0[3]);
        mma16(ds[2], a1[0], a1[1], a1[2], a1[3], q1[0], q1[1]);
        mma16(ds[3], a1[0], a1[1], a1[2], a1[3], q1[2], q1[3]);
        float t[2];
#pragma unroll
        for (int i = 0; i < 2; i++)
          t[i] = ((ds[0][i] + ds[0][i + 2]) + (ds[1][i] + ds[1][i + 2])) + ((ds[2][i] + ds[2][i + 2]) + (ds[3][i] + ds[3][i + 2]));
        const uint32_t w0 = pack2(t[0], t[1]);
        st_async32(x1, w0, bX + r1);
        st_async32(x2, w0, bX + r2);
        sts32(xo, w0);
      }
      TM(3);
      const uint4 id = lds128(l16 + CH_ID);
      float sc[5][4] = {};
      uint4 v[2];
      sum_v(dv);
      bar_sync(4, 256);
      uint32_t r[12], wd[12], we[12] = {};
      ldsm4(&r[0], l16 + CH_SX); ldsm2(&r[4], l16 + CH_SX + 512);
      const uint2 vp = lds64(l8 + CH_VP);
      pin();
      v[0] = lds128(lw + CH_VT); v[1] = lds128(lw + CH_VT + 512);
#pragma unroll
      for (int u = 0; u < 3; u++) ldsm4t(&wd[4 * u], wo + u * 28672);
      pin();
#pragma unroll
      for (int q = 0; q < 4; q++) mma8(sc[q], id.x, id.y, r[q]);
      mma16(sc[4], id.x, id.y, id.z, id.w, r[4], r[5]);
      uint32_t big = absmax2(absmax2(absmax2(r[0], r[1]), absmax2(r[2], r[3])), absmax2(r[4], r[5]));
      const uint2 vm = memory_v(vp, dv);
      const uint32_t ones = 0x3f803f80u;
      pin();
      mbar_wait_hot(bX, s & 1);
      TM(4);
      ldsm4(&r[0], l16 + CH_SX + 768);
      __syncwarp();
      ldsm4(&r[8], l16 + CH_SX + 1792);
      __syncwarp();
      ldsm4(&r[4], l16 + CH_SX + 1280);
      bar_arrive(10, 256);
      pin();
      auto add = [&](int q) { mma16(sc[min(q, 4)], id.x, id.y, id.z, id.w, r[2 * q], r[2 * q + 1]); };
      add(0); add(1);
      pin();
      add(4);
      pin();
      uint32_t pr[5], o0, o1;
      bool redo = false;
      auto attend = [&](auto first) {
        float o[2][4] = {}, e[10];
        auto exps = [&](int q) {
#pragma unroll
          for (int i = 0; i < 2; i++) asm volatile("ex2.approx.ftz.f32 %0, %1;" : "=f"(e[2 * q + i]) : "f"(sc[q][i]));
        };
        auto merge = [&](int q) { big = absmax2(big, absmax2(absmax2(r[4 * q], r[4 * q + 1]), absmax2(r[4 * q + 2], r[4 * q + 3]))); };
        exps(0);
        if (first.value) { merge(0); pin(); add(2); add(5); add(3); }
        exps(1);
        if (first.value) { merge(2); pin(); }
        exps(2);
        if (first.value) { merge(1); pin(); }
        pr[0] = pack2(e[0], e[1]); pr[1] = pack2(e[2], e[3]);
        mma16h(o[0], pr[0], pr[1], v[0].x, v[0].y);
        mma16h(o[1], pr[0], pr[1], v[0].z, v[0].w);
        exps(4);
        if (first.value) pin();
        exps(3);
        if (first.value) redo = __any_sync(~0u, (absmax2(big, big << 16) & 0x7fff0000u) >= 0x41800000u);
        const bool drop = first.value && redo;
        const uint32_t a1 = l4 + (drop ? CH_PS : r1 + CH_O), a2 = l4 + (drop ? CH_PS : r2 + CH_O + 2048);
        const uint32_t b1 = drop ? bWq : bO + r1, b2 = drop ? bWq : bO + r2;
        pr[2] = pack2(e[4], e[5]); pr[3] = pack2(e[6], e[7]); pr[4] = pack2(e[8], e[9]);
        mma8h(o[0], pr[4], vm.x);
        mma8h(o[1], pr[4], vm.y);
        mma16h(o[0], pr[2], pr[3], v[1].x, v[1].y);
        mma16h(o[1], pr[2], pr[3], v[1].z, v[1].w);
        o0 = pack2(o[0][0], o[0][1]); o1 = pack2(o[1][0], o[1][1]);
        st_async32(a1, o0, b1); st_async32(a2, o0, b2);
        st_async32(a1 + 128, o1, b1); st_async32(a2 + 128, o1, b2);
        sts32(l4 + CH_O + 1024, o0); sts32(l4 + CH_O + 1152, o1);
        asm volatile("{.reg .pred p; setp.eq.u32 p, %0, 0; @p bar.arrive 2, 256;}" :: "r"((uint32_t)drop) : "memory");
      };
      attend(Int<1>());
      pin();
      if (__builtin_expect(redo, 0)) {
        float mx = -INFINITY;
#pragma unroll
        for (int q = 0; q < 5; q++) mx = fmaxf(mx, fmaxf(sc[q][0], sc[q][1]));
        mx = fmaxf(mx, __shfl_xor_sync(~0u, mx, 1));
        mx = fmaxf(mx, __shfl_xor_sync(~0u, mx, 2));
#pragma unroll
        for (int q = 0; q < 5; q++) { sc[q][0] -= mx; sc[q][1] -= mx; }
        attend(Int<0>());
      }
      TM(6);
      float l[4] = {}, l2[4] = {};
      mma16h(l, pr[0], pr[1], ones, ones);
      mma16h(l2, pr[2], pr[3], ones, ones);
      mma8h(l, pr[4], ones);
      l[0] += l2[0];
      float inv;
      asm("rcp.approx.ftz.f32 %0, %1;" : "=f"(inv) : "f"(l[0]));
      sts32((l8 & ~0xffu) + ((l8 ^ tag) >> 3 & 28) + CH_VP, __float_as_uint(inv));
      __syncwarp();
      if (elect()) mbar_arrive(bO);
      {
        float z[2][4] = {}, y[2][4] = {};
        mma16(z[0], wd[0], wd[1], wd[2], wd[3], o0, o1);
        if (j == 0) {
#pragma unroll
          for (int u = 0; u < 3; u++) ldsm4t(&we[4 * u], (wo ^ 32) + u * 28672);
          mma16(y[0], we[0], we[1], we[2], we[3], o0, o1);
        }
        const float2 iv = lds64f((l8 & ~0xe0u) + CH_VP);
        uint8_t* dst = pool(pdst[0]);
        const uint32_t mask = ((l16 ^ tag) & 48) == 0;
        const uint32_t oa = qa + ((tag & 0xfffe) + CH_O - CH_QK + t4 * 256 - (t4 == 3 ? 1024 : 0));
        const uint32_t za = l16 + ((tag & 0xfffe) + (t4 >> 1) * 512 + (t4 & 1) * 8);
        pin();
        mbar_wait(bO, s & 1);
        uint32_t a[4];
        ldsm4(a, oa);
        mma16(z[0], wd[4], wd[5], wd[6], wd[7], a[0], a[1]);
        mma16(z[1], wd[8], wd[9], wd[10], wd[11], a[2], a[3]);
        if (j == 0) {
          mma16(y[0], we[4], we[5], we[6], we[7], a[0], a[1]);
          mma16(y[1], we[8], we[9], we[10], we[11], a[2], a[3]);
          sts128f(lw + CH_VT + 512, y[0][0] + y[1][0], y[0][1] + y[1][1], y[0][2] + y[1][2], y[0][3] + y[1][3]);
        }
        sts128f(lw + CH_VT, z[0][0] + z[1][0], z[0][1] + z[1][1], z[0][2] + z[1][2], z[0][3] + z[1][3]);
        bar_sync(3, 128);
        if (j == 0 || t4 < 2) {
          float2 q[4];
#pragma unroll
          for (int i = 0; i < 4; i++) q[i] = lds64f(za + CH_VT + i * 1024);
          stg_strong32(dst, pack_tag(((q[0].x + q[1].x) + (q[2].x + q[3].x)) * iv.x, ((q[0].y + q[1].y) + (q[2].y + q[3].y)) * iv.y, tag, mask));
        }
      }
      TM(2);
      if (!NOX) mbar_wait_hot(bXA, (s + 1) & 1);
      if (CH_KP == 2) bulk_wait_read<0>();
      float dk[16], dw[16];
      bar_sync(5, 256);
      wg_fence();
      pass(dk, ak, Int<0>(), Int<20>());
      pass(dw, av, Int<0>(), Int<20>());
      TM(5);
      pin();
      if (CH_EX == 0) publish_v(s, v, vm);
      if (elect()) {
        mbar_expect(bG + t4 * 8, 2560);
        if (t4 == 1 && s + 2 < NSEG) { mbar_expect(bX, 1536); mbar_expect(bO, 2048); }
      }
      if (CH_KD == 0) { wg_wait<1>(); dump(dk, lw + CH_KT); }
      wg_wait<0>();
      if (CH_KD == 1) dump(dk, lw + CH_KT);
      TM(7);
      dump(dw, lw + CH_VT);
      bar_arrive(9, 256);
      pin();
#pragma unroll
      for (int k = 0; k < CH_RB; k++) ldsm4t(&tw[4 * k], wq + k * 2048);
      if (t4 < 2) {
        if (CH_EX == 2) { publish_v(s, v, vm); pin(); }
#pragma unroll
        for (int k = CH_RB; k < CH_RC; k++) ldsm4t(&tw[4 * k], wq + k * 2048);
        const int q = t4 ? 3 : j, o = t4 ? j * 896 : 0;
        const uint8_t* src = p.pool + ((80 + st * 4 + q) * 8192 + (pages >> (st * 4 + q) & 1) * 4096 + o);
        asm volatile("bar.sync 8, 256;" ::: "memory");
        const uint32_t t1 = clk32() + CH_D2;
        if (CH_EX == 1) publish_v(s, v, vm);
        auto fetch = [&](auto n) {
          mbar_wait(bH, s & 1);
          until(t1);
          TR(4, clk32());
          if (elect())
            asm volatile("cp.async.bulk.shared::cluster.global.mbarrier::complete_tx::bytes.multicast::cluster [%0], [%1], %2, [%3], 7;"
                         :: "r"(sb + CH_M + q * 2560 + o), "l"(src), "n"(n.value), "r"(bG + q * 8) : "memory");
        };
        if (!t4) fetch(Int<2560>()); else if (j == 2) fetch(Int<768>()); else fetch(Int<896>());
      } else {
        asm volatile("bar.sync 8, 256; " ::: "memory");
        if (elect()) asm volatile("mbarrier.arrive.relaxed.cluster.shared::cluster.b64 _, [%0];" :: "r"(bH + (t4 == 2 ? r1 : r2)) : "memory");
        pin();
        if (CH_EX) publish_v(s, v, vm);
#pragma unroll
        for (int k = CH_RB; k < CH_RC; k++) ldsm4t(&tw[4 * k], wq + k * 2048);
      }
      TM(9);
      pin();
#pragma unroll
      for (int k = CH_RC; k < CH_TW - CH_P1; k++) ldsm4t(&tw[4 * k], wq + k * 2048);
      if (CH_KP == 2 && t4 == CH_KW) { bar_sync(7, 160); publish_k(s + 1); }
      TM(10);
    }
    if (++st == 3) st = 0;
    tag ^= 0x10001;
  }
}

__global__ void __launch_bounds__(256, 1) chain_kernel(const __grid_constant__ ChainParams p) {
  extern __shared__ __align__(1024) uint8_t smem_raw[];
  const uint32_t sb = s2u(smem_raw);
  const int tid = threadIdx.x, warp = __shfl_sync(~0u, tid >> 5, 0), lane = tid & 31;
  const int cta = blockIdx.x, h = cta / 3, j = cta - 3 * h, colbase = cta * 64;
  const uint32_t bWo = sb + CH_BAR, bWq = bWo + 8, bXA = bWo + 24, bWk = bWo + 80, bWv = bWo + 88;
  uint32_t smid; asm("mov.u32 %0, %%smid;" : "=r"(smid));
  PRO(0);
  if (sb != mapa(CH_BASE, j)) __trap();
  uint32_t entry = 0;
  auto place = [&]() {
    const int i = tid - 128;
    if (i >= 0 && i <= NSLOT) {
      const uint32_t side = ldg_strong32(g_smpart + (smid & 255));
      if (i < NSLOT) {
        entry = i * 8192 + (ldg_strong32(g_orient + i) == (i < 80 ? i & 1 : side) ? 0 : 4096);
      } else {
        entry = 2 * (atomicAdd(g_bo + p.layer * 128 + 1, 1 << 8 * side) >> 8 * side & 255) + side;
      }
    }
    __syncwarp();
  };
  if (warp == 2 && lane < 4) asm volatile("prefetch.tensormap [%0];" :: "l"(&p.wq + lane) : "memory");
  if (p.layer) place();
  if (warp == 0 && elect()) {
#pragma unroll 1
    for (int i = 0; i < 17; i++) mbar_init(bWo + 8 * i, i == 5 ? 5 : i == 3 || i == 4 ? 4 : i == 12 ? 2 : 1);
    asm volatile("fence.mbarrier_init.release.cluster;" ::: "memory");
    mbar_expect(bWk, 81920);
    tma_load3<(WEF & 1) != 0>(sb + CH_WQ, &p.wk, colbase, 0, bWk);
    mbar_expect(bWv, 81920);
    tma_load3<(WEF & 1) != 0>(sb + CH_WO, &p.wv, colbase, 0, bWv);
    mbar_expect(bWo + 16, 1536);
    mbar_expect(bWo + 40, 2048);
    mbar_expect(bWo, 86016); mbar_expect(bWq, 81920);
#pragma unroll 1
    for (int i = 0; i < 8; i++) mbar_expect(bXA + 8 * (i & 1), 5120);
  }
  if (warp == 1) {
    const uint32_t id = (lane >> 3) == (lane & 3) ? ((lane & 4) ? 0x3f800000u : 0x00003f80u) : 0u;
    sts128(sb + CH_ID + lane * 16, make_uint4(id, 0, id, 0));
  }
  __syncthreads();
  asm volatile("barrier.cluster.arrive.relaxed.aligned;" ::: "memory");
  uint32_t ak[80], av[80];
  const uint32_t wq = opaque(sb + CH_WQ + ((warp >> 2) * 320 + (lane & 7) + (lane >> 4) * 8) * 128 + (((2 * (warp & 3) + ((lane >> 3) & 1)) ^ (lane & 7)) << 4));
  pdl_wait();
  if (tid == 32) stg_strong32(g_smuse + (smid & 255), p.layer + 1);
  pdl_launch();
  PRO(1);
  if (warp == 0 && elect()) {
    bulk_load(sb + CH_X + 20480, p.xc + 5120, 20480, bXA);
    bulk_load(sb + CH_X, p.xc, 20480, bXA + 8);
  }
  if (!p.layer) place();
  __syncwarp();
  PRO(2);
  mbar_wait(bWk, 0);
  PRO(3);
#pragma unroll
  for (int k = 0; k < 20; k++) ldsm4t(&ak[4 * k], wq + k * 2048);
  bar_sync(6, 256);
  if (warp == 0 && elect()) tma_load3<(WEF & 2) != 0>(sb + CH_WQ, &p.wq, colbase, 0, bWq);
  __syncwarp();
  PRO(4);
  mbar_wait(bWv, 0);
  PRO(5);
#pragma unroll
  for (int k = 0; k < 20; k++) ldsm4t(&av[4 * k], wq + CH_WO + k * 2048);
  bar_sync(6, 256);
  PRO(6);
  if (warp >= 5 && elect()) tma_load3<(WEF & 2) != 0>(sb + CH_WO + (warp - 5) * 28672, &p.wo, j == 0 ? 0 : 32 + j * 192, h * 192 + (j + 8 - warp) % 3 * 64, bWo);
  if (tid == 128 + NSLOT && entry >= 80) {
    uint32_t c;
    int n = 0;
    do { c = ldg_strong32(g_bo + p.layer * 128 + 1); spin_guard(n); } while ((c & 255) + (c >> 8) < 96);
    const uint32_t other = (c >> 8 * (~entry & 1) & 255) + (entry >> 1) - 40;
    entry = other < 40 ? 2 * other + (~entry & 1) : entry % 80;
  }
  if (tid >= 128 && tid <= 128 + NSLOT) sts32(sb + CH_O + (tid - 128) * 4, entry);
  PRO(7);
  __syncthreads();
  if (__shfl_sync(~0u, tid >> 7, 0) == 0) chain_body<0>(p, wq, ak, av); else chain_body<1>(p, wq, ak, av);
}

struct PostParams { CUtensorMap wq, wo, wb, wo2, wb2; int gap, share, layer, look, gap2, pol, slow_n, slow_gap; };
constexpr int PS = 8, PB = 28672;
constexpr int OP_SMEM = PS * PB + 512 + 2048;
enum { IT_ATT = 0, IT_OP = 1, IT_FIN = 2, IT_BQ = 3, IT_Q = 4 };

__device__ __forceinline__ uint32_t item_count(int type, int b) {
  return type == IT_ATT ? 32 : type == IT_OP ? op_split(b) * (b < OP_160 ? 2 : 4) : type == IT_FIN ? 16 : b < BQ_160 ? 6 : b < BQ_80 ? 12 : 24; }
__device__ __forceinline__ uint32_t item_need(int type, int b) { return type == IT_ATT ? 96 : item_count(type - 1, b); }

struct Ring {
  uint32_t sb, bars; int st; uint32_t ph;
  __device__ __forceinline__ uint32_t wait() const { mbar_wait(bars + 8 * st, ph); return sb + st * PB; }
  __device__ __forceinline__ void next() { if (++st == PS) { st = 0; ph ^= 1; } }
  __device__ __forceinline__ void release(int s) const { if ((threadIdx.x & 31) == 0) mbar_arrive(bars + 8 * (PS + s)); }
  __device__ __forceinline__ void pop() { __syncwarp(); release(st); next(); }
};

template <int N>
__device__ __forceinline__ void gemm_item(Ring& r, float* d, int nst, uint32_t go, int go_at, uint32_t wg) {
  auto desc = [](uint32_t lo, uint32_t hi) { uint64_t x; asm("mov.b64 %0, {%1, %2};" : "=l"(x) : "r"(lo), "r"(hi)); return x; };
  auto stage = [&](auto first) {
    const uint32_t base = (r.wait() & 0x3ffff) >> 4, a = base + wg * 256 + (8 << 16), w = base + 512 + (256 << 16);
    wg_fence();
#pragma unroll
    for (int kk = 0; kk < 2; kk++) {
      const uint64_t da = desc(a + kk * 16, 32), db = desc(w + kk * 128, 64 | 1 << 30);
      const int acc = kk || !first.value;
      if (N == 80) wg_ss80_01(d, da, db, acc);
      if (N == 160) wg_ss160_01(d, da, db, acc);
      if (N >= 192) wg_ss192_01(d, da, db, acc);
      if (N == 320) wg_ss128_01(d + 96, da, desc(w + kk * 128 + 768, 64 | 1 << 30), acc);
    }
    wg_commit();
  };
  stage(Int<1>());
  int prev = r.st;
  r.next();
#pragma unroll 1
  for (int kb = 1; kb < nst; kb++) {
    stage(Int<0>());
    if (kb == go_at && threadIdx.x == 0) mbar_arrive(go);
    wg_wait<1>();
    r.release(prev);
    prev = r.st;
    r.next();
  }
  wg_wait<0>();
  reg_fence<N / 2>(d);
  r.release(prev);
}

template <int HALF>
__device__ __forceinline__ void attn_a_warp(Ring& r, const uint32_t (&q)[48], int b, int h) {
  constexpr int NT = HALF ? 5 : 3, NF = 8 * NT;
  const int lane = threadIdx.x & 31, g = lane >> 2, c = lane & 3, seg = (threadIdx.x >> 5) & 3;
  uint32_t f[6][NF];
  int slot[6];
  auto fetch = [&](int u) {
    const uint32_t kv = r.wait() + seg * KV_BYTES;
    slot[u] = r.st;
    r.next();
#pragma unroll
    for (int w = 0; w < 4; w++) {
      uint32_t* d = &f[u][2 * NT * w];
#pragma unroll
      for (int t = 0; t <= HALF; t++) {
        if (u < 3) {
          ldsm4(d + 4 * t, kv + w * 1024 + t * 512 + (lane & 8) * 32 + (lane & 16) * 8 + (lane & 7) * 16);
        } else {
          const uint4 v = lds128(kv + w * 1024 + t * 512 + lane * 16);
          d[4 * t] = v.x; d[4 * t + 1] = v.y; d[4 * t + 2] = v.z; d[4 * t + 3] = v.w;
        }
      }
      const uint2 m = lds64(kv + KV_M + w * 256 + lane * 8);
      d[2 * NT - 2] = m.x; d[2 * NT - 1] = m.y;
    }
    pdl_launch();
  };
  float s[NT][4] = {};
  fetch(0);
#pragma unroll
  for (int u = 0; u < 3; u++) {
    fetch(u + 1);
#pragma unroll
    for (int kk = 0; kk < 4; kk++) {
      const uint32_t* a = &q[16 * u + 4 * kk];
#pragma unroll
      for (int n = 0; n < NT; n++) mma16(s[(n + 1) % NT], a[0], a[1], a[2], a[3], f[u][2 * NT * kk + 2 * n], f[u][2 * NT * kk + 2 * n + 1]);
    }
    r.release(slot[u]);
    pdl_launch();
  }
  fetch(4);
  const float k2 = 0.07216878364870322f * 1.44269504089f, NEG = -INFINITY;
  if (2 * c > g) { s[NT - 2][0] = NEG; s[NT - 1][2] = NEG; }
  if (2 * c + 1 > g) { s[NT - 2][1] = NEG; s[NT - 1][3] = NEG; }
  s[NT - 1][0] = s[NT - 1][1] = NEG;
  uint32_t pp[NT][2]; float inv[2];
#pragma unroll
  for (int hh = 0; hh < 2; hh++) {
    float m = NEG, l = 0.f;
#pragma unroll
    for (int n = 0; n < NT; n++) m = fmaxf(m, fmaxf(s[n][2 * hh], s[n][2 * hh + 1]));
    m = fmaxf(m, __shfl_xor_sync(~0u, m, 1)); m = fmaxf(m, __shfl_xor_sync(~0u, m, 2));
#pragma unroll
    for (int n = 0; n < NT; n++) { const float x = ex2((s[n][2 * hh] - m) * k2), y = ex2((s[n][2 * hh + 1] - m) * k2); l += x + y; pp[n][hh] = pack2(x, y); }
    l += __shfl_xor_sync(~0u, l, 1); l += __shfl_xor_sync(~0u, l, 2);
    asm("rcp.approx.ftz.f32 %0, %1;" : "=f"(inv[hh]) : "f"(l));
  }
  uint32_t* dst = g_o + ((b * 192 + h * 6) * 16 + seg * 4 + HALF * 2) * 128 + lane;
#pragma unroll
  for (int u = 3; u < 6; u++) {
    float o[8][4] = {};
#pragma unroll
    for (int n = 0; n < 8; n++) mma8(o[n], pp[0][0], pp[0][1], f[u][2 * NT * (n >> 1) + 2 * NT - 2 + (n & 1)]);
#pragma unroll
    for (int t = 0; t <= HALF; t++)
#pragma unroll
      for (int n = 0; n < 8; n++) {
        const uint32_t* v = &f[u][2 * NT * (n >> 1) + 4 * t + 2 * (n & 1)];
        mma16(o[n], pp[1 + 2 * t][0], pp[1 + 2 * t][1], pp[2 + 2 * t][0], pp[2 + 2 * t][1], v[0], v[1]);
      }
    r.release(slot[u]);
    if (u == 3) fetch(5);
#pragma unroll
    for (int n = 0; n < 8; n++) {
      dst[(u - 3) * 4096 + (n >> 2) * 2048 + (n & 3) * 32] = pack2(o[n][0] * inv[0], o[n][1] * inv[0]);
      dst[(u - 3) * 4096 + (n >> 2) * 2048 + (n & 3) * 32 + 128] = pack2(o[n][2] * inv[1], o[n][3] * inv[1]);
    }
  }
}

__device__ __forceinline__ void fin_item(Ring& r, uint32_t scratch, int b, int idx) {
  const int warp = threadIdx.x >> 5, lane = threadIdx.x & 31;
  float4 v[1][5];
  {
    const uint32_t base = r.wait();
#pragma unroll
    for (int i = 0; i < 5; i++) v[0][i] = unpack4(lds64(base + ((warp * 5 + i) * 32 + lane) * 8));
    r.pop();
  }
#pragma unroll 1
  for (int k = 0; k < op_split(b); k += 2) {
    const uint32_t base = r.wait();
#pragma unroll
    for (int i = 0; i < 10; i++) {
      const uint2 q = lds64(base + ((i / 5 * 40 + warp * 5 + i % 5) * 32 + lane) * 8);
      float4& t = v[0][i % 5];
      t.x += bf_lo(q.x); t.y += bf_hi(q.x); t.z += bf_lo(q.y); t.w += bf_hi(q.y);
    }
    r.pop();
  }
#pragma unroll
  for (int i = 0; i < 5; i++) g_x[((b * 16 + idx) * 40 + warp * 5 + i) * 32 + lane] = pack4(v[0][i]);
  float mean[1], rs[1];
  ln_stats<1>(v, scratch, mean, rs);
#pragma unroll
  for (int i = 0; i < 5; i++) {
    const int u = warp * 5 + i;
    uint32_t* xn = g_xn + ((b * 20 + (u >> 1)) * 16 + idx) * 128 + (u & 1) * 64 + lane;
    xn[0] = pack2((v[0][i].x - mean[0]) * rs[0], (v[0][i].y - mean[0]) * rs[0]);
    xn[32] = pack2((v[0][i].z - mean[0]) * rs[0], (v[0][i].w - mean[0]) * rs[0]);
  }
}

__global__ void __launch_bounds__(384, 1) post_kernel(const __grid_constant__ PostParams p) {
  extern __shared__ __align__(1024) uint8_t smem_raw[];
  const uint32_t sb = s2u(smem_raw), bars = sb + PS * PB;
  const uint32_t bIF = bars + 128, bIE = bars + 160, done = bars + 192, bGo = bars + 224, slots = bars + 240, scratch = bars + 512;
  const int warp = __shfl_sync(~0u, threadIdx.x >> 5, 0), lane = threadIdx.x & 31;
  if (warp == 9) PST(0);
  if (warp == 0 && blockIdx.x < 36) TRACE(0);
  if (warp >= 8) {
    asm volatile("setmaxnreg.dec.sync.aligned.u32 56;");
    if (warp == 10) {
      pdl_launch();
      if (sb & 1023) __trap();
      if (lane < 29) mbar_init(bars + 8 * lane, lane < 8 ? 1 : lane < 16 ? 8 : lane < 20 ? 1 : lane < 24 ? 2 : lane < 28 ? 8 : 1);
      if (lane == 0) sts32(slots + 16, p.gap);
      fence_async();
    }
    if (warp == 8 && lane < 5) asm volatile("prefetch.tensormap [%0];" :: "l"(&p.wq + lane) : "memory");
    if (warp != 9) bar_sync(2, 384);
    if (warp == 9) {
      PST(1);
      const int b = lane & 15;
      uint32_t smid; asm("mov.u32 %0, %%smid;" : "=r"(smid));
      bool queries = QA_END < 16 && blockIdx.x < 36;
      for (int n = 0;; n++) {
        if (n > 0) { mbar_wait(bGo, (n - 1) & 1); mbar_wait(bIE + 8 * (n & 3), ((n >> 2) & 1) ^ 1); }
        int code = -1, spin = 0, ticket = 0;
        if (queries) {
          if (lane == 0) ticket = n == 0 ? blockIdx.x : 36 + atomicAdd(g_sync + SY_QC, 1);
          ticket = __shfl_sync(~0u, ticket, 0);
          queries = ticket < (16 - QA_END) * 32;
          if (queries) code = IT_Q << 16 | (QA_END + ticket % (16 - QA_END)) << 8 | ticket / (16 - QA_END);
        }
        if (!queries && lane == 0) asm volatile("atom.relaxed.gpu.global.add.u32 %0, [%1], 1;" : "=r"(ticket) : "l"(g_sync + SY_T) : "memory");
        while (!queries) {
          const uint4 hd = ldg_strong128(g_sync + b * 8), pr = ldg_strong128(g_sync + b * 8 + 4);
          if (n == 0 && spin == 0 && hd.x != 0x7fffffff) PST(2);
          const bool shared_tpc = MIXP && ldg_strong32(g_smuse + ((smid ^ 1) & 255)) == p.layer + 1;
          const uint32_t hv[4] = {hd.x, hd.y, hd.z, hd.w}, pv[4] = {pr.x, pr.y, pr.z, pr.w};
          const uint32_t chain_done = __ballot_sync(~0u, (pr.x & 0xffff) >= 96) & 0xffff;
          int left[4], avail[4], rdy = 0, claimed = 0, upstream = 0;
#pragma unroll
          for (int t = 0; t < 4; t++) {
            const int cnt = lane < 16 ? item_count(t, b) : 0;
            left[t] = max(cnt - (int)hv[t], 0);
            claimed += cnt - left[t];
            const bool ready = (pv[t] & 0xffff) >= item_need(t, b);
            rdy |= ready << t;
            bool ok = ready || (t == IT_ATT ? pr.x >= 0x10000 : !upstream || (t == IT_OP && (chain_done >> 15 & 1)));
            if (t == IT_BQ && (chain_done >> BQ_HOLD & 1) && !(chain_done >> 15)) ok = false;
            if (shared_tpc && !(chain_done >> 15) && (t != IT_OP || MIXP == 2)) ok = false;
            avail[t] = ok ? left[t] : 0;
            upstream |= __any_sync(~0u, left[t] > 0);
          }
          if (!upstream) break;
          int rank = max(__shfl_sync(~0u, ticket, 0) - __reduce_add_sync(~0u, claimed) - (MIXP && !(chain_done >> 15) ? 2 : 0), 0), type = -1, mine = 0;
          {
            const int a = b >= BQ_RUSH && (rdy >> IT_BQ & 1) ? avail[IT_BQ] : 0, tot = __reduce_add_sync(~0u, a);
            if (rank < tot) { type = IT_BQ; mine = a; } else rank -= tot;
            avail[IT_BQ] -= a;
          }
#pragma unroll
          for (int c = 0; c < 8; c++) {
            const int t = c == PR_FIN || c == 5 ? IT_FIN : c == PR_ATT || c == 7 ? IT_ATT : c == PR_OP || c == 4 ? IT_OP : IT_BQ;
            int a = c == PR_ATT || ((rdy >> t & 1) == (c < 4)) ? avail[t] : 0;
            if (t == IT_OP && OP_EARLY) a = c == PR_OP ? avail[t] : 0;
            if (c == 7) a = b < QA_END && !(rdy & 1) && ((chain_done << 1 | 1) >> b & 1) && !shared_tpc ? left[t] : 0;
            const int tot = __reduce_add_sync(~0u, a);
            if (type < 0) { if (rank < tot) { type = t; mine = a; } else rank -= tot; }
          }
          if (type >= 0) {
#pragma unroll
            for (int o = 1; o < 16; o <<= 1) { const int y = __shfl_up_sync(~0u, mine, o); if (lane >= o) mine += y; }
            const int blk = __ffs(__ballot_sync(~0u, mine > rank)) - 1;
            const int early = !(__shfl_sync(~0u, rdy, blk) >> type & 1);
            uint32_t idx = 0;
            if (n == 0 && spin == 0) PST(3);
            if (lane == 0) asm volatile("atom.relaxed.gpu.global.add.u32 %0, [%1], 1;" : "=r"(idx) : "l"(g_sync + blk * 8 + type) : "memory");
            ld_acquire(g_sync + blk * 8 + 4 + type);
            idx = __shfl_sync(~0u, idx, 0);
            if (idx < item_count(type, blk)) { code = (__shfl_sync(~0u, pr.y, 15) < 32) << 23 | (chain_done >> 15 & 1) << 22 | (chain_done >> p.look & 1) << 21 | early << 20 | type << 16 | blk << 8 | idx; break; }
          } else {
            __nanosleep(shared_tpc ? 2000 : 50);
          }
          spin_guard(spin);
        }
        if (n == 0) bar_sync(2, 384);
        if (lane == 0) {
          fence_async_global();
          sts32(slots + 4 * (n & 3), code);
          mbar_arrive(bIF + 8 * (n & 3));
        }
        __syncwarp();
        if (code < 0) break;
      }
    } else if (warp == 8) {
      if (elect()) {
        uint32_t dst = sb, bar = bars, ph = 1, next = clk32(), gap = 0;
        auto acquire = [&](uint32_t kb) {
          mbar_wait(bar + 8 * PS, ph);
          mbar_expect(bar, kb * 1024);
          if (gap) {
            uint32_t now;
            do now = clk32(); while ((int)(now - next) < 0);
            next = ((int)(now - next) > 100 ? now - 100 : next) + kb * gap;
          }
        };
        auto advance = [&]() { dst += PB; bar += 8; if (dst == bars) { dst = sb; bar = bars; ph ^= 1; } };
        auto depend = [&](const uint32_t* c, uint32_t need) { wait_count(c, need); fence_async_global(); };
#pragma unroll 1
        for (int n = 0;; n++) {
          mbar_wait(bIF + 8 * (n & 3), (n >> 2) & 1);
          const int code = (int)lds32(slots + 4 * (n & 3));
          if (code < 0) break;
          const int type = (code >> 16) & 15, b = (code >> 8) & 255, idx = code & 255;
          const bool early = code >> 20 & 1, go = !(code >> 21 & 1);
          mbar_arrive(bIE + 8 * (n & 3));
          gap = !(code >> 22 & 1) ? lds32(slots + 16) : type == IT_ATT || type == IT_FIN ? 0 : p.gap2;
          const uint32_t* progress = g_sync + b * 8 + 4 + type;
          if (type == IT_ATT && b >= QA_END) {
            depend(g_sync + SY_Q, (16 - QA_END) * 32);
#pragma unroll 1
            for (int u = 0; u < 2; u++) { acquire(24); bulk_load_last(dst, g_q + (((b - QA_END) * 32 + idx) * 2 + u) * 1536, 24576, bar); advance(); }
          } else if (type == IT_FIN) {
            acquire(10);
            bulk_load(dst, g_x + (b * 16 + idx) * 1280, 10240, bar);
            advance();
            if (early) depend(progress, item_need(type, b));
            if (go) mbar_arrive(bGo);
            const uint2* src = g_part + (b * 16 + idx) * 16 * 1280;
#pragma unroll 1
            for (int i = 0; i < op_split(b); i += 2) { acquire(20); bulk_load_last(dst, src + i * 1280, 20480, bar); advance(); }
            if (!go && p.pol) mbar_arrive(bGo);
          } else {
            const bool op = type == IT_OP, bq = type == IT_BQ;
            const int width = op ? op_width(b) : bq ? bq_width(b) : 192, nb = (width + 63) >> 6, lt = width == 320 ? 1 : 2;
            const int nst = op ? 192 / op_split(b) : 20, kb0 = op ? (idx >> lt) * nst : 0;
            const int col = (op ? idx & ((1 << lt) - 1) : idx) * width;
            const bool whole = !(width & 63);
            const CUtensorMap* m = op ? (whole ? &p.wo : &p.wo2) : bq ? (whole ? &p.wb : &p.wb2) : &p.wq;
            const uint32_t* a = op ? g_o + (b * 192 + kb0) * 2048 : g_xn + b * 20 * 2048;
            int row = kb0 * 32, pre = early && (op || bq) ? min(nst, PRE_MAX) : 0;
            int slow = (code >> 22 & 3) == 3 ? p.slow_n : 0;
            if (slow) gap = p.slow_gap;
            auto weights = [&]() {
              if (slow && --slow == 0) gap = 0;
              acquire(8 + nb * 4);
              if (whole) {
                tma_load3z(dst + 8192, m, row, col >> 6, bar);
              } else {
                tma_load(dst + 8192, m, col, row, bar); tma_load(dst + 12288, m, col + 64, row, bar);
                if (nb == 3) tma_load(dst + 16384, m, col + 128, row, bar);
              }
              row += 32;
            };
            if (pre) {
              uint32_t da = dst, ba = bar;
#pragma unroll 1
              for (int kb = 0; kb < pre; kb++) { weights(); advance(); }
              depend(progress, item_need(type, b));
#pragma unroll 1
              for (int kb = 0; kb < pre; kb++) {
                bulk_load(da, a, 8192, ba);
                a += 2048; da += PB; ba += 8;
                if (da == bars) { da = sb; ba = bars; }
              }
            }
#pragma unroll 1
            for (int kb = pre; kb < nst; kb++) { weights(); if (op && OEF) bulk_load_last(dst, a, 8192, bar); else bulk_load(dst, a, 8192, bar); a += 2048; advance(); }
          }
          if (type == IT_ATT) {
            if (early) depend(progress, 96);
            if (go) mbar_arrive(bGo);
            const uint8_t* src = g_kv + (size_t)(idx * 6 * NSEG + b * 4) * KV_BYTES;
#pragma unroll 1
            for (int u = 0; u < 6; u++) {
              acquire(20);
              bulk_load_last(dst, src, 20480, bar);
              src += u == 2 ? -3 * KV_V : 2 * KV_V;
              advance();
            }
            if (!go && p.pol && ATT_LOOK) mbar_arrive(bGo);
          }
        }
      }
    } else if (warp == 11) {
      uint32_t smid, nsm, used = 0;
      asm("mov.u32 %0, %%smid;" : "=r"(smid)); asm("mov.u32 %0, %%nsmid;" : "=r"(nsm));
      for (int n = 0; n < 64 && used < 96; n++) {
        uint32_t peers = 0;
        used = 0;
        for (uint32_t i = lane; i < min(nsm, 256u); i += 32) {
          const bool taken = ldg_strong32(g_smuse + i) == p.layer + 1;
          used += taken;
          peers += abs((int)(g_smclk[i] - g_smclk[smid & 255])) < 4000 && !taken;
        }
        used = __reduce_add_sync(~0u, used);
        sts32(slots + 16, max(p.gap, (int)min(__reduce_add_sync(~0u, peers), 18u) * p.share >> 3));
      }
    } else if (warp == 10 && lane == 0) {
      for (int n = 0;; n++) {
        mbar_wait(bIF + 8 * (n & 3), (n >> 2) & 1);
        const int code = (int)lds32(slots + 4 * (n & 3));
        if (code < 0) break;
        const int type = (code >> 16) & 15, b = (code >> 8) & 255;
        mbar_wait(done + 8 * (n & 3), (n >> 2) & 1);
        if (type != IT_BQ) red_release(type == IT_Q ? g_sync + SY_Q : g_sync + b * 8 + 5 + type, 1);
        mbar_arrive(bIE + 8 * (n & 3));
      }
    }
  } else {
    asm volatile("setmaxnreg.inc.sync.aligned.u32 224;");
    bar_sync(2, 384);
    const int g = lane >> 2, c = lane & 3;
    Ring r = {sb, bars, 0, 0};
#pragma unroll 1
    for (int n = 0;; n++) {
      mbar_wait(bIF + 8 * (n & 3), (n >> 2) & 1);
      const int code = __shfl_sync(~0u, (int)lds32(slots + 4 * (n & 3)), 0);
      if (code < 0) { TRACE(2); break; }
      const int type = (code >> 16) & 15, b = (code >> 8) & 255, idx = code & 255;
      ITEM(code & 0xfffff, 0);
      if (type == IT_ATT || type == IT_Q) {
        uint32_t q[48];
        if (type == IT_Q || b < QA_END) {
          float d[96];
          gemm_item<192>(r, d, 20, bGo, type == IT_Q ? 12 : -1, warp >> 2);
#pragma unroll
          for (int i = 0; i < 48; i++) q[i] = pack2(d[2 * i], d[2 * i + 1]);
        } else {
#pragma unroll
          for (int u = 0; u < 2; u++) {
            const uint32_t base = r.wait() + threadIdx.x * 16;
#pragma unroll
            for (int i = 0; i < 6; i++) {
              const uint4 v = lds128(base + i * 4096);
              q[24 * u + 4 * i] = v.x; q[24 * u + 4 * i + 1] = v.y; q[24 * u + 4 * i + 2] = v.z; q[24 * u + 4 * i + 3] = v.w;
            }
            r.pop();
          }
        }
        if (type == IT_Q) {
          uint4* dst = g_q + ((b - QA_END) * 32 + idx) * 3072 + threadIdx.x;
#pragma unroll
          for (int i = 0; i < 12; i++) dst[i * 256] = make_uint4(q[4 * i], q[4 * i + 1], q[4 * i + 2], q[4 * i + 3]);
        } else if (warp < 4) {
          attn_a_warp<0>(r, q, b, idx);
        } else {
          attn_a_warp<1>(r, q, b, idx);
        }
      } else if (type == IT_FIN) {
        fin_item(r, scratch, b, idx);
      } else {
        float d[160];
        const int width = type == IT_OP ? op_width(b) : bq_width(b), nst = type == IT_OP ? 192 / op_split(b) : 20;
        const int go_at = max(nst - (code >> 21 & 1 ? p.pol : 6), 1);
        if (width == 320) {
          gemm_item<320>(r, d, nst, bGo, go_at, warp >> 2);
        } else if (width == 160 || BQ_80 == 16) {
          gemm_item<160>(r, d, nst, bGo, go_at, warp >> 2);
#pragma unroll
          for (int i = 80; i < 160; i++) d[i] = 0.f;
        } else {
          gemm_item<80>(r, d, nst, bGo, go_at, warp >> 2);
#pragma unroll
          for (int i = 40; i < 160; i++) d[i] = 0.f;
        }
        if (type == IT_OP) {
          const int tiles = DM / width;
          uint2* dst = g_part + (((b * 16 + warp * 2) * 16 + idx / tiles) * 40 + idx % tiles * (width / 16)) * 32 + lane;
#pragma unroll
          for (int u = 0; u < 20; u++) {
            if (u % 5 == 0 && u * 16 >= width) break;
            dst[u * 32] = make_uint2(pack2(d[8 * u], d[8 * u + 1]), pack2(d[8 * u + 4], d[8 * u + 5]));
            dst[(640 + u) * 32] = make_uint2(pack2(d[8 * u + 2], d[8 * u + 3]), pack2(d[8 * u + 6], d[8 * u + 7]));
          }
        } else {
          const int row = b * 128 + warp * 16 + g;
          const int h0 = idx * (width / 20);
          const float sc = h0 < 32 ? 0.22360679775f * 1.44269504089f : 1.f;
          const bool lo = c < 2;
          uint32_t* da = g_bqkv + (h0 * 256 + (row >> 3)) * 96 + lane;
          uint32_t* db = da + 256 * 96 + (lo ? 2 : -2);
          uint32_t pad[2];
#pragma unroll
          for (int rr = 0; rr < 2; rr++) pad[rr] = c & 1 || h0 < 32 ? 0u : h0 >= 64 ? 0x00003f80u : poly_group((row >> 3) + rr) ? 0x3f803f80u : 0u;
#pragma unroll
          for (int q = 0; q < 8; q++) {
            if (!(q & 1) && q * 40 >= width) break;
#pragma unroll
            for (int rr = 0; rr < 2; rr++) {
              uint32_t w[5];
#pragma unroll
              for (int i = 0; i < 5; i++) w[i] = pack2(d[20 * q + 4 * i + 2 * rr] * sc, d[20 * q + 4 * i + 2 * rr + 1] * sc);
              const int o = q * 2 * 256 * 96 + rr * 96;
              da[o] = w[0]; da[o + 32] = w[1]; da[o + 64] = lo ? w[2] : pad[rr];
              db[o] = lo ? w[3] : w[2]; db[o + 32] = lo ? w[4] : w[3]; db[o + 64] = lo ? pad[rr] : w[4];
            }
          }
        }
      }
      __syncwarp();
      if (lane == 0) mbar_arrive(done + 8 * (n & 3));
      if ((code >> 21 & 1) && (p.pol == 0 || (type == IT_ATT && !ATT_LOOK)) && threadIdx.x == 128) mbar_arrive(bGo);
      ITEM(code & 0xfffff, 1);
    }
  }
}

constexpr int AB_SMEM = 1024 + 98304 + 51200 + 4 * 16384 + 256 + 10240;
#define AB_LW 1
#define AB_U 8
#define AB_WG 4
constexpr int AB_T = AB_WG * 128, AB_PASS = 8 / AB_WG;
__device__ __forceinline__ uint32_t fma2(uint32_t a, uint32_t b, uint32_t c) { uint32_t r; asm("fma.rn.bf16x2 %0, %1, %2, %3;" : "=r"(r) : "r"(a), "r"(b), "r"(c)); return r; }
__device__ __forceinline__ uint32_t ex2_pair(float a, float b, uint32_t one, uint32_t c0) {
  const uint32_t e = __byte_perm(__float_as_uint(a), __float_as_uint(b), 0x6521);
  uint32_t x, r;
  asm("lop3.b32 %0, %1, 0x007f007f, %2, 0xEA;" : "=r"(x) : "r"(e), "r"(one));
  const uint32_t m = fma2(fma2(c0, x, 0x3c0d3c0du), x, 0x3f2b3f2bu);
  asm("lop3.b32 %0, %1, %2, 0x7f807f80, 0xE4;" : "=r"(r) : "r"(e), "r"(m));
  return r;
}
__device__ __forceinline__ float sq2(uint32_t w) { const float a = bf_lo(w), b = bf_hi(w); return fmaf(a, a, b * b); }

__device__ __forceinline__ void attn_b_store(const float* o, int h, int row0, int lane) {
  const int g = lane >> 2, c = lane & 3;
  const float i0 = __frcp_rn(__shfl_sync(~0u, o[8], (lane & ~3) | 2)), i1 = __frcp_rn(__shfl_sync(~0u, o[10], (lane & ~3) | 2));
#pragma unroll
  for (int jj = 0; jj < 3; jj++) {
    if (jj < 2 || c < 2) {
      const int col = h * 20 + 8 * jj + 2 * c;
      uint32_t* dst = g_of + (((row0 >> 7) * 10 + (col >> 6)) * 16 + (row0 >> 3 & 15)) * 256 + (col >> 3 & 7) * 32 + g * 4 + (col >> 1 & 3);
      dst[0] = pack2(o[4 * jj] * i0, o[4 * jj + 1] * i0);
      dst[256] = pack2(o[4 * jj + 2] * i1, o[4 * jj + 3] * i1);
    }
  }
}

struct AbParams { Weights next; uint32_t* done; uint32_t* out; };
__global__ void __launch_bounds__(AB_T + 32, 1) attn_b_kernel(const __grid_constant__ AbParams p) {
  extern __shared__ uint8_t smem_raw[];
  const uint32_t sb = (s2u(smem_raw) + 1023) & ~1023u, sK = sb, sV = sb + 98304, bars = sV + 51200 + 4 * 16384;
  const uint32_t bF = bars + 64, bW = bars + 72, bA = bars + 80, bE = bars + 128, smax = bars + 176;
  auto ring = [&](int i) { return i < 2 ? sK + 51200 + i * 16384 : sV + 51200 + (i - 2) * 16384; };
  const int warp = __shfl_sync(~0u, threadIdx.x >> 5, 0), lane = threadIdx.x & 31;
  const int h = blockIdx.x >> 2, quarter = blockIdx.x & 3;
  TRACE(0);
  if (threadIdx.x < 22) mbar_init(bars + 8 * threadIdx.x, threadIdx.x == 8 ? AB_T / 32 : threadIdx.x >= 16 ? 8 : 1);
  if (threadIdx.x == 32) sts64(smax, 0, 0);
  fence_async();
  __syncthreads();
  pdl_wait();
  const int blk = quarter * 4 + (h >> 3), cg = h & 7;
  auto unsafe = [&]() { const float2 m = lds64f(smax); return !(m.x * m.y <= 10000.f); };
  if (warp == AB_T / 32) {
    auto load_w = [&]() {
      mbar_expect(bW, 102400);
      for (int i = 0; i < 4; i++) bulk_load((i < 2 ? sK : sV) + (i & 1) * 25600, g_wb + cg * 6400 + i * 1600, 25600, bW);
    };
    if (elect()) {
      const uint32_t* gk = g_bqkv + (32 + h) * 256 * 96;
#pragma unroll 1
      for (int i = 0; i < 8; i++) {
        if (i >= AB_LW) mbar_wait(bars + 8 * (i - AB_LW), 0);
        mbar_expect(bars + 8 * i, 24576);
        bulk_load_last(sK + i * 12288, gk + i * 3072, 12288, bars + 8 * i);
        bulk_load_last(sV + i * 12288, gk + 32 * 256 * 96 + i * 3072, 12288, bars + 8 * i);
      }
    }
    __syncwarp();
    if (blockIdx.x < NSLOT) for (int i = lane; i < 512; i += 32) reinterpret_cast<uint4*>(pool_at(blockIdx.x * 8192))[i] = make_uint4(0, 0, 0, 0);
    if (blockIdx.x == 127) for (int i = lane; i < SY_N; i += 32) g_sync[i] = 0;
    if (p.next.w[0] && lane == 0) {
      for (int i = 0; i < AB_PF; i++) { const uint32_t t0 = clk32(); while (clk32() - t0 < (i ? AB_PFD : AB_PF0)) __nanosleep(200); prefetch_weights(p.next, i); }
    }
    __syncwarp();
    mbar_wait(bF, 0);
    const bool redo = unsafe();
    if (!redo && lane == 0) load_w();
    if (lane < 16) asm volatile("cp.async.bulk.prefetch.L2.global [%0], 1280;" :: "l"(g_x + ((blk * 16 + lane) * 40 + cg * 5) * 32) : "memory");
    __syncwarp();
    bar_sync(1, AB_T + 32);
    if (lane == 0) {
      ABT(!!p.out, 1);
      red_release(p.done + quarter * 32, 1);
      ABT(!!p.out, 2);
      if (redo) load_w();
      wait_count(p.done + quarter * 32, 32);
      fence_async_global();
      ABT(!!p.out, 3);
      for (int kb = 0; kb < 10; kb++) {
        const int i = kb < 6 ? kb : kb - 6;
        if (kb >= 6) mbar_wait(bE + 8 * i, 0);
        mbar_expect(bA + 8 * i, 16384);
        bulk_load(ring(i), g_of + (blk * 10 + kb) * 4096, 16384, bA + 8 * i);
      }
    }
    return;
  }
  float qmax = 0.f;
  const uint32_t one = opaque(0x3f803f80u + (threadIdx.x >> 10)), c0 = opaque(0x3ea83ea8u + (threadIdx.x >> 10));
#pragma unroll 1
  for (int pass = 0; pass < AB_PASS; pass++) {
    const int row0 = quarter * 512 + ((warp >> 2) * AB_PASS + pass) * 64 + (warp & 3) * 16;
    const uint32_t* gq = g_bqkv + (h * 256 + (row0 >> 3)) * 96 + lane;
    const uint32_t q0 = gq[0], q1 = gq[96], q2 = gq[32], q3 = gq[128];
    uint32_t q4 = gq[64], q5 = gq[160];
    const uint32_t z0 = gq[64 + 3 - (lane & 3)], z1 = gq[160 + 3 - (lane & 3)];
    {
      float n0 = sq2(q0) + sq2(q2) + sq2(q4), n1 = sq2(q1) + sq2(q3) + sq2(q5);
      n0 += __shfl_xor_sync(~0u, n0, 1); n1 += __shfl_xor_sync(~0u, n1, 1);
      n0 += __shfl_xor_sync(~0u, n0, 2); n1 += __shfl_xor_sync(~0u, n1, 2);
      qmax = (n0 > qmax || n0 != n0) ? n0 : qmax;
      qmax = (n1 > qmax || n1 != n1) ? n1 : qmax;
    }
    if (pass == AB_PASS - 1) {
      float kmax = 0.f;
#pragma unroll
      for (int i = 0; i < SEQ / AB_T; i++) {
        const int key = threadIdx.x + AB_T * i;
        const uint32_t a = sK + (key >> 3) * 384 + (key & 7) * 16;
        const uint4 x = lds128(a), y = lds128(a + 128);
        const uint2 z = lds64(a + 256);
        const float n = ((sq2(x.x) + sq2(x.y)) + (sq2(x.z) + sq2(x.w))) + ((sq2(y.x) + sq2(y.y)) + (sq2(y.z) + sq2(y.w))) + (sq2(z.x) + sq2(z.y));
        kmax = (n > kmax || n != n) ? n : kmax;
      }
      const uint32_t kb = __reduce_max_sync(~0u, __float_as_uint(kmax) & 0x7fffffffu), qb = __reduce_max_sync(~0u, __float_as_uint(qmax) & 0x7fffffffu);
      if (lane < 2) asm volatile("red.shared.max.u32 [%0], %1;" :: "r"(smax + 4 * lane), "r"(lane ? kb : qb) : "memory");
      __syncwarp();
    }
    if ((lane & 3) == 2) { q4 = 0xBF8043C0u; q5 = 0xBF8043C0u; }
    float o[12];
    auto desc = [](uint32_t lo, uint32_t hi) { uint64_t d; asm("mov.b64 %0, {%1, %2};" : "=l"(d) : "r"(lo), "r"(hi)); return d; };
    const uint32_t k0 = (uint32_t)mkdesc(sK, 128, 0, 0), k1 = (uint32_t)mkdesc(sK + 256, 0, 0, 0), v0 = (uint32_t)mkdesc(sV, 384, 0, 0);
    float sa[16], sb2[16];
    uint32_t pa[8], pb[8];
    auto qk = [&](float* s, uint32_t t) {
      wg_rs32_00(s, q0, q1, q2, q3, desc(k0 + t, 24), 0);
      wg_rs32_00(s, q4, q5, z0, z1, desc(k1 + t, 24), 1);
      wg_commit();
    };
    auto step = [&](float* s, uint32_t* pp, int g0, uint32_t t, uint32_t nx, int acc) {
      wg_wait<1>();
      reg_fence<16>(s);
#pragma unroll
      for (int i = 0; i < 8; i++) pp[i] = poly_group(g0 + (i >> 1)) ? ex2_pair(s[2 * i], s[2 * i + 1], one, c0) : pack2(ex2(s[2 * i]), ex2(s[2 * i + 1]));
      wg_fence();
      wg_rs24_01(o, pp[0], pp[1], pp[2], pp[3], desc(v0 + t, 8), acc);
      wg_rs24_01(o, pp[4], pp[5], pp[6], pp[7], desc(v0 + t + 48, 8), 1);
      qk(s, nx);
    };
    if (pass == 0) mbar_wait(bars, 0);
    wg_fence();
    qk(sa, 0);
    qk(sb2, 96);
#pragma unroll 1
    for (uint32_t t = 0; t < 64 * 96; t += AB_U * 96) {
      const uint32_t nx = t + AB_U * 96 < 64 * 96 ? t + AB_U * 96 : 0;
      if (pass == AB_PASS - 1 && t == 40 * 96 && lane == 0) mbar_arrive(bF);
#pragma unroll
      for (int u = 0; u < AB_U; u += 2) {
        if (u == AB_U - 2 && pass == 0) mbar_wait(bars + 8 * (nx / 768), 0);
        step(sa, pa, 0, t + u * 96, u + 2 < AB_U ? t + (u + 2) * 96 : nx, u | t);
        step(sb2, pb, 4, t + u * 96 + 96, (u + 2 < AB_U ? t + (u + 2) * 96 : nx) + 96, 1);
      }
    }
    wg_wait<0>();
    reg_fence<12>(o); reg_fence<16>(sa); reg_fence<16>(sb2);
    attn_b_store(o, h, row0, lane);
  }
  mbar_wait(bF, 0);
  if (unsafe())
#pragma unroll 1
  for (int pass = 0; pass < AB_PASS; pass++) {
    const int row0 = quarter * 512 + ((warp >> 2) * AB_PASS + pass) * 64 + (warp & 3) * 16;
    const uint32_t* gq = g_bqkv + (h * 256 + (row0 >> 3)) * 96 + lane;
    const uint32_t q0 = gq[0], q1 = gq[96], q2 = gq[32], q3 = gq[128], q4 = gq[64], q5 = gq[160];
    float o[12];
#pragma unroll
    for (int i = 0; i < 12; i++) o[i] = 0.f;
    float m0 = -INFINITY, m1 = -INFINITY;
#pragma unroll 1
    for (int kt = 0; kt < 32; kt++) {
      float s[32];
      const uint64_t dk = mkdesc(sK + kt * 3072, 128, 384, 0), dk2 = mkdesc(sK + kt * 3072 + 256, 0, 384, 0);
      wg_fence();
      wg_rs64_00(s, q0, q1, q2, q3, dk, 0);
      wg_rs64_00(s, q4, q5, 0, 0, dk2, 1);
      wg_commit();
      wg_wait<0>();
      reg_fence<32>(s); reg_fence<12>(o);
      float n0 = m0, n1 = m1;
#pragma unroll
      for (int jj = 0; jj < 8; jj++) { n0 = fmaxf(n0, fmaxf(s[4 * jj], s[4 * jj + 1])); n1 = fmaxf(n1, fmaxf(s[4 * jj + 2], s[4 * jj + 3])); }
      n0 = fmaxf(n0, __shfl_xor_sync(~0u, n0, 1)); n0 = fmaxf(n0, __shfl_xor_sync(~0u, n0, 2));
      n1 = fmaxf(n1, __shfl_xor_sync(~0u, n1, 1)); n1 = fmaxf(n1, __shfl_xor_sync(~0u, n1, 2));
      const float r0 = ex2(m0 - n0), r1 = ex2(m1 - n1);
      m0 = n0; m1 = n1;
#pragma unroll
      for (int jj = 0; jj < 3; jj++) { o[4 * jj] *= r0; o[4 * jj + 1] *= r0; o[4 * jj + 2] *= r1; o[4 * jj + 3] *= r1; }
      uint32_t pp[16];
#pragma unroll
      for (int jj = 0; jj < 8; jj++) {
        pp[2 * jj] = pack2(ex2(s[4 * jj] - m0), ex2(s[4 * jj + 1] - m0));
        pp[2 * jj + 1] = pack2(ex2(s[4 * jj + 2] - m1), ex2(s[4 * jj + 3] - m1));
      }
      const uint64_t dv = mkdesc(sV + kt * 3072, 384, 128, 0);
      wg_fence();
#pragma unroll
      for (int kk = 0; kk < 4; kk++) wg_rs24_01(o, pp[4 * kk], pp[4 * kk + 1], pp[4 * kk + 2], pp[4 * kk + 3], dv + kk * 48, 1);
      wg_commit();
    }
    wg_wait<0>();
    reg_fence<12>(o);
    attn_b_store(o, h, row0, lane);
  }
  ABT(!!p.out, 0);
  bar_arrive(1, AB_T + 32);
  if (warp >= 12) return;
  const int g = lane >> 2, c = lane & 3;
  const bool live = opaque(threadIdx.x) < 256;
  float d[40] = {};
  uint2* x = g_x + ((blk * 16 + warp * 2) * 40 + cg * 5) * 32 + lane;
  if (warp < 8) {
#pragma unroll
  for (int i = 0; i < 10; i++) {
    const int r = i / 5, u = i % 5;
    const float4 t = unpack4(x[(r * 40 + u) * 32]);
    d[8 * u + 2 * r] = t.x; d[8 * u + 2 * r + 1] = t.y; d[8 * u + 4 + 2 * r] = t.z; d[8 * u + 5 + 2 * r] = t.w;
  }
  mbar_wait(bW, 0);
  reg_fence<40>(d);
  ABT(!!p.out, 4);
#pragma unroll 1
  for (int kb = 0; kb < 10; kb++) {
    const int i = kb < 6 ? kb : kb - 6;
    mbar_wait(bA + 8 * i, kb >= 6);
    const uint64_t da = mkdesc(ring(i) + (warp >> 2) * 8192, 128, 1024, 0), db = mkdesc(kb < 5 ? sK + kb * 10240 : sV + (kb - 5) * 10240, 1280, 128, 0);
    wg_fence();
#pragma unroll
    for (int kk = 0; kk < 4; kk++) wg_ss80_01(d, da + kk * 16, db + kk * 160, 1);
    wg_commit();
    if (kb > 0 && kb < 5) { wg_wait<1>(); if (lane == 0) mbar_arrive(bE + 8 * (kb - 1)); }
  }
  wg_wait<0>();
  reg_fence<40>(d);
  }
  ABT(!!p.out, 5);
  if (p.out) {
    if (warp >= 8) return;
    const uint32_t stage = sK + 83968 + warp * 2560 + (warp < 4 ? 0 : 131328 - 10240);
#pragma unroll
    for (int u = 0; u < 5; u++)
      stsm4(stage + (lane & 15) * 160 + u * 32 + (lane >> 4) * 16, pack2(d[8 * u], d[8 * u + 1]), pack2(d[8 * u + 2], d[8 * u + 3]),
            pack2(d[8 * u + 4], d[8 * u + 5]), pack2(d[8 * u + 6], d[8 * u + 7]));
    __syncwarp();
    uint4* out = reinterpret_cast<uint4*>(p.out + (blk * 128 + warp * 16) * (DM / 2) + cg * 40);
#pragma unroll
    for (int i = 0; i < 5; i++) { const int e = i * 32 + lane, r = e / 10; out[r * (DM / 8) + e - r * 10] = lds128(stage + e * 16); }
  } else {
    float2* stat = g_stat + blk * 1024 + (warp & 7) * 16 + g;
    float mean[2], rs[2];
#pragma unroll
    for (int r = 0; r < 2; r++) {
      float t = 0.f, q = 0.f;
#pragma unroll
      for (int i = 0; i < 10; i++) t += d[4 * i + 2 * r] + d[4 * i + 2 * r + 1];
      t += __shfl_xor_sync(~0u, t, 1); t += __shfl_xor_sync(~0u, t, 2);
      t *= 1.f / 80;
#pragma unroll
      for (int i = 0; i < 10; i++) { const float a = d[4 * i + 2 * r] - t, b = d[4 * i + 2 * r + 1] - t; q += a * a + b * b; }
      q += __shfl_xor_sync(~0u, q, 1); q += __shfl_xor_sync(~0u, q, 2);
      if (c == r && live) asm volatile("st.relaxed.gpu.global.v2.b32 [%0], {%1, %2};" :: "l"(stat + cg * 128 + r * 8), "r"(__float_as_uint(t)), "r"(nz(__float_as_uint(q))) : "memory");
    }
#pragma unroll
    for (int i = 0; i < 10; i++) {
      const int r = i / 5, u = i % 5;
      if (live) x[(r * 40 + u) * 32] = make_uint2(pack2(d[8 * u + 2 * r], d[8 * u + 2 * r + 1]), pack2(d[8 * u + 4 + 2 * r], d[8 * u + 5 + 2 * r]));
    }
    ABT(0, 6);
    uint2 e[4];
    int n = 0;
    do {
#pragma unroll
      for (int i = 0; i < 4; i++)
        asm volatile("ld.relaxed.gpu.global.v2.b32 {%0, %1}, [%2];" : "=r"(e[i].x), "=r"(e[i].y) : "l"(stat + (2 * c + (i & 1)) * 128 + (i >> 1) * 8) : "memory");
      spin_guard(n);
    } while (__any_sync(~0u, min(min(e[0].y, e[1].y), min(e[2].y, e[3].y)) == 0 && live));
#pragma unroll
    for (int r = 0; r < 2; r++) {
      const float m0 = __uint_as_float(e[2 * r].x), m1 = __uint_as_float(e[2 * r + 1].x);
      float t = m0 + m1;
      t += __shfl_xor_sync(~0u, t, 1); t += __shfl_xor_sync(~0u, t, 2);
      t *= 0.125f;
      float q = __uint_as_float(e[2 * r].y) + __uint_as_float(e[2 * r + 1].y) + 80.f * ((m0 - t) * (m0 - t) + (m1 - t) * (m1 - t));
      q += __shfl_xor_sync(~0u, q, 1); q += __shfl_xor_sync(~0u, q, 2);
      mean[r] = t; rs[r] = rsqrtf(q * (1.f / DM) + 1e-5f);
    }
    ABT(0, 7);
    uint32_t w[2][5][2];
#pragma unroll
    for (int i = 0; i < 20; i++) w[i & 1][i >> 2][i >> 1 & 1] = pack2((d[2 * i] - mean[i & 1]) * rs[i & 1], (d[2 * i + 1] - mean[i & 1]) * rs[i & 1]);
    if (TRIG == 2 && warp < 8) pdl_launch();
    ln_store(w, blk * 8 + warp, cg * 5, live);
    if (TRIG == 1 && warp < 8) pdl_launch();
  }
  ABT(!!p.out, 8);
  TRACE(2);
}

typedef CUresult (*EncodeFn)(CUtensorMap*, CUtensorMapDataType, cuuint32_t, void*, const cuuint64_t*, const cuuint64_t*,
                             const cuuint32_t*, const cuuint32_t*, CUtensorMapInterleave, CUtensorMapSwizzle,
                             CUtensorMapL2promotion, CUtensorMapFloatOOBfill);

void make_map(EncodeFn enc, CUtensorMap* m, const void* ptr, int cols, int rows, int nb) {
  const cuuint64_t dims[3] = {(cuuint64_t)(nb ? 64 : cols), (cuuint64_t)rows, (cuuint64_t)cols / 64};
  const cuuint64_t strides[2] = {(cuuint64_t)cols * 2, 128};
  const cuuint32_t box[3] = {64, 32, (cuuint32_t)nb}, es[3] = {1, 1, 1};
  enc(m, CU_TENSOR_MAP_DATA_TYPE_BFLOAT16, nb ? 3 : 2, const_cast<void*>(ptr), dims, strides, box, es, CU_TENSOR_MAP_INTERLEAVE_NONE,
      CU_TENSOR_MAP_SWIZZLE_128B, CU_TENSOR_MAP_L2_PROMOTION_L2_128B, CU_TENSOR_MAP_FLOAT_OOB_FILL_NONE);
}
template <class... KA, class... A>
void launch(void (*kern)(KA...), int grid, int block, int smem, int cluster, bool pdl, A... args) {
  cudaFuncSetAttribute(kern, cudaFuncAttributeMaxDynamicSharedMemorySize, smem);
  cudaLaunchConfig_t cfg = {};
  cfg.gridDim = dim3(grid); cfg.blockDim = dim3(block); cfg.dynamicSmemBytes = smem; cfg.stream = cudaStreamPerThread;
  cudaLaunchAttribute at[2];
  int n = 0;
  if (cluster > 1) { at[n].id = cudaLaunchAttributeClusterDimension; at[n].val.clusterDim.x = cluster; at[n].val.clusterDim.y = 1; at[n].val.clusterDim.z = 1; n++; }
  if (pdl) { at[n].id = cudaLaunchAttributeProgrammaticStreamSerialization; at[n].val.programmaticStreamSerializationAllowed = 1; n++; }
  cfg.attrs = at; cfg.numAttrs = n;
  cudaLaunchKernelEx(&cfg, kern, args...);
}
template <class T> void* sym(T& s) { void* p = nullptr; cudaGetSymbolAddress(&p, s); return p; }

}

#define MODE(b) 0
extern "C" void kernel_launch(void* const* d_in, const int* in_sizes, int n_in, void* d_out, int out_size) {
  const __nv_bfloat16* x = (const __nv_bfloat16*)d_in[0];
  void* fn = nullptr; cudaDriverEntryPointQueryResult qr;
  cudaGetDriverEntryPoint("cuTensorMapEncodeTiled", &fn, cudaEnableDefault, &qr);
  EncodeFn enc = (EncodeFn)fn;

  ChainParams ch = {};
  PostParams op = {};
  for (int i = 0; i < 3; i++) {
    const cuuint64_t dims[3] = {HD, 128, 5}, strides[2] = {HD * 2, HD * 256};
    const cuuint32_t box[3] = {64, 128, 5}, es[3] = {1, 1, 1};
    enc(i == 0 ? &ch.wq : i == 1 ? &ch.wk : &ch.wv, CU_TENSOR_MAP_DATA_TYPE_BFLOAT16, 3, d_in[2 + i], dims, strides, box, es, CU_TENSOR_MAP_INTERLEAVE_NONE,
        CU_TENSOR_MAP_SWIZZLE_128B, W_PROMO, CU_TENSOR_MAP_FLOAT_OOB_FILL_NONE);
  }
  {
    const cuuint64_t dims[3] = {DM, HD, 7}, strides[2] = {DM * 2, 64};
    const cuuint32_t box[3] = {32, 64, 7}, es[3] = {1, 1, 1};
    enc(&ch.wo, CU_TENSOR_MAP_DATA_TYPE_BFLOAT16, 3, d_in[5], dims, strides, box, es, CU_TENSOR_MAP_INTERLEAVE_NONE,
        CU_TENSOR_MAP_SWIZZLE_64B, CU_TENSOR_MAP_L2_PROMOTION_L2_128B, CU_TENSOR_MAP_FLOAT_OOB_FILL_NONE);
  }
  ch.mem0 = (const __nv_bfloat16*)d_in[1];
  ch.pool = (uint8_t*)(((uintptr_t)sym(g_pool) + 8191) & ~(uintptr_t)8191); ch.kv = (uint8_t*)sym(g_kv); ch.xc = (const uint32_t*)sym(g_xc); ch.sync = (uint32_t*)sym(g_sync);
  ch.d1 = 0; ch.d1b = 0; ch.d2 = 0; ch.d2b = 0;
  make_map(enc, &op.wq, d_in[2], HD, DM, 3);
  make_map(enc, &op.wo, d_in[5], DM, HD, 5); make_map(enc, &op.wo2, d_in[5], DM, HD, 0);
  make_map(enc, &op.wb, d_in[8], 1920, DM, 5); make_map(enc, &op.wb2, d_in[8], 1920, DM, 0);
  op.gap = 17; op.share = 20; op.look = 20; op.gap2 = 0; op.pol = 1; op.slow_n = 8; op.slow_gap = 23;

  const Weights wa = {{(const uint8_t*)d_in[3], (const uint8_t*)d_in[4], (const uint8_t*)d_in[2], (const uint8_t*)d_in[5]}}, none = {};
  launch(first_kernel, 132, 384, 128 * 1024, 1, false, x, (const uint4*)d_in[9], wa);
  for (int layer = 0; layer < (MODE(4) ? 1 : 2); layer++) {
    ch.layer = ch.d2b = op.layer = layer;
    launch(chain_kernel, 96, 256, CH_SMEM, 3, CH_PDL >> layer & 1, ch);
    launch(post_kernel, MODE(3) ? 36 : 132, 384, OP_SMEM, 1, !MODE(1), op);
    const AbParams ab = {layer == 0 ? wa : none, (uint32_t*)sym(g_bo) + layer * 128, layer == 0 ? nullptr : (uint32_t*)d_out};
    launch(attn_b_kernel, 128, AB_T + 32, AB_SMEM, 1, true, ab);
  }
}
```
